```python
import torch

def _softmax(x, axis=-1):
    return torch.softmax(x, dim=axis)
def _gelu(x):
    return torch.nn.functional.gelu(x, approximate="tanh")
def _silu(x):
    return torch.nn.functional.silu(x)
def _sigmoid(x):
    return torch.sigmoid(x)
def _layernorm(x, axis=-1, eps=1e-5):
    m = x.mean(dim=axis, keepdim=True)
    v = x.var(dim=axis, keepdim=True, unbiased=False)
    return (x - m) / torch.sqrt(v + eps)
def _scatter_add(tgt, idx, src, axis=0):
    return tgt.clone().index_add_(axis, idx, src)
def _segment_sum(src, seg, n):
    out = torch.zeros((n,) + src.shape[1:], dtype=src.dtype)
    return out.index_add_(0, seg, src)
def _pad(x, pw):
    flat = tuple(v for pair in reversed(pw) for v in pair)
    return torch.nn.functional.pad(x, flat)

kernel_name = 'interleave_layers__sliding_local_dilated__softmax_full_mha__prompt'

def setup_inputs():

    _w = (lambda a: (lambda t: t.to(torch.bfloat16) if t.is_floating_point() else t)(torch.as_tensor(a)))
    def _A_setup():
        B, S, D = 1, 2048, 1024
        return {
            "x": _w((lambda *s: torch.randn(*s, dtype=torch.bfloat16) * 0.05)(B, S, D)),
            "wqkv": _w((lambda *s: torch.randn(*s, dtype=torch.bfloat16) * 0.05)(D, 3 * D)),
            "wo": _w((lambda *s: torch.randn(*s, dtype=torch.bfloat16) * 0.05)(D, D)),
        }
    _A_in = _A_setup()

    def _B_setup():
        B, S, D = 1, 2048, 1024
        return {
            "x": _w((lambda *s: torch.randn(*s, dtype=torch.bfloat16) * 0.05)(B, S, D)),
            "wqkv": _w((lambda *s: torch.randn(*s, dtype=torch.bfloat16) * 0.05)(D, 3 * D)),
            "wo": _w((lambda *s: torch.randn(*s, dtype=torch.bfloat16) * 0.05)(D, D)),
        }
    _B_in = _B_setup()

    return {
        "A_x": _A_in["x"],
        "A_wqkv": _A_in["wqkv"],
        "A_wo": _A_in["wo"],
        "B_x": _B_in["x"],
        "B_wqkv": _B_in["wqkv"],
        "B_wo": _B_in["wo"],
    }

def reference(A_x, A_wqkv, A_wo, B_x, B_wqkv, B_wo):
    def _A_ref(x, wqkv, wo):
        B, S, D = x.shape
        H = 32; Dh = D // H
        W, dil = 8, 2
        qkv = (lambda x, *d: x.permute(*d))((x @ wqkv).reshape(B, S, 3, H, Dh), 2, 0, 3, 1, 4)
        q, k, v = qkv[0], qkv[1], qkv[2]
        scale = Dh ** -0.5
        pos = torch.arange(S)
        off = torch.arange(W) * dil
        idx = pos[:, None] - off[None, :]
        mask = idx >= 0
        idx_c = torch.where(mask, idx, 0).reshape(-1)
        kg = k[:, :, idx_c, :].reshape(B, H, S, W, Dh)
        vg = v[:, :, idx_c, :].reshape(B, H, S, W, Dh)
        logits = torch.einsum("bhsd,bhswd->bhsw", q, kg) * scale
        logits = torch.where(mask[None, None, :, :], logits, -1e9)
        attn = _softmax(logits, axis=-1)
        o = torch.einsum("bhsw,bhswd->bhsd", attn, vg)
        return (lambda x, *d: x.permute(*d))(o, 0, 2, 1, 3).reshape(B, S, D) @ wo

    def _B_ref(x, wqkv, wo):
        B, S, D = x.shape
        H = 32; Dh = D // H
        qkv = (lambda x, *d: x.permute(*d))((x @ wqkv).reshape(B, S, 3, H, Dh), 2, 0, 3, 1, 4)
        q, k, v = qkv[0], qkv[1], qkv[2]
        scale = Dh ** -0.5
        scores = torch.einsum("bhqd,bhkd->bhqk", q, k) * scale
        p = _softmax(scores, axis=-1)
        o = torch.einsum("bhqk,bhkd->bhqd", p, v)
        return (lambda x, *d: x.permute(*d))(o, 0, 2, 1, 3).reshape(B, S, D) @ wo

    x = A_x
    x = x + _A_ref(_layernorm(x, axis=-1), A_wqkv, A_wo)
    x = x + _B_ref(_layernorm(x, axis=-1), B_wqkv, B_wo)
    x = x + _A_ref(_layernorm(x, axis=-1), A_wqkv, A_wo)
    x = x + _B_ref(_layernorm(x, axis=-1), B_wqkv, B_wo)
    return x
```

```cpp
#include <cuda_runtime.h>
#include <cuda_bf16.h>
#include <cuda.h>
#include <stdint.h>

typedef __nv_bfloat16 bf16;

__device__ __forceinline__ void wgmma_m64n192k16_ss_tb(float (&d)[96], uint64_t da, uint64_t db, int scale_d) {
  asm volatile("{\n.reg .pred p;\nsetp.ne.b32 p, %98, 0;\n"
    "wgmma.mma_async.sync.aligned.m64n192k16.f32.bf16.bf16 "
    "{%0, %1, %2, %3, %4, %5, %6, %7, %8, %9, %10, %11, %12, %13, %14, %15, "
    "%16, %17, %18, %19, %20, %21, %22, %23, %24, %25, %26, %27, %28, %29, %30, %31, "
    "%32, %33, %34, %35, %36, %37, %38, %39, %40, %41, %42, %43, %44, %45, %46, %47, "
    "%48, %49, %50, %51, %52, %53, %54, %55, %56, %57, %58, %59, %60, %61, %62, %63, "
    "%64, %65, %66, %67, %68, %69, %70, %71, %72, %73, %74, %75, %76, %77, %78, %79, "
    "%80, %81, %82, %83, %84, %85, %86, %87, %88, %89, %90, %91, %92, %93, %94, %95}, "
    "%96, %97, p, 1, 1, 0, 1;\n}\n"
    : "+f"(d[0]), "+f"(d[1]), "+f"(d[2]), "+f"(d[3]), "+f"(d[4]), "+f"(d[5]), "+f"(d[6]), "+f"(d[7]),
      "+f"(d[8]), "+f"(d[9]), "+f"(d[10]), "+f"(d[11]), "+f"(d[12]), "+f"(d[13]), "+f"(d[14]), "+f"(d[15]),
      "+f"(d[16]), "+f"(d[17]), "+f"(d[18]), "+f"(d[19]), "+f"(d[20]), "+f"(d[21]), "+f"(d[22]), "+f"(d[23]),
      "+f"(d[24]), "+f"(d[25]), "+f"(d[26]), "+f"(d[27]), "+f"(d[28]), "+f"(d[29]), "+f"(d[30]), "+f"(d[31]),
      "+f"(d[32]), "+f"(d[33]), "+f"(d[34]), "+f"(d[35]), "+f"(d[36]), "+f"(d[37]), "+f"(d[38]), "+f"(d[39]),
      "+f"(d[40]), "+f"(d[41]), "+f"(d[42]), "+f"(d[43]), "+f"(d[44]), "+f"(d[45]), "+f"(d[46]), "+f"(d[47]),
      "+f"(d[48]), "+f"(d[49]), "+f"(d[50]), "+f"(d[51]), "+f"(d[52]), "+f"(d[53]), "+f"(d[54]), "+f"(d[55]),
      "+f"(d[56]), "+f"(d[57]), "+f"(d[58]), "+f"(d[59]), "+f"(d[60]), "+f"(d[61]), "+f"(d[62]), "+f"(d[63]),
      "+f"(d[64]), "+f"(d[65]), "+f"(d[66]), "+f"(d[67]), "+f"(d[68]), "+f"(d[69]), "+f"(d[70]), "+f"(d[71]),
      "+f"(d[72]), "+f"(d[73]), "+f"(d[74]), "+f"(d[75]), "+f"(d[76]), "+f"(d[77]), "+f"(d[78]), "+f"(d[79]),
      "+f"(d[80]), "+f"(d[81]), "+f"(d[82]), "+f"(d[83]), "+f"(d[84]), "+f"(d[85]), "+f"(d[86]), "+f"(d[87]),
      "+f"(d[88]), "+f"(d[89]), "+f"(d[90]), "+f"(d[91]), "+f"(d[92]), "+f"(d[93]), "+f"(d[94]), "+f"(d[95])
    : "l"(da), "l"(db), "r"(scale_d));
}

__device__ __forceinline__ void wgmma_m64n128k16_ss_tb(float (&d)[64], uint64_t da, uint64_t db, int scale_d) {
  asm volatile("{\n.reg .pred p;\nsetp.ne.b32 p, %66, 0;\n"
    "wgmma.mma_async.sync.aligned.m64n128k16.f32.bf16.bf16 "
    "{%0, %1, %2, %3, %4, %5, %6, %7, %8, %9, %10, %11, %12, %13, %14, %15, "
    "%16, %17, %18, %19, %20, %21, %22, %23, %24, %25, %26, %27, %28, %29, %30, %31, "
    "%32, %33, %34, %35, %36, %37, %38, %39, %40, %41, %42, %43, %44, %45, %46, %47, "
    "%48, %49, %50, %51, %52, %53, %54, %55, %56, %57, %58, %59, %60, %61, %62, %63}, "
    "%64, %65, p, 1, 1, 0, 1;\n}\n"
    : "+f"(d[0]), "+f"(d[1]), "+f"(d[2]), "+f"(d[3]), "+f"(d[4]), "+f"(d[5]), "+f"(d[6]), "+f"(d[7]),
      "+f"(d[8]), "+f"(d[9]), "+f"(d[10]), "+f"(d[11]), "+f"(d[12]), "+f"(d[13]), "+f"(d[14]), "+f"(d[15]),
      "+f"(d[16]), "+f"(d[17]), "+f"(d[18]), "+f"(d[19]), "+f"(d[20]), "+f"(d[21]), "+f"(d[22]), "+f"(d[23]),
      "+f"(d[24]), "+f"(d[25]), "+f"(d[26]), "+f"(d[27]), "+f"(d[28]), "+f"(d[29]), "+f"(d[30]), "+f"(d[31]),
      "+f"(d[32]), "+f"(d[33]), "+f"(d[34]), "+f"(d[35]), "+f"(d[36]), "+f"(d[37]), "+f"(d[38]), "+f"(d[39]),
      "+f"(d[40]), "+f"(d[41]), "+f"(d[42]), "+f"(d[43]), "+f"(d[44]), "+f"(d[45]), "+f"(d[46]), "+f"(d[47]),
      "+f"(d[48]), "+f"(d[49]), "+f"(d[50]), "+f"(d[51]), "+f"(d[52]), "+f"(d[53]), "+f"(d[54]), "+f"(d[55]),
      "+f"(d[56]), "+f"(d[57]), "+f"(d[58]), "+f"(d[59]), "+f"(d[60]), "+f"(d[61]), "+f"(d[62]), "+f"(d[63])
    : "l"(da), "l"(db), "r"(scale_d));
}

__device__ __forceinline__ void wgmma_m64n40k16_rs_tb(float (&d)[20], uint32_t a0, uint32_t a1, uint32_t a2, uint32_t a3, uint64_t db, int scale_d) {
  asm volatile("{\n.reg .pred p;\nsetp.ne.b32 p, %25, 0;\n"
    "wgmma.mma_async.sync.aligned.m64n40k16.f32.bf16.bf16 "
    "{%0, %1, %2, %3, %4, %5, %6, %7, %8, %9, %10, %11, %12, %13, %14, %15, "
    "%16, %17, %18, %19}, "
    "{%20, %21, %22, %23}, %24, p, 1, 1, 1;\n}\n"
    : "+f"(d[0]), "+f"(d[1]), "+f"(d[2]), "+f"(d[3]), "+f"(d[4]), "+f"(d[5]), "+f"(d[6]), "+f"(d[7]),
      "+f"(d[8]), "+f"(d[9]), "+f"(d[10]), "+f"(d[11]), "+f"(d[12]), "+f"(d[13]), "+f"(d[14]), "+f"(d[15]),
      "+f"(d[16]), "+f"(d[17]), "+f"(d[18]), "+f"(d[19])
    : "r"(a0), "r"(a1), "r"(a2), "r"(a3), "l"(db), "r"(scale_d));
}

__device__ __forceinline__ void wg_n64_rs_nb_f16_f32(float (&d)[32], uint32_t a0, uint32_t a1, uint32_t a2, uint32_t a3, uint64_t db, int scale_d) {
  asm volatile("{\n.reg .pred p;\nsetp.ne.b32 p, %37, 0;\n"
    "wgmma.mma_async.sync.aligned.m64n64k16.f32.f16.f16 "
    "{%0, %1, %2, %3, %4, %5, %6, %7, %8, %9, %10, %11, %12, %13, %14, %15, "
    "%16, %17, %18, %19, %20, %21, %22, %23, %24, %25, %26, %27, %28, %29, %30, %31}, "
    "{%32, %33, %34, %35}, %36, p, 1, 1, 0;\n}\n"
    : "+f"(d[0]), "+f"(d[1]), "+f"(d[2]), "+f"(d[3]), "+f"(d[4]), "+f"(d[5]), "+f"(d[6]), "+f"(d[7]),
      "+f"(d[8]), "+f"(d[9]), "+f"(d[10]), "+f"(d[11]), "+f"(d[12]), "+f"(d[13]), "+f"(d[14]), "+f"(d[15]),
      "+f"(d[16]), "+f"(d[17]), "+f"(d[18]), "+f"(d[19]), "+f"(d[20]), "+f"(d[21]), "+f"(d[22]), "+f"(d[23]),
      "+f"(d[24]), "+f"(d[25]), "+f"(d[26]), "+f"(d[27]), "+f"(d[28]), "+f"(d[29]), "+f"(d[30]), "+f"(d[31])
    : "r"(a0), "r"(a1), "r"(a2), "r"(a3), "l"(db), "r"(scale_d));
}

__device__ __forceinline__ void wg_n64_rs_nb_f16_f16(uint32_t (&d)[16], uint32_t a0, uint32_t a1, uint32_t a2, uint32_t a3, uint64_t db, int scale_d) {
  asm volatile("{\n.reg .pred p;\nsetp.ne.b32 p, %21, 0;\n"
    "wgmma.mma_async.sync.aligned.m64n64k16.f16.f16.f16 "
    "{%0, %1, %2, %3, %4, %5, %6, %7, %8, %9, %10, %11, %12, %13, %14, %15}, "
    "{%16, %17, %18, %19}, %20, p, 1, 1, 0;\n}\n"
    : "+r"(d[0]), "+r"(d[1]), "+r"(d[2]), "+r"(d[3]), "+r"(d[4]), "+r"(d[5]), "+r"(d[6]), "+r"(d[7]),
      "+r"(d[8]), "+r"(d[9]), "+r"(d[10]), "+r"(d[11]), "+r"(d[12]), "+r"(d[13]), "+r"(d[14]), "+r"(d[15])
    : "r"(a0), "r"(a1), "r"(a2), "r"(a3), "l"(db), "r"(scale_d));
}

#define DEVINL __device__ __forceinline__
DEVINL void wg_fence() { asm volatile("wgmma.fence.sync.aligned;" ::: "memory"); }
DEVINL void wg_commit() { asm volatile("wgmma.commit_group.sync.aligned;" ::: "memory"); }
template <int N> DEVINL void wg_wait() { asm volatile("wgmma.wait_group.sync.aligned %0;" ::"n"(N) : "memory"); }
DEVINL uint64_t mkdesc(uint32_t addr, uint32_t lbo, uint32_t sbo, int sw) {
  return (uint64_t)((addr & 0x3FFFF) >> 4) | ((uint64_t)(lbo >> 4) << 16) | ((uint64_t)(sbo >> 4) << 32) | ((uint64_t)sw << 62);
}
DEVINL void mbar_init(uint32_t bar, uint32_t cnt) { asm volatile("mbarrier.init.shared::cta.b64 [%0], %1;" ::"r"(bar), "r"(cnt) : "memory"); }
DEVINL void mbar_arrive(uint32_t bar) { asm volatile("mbarrier.arrive.shared::cta.b64 _, [%0];" ::"r"(bar) : "memory"); }
DEVINL bool mbar_try(uint32_t bar, uint32_t parity) {
  uint32_t ok;
  asm volatile("{\n.reg .pred p;\nmbarrier.try_wait.parity.shared::cta.b64 p, [%1], %2;\nselp.u32 %0, 1, 0, p;\n}" : "=r"(ok) : "r"(bar), "r"(parity) : "memory");
  return ok;
}
DEVINL bool mbar_test(uint32_t bar, uint32_t parity) {
  uint32_t ok;
  asm volatile("{\n.reg .pred p;\nmbarrier.test_wait.parity.shared::cta.b64 p, [%1], %2;\nselp.u32 %0, 1, 0, p;\n}" : "=r"(ok) : "r"(bar), "r"(parity) : "memory");
  return ok;
}
DEVINL void mbar_hint(uint32_t bar, uint32_t parity) {
#pragma unroll 1
  for (uint32_t n = 0; n < 16u; n++) if (mbar_try(bar, parity)) break;
}
DEVINL void mbar_wait(uint32_t bar, uint32_t parity) {
#pragma unroll 1
  for (uint32_t n = 0; n < 100000u; n++) if (mbar_try(bar, parity)) break;
}
#define EL(txt) "{\n.reg .pred pe;\nelect.sync _|pe, 0xffffffff;\n@pe " txt "\n}"
DEVINL void e_expect_tx(uint32_t bar, uint32_t bytes) { asm volatile(EL("mbarrier.arrive.expect_tx.shared::cta.b64 _, [%0], %1;") ::"r"(bar), "r"(bytes) : "memory"); }
DEVINL void e_arrive(uint32_t bar) { asm volatile(EL("mbarrier.arrive.shared::cta.b64 _, [%0];") ::"r"(bar) : "memory"); }
DEVINL void e_red(uint32_t* p) { asm volatile(EL("red.release.gpu.global.add.u32 [%0], 1;") ::"l"(p) : "memory"); }
DEVINL void e_red_relaxed(uint32_t* p) { asm volatile(EL("red.relaxed.gpu.global.add.u32 [%0], 1;") ::"l"(p) : "memory"); }
DEVINL void tma_ld(uint32_t dst, const CUtensorMap* m, int c0, int c1, uint32_t bar) {
  asm volatile(EL("cp.async.bulk.tensor.2d.shared::cluster.global.mbarrier::complete_tx::bytes [%0], [%1, {%3, %4}], [%2];")
               ::"r"(dst), "l"(m), "r"(bar), "r"(c0), "r"(c1) : "memory");
}
DEVINL void tma_ld3(uint32_t dst, const CUtensorMap* m, int c0, int c1, int c2, uint32_t bar) {
  asm volatile(EL("cp.async.bulk.tensor.3d.shared::cluster.global.mbarrier::complete_tx::bytes [%0], [%1, {%3, %4, %5}], [%2];")
               ::"r"(dst), "l"(m), "r"(bar), "r"(c0), "r"(c1), "r"(c2) : "memory");
}
DEVINL void tma_ld5(uint32_t dst, const CUtensorMap* m, int c2, int c3, int c4, uint32_t bar) {
  asm volatile(EL("cp.async.bulk.tensor.5d.shared::cluster.global.mbarrier::complete_tx::bytes [%0], [%1, {0, 0, %3, %4, %5}], [%2];")
               ::"r"(dst), "l"(m), "r"(bar), "r"(c2), "r"(c3), "r"(c4) : "memory");
}
DEVINL void tma_ld_mc(uint32_t dst, const CUtensorMap* m, int c0, int c1, uint32_t bar) {
  asm volatile(EL("cp.async.bulk.tensor.2d.shared::cluster.global.mbarrier::complete_tx::bytes.multicast::cluster [%0], [%1, {%3, %4}], [%2], %5;")
               ::"r"(dst), "l"(m), "r"(bar), "r"(c0), "r"(c1), "h"((uint16_t)3) : "memory");
}
DEVINL void e_arrive_both(uint32_t bar) {
  asm volatile("{\n.reg .pred pe;\n.reg .b32 r0, r1;\nelect.sync _|pe, 0xffffffff;\nmapa.shared::cluster.u32 r0, %0, 0;\nmapa.shared::cluster.u32 r1, %0, 1;\n"
               "@pe mbarrier.arrive.shared::cluster.b64 _, [r0];\n@pe mbarrier.arrive.shared::cluster.b64 _, [r1];\n}" ::"r"(bar) : "memory");
}
DEVINL void tma_st(const CUtensorMap* m, int c0, int c1, uint32_t src) {
  asm volatile(EL("cp.async.bulk.tensor.2d.global.shared::cta.bulk_group [%0, {%2, %3}], [%1];") ::"l"(m), "r"(src), "r"(c0), "r"(c1) : "memory");
}
DEVINL void bulk_commit() { asm volatile("cp.async.bulk.commit_group;" ::: "memory"); }
template <int N> DEVINL void bulk_wait_n() { asm volatile("cp.async.bulk.wait_group %0;\nbar.warp.sync 0xffffffff;" ::"n"(N) : "memory"); }
DEVINL void l2_prefetch(const void* g, uint32_t bytes) { asm volatile(EL("cp.async.bulk.prefetch.L2.global [%0], %1;") ::"l"(g), "r"(bytes) : "memory"); }
DEVINL void fence_async_smem() { asm volatile("fence.proxy.async.shared::cta;" ::: "memory"); }
DEVINL void fence_async_gl() { asm volatile("fence.proxy.async.global;" ::: "memory"); }
DEVINL void cluster_wait() { asm volatile("barrier.cluster.wait.aligned;" ::: "memory"); }
DEVINL void bar_sync(int id, int n) { asm volatile("bar.sync %0, %1;" ::"r"(id), "r"(n) : "memory"); }
DEVINL void bar_arrive(int id, int n) { asm volatile("bar.arrive %0, %1;" ::"r"(id), "r"(n) : "memory"); }
DEVINL uint32_t ld_acquire(const uint32_t* p) { uint32_t v; asm volatile("ld.acquire.gpu.global.u32 %0, [%1];" : "=r"(v) : "l"(p) : "memory"); return v; }
DEVINL void watch(const uint32_t* p, uint32_t target, uint32_t all, uint32_t tag, uint32_t slot) {
  uint32_t seen = 0;
#pragma unroll 1
  for (uint32_t n = 0; n < 200000u && seen != all; n++) {
    const uint32_t m = __ballot_sync(~0u, (int)(ld_acquire(p) - target) >= 0) & all;
    if (m != seen) { seen = m; asm volatile("st.release.cta.shared.u32 [%0], %1;" ::"r"(slot), "r"(tag << 16 | m) : "memory"); }
  }
}
template <bool RELAXED = false> DEVINL void await_bit(uint32_t slot, uint32_t tag, int j, uint32_t& rdy) {
  if ((rdy >> j) & 1) return;
#pragma unroll 1
  for (uint32_t n = 0; n < 8000000u; n++) {
    uint32_t v;
    asm volatile("ld.acquire.cta.shared.u32 %0, [%1];" : "=r"(v) : "r"(slot) : "memory");
    if ((v >> 16) == tag && ((v >> j) & 1)) { rdy = v; break; }
    if (RELAXED) __nanosleep(200);
  }
  asm volatile("fence.proxy.async.global;" ::: "memory");
}
DEVINL void poll_ge(const uint32_t* p, uint32_t target) {
#pragma unroll 1
  for (uint32_t n = 0; n < 200000u; n++) if (__all_sync(~0u, (int)(ld_acquire(p) - target) >= 0)) break;
}
DEVINL int lane_id() { int v; asm volatile("mov.u32 %0, %%laneid;" : "=r"(v)); return v; }
__host__ DEVINL int remap(int v) {
  const int c = v >> 1, u = c - 36, r = (u * 37) >> 8;
  const int L = c < 4 ? 32 + 8 * c : c < 36 ? c - 4 : 33 + u + r;
  return 2 * L + (v & 1);
}
DEVINL int block_id() { int v; asm volatile("mov.u32 %0, %%ctaid.x;" : "=r"(v)); return v; }
#define cta_id() prm.map[block_id()]
#define IDS() const int lane = lane_id(), b = cta_id(), bm = b >> 4, bn = b & 15, rank = b & 1, pm = 2 * bm + (bn >> 3), pn = bn & 7, po = pm & 1; \
  (void)lane; (void)bm; (void)bn; (void)rank; (void)pm; (void)pn; (void)po
DEVINL void st_tagged(unsigned long long* p, uint32_t v, uint32_t tag) {
  asm volatile("{\n.reg .b64 t;\nmov.b64 t, {%1, %2};\nst.relaxed.gpu.global.b64 [%0], t;\n}" ::"l"(p), "r"(v), "r"(tag) : "memory");
}
DEVINL float ex2(float x) { float y; asm("ex2.approx.ftz.f32 %0, %1;" : "=f"(y) : "f"(x)); return y; }
DEVINL float rcp(float x) { float y; asm("rcp.approx.ftz.f32 %0, %1;" : "=f"(y) : "f"(x)); return y; }
DEVINL uint32_t pack2(float lo, float hi) { uint32_t r; asm("cvt.rn.bf16x2.f32 %0, %1, %2;" : "=r"(r) : "f"(hi), "f"(lo)); return r; }
DEVINL uint32_t pack2h(float lo, float hi) { uint32_t r; asm("cvt.rn.f16x2.f32 %0, %1, %2;" : "=r"(r) : "f"(hi), "f"(lo)); return r; }
DEVINL uint32_t hadd2(uint32_t a, uint32_t b) { uint32_t r; asm("add.rn.f16x2 %0, %1, %2;" : "=r"(r) : "r"(a), "r"(b)); return r; }
DEVINL uint32_t hfma2(uint32_t a, uint32_t b, uint32_t c) { uint32_t r; asm("fma.rn.f16x2 %0, %1, %2, %3;" : "=r"(r) : "r"(a), "r"(b), "r"(c)); return r; }
DEVINL float bf_lo(uint32_t w) { return __uint_as_float(w << 16); }
DEVINL float bf_hi(uint32_t w) { return __uint_as_float(w & 0xFFFF0000u); }
DEVINL float bf_round(float x) { return bf_lo(pack2(x, 0.f)); }
DEVINL uint32_t add_bf16x2(uint32_t a, uint32_t b) { uint32_t r; asm("add.rn.bf16x2 %0, %1, %2;" : "=r"(r) : "r"(a), "r"(b)); return r; }
DEVINL void stsm4(uint32_t addr, uint32_t a, uint32_t b, uint32_t c, uint32_t d) {
  asm volatile("stmatrix.sync.aligned.m8n8.x4.shared.b16 [%0], {%1, %2, %3, %4};" ::"r"(addr), "r"(a), "r"(b), "r"(c), "r"(d) : "memory");
}
DEVINL void ldsm4(uint32_t addr, uint32_t (&r)[4]) {
  asm volatile("ldmatrix.sync.aligned.m8n8.x4.shared.b16 {%0, %1, %2, %3}, [%4];" : "=r"(r[0]), "=r"(r[1]), "=r"(r[2]), "=r"(r[3]) : "r"(addr) : "memory");
}
DEVINL void ldsm4t(uint32_t addr, uint32_t (&r)[4]) {
  asm volatile("ldmatrix.sync.aligned.m8n8.x4.trans.shared.b16 {%0, %1, %2, %3}, [%4];" : "=r"(r[0]), "=r"(r[1]), "=r"(r[2]), "=r"(r[3]) : "r"(addr) : "memory");
}
DEVINL void sts128(uint32_t addr, uint32_t a, uint32_t b, uint32_t c, uint32_t d) {
  asm volatile("st.shared.v4.b32 [%0], {%1, %2, %3, %4};" ::"r"(addr), "r"(a), "r"(b), "r"(c), "r"(d) : "memory");
}
DEVINL float2 lds64f(uint32_t addr) { float2 v; asm volatile("ld.shared.v2.f32 {%0, %1}, [%2];" : "=f"(v.x), "=f"(v.y) : "r"(addr) : "memory"); return v; }
DEVINL void mma16816(float (&d)[4], uint32_t a0, uint32_t a1, uint32_t a2, uint32_t a3, uint32_t b0, uint32_t b1) {
  asm("mma.sync.aligned.m16n8k16.row.col.f32.bf16.bf16.f32 {%0, %1, %2, %3}, {%4, %5, %6, %7}, {%8, %9}, {%0, %1, %2, %3};"
               : "+f"(d[0]), "+f"(d[1]), "+f"(d[2]), "+f"(d[3]) : "r"(a0), "r"(a1), "r"(a2), "r"(a3), "r"(b0), "r"(b1));
}
template <int N> DEVINL void fence_regs(float (&d)[N]) {
#pragma unroll
  for (int i = 0; i < N; i++) asm volatile("" : "+f"(d[i])::"memory");
}
template <int N> DEVINL void fence_regs(uint32_t (&d)[N]) {
#pragma unroll
  for (int i = 0; i < N; i++) asm volatile("" : "+r"(d[i])::"memory");
}
DEVINL void lds128(uint32_t addr, uint32_t* r) {
  asm volatile("ld.shared.v4.b32 {%0, %1, %2, %3}, [%4];" : "=r"(r[0]), "=r"(r[1]), "=r"(r[2]), "=r"(r[3]) : "r"(addr) : "memory");
}
DEVINL void sched_fence() { asm volatile("griddepcontrol.launch_dependents;" ::: "memory"); }

__device__ __align__(1024) bf16 g_xs[2048 * 1024];
__device__ __align__(1024) bf16 g_os[2048 * 1024];
__device__ __align__(1024) bf16 g_k[32 * 2048 * 32];
__device__ __align__(1024) bf16 g_v[32 * 2048 * 32];
__device__ __align__(16) uint32_t g_esc[4 * 65536 * 16];
__device__ __align__(128) float2 g_stats[8 * 2048];
__device__ __align__(16) float g_csp[2 * 16 * 8 * 192];
__device__ __align__(128) float g_kn[2 * 128 * 16];
__device__ unsigned long long g_halo[2 * 128 * 32 * 32];
__device__ __align__(128) uint32_t g_cnt[256 * 32];
__device__ uint32_t g_epoch;

DEVINL uint32_t* cnt_x(int l, int bm) { return g_cnt + (l * 8 + bm) * 32; }
DEVINL uint32_t* cnt_o(int l, int pm, int h) { return g_cnt + (32 + (l * 16 + pm) * 2 + h) * 32; }
DEVINL uint32_t* cnt_kv(int lb, int bn) { return g_cnt + (160 + lb * 16 + bn) * 32; }
DEVINL uint32_t* cnt_ad(int bn) { return g_cnt + (192 + bn) * 32; }
DEVINL uint32_t* cnt_cs(int t, int bn) { return g_cnt + (208 + t * 16 + bn) * 32; }

DEVINL int qord(int i, int l, int pn) { return l == 0 ? i : i < 4 ? ((2 * pn) ^ (i & 2)) + (i & 1) : i - 4 < 2 * (pn & 6) ? i - 4 : i; }
struct Params {
  CUtensorMap m[15];
  const bf16* x0;
  const bf16* wq[2];
  uint32_t zero;
  int map[128];
  struct { uint64_t kd, vd; } kv[9];
};
enum { M_X0A = 0, M_XSA, M_WQA, M_WQB, M_WOA, M_WOB, M_OS, M_K, M_V, M_X0R, M_XSR, M_XSO, M_OUT, M_XST, M_X0H, M_COUNT };

constexpr uint32_t QSTG = 57344;
constexpr uint32_t T0 = 65536, TSTG = 32768;
constexpr uint32_t ONES = 230400;
constexpr uint32_t PSTG = 32768, RES = 196608;
constexpr uint32_t KSC = 98304, VSC = 133120;
constexpr uint32_t ROWST = 229376, COLS = 231424, BARS = 232192, SMEM_BYTES = 232448;
constexpr uint32_t B_QF = BARS, B_QE = BARS + 32, B_TF = BARS + 64, B_TE = BARS + 96, B_PF = BARS + 128, B_PE = BARS + 176,
                   B_RF = BARS + 224, W_X = BARS + 232, W_O = BARS + 236, B_QL = BARS + 240, B_PA = BARS + 248;
enum { NB_ST = 1, NB_KV = 2  , NB_DONE = 3, NB_SC = 4, NB_SIG = 5  , NB_KN = 9  , NB_X = 11, NB_HALO = 12  , NB_X0 = 15 };

DEVINL uint32_t pslot_b(uint32_t s) { return ((0x320415u >> (4 * s)) & 7) * 16384u; }
DEVINL uint32_t pslot_a(uint32_t s, int l) { return 98304u + ((((l & 1) ? 0x541230u : 0x041235u) >> (4 * s)) & 7) * 16384u; }

constexpr float QSCALE = 0.17677669529663687f * 1.4426950408889634f;
constexpr uint32_t QPARK = 32768;

DEVINL uint32_t exp2_pair(float s0, float s1, uint32_t half, uint32_t lsb) {
  constexpr float M = 383.f - 0.591914f + 0.00390625f;
  const uint32_t B = __byte_perm(__float_as_uint(s0 + M), __float_as_uint(s1 + M), 0x6521);
  uint32_t w, E, r;
  asm("lop3.b32 %0, %1, 0x807F807F, %2, 0xEA;" : "=r"(w) : "r"(B), "r"(half));
  asm("lop3.b32 %0, %1, 0x7F807F80, %2, 0xEA;" : "=r"(E) : "r"(B), "r"(lsb));
  asm("fma.rn.bf16x2 %0, %1, %2, %3;" : "=r"(r) : "r"(B), "r"(w), "r"(E));
  return r;
}
DEVINL uint32_t exp2_h2(uint32_t s, uint32_t nsig) {
  uint32_t r = hadd2(s, 0x65F565F5u), d;
  asm("{.reg .b64 t; cvt.u64.u32 t, %0; cvt.u32.u64 %0, t;}" : "+r"(r));
  const uint32_t w = hfma2(s, 0x38A038A0u, hfma2(r, nsig, 0x62E562E5u));
  const uint32_t m = hfma2(w, w, 0x48244857u);
  asm("{.reg .b32 t; shl.b32 t, %1, 7; add.u32 %0, t, %2;}" : "=r"(d) : "r"(r), "r"(m));
  return d;
}
DEVINL uint32_t unesc(uint32_t u, const uint32_t* esc) {
  if ((u & 0x7C00u) == 0x7C00u || (u & 0x7C000000u) == 0x7C000000u) return __ldcg(esc);
  float lo, hi;
  asm("{.reg .f16 a, b; mov.b32 {a, b}, %2; cvt.f32.f16 %0, a; cvt.f32.f16 %1, b;}" : "=f"(lo), "=f"(hi) : "r"(u));
  return pack2(lo, hi);
}

DEVINL void attn_slow(const uint32_t (&q)[8], int head, const uint32_t* kesc, float (&res)[20], int lane) {
  const int g = lane >> 2, qd = lane & 3;
  const bf16* kb = g_k + (size_t)head * 2048 * 32;
  const bf16* vb = g_v + (size_t)head * 2048 * 32;
  float o[4][4], m0 = -INFINITY, m1 = -INFINITY, l0 = 0.f, l1 = 0.f;
#pragma unroll
  for (int j = 0; j < 4; j++) { o[j][0] = o[j][1] = o[j][2] = o[j][3] = 0.f; }
#pragma unroll 1
  for (int k0 = 0; k0 < 2048; k0 += 16) {
    float s[2][4];
#pragma unroll
    for (int nt = 0; nt < 2; nt++) {
      s[nt][0] = s[nt][1] = s[nt][2] = s[nt][3] = 0.f;
      const uint32_t* kp = (const uint32_t*)(kb + (size_t)(k0 + nt * 8 + g) * 32) + qd;
      const uint32_t* ke = kesc + (k0 + nt * 8 + g) * 16 + qd;
      const uint32_t k0r = unesc(__ldcg(kp), ke), k1r = unesc(__ldcg(kp + 4), ke + 4), k2r = unesc(__ldcg(kp + 8), ke + 8), k3r = unesc(__ldcg(kp + 12), ke + 12);
      __syncwarp();
      mma16816(s[nt], q[0], q[1], q[2], q[3], k0r, k1r);
      mma16816(s[nt], q[4], q[5], q[6], q[7], k2r, k3r);
    }
    float a0 = fmaxf(fmaxf(s[0][0], s[0][1]), fmaxf(s[1][0], s[1][1]));
    float a1 = fmaxf(fmaxf(s[0][2], s[0][3]), fmaxf(s[1][2], s[1][3]));
    a0 = fmaxf(a0, __shfl_xor_sync(~0u, a0, 1)); a0 = fmaxf(a0, __shfl_xor_sync(~0u, a0, 2));
    a1 = fmaxf(a1, __shfl_xor_sync(~0u, a1, 1)); a1 = fmaxf(a1, __shfl_xor_sync(~0u, a1, 2));
    const float n0 = fmaxf(m0, a0), n1 = fmaxf(m1, a1);
    const float c0 = (m0 == n0) ? 1.f : ex2(m0 - n0), c1 = (m1 == n1) ? 1.f : ex2(m1 - n1);
    m0 = n0; m1 = n1;
    const uint32_t p0 = pack2(ex2(s[0][0] - n0), ex2(s[0][1] - n0)), p1 = pack2(ex2(s[0][2] - n1), ex2(s[0][3] - n1));
    const uint32_t p2 = pack2(ex2(s[1][0] - n0), ex2(s[1][1] - n0)), p3 = pack2(ex2(s[1][2] - n1), ex2(s[1][3] - n1));
    l0 = l0 * c0 + bf_lo(p0) + bf_hi(p0) + bf_lo(p2) + bf_hi(p2);
    l1 = l1 * c1 + bf_lo(p1) + bf_hi(p1) + bf_lo(p3) + bf_hi(p3);
#pragma unroll
    for (int j = 0; j < 4; j++) {
      o[j][0] *= c0; o[j][1] *= c0; o[j][2] *= c1; o[j][3] *= c1;
      const unsigned short* vp = (const unsigned short*)(vb + (size_t)(k0 + 2 * qd) * 32 + j * 8 + g);
      const uint32_t b0 = (uint32_t)__ldcg(vp) | ((uint32_t)__ldcg(vp + 32) << 16);
      const uint32_t b1 = (uint32_t)__ldcg(vp + 256) | ((uint32_t)__ldcg(vp + 288) << 16);
      mma16816(o[j], p0, p1, p2, p3, b0, b1);
    }
  }
  l0 += __shfl_xor_sync(~0u, l0, 1); l0 += __shfl_xor_sync(~0u, l0, 2);
  l1 += __shfl_xor_sync(~0u, l1, 1); l1 += __shfl_xor_sync(~0u, l1, 2);
#pragma unroll
  for (int j = 0; j < 4; j++) { res[4 * j] = o[j][0]; res[4 * j + 1] = o[j][1]; res[4 * j + 2] = o[j][2]; res[4 * j + 3] = o[j][3]; }
  res[16] = l0; res[18] = l1;
}

__global__ void __cluster_dims__(2, 1, 1) __launch_bounds__(384, 1) fused_kernel(const __grid_constant__ Params prm) {
  extern __shared__ __align__(1024) char smem[];
  const uint32_t sb = (uint32_t)__cvta_generic_to_shared(smem);
  const int tid = threadIdx.x, lane = tid & 31;
  const int wg = __shfl_sync(0xffffffffu, tid >> 7, 0);
  const int w = __shfl_sync(0xffffffffu, (tid >> 5) & 3, 0);
  const int bm = remap(blockIdx.x) >> 4, bn = remap(blockIdx.x) & 15;

  auto first_tile = [&](int kt) {
    e_expect_tx(sb + B_QF + 8 * kt, QSTG);
    tma_ld(sb + kt * QSTG, &prm.m[M_X0A], kt * 64, bm * 256, sb + B_QF + 8 * kt);
    tma_ld3(sb + kt * QSTG + 32768, &prm.m[M_WQA], bn * 64, kt * 64, 0, sb + B_QF + 8 * kt);
  };
  if (wg < 2) {
  } else if (w == 0) {
    if (lane < 4) { mbar_init(sb + B_QF + 8 * lane, 1); asm volatile("fence.mbarrier_init.release.cluster;" ::: "memory"); }
    __syncwarp();
    first_tile(0);
  } else if (w == 1) {
    if (lane == 25) *(uint2*)(smem + W_X) = make_uint2(0u, 0u);
    else if (lane < 28) {
      mbar_init(sb + B_QE + 8 * lane, lane < 4 ? 4 : lane < 8 ? 1 : lane < 12 ? 2 : lane < 18 ? 1 : lane < 24 ? 4 : lane < 27 ? 1 : 2);
      asm volatile("fence.mbarrier_init.release.cluster;" ::: "memory");
    }
  } else if (w == 2 && lane < M_COUNT) {
    asm volatile("prefetch.tensormap [%0];" ::"l"(&prm.m[lane]) : "memory");
  }
  __syncthreads();
  asm volatile("barrier.cluster.arrive.relaxed.aligned;" ::: "memory");

  if (wg == 2) {
    asm volatile("setmaxnreg.dec.sync.aligned.u32 56;");
    const uint32_t ep1 = *(volatile uint32_t*)&g_epoch + 1;
    if (w == 0) {
      first_tile(1);
      mbar_wait(sb + B_QF, 0);
      first_tile(2); first_tile(3);
#pragma unroll 1
      for (int kt = 4; kt < 16; kt++) l2_prefetch(prm.wq[0] + kt * 196608 + blockIdx.x * 1536, 3072);
      cluster_wait();
#pragma unroll 1
      for (int l = 0; l < 4; l++) {
        IDS();
        const CUtensorMap* mw = &prm.m[M_WQA + (l & 1)];
        const CUtensorMap* mx = &prm.m[l == 0 ? M_X0A : M_XSA];
        const CUtensorMap* mh = &prm.m[l == 0 ? M_X0H : M_XSO];
        const CUtensorMap* mo = &prm.m[M_WOA + (l & 1)];
        auto q_b = [&](int i) {
          const int s = i & 3;
          mbar_wait(sb + B_QE + 8 * s, ((i >> 2) & 1) ^ 1);
          e_expect_tx(sb + B_QF + 8 * s, QSTG);
          tma_ld3(sb + s * QSTG + 32768, mw, bn * 64, qord(i, l, pn) * 64, 0, sb + B_QF + 8 * s);
        };
        uint32_t rdy = l ? 0u : ~0u;
        auto q_a = [&](int i) {
          const int kt = qord(i, l, pn);
          await_bit(sb + W_X, l, kt >> 1, rdy);
          if (i < 4) tma_ld(sb + i * QSTG, mx, kt * 64, bm * 256, sb + B_QF + 8 * i);
          else tma_ld_mc(sb + (i & 3) * QSTG + rank * 16384, mh, kt * 64, bm * 256 + rank * 128, sb + B_QF + 8 * (i & 3));
        };
        if (l > 0) {
          await_bit(sb + W_X, l, pn, rdy);
#pragma unroll 1
          for (int i = 0; i < 2; i++) {
            e_expect_tx(sb + B_QF + 8 * i, 16384);
            tma_ld(sb + i * QSTG + (po ^ 1) * 16384, &prm.m[M_XSO], (2 * pn + i) * 64, (pm ^ 1) * 128, sb + B_QF + 8 * i);
          }
          mbar_wait(sb + B_QF, 0);
          q_a(2);
          mbar_wait(sb + B_QF + 8, 0);
        }
#pragma unroll 1
        for (int i = l ? 3 : 4; i < 16; i++) {
          q_b(i); q_a(i);
        }
        if (l & 1) {
          if (l == 3) poll_ge(cnt_ad(bn), ep1 * 16);
          bar_sync(NB_KV, 288);
          sts128(sb + ONES + lane * 32, 0x3f803f80u, 0x3f803f80u, 0x3f803f80u, 0x3f803f80u);
          sts128(sb + ONES + lane * 32 + 16, 0x3f803f80u, 0x3f803f80u, 0x3f803f80u, 0x3f803f80u);
          fence_async_smem();
          __syncwarp();
          e_arrive(sb + B_TF);
          const int krow = 2 * bn * 2048 + bm * 256;
          uint32_t* kvc = cnt_kv(l >> 1, bn);
          tma_st(&prm.m[M_K], 0, krow, sb + T0);
          tma_st(&prm.m[M_V], 0, krow, sb + T0 + 16384);
          bulk_commit(); bulk_wait_n<0>();
          e_red(kvc + bm);
          bar_sync(NB_KV + 12, 288);
          tma_st(&prm.m[M_K], 0, krow + 2048, sb);
          tma_st(&prm.m[M_V], 0, krow + 2048, sb + 16384);
          bulk_commit();
          uint32_t seen = 0;
#pragma unroll 1
          for (int it = 1; it < 16; it++) {
            const int s = it & 3, blk = it;
            if (it == 4) { bulk_wait_n<0>(); e_red(kvc + bm); }
            if (it == 12) { e_expect_tx(sb + B_RF, 32768); tma_ld3(sb + RES, &prm.m[M_XSR], 0, pm * 128, 2 * pn, sb + B_RF); }
            if (it == 2 || it == 3) mbar_wait(sb + B_TF + 8 * (it - 1), 0);
            mbar_wait(sb + B_TE + 8 * s, ((it >> 2) & 1) ^ 1);
            if (it < 8) {
#pragma unroll 1
              for (uint32_t n = 0; n < 200000u && !((seen >> it) & 1); n++)
                seen = __ballot_sync(~0u, (int)(ld_acquire(kvc + ((bm + lane) & 7)) - (ep1 * 2 - 1)) >= 0);
              fence_async_gl();
            } else if (it == 8) { poll_ge(kvc + (lane & 7), ep1 * 2); fence_async_gl(); }
            const int row = (2 * bn + (it >> 3)) * 2048 + ((bm + blk) & 7) * 256;
            e_expect_tx(sb + B_TF + 8 * s, 32768);
            tma_ld(sb + T0 + s * TSTG, &prm.m[M_K], 0, row, sb + B_TF + 8 * s);
            tma_ld(sb + T0 + s * TSTG + 16384, &prm.m[M_V], 0, row, sb + B_TF + 8 * s);
          }
        }
        auto p_b = [&](int i, uint32_t s, uint32_t par) {
          mbar_wait(sb + B_PE + 8 * s, par ^ 1);
          e_expect_tx(sb + B_PF + 8 * s, PSTG);
          tma_ld5(sb + pslot_b(s), mo, i >> 3, 2 * (i & 7), 2 * pn, sb + B_PF + 8 * s);
        };
        auto p_a = [&](int i, uint32_t s) {
          await_bit(sb + W_O, l + 1, i, rdy);
          tma_ld_mc(sb + pslot_a(s, l) + rank * 8192, &prm.m[M_OS], i * 64, pm * 128 + rank * 64, sb + B_PF + 8 * s);
        };
        auto p_a2 = [&](int i) {
          await_bit(sb + W_O, l + 1, i, rdy);
          tma_ld(sb + pslot_a(i, l), &prm.m[M_OS], i * 64, pm * 128, sb + B_PF + 8 * i);
          tma_ld(sb + pslot_a(i, l) + 8192, &prm.m[M_OS], i * 64, pm * 128 + 64, sb + B_PF + 8 * i);
        };
        rdy = 0;
        if (l & 1) {
#pragma unroll 1
          for (int u = 0; u < 6; u++) { const int i = (0x205413 >> (4 * u)) & 7; if (u == 4) mbar_wait(sb + B_TE, 1); p_b(i, i, i < 4 ? 1 : 0); }
#pragma unroll 1
          for (int u = 0; u < 6; u++) {
            const int i = (0x542130 >> (4 * u)) & 7;
            if (!(u & 1)) mbar_wait(sb + B_TE + 8 + 4 * u, 1);
            p_a2(i);
          }
        } else {
#pragma unroll 1
          for (int u = 0; u < 6; u++) { const int i = (0x025413 >> (4 * u)) & 7; if (u == 0 || u == 3) mbar_wait(sb + B_QE + 8 * (u / 3), 1); p_b(i, i, 0); }
          mbar_wait(sb + B_QE + 24, 1);
          e_expect_tx(sb + B_RF, 32768);
          tma_ld3(sb + RES, &prm.m[l == 0 ? M_X0R : M_XSR], 0, pm * 128, 2 * pn, sb + B_RF);
          p_a2(0);
          bar_sync(NB_DONE, 96);
          e_arrive_both(sb + B_PA);
          p_a2(1); p_a2(2);
          mbar_wait(sb + B_PA, (l >> 1) & 1);
#pragma unroll 1
          for (int i = 3; i < 6; i++) { if (i == 4) mbar_wait(sb + B_PF + 8, 0); p_a(i, i); }
        }
        uint32_t s = 0, lap = 1;
#pragma unroll 1
        for (int i = 6; i < 16; i++) {
          p_b(i, s, ((s < 4 ? l : 0) + lap) & 1);
          p_a(i, s);
          if (++s == 6) { s = 0; lap++; }
        }
        const CUtensorMap* mn = &prm.m[M_WQA + ((l + 1) & 1)];
        if (l < 3) {
          mbar_wait(sb + B_PE + 8 * 4, 1); mbar_wait(sb + B_PE + 8 * 5, 1);
          tma_ld3(sb + 32768, mn, bn * 64, 2 * pn * 64, 0, sb + B_QL);
          mbar_wait(sb + B_PE + 8 * 0, l & 1);
          tma_ld3(sb + QSTG + 32768, mn, bn * 64, (2 * pn + 1) * 64, 0, sb + B_QL);
          mbar_wait(sb + B_PE + 8 * 1, l & 1);
          e_expect_tx(sb + B_QF + 16, QSTG);
          tma_ld3(sb + 2 * QSTG + 32768, mn, bn * 64, ((2 * pn) ^ 2) * 64, 0, sb + B_QF + 16);
        }
        if (l < 3) { bar_sync(NB_X, 288); e_expect_tx(sb + B_QL, 49152); }
      }
      if (blockIdx.x == 0 && lane_id() == 0) *(volatile uint32_t*)&g_epoch = ep1;
    } else {
      const int hw = w - 1;
      cluster_wait();
      mbar_wait(sb + B_QF, 0);
#pragma unroll 1
      for (int l = 0; l < 4; l++) {
        IDS();
        if (hw == 2 && l > 0) watch(cnt_x(l, bm) + (lane & 7), ep1 * 2, 0xFFu, l, sb + W_X);
        if (l == 0) {
#pragma unroll 1
          for (int r = 2 * hw; r < 16; r += 6) {
            const uint4* p = (const uint4*)(prm.x0 + (size_t)(b * 16 + r) * 1024) + lane;
            float s1[2] = {0.f, 0.f}, s2[2] = {0.f, 0.f};
#pragma unroll
            for (int i = 0; i < 8; i++) {
              const uint4 v = __ldg(p + 32 * i);
              const uint32_t u[4] = {v.x, v.y, v.z, v.w};
#pragma unroll
              for (int k = 0; k < 4; k++) { const float a = bf_lo(u[k]), c = bf_hi(u[k]); s1[i >> 2] += a + c; s2[i >> 2] = fmaf(a, a, fmaf(c, c, s2[i >> 2])); }
            }
#pragma unroll
            for (int o = 16; o; o >>= 1)
#pragma unroll
              for (int rr = 0; rr < 2; rr++) { s1[rr] += __shfl_xor_sync(~0u, s1[rr], o); s2[rr] += __shfl_xor_sync(~0u, s2[rr], o); }
            if (lane == 0) *(float4*)&g_stats[b * 16 + r] = make_float4(s1[0], s2[0], s1[1], s2[1]);
          }
        }
        if (l == 1) { uint32_t rdy = 0; await_bit<true>(sb + W_X, 1, pn, rdy); mbar_hint(sb + B_QF + 8, 0); }
        if (l < 2) {
          float cs[8];
#pragma unroll
          for (int i = 0; i < 8; i++) cs[i] = 0.f;
          const uint4* wp = (const uint4*)(prm.wq[l] + (size_t)(bm * 128 + (lane >> 3)) * 3072 + hw * 1024 + bn * 64) + (lane & 7);
#pragma unroll 8
          for (int i = 0; i < 32; i++) {
            const uint4 v = __ldg(wp + (size_t)i * 4 * 384);
            cs[0] += bf_lo(v.x); cs[1] += bf_hi(v.x); cs[2] += bf_lo(v.y); cs[3] += bf_hi(v.y);
            cs[4] += bf_lo(v.z); cs[5] += bf_hi(v.z); cs[6] += bf_lo(v.w); cs[7] += bf_hi(v.w);
          }
#pragma unroll
          for (int i = 0; i < 8; i++) { cs[i] += __shfl_xor_sync(~0u, cs[i], 8); cs[i] += __shfl_xor_sync(~0u, cs[i], 16); }
          if (lane < 8) {
            float4* d = (float4*)(g_csp + ((l * 16 + bn) * 8 + bm) * 192 + hw * 64 + lane * 8);
            d[0] = make_float4(cs[0], cs[1], cs[2], cs[3]); d[1] = make_float4(cs[4], cs[5], cs[6], cs[7]);
          }
          __syncwarp();
          asm volatile("fence.acq_rel.gpu;" ::: "memory");
          e_red_relaxed(cnt_cs(l, bn));
          if (l == 0) e_red_relaxed(cnt_x(0, bm) + pn);
          poll_ge(lane < 8 && l == 0 ? cnt_x(0, bm) + lane : cnt_cs(l, bn), ep1 * (lane < 8 && l == 0 ? 6 : 24));
        }
        if (l > 0) {
          uint32_t rdy = 0;
#pragma unroll 1
          for (int j = 0; j < 8; j++) await_bit<true>(sb + W_X, l, j, rdy);
        }
#pragma unroll 1
        for (int it = hw * 32 + lane; it < 176; it += 96) {
          const bool rows = it < 128;
          const float4* p = rows ? (const float4*)(g_stats + bm * 256) + it : (const float4*)(g_csp + ((l & 1) * 16 + bn) * 8 * 192) + (it - 128);
          const int stride = rows ? 1024 : 48, np = rows && l == 0 ? 1 : 8;
          float4 a = make_float4(0.f, 0.f, 0.f, 0.f);
#pragma unroll
          for (int k = 0; k < 8; k++) if (k < np) { const float4 v = __ldcg(p + k * stride); a.x += v.x; a.y += v.y; a.z += v.z; a.w += v.w; }
          if (rows) {
            const float m0 = a.x * (1.f / 1024.f), m1 = a.z * (1.f / 1024.f);
            const float v0 = fmaxf(a.y * (1.f / 1024.f) - m0 * m0, 0.f), v1 = fmaxf(a.w * (1.f / 1024.f) - m1 * m1, 0.f);
            const float r0 = __fdividef(1.f, bf_round(sqrtf(bf_round(bf_round(v0) + 1e-5f)))), r1 = __fdividef(1.f, bf_round(sqrtf(bf_round(bf_round(v1) + 1e-5f))));
            a = make_float4(r0, -bf_round(m0) * r0, r1, -bf_round(m1) * r1);
          }
          *(float4*)(smem + ROWST + it * 16) = a;
        }
        __syncwarp();
        if (lane == 0) asm volatile("red.release.cta.shared.add.u32 [%0], 0x100;" ::"r"(sb + W_X) : "memory");
        if (hw == 2) {
          if (!(l & 1)) {
            bar_sync(NB_ST, 288);
            const volatile unsigned long long* hp = g_halo + ((size_t)(l >> 1) * 128 + b - 16) * 1024 + lane;
#pragma unroll 1
            for (int h = 0; h < 2; h++) {
              uint32_t t[16];
#pragma unroll
              for (int i = 0; i < 16; i++) t[i] = 0;
#pragma unroll 1
              for (uint32_t n = bm ? 0 : 100000u; n < 100000u; n++) {
                uint32_t miss = 0;
#pragma unroll
                for (int i = 0; i < 16; i++) {
                  const unsigned long long v = hp[h * 512 + i * 32];
                  t[i] = (uint32_t)v; miss |= (uint32_t)(v >> 32) ^ ep1;
                }
                if (__all_sync(~0u, !miss)) break;
              }
              const uint32_t r = (lane & 7) + ((lane >> 3) & 1) * 8, rv = lane >> 2;
#pragma unroll
              for (int jj = 0; jj < 2; jj++) stsm4(sb + KSC + r * 128 + (((4 * h + 2 * jj + (lane >> 4)) ^ (r & 7)) << 4), t[4 * jj], t[4 * jj + 1], t[4 * jj + 2], t[4 * jj + 3]);
              const uint32_t ad = sb + VSC + rv * 128 + (((4 * h + (lane & 3)) ^ (rv & 7)) << 4);
              sts128(ad, t[8], t[10], t[12], t[14]); sts128(ad + 1024, t[9], t[11], t[13], t[15]);
              bar_arrive(NB_HALO + h, 64);
            }
          } else {
            mbar_hint(sb + B_TF + 8, 0);
            poll_ge(cnt_kv(l >> 1, bn) + (lane & 7), ep1 * 2);
            const uint4 v = __ldcg((const uint4*)(g_kn + ((l >> 1) * 128 + bn * 8) * 16) + lane);
            const uint32_t mx = max(max(v.x, v.y), max(v.z, v.w));
            const uint32_t m0 = __reduce_max_sync(~0u, (lane & 2) ? 0u : mx), m1 = __reduce_max_sync(~0u, (lane & 2) ? mx : 0u);
            if (lane == 0) *(uint2*)(smem + ROWST) = make_uint2(m0, m1);
            __syncwarp();
            bar_arrive(NB_KN, 160); bar_arrive(NB_KN + 1, 160);
          }
        } else {
#pragma unroll 1
          for (int h = 0; h < 2; h++) {
            bar_sync(NB_SIG + 2 * h + hw, 160);
            if (h == 1 && !(l & 1)) bar_arrive(NB_DONE, 96);
            e_red(cnt_o(l, 2 * bm + hw, h) + (bn >> 1));
            if (h == 1 && l == 1) e_red(cnt_ad(bn));
          }
        }
        if (hw == 2) watch(cnt_o(l, pm, (lane >> 3) & 1) + (lane & 7), ep1 * 2, 0xFFFFu, l + 1, sb + W_O);
        if (hw == 0 && l < 3) {
          bar_sync(NB_X0, 288);
          e_red(cnt_x(l + 1, bm) + pn);
        }
      }
    }
  } else {
    asm volatile("setmaxnreg.inc.sync.aligned.u32 224;");
    const uint32_t zero = prm.zero;
    cluster_wait();
#pragma unroll 1
    for (int l = 0; l < 4; l++) {
      {
        float acc[2][96];
#pragma unroll
        for (int i = 0; i < 96; i++) { acc[0][i] = 0.f; acc[1][i] = 0.f; }
        fence_regs(acc[0]); fence_regs(acc[1]);
        const bool early = l > 0 && wg == ((cta_id() >> 3) & 1);
        const uint32_t ep1 = *(volatile uint32_t*)&g_epoch + 1;
#pragma unroll 1
        for (int kt = 0; kt < 16; kt++) {
          const int s = kt & 3;
          if (l > 0 && kt == 0) mbar_wait(sb + B_QL, (l + 1) & 1);
          if (!(early && kt < 2)) mbar_wait(sb + B_QF + 8 * s, (kt >> 2) & 1);
          const uint64_t da = mkdesc(sb + s * QSTG + wg * 16384, 16, 1024, 1), db = mkdesc(sb + s * QSTG + 32768, 8192, 1024, 1);
          wg_fence();
#pragma unroll
          for (int k = 0; k < 4; k++)
#pragma unroll
            for (int m = 0; m < 2; m++) wgmma_m64n192k16_ss_tb(acc[m], da + m * 512 + k * 2, db + k * 128, 1);
          wg_commit();
          wg_wait<1>();
          if (early && (kt == 1 || kt == 2)) mbar_wait(sb + B_QF + 8 * (kt - 1), 0);
          if (kt > 0 && w == 0) e_arrive_both(sb + B_QE + 8 * ((kt - 1) & 3));
        }
#pragma unroll 1
        for (uint32_t n = 0; n < 4000000u; n++) {
          uint32_t v;
          asm volatile("ld.acquire.cta.shared.u32 %0, [%1];" : "=r"(v) : "r"(sb + W_X) : "memory");
          if ((v >> 8) == (uint32_t)(l * 256 + 3)) break;
        }
        IDS();
        const int g = lane >> 2, qd = lane & 3;
        float2 st[2][2];
#pragma unroll
        for (int m = 0; m < 2; m++)
#pragma unroll
          for (int hh = 0; hh < 2; hh++) st[m][hh] = lds64f(sb + ROWST + (wg * 128 + m * 64 + w * 16 + g + 8 * hh) * 8);
        float2 cs[4];
        auto load_cs = [&](int gi) {
#pragma unroll
          for (int j = 0; j < 4; j++) cs[j] = lds64f(sb + COLS + (gi * 32 + j * 8 + 2 * qd) * 4);
        };
        load_cs(2);
        wg_wait<0>();
        fence_regs(acc[0]); fence_regs(acc[1]);
        if (w == 0) e_arrive_both(sb + B_QE + 8 * 3);
        if (!(l & 1)) bar_arrive(NB_ST, 288);
        auto norm_tile = [&](int gi, int m, float sc, uint32_t (&t)[8], float (&nrm)[2], bool h16 = false) {
          const float r0 = st[m][0].x * sc, s0 = st[m][0].y * sc, r1 = st[m][1].x * sc, s1 = st[m][1].y * sc;
          float n0 = 0.f, n1 = 0.f;
#pragma unroll
          for (int j = 0; j < 4; j++) {
            const float* a = &acc[m][16 * gi + 4 * j];
            const float v0 = fmaf(a[0], r0, s0 * cs[j].x), v1 = fmaf(a[1], r0, s0 * cs[j].y);
            const float v2 = fmaf(a[2], r1, s1 * cs[j].x), v3 = fmaf(a[3], r1, s1 * cs[j].y);
            n0 = fmaf(v0, v0, fmaf(v1, v1, n0)); n1 = fmaf(v2, v2, fmaf(v3, v3, n1));
            t[2 * j] = h16 ? pack2h(v0, v1) : pack2(v0, v1); t[2 * j + 1] = h16 ? pack2h(v2, v3) : pack2(v2, v3);
          }
          nrm[0] = n0; nrm[1] = n1;
        };
        auto norm_group = [&](int gi, float sc, uint32_t (&t)[2][8], float (&nrm)[2][2]) { norm_tile(gi, 0, sc, t[0], nrm[0]); norm_tile(gi, 1, sc, t[1], nrm[1]); };
        uint32_t q[2][2][8];
        const uint32_t srow = (lane & 7) + ((lane >> 3) & 1) * 8;
        const uint32_t row0 = wg * 128 + w * 16;
        auto put_o = [&](int h, int m, const float (&o)[16], float i0, float i1) {
          IDS();
          bf16* op = g_os + (size_t)(bm * 256 + row0 + m * 64 + (lane >> 2)) * 1024 + h * 512 + bn * 32 + (lane & 3) * 8;
          *(uint4*)op = make_uint4(pack2(o[0] * i0, o[1] * i0), pack2(o[4] * i0, o[5] * i0), pack2(o[8] * i0, o[9] * i0), pack2(o[12] * i0, o[13] * i0));
          *(uint4*)(op + 8 * 1024) = make_uint4(pack2(o[2] * i1, o[3] * i1), pack2(o[6] * i1, o[7] * i1), pack2(o[10] * i1, o[11] * i1), pack2(o[14] * i1, o[15] * i1));
        };
        if (!(l & 1)) {
          auto put_kv = [&](int gi, uint32_t r0, const uint32_t (&t)[8]) {
            if (gi < 4) {
              const uint32_t r = r0 + srow;
#pragma unroll
              for (int jj = 0; jj < 2; jj++) stsm4(sb + KSC + r * 128 + (((4 * (gi - 2) + 2 * jj + (lane >> 4)) ^ (r & 7)) << 4), t[4 * jj], t[4 * jj + 1], t[4 * jj + 2], t[4 * jj + 3]);
            } else {
              const uint32_t r = r0 + g, ad = sb + VSC + r * 128 + (((4 * (gi - 4) + qd) ^ (r & 7)) << 4);
              sts128(ad, t[0], t[2], t[4], t[6]); sts128(ad + 1024, t[1], t[3], t[5], t[7]);
            }
          };
          const bool send = wg == 1 && w == 3 && bm < 7;
          unsigned long long* hp = g_halo + ((size_t)(l >> 1) * 128 + b) * 1024 + lane;
          uint32_t t[4][2][8];
#pragma unroll
          for (int mm = 0; mm < 2; mm++)
#pragma unroll
            for (int u = 0; u < 4; u++) {
              float nrm[2];
              norm_tile(2 + (u >> 1) + 2 * (u & 1), 1 - mm, 1.f, t[u][1 - mm], nrm);
              load_cs(u == 0 ? 4 : u == 1 ? 3 : u == 2 ? 5 : mm == 0 ? 2 : 0);
              if (mm == 0 && send) {
#pragma unroll
                for (int i = 0; i < 8; i++) st_tagged(hp + (u * 8 + i) * 32, t[u][1][i], ep1);
              }
            }
          mbar_wait(sb + B_QE + 24, 1);
#pragma unroll
          for (int u = 0; u < 4; u++) { put_kv(2 + (u >> 1) + 2 * (u & 1), 16 + row0, t[u][0]); put_kv(2 + (u >> 1) + 2 * (u & 1), 16 + row0 + 64, t[u][1]); }
          { float nrm[2][2]; norm_group(0, 1.f, q[0], nrm); }
          bar_sync(NB_SC, 256);
          const bool e = g & 1, sel = 2 * qd + (g & 1) >= g + 2, first = bm == 0 && row0 == 0;
#pragma unroll 1
          for (int h = 0; h < 2; h++) {
            if (row0 == 0) bar_sync(NB_HALO + h, 64);
            float s[2][4][4];
            uint32_t vf[2][4][4], pf[2][2][4];
#pragma unroll
            for (int m = 0; m < 2; m++)
#pragma unroll
              for (int nt = 0; nt < 4; nt++) {
                uint32_t kf[4];
                const uint32_t r = row0 + m * 64 + 8 * nt + (lane & 7), ch = 4 * h + (lane >> 3);
                ldsm4(sb + KSC + r * 128 + ((ch ^ (r & 7)) << 4), kf);
                s[m][nt][0] = s[m][nt][1] = s[m][nt][2] = s[m][nt][3] = 0.f;
                mma16816(s[m][nt], q[0][m][0], q[0][m][1], q[0][m][2], q[0][m][3], kf[0], kf[1]);
                mma16816(s[m][nt], q[0][m][4], q[0][m][5], q[0][m][6], q[0][m][7], kf[2], kf[3]);
              }
#pragma unroll
            for (int m = 0; m < 2; m++)
#pragma unroll
              for (int i = 0; i < 4; i++) {
                const uint32_t r = row0 + m * 64 + 16 * (i >> 1) + srow, ch = 4 * h + 2 * (i & 1) + (lane >> 4);
                ldsm4t(sb + VSC + r * 128 + ((ch ^ (r & 7)) << 4), vf[m][i]);
              }
            float va[4], vb[4], mx[4];
#pragma unroll
            for (int i = 0; i < 4; i++) {
              const int m = i >> 1, hh = i & 1;
              const float a = e ? s[m][hh + 1][2 * hh + 1] : s[m][hh + 1][2 * hh];
              const float lo = e ? s[m][hh][2 * hh + 1] : s[m][hh][2 * hh], hi = e ? s[m][hh + 2][2 * hh + 1] : s[m][hh + 2][2 * hh];
              const uint32_t t = pack2(a, sel ? lo : hi);
              const uint32_t u = pack2(bf_lo(t) * 0.17677669529663687f, bf_hi(t) * 0.17677669529663687f);
              va[i] = (m == 0 && hh == 0 && first) ? -INFINITY : bf_lo(u);
              vb[i] = (m == 0 && first && sel) ? -INFINITY : bf_hi(u);
              mx[i] = fmaxf(va[i], vb[i]);
            }
#pragma unroll
            for (int i = 0; i < 4; i++) mx[i] = fmaxf(mx[i], __shfl_xor_sync(~0u, mx[i], 1));
#pragma unroll
            for (int i = 0; i < 4; i++) mx[i] = fmaxf(mx[i], __shfl_xor_sync(~0u, mx[i], 2));
#pragma unroll
            for (int i = 0; i < 4; i++) {
              va[i] = ex2((va[i] - mx[i]) * 1.4426950408889634f); vb[i] = ex2((vb[i] - mx[i]) * 1.4426950408889634f);
              mx[i] = va[i] + vb[i];
            }
#pragma unroll
            for (int i = 0; i < 4; i++) mx[i] += __shfl_xor_sync(~0u, mx[i], 1);
#pragma unroll
            for (int i = 0; i < 4; i++) mx[i] += __shfl_xor_sync(~0u, mx[i], 2);
#pragma unroll
            for (int i = 0; i < 4; i++) {
              const int m = i >> 1, hh = i & 1;
              const float inv = rcp(mx[i]);
              const uint32_t t = pack2(va[i] * inv, vb[i] * inv);
              const uint32_t pa = e ? t << 16 : t & 0xFFFFu, pb = e ? t & 0xFFFF0000u : t >> 16;
              pf[m][hh][hh + 1] = pa; pf[m][hh][hh] = sel ? pb : 0u; pf[m][hh][hh + 2] = sel ? 0u : pb; pf[m][hh][3 - 3 * hh] = 0u;
            }
#pragma unroll
            for (int m = 0; m < 2; m++) {
              float o[4][4];
#pragma unroll
              for (int j = 0; j < 4; j++) o[j][0] = o[j][1] = o[j][2] = o[j][3] = 0.f;
#pragma unroll
              for (int i = 0; i < 4; i++) {
                const int kk = i >> 1, jj = 2 * (i & 1);
                mma16816(o[jj], pf[m][0][2 * kk], pf[m][1][2 * kk], pf[m][0][2 * kk + 1], pf[m][1][2 * kk + 1], vf[m][i][0], vf[m][i][1]);
                mma16816(o[jj + 1], pf[m][0][2 * kk], pf[m][1][2 * kk], pf[m][0][2 * kk + 1], pf[m][1][2 * kk + 1], vf[m][i][2], vf[m][i][3]);
              }
              const float of[16] = {o[0][0], o[0][1], o[0][2], o[0][3], o[1][0], o[1][1], o[1][2], o[1][3], o[2][0], o[2][1], o[2][2], o[2][3], o[3][0], o[3][1], o[3][2], o[3][3]};
              put_o(h, m, of, 1.f, 1.f);
            }
            bar_arrive(NB_SIG + 2 * h + wg, 160);
            if (h == 0) {
              float nrm[2][2];
              load_cs(1);
              norm_group(1, 1.f, q[0], nrm);
            }
          }
        } else {
          float qn[2];
          auto esc_ptr = [&](int gi) { IDS(); return g_esc + (size_t)(((l & 2) + (gi >> 1)) * 65536 + (2 * bn + (gi & 1)) * 2048) * 16; };
          auto norm_half = [&](int gi, float sc, uint32_t (&t)[2][8], float (&nrm)[2][2]) {
            norm_tile(gi, 0, sc, t[0], nrm[0], true); norm_tile(gi, 1, sc, t[1], nrm[1], true);
            if (!((nrm[0][0] + nrm[0][1]) + (nrm[1][0] + nrm[1][1]) <= 4e9f)) {
              uint32_t* p = esc_ptr(gi) + (bm * 256 + row0 + g) * 16 + qd;
#pragma unroll
              for (int m = 0; m < 2; m++) {
                uint32_t u[8]; float d[2];
                norm_tile(gi, m, sc, u, d);
#pragma unroll
                for (int i = 0; i < 8; i++) p[(m * 64 + (i & 1) * 8) * 16 + (i >> 1) * 4] = u[i];
              }
            }
            __syncwarp();
          };
          {
            auto max_norm = [&](const float (&nrm)[2][2]) {
              const bool o1 = qd & 1, o2 = qd & 2;
              const float a = (o1 ? nrm[1][0] : nrm[0][0]) + __shfl_xor_sync(~0u, o1 ? nrm[0][0] : nrm[1][0], 1);
              const float c = (o1 ? nrm[1][1] : nrm[0][1]) + __shfl_xor_sync(~0u, o1 ? nrm[0][1] : nrm[1][1], 1);
              const float d = (o2 ? c : a) + __shfl_xor_sync(~0u, o2 ? a : c, 2);
              return __uint_as_float(__reduce_max_sync(~0u, __float_as_uint(d)));
            };
#pragma unroll
            for (int h = 0; h < 2; h++) {
              uint32_t t[2][8]; float nrm[2][2];
              const uint32_t kb = sb + (h ? 0 : T0);
              if (h) load_cs(3);
              uint32_t tv[2][8];
              norm_half(2 + h, 1.f, t, nrm);
              load_cs(4 + h);
              float nv[2][2];
              if (h == 1) { const float kn = max_norm(nrm); if (lane == 0) g_kn[((l >> 1) * 128 + bn * 8 + bm) * 16 + 8 + wg * 4 + w] = kn; }
              norm_group(4 + h, 1.f, tv, nv);
              load_cs(h);
              if (h == 0) mbar_wait(sb + B_QE + 24, 1);
#pragma unroll
              for (int i = 0; i < 4; i++) {
                const uint32_t r = row0 + (i >> 1) * 64 + srow;
                stsm4(kb + r * 64 + (((2 * (i & 1) + (lane >> 4)) ^ ((r >> 1) & 3)) << 4), t[i >> 1][4 * (i & 1)], t[i >> 1][4 * (i & 1) + 1], t[i >> 1][4 * (i & 1) + 2], t[i >> 1][4 * (i & 1) + 3]);
              }
#pragma unroll
              for (int m = 0; m < 2; m++) {
                const uint32_t r = row0 + m * 64 + g, ad = kb + 16384 + r * 64 + ((qd ^ ((r >> 1) & 3)) << 4);
                sts128(ad, tv[m][0], tv[m][2], tv[m][4], tv[m][6]); sts128(ad + 512, tv[m][1], tv[m][3], tv[m][5], tv[m][7]);
              }
              fence_async_smem();
              bar_arrive(NB_KV + 12 * h, 288);
              if (h == 0) { const float kn = max_norm(nrm); if (lane == 0) g_kn[((l >> 1) * 128 + bn * 8 + bm) * 16 + wg * 4 + w] = kn; }
              norm_half(h, QSCALE, q[h], nrm);
              qn[h] = max_norm(nrm);
            }
#pragma unroll
            for (int i = 0; i < 4; i++) sts128(sb + QPARK + (wg * 128 + w * 32 + lane) * 16 + i * 4096, q[1][i >> 1][4 * (i & 1)], q[1][i >> 1][4 * (i & 1) + 1], q[1][i >> 1][4 * (i & 1) + 2], q[1][i >> 1][4 * (i & 1) + 3]);
          }
          const bool elected = w == 0 && lane == 0;
          constexpr uint64_t VSTEP = 64 - (64ull << 16);
          constexpr int SK = 2;
          const uint32_t c_nsig = 0xB8A0B8A0u + (lane_id() & zero), c_half = 0x3F003F00u + (lane_id() & zero), c_lsb = 0x00010001u + (lane_id() & zero);
#pragma unroll 1
          for (int pass = 0; pass < 2; pass++) {
            float o[2][20], S[2][32], e[2 * SK];
            uint32_t H[2][16], P0[4], P1[4];
#pragma unroll
            for (int m = 0; m < 2; m++) {
#pragma unroll
              for (int i = 0; i < 20; i++) o[m][i] = 0.f;
#pragma unroll
              for (int i = 0; i < 32; i++) S[m][i] = -126.f;
#pragma unroll
              for (int i = 0; i < 16; i++) H[m][i] = 0xD820D820u;
              fence_regs(o[m]); fence_regs(S[m]); fence_regs(H[m]);
            }
#pragma unroll
            for (int i = 0; i < 4; i++) P0[i] = P1[i] = zero;
#pragma unroll
            for (int i = 0; i < 2 * SK; i++) e[i] = __uint_as_float(zero);
            auto qk = [&](int b, int ks, uint64_t d) {
              wg_n64_rs_nb_f16_f32(S[b], q[0][0][4 * ks], q[0][0][4 * ks + 1], q[0][0][4 * ks + 2], q[0][0][4 * ks + 3], d, ks ? 1 : zero);
              wg_n64_rs_nb_f16_f16(H[b], q[0][1][4 * ks], q[0][1][4 * ks + 1], q[0][1][4 * ks + 2], q[0][1][4 * ks + 3], d, ks ? 1 : zero);
            };
            auto pv = [&](uint64_t d) {
              wgmma_m64n40k16_rs_tb(o[0], P0[0], P0[1], P0[2], P0[3], d, 1);
              wgmma_m64n40k16_rs_tb(o[1], P1[0], P1[1], P1[2], P1[3], d, 1);
            };
            auto finish = [&](int b, int c) {
#pragma unroll
              for (int i = 0; i < 4; i++) {
                const float s0 = S[b][8 * c + 2 * i], s1 = S[b][8 * c + 2 * i + 1];
                P0[i] = i < SK ? pack2(e[2 * i], e[2 * i + 1]) : i < 3 ? pack2(ex2(s0), ex2(s1)) : exp2_pair(s0, s1, c_half, c_lsb);
                P1[i] = exp2_h2(H[b][4 * c + i], c_nsig);
              }
            };
            uint64_t kd = prm.kv[0].kd, vd = prm.kv[0].vd;
            mbar_wait(sb + B_TF, 0);
            wg_fence(); qk(0, 0, kd); qk(0, 1, kd + 2); wg_commit();
            wg_wait<0>(); fence_regs(S[0]); fence_regs(H[0]);
#pragma unroll 1
            for (int j = 1; j < 9; j++) {
              bool landed = false;
#pragma unroll
              for (int h = 0; h < 16; h++) {
                const int p = h >> 2, px = p + 1, c = h & 3;
                wg_fence();
                if (h == 13) kd = prm.kv[j].kd;
                if (h == 2) vd = prm.kv[j].vd;
                if (c == 1 || c == 2) qk(px & 1, c - 1, kd + (px & 3) * 256 + 2 * (c - 1));
                pv(vd + ((h - 2) & 15) * VSTEP);
                wg_commit();
                if (h == 11) landed = mbar_test(sb + B_TF + 8 * (j & 3), (j >> 2) & 1) || j == 8;
                finish(((h - 1) >> 2) & 1, (h - 1) & 3);
#pragma unroll
                for (int i = 0; i < 2 * SK; i++) e[i] = ex2(S[p & 1][8 * c + i]);
                fence_regs(e); fence_regs(P0); fence_regs(P1);
                sched_fence();
                if (h == 12 && !landed) mbar_wait(sb + B_TF + 8 * (j & 3), (j >> 2) & 1);
                if (h == 15) wg_wait<0>(); else wg_wait<1>();
                if (c == 3) { fence_regs(S[px & 1]); fence_regs(H[px & 1]); }
                if (h == 2 && elected && j > 1) mbar_arrive(sb + B_TE + 8 * ((j + 2) & 3));
              }
            }
            int badm = 0;
            wg_fence(); pv(vd + 14 * VSTEP); wg_commit();
            finish(1, 3); fence_regs(P0); fence_regs(P1);
            wg_fence(); pv(vd + 15 * VSTEP); wg_commit();
            if (pass == 0) bar_sync(NB_KN + wg, 160);
            const float kmax = *(volatile float*)(smem + ROWST + 4 * pass);
            const float bound = qn[0] <= 1.6e7f && kmax <= 1.6e7f ? qn[0] * kmax : INFINITY;
#pragma unroll
            for (int m = 0; m < 2; m++) {
              if (m == 0) { wg_wait<0>(); fence_regs(o[0]); fence_regs(o[1]); if (w == 0) e_arrive(sb + B_TE + 8 * 3); }
              float chk[4] = {0.f, 0.f, 0.f, 0.f};
#pragma unroll
              for (int i = 0; i < 20; i++) chk[i & 3] = fmaf(o[m][i], 0.f, chk[i & 3]);
              const bool bad = !(bound <= 112.f * 112.f) || !(o[m][16] >= 9.3e-10f) || !(o[m][18] >= 9.3e-10f) || ((chk[0] + chk[1]) + (chk[2] + chk[3]) != 0.f);
              badm |= __any_sync(~0u, bad) << m;
              const float of[16] = {o[m][0], o[m][1], o[m][2], o[m][3], o[m][4], o[m][5], o[m][6], o[m][7], o[m][8], o[m][9], o[m][10], o[m][11], o[m][12], o[m][13], o[m][14], o[m][15]};
              put_o(pass, m, of, rcp(o[m][16]), rcp(o[m][18]));
            }
            if (badm) {
#pragma unroll 1
              for (int m = 0; m < 2; m++) if ((badm >> m) & 1) {
                uint32_t qq[8]; float res[20];
#pragma unroll
                for (int i = 0; i < 8; i++)
                  qq[i] = unesc(m ? q[0][1][i] : q[0][0][i], esc_ptr(pass) + ((cta_id() >> 4) * 256 + row0 + m * 64 + (i & 1) * 8 + (lane_id() >> 2)) * 16 + (i >> 1) * 4 + (lane_id() & 3));
                __syncwarp();
                attn_slow(qq, 2 * (cta_id() & 15) + pass, esc_ptr(2 + pass), res, lane_id());
                const float of[16] = {res[0], res[1], res[2], res[3], res[4], res[5], res[6], res[7], res[8], res[9], res[10], res[11], res[12], res[13], res[14], res[15]};
                put_o(pass, m, of, rcp(res[16]), rcp(res[18]));
              }
            }
            bar_arrive(NB_SIG + 2 * pass + wg, 160);
            qn[0] = qn[1];
            if (pass == 0) {
#pragma unroll
              for (int i = 0; i < 4; i++) lds128(sb + QPARK + (wg * 128 + w * 32 + lane_id()) * 16 + i * 4096, &q[0][i >> 1][4 * (i & 1)]);
            }
          }
        }
      }
      {
        float acc[64];
#pragma unroll
        for (int i = 0; i < 64; i++) acc[i] = 0.f;
        fence_regs(acc);
        uint32_t s = 0, lap = 0;
#pragma unroll 1
        for (int kt = 0; kt < 16; kt++) {
          mbar_wait(sb + B_PF + 8 * s, ((s < 4 ? l : 0) + lap) & 1);
          const uint64_t da = mkdesc(sb + pslot_a(s, l) + wg * 8192, 16, 1024, 1), db = mkdesc(sb + pslot_b(s), 8192, 1024, 1);
          wg_fence();
#pragma unroll
          for (int k = 0; k < 4; k++) wgmma_m64n128k16_ss_tb(acc, da + k * 2, db + k * 128, 1);
          wg_commit();
          wg_wait<1>();
          if (kt > 0 && w == 0) e_arrive_both(sb + B_PE + 8 * (s ? s - 1 : 5));
          if (++s == 6) { s = 0; lap++; }
        }
        IDS();
        const int g = lane >> 2, qd = lane & 3;
        const int r0 = wg * 64 + w * 16;
        const uint32_t r = r0 + (lane & 7) + ((lane >> 3) & 1) * 8;
        uint32_t x[8][4];
        mbar_wait(sb + B_RF, l & 1);
#pragma unroll
        for (int jj = 0; jj < 8; jj++) ldsm4(sb + RES + (jj >> 2) * 16384 + r * 128 + ((((2 * jj + (lane >> 4)) & 7) ^ (r & 7)) << 4), x[jj]);
        wg_wait<0>();
        fence_regs(acc);
        if (w == 0) e_arrive_both(sb + B_PE + 8 * 3);
        bar_sync(NB_SC, 256);
        const CUtensorMap* mo = &prm.m[l == 3 ? M_OUT : M_XST];
#pragma unroll
        for (int jj = 0; jj < 8; jj++) {
#pragma unroll
          for (int i = 0; i < 4; i++) x[jj][i] = add_bf16x2(x[jj][i], pack2(acc[8 * jj + 2 * i], acc[8 * jj + 2 * i + 1]));
          stsm4(sb + (jj >> 2) * QSTG + po * 16384 + r * 128 + ((((2 * jj + (lane >> 4)) & 7) ^ (r & 7)) << 4), x[jj][0], x[jj][1], x[jj][2], x[jj][3]);
          if ((jj & 3) == 3) { fence_async_smem(); __syncwarp(); tma_st(mo, pn * 128 + (jj >> 2) * 64, pm * 128 + r0, sb + (jj >> 2) * QSTG + po * 16384 + r0 * 128); }
        }
        bulk_commit();
        if (l < 3) {
          bar_arrive(NB_X, 288);
          float s1[2] = {0.f, 0.f}, s2[2] = {0.f, 0.f};
#pragma unroll
          for (int i = 0; i < 32; i++) {
            const float a = bf_lo(x[i >> 2][i & 3]), c = bf_hi(x[i >> 2][i & 3]);
            s1[i & 1] += a + c; s2[i & 1] = fmaf(a, a, fmaf(c, c, s2[i & 1]));
          }
#pragma unroll
          for (int hh = 0; hh < 2; hh++) { s1[hh] += __shfl_xor_sync(~0u, s1[hh], 1); s2[hh] += __shfl_xor_sync(~0u, s2[hh], 1); }
#pragma unroll
          for (int hh = 0; hh < 2; hh++) {
            s1[hh] += __shfl_xor_sync(~0u, s1[hh], 2); s2[hh] += __shfl_xor_sync(~0u, s2[hh], 2);
            if (qd == 0) g_stats[pn * 2048 + pm * 128 + r0 + g + 8 * hh] = make_float2(s1[hh], s2[hh]);
          }
        }
        bulk_wait_n<0>();
        if (l < 3) bar_arrive(NB_X0, 288);
      }
    }
  }
  asm volatile("barrier.cluster.arrive.relaxed.aligned;\nbarrier.cluster.wait.aligned;" ::: "memory");
}

typedef CUresult (*EncodeFn)(CUtensorMap*, CUtensorMapDataType, cuuint32_t, void*, const cuuint64_t*, const cuuint64_t*, const cuuint32_t*,
                             const cuuint32_t*, CUtensorMapInterleave, CUtensorMapSwizzle, CUtensorMapL2promotion, CUtensorMapFloatOOBfill);

static void make_map(EncodeFn fn, CUtensorMap* m, const void* ptr, int rank, const uint64_t* dims, const uint64_t* strides, const uint32_t* box, CUtensorMapSwizzle sw) {
  cuuint64_t d[5], st[4];
  cuuint32_t bx[5], es[5];
  for (int i = 0; i < rank; i++) { d[i] = dims[i]; bx[i] = box[i]; es[i] = 1; if (i) st[i - 1] = strides[i - 1] * 2; }
  fn(m, CU_TENSOR_MAP_DATA_TYPE_BFLOAT16, rank, (void*)ptr, d, st, bx, es, CU_TENSOR_MAP_INTERLEAVE_NONE, sw,
     CU_TENSOR_MAP_L2_PROMOTION_L2_128B, CU_TENSOR_MAP_FLOAT_OOB_FILL_NONE);
}
static void map2(EncodeFn fn, CUtensorMap* m, const void* ptr, uint64_t inner, uint64_t outer, uint32_t bi, uint32_t bo, CUtensorMapSwizzle sw) {
  const uint64_t d[2] = {inner, outer}, st[1] = {inner};
  const uint32_t bx[2] = {bi, bo};
  make_map(fn, m, ptr, 2, d, st, bx, sw);
}

extern "C" void kernel_launch(void* const* d_in, const int* in_sizes, int n_in, void* d_out, int out_size) {
  (void)in_sizes; (void)n_in; (void)out_size;
  static EncodeFn enc = nullptr;
  static void *xs, *os, *kk, *vv;
  static int sbase = 1024;
  if (!enc) {
    void* p = nullptr;
    cudaDriverEntryPointQueryResult qr;
    cudaGetDriverEntryPoint("cuTensorMapEncodeTiled", &p, cudaEnableDefault, &qr);
    enc = (EncodeFn)p;
    cudaGetSymbolAddress(&xs, g_xs); cudaGetSymbolAddress(&os, g_os); cudaGetSymbolAddress(&kk, g_k); cudaGetSymbolAddress(&vv, g_v);
    int dev = 0;
    cudaGetDevice(&dev);
    cudaDeviceGetAttribute(&sbase, cudaDevAttrReservedSharedMemoryPerBlock, dev);
    cudaFuncSetAttribute(fused_kernel, cudaFuncAttributeMaxDynamicSharedMemorySize, SMEM_BYTES);
  }
  Params prm;
  const CUtensorMapSwizzle S128 = CU_TENSOR_MAP_SWIZZLE_128B, S64 = CU_TENSOR_MAP_SWIZZLE_64B;
  map2(enc, &prm.m[M_X0A], d_in[0], 1024, 2048, 64, 256, S128);
  map2(enc, &prm.m[M_XSA], xs, 1024, 2048, 64, 256, S128);
  for (int t = 0; t < 2; t++) {
    const uint64_t d3[3] = {1024, 1024, 3}, s3[2] = {3072, 1024};
    const uint32_t b3[3] = {64, 64, 3};
    make_map(enc, &prm.m[M_WQA + t], d_in[1 + 3 * t], 3, d3, s3, b3, S128);
    const uint64_t d5[5] = {64, 32, 2, 16, 16}, s5[4] = {1024, 32 * 1024, 64 * 1024, 64};
    const uint32_t b5[5] = {64, 32, 1, 2, 2};
    make_map(enc, &prm.m[M_WOA + t], d_in[2 + 3 * t], 5, d5, s5, b5, S128);
    const uint64_t dr[3] = {64, 2048, 16}, sr[2] = {1024, 64};
    const uint32_t br[3] = {64, 128, 2};
    make_map(enc, &prm.m[M_X0R + t], t ? xs : d_in[0], 3, dr, sr, br, S128);
  }
  map2(enc, &prm.m[M_OS], os, 1024, 2048, 64, 64, S128);
  map2(enc, &prm.m[M_K], kk, 32, 65536, 32, 256, S64);
  map2(enc, &prm.m[M_V], vv, 32, 65536, 32, 256, S64);
  map2(enc, &prm.m[M_XSO], xs, 1024, 2048, 64, 128, S128);
  map2(enc, &prm.m[M_X0H], d_in[0], 1024, 2048, 64, 128, S128);
  map2(enc, &prm.m[M_XST], xs, 1024, 2048, 64, 16, S128);
  map2(enc, &prm.m[M_OUT], d_out, 1024, 2048, 64, 16, S128);
  prm.x0 = (const bf16*)d_in[0];
  prm.wq[0] = (const bf16*)d_in[1]; prm.wq[1] = (const bf16*)d_in[4];
  prm.zero = 0;
  for (int i = 0; i < 128; i++) prm.map[i] = remap(i);
  {
    const uint64_t hi = 0x80000020ull << 32, k0 = sbase + T0, v0 = k0 + 16384, vstep = 64 - (64ull << 16);
    for (int j = 0; j < 9; j++) {
      prm.kv[j].kd = (hi | 1u << 16 | k0 >> 4) + 2048 * ((j < 8 ? j : 7) & 3);
      prm.kv[j].vd = (hi | (uint64_t)(ONES - T0 - 16384) >> 4 << 16 | v0 >> 4) + 32 * vstep * ((j ? j - 1 : 0) & 3);
    }
  }
  fused_kernel<<<128, 384, SMEM_BYTES>>>(prm);
}
```

```cpp
#include <cuda_runtime.h>
#include <cuda_bf16.h>
#include <cuda.h>
#include <stdint.h>

typedef __nv_bfloat16 bf16;

__device__ __forceinline__ void wgmma_m64n192k16_ss_tb(float (&d)[96], uint64_t da, uint64_t db, int scale_d) {
  asm volatile("{\n.reg .pred p;\nsetp.ne.b32 p, %98, 0;\n"
    "wgmma.mma_async.sync.aligned.m64n192k16.f32.bf16.bf16 "
    "{%0, %1, %2, %3, %4, %5, %6, %7, %8, %9, %10, %11, %12, %13, %14, %15, "
    "%16, %17, %18, %19, %20, %21, %22, %23, %24, %25, %26, %27, %28, %29, %30, %31, "
    "%32, %33, %34, %35, %36, %37, %38, %39, %40, %41, %42, %43, %44, %45, %46, %47, "
    "%48, %49, %50, %51, %52, %53, %54, %55, %56, %57, %58, %59, %60, %61, %62, %63, "
    "%64, %65, %66, %67, %68, %69, %70, %71, %72, %73, %74, %75, %76, %77, %78, %79, "
    "%80, %81, %82, %83, %84, %85, %86, %87, %88, %89, %90, %91, %92, %93, %94, %95}, "
    "%96, %97, p, 1, 1, 0, 1;\n}\n"
    : "+f"(d[0]), "+f"(d[1]), "+f"(d[2]), "+f"(d[3]), "+f"(d[4]), "+f"(d[5]), "+f"(d[6]), "+f"(d[7]),
      "+f"(d[8]), "+f"(d[9]), "+f"(d[10]), "+f"(d[11]), "+f"(d[12]), "+f"(d[13]), "+f"(d[14]), "+f"(d[15]),
      "+f"(d[16]), "+f"(d[17]), "+f"(d[18]), "+f"(d[19]), "+f"(d[20]), "+f"(d[21]), "+f"(d[22]), "+f"(d[23]),
      "+f"(d[24]), "+f"(d[25]), "+f"(d[26]), "+f"(d[27]), "+f"(d[28]), "+f"(d[29]), "+f"(d[30]), "+f"(d[31]),
      "+f"(d[32]), "+f"(d[33]), "+f"(d[34]), "+f"(d[35]), "+f"(d[36]), "+f"(d[37]), "+f"(d[38]), "+f"(d[39]),
      "+f"(d[40]), "+f"(d[41]), "+f"(d[42]), "+f"(d[43]), "+f"(d[44]), "+f"(d[45]), "+f"(d[46]), "+f"(d[47]),
      "+f"(d[48]), "+f"(d[49]), "+f"(d[50]), "+f"(d[51]), "+f"(d[52]), "+f"(d[53]), "+f"(d[54]), "+f"(d[55]),
      "+f"(d[56]), "+f"(d[57]), "+f"(d[58]), "+f"(d[59]), "+f"(d[60]), "+f"(d[61]), "+f"(d[62]), "+f"(d[63]),
      "+f"(d[64]), "+f"(d[65]), "+f"(d[66]), "+f"(d[67]), "+f"(d[68]), "+f"(d[69]), "+f"(d[70]), "+f"(d[71]),
      "+f"(d[72]), "+f"(d[73]), "+f"(d[74]), "+f"(d[75]), "+f"(d[76]), "+f"(d[77]), "+f"(d[78]), "+f"(d[79]),
      "+f"(d[80]), "+f"(d[81]), "+f"(d[82]), "+f"(d[83]), "+f"(d[84]), "+f"(d[85]), "+f"(d[86]), "+f"(d[87]),
      "+f"(d[88]), "+f"(d[89]), "+f"(d[90]), "+f"(d[91]), "+f"(d[92]), "+f"(d[93]), "+f"(d[94]), "+f"(d[95])
    : "l"(da), "l"(db), "r"(scale_d));
}

__device__ __forceinline__ void wgmma_m64n128k16_ss_tb(float (&d)[64], uint64_t da, uint64_t db, int scale_d) {
  asm volatile("{\n.reg .pred p;\nsetp.ne.b32 p, %66, 0;\n"
    "wgmma.mma_async.sync.aligned.m64n128k16.f32.bf16.bf16 "
    "{%0, %1, %2, %3, %4, %5, %6, %7, %8, %9, %10, %11, %12, %13, %14, %15, "
    "%16, %17, %18, %19, %20, %21, %22, %23, %24, %25, %26, %27, %28, %29, %30, %31, "
    "%32, %33, %34, %35, %36, %37, %38, %39, %40, %41, %42, %43, %44, %45, %46, %47, "
    "%48, %49, %50, %51, %52, %53, %54, %55, %56, %57, %58, %59, %60, %61, %62, %63}, "
    "%64, %65, p, 1, 1, 0, 1;\n}\n"
    : "+f"(d[0]), "+f"(d[1]), "+f"(d[2]), "+f"(d[3]), "+f"(d[4]), "+f"(d[5]), "+f"(d[6]), "+f"(d[7]),
      "+f"(d[8]), "+f"(d[9]), "+f"(d[10]), "+f"(d[11]), "+f"(d[12]), "+f"(d[13]), "+f"(d[14]), "+f"(d[15]),
      "+f"(d[16]), "+f"(d[17]), "+f"(d[18]), "+f"(d[19]), "+f"(d[20]), "+f"(d[21]), "+f"(d[22]), "+f"(d[23]),
      "+f"(d[24]), "+f"(d[25]), "+f"(d[26]), "+f"(d[27]), "+f"(d[28]), "+f"(d[29]), "+f"(d[30]), "+f"(d[31]),
      "+f"(d[32]), "+f"(d[33]), "+f"(d[34]), "+f"(d[35]), "+f"(d[36]), "+f"(d[37]), "+f"(d[38]), "+f"(d[39]),
      "+f"(d[40]), "+f"(d[41]), "+f"(d[42]), "+f"(d[43]), "+f"(d[44]), "+f"(d[45]), "+f"(d[46]), "+f"(d[47]),
      "+f"(d[48]), "+f"(d[49]), "+f"(d[50]), "+f"(d[51]), "+f"(d[52]), "+f"(d[53]), "+f"(d[54]), "+f"(d[55]),
      "+f"(d[56]), "+f"(d[57]), "+f"(d[58]), "+f"(d[59]), "+f"(d[60]), "+f"(d[61]), "+f"(d[62]), "+f"(d[63])
    : "l"(da), "l"(db), "r"(scale_d));
}

__device__ __forceinline__ void wgmma_m64n40k16_rs_tb(float (&d)[20], uint32_t a0, uint32_t a1, uint32_t a2, uint32_t a3, uint64_t db, int scale_d) {
  asm volatile("{\n.reg .pred p;\nsetp.ne.b32 p, %25, 0;\n"
    "wgmma.mma_async.sync.aligned.m64n40k16.f32.bf16.bf16 "
    "{%0, %1, %2, %3, %4, %5, %6, %7, %8, %9, %10, %11, %12, %13, %14, %15, "
    "%16, %17, %18, %19}, "
    "{%20, %21, %22, %23}, %24, p, 1, 1, 1;\n}\n"
    : "+f"(d[0]), "+f"(d[1]), "+f"(d[2]), "+f"(d[3]), "+f"(d[4]), "+f"(d[5]), "+f"(d[6]), "+f"(d[7]),
      "+f"(d[8]), "+f"(d[9]), "+f"(d[10]), "+f"(d[11]), "+f"(d[12]), "+f"(d[13]), "+f"(d[14]), "+f"(d[15]),
      "+f"(d[16]), "+f"(d[17]), "+f"(d[18]), "+f"(d[19])
    : "r"(a0), "r"(a1), "r"(a2), "r"(a3), "l"(db), "r"(scale_d));
}

__device__ __forceinline__ void wg_n64_rs_nb_f16_f32(float (&d)[32], uint32_t a0, uint32_t a1, uint32_t a2, uint32_t a3, uint64_t db, int scale_d) {
  asm volatile("{\n.reg .pred p;\nsetp.ne.b32 p, %37, 0;\n"
    "wgmma.mma_async.sync.aligned.m64n64k16.f32.f16.f16 "
    "{%0, %1, %2, %3, %4, %5, %6, %7, %8, %9, %10, %11, %12, %13, %14, %15, "
    "%16, %17, %18, %19, %20, %21, %22, %23, %24, %25, %26, %27, %28, %29, %30, %31}, "
    "{%32, %33, %34, %35}, %36, p, 1, 1, 0;\n}\n"
    : "+f"(d[0]), "+f"(d[1]), "+f"(d[2]), "+f"(d[3]), "+f"(d[4]), "+f"(d[5]), "+f"(d[6]), "+f"(d[7]),
      "+f"(d[8]), "+f"(d[9]), "+f"(d[10]), "+f"(d[11]), "+f"(d[12]), "+f"(d[13]), "+f"(d[14]), "+f"(d[15]),
      "+f"(d[16]), "+f"(d[17]), "+f"(d[18]), "+f"(d[19]), "+f"(d[20]), "+f"(d[21]), "+f"(d[22]), "+f"(d[23]),
      "+f"(d[24]), "+f"(d[25]), "+f"(d[26]), "+f"(d[27]), "+f"(d[28]), "+f"(d[29]), "+f"(d[30]), "+f"(d[31])
    : "r"(a0), "r"(a1), "r"(a2), "r"(a3), "l"(db), "r"(scale_d));
}

__device__ __forceinline__ void wg_n64_rs_nb_f16_f16(uint32_t (&d)[16], uint32_t a0, uint32_t a1, uint32_t a2, uint32_t a3, uint64_t db, int scale_d) {
  asm volatile("{\n.reg .pred p;\nsetp.ne.b32 p, %21, 0;\n"
    "wgmma.mma_async.sync.aligned.m64n64k16.f16.f16.f16 "
    "{%0, %1, %2, %3, %4, %5, %6, %7, %8, %9, %10, %11, %12, %13, %14, %15}, "
    "{%16, %17, %18, %19}, %20, p, 1, 1, 0;\n}\n"
    : "+r"(d[0]), "+r"(d[1]), "+r"(d[2]), "+r"(d[3]), "+r"(d[4]), "+r"(d[5]), "+r"(d[6]), "+r"(d[7]),
      "+r"(d[8]), "+r"(d[9]), "+r"(d[10]), "+r"(d[11]), "+r"(d[12]), "+r"(d[13]), "+r"(d[14]), "+r"(d[15])
    : "r"(a0), "r"(a1), "r"(a2), "r"(a3), "l"(db), "r"(scale_d));
}

__device__ __forceinline__ void wg_n64_rs_nb_f16_f32_z(float (&d)[32], uint32_t a0, uint32_t a1, uint32_t a2, uint32_t a3, uint64_t db, int scale_d) {
  asm volatile("{\n.reg .pred p;\nsetp.ne.b32 p, %37, 0;\n"
    "wgmma.mma_async.sync.aligned.m64n64k16.f32.f16.f16 "
    "{%0, %1, %2, %3, %4, %5, %6, %7, %8, %9, %10, %11, %12, %13, %14, %15, "
    "%16, %17, %18, %19, %20, %21, %22, %23, %24, %25, %26, %27, %28, %29, %30, %31}, "
    "{%32, %33, %34, %35}, %36, p, 1, 1, 0;\n}\n"
    : "=f"(d[0]), "=f"(d[1]), "=f"(d[2]), "=f"(d[3]), "=f"(d[4]), "=f"(d[5]), "=f"(d[6]), "=f"(d[7]),
      "=f"(d[8]), "=f"(d[9]), "=f"(d[10]), "=f"(d[11]), "=f"(d[12]), "=f"(d[13]), "=f"(d[14]), "=f"(d[15]),
      "=f"(d[16]), "=f"(d[17]), "=f"(d[18]), "=f"(d[19]), "=f"(d[20]), "=f"(d[21]), "=f"(d[22]), "=f"(d[23]),
      "=f"(d[24]), "=f"(d[25]), "=f"(d[26]), "=f"(d[27]), "=f"(d[28]), "=f"(d[29]), "=f"(d[30]), "=f"(d[31])
    : "r"(a0), "r"(a1), "r"(a2), "r"(a3), "l"(db), "r"(scale_d));
}

__device__ __forceinline__ void wg_n64_rs_nb_f16_f16_z(uint32_t (&d)[16], uint32_t a0, uint32_t a1, uint32_t a2, uint32_t a3, uint64_t db, int scale_d) {
  asm volatile("{\n.reg .pred p;\nsetp.ne.b32 p, %21, 0;\n"
    "wgmma.mma_async.sync.aligned.m64n64k16.f16.f16.f16 "
    "{%0, %1, %2, %3, %4, %5, %6, %7, %8, %9, %10, %11, %12, %13, %14, %15}, "
    "{%16, %17, %18, %19}, %20, p, 1, 1, 0;\n}\n"
    : "=r"(d[0]), "=r"(d[1]), "=r"(d[2]), "=r"(d[3]), "=r"(d[4]), "=r"(d[5]), "=r"(d[6]), "=r"(d[7]),
      "=r"(d[8]), "=r"(d[9]), "=r"(d[10]), "=r"(d[11]), "=r"(d[12]), "=r"(d[13]), "=r"(d[14]), "=r"(d[15])
    : "r"(a0), "r"(a1), "r"(a2), "r"(a3), "l"(db), "r"(scale_d));
}

#define DEVINL __device__ __forceinline__
DEVINL void wg_fence() { asm volatile("wgmma.fence.sync.aligned;" ::: "memory"); }
DEVINL void wg_commit() { asm volatile("wgmma.commit_group.sync.aligned;" ::: "memory"); }
template <int N> DEVINL void wg_wait() { asm volatile("wgmma.wait_group.sync.aligned %0;" ::"n"(N) : "memory"); }
DEVINL uint64_t mkdesc(uint32_t addr, uint32_t lbo, uint32_t sbo, int sw) {
  return (uint64_t)((addr & 0x3FFFF) >> 4) | ((uint64_t)(lbo >> 4) << 16) | ((uint64_t)(sbo >> 4) << 32) | ((uint64_t)sw << 62);
}
DEVINL void mbar_init(uint32_t bar, uint32_t cnt) { asm volatile("mbarrier.init.shared::cta.b64 [%0], %1;" ::"r"(bar), "r"(cnt) : "memory"); }
DEVINL void mbar_arrive(uint32_t bar) { asm volatile("mbarrier.arrive.shared::cta.b64 _, [%0];" ::"r"(bar) : "memory"); }
DEVINL bool mbar_try(uint32_t bar, uint32_t parity) {
  uint32_t ok;
  asm volatile("{\n.reg .pred p;\nmbarrier.try_wait.parity.shared::cta.b64 p, [%1], %2;\nselp.u32 %0, 1, 0, p;\n}" : "=r"(ok) : "r"(bar), "r"(parity) : "memory");
  return ok;
}
DEVINL bool mbar_test(uint32_t bar, uint32_t parity) {
  uint32_t ok;
  asm volatile("{\n.reg .pred p;\nmbarrier.test_wait.parity.shared::cta.b64 p, [%1], %2;\nselp.u32 %0, 1, 0, p;\n}" : "=r"(ok) : "r"(bar), "r"(parity) : "memory");
  return ok;
}
DEVINL void mbar_hint(uint32_t bar, uint32_t parity) {
#pragma unroll 1
  for (uint32_t n = 0; n < 16u; n++) if (mbar_try(bar, parity)) break;
}
DEVINL void mbar_wait(uint32_t bar, uint32_t parity) {
#pragma unroll 1
  for (uint32_t n = 0; n < 100000u; n++) if (mbar_try(bar, parity)) break;
}
#define EL(txt) "{\n.reg .pred pe;\nelect.sync _|pe, 0xffffffff;\n@pe " txt "\n}"
DEVINL void e_expect_tx(uint32_t bar, uint32_t bytes) { asm volatile(EL("mbarrier.arrive.expect_tx.shared::cta.b64 _, [%0], %1;") ::"r"(bar), "r"(bytes) : "memory"); }
DEVINL void e_arrive(uint32_t bar) { asm volatile(EL("mbarrier.arrive.shared::cta.b64 _, [%0];") ::"r"(bar) : "memory"); }
DEVINL void e_red(uint32_t* p) { asm volatile(EL("red.release.gpu.global.add.u32 [%0], 1;") ::"l"(p) : "memory"); }
DEVINL void e_red_relaxed(uint32_t* p) { asm volatile(EL("red.relaxed.gpu.global.add.u32 [%0], 1;") ::"l"(p) : "memory"); }
DEVINL void tma_ld(uint32_t dst, const CUtensorMap* m, int c0, int c1, uint32_t bar) {
  asm volatile(EL("cp.async.bulk.tensor.2d.shared::cluster.global.mbarrier::complete_tx::bytes [%0], [%1, {%3, %4}], [%2];")
               ::"r"(dst), "l"(m), "r"(bar), "r"(c0), "r"(c1) : "memory");
}
DEVINL void tma_ld3(uint32_t dst, const CUtensorMap* m, int c0, int c1, int c2, uint32_t bar) {
  asm volatile(EL("cp.async.bulk.tensor.3d.shared::cluster.global.mbarrier::complete_tx::bytes [%0], [%1, {%3, %4, %5}], [%2];")
               ::"r"(dst), "l"(m), "r"(bar), "r"(c0), "r"(c1), "r"(c2) : "memory");
}
DEVINL void tma_ld5(uint32_t dst, const CUtensorMap* m, int c2, int c3, int c4, uint32_t bar) {
  asm volatile(EL("cp.async.bulk.tensor.5d.shared::cluster.global.mbarrier::complete_tx::bytes [%0], [%1, {0, 0, %3, %4, %5}], [%2];")
               ::"r"(dst), "l"(m), "r"(bar), "r"(c2), "r"(c3), "r"(c4) : "memory");
}
DEVINL void tma_ld_mc(uint32_t dst, const CUtensorMap* m, int c0, int c1, uint32_t bar) {
  asm volatile(EL("cp.async.bulk.tensor.2d.shared::cluster.global.mbarrier::complete_tx::bytes.multicast::cluster [%0], [%1, {%3, %4}], [%2], %5;")
               ::"r"(dst), "l"(m), "r"(bar), "r"(c0), "r"(c1), "h"((uint16_t)3) : "memory");
}
DEVINL void e_arrive_both(uint32_t bar) {
  asm volatile("{\n.reg .pred pe;\n.reg .b32 r0, r1;\nelect.sync _|pe, 0xffffffff;\nmapa.shared::cluster.u32 r0, %0, 0;\nmapa.shared::cluster.u32 r1, %0, 1;\n"
               "@pe mbarrier.arrive.shared::cluster.b64 _, [r0];\n@pe mbarrier.arrive.shared::cluster.b64 _, [r1];\n}" ::"r"(bar) : "memory");
}
DEVINL void tma_st(const CUtensorMap* m, int c0, int c1, uint32_t src) {
  asm volatile(EL("cp.async.bulk.tensor.2d.global.shared::cta.bulk_group [%0, {%2, %3}], [%1];") ::"l"(m), "r"(src), "r"(c0), "r"(c1) : "memory");
}
DEVINL void bulk_commit() { asm volatile("cp.async.bulk.commit_group;" ::: "memory"); }
template <int N> DEVINL void bulk_wait_n() { asm volatile("cp.async.bulk.wait_group %0;\nbar.warp.sync 0xffffffff;" ::"n"(N) : "memory"); }
DEVINL void l2_prefetch(const void* g, uint32_t bytes) { asm volatile(EL("cp.async.bulk.prefetch.L2.global [%0], %1;") ::"l"(g), "r"(bytes) : "memory"); }
DEVINL void fence_async_smem() { asm volatile("fence.proxy.async.shared::cta;" ::: "memory"); }
DEVINL void fence_async_gl() { asm volatile("fence.proxy.async.global;" ::: "memory"); }
DEVINL void cluster_wait() { asm volatile("barrier.cluster.wait.aligned;" ::: "memory"); }
DEVINL void bar_sync(int id, int n) { asm volatile("bar.sync %0, %1;" ::"r"(id), "r"(n) : "memory"); }
DEVINL void bar_arrive(int id, int n) { asm volatile("bar.arrive %0, %1;" ::"r"(id), "r"(n) : "memory"); }
DEVINL uint32_t ld_acquire(const uint32_t* p) { uint32_t v; asm volatile("ld.acquire.gpu.global.u32 %0, [%1];" : "=r"(v) : "l"(p) : "memory"); return v; }
DEVINL void watch(const uint32_t* p, uint32_t target, uint32_t all, uint32_t tag, uint32_t slot) {
  uint32_t seen = 0;
#pragma unroll 1
  for (uint32_t n = 0; n < 200000u && seen != all; n++) {
    const uint32_t m = __ballot_sync(~0u, (int)(ld_acquire(p) - target) >= 0) & all;
    if (m != seen) { seen = m; asm volatile("st.release.cta.shared.u32 [%0], %1;" ::"r"(slot), "r"(tag << 16 | m) : "memory"); }
  }
}
template <bool RELAXED = false> DEVINL void await_bit(uint32_t slot, uint32_t tag, int j, uint32_t& rdy) {
  if ((rdy >> j) & 1) return;
#pragma unroll 1
  for (uint32_t n = 0; n < 8000000u; n++) {
    uint32_t v;
    asm volatile("ld.acquire.cta.shared.u32 %0, [%1];" : "=r"(v) : "r"(slot) : "memory");
    if ((v >> 16) == tag && ((v >> j) & 1)) { rdy = v; break; }
    if (RELAXED) __nanosleep(200);
  }
  asm volatile("fence.proxy.async.global;" ::: "memory");
}
DEVINL void poll_ge(const uint32_t* p, uint32_t target) {
#pragma unroll 1
  for (uint32_t n = 0; n < 200000u; n++) if (__all_sync(~0u, (int)(ld_acquire(p) - target) >= 0)) break;
}
DEVINL int lane_id() { int v; asm volatile("mov.u32 %0, %%laneid;" : "=r"(v)); return v; }
__host__ DEVINL int remap(int v) {
  const int c = v >> 1, u = c - 36, r = (u * 37) >> 8;
  const int L = c < 4 ? 32 + 8 * c : c < 36 ? c - 4 : 33 + u + r;
  return 2 * L + (v & 1);
}
DEVINL int block_id() { int v; asm volatile("mov.u32 %0, %%ctaid.x;" : "=r"(v)); return v; }
#define cta_id() prm.map[block_id()]
#define IDS() const int lane = lane_id(), b = cta_id(), bm = b >> 4, bn = b & 15, rank = b & 1, pm = 2 * bm + (bn >> 3), pn = bn & 7, po = pm & 1; \
  (void)lane; (void)bm; (void)bn; (void)rank; (void)pm; (void)pn; (void)po
DEVINL void st_tagged(unsigned long long* p, uint32_t v, uint32_t tag) {
  asm volatile("{\n.reg .b64 t;\nmov.b64 t, {%1, %2};\nst.relaxed.gpu.global.b64 [%0], t;\n}" ::"l"(p), "r"(v), "r"(tag) : "memory");
}
DEVINL float ex2(float x) { float y; asm("ex2.approx.ftz.f32 %0, %1;" : "=f"(y) : "f"(x)); return y; }
DEVINL float rcp(float x) { float y; asm("rcp.approx.ftz.f32 %0, %1;" : "=f"(y) : "f"(x)); return y; }
DEVINL uint32_t pack2(float lo, float hi) { uint32_t r; asm("cvt.rn.bf16x2.f32 %0, %1, %2;" : "=r"(r) : "f"(hi), "f"(lo)); return r; }
DEVINL uint32_t pack2h(float lo, float hi) { uint32_t r; asm("cvt.rn.f16x2.f32 %0, %1, %2;" : "=r"(r) : "f"(hi), "f"(lo)); return r; }
DEVINL uint32_t hadd2(uint32_t a, uint32_t b) { uint32_t r; asm("add.rn.f16x2 %0, %1, %2;" : "=r"(r) : "r"(a), "r"(b)); return r; }
DEVINL uint32_t hfma2(uint32_t a, uint32_t b, uint32_t c) { uint32_t r; asm("fma.rn.f16x2 %0, %1, %2, %3;" : "=r"(r) : "r"(a), "r"(b), "r"(c)); return r; }
DEVINL float bf_lo(uint32_t w) { return __uint_as_float(w << 16); }
DEVINL float bf_hi(uint32_t w) { return __uint_as_float(w & 0xFFFF0000u); }
DEVINL float bf_round(float x) { return bf_lo(pack2(x, 0.f)); }
DEVINL uint32_t add_bf16x2(uint32_t a, uint32_t b) { uint32_t r; asm("add.rn.bf16x2 %0, %1, %2;" : "=r"(r) : "r"(a), "r"(b)); return r; }
DEVINL void stsm4(uint32_t addr, uint32_t a, uint32_t b, uint32_t c, uint32_t d) {
  asm volatile("stmatrix.sync.aligned.m8n8.x4.shared.b16 [%0], {%1, %2, %3, %4};" ::"r"(addr), "r"(a), "r"(b), "r"(c), "r"(d) : "memory");
}
DEVINL void ldsm4(uint32_t addr, uint32_t (&r)[4]) {
  asm volatile("ldmatrix.sync.aligned.m8n8.x4.shared.b16 {%0, %1, %2, %3}, [%4];" : "=r"(r[0]), "=r"(r[1]), "=r"(r[2]), "=r"(r[3]) : "r"(addr) : "memory");
}
DEVINL void ldsm4t(uint32_t addr, uint32_t (&r)[4]) {
  asm volatile("ldmatrix.sync.aligned.m8n8.x4.trans.shared.b16 {%0, %1, %2, %3}, [%4];" : "=r"(r[0]), "=r"(r[1]), "=r"(r[2]), "=r"(r[3]) : "r"(addr) : "memory");
}
DEVINL void sts128(uint32_t addr, uint32_t a, uint32_t b, uint32_t c, uint32_t d) {
  asm volatile("st.shared.v4.b32 [%0], {%1, %2, %3, %4};" ::"r"(addr), "r"(a), "r"(b), "r"(c), "r"(d) : "memory");
}
DEVINL float2 lds64f(uint32_t addr) { float2 v; asm volatile("ld.shared.v2.f32 {%0, %1}, [%2];" : "=f"(v.x), "=f"(v.y) : "r"(addr) : "memory"); return v; }
DEVINL void mma16816(float (&d)[4], uint32_t a0, uint32_t a1, uint32_t a2, uint32_t a3, uint32_t b0, uint32_t b1) {
  asm("mma.sync.aligned.m16n8k16.row.col.f32.bf16.bf16.f32 {%0, %1, %2, %3}, {%4, %5, %6, %7}, {%8, %9}, {%0, %1, %2, %3};"
               : "+f"(d[0]), "+f"(d[1]), "+f"(d[2]), "+f"(d[3]) : "r"(a0), "r"(a1), "r"(a2), "r"(a3), "r"(b0), "r"(b1));
}
template <int N> DEVINL void fence_regs(float (&d)[N]) {
#pragma unroll
  for (int i = 0; i < N; i++) asm volatile("" : "+f"(d[i])::"memory");
}
template <int N> DEVINL void fence_regs(uint32_t (&d)[N]) {
#pragma unroll
  for (int i = 0; i < N; i++) asm volatile("" : "+r"(d[i])::"memory");
}
DEVINL void lds128(uint32_t addr, uint32_t* r) {
  asm volatile("ld.shared.v4.b32 {%0, %1, %2, %3}, [%4];" : "=r"(r[0]), "=r"(r[1]), "=r"(r[2]), "=r"(r[3]) : "r"(addr) : "memory");
}
DEVINL void sched_fence() { asm volatile("griddepcontrol.launch_dependents;" ::: "memory"); }

__device__ __align__(1024) bf16 g_xs[2048 * 1024];
__device__ __align__(1024) bf16 g_os[2048 * 1024];
__device__ __align__(1024) bf16 g_k[32 * 2048 * 32];
__device__ __align__(1024) bf16 g_v[32 * 2048 * 32];
__device__ __align__(16) uint32_t g_esc[4 * 65536 * 16];
__device__ __align__(128) float2 g_stats[8 * 2048];
__device__ __align__(16) float g_csp[2 * 16 * 8 * 192];
__device__ __align__(128) float g_kn[2 * 128 * 16];
__device__ unsigned long long g_halo[2 * 128 * 32 * 32];
__device__ __align__(128) uint32_t g_cnt[256 * 32];
__device__ uint32_t g_epoch;

DEVINL uint32_t* cnt_x(int l, int bm) { return g_cnt + (l * 8 + bm) * 32; }
DEVINL uint32_t* cnt_o(int l, int pm, int h) { return g_cnt + (32 + (l * 16 + pm) * 2 + h) * 32; }
DEVINL uint32_t* cnt_kv(int lb, int bn) { return g_cnt + (160 + lb * 16 + bn) * 32; }
DEVINL uint32_t* cnt_ad(int bn) { return g_cnt + (192 + bn) * 32; }
DEVINL uint32_t* cnt_cs(int t, int bn) { return g_cnt + (208 + t * 16 + bn) * 32; }

DEVINL int qord(int i, int l, int pn) { return l == 0 ? i : i < 4 ? ((2 * pn) ^ (i & 2)) + (i & 1) : i - 4 < 2 * (pn & 6) ? i - 4 : i; }
struct Params {
  CUtensorMap m[15];
  const bf16* x0;
  const bf16* wq[2];
  uint32_t zero;
  int map[128];
  struct { uint64_t kd, vd; } kv[17];
};
enum { M_X0A = 0, M_XSA, M_WQA, M_WQB, M_WOA, M_WOB, M_OS, M_K, M_V, M_X0R, M_XSR, M_XSO, M_OUT, M_XST, M_X0H, M_COUNT };

constexpr uint32_t QSTG = 57344;
constexpr uint32_t T0 = 65536, TSTG = 32768;
constexpr uint32_t ONES = 230400;
constexpr uint32_t PSTG = 32768, RES = 196608;
constexpr uint32_t KSC = 98304, VSC = 133120;
constexpr uint32_t ROWST = 229376, COLS = 231424, BARS = 232192, SMEM_BYTES = 232448;
constexpr uint32_t B_QF = BARS, B_QE = BARS + 32, B_TF = BARS + 64, B_TE = BARS + 96, B_PF = BARS + 128, B_PE = BARS + 176,
                   B_RF = BARS + 224, W_X = BARS + 232, W_O = BARS + 236, B_QL = BARS + 240, B_PA = BARS + 248;
enum { NB_ST = 1, NB_KV = 2  , NB_DONE = 3, NB_SC = 4, NB_SIG = 5  , NB_KN = 9  , NB_X = 11, NB_HALO = 12  , NB_X0 = 15 };

DEVINL uint32_t pslot_b(uint32_t s) { return ((0x320415u >> (4 * s)) & 7) * 16384u; }
DEVINL uint32_t pslot_a(uint32_t s, int l) { return 98304u + ((((l & 1) ? 0x541230u : 0x041235u) >> (4 * s)) & 7) * 16384u; }

constexpr float QSCALE = 0.17677669529663687f * 1.4426950408889634f;
#define JLAG 4
constexpr uint32_t QPARK = 32768;

DEVINL uint32_t exp2_pair(float s0, float s1, uint32_t half, uint32_t lsb) {
  constexpr float M = 383.f - 0.591914f + 0.00390625f;
  const uint32_t B = __byte_perm(__float_as_uint(s0 + M), __float_as_uint(s1 + M), 0x6521);
  uint32_t w, E, r;
  asm("lop3.b32 %0, %1, 0x807F807F, %2, 0xEA;" : "=r"(w) : "r"(B), "r"(half));
  asm("lop3.b32 %0, %1, 0x7F807F80, %2, 0xEA;" : "=r"(E) : "r"(B), "r"(lsb));
  asm("fma.rn.bf16x2 %0, %1, %2, %3;" : "=r"(r) : "r"(B), "r"(w), "r"(E));
  return r;
}
DEVINL uint32_t exp2_h2(uint32_t s, uint32_t nsig) {
  uint32_t r = hadd2(s, 0x65F565F5u), d;
  asm("{.reg .b64 t; cvt.u64.u32 t, %0; cvt.u32.u64 %0, t;}" : "+r"(r));
  const uint32_t w = hfma2(s, 0x38A038A0u, hfma2(r, nsig, 0x62E562E5u));
  const uint32_t m = hfma2(w, w, 0x48244857u);
  asm("{.reg .b32 t; shl.b32 t, %1, 7; add.u32 %0, t, %2;}" : "=r"(d) : "r"(r), "r"(m));
  return d;
}
DEVINL uint32_t unesc(uint32_t u, const uint32_t* esc) {
  if ((u & 0x7C00u) == 0x7C00u || (u & 0x7C000000u) == 0x7C000000u) return __ldcg(esc);
  float lo, hi;
  asm("{.reg .f16 a, b; mov.b32 {a, b}, %2; cvt.f32.f16 %0, a; cvt.f32.f16 %1, b;}" : "=f"(lo), "=f"(hi) : "r"(u));
  return pack2(lo, hi);
}

DEVINL void attn_slow(const uint32_t (&q)[8], int head, const uint32_t* kesc, float (&res)[20], int lane) {
  const int g = lane >> 2, qd = lane & 3;
  const bf16* kb = g_k + (size_t)head * 2048 * 32;
  const bf16* vb = g_v + (size_t)head * 2048 * 32;
  float o[4][4], m0 = -INFINITY, m1 = -INFINITY, l0 = 0.f, l1 = 0.f;
#pragma unroll
  for (int j = 0; j < 4; j++) { o[j][0] = o[j][1] = o[j][2] = o[j][3] = 0.f; }
#pragma unroll 1
  for (int k0 = 0; k0 < 2048; k0 += 16) {
    float s[2][4];
#pragma unroll
    for (int nt = 0; nt < 2; nt++) {
      s[nt][0] = s[nt][1] = s[nt][2] = s[nt][3] = 0.f;
      const uint32_t* kp = (const uint32_t*)(kb + (size_t)(k0 + nt * 8 + g) * 32) + qd;
      const uint32_t* ke = kesc + (k0 + nt * 8 + g) * 16 + qd;
      const uint32_t k0r = unesc(__ldcg(kp), ke), k1r = unesc(__ldcg(kp + 4), ke + 4), k2r = unesc(__ldcg(kp + 8), ke + 8), k3r = unesc(__ldcg(kp + 12), ke + 12);
      __syncwarp();
      mma16816(s[nt], q[0], q[1], q[2], q[3], k0r, k1r);
      mma16816(s[nt], q[4], q[5], q[6], q[7], k2r, k3r);
    }
    float a0 = fmaxf(fmaxf(s[0][0], s[0][1]), fmaxf(s[1][0], s[1][1]));
    float a1 = fmaxf(fmaxf(s[0][2], s[0][3]), fmaxf(s[1][2], s[1][3]));
    a0 = fmaxf(a0, __shfl_xor_sync(~0u, a0, 1)); a0 = fmaxf(a0, __shfl_xor_sync(~0u, a0, 2));
    a1 = fmaxf(a1, __shfl_xor_sync(~0u, a1, 1)); a1 = fmaxf(a1, __shfl_xor_sync(~0u, a1, 2));
    const float n0 = fmaxf(m0, a0), n1 = fmaxf(m1, a1);
    const float c0 = (m0 == n0) ? 1.f : ex2(m0 - n0), c1 = (m1 == n1) ? 1.f : ex2(m1 - n1);
    m0 = n0; m1 = n1;
    const uint32_t p0 = pack2(ex2(s[0][0] - n0), ex2(s[0][1] - n0)), p1 = pack2(ex2(s[0][2] - n1), ex2(s[0][3] - n1));
    const uint32_t p2 = pack2(ex2(s[1][0] - n0), ex2(s[1][1] - n0)), p3 = pack2(ex2(s[1][2] - n1), ex2(s[1][3] - n1));
    l0 = l0 * c0 + bf_lo(p0) + bf_hi(p0) + bf_lo(p2) + bf_hi(p2);
    l1 = l1 * c1 + bf_lo(p1) + bf_hi(p1) + bf_lo(p3) + bf_hi(p3);
#pragma unroll
    for (int j = 0; j < 4; j++) {
      o[j][0] *= c0; o[j][1] *= c0; o[j][2] *= c1; o[j][3] *= c1;
      const unsigned short* vp = (const unsigned short*)(vb + (size_t)(k0 + 2 * qd) * 32 + j * 8 + g);
      const uint32_t b0 = (uint32_t)__ldcg(vp) | ((uint32_t)__ldcg(vp + 32) << 16);
      const uint32_t b1 = (uint32_t)__ldcg(vp + 256) | ((uint32_t)__ldcg(vp + 288) << 16);
      mma16816(o[j], p0, p1, p2, p3, b0, b1);
    }
  }
  l0 += __shfl_xor_sync(~0u, l0, 1); l0 += __shfl_xor_sync(~0u, l0, 2);
  l1 += __shfl_xor_sync(~0u, l1, 1); l1 += __shfl_xor_sync(~0u, l1, 2);
#pragma unroll
  for (int j = 0; j < 4; j++) { res[4 * j] = o[j][0]; res[4 * j + 1] = o[j][1]; res[4 * j + 2] = o[j][2]; res[4 * j + 3] = o[j][3]; }
  res[16] = l0; res[18] = l1;
}

__global__ void __cluster_dims__(2, 1, 1) __launch_bounds__(384, 1) fused_kernel(const __grid_constant__ Params prm) {
  extern __shared__ __align__(1024) char smem[];
  const uint32_t sb = (uint32_t)__cvta_generic_to_shared(smem);
  const int tid = threadIdx.x, lane = tid & 31;
  const int wg = __shfl_sync(0xffffffffu, tid >> 7, 0);
  const int w = __shfl_sync(0xffffffffu, (tid >> 5) & 3, 0);
  const int bm = remap(blockIdx.x) >> 4, bn = remap(blockIdx.x) & 15;

  auto first_tile = [&](int kt) {
    e_expect_tx(sb + B_QF + 8 * kt, QSTG);
    tma_ld(sb + kt * QSTG, &prm.m[M_X0A], kt * 64, bm * 256, sb + B_QF + 8 * kt);
    tma_ld3(sb + kt * QSTG + 32768, &prm.m[M_WQA], bn * 64, kt * 64, 0, sb + B_QF + 8 * kt);
  };
  if (wg < 2) {
  } else if (w == 0) {
    if (lane < 4) { mbar_init(sb + B_QF + 8 * lane, 1); asm volatile("fence.mbarrier_init.release.cluster;" ::: "memory"); }
    __syncwarp();
    first_tile(0);
  } else if (w == 1) {
    if (lane == 25) *(uint2*)(smem + W_X) = make_uint2(0u, 0u);
    else if (lane < 28) {
      mbar_init(sb + B_QE + 8 * lane, lane < 4 ? 4 : lane < 8 ? 1 : lane < 12 ? 2 : lane < 18 ? 1 : lane < 24 ? 4 : lane < 27 ? 1 : 2);
      asm volatile("fence.mbarrier_init.release.cluster;" ::: "memory");
    }
  } else if (w == 2 && lane < M_COUNT) {
    asm volatile("prefetch.tensormap [%0];" ::"l"(&prm.m[lane]) : "memory");
  }
  __syncthreads();
  asm volatile("barrier.cluster.arrive.relaxed.aligned;" ::: "memory");

  if (wg == 2) {
    asm volatile("setmaxnreg.dec.sync.aligned.u32 56;");
    const uint32_t ep1 = *(volatile uint32_t*)&g_epoch + 1;
    if (w == 0) {
      first_tile(1);
      mbar_wait(sb + B_QF, 0);
      first_tile(2); first_tile(3);
#pragma unroll 1
      for (int kt = 4; kt < 16; kt++) l2_prefetch(prm.wq[0] + kt * 196608 + blockIdx.x * 1536, 3072);
      cluster_wait();
#pragma unroll 1
      for (int l = 0; l < 4; l++) {
        IDS();
        const CUtensorMap* mw = &prm.m[M_WQA + (l & 1)];
        const CUtensorMap* mx = &prm.m[l == 0 ? M_X0A : M_XSA];
        const CUtensorMap* mh = &prm.m[l == 0 ? M_X0H : M_XSO];
        const CUtensorMap* mo = &prm.m[M_WOA + (l & 1)];
        auto q_b = [&](int i) {
          const int s = i & 3;
          mbar_wait(sb + B_QE + 8 * s, ((i >> 2) & 1) ^ 1);
          e_expect_tx(sb + B_QF + 8 * s, QSTG);
          tma_ld3(sb + s * QSTG + 32768, mw, bn * 64, qord(i, l, pn) * 64, 0, sb + B_QF + 8 * s);
        };
        uint32_t rdy = l ? 0u : ~0u;
        auto q_a = [&](int i) {
          const int kt = qord(i, l, pn);
          await_bit(sb + W_X, l, kt >> 1, rdy);
          if (i < 4) tma_ld(sb + i * QSTG, mx, kt * 64, bm * 256, sb + B_QF + 8 * i);
          else tma_ld_mc(sb + (i & 3) * QSTG + rank * 16384, mh, kt * 64, bm * 256 + rank * 128, sb + B_QF + 8 * (i & 3));
        };
        if (l > 0) {
          await_bit(sb + W_X, l, pn, rdy);
#pragma unroll 1
          for (int i = 0; i < 2; i++) {
            e_expect_tx(sb + B_QF + 8 * i, 16384);
            tma_ld(sb + i * QSTG + (po ^ 1) * 16384, &prm.m[M_XSO], (2 * pn + i) * 64, (pm ^ 1) * 128, sb + B_QF + 8 * i);
          }
          mbar_wait(sb + B_QF, 0);
          q_a(2);
          mbar_wait(sb + B_QF + 8, 0);
        }
#pragma unroll 1
        for (int i = l ? 3 : 4; i < 16; i++) {
          q_b(i); q_a(i);
        }
        if (l & 1) {
          if (l == 3) poll_ge(cnt_ad(bn), ep1 * 16);
          bar_sync(NB_KV, 288);
          sts128(sb + ONES + lane * 32, 0x3f803f80u, 0x3f803f80u, 0x3f803f80u, 0x3f803f80u);
          sts128(sb + ONES + lane * 32 + 16, 0x3f803f80u, 0x3f803f80u, 0x3f803f80u, 0x3f803f80u);
          fence_async_smem();
          __syncwarp();
          e_arrive(sb + B_TF);
          const int krow = 2 * bn * 2048 + bm * 256;
          uint32_t* kvc = cnt_kv(l >> 1, bn);
          tma_st(&prm.m[M_K], 0, krow, sb + T0);
          tma_st(&prm.m[M_V], 0, krow, sb + T0 + 16384);
          bulk_commit(); bulk_wait_n<0>();
          e_red(kvc + bm);
          uint32_t seen = 0;
#pragma unroll 1
          for (int it = 1; it < 16; it++) {
            const int s = it & 3, blk = it;
            if (it == 4) {
              bar_sync(NB_KV + 12, 288);
              mbar_wait(sb + B_TF + 24, 0);
              tma_st(&prm.m[M_K], 0, krow + 2048, sb);
              tma_st(&prm.m[M_V], 0, krow + 2048, sb + 16384);
              bulk_commit();
            }
            if (it == 5) { bulk_wait_n<0>(); e_red(kvc + bm); }
            if (it == 12) { e_expect_tx(sb + B_RF, 32768); tma_ld3(sb + RES, &prm.m[M_XSR], 0, pm * 128, 2 * pn, sb + B_RF); }
            if (it == 2 || it == 3) mbar_wait(sb + B_TF + 8 * (it - 1), 0);
            mbar_wait(sb + B_TE + 8 * s, ((it >> 2) & 1) ^ 1);
            if (it < 8) {
#pragma unroll 1
              for (uint32_t n = 0; n < 200000u && !((seen >> it) & 1); n++)
                seen = __ballot_sync(~0u, (int)(ld_acquire(kvc + ((bm + lane) & 7)) - (ep1 * 2 - 1)) >= 0);
              fence_async_gl();
            } else if (it == 8) { poll_ge(kvc + (lane & 7), ep1 * 2); fence_async_gl(); }
            const int row = (2 * bn + (it >> 3)) * 2048 + ((bm + blk) & 7) * 256;
            e_expect_tx(sb + B_TF + 8 * s, 32768);
            tma_ld(sb + T0 + s * TSTG, &prm.m[M_K], 0, row, sb + B_TF + 8 * s);
            tma_ld(sb + T0 + s * TSTG + 16384, &prm.m[M_V], 0, row, sb + B_TF + 8 * s);
          }
        }
        auto p_b = [&](int i, uint32_t s, uint32_t par) {
          mbar_wait(sb + B_PE + 8 * s, par ^ 1);
          e_expect_tx(sb + B_PF + 8 * s, PSTG);
          tma_ld5(sb + pslot_b(s), mo, i >> 3, 2 * (i & 7), 2 * pn, sb + B_PF + 8 * s);
        };
        auto p_a = [&](int i, uint32_t s) {
          await_bit(sb + W_O, l + 1, i, rdy);
          tma_ld_mc(sb + pslot_a(s, l) + rank * 8192, &prm.m[M_OS], i * 64, pm * 128 + rank * 64, sb + B_PF + 8 * s);
        };
        auto p_a2 = [&](int i) {
          await_bit(sb + W_O, l + 1, i, rdy);
          tma_ld(sb + pslot_a(i, l), &prm.m[M_OS], i * 64, pm * 128, sb + B_PF + 8 * i);
          tma_ld(sb + pslot_a(i, l) + 8192, &prm.m[M_OS], i * 64, pm * 128 + 64, sb + B_PF + 8 * i);
        };
        rdy = 0;
        if (l & 1) {
#pragma unroll 1
          for (int u = 0; u < 6; u++) { const int i = (0x205413 >> (4 * u)) & 7; if (u == 4) mbar_wait(sb + B_TE, 1); p_b(i, i, i < 4 ? 1 : 0); }
#pragma unroll 1
          for (int u = 0; u < 6; u++) {
            const int i = (0x542130 >> (4 * u)) & 7;
            if (!(u & 1)) mbar_wait(sb + B_TE + 8 + 4 * u, 1);
            p_a2(i);
          }
        } else {
#pragma unroll 1
          for (int u = 0; u < 6; u++) { const int i = (0x025413 >> (4 * u)) & 7; if (u == 0 || u == 3) mbar_wait(sb + B_QE + 8 * (u / 3), 1); p_b(i, i, 0); }
          mbar_wait(sb + B_QE + 24, 1);
          e_expect_tx(sb + B_RF, 32768);
          tma_ld3(sb + RES, &prm.m[l == 0 ? M_X0R : M_XSR], 0, pm * 128, 2 * pn, sb + B_RF);
          p_a2(0);
          bar_sync(NB_DONE, 96);
          e_arrive_both(sb + B_PA);
          p_a2(1); p_a2(2);
          mbar_wait(sb + B_PA, (l >> 1) & 1);
#pragma unroll 1
          for (int i = 3; i < 6; i++) { if (i == 4) mbar_wait(sb + B_PF + 8, 0); p_a(i, i); }
        }
        uint32_t s = 0, lap = 1;
#pragma unroll 1
        for (int i = 6; i < 16; i++) {
          p_b(i, s, ((s < 4 ? l : 0) + lap) & 1);
          p_a(i, s);
          if (++s == 6) { s = 0; lap++; }
        }
        const CUtensorMap* mn = &prm.m[M_WQA + ((l + 1) & 1)];
        if (l < 3) {
          mbar_wait(sb + B_PE + 8 * 4, 1); mbar_wait(sb + B_PE + 8 * 5, 1);
          tma_ld3(sb + 32768, mn, bn * 64, 2 * pn * 64, 0, sb + B_QL);
          mbar_wait(sb + B_PE + 8 * 0, l & 1);
          tma_ld3(sb + QSTG + 32768, mn, bn * 64, (2 * pn + 1) * 64, 0, sb + B_QL);
          mbar_wait(sb + B_PE + 8 * 1, l & 1);
          e_expect_tx(sb + B_QF + 16, QSTG);
          tma_ld3(sb + 2 * QSTG + 32768, mn, bn * 64, ((2 * pn) ^ 2) * 64, 0, sb + B_QF + 16);
        }
        if (l < 3) { bar_sync(NB_X, 288); e_expect_tx(sb + B_QL, 49152); }
      }
      if (blockIdx.x == 0 && lane_id() == 0) *(volatile uint32_t*)&g_epoch = ep1;
    } else {
      const int hw = w - 1;
      cluster_wait();
      mbar_wait(sb + B_QF, 0);
#pragma unroll 1
      for (int l = 0; l < 4; l++) {
        IDS();
        if (hw == 2 && l > 0) watch(cnt_x(l, bm) + (lane & 7), ep1 * 2, 0xFFu, l, sb + W_X);
        if (l == 0) {
#pragma unroll 1
          for (int r = 2 * hw; r < 16; r += 6) {
            const uint4* p = (const uint4*)(prm.x0 + (size_t)(b * 16 + r) * 1024) + lane;
            float s1[2] = {0.f, 0.f}, s2[2] = {0.f, 0.f};
#pragma unroll
            for (int i = 0; i < 8; i++) {
              const uint4 v = __ldg(p + 32 * i);
              const uint32_t u[4] = {v.x, v.y, v.z, v.w};
#pragma unroll
              for (int k = 0; k < 4; k++) { const float a = bf_lo(u[k]), c = bf_hi(u[k]); s1[i >> 2] += a + c; s2[i >> 2] = fmaf(a, a, fmaf(c, c, s2[i >> 2])); }
            }
#pragma unroll
            for (int o = 16; o; o >>= 1)
#pragma unroll
              for (int rr = 0; rr < 2; rr++) { s1[rr] += __shfl_xor_sync(~0u, s1[rr], o); s2[rr] += __shfl_xor_sync(~0u, s2[rr], o); }
            if (lane == 0) *(float4*)&g_stats[b * 16 + r] = make_float4(s1[0], s2[0], s1[1], s2[1]);
          }
        }
        if (l == 1) { uint32_t rdy = 0; await_bit<true>(sb + W_X, 1, pn, rdy); mbar_hint(sb + B_QF + 8, 0); }
        if (l < 2) {
          float cs[8];
#pragma unroll
          for (int i = 0; i < 8; i++) cs[i] = 0.f;
          const uint4* wp = (const uint4*)(prm.wq[l] + (size_t)(bm * 128 + (lane >> 3)) * 3072 + hw * 1024 + bn * 64) + (lane & 7);
#pragma unroll 8
          for (int i = 0; i < 32; i++) {
            const uint4 v = __ldg(wp + (size_t)i * 4 * 384);
            cs[0] += bf_lo(v.x); cs[1] += bf_hi(v.x); cs[2] += bf_lo(v.y); cs[3] += bf_hi(v.y);
            cs[4] += bf_lo(v.z); cs[5] += bf_hi(v.z); cs[6] += bf_lo(v.w); cs[7] += bf_hi(v.w);
          }
#pragma unroll
          for (int i = 0; i < 8; i++) { cs[i] += __shfl_xor_sync(~0u, cs[i], 8); cs[i] += __shfl_xor_sync(~0u, cs[i], 16); }
          if (lane < 8) {
            float4* d = (float4*)(g_csp + ((l * 16 + bn) * 8 + bm) * 192 + hw * 64 + lane * 8);
            d[0] = make_float4(cs[0], cs[1], cs[2], cs[3]); d[1] = make_float4(cs[4], cs[5], cs[6], cs[7]);
          }
          __syncwarp();
          asm volatile("fence.acq_rel.gpu;" ::: "memory");
          e_red_relaxed(cnt_cs(l, bn));
          if (l == 0) e_red_relaxed(cnt_x(0, bm) + pn);
          poll_ge(lane < 8 && l == 0 ? cnt_x(0, bm) + lane : cnt_cs(l, bn), ep1 * (lane < 8 && l == 0 ? 6 : 24));
        }
        if (l > 0) {
          uint32_t rdy = 0;
#pragma unroll 1
          for (int j = 0; j < 8; j++) await_bit<true>(sb + W_X, l, j, rdy);
        }
#pragma unroll 1
        for (int it = hw * 32 + lane; it < 176; it += 96) {
          const bool rows = it < 128;
          const float4* p = rows ? (const float4*)(g_stats + bm * 256) + it : (const float4*)(g_csp + ((l & 1) * 16 + bn) * 8 * 192) + (it - 128);
          const int stride = rows ? 1024 : 48, np = rows && l == 0 ? 1 : 8;
          float4 a = make_float4(0.f, 0.f, 0.f, 0.f);
#pragma unroll
          for (int k = 0; k < 8; k++) if (k < np) { const float4 v = __ldcg(p + k * stride); a.x += v.x; a.y += v.y; a.z += v.z; a.w += v.w; }
          if (rows) {
            const float m0 = a.x * (1.f / 1024.f), m1 = a.z * (1.f / 1024.f);
            const float v0 = fmaxf(a.y * (1.f / 1024.f) - m0 * m0, 0.f), v1 = fmaxf(a.w * (1.f / 1024.f) - m1 * m1, 0.f);
            const float r0 = __fdividef(1.f, bf_round(sqrtf(bf_round(bf_round(v0) + 1e-5f)))), r1 = __fdividef(1.f, bf_round(sqrtf(bf_round(bf_round(v1) + 1e-5f))));
            a = make_float4(r0, -bf_round(m0) * r0, r1, -bf_round(m1) * r1);
          }
          *(float4*)(smem + ROWST + it * 16) = a;
        }
        __syncwarp();
        if (lane == 0) asm volatile("red.release.cta.shared.add.u32 [%0], 0x100;" ::"r"(sb + W_X) : "memory");
        if (hw == 2) {
          if (!(l & 1)) {
            bar_sync(NB_ST, 288);
            const volatile unsigned long long* hp = g_halo + ((size_t)(l >> 1) * 128 + b - 16) * 1024 + lane;
#pragma unroll 1
            for (int h = 0; h < 2; h++) {
              uint32_t t[16];
#pragma unroll
              for (int i = 0; i < 16; i++) t[i] = 0;
#pragma unroll 1
              for (uint32_t n = bm ? 0 : 100000u; n < 100000u; n++) {
                uint32_t miss = 0;
#pragma unroll
                for (int i = 0; i < 16; i++) {
                  const unsigned long long v = hp[h * 512 + i * 32];
                  t[i] = (uint32_t)v; miss |= (uint32_t)(v >> 32) ^ ep1;
                }
                if (__all_sync(~0u, !miss)) break;
              }
              const uint32_t r = (lane & 7) + ((lane >> 3) & 1) * 8, rv = lane >> 2;
#pragma unroll
              for (int jj = 0; jj < 2; jj++) stsm4(sb + KSC + r * 128 + (((4 * h + 2 * jj + (lane >> 4)) ^ (r & 7)) << 4), t[4 * jj], t[4 * jj + 1], t[4 * jj + 2], t[4 * jj + 3]);
              const uint32_t ad = sb + VSC + rv * 128 + (((4 * h + (lane & 3)) ^ (rv & 7)) << 4);
              sts128(ad, t[8], t[10], t[12], t[14]); sts128(ad + 1024, t[9], t[11], t[13], t[15]);
              bar_arrive(NB_HALO + h, 64);
            }
          } else {
            mbar_wait(sb + B_TF + 16, 0); mbar_wait(sb + B_TF + 16, 1);
            poll_ge(cnt_kv(l >> 1, bn) + (lane & 7), ep1 * 2);
            const uint4 v = __ldcg((const uint4*)(g_kn + ((l >> 1) * 128 + bn * 8) * 16) + lane);
            const uint32_t mx = max(max(v.x, v.y), max(v.z, v.w));
            const uint32_t m0 = __reduce_max_sync(~0u, (lane & 2) ? 0u : mx), m1 = __reduce_max_sync(~0u, (lane & 2) ? mx : 0u);
            if (lane == 0) *(uint2*)(smem + ROWST) = make_uint2(m0, m1);
            __syncwarp();
            bar_arrive(NB_KN, 160); bar_arrive(NB_KN + 1, 160);
            mbar_wait(sb + B_TF + 16, 0); mbar_wait(sb + B_TF + 16, 1);
          }
        } else {
#pragma unroll 1
          for (int h = 0; h < 2; h++) {
            bar_sync(NB_SIG + 2 * h + hw, 160);
            if (h == 1 && !(l & 1)) bar_arrive(NB_DONE, 96);
            e_red(cnt_o(l, 2 * bm + hw, h) + (bn >> 1));
            if (h == 1 && l == 1) e_red(cnt_ad(bn));
          }
        }
        if (hw == 2) watch(cnt_o(l, pm, (lane >> 3) & 1) + (lane & 7), ep1 * 2, 0xFFFFu, l + 1, sb + W_O);
        if (hw == 0 && l < 3) {
          bar_sync(NB_X0, 288);
          e_red(cnt_x(l + 1, bm) + pn);
        }
      }
    }
  } else {
    asm volatile("setmaxnreg.inc.sync.aligned.u32 224;");
    const uint32_t zero = prm.zero;
    cluster_wait();
#pragma unroll 1
    for (int l = 0; l < 4; l++) {
      {
        float acc[2][96];
#pragma unroll
        for (int i = 0; i < 96; i++) { acc[0][i] = 0.f; acc[1][i] = 0.f; }
        fence_regs(acc[0]); fence_regs(acc[1]);
        const bool early = l > 0 && wg == ((cta_id() >> 3) & 1);
        const uint32_t ep1 = *(volatile uint32_t*)&g_epoch + 1;
#pragma unroll 1
        for (int kt = 0; kt < 16; kt++) {
          const int s = kt & 3;
          if (l > 0 && kt == 0) mbar_wait(sb + B_QL, (l + 1) & 1);
          if (!(early && kt < 2)) mbar_wait(sb + B_QF + 8 * s, (kt >> 2) & 1);
          const uint64_t da = mkdesc(sb + s * QSTG + wg * 16384, 16, 1024, 1), db = mkdesc(sb + s * QSTG + 32768, 8192, 1024, 1);
          wg_fence();
#pragma unroll
          for (int k = 0; k < 4; k++)
#pragma unroll
            for (int m = 0; m < 2; m++) wgmma_m64n192k16_ss_tb(acc[m], da + m * 512 + k * 2, db + k * 128, 1);
          wg_commit();
          wg_wait<1>();
          if (early && (kt == 1 || kt == 2)) mbar_wait(sb + B_QF + 8 * (kt - 1), 0);
          if (kt > 0 && w == 0) e_arrive_both(sb + B_QE + 8 * ((kt - 1) & 3));
        }
#pragma unroll 1
        for (uint32_t n = 0; n < 4000000u; n++) {
          uint32_t v;
          asm volatile("ld.acquire.cta.shared.u32 %0, [%1];" : "=r"(v) : "r"(sb + W_X) : "memory");
          if ((v >> 8) == (uint32_t)(l * 256 + 3)) break;
        }
        IDS();
        const int g = lane >> 2, qd = lane & 3;
        float2 st[2][2];
#pragma unroll
        for (int m = 0; m < 2; m++)
#pragma unroll
          for (int hh = 0; hh < 2; hh++) st[m][hh] = lds64f(sb + ROWST + (wg * 128 + m * 64 + w * 16 + g + 8 * hh) * 8);
        float2 cs[4];
        auto load_cs = [&](int gi) {
#pragma unroll
          for (int j = 0; j < 4; j++) cs[j] = lds64f(sb + COLS + (gi * 32 + j * 8 + 2 * qd) * 4);
        };
        load_cs(2);
        wg_wait<0>();
        fence_regs(acc[0]); fence_regs(acc[1]);
        if (w == 0) e_arrive_both(sb + B_QE + 8 * 3);
        if (!(l & 1)) bar_arrive(NB_ST, 288);
        auto norm_tile = [&](int gi, int m, float sc, uint32_t (&t)[8], float (&nrm)[2], bool h16 = false) {
          const float r0 = st[m][0].x * sc, s0 = st[m][0].y * sc, r1 = st[m][1].x * sc, s1 = st[m][1].y * sc;
          float n0 = 0.f, n1 = 0.f;
#pragma unroll
          for (int j = 0; j < 4; j++) {
            const float* a = &acc[m][16 * gi + 4 * j];
            const float v0 = fmaf(a[0], r0, s0 * cs[j].x), v1 = fmaf(a[1], r0, s0 * cs[j].y);
            const float v2 = fmaf(a[2], r1, s1 * cs[j].x), v3 = fmaf(a[3], r1, s1 * cs[j].y);
            n0 = fmaf(v0, v0, fmaf(v1, v1, n0)); n1 = fmaf(v2, v2, fmaf(v3, v3, n1));
            t[2 * j] = h16 ? pack2h(v0, v1) : pack2(v0, v1); t[2 * j + 1] = h16 ? pack2h(v2, v3) : pack2(v2, v3);
          }
          nrm[0] = n0; nrm[1] = n1;
        };
        auto norm_group = [&](int gi, float sc, uint32_t (&t)[2][8], float (&nrm)[2][2]) { norm_tile(gi, 0, sc, t[0], nrm[0]); norm_tile(gi, 1, sc, t[1], nrm[1]); };
        uint32_t q[2][2][8];
        const uint32_t srow = (lane & 7) + ((lane >> 3) & 1) * 8;
        const uint32_t row0 = wg * 128 + w * 16;
        auto put_o = [&](int h, int m, const float (&o)[16], float i0, float i1) {
          IDS();
          bf16* op = g_os + (size_t)(bm * 256 + row0 + m * 64 + (lane >> 2)) * 1024 + h * 512 + bn * 32 + (lane & 3) * 8;
          *(uint4*)op = make_uint4(pack2(o[0] * i0, o[1] * i0), pack2(o[4] * i0, o[5] * i0), pack2(o[8] * i0, o[9] * i0), pack2(o[12] * i0, o[13] * i0));
          *(uint4*)(op + 8 * 1024) = make_uint4(pack2(o[2] * i1, o[3] * i1), pack2(o[6] * i1, o[7] * i1), pack2(o[10] * i1, o[11] * i1), pack2(o[14] * i1, o[15] * i1));
        };
        if (!(l & 1)) {
          auto put_kv = [&](int gi, uint32_t r0, const uint32_t (&t)[8]) {
            if (gi < 4) {
              const uint32_t r = r0 + srow;
#pragma unroll
              for (int jj = 0; jj < 2; jj++) stsm4(sb + KSC + r * 128 + (((4 * (gi - 2) + 2 * jj + (lane >> 4)) ^ (r & 7)) << 4), t[4 * jj], t[4 * jj + 1], t[4 * jj + 2], t[4 * jj + 3]);
            } else {
              const uint32_t r = r0 + g, ad = sb + VSC + r * 128 + (((4 * (gi - 4) + qd) ^ (r & 7)) << 4);
              sts128(ad, t[0], t[2], t[4], t[6]); sts128(ad + 1024, t[1], t[3], t[5], t[7]);
            }
          };
          const bool send = wg == 1 && w == 3 && bm < 7;
          unsigned long long* hp = g_halo + ((size_t)(l >> 1) * 128 + b) * 1024 + lane;
          uint32_t t[4][2][8];
#pragma unroll
          for (int mm = 0; mm < 2; mm++)
#pragma unroll
            for (int u = 0; u < 4; u++) {
              float nrm[2];
              norm_tile(2 + (u >> 1) + 2 * (u & 1), 1 - mm, 1.f, t[u][1 - mm], nrm);
              load_cs(u == 0 ? 4 : u == 1 ? 3 : u == 2 ? 5 : mm == 0 ? 2 : 0);
              if (mm == 0 && send) {
#pragma unroll
                for (int i = 0; i < 8; i++) st_tagged(hp + (u * 8 + i) * 32, t[u][1][i], ep1);
              }
            }
          mbar_wait(sb + B_QE + 24, 1);
#pragma unroll
          for (int u = 0; u < 4; u++) { put_kv(2 + (u >> 1) + 2 * (u & 1), 16 + row0, t[u][0]); put_kv(2 + (u >> 1) + 2 * (u & 1), 16 + row0 + 64, t[u][1]); }
          { float nrm[2][2]; norm_group(0, 1.f, q[0], nrm); }
          bar_sync(NB_SC, 256);
          const bool e = g & 1, sel = 2 * qd + (g & 1) >= g + 2, first = bm == 0 && row0 == 0;
#pragma unroll 1
          for (int h = 0; h < 2; h++) {
            if (row0 == 0) bar_sync(NB_HALO + h, 64);
            float s[2][4][4];
            uint32_t vf[2][4][4], pf[2][2][4];
#pragma unroll
            for (int m = 0; m < 2; m++)
#pragma unroll
              for (int nt = 0; nt < 4; nt++) {
                uint32_t kf[4];
                const uint32_t r = row0 + m * 64 + 8 * nt + (lane & 7), ch = 4 * h + (lane >> 3);
                ldsm4(sb + KSC + r * 128 + ((ch ^ (r & 7)) << 4), kf);
                s[m][nt][0] = s[m][nt][1] = s[m][nt][2] = s[m][nt][3] = 0.f;
                mma16816(s[m][nt], q[0][m][0], q[0][m][1], q[0][m][2], q[0][m][3], kf[0], kf[1]);
                mma16816(s[m][nt], q[0][m][4], q[0][m][5], q[0][m][6], q[0][m][7], kf[2], kf[3]);
              }
#pragma unroll
            for (int m = 0; m < 2; m++)
#pragma unroll
              for (int i = 0; i < 4; i++) {
                const uint32_t r = row0 + m * 64 + 16 * (i >> 1) + srow, ch = 4 * h + 2 * (i & 1) + (lane >> 4);
                ldsm4t(sb + VSC + r * 128 + ((ch ^ (r & 7)) << 4), vf[m][i]);
              }
            float va[4], vb[4], mx[4];
#pragma unroll
            for (int i = 0; i < 4; i++) {
              const int m = i >> 1, hh = i & 1;
              const float a = e ? s[m][hh + 1][2 * hh + 1] : s[m][hh + 1][2 * hh];
              const float lo = e ? s[m][hh][2 * hh + 1] : s[m][hh][2 * hh], hi = e ? s[m][hh + 2][2 * hh + 1] : s[m][hh + 2][2 * hh];
              const uint32_t t = pack2(a, sel ? lo : hi);
              const uint32_t u = pack2(bf_lo(t) * 0.17677669529663687f, bf_hi(t) * 0.17677669529663687f);
              va[i] = (m == 0 && hh == 0 && first) ? -INFINITY : bf_lo(u);
              vb[i] = (m == 0 && first && sel) ? -INFINITY : bf_hi(u);
              mx[i] = fmaxf(va[i], vb[i]);
            }
#pragma unroll
            for (int i = 0; i < 4; i++) mx[i] = fmaxf(mx[i], __shfl_xor_sync(~0u, mx[i], 1));
#pragma unroll
            for (int i = 0; i < 4; i++) mx[i] = fmaxf(mx[i], __shfl_xor_sync(~0u, mx[i], 2));
#pragma unroll
            for (int i = 0; i < 4; i++) {
              va[i] = ex2((va[i] - mx[i]) * 1.4426950408889634f); vb[i] = ex2((vb[i] - mx[i]) * 1.4426950408889634f);
              mx[i] = va[i] + vb[i];
            }
#pragma unroll
            for (int i = 0; i < 4; i++) mx[i] += __shfl_xor_sync(~0u, mx[i], 1);
#pragma unroll
            for (int i = 0; i < 4; i++) mx[i] += __shfl_xor_sync(~0u, mx[i], 2);
#pragma unroll
            for (int i = 0; i < 4; i++) {
              const int m = i >> 1, hh = i & 1;
              const float inv = rcp(mx[i]);
              const uint32_t t = pack2(va[i] * inv, vb[i] * inv);
              const uint32_t pa = e ? t << 16 : t & 0xFFFFu, pb = e ? t & 0xFFFF0000u : t >> 16;
              pf[m][hh][hh + 1] = pa; pf[m][hh][hh] = sel ? pb : 0u; pf[m][hh][hh + 2] = sel ? 0u : pb; pf[m][hh][3 - 3 * hh] = 0u;
            }
#pragma unroll
            for (int m = 0; m < 2; m++) {
              float o[4][4];
#pragma unroll
              for (int j = 0; j < 4; j++) o[j][0] = o[j][1] = o[j][2] = o[j][3] = 0.f;
#pragma unroll
              for (int i = 0; i < 4; i++) {
                const int kk = i >> 1, jj = 2 * (i & 1);
                mma16816(o[jj], pf[m][0][2 * kk], pf[m][1][2 * kk], pf[m][0][2 * kk + 1], pf[m][1][2 * kk + 1], vf[m][i][0], vf[m][i][1]);
                mma16816(o[jj + 1], pf[m][0][2 * kk], pf[m][1][2 * kk], pf[m][0][2 * kk + 1], pf[m][1][2 * kk + 1], vf[m][i][2], vf[m][i][3]);
              }
              const float of[16] = {o[0][0], o[0][1], o[0][2], o[0][3], o[1][0], o[1][1], o[1][2], o[1][3], o[2][0], o[2][1], o[2][2], o[2][3], o[3][0], o[3][1], o[3][2], o[3][3]};
              put_o(h, m, of, 1.f, 1.f);
            }
            bar_arrive(NB_SIG + 2 * h + wg, 160);
            if (h == 0) {
              float nrm[2][2];
              load_cs(1);
              norm_group(1, 1.f, q[0], nrm);
            }
          }
        } else {
          float qn[2];
          auto esc_ptr = [&](int gi) { IDS(); return g_esc + (size_t)(((l & 2) + (gi >> 1)) * 65536 + (2 * bn + (gi & 1)) * 2048) * 16; };
          auto norm_half = [&](int gi, float sc, uint32_t (&t)[2][8], float (&nrm)[2][2]) {
            norm_tile(gi, 0, sc, t[0], nrm[0], true); norm_tile(gi, 1, sc, t[1], nrm[1], true);
            if (!((nrm[0][0] + nrm[0][1]) + (nrm[1][0] + nrm[1][1]) <= 4e9f)) {
              uint32_t* p = esc_ptr(gi) + (bm * 256 + row0 + g) * 16 + qd;
#pragma unroll
              for (int m = 0; m < 2; m++) {
                uint32_t u[8]; float d[2];
                norm_tile(gi, m, sc, u, d);
#pragma unroll
                for (int i = 0; i < 8; i++) p[(m * 64 + (i & 1) * 8) * 16 + (i >> 1) * 4] = u[i];
              }
            }
            __syncwarp();
          };
          {
            auto max_norm = [&](const float (&nrm)[2][2]) {
              const bool o1 = qd & 1, o2 = qd & 2;
              const float a = (o1 ? nrm[1][0] : nrm[0][0]) + __shfl_xor_sync(~0u, o1 ? nrm[0][0] : nrm[1][0], 1);
              const float c = (o1 ? nrm[1][1] : nrm[0][1]) + __shfl_xor_sync(~0u, o1 ? nrm[0][1] : nrm[1][1], 1);
              const float d = (o2 ? c : a) + __shfl_xor_sync(~0u, o2 ? a : c, 2);
              return __uint_as_float(__reduce_max_sync(~0u, __float_as_uint(d)));
            };
#pragma unroll
            for (int h = 0; h < 2; h++) {
              uint32_t t[2][8]; float nrm[2][2];
              const uint32_t kb = sb + (h ? 0 : T0);
              if (h) load_cs(3);
              uint32_t tv[2][8];
              norm_half(2 + h, 1.f, t, nrm);
              load_cs(4 + h);
              float nv[2][2];
              if (h == 1) { const float kn = max_norm(nrm); if (lane == 0) g_kn[((l >> 1) * 128 + bn * 8 + bm) * 16 + 8 + wg * 4 + w] = kn; }
              norm_group(4 + h, 1.f, tv, nv);
              load_cs(h);
              if (h == 0) mbar_wait(sb + B_QE + 24, 1);
#pragma unroll
              for (int i = 0; i < 4; i++) {
                const uint32_t r = row0 + (i >> 1) * 64 + srow;
                stsm4(kb + r * 64 + (((2 * (i & 1) + (lane >> 4)) ^ ((r >> 1) & 3)) << 4), t[i >> 1][4 * (i & 1)], t[i >> 1][4 * (i & 1) + 1], t[i >> 1][4 * (i & 1) + 2], t[i >> 1][4 * (i & 1) + 3]);
              }
#pragma unroll
              for (int m = 0; m < 2; m++) {
                const uint32_t r = row0 + m * 64 + g, ad = kb + 16384 + r * 64 + ((qd ^ ((r >> 1) & 3)) << 4);
                sts128(ad, tv[m][0], tv[m][2], tv[m][4], tv[m][6]); sts128(ad + 512, tv[m][1], tv[m][3], tv[m][5], tv[m][7]);
              }
              fence_async_smem();
              bar_arrive(NB_KV + 12 * h, 288);
              if (h == 0) { const float kn = max_norm(nrm); if (lane == 0) g_kn[((l >> 1) * 128 + bn * 8 + bm) * 16 + wg * 4 + w] = kn; }
              norm_half(h, QSCALE, q[h], nrm);
#pragma unroll
              for (int i = 0; i < 4; i++) sts128(sb + QPARK + h * 16384 + (wg * 128 + w * 32 + lane) * 16 + i * 4096, q[h][i >> 1][4 * (i & 1)], q[h][i >> 1][4 * (i & 1) + 1], q[h][i >> 1][4 * (i & 1) + 2], q[h][i >> 1][4 * (i & 1) + 3]);
              qn[h] = max_norm(nrm);
            }
          }
          const bool elected = w == 0 && lane == 0;
          constexpr uint64_t VSTEP = 64 - (64ull << 16);
          constexpr int SK = 2;
          const uint32_t c_nsig = 0xB8A0B8A0u + (lane_id() & zero), c_half = 0x3F003F00u + (lane_id() & zero), c_lsb = 0x00010001u + (lane_id() & zero);
          float o[2][20], S[2][32], e[2 * SK];
          uint32_t H[2][16], P0[4] = {}, P1[4] = {};
#pragma unroll
          for (int m = 0; m < 2; m++) {
#pragma unroll
            for (int i = 0; i < 20; i++) o[m][i] = 0.f;
            fence_regs(o[m]);
          }
          auto qk = [&](int b, int ks, uint64_t d) {
            wg_n64_rs_nb_f16_f32(S[b], q[0][0][4 * ks], q[0][0][4 * ks + 1], q[0][0][4 * ks + 2], q[0][0][4 * ks + 3], d, ks ? 1 : zero);
            wg_n64_rs_nb_f16_f16(H[b], q[0][1][4 * ks], q[0][1][4 * ks + 1], q[0][1][4 * ks + 2], q[0][1][4 * ks + 3], d, ks ? 1 : zero);
          };
          auto pv = [&](uint64_t d) {
            wgmma_m64n40k16_rs_tb(o[0], P0[0], P0[1], P0[2], P0[3], d, 1);
            wgmma_m64n40k16_rs_tb(o[1], P1[0], P1[1], P1[2], P1[3], d, 1);
          };
          auto start = [&](int h) {
#pragma unroll
            for (int i = 0; i < 2 * SK; i++) e[i] = ex2(S[(h >> 2) & 1][8 * (h & 3) + i]);
            fence_regs(e);
          };
          auto finish = [&](int h) {
            const int b = (h >> 2) & 1, c = h & 3;
#pragma unroll
            for (int i = 0; i < 4; i++) {
              const float s0 = S[b][8 * c + 2 * i], s1 = S[b][8 * c + 2 * i + 1];
              P0[i] = i < SK ? pack2(e[2 * i], e[2 * i + 1]) : i < 3 ? pack2(ex2(s0), ex2(s1)) : exp2_pair(s0, s1, c_half, c_lsb);
              P1[i] = exp2_h2(H[b][4 * c + i], c_nsig);
            }
            fence_regs(P0); fence_regs(P1);
          };
          uint64_t kd = prm.kv[0].kd;
          mbar_wait(sb + B_TF, 0);
          wg_fence();
#pragma unroll
          for (int b = 0; b < 2; b++) {
            wg_n64_rs_nb_f16_f32_z(S[b], q[0][0][0], q[0][0][1], q[0][0][2], q[0][0][3], kd + 256 * b, 0);
            wg_n64_rs_nb_f16_f16_z(H[b], q[0][1][0], q[0][1][1], q[0][1][2], q[0][1][3], kd + 256 * b, 0);
            if (b == 0) qk(0, 1, kd + 2);
            wg_commit();
          }
          wg_wait<1>(); fence_regs(S[0]); fence_regs(H[0]);
          start(0); finish(0); start(1);
          wg_wait<0>();
          const int jlag = JLAG - wg;
          int redo = 0;
#pragma unroll 1
          for (int pass = 0, j = 1; pass < 2; pass++) {
#pragma unroll 1
           do {
            const uint64_t vd = prm.kv[j].vd;
            bool go = false;
#pragma unroll
            for (int h = 2; h < 18; h++) {
              const int px = (h >> 2) + 1, c = h & 3;
              wg_fence();
              if (h == 13) kd = prm.kv[j].kd;
              if (h == 2) qk(1, 0, kd + 256);
              else if ((c == 1 || c == 2) && h < 17) qk(px & 1, c - 1, kd + (px & 3) * 256 + 2 * (c - 1));
              pv(vd + (h - 2) * VSTEP);
              if (h == 2) qk(1, 1, kd + 258);
              wg_commit();
              if (h == 11) go = mbar_test(sb + B_TF + 8 * (j & 3), (j >> 2) & 1) && j != jlag && j != 8;
              finish(h - 1); start(h);
              if (h != 12 && h != 17) sched_fence();
              if (h == 12 && !go) {
                if (j < 16) mbar_wait(sb + B_TF + 8 * (j & 3), (j >> 2) & 1);
                if (j == jlag) { if (wg) bar_sync(NB_HALO, 256); else bar_arrive(NB_HALO, 256); }
                if (j == 8) {
#pragma unroll
                  for (int i = 0; i < 4; i++) lds128(sb + QPARK + 16384 + (wg * 128 + w * 32 + lane_id()) * 16 + i * 4096, &q[0][i >> 1][4 * (i & 1)]);
                }
              }
              if (h == 17) wg_wait<0>(); else if (h & 1) wg_wait<1>();
              if (c == 3) { fence_regs(S[px & 1]); fence_regs(H[px & 1]); }
            }
            if (elected) mbar_arrive(sb + B_TE + 8 * ((j + 3) & 3));
           } while (j++ & 7);
            fence_regs(o[0]); fence_regs(o[1]);
            if (pass == 0) bar_sync(NB_KN + wg, 160);
            const float kmax = *(volatile float*)(smem + ROWST + 4 * pass);
            const bool wide = !(qn[0] <= 1.6e7f && kmax <= 1.6e7f && qn[0] * kmax <= 112.f * 112.f);
            uint32_t pk[2][8];
            auto norm_o = [&](uint32_t (&u)[8], const float (&a)[20]) {
              const float i0 = rcp(a[16]), i1 = rcp(a[18]);
#pragma unroll
              for (int i = 0; i < 4; i++) { u[i] = pack2(a[4 * i] * i0, a[4 * i + 1] * i0); u[4 + i] = pack2(a[4 * i + 2] * i1, a[4 * i + 3] * i1); }
            };
            int badm = 0;
#pragma unroll
            for (int m = 0; m < 2; m++) {
              norm_o(pk[m], o[m]);
              uint32_t chk[2] = {0u, 0u};
#pragma unroll
              for (int i = 0; i < 8; i++) asm("fma.rn.bf16x2 %0, %1, %2, %0;" : "+r"(chk[i & 1]) : "r"(pk[m][i]), "r"(0u));
              const bool bad = wide | !(fminf(o[m][16], o[m][18]) >= 9.3e-10f) | !(o[m][16] + o[m][18] <= 1e36f) | (((chk[0] | chk[1]) & 0x7FFF7FFFu) != 0);
              badm |= __any_sync(~0u, bad) << m;
            }
            if (badm) {
              redo |= badm << 2 * pass;
              uint32_t* p = esc_ptr(pass) + ((cta_id() >> 4) * 256 + row0 + (lane_id() >> 2)) * 16 + (lane_id() & 3);
#pragma unroll
              for (int i = 0; i < 4; i++) {
                uint32_t u[4] = {q[0][i >> 1][4 * (i & 1)], q[0][i >> 1][4 * (i & 1) + 1], q[0][i >> 1][4 * (i & 1) + 2], q[0][i >> 1][4 * (i & 1) + 3]};
                if (pass == 0) lds128(sb + QPARK + (wg * 128 + w * 32 + lane_id()) * 16 + i * 4096, u);
#pragma unroll
                for (int k = 0; k < 4; k++) { uint32_t* a = p + ((i >> 1) * 64 + (k & 1) * 8) * 16 + (2 * (i & 1) + (k >> 1)) * 4; *a = unesc(u[k], a); }
              }
              __syncwarp();
            }
            {
              IDS();
              bf16* op = g_os + (size_t)(bm * 256 + row0 + (lane >> 2)) * 1024 + pass * 512 + bn * 32 + (lane & 3) * 8;
#pragma unroll
              for (int i = 0; i < 4; i++) *(uint4*)(op + ((i >> 1) * 64 + (i & 1) * 8) * 1024) = make_uint4(pk[i >> 1][4 * (i & 1)], pk[i >> 1][4 * (i & 1) + 1], pk[i >> 1][4 * (i & 1) + 2], pk[i >> 1][4 * (i & 1) + 3]);
            }
            if (!badm) bar_arrive(NB_SIG + 2 * pass + wg, 160);
            qn[0] = qn[1];
#pragma unroll
            for (int m = 0; m < 2; m++) {
#pragma unroll
              for (int i = 0; i < 20; i++) o[m][i] = 0.f;
              fence_regs(o[m]);
            }
          }
          if (redo) {
#pragma unroll 1
            for (int t = 0; t < 4; t++) {
              const int pass = t >> 1, m = t & 1;
              if ((redo >> t) & 1) {
                uint32_t qq[8]; float res[20];
                const uint32_t* p = esc_ptr(pass) + ((cta_id() >> 4) * 256 + row0 + m * 64 + (lane_id() >> 2)) * 16 + (lane_id() & 3);
#pragma unroll
                for (int i = 0; i < 8; i++) qq[i] = __ldcg(p + (i & 1) * 128 + (i >> 1) * 4);
                attn_slow(qq, 2 * (cta_id() & 15) + pass, esc_ptr(2 + pass), res, lane_id());
                const float of[16] = {res[0], res[1], res[2], res[3], res[4], res[5], res[6], res[7], res[8], res[9], res[10], res[11], res[12], res[13], res[14], res[15]};
                put_o(pass, m, of, rcp(res[16]), rcp(res[18]));
              }
              if (m && ((redo >> 2 * pass) & 3)) bar_arrive(NB_SIG + 2 * pass + wg, 160);
            }
          }
        }
      }
      {
        float acc[64];
#pragma unroll
        for (int i = 0; i < 64; i++) acc[i] = 0.f;
        fence_regs(acc);
        uint32_t s = 0, lap = 0;
#pragma unroll 1
        for (int kt = 0; kt < 16; kt++) {
          mbar_wait(sb + B_PF + 8 * s, ((s < 4 ? l : 0) + lap) & 1);
          const uint64_t da = mkdesc(sb + pslot_a(s, l) + wg * 8192, 16, 1024, 1), db = mkdesc(sb + pslot_b(s), 8192, 1024, 1);
          wg_fence();
#pragma unroll
          for (int k = 0; k < 4; k++) wgmma_m64n128k16_ss_tb(acc, da + k * 2, db + k * 128, 1);
          wg_commit();
          wg_wait<1>();
          if (kt > 0 && w == 0) e_arrive_both(sb + B_PE + 8 * (s ? s - 1 : 5));
          if (++s == 6) { s = 0; lap++; }
        }
        IDS();
        const int g = lane >> 2, qd = lane & 3;
        const int r0 = wg * 64 + w * 16;
        const uint32_t r = r0 + (lane & 7) + ((lane >> 3) & 1) * 8;
        uint32_t x[8][4];
        mbar_wait(sb + B_RF, l & 1);
#pragma unroll
        for (int jj = 0; jj < 8; jj++) ldsm4(sb + RES + (jj >> 2) * 16384 + r * 128 + ((((2 * jj + (lane >> 4)) & 7) ^ (r & 7)) << 4), x[jj]);
        wg_wait<0>();
        fence_regs(acc);
        if (w == 0) e_arrive_both(sb + B_PE + 8 * 3);
        bar_sync(NB_SC, 256);
        const CUtensorMap* mo = &prm.m[l == 3 ? M_OUT : M_XST];
#pragma unroll
        for (int jj = 0; jj < 8; jj++) {
#pragma unroll
          for (int i = 0; i < 4; i++) x[jj][i] = add_bf16x2(x[jj][i], pack2(acc[8 * jj + 2 * i], acc[8 * jj + 2 * i + 1]));
          stsm4(sb + (jj >> 2) * QSTG + po * 16384 + r * 128 + ((((2 * jj + (lane >> 4)) & 7) ^ (r & 7)) << 4), x[jj][0], x[jj][1], x[jj][2], x[jj][3]);
          if ((jj & 3) == 3) { fence_async_smem(); __syncwarp(); tma_st(mo, pn * 128 + (jj >> 2) * 64, pm * 128 + r0, sb + (jj >> 2) * QSTG + po * 16384 + r0 * 128); }
        }
        bulk_commit();
        if (l < 3) {
          bar_arrive(NB_X, 288);
          float s1[2] = {0.f, 0.f}, s2[2] = {0.f, 0.f};
#pragma unroll
          for (int i = 0; i < 32; i++) {
            const float a = bf_lo(x[i >> 2][i & 3]), c = bf_hi(x[i >> 2][i & 3]);
            s1[i & 1] += a + c; s2[i & 1] = fmaf(a, a, fmaf(c, c, s2[i & 1]));
          }
#pragma unroll
          for (int hh = 0; hh < 2; hh++) { s1[hh] += __shfl_xor_sync(~0u, s1[hh], 1); s2[hh] += __shfl_xor_sync(~0u, s2[hh], 1); }
#pragma unroll
          for (int hh = 0; hh < 2; hh++) {
            s1[hh] += __shfl_xor_sync(~0u, s1[hh], 2); s2[hh] += __shfl_xor_sync(~0u, s2[hh], 2);
            if (qd == 0) g_stats[pn * 2048 + pm * 128 + r0 + g + 8 * hh] = make_float2(s1[hh], s2[hh]);
          }
        }
        bulk_wait_n<0>();
        if (l < 3) bar_arrive(NB_X0, 288);
      }
    }
  }
  asm volatile("barrier.cluster.arrive.relaxed.aligned;\nbarrier.cluster.wait.aligned;" ::: "memory");
}

typedef CUresult (*EncodeFn)(CUtensorMap*, CUtensorMapDataType, cuuint32_t, void*, const cuuint64_t*, const cuuint64_t*, const cuuint32_t*,
                             const cuuint32_t*, CUtensorMapInterleave, CUtensorMapSwizzle, CUtensorMapL2promotion, CUtensorMapFloatOOBfill);

static void make_map(EncodeFn fn, CUtensorMap* m, const void* ptr, int rank, const uint64_t* dims, const uint64_t* strides, const uint32_t* box, CUtensorMapSwizzle sw) {
  cuuint64_t d[5], st[4];
  cuuint32_t bx[5], es[5];
  for (int i = 0; i < rank; i++) { d[i] = dims[i]; bx[i] = box[i]; es[i] = 1; if (i) st[i - 1] = strides[i - 1] * 2; }
  fn(m, CU_TENSOR_MAP_DATA_TYPE_BFLOAT16, rank, (void*)ptr, d, st, bx, es, CU_TENSOR_MAP_INTERLEAVE_NONE, sw,
     CU_TENSOR_MAP_L2_PROMOTION_L2_128B, CU_TENSOR_MAP_FLOAT_OOB_FILL_NONE);
}
static void map2(EncodeFn fn, CUtensorMap* m, const void* ptr, uint64_t inner, uint64_t outer, uint32_t bi, uint32_t bo, CUtensorMapSwizzle sw) {
  const uint64_t d[2] = {inner, outer}, st[1] = {inner};
  const uint32_t bx[2] = {bi, bo};
  make_map(fn, m, ptr, 2, d, st, bx, sw);
}

extern "C" void kernel_launch(void* const* d_in, const int* in_sizes, int n_in, void* d_out, int out_size) {
  (void)in_sizes; (void)n_in; (void)out_size;
  static EncodeFn enc = nullptr;
  static void *xs, *os, *kk, *vv;
  static int sbase = 1024;
  if (!enc) {
    void* p = nullptr;
    cudaDriverEntryPointQueryResult qr;
    cudaGetDriverEntryPoint("cuTensorMapEncodeTiled", &p, cudaEnableDefault, &qr);
    enc = (EncodeFn)p;
    cudaGetSymbolAddress(&xs, g_xs); cudaGetSymbolAddress(&os, g_os); cudaGetSymbolAddress(&kk, g_k); cudaGetSymbolAddress(&vv, g_v);
    int dev = 0;
    cudaGetDevice(&dev);
    cudaDeviceGetAttribute(&sbase, cudaDevAttrReservedSharedMemoryPerBlock, dev);
    cudaFuncSetAttribute(fused_kernel, cudaFuncAttributeMaxDynamicSharedMemorySize, SMEM_BYTES);
  }
  Params prm;
  const CUtensorMapSwizzle S128 = CU_TENSOR_MAP_SWIZZLE_128B, S64 = CU_TENSOR_MAP_SWIZZLE_64B;
  map2(enc, &prm.m[M_X0A], d_in[0], 1024, 2048, 64, 256, S128);
  map2(enc, &prm.m[M_XSA], xs, 1024, 2048, 64, 256, S128);
  for (int t = 0; t < 2; t++) {
    const uint64_t d3[3] = {1024, 1024, 3}, s3[2] = {3072, 1024};
    const uint32_t b3[3] = {64, 64, 3};
    make_map(enc, &prm.m[M_WQA + t], d_in[1 + 3 * t], 3, d3, s3, b3, S128);
    const uint64_t d5[5] = {64, 32, 2, 16, 16}, s5[4] = {1024, 32 * 1024, 64 * 1024, 64};
    const uint32_t b5[5] = {64, 32, 1, 2, 2};
    make_map(enc, &prm.m[M_WOA + t], d_in[2 + 3 * t], 5, d5, s5, b5, S128);
    const uint64_t dr[3] = {64, 2048, 16}, sr[2] = {1024, 64};
    const uint32_t br[3] = {64, 128, 2};
    make_map(enc, &prm.m[M_X0R + t], t ? xs : d_in[0], 3, dr, sr, br, S128);
  }
  map2(enc, &prm.m[M_OS], os, 1024, 2048, 64, 64, S128);
  map2(enc, &prm.m[M_K], kk, 32, 65536, 32, 256, S64);
  map2(enc, &prm.m[M_V], vv, 32, 65536, 32, 256, S64);
  map2(enc, &prm.m[M_XSO], xs, 1024, 2048, 64, 128, S128);
  map2(enc, &prm.m[M_X0H], d_in[0], 1024, 2048, 64, 128, S128);
  map2(enc, &prm.m[M_XST], xs, 1024, 2048, 64, 16, S128);
  map2(enc, &prm.m[M_OUT], d_out, 1024, 2048, 64, 16, S128);
  prm.x0 = (const bf16*)d_in[0];
  prm.wq[0] = (const bf16*)d_in[1]; prm.wq[1] = (const bf16*)d_in[4];
  prm.zero = 0;
  for (int i = 0; i < 128; i++) prm.map[i] = remap(i);
  {
    const uint64_t hi = 0x80000020ull << 32, k0 = sbase + T0, v0 = k0 + 16384, vstep = 64 - (64ull << 16);
    for (int j = 0; j < 17; j++) {
      prm.kv[j].kd = (hi | 1u << 16 | k0 >> 4) + 2048 * ((j < 16 ? j : 15) & 3);
      prm.kv[j].vd = (hi | (uint64_t)(ONES - T0 - 16384) >> 4 << 16 | v0 >> 4) + 32 * vstep * ((j ? j - 1 : 0) & 3);
    }
  }
  fused_kernel<<<128, 384, SMEM_BYTES>>>(prm);
}
```

```cpp
#include <cuda_runtime.h>
#include <cuda_bf16.h>
#include <cuda.h>
#include <stdint.h>

typedef __nv_bfloat16 bf16;

__device__ __forceinline__ void wgmma_m64n192k16_ss_tb(float (&d)[96], uint64_t da, uint64_t db, int scale_d) {
  asm volatile("{\n.reg .pred p;\nsetp.ne.b32 p, %98, 0;\n"
    "wgmma.mma_async.sync.aligned.m64n192k16.f32.bf16.bf16 "
    "{%0, %1, %2, %3, %4, %5, %6, %7, %8, %9, %10, %11, %12, %13, %14, %15, "
    "%16, %17, %18, %19, %20, %21, %22, %23, %24, %25, %26, %27, %28, %29, %30, %31, "
    "%32, %33, %34, %35, %36, %37, %38, %39, %40, %41, %42, %43, %44, %45, %46, %47, "
    "%48, %49, %50, %51, %52, %53, %54, %55, %56, %57, %58, %59, %60, %61, %62, %63, "
    "%64, %65, %66, %67, %68, %69, %70, %71, %72, %73, %74, %75, %76, %77, %78, %79, "
    "%80, %81, %82, %83, %84, %85, %86, %87, %88, %89, %90, %91, %92, %93, %94, %95}, "
    "%96, %97, p, 1, 1, 0, 1;\n}\n"
    : "+f"(d[0]), "+f"(d[1]), "+f"(d[2]), "+f"(d[3]), "+f"(d[4]), "+f"(d[5]), "+f"(d[6]), "+f"(d[7]),
      "+f"(d[8]), "+f"(d[9]), "+f"(d[10]), "+f"(d[11]), "+f"(d[12]), "+f"(d[13]), "+f"(d[14]), "+f"(d[15]),
      "+f"(d[16]), "+f"(d[17]), "+f"(d[18]), "+f"(d[19]), "+f"(d[20]), "+f"(d[21]), "+f"(d[22]), "+f"(d[23]),
      "+f"(d[24]), "+f"(d[25]), "+f"(d[26]), "+f"(d[27]), "+f"(d[28]), "+f"(d[29]), "+f"(d[30]), "+f"(d[31]),
      "+f"(d[32]), "+f"(d[33]), "+f"(d[34]), "+f"(d[35]), "+f"(d[36]), "+f"(d[37]), "+f"(d[38]), "+f"(d[39]),
      "+f"(d[40]), "+f"(d[41]), "+f"(d[42]), "+f"(d[43]), "+f"(d[44]), "+f"(d[45]), "+f"(d[46]), "+f"(d[47]),
      "+f"(d[48]), "+f"(d[49]), "+f"(d[50]), "+f"(d[51]), "+f"(d[52]), "+f"(d[53]), "+f"(d[54]), "+f"(d[55]),
      "+f"(d[56]), "+f"(d[57]), "+f"(d[58]), "+f"(d[59]), "+f"(d[60]), "+f"(d[61]), "+f"(d[62]), "+f"(d[63]),
      "+f"(d[64]), "+f"(d[65]), "+f"(d[66]), "+f"(d[67]), "+f"(d[68]), "+f"(d[69]), "+f"(d[70]), "+f"(d[71]),
      "+f"(d[72]), "+f"(d[73]), "+f"(d[74]), "+f"(d[75]), "+f"(d[76]), "+f"(d[77]), "+f"(d[78]), "+f"(d[79]),
      "+f"(d[80]), "+f"(d[81]), "+f"(d[82]), "+f"(d[83]), "+f"(d[84]), "+f"(d[85]), "+f"(d[86]), "+f"(d[87]),
      "+f"(d[88]), "+f"(d[89]), "+f"(d[90]), "+f"(d[91]), "+f"(d[92]), "+f"(d[93]), "+f"(d[94]), "+f"(d[95])
    : "l"(da), "l"(db), "r"(scale_d));
}

__device__ __forceinline__ void wgmma_m64n128k16_ss_tb(float (&d)[64], uint64_t da, uint64_t db, int scale_d) {
  asm volatile("{\n.reg .pred p;\nsetp.ne.b32 p, %66, 0;\n"
    "wgmma.mma_async.sync.aligned.m64n128k16.f32.bf16.bf16 "
    "{%0, %1, %2, %3, %4, %5, %6, %7, %8, %9, %10, %11, %12, %13, %14, %15, "
    "%16, %17, %18, %19, %20, %21, %22, %23, %24, %25, %26, %27, %28, %29, %30, %31, "
    "%32, %33, %34, %35, %36, %37, %38, %39, %40, %41, %42, %43, %44, %45, %46, %47, "
    "%48, %49, %50, %51, %52, %53, %54, %55, %56, %57, %58, %59, %60, %61, %62, %63}, "
    "%64, %65, p, 1, 1, 0, 1;\n}\n"
    : "+f"(d[0]), "+f"(d[1]), "+f"(d[2]), "+f"(d[3]), "+f"(d[4]), "+f"(d[5]), "+f"(d[6]), "+f"(d[7]),
      "+f"(d[8]), "+f"(d[9]), "+f"(d[10]), "+f"(d[11]), "+f"(d[12]), "+f"(d[13]), "+f"(d[14]), "+f"(d[15]),
      "+f"(d[16]), "+f"(d[17]), "+f"(d[18]), "+f"(d[19]), "+f"(d[20]), "+f"(d[21]), "+f"(d[22]), "+f"(d[23]),
      "+f"(d[24]), "+f"(d[25]), "+f"(d[26]), "+f"(d[27]), "+f"(d[28]), "+f"(d[29]), "+f"(d[30]), "+f"(d[31]),
      "+f"(d[32]), "+f"(d[33]), "+f"(d[34]), "+f"(d[35]), "+f"(d[36]), "+f"(d[37]), "+f"(d[38]), "+f"(d[39]),
      "+f"(d[40]), "+f"(d[41]), "+f"(d[42]), "+f"(d[43]), "+f"(d[44]), "+f"(d[45]), "+f"(d[46]), "+f"(d[47]),
      "+f"(d[48]), "+f"(d[49]), "+f"(d[50]), "+f"(d[51]), "+f"(d[52]), "+f"(d[53]), "+f"(d[54]), "+f"(d[55]),
      "+f"(d[56]), "+f"(d[57]), "+f"(d[58]), "+f"(d[59]), "+f"(d[60]), "+f"(d[61]), "+f"(d[62]), "+f"(d[63])
    : "l"(da), "l"(db), "r"(scale_d));
}

__device__ __forceinline__ void wgmma_m64n40k16_rs_tb(float (&d)[20], uint32_t a0, uint32_t a1, uint32_t a2, uint32_t a3, uint64_t db, int scale_d) {
  asm volatile("{\n.reg .pred p;\nsetp.ne.b32 p, %25, 0;\n"
    "wgmma.mma_async.sync.aligned.m64n40k16.f32.bf16.bf16 "
    "{%0, %1, %2, %3, %4, %5, %6, %7, %8, %9, %10, %11, %12, %13, %14, %15, "
    "%16, %17, %18, %19}, "
    "{%20, %21, %22, %23}, %24, p, 1, 1, 1;\n}\n"
    : "+f"(d[0]), "+f"(d[1]), "+f"(d[2]), "+f"(d[3]), "+f"(d[4]), "+f"(d[5]), "+f"(d[6]), "+f"(d[7]),
      "+f"(d[8]), "+f"(d[9]), "+f"(d[10]), "+f"(d[11]), "+f"(d[12]), "+f"(d[13]), "+f"(d[14]), "+f"(d[15]),
      "+f"(d[16]), "+f"(d[17]), "+f"(d[18]), "+f"(d[19])
    : "r"(a0), "r"(a1), "r"(a2), "r"(a3), "l"(db), "r"(scale_d));
}

__device__ __forceinline__ void wg_n64_rs_nb_f16_f32(float (&d)[32], uint32_t a0, uint32_t a1, uint32_t a2, uint32_t a3, uint64_t db, int scale_d) {
  asm volatile("{\n.reg .pred p;\nsetp.ne.b32 p, %37, 0;\n"
    "wgmma.mma_async.sync.aligned.m64n64k16.f32.f16.f16 "
    "{%0, %1, %2, %3, %4, %5, %6, %7, %8, %9, %10, %11, %12, %13, %14, %15, "
    "%16, %17, %18, %19, %20, %21, %22, %23, %24, %25, %26, %27, %28, %29, %30, %31}, "
    "{%32, %33, %34, %35}, %36, p, 1, 1, 0;\n}\n"
    : "+f"(d[0]), "+f"(d[1]), "+f"(d[2]), "+f"(d[3]), "+f"(d[4]), "+f"(d[5]), "+f"(d[6]), "+f"(d[7]),
      "+f"(d[8]), "+f"(d[9]), "+f"(d[10]), "+f"(d[11]), "+f"(d[12]), "+f"(d[13]), "+f"(d[14]), "+f"(d[15]),
      "+f"(d[16]), "+f"(d[17]), "+f"(d[18]), "+f"(d[19]), "+f"(d[20]), "+f"(d[21]), "+f"(d[22]), "+f"(d[23]),
      "+f"(d[24]), "+f"(d[25]), "+f"(d[26]), "+f"(d[27]), "+f"(d[28]), "+f"(d[29]), "+f"(d[30]), "+f"(d[31])
    : "r"(a0), "r"(a1), "r"(a2), "r"(a3), "l"(db), "r"(scale_d));
}

__device__ __forceinline__ void wg_n64_rs_nb_f16_f16(uint32_t (&d)[16], uint32_t a0, uint32_t a1, uint32_t a2, uint32_t a3, uint64_t db, int scale_d) {
  asm volatile("{\n.reg .pred p;\nsetp.ne.b32 p, %21, 0;\n"
    "wgmma.mma_async.sync.aligned.m64n64k16.f16.f16.f16 "
    "{%0, %1, %2, %3, %4, %5, %6, %7, %8, %9, %10, %11, %12, %13, %14, %15}, "
    "{%16, %17, %18, %19}, %20, p, 1, 1, 0;\n}\n"
    : "+r"(d[0]), "+r"(d[1]), "+r"(d[2]), "+r"(d[3]), "+r"(d[4]), "+r"(d[5]), "+r"(d[6]), "+r"(d[7]),
      "+r"(d[8]), "+r"(d[9]), "+r"(d[10]), "+r"(d[11]), "+r"(d[12]), "+r"(d[13]), "+r"(d[14]), "+r"(d[15])
    : "r"(a0), "r"(a1), "r"(a2), "r"(a3), "l"(db), "r"(scale_d));
}

__device__ __forceinline__ void wg_n64_rs_nb_f16_f32_z(float (&d)[32], uint32_t a0, uint32_t a1, uint32_t a2, uint32_t a3, uint64_t db, int scale_d) {
  asm volatile("{\n.reg .pred p;\nsetp.ne.b32 p, %37, 0;\n"
    "wgmma.mma_async.sync.aligned.m64n64k16.f32.f16.f16 "
    "{%0, %1, %2, %3, %4, %5, %6, %7, %8, %9, %10, %11, %12, %13, %14, %15, "
    "%16, %17, %18, %19, %20, %21, %22, %23, %24, %25, %26, %27, %28, %29, %30, %31}, "
    "{%32, %33, %34, %35}, %36, p, 1, 1, 0;\n}\n"
    : "=f"(d[0]), "=f"(d[1]), "=f"(d[2]), "=f"(d[3]), "=f"(d[4]), "=f"(d[5]), "=f"(d[6]), "=f"(d[7]),
      "=f"(d[8]), "=f"(d[9]), "=f"(d[10]), "=f"(d[11]), "=f"(d[12]), "=f"(d[13]), "=f"(d[14]), "=f"(d[15]),
      "=f"(d[16]), "=f"(d[17]), "=f"(d[18]), "=f"(d[19]), "=f"(d[20]), "=f"(d[21]), "=f"(d[22]), "=f"(d[23]),
      "=f"(d[24]), "=f"(d[25]), "=f"(d[26]), "=f"(d[27]), "=f"(d[28]), "=f"(d[29]), "=f"(d[30]), "=f"(d[31])
    : "r"(a0), "r"(a1), "r"(a2), "r"(a3), "l"(db), "r"(scale_d));
}

__device__ __forceinline__ void wg_n64_rs_nb_f16_f16_z(uint32_t (&d)[16], uint32_t a0, uint32_t a1, uint32_t a2, uint32_t a3, uint64_t db, int scale_d) {
  asm volatile("{\n.reg .pred p;\nsetp.ne.b32 p, %21, 0;\n"
    "wgmma.mma_async.sync.aligned.m64n64k16.f16.f16.f16 "
    "{%0, %1, %2, %3, %4, %5, %6, %7, %8, %9, %10, %11, %12, %13, %14, %15}, "
    "{%16, %17, %18, %19}, %20, p, 1, 1, 0;\n}\n"
    : "=r"(d[0]), "=r"(d[1]), "=r"(d[2]), "=r"(d[3]), "=r"(d[4]), "=r"(d[5]), "=r"(d[6]), "=r"(d[7]),
      "=r"(d[8]), "=r"(d[9]), "=r"(d[10]), "=r"(d[11]), "=r"(d[12]), "=r"(d[13]), "=r"(d[14]), "=r"(d[15])
    : "r"(a0), "r"(a1), "r"(a2), "r"(a3), "l"(db), "r"(scale_d));
}

#define DEVINL __device__ __forceinline__
DEVINL void wg_fence() { asm volatile("wgmma.fence.sync.aligned;" ::: "memory"); }
DEVINL void wg_commit() { asm volatile("wgmma.commit_group.sync.aligned;" ::: "memory"); }
template <int N> DEVINL void wg_wait() { asm volatile("wgmma.wait_group.sync.aligned %0;" ::"n"(N) : "memory"); }
DEVINL uint64_t mkdesc(uint32_t addr, uint32_t lbo, uint32_t sbo, int sw) {
  return (uint64_t)((addr & 0x3FFFF) >> 4) | ((uint64_t)(lbo >> 4) << 16) | ((uint64_t)(sbo >> 4) << 32) | ((uint64_t)sw << 62);
}
DEVINL void mbar_init(uint32_t bar, uint32_t cnt) { asm volatile("mbarrier.init.shared::cta.b64 [%0], %1;" ::"r"(bar), "r"(cnt) : "memory"); }
DEVINL void mbar_arrive(uint32_t bar) { asm volatile("mbarrier.arrive.shared::cta.b64 _, [%0];" ::"r"(bar) : "memory"); }
DEVINL bool mbar_try(uint32_t bar, uint32_t parity) {
  uint32_t ok;
  asm volatile("{\n.reg .pred p;\nmbarrier.try_wait.parity.shared::cta.b64 p, [%1], %2;\nselp.u32 %0, 1, 0, p;\n}" : "=r"(ok) : "r"(bar), "r"(parity) : "memory");
  return ok;
}
DEVINL bool mbar_test(uint32_t bar, uint32_t parity) {
  uint32_t ok;
  asm volatile("{\n.reg .pred p;\nmbarrier.test_wait.parity.shared::cta.b64 p, [%1], %2;\nselp.u32 %0, 1, 0, p;\n}" : "=r"(ok) : "r"(bar), "r"(parity) : "memory");
  return ok;
}
DEVINL void mbar_hint(uint32_t bar, uint32_t parity) {
#pragma unroll 1
  for (uint32_t n = 0; n < 16u; n++) if (mbar_try(bar, parity)) break;
}
DEVINL void mbar_wait(uint32_t bar, uint32_t parity) {
#pragma unroll 1
  for (uint32_t n = 0; n < 100000u; n++) if (mbar_try(bar, parity)) break;
}
#define EL(txt) "{\n.reg .pred pe;\nelect.sync _|pe, 0xffffffff;\n@pe " txt "\n}"
DEVINL void e_expect_tx(uint32_t bar, uint32_t bytes) { asm volatile(EL("mbarrier.arrive.expect_tx.shared::cta.b64 _, [%0], %1;") ::"r"(bar), "r"(bytes) : "memory"); }
DEVINL void e_arrive(uint32_t bar) { asm volatile(EL("mbarrier.arrive.shared::cta.b64 _, [%0];") ::"r"(bar) : "memory"); }
DEVINL void e_red(uint32_t* p) { asm volatile(EL("red.release.gpu.global.add.u32 [%0], 1;") ::"l"(p) : "memory"); }
DEVINL void e_red_relaxed(uint32_t* p) { asm volatile(EL("red.relaxed.gpu.global.add.u32 [%0], 1;") ::"l"(p) : "memory"); }
DEVINL void tma_ld(uint32_t dst, const CUtensorMap* m, int c0, int c1, uint32_t bar) {
  asm volatile(EL("cp.async.bulk.tensor.2d.shared::cluster.global.mbarrier::complete_tx::bytes [%0], [%1, {%3, %4}], [%2];")
               ::"r"(dst), "l"(m), "r"(bar), "r"(c0), "r"(c1) : "memory");
}
DEVINL void tma_ld3(uint32_t dst, const CUtensorMap* m, int c0, int c1, int c2, uint32_t bar) {
  asm volatile(EL("cp.async.bulk.tensor.3d.shared::cluster.global.mbarrier::complete_tx::bytes [%0], [%1, {%3, %4, %5}], [%2];")
               ::"r"(dst), "l"(m), "r"(bar), "r"(c0), "r"(c1), "r"(c2) : "memory");
}
DEVINL void tma_ld5(uint32_t dst, const CUtensorMap* m, int c2, int c3, int c4, uint32_t bar) {
  asm volatile(EL("cp.async.bulk.tensor.5d.shared::cluster.global.mbarrier::complete_tx::bytes [%0], [%1, {0, 0, %3, %4, %5}], [%2];")
               ::"r"(dst), "l"(m), "r"(bar), "r"(c2), "r"(c3), "r"(c4) : "memory");
}
DEVINL void tma_ld_mc(uint32_t dst, const CUtensorMap* m, int c0, int c1, uint32_t bar) {
  asm volatile(EL("cp.async.bulk.tensor.2d.shared::cluster.global.mbarrier::complete_tx::bytes.multicast::cluster [%0], [%1, {%3, %4}], [%2], %5;")
               ::"r"(dst), "l"(m), "r"(bar), "r"(c0), "r"(c1), "h"((uint16_t)3) : "memory");
}
DEVINL void e_arrive_both(uint32_t bar) {
  asm volatile("{\n.reg .pred pe;\n.reg .b32 r0, r1;\nelect.sync _|pe, 0xffffffff;\nmapa.shared::cluster.u32 r0, %0, 0;\nmapa.shared::cluster.u32 r1, %0, 1;\n"
               "@pe mbarrier.arrive.shared::cluster.b64 _, [r0];\n@pe mbarrier.arrive.shared::cluster.b64 _, [r1];\n}" ::"r"(bar) : "memory");
}
DEVINL void tma_st(const CUtensorMap* m, int c0, int c1, uint32_t src) {
  asm volatile(EL("cp.async.bulk.tensor.2d.global.shared::cta.bulk_group [%0, {%2, %3}], [%1];") ::"l"(m), "r"(src), "r"(c0), "r"(c1) : "memory");
}
DEVINL void bulk_commit() { asm volatile("cp.async.bulk.commit_group;" ::: "memory"); }
template <int N> DEVINL void bulk_wait_n() { asm volatile("cp.async.bulk.wait_group %0;\nbar.warp.sync 0xffffffff;" ::"n"(N) : "memory"); }
DEVINL void l2_prefetch(const void* g, uint32_t bytes) { asm volatile(EL("cp.async.bulk.prefetch.L2.global [%0], %1;") ::"l"(g), "r"(bytes) : "memory"); }
DEVINL void fence_async_smem() { asm volatile("fence.proxy.async.shared::cta;" ::: "memory"); }
DEVINL void fence_async_gl() { asm volatile("fence.proxy.async.global;" ::: "memory"); }
DEVINL void cluster_wait() { asm volatile("barrier.cluster.wait.aligned;" ::: "memory"); }
DEVINL void bar_sync(int id, int n) { asm volatile("bar.sync %0, %1;" ::"r"(id), "r"(n) : "memory"); }
DEVINL void bar_arrive(int id, int n) { asm volatile("bar.arrive %0, %1;" ::"r"(id), "r"(n) : "memory"); }
DEVINL uint32_t ld_acquire(const uint32_t* p) { uint32_t v; asm volatile("ld.acquire.gpu.global.u32 %0, [%1];" : "=r"(v) : "l"(p) : "memory"); return v; }
DEVINL void watch(const uint32_t* p, uint32_t target, uint32_t all, uint32_t tag, uint32_t slot) {
  uint32_t seen = 0;
#pragma unroll 1
  for (uint32_t n = 0; n < 200000u && seen != all; n++) {
    const uint32_t m = __ballot_sync(~0u, (int)(ld_acquire(p) - target) >= 0) & all;
    if (m != seen) { seen = m; asm volatile("st.release.cta.shared.u32 [%0], %1;" ::"r"(slot), "r"(tag << 16 | m) : "memory"); }
  }
}
template <bool RELAXED = false> DEVINL void await_bit(uint32_t slot, uint32_t tag, int j, uint32_t& rdy) {
  if ((rdy >> j) & 1) return;
#pragma unroll 1
  for (uint32_t n = 0; n < 8000000u; n++) {
    uint32_t v;
    asm volatile("ld.acquire.cta.shared.u32 %0, [%1];" : "=r"(v) : "r"(slot) : "memory");
    if ((v >> 16) == tag && ((v >> j) & 1)) { rdy = v; break; }
    if (RELAXED) __nanosleep(200);
  }
  asm volatile("fence.proxy.async.global;" ::: "memory");
}
DEVINL void poll_ge(const uint32_t* p, uint32_t target) {
#pragma unroll 1
  for (uint32_t n = 0; n < 200000u; n++) if (__all_sync(~0u, (int)(ld_acquire(p) - target) >= 0)) break;
}
DEVINL int lane_id() { int v; asm volatile("mov.u32 %0, %%laneid;" : "=r"(v)); return v; }
__host__ DEVINL int remap(int v) {
  const int c = v >> 1, u = c - 36, r = (u * 37) >> 8;
  const int L = c < 4 ? 32 + 8 * c : c < 36 ? c - 4 : 33 + u + r;
  return 2 * L + (v & 1);
}
DEVINL int block_id() { int v; asm volatile("mov.u32 %0, %%ctaid.x;" : "=r"(v)); return v; }
#define cta_id() prm.map[block_id()]
#define IDS() const int lane = lane_id(), b = cta_id(), bm = b >> 4, bn = b & 15, rank = b & 1, pm = 2 * bm + (bn >> 3), pn = bn & 7, po = pm & 1; \
  (void)lane; (void)bm; (void)bn; (void)rank; (void)pm; (void)pn; (void)po
DEVINL void st_tagged(unsigned long long* p, uint32_t v, uint32_t tag) {
  asm volatile("{\n.reg .b64 t;\nmov.b64 t, {%1, %2};\nst.relaxed.gpu.global.b64 [%0], t;\n}" ::"l"(p), "r"(v), "r"(tag) : "memory");
}
DEVINL float ex2(float x) { float y; asm("ex2.approx.ftz.f32 %0, %1;" : "=f"(y) : "f"(x)); return y; }
DEVINL float rcp(float x) { float y; asm("rcp.approx.ftz.f32 %0, %1;" : "=f"(y) : "f"(x)); return y; }
DEVINL uint32_t pack2(float lo, float hi) { uint32_t r; asm("cvt.rn.bf16x2.f32 %0, %1, %2;" : "=r"(r) : "f"(hi), "f"(lo)); return r; }
DEVINL uint32_t pack2h(float lo, float hi) { uint32_t r; asm("cvt.rn.f16x2.f32 %0, %1, %2;" : "=r"(r) : "f"(hi), "f"(lo)); return r; }
DEVINL uint32_t hadd2(uint32_t a, uint32_t b) { uint32_t r; asm("add.rn.f16x2 %0, %1, %2;" : "=r"(r) : "r"(a), "r"(b)); return r; }
DEVINL uint32_t hfma2(uint32_t a, uint32_t b, uint32_t c) { uint32_t r; asm("fma.rn.f16x2 %0, %1, %2, %3;" : "=r"(r) : "r"(a), "r"(b), "r"(c)); return r; }
DEVINL float bf_lo(uint32_t w) { return __uint_as_float(w << 16); }
DEVINL float bf_hi(uint32_t w) { return __uint_as_float(w & 0xFFFF0000u); }
DEVINL float bf_round(float x) { return bf_lo(pack2(x, 0.f)); }
DEVINL uint32_t add_bf16x2(uint32_t a, uint32_t b) { uint32_t r; asm("add.rn.bf16x2 %0, %1, %2;" : "=r"(r) : "r"(a), "r"(b)); return r; }
DEVINL void stsm4(uint32_t addr, uint32_t a, uint32_t b, uint32_t c, uint32_t d) {
  asm volatile("stmatrix.sync.aligned.m8n8.x4.shared.b16 [%0], {%1, %2, %3, %4};" ::"r"(addr), "r"(a), "r"(b), "r"(c), "r"(d) : "memory");
}
DEVINL void ldsm4(uint32_t addr, uint32_t (&r)[4]) {
  asm volatile("ldmatrix.sync.aligned.m8n8.x4.shared.b16 {%0, %1, %2, %3}, [%4];" : "=r"(r[0]), "=r"(r[1]), "=r"(r[2]), "=r"(r[3]) : "r"(addr) : "memory");
}
DEVINL void ldsm4t(uint32_t addr, uint32_t (&r)[4]) {
  asm volatile("ldmatrix.sync.aligned.m8n8.x4.trans.shared.b16 {%0, %1, %2, %3}, [%4];" : "=r"(r[0]), "=r"(r[1]), "=r"(r[2]), "=r"(r[3]) : "r"(addr) : "memory");
}
DEVINL void sts128(uint32_t addr, uint32_t a, uint32_t b, uint32_t c, uint32_t d) {
  asm volatile("st.shared.v4.b32 [%0], {%1, %2, %3, %4};" ::"r"(addr), "r"(a), "r"(b), "r"(c), "r"(d) : "memory");
}
DEVINL float2 lds64f(uint32_t addr) { float2 v; asm volatile("ld.shared.v2.f32 {%0, %1}, [%2];" : "=f"(v.x), "=f"(v.y) : "r"(addr) : "memory"); return v; }
DEVINL void mma16816(float (&d)[4], uint32_t a0, uint32_t a1, uint32_t a2, uint32_t a3, uint32_t b0, uint32_t b1) {
  asm("mma.sync.aligned.m16n8k16.row.col.f32.bf16.bf16.f32 {%0, %1, %2, %3}, {%4, %5, %6, %7}, {%8, %9}, {%0, %1, %2, %3};"
               : "+f"(d[0]), "+f"(d[1]), "+f"(d[2]), "+f"(d[3]) : "r"(a0), "r"(a1), "r"(a2), "r"(a3), "r"(b0), "r"(b1));
}
template <int N> DEVINL void fence_regs(float (&d)[N]) {
#pragma unroll
  for (int i = 0; i < N; i++) asm volatile("" : "+f"(d[i])::"memory");
}
template <int N> DEVINL void fence_regs(uint32_t (&d)[N]) {
#pragma unroll
  for (int i = 0; i < N; i++) asm volatile("" : "+r"(d[i])::"memory");
}
DEVINL void lds128(uint32_t addr, uint32_t* r) {
  asm volatile("ld.shared.v4.b32 {%0, %1, %2, %3}, [%4];" : "=r"(r[0]), "=r"(r[1]), "=r"(r[2]), "=r"(r[3]) : "r"(addr) : "memory");
}
DEVINL void sched_fence() { asm volatile("griddepcontrol.launch_dependents;" ::: "memory"); }

__device__ __align__(1024) bf16 g_xs[2048 * 1024];
__device__ __align__(1024) bf16 g_os[2048 * 1024];
__device__ __align__(1024) bf16 g_k[32 * 2048 * 32];
__device__ __align__(1024) bf16 g_v[32 * 2048 * 32];
__device__ __align__(16) uint32_t g_esc[4 * 65536 * 16];
__device__ __align__(128) float2 g_stats[8 * 2048];
__device__ __align__(16) float g_csp[2 * 16 * 8 * 192];
__device__ __align__(128) float g_kn[2 * 128 * 16];
__device__ unsigned long long g_halo[2 * 128 * 32 * 32];
__device__ __align__(128) uint32_t g_cnt[256 * 32];
__device__ uint32_t g_epoch;

DEVINL uint32_t* cnt_x(int l, int bm) { return g_cnt + (l * 8 + bm) * 32; }
DEVINL uint32_t* cnt_o(int l, int pm, int h) { return g_cnt + (32 + (l * 16 + pm) * 2 + h) * 32; }
DEVINL uint32_t* cnt_kv(int lb, int bn) { return g_cnt + (160 + lb * 16 + bn) * 32; }
DEVINL uint32_t* cnt_ad(int bn) { return g_cnt + (192 + bn) * 32; }
DEVINL uint32_t* cnt_cs(int t, int bn) { return g_cnt + (208 + t * 16 + bn) * 32; }

DEVINL int qord(int i, int l, int pn) { return l == 0 ? i : i < 4 ? ((2 * pn) ^ (i & 2)) + (i & 1) : i - 4 < 2 * (pn & 6) ? i - 4 : i; }
struct Params {
  CUtensorMap m[15];
  const bf16* x0;
  const bf16* wq[2];
  uint32_t zero;
  int map[128];
  struct { uint64_t kd, vd; } kv[17];
};
enum { M_X0A = 0, M_XSA, M_WQA, M_WQB, M_WOA, M_WOB, M_OS, M_K, M_V, M_X0R, M_XSR, M_XSO, M_OUT, M_XST, M_X0H, M_COUNT };

constexpr uint32_t QSTG = 57344;
constexpr uint32_t T0 = 65536, TSTG = 32768;
constexpr uint32_t ONES = 230400;
constexpr uint32_t PSTG = 32768, RES = 196608;
constexpr uint32_t KSC = 98304, VSC = 133120;
constexpr uint32_t ROWST = 229376, COLS = 231424, BARS = 232192, SMEM_BYTES = 232448;
constexpr uint32_t B_QF = BARS, B_QE = BARS + 32, B_TF = BARS + 64, B_TE = BARS + 96, B_PF = BARS + 128, B_PE = BARS + 176,
                   B_RF = BARS + 224, W_X = BARS + 232, W_O = BARS + 236, B_QL = BARS + 240, B_PA = BARS + 248;
enum { NB_ST = 1, NB_KV = 2  , NB_DONE = 3, NB_SC = 4, NB_SIG = 5  , NB_KN = 9  , NB_X = 11, NB_HALO = 12  , NB_X0 = 15 };

DEVINL uint32_t pslot_b(uint32_t s) { return ((0x320415u >> (4 * s)) & 7) * 16384u; }
DEVINL uint32_t pslot_a(uint32_t s, int l) { return 98304u + ((((l & 1) ? 0x541230u : 0x041235u) >> (4 * s)) & 7) * 16384u; }

constexpr float QSCALE = 0.17677669529663687f * 1.4426950408889634f;
#define JLAG 4
constexpr uint32_t QPARK = 32768;

DEVINL uint32_t exp2_pair(float s0, float s1, uint32_t half, uint32_t lsb) {
  constexpr float M = 383.f - 0.591914f + 0.00390625f;
  const uint32_t B = __byte_perm(__float_as_uint(s0 + M), __float_as_uint(s1 + M), 0x6521);
  uint32_t w, E, r;
  asm("lop3.b32 %0, %1, 0x807F807F, %2, 0xEA;" : "=r"(w) : "r"(B), "r"(half));
  asm("lop3.b32 %0, %1, 0x7F807F80, %2, 0xEA;" : "=r"(E) : "r"(B), "r"(lsb));
  asm("fma.rn.bf16x2 %0, %1, %2, %3;" : "=r"(r) : "r"(B), "r"(w), "r"(E));
  return r;
}
DEVINL uint32_t exp2_h2(uint32_t s, uint32_t nsig) {
  uint32_t r = hadd2(s, 0x65F565F5u), d;
  asm("{.reg .b64 t; cvt.u64.u32 t, %0; cvt.u32.u64 %0, t;}" : "+r"(r));
  const uint32_t w = hfma2(s, 0x38A038A0u, hfma2(r, nsig, 0x62E562E5u));
  const uint32_t m = hfma2(w, w, 0x48244833u);
  asm("{.reg .b32 t; shf.l.clamp.b32 t, %2, %1, 7; add.u32 %0, t, %2;}" : "=r"(d) : "r"(r), "r"(m));
  return d;
}
DEVINL uint32_t unesc(uint32_t u, const uint32_t* esc) {
  if ((u & 0x7C00u) == 0x7C00u || (u & 0x7C000000u) == 0x7C000000u) return __ldcg(esc);
  float lo, hi;
  asm("{.reg .f16 a, b; mov.b32 {a, b}, %2; cvt.f32.f16 %0, a; cvt.f32.f16 %1, b;}" : "=f"(lo), "=f"(hi) : "r"(u));
  return pack2(lo, hi);
}

DEVINL void attn_slow(const uint32_t (&q)[8], int head, const uint32_t* kesc, float (&res)[20], int lane) {
  const int g = lane >> 2, qd = lane & 3;
  const bf16* kb = g_k + (size_t)head * 2048 * 32;
  const bf16* vb = g_v + (size_t)head * 2048 * 32;
  float o[4][4], m0 = -INFINITY, m1 = -INFINITY, l0 = 0.f, l1 = 0.f;
#pragma unroll
  for (int j = 0; j < 4; j++) { o[j][0] = o[j][1] = o[j][2] = o[j][3] = 0.f; }
#pragma unroll 1
  for (int k0 = 0; k0 < 2048; k0 += 16) {
    float s[2][4];
#pragma unroll
    for (int nt = 0; nt < 2; nt++) {
      s[nt][0] = s[nt][1] = s[nt][2] = s[nt][3] = 0.f;
      const uint32_t* kp = (const uint32_t*)(kb + (size_t)(k0 + nt * 8 + g) * 32) + qd;
      const uint32_t* ke = kesc + (k0 + nt * 8 + g) * 16 + qd;
      const uint32_t k0r = unesc(__ldcg(kp), ke), k1r = unesc(__ldcg(kp + 4), ke + 4), k2r = unesc(__ldcg(kp + 8), ke + 8), k3r = unesc(__ldcg(kp + 12), ke + 12);
      __syncwarp();
      mma16816(s[nt], q[0], q[1], q[2], q[3], k0r, k1r);
      mma16816(s[nt], q[4], q[5], q[6], q[7], k2r, k3r);
    }
    float a0 = fmaxf(fmaxf(s[0][0], s[0][1]), fmaxf(s[1][0], s[1][1]));
    float a1 = fmaxf(fmaxf(s[0][2], s[0][3]), fmaxf(s[1][2], s[1][3]));
    a0 = fmaxf(a0, __shfl_xor_sync(~0u, a0, 1)); a0 = fmaxf(a0, __shfl_xor_sync(~0u, a0, 2));
    a1 = fmaxf(a1, __shfl_xor_sync(~0u, a1, 1)); a1 = fmaxf(a1, __shfl_xor_sync(~0u, a1, 2));
    const float n0 = fmaxf(m0, a0), n1 = fmaxf(m1, a1);
    const float c0 = (m0 == n0) ? 1.f : ex2(m0 - n0), c1 = (m1 == n1) ? 1.f : ex2(m1 - n1);
    m0 = n0; m1 = n1;
    const uint32_t p0 = pack2(ex2(s[0][0] - n0), ex2(s[0][1] - n0)), p1 = pack2(ex2(s[0][2] - n1), ex2(s[0][3] - n1));
    const uint32_t p2 = pack2(ex2(s[1][0] - n0), ex2(s[1][1] - n0)), p3 = pack2(ex2(s[1][2] - n1), ex2(s[1][3] - n1));
    l0 = l0 * c0 + bf_lo(p0) + bf_hi(p0) + bf_lo(p2) + bf_hi(p2);
    l1 = l1 * c1 + bf_lo(p1) + bf_hi(p1) + bf_lo(p3) + bf_hi(p3);
#pragma unroll
    for (int j = 0; j < 4; j++) {
      o[j][0] *= c0; o[j][1] *= c0; o[j][2] *= c1; o[j][3] *= c1;
      const unsigned short* vp = (const unsigned short*)(vb + (size_t)(k0 + 2 * qd) * 32 + j * 8 + g);
      const uint32_t b0 = (uint32_t)__ldcg(vp) | ((uint32_t)__ldcg(vp + 32) << 16);
      const uint32_t b1 = (uint32_t)__ldcg(vp + 256) | ((uint32_t)__ldcg(vp + 288) << 16);
      mma16816(o[j], p0, p1, p2, p3, b0, b1);
    }
  }
  l0 += __shfl_xor_sync(~0u, l0, 1); l0 += __shfl_xor_sync(~0u, l0, 2);
  l1 += __shfl_xor_sync(~0u, l1, 1); l1 += __shfl_xor_sync(~0u, l1, 2);
#pragma unroll
  for (int j = 0; j < 4; j++) { res[4 * j] = o[j][0]; res[4 * j + 1] = o[j][1]; res[4 * j + 2] = o[j][2]; res[4 * j + 3] = o[j][3]; }
  res[16] = l0; res[18] = l1;
}

__global__ void __cluster_dims__(2, 1, 1) __launch_bounds__(384, 1) fused_kernel(const __grid_constant__ Params prm) {
  extern __shared__ __align__(1024) char smem[];
  const uint32_t sb = (uint32_t)__cvta_generic_to_shared(smem);
  const int tid = threadIdx.x, lane = tid & 31;
  const int wg = __shfl_sync(0xffffffffu, tid >> 7, 0);
  const int w = __shfl_sync(0xffffffffu, (tid >> 5) & 3, 0);
  const int bm = remap(blockIdx.x) >> 4, bn = remap(blockIdx.x) & 15;

  auto first_tile = [&](int kt) {
    e_expect_tx(sb + B_QF + 8 * kt, QSTG);
    tma_ld(sb + kt * QSTG, &prm.m[M_X0A], kt * 64, bm * 256, sb + B_QF + 8 * kt);
    tma_ld3(sb + kt * QSTG + 32768, &prm.m[M_WQA], bn * 64, kt * 64, 0, sb + B_QF + 8 * kt);
  };
  auto init4 = [&](uint32_t bar, uint32_t c0, uint32_t c1, uint32_t c2, uint32_t c3) {
    asm volatile("{\n.reg .pred pe;\nelect.sync _|pe, 0xffffffff;\n@pe mbarrier.init.shared::cta.b64 [%0], %1;\n@pe mbarrier.init.shared::cta.b64 [%0+8], %2;\n"
                 "@pe mbarrier.init.shared::cta.b64 [%0+16], %3;\n@pe mbarrier.init.shared::cta.b64 [%0+24], %4;\n@pe fence.mbarrier_init.release.cluster;\n}"
                 ::"r"(bar), "r"(c0), "r"(c1), "r"(c2), "r"(c3) : "memory");
  };
  if (wg < 2) {
    const uint32_t k = wg * 4 + w, lo = (0x1411214u >> (4 * k)) & 7, hi = (0x1441214u >> (4 * k)) & 7;
    if (tid < 32) asm volatile("prefetch.global.L2 [%0];" ::"l"(prm.x0 + (size_t)(bm * 256 + bn * 16 + (tid & 15)) * 1024 + (tid >> 4) * 64));
    else if (tid < 80) asm volatile("prefetch.global.L2 [%0];" ::"l"(prm.wq[0] + (bm * 16 + (tid & 15)) * 3072 + ((tid >> 4) - 2) * 1024 + bn * 64));
    __syncwarp();
    if (k < 7) init4(sb + B_QE + 32 * k, lo, lo, hi, k == 6 ? 2 : hi);
    __syncwarp();
    if (k == 6 && lane == 0) *(volatile unsigned long long*)(smem + W_X) = 0ull;
  } else if (w == 0) {
    init4(sb + B_QF, 1, 1, 1, 1);
    __syncwarp();
    first_tile(0);
  } else if (lane < 5) {
    asm volatile("prefetch.tensormap [%0];" ::"l"(&prm.m[5 * (w - 1) + lane]) : "memory");
  }
  __syncthreads();
  asm volatile("barrier.cluster.arrive.relaxed.aligned;" ::: "memory");

  if (wg == 2) {
    asm volatile("setmaxnreg.dec.sync.aligned.u32 56;");
    const uint32_t ep1 = *(volatile uint32_t*)&g_epoch + 1;
    if (w == 0) {
      first_tile(1);
      mbar_wait(sb + B_QF, 0);
      first_tile(2); first_tile(3);
#pragma unroll 1
      for (int kt = 4; kt < 16; kt++) l2_prefetch(prm.wq[0] + kt * 196608 + blockIdx.x * 1536, 3072);
      cluster_wait();
#pragma unroll 1
      for (int l = 0; l < 4; l++) {
        IDS();
        const CUtensorMap* mw = &prm.m[M_WQA + (l & 1)];
        const CUtensorMap* mx = &prm.m[l == 0 ? M_X0A : M_XSA];
        const CUtensorMap* mh = &prm.m[l == 0 ? M_X0H : M_XSO];
        const CUtensorMap* mo = &prm.m[M_WOA + (l & 1)];
        auto q_b = [&](int i) {
          const int s = i & 3;
          mbar_wait(sb + B_QE + 8 * s, ((i >> 2) & 1) ^ 1);
          e_expect_tx(sb + B_QF + 8 * s, QSTG);
          tma_ld3(sb + s * QSTG + 32768, mw, bn * 64, qord(i, l, pn) * 64, 0, sb + B_QF + 8 * s);
        };
        uint32_t rdy = l ? 0u : ~0u;
        auto q_a = [&](int i) {
          const int kt = qord(i, l, pn);
          await_bit(sb + W_X, l, kt >> 1, rdy);
          if (i < 4) tma_ld(sb + i * QSTG, mx, kt * 64, bm * 256, sb + B_QF + 8 * i);
          else tma_ld_mc(sb + (i & 3) * QSTG + rank * 16384, mh, kt * 64, bm * 256 + rank * 128, sb + B_QF + 8 * (i & 3));
        };
        if (l > 0) {
          await_bit(sb + W_X, l, pn, rdy);
#pragma unroll 1
          for (int i = 0; i < 2; i++) {
            e_expect_tx(sb + B_QF + 8 * i, 16384);
            tma_ld(sb + i * QSTG + (po ^ 1) * 16384, &prm.m[M_XSO], (2 * pn + i) * 64, (pm ^ 1) * 128, sb + B_QF + 8 * i);
          }
          mbar_wait(sb + B_QF, 0);
          q_a(2);
          mbar_wait(sb + B_QF + 8, 0);
        }
#pragma unroll 1
        for (int i = l ? 3 : 4; i < 16; i++) {
          q_b(i); q_a(i);
        }
        if (l & 1) {
          if (l == 3) poll_ge(cnt_ad(bn), ep1 * 16);
          bar_sync(NB_KV, 288);
          sts128(sb + ONES + lane * 32, 0x3f803f80u, 0x3f803f80u, 0x3f803f80u, 0x3f803f80u);
          sts128(sb + ONES + lane * 32 + 16, 0x3f803f80u, 0x3f803f80u, 0x3f803f80u, 0x3f803f80u);
          fence_async_smem();
          __syncwarp();
          e_arrive(sb + B_TF);
          const int krow = 2 * bn * 2048 + bm * 256;
          uint32_t* kvc = cnt_kv(l >> 1, bn);
          tma_st(&prm.m[M_K], 0, krow, sb + T0);
          tma_st(&prm.m[M_V], 0, krow, sb + T0 + 16384);
          bulk_commit(); bulk_wait_n<0>();
          e_red(kvc + bm);
          uint32_t seen = 0;
#pragma unroll 1
          for (int it = 1; it < 16; it++) {
            const int s = it & 3, blk = it;
            if (it == 4) {
              bar_sync(NB_KV + 12, 288);
              mbar_wait(sb + B_TF + 24, 0);
              tma_st(&prm.m[M_K], 0, krow + 2048, sb);
              tma_st(&prm.m[M_V], 0, krow + 2048, sb + 16384);
              bulk_commit();
            }
            if (it == 5) { bulk_wait_n<0>(); e_red(kvc + bm); }
            if (it == 12) { e_expect_tx(sb + B_RF, 32768); tma_ld3(sb + RES, &prm.m[M_XSR], 0, pm * 128, 2 * pn, sb + B_RF); }
            if (it == 2 || it == 3) mbar_wait(sb + B_TF + 8 * (it - 1), 0);
            mbar_wait(sb + B_TE + 8 * s, ((it >> 2) & 1) ^ 1);
            if (it < 8) {
#pragma unroll 1
              for (uint32_t n = 0; n < 200000u && !((seen >> it) & 1); n++)
                seen = __ballot_sync(~0u, (int)(ld_acquire(kvc + ((bm + lane) & 7)) - (ep1 * 2 - 1)) >= 0);
              fence_async_gl();
            } else if (it == 8) { poll_ge(kvc + (lane & 7), ep1 * 2); fence_async_gl(); }
            const int row = (2 * bn + (it >> 3)) * 2048 + ((bm + blk) & 7) * 256;
            e_expect_tx(sb + B_TF + 8 * s, 32768);
            tma_ld(sb + T0 + s * TSTG, &prm.m[M_K], 0, row, sb + B_TF + 8 * s);
            tma_ld(sb + T0 + s * TSTG + 16384, &prm.m[M_V], 0, row, sb + B_TF + 8 * s);
          }
        }
        auto p_b = [&](int i, uint32_t s, uint32_t par) {
          mbar_wait(sb + B_PE + 8 * s, par ^ 1);
          e_expect_tx(sb + B_PF + 8 * s, PSTG);
          tma_ld5(sb + pslot_b(s), mo, i >> 3, 2 * (i & 7), 2 * pn, sb + B_PF + 8 * s);
        };
        auto p_a = [&](int i, uint32_t s) {
          await_bit(sb + W_O, l + 1, i, rdy);
          tma_ld_mc(sb + pslot_a(s, l) + rank * 8192, &prm.m[M_OS], i * 64, pm * 128 + rank * 64, sb + B_PF + 8 * s);
        };
        auto p_a2 = [&](int i) {
          await_bit(sb + W_O, l + 1, i, rdy);
          tma_ld(sb + pslot_a(i, l), &prm.m[M_OS], i * 64, pm * 128, sb + B_PF + 8 * i);
          tma_ld(sb + pslot_a(i, l) + 8192, &prm.m[M_OS], i * 64, pm * 128 + 64, sb + B_PF + 8 * i);
        };
        rdy = 0;
        if (l & 1) {
#pragma unroll 1
          for (int u = 0; u < 6; u++) { const int i = (0x205413 >> (4 * u)) & 7; if (u == 4) mbar_wait(sb + B_TE, 1); p_b(i, i, i < 4 ? 1 : 0); }
#pragma unroll 1
          for (int u = 0; u < 6; u++) {
            const int i = (0x542130 >> (4 * u)) & 7;
            if (!(u & 1)) mbar_wait(sb + B_TE + 8 + 4 * u, 1);
            p_a2(i);
          }
        } else {
#pragma unroll 1
          for (int u = 0; u < 6; u++) { const int i = (0x025413 >> (4 * u)) & 7; if (u == 0 || u == 3) mbar_wait(sb + B_QE + 8 * (u / 3), 1); p_b(i, i, 0); }
          mbar_wait(sb + B_QE + 24, 1);
          e_expect_tx(sb + B_RF, 32768);
          tma_ld3(sb + RES, &prm.m[l == 0 ? M_X0R : M_XSR], 0, pm * 128, 2 * pn, sb + B_RF);
          p_a2(0);
          bar_sync(NB_DONE, 96);
          e_arrive_both(sb + B_PA);
          p_a2(1); p_a2(2);
          mbar_wait(sb + B_PA, (l >> 1) & 1);
#pragma unroll 1
          for (int i = 3; i < 6; i++) { if (i == 4) mbar_wait(sb + B_PF + 8, 0); p_a(i, i); }
        }
        uint32_t s = 0, lap = 1;
#pragma unroll 1
        for (int i = 6; i < 16; i++) {
          p_b(i, s, ((s < 4 ? l : 0) + lap) & 1);
          p_a(i, s);
          if (++s == 6) { s = 0; lap++; }
        }
        const CUtensorMap* mn = &prm.m[M_WQA + ((l + 1) & 1)];
        if (l < 3) {
          mbar_wait(sb + B_PE + 8 * 4, 1); mbar_wait(sb + B_PE + 8 * 5, 1);
          tma_ld3(sb + 32768, mn, bn * 64, 2 * pn * 64, 0, sb + B_QL);
          mbar_wait(sb + B_PE + 8 * 0, l & 1);
          tma_ld3(sb + QSTG + 32768, mn, bn * 64, (2 * pn + 1) * 64, 0, sb + B_QL);
          mbar_wait(sb + B_PE + 8 * 1, l & 1);
          e_expect_tx(sb + B_QF + 16, QSTG);
          tma_ld3(sb + 2 * QSTG + 32768, mn, bn * 64, ((2 * pn) ^ 2) * 64, 0, sb + B_QF + 16);
        }
        if (l < 3) { bar_sync(NB_X, 288); e_expect_tx(sb + B_QL, 49152); }
      }
      if (blockIdx.x == 0 && lane_id() == 0) *(volatile uint32_t*)&g_epoch = ep1;
    } else {
      const int hw = w - 1;
      cluster_wait();
      mbar_wait(sb + B_QF, 0);
#pragma unroll 1
      for (int l = 0; l < 4; l++) {
        IDS();
        if (hw == 2 && l > 0) watch(cnt_x(l, bm) + (lane & 7), ep1 * 2, 0xFFu, l, sb + W_X);
        if (l == 0) {
#pragma unroll 1
          for (int r = 2 * hw; r < 16; r += 6) {
            const uint4* p = (const uint4*)(prm.x0 + (size_t)(b * 16 + r) * 1024) + lane;
            float s1[2] = {0.f, 0.f}, s2[2] = {0.f, 0.f};
#pragma unroll
            for (int i = 0; i < 8; i++) {
              const uint4 v = __ldg(p + 32 * i);
              const uint32_t u[4] = {v.x, v.y, v.z, v.w};
#pragma unroll
              for (int k = 0; k < 4; k++) { const float a = bf_lo(u[k]), c = bf_hi(u[k]); s1[i >> 2] += a + c; s2[i >> 2] = fmaf(a, a, fmaf(c, c, s2[i >> 2])); }
            }
#pragma unroll
            for (int o = 16; o; o >>= 1)
#pragma unroll
              for (int rr = 0; rr < 2; rr++) { s1[rr] += __shfl_xor_sync(~0u, s1[rr], o); s2[rr] += __shfl_xor_sync(~0u, s2[rr], o); }
            if (lane == 0) *(float4*)&g_stats[b * 16 + r] = make_float4(s1[0], s2[0], s1[1], s2[1]);
          }
        }
        if (l == 1) { uint32_t rdy = 0; await_bit<true>(sb + W_X, 1, pn, rdy); mbar_hint(sb + B_QF + 8, 0); }
        if (l < 2) {
          float cs[8];
#pragma unroll
          for (int i = 0; i < 8; i++) cs[i] = 0.f;
          const uint4* wp = (const uint4*)(prm.wq[l] + (size_t)(bm * 128 + (lane >> 3)) * 3072 + hw * 1024 + bn * 64) + (lane & 7);
#pragma unroll 8
          for (int i = 0; i < 32; i++) {
            const uint4 v = __ldg(wp + (size_t)i * 4 * 384);
            cs[0] += bf_lo(v.x); cs[1] += bf_hi(v.x); cs[2] += bf_lo(v.y); cs[3] += bf_hi(v.y);
            cs[4] += bf_lo(v.z); cs[5] += bf_hi(v.z); cs[6] += bf_lo(v.w); cs[7] += bf_hi(v.w);
          }
#pragma unroll
          for (int i = 0; i < 8; i++) { cs[i] += __shfl_xor_sync(~0u, cs[i], 8); cs[i] += __shfl_xor_sync(~0u, cs[i], 16); }
          if (lane < 8) {
            float4* d = (float4*)(g_csp + ((l * 16 + bn) * 8 + bm) * 192 + hw * 64 + lane * 8);
            d[0] = make_float4(cs[0], cs[1], cs[2], cs[3]); d[1] = make_float4(cs[4], cs[5], cs[6], cs[7]);
          }
          __syncwarp();
          asm volatile("fence.acq_rel.gpu;" ::: "memory");
          e_red_relaxed(cnt_cs(l, bn));
          if (l == 0) e_red_relaxed(cnt_x(0, bm) + pn);
          poll_ge(lane < 8 && l == 0 ? cnt_x(0, bm) + lane : cnt_cs(l, bn), ep1 * (lane < 8 && l == 0 ? 6 : 24));
        }
        if (l > 0) {
          uint32_t rdy = 0;
#pragma unroll 1
          for (int j = 0; j < 8; j++) await_bit<true>(sb + W_X, l, j, rdy);
        }
#pragma unroll 1
        for (int it = hw * 32 + lane; it < 176; it += 96) {
          const bool rows = it < 128;
          const float4* p = rows ? (const float4*)(g_stats + bm * 256) + it : (const float4*)(g_csp + ((l & 1) * 16 + bn) * 8 * 192) + (it - 128);
          const int stride = rows ? 1024 : 48, np = rows && l == 0 ? 1 : 8;
          float4 a = make_float4(0.f, 0.f, 0.f, 0.f);
#pragma unroll
          for (int k = 0; k < 8; k++) if (k < np) { const float4 v = __ldcg(p + k * stride); a.x += v.x; a.y += v.y; a.z += v.z; a.w += v.w; }
          if (rows) {
            const float m0 = a.x * (1.f / 1024.f), m1 = a.z * (1.f / 1024.f);
            const float v0 = fmaxf(a.y * (1.f / 1024.f) - m0 * m0, 0.f), v1 = fmaxf(a.w * (1.f / 1024.f) - m1 * m1, 0.f);
            const float r0 = __fdividef(1.f, bf_round(sqrtf(bf_round(bf_round(v0) + 1e-5f)))), r1 = __fdividef(1.f, bf_round(sqrtf(bf_round(bf_round(v1) + 1e-5f))));
            a = make_float4(r0, -bf_round(m0) * r0, r1, -bf_round(m1) * r1);
          }
          *(float4*)(smem + ROWST + it * 16) = a;
        }
        __syncwarp();
        if (lane == 0) asm volatile("red.release.cta.shared.add.u32 [%0], 0x100;" ::"r"(sb + W_X) : "memory");
        if (hw == 2) {
          if (!(l & 1)) {
            bar_sync(NB_ST, 288);
            const volatile unsigned long long* hp = g_halo + ((size_t)(l >> 1) * 128 + b - 16) * 1024 + lane;
#pragma unroll 1
            for (int h = 0; h < 2; h++) {
              uint32_t t[16];
#pragma unroll
              for (int i = 0; i < 16; i++) t[i] = 0;
#pragma unroll 1
              for (uint32_t n = bm ? 0 : 100000u; n < 100000u; n++) {
                uint32_t miss = 0;
#pragma unroll
                for (int i = 0; i < 16; i++) {
                  const unsigned long long v = hp[h * 512 + i * 32];
                  t[i] = (uint32_t)v; miss |= (uint32_t)(v >> 32) ^ ep1;
                }
                if (__all_sync(~0u, !miss)) break;
              }
              mbar_wait(sb + B_QE + 24, 1);
              const uint32_t r = (lane & 7) + ((lane >> 3) & 1) * 8, rv = lane >> 2;
#pragma unroll
              for (int jj = 0; jj < 2; jj++) stsm4(sb + KSC + r * 128 + (((4 * h + 2 * jj + (lane >> 4)) ^ (r & 7)) << 4), t[4 * jj], t[4 * jj + 1], t[4 * jj + 2], t[4 * jj + 3]);
              const uint32_t ad = sb + VSC + rv * 128 + (((4 * h + (lane & 3)) ^ (rv & 7)) << 4);
              sts128(ad, t[8], t[10], t[12], t[14]); sts128(ad + 1024, t[9], t[11], t[13], t[15]);
              bar_arrive(NB_HALO + h, 64);
            }
          } else {
            mbar_wait(sb + B_TF + 16, 0); mbar_wait(sb + B_TF + 16, 1);
            poll_ge(cnt_kv(l >> 1, bn) + (lane & 7), ep1 * 2);
            const uint4 v = __ldcg((const uint4*)(g_kn + ((l >> 1) * 128 + bn * 8) * 16) + lane);
            const uint32_t mx = max(max(v.x, v.y), max(v.z, v.w));
            const uint32_t m0 = __reduce_max_sync(~0u, (lane & 2) ? 0u : mx), m1 = __reduce_max_sync(~0u, (lane & 2) ? mx : 0u);
            if (lane == 0) *(uint2*)(smem + ROWST) = make_uint2(m0, m1);
            __syncwarp();
            bar_arrive(NB_KN, 160); bar_arrive(NB_KN + 1, 160);
            mbar_wait(sb + B_TF + 16, 0); mbar_wait(sb + B_TF + 16, 1);
          }
        } else {
#pragma unroll 1
          for (int h = 0; h < 2; h++) {
            bar_sync(NB_SIG + 2 * h + hw, 160);
            if (h == 1 && !(l & 1)) bar_arrive(NB_DONE, 96);
            e_red(cnt_o(l, 2 * bm + hw, h) + (bn >> 1));
            if (h == 1 && l == 1) e_red(cnt_ad(bn));
          }
        }
        if (hw == 2) watch(cnt_o(l, pm, (lane >> 3) & 1) + (lane & 7), ep1 * 2, 0xFFFFu, l + 1, sb + W_O);
        if (hw == 0 && l < 3) {
          bar_sync(NB_X0, 288);
          e_red(cnt_x(l + 1, bm) + pn);
        }
      }
    }
  } else {
    asm volatile("setmaxnreg.inc.sync.aligned.u32 224;");
    const uint32_t zero = prm.zero;
    cluster_wait();
#pragma unroll 1
    for (int l = 0; l < 4; l++) {
      {
        float acc[2][96];
#pragma unroll
        for (int i = 0; i < 96; i++) { acc[0][i] = 0.f; acc[1][i] = 0.f; }
        fence_regs(acc[0]); fence_regs(acc[1]);
        const bool early = l > 0 && wg == ((cta_id() >> 3) & 1);
        uint32_t ep1 = 0;
#pragma unroll 1
        for (int kt = 0; kt < 16; kt++) {
          const int s = kt & 3;
          if (l > 0 && kt == 0) mbar_wait(sb + B_QL, (l + 1) & 1);
          if (!(early && kt < 2)) mbar_wait(sb + B_QF + 8 * s, (kt >> 2) & 1);
          const uint64_t da = mkdesc(sb + s * QSTG + wg * 16384, 16, 1024, 1), db = mkdesc(sb + s * QSTG + 32768, 8192, 1024, 1);
          wg_fence();
#pragma unroll
          for (int k = 0; k < 4; k++)
#pragma unroll
            for (int m = 0; m < 2; m++) wgmma_m64n192k16_ss_tb(acc[m], da + m * 512 + k * 2, db + k * 128, 1);
          wg_commit();
          if (kt == 15 && !(l & 1)) bar_arrive(NB_ST, 288);
          if (kt == 4) ep1 = *(volatile uint32_t*)&g_epoch + 1;
          wg_wait<1>();
          if (early && (kt == 1 || kt == 2)) mbar_wait(sb + B_QF + 8 * (kt - 1), 0);
          if (kt > 0 && w == 0) e_arrive_both(sb + B_QE + 8 * ((kt - 1) & 3));
        }
#pragma unroll 1
        for (uint32_t n = 0; n < 4000000u; n++) {
          uint32_t v;
          asm volatile("ld.acquire.cta.shared.u32 %0, [%1];" : "=r"(v) : "r"(sb + W_X) : "memory");
          if ((v >> 8) == (uint32_t)(l * 256 + 3)) break;
        }
        IDS();
        const int g = lane >> 2, qd = lane & 3;
        float2 st[2][2];
#pragma unroll
        for (int m = 0; m < 2; m++)
#pragma unroll
          for (int hh = 0; hh < 2; hh++) st[m][hh] = lds64f(sb + ROWST + (wg * 128 + m * 64 + w * 16 + g + 8 * hh) * 8);
        float2 cs[4];
        auto load_cs = [&](int gi) {
#pragma unroll
          for (int j = 0; j < 4; j++) cs[j] = lds64f(sb + COLS + (gi * 32 + j * 8 + 2 * qd) * 4);
        };
        load_cs(2);
        wg_wait<0>();
        fence_regs(acc[0]); fence_regs(acc[1]);
        if (w == 0) e_arrive_both(sb + B_QE + 8 * 3);
        auto norm_tile = [&](int gi, int m, float sc, uint32_t (&t)[8], float (&nrm)[2], bool h16 = false) {
          const float r0 = st[m][0].x * sc, s0 = st[m][0].y * sc, r1 = st[m][1].x * sc, s1 = st[m][1].y * sc;
          float n0 = 0.f, n1 = 0.f;
#pragma unroll
          for (int j = 0; j < 4; j++) {
            const float* a = &acc[m][16 * gi + 4 * j];
            const float v0 = fmaf(a[0], r0, s0 * cs[j].x), v1 = fmaf(a[1], r0, s0 * cs[j].y);
            const float v2 = fmaf(a[2], r1, s1 * cs[j].x), v3 = fmaf(a[3], r1, s1 * cs[j].y);
            n0 = fmaf(v0, v0, fmaf(v1, v1, n0)); n1 = fmaf(v2, v2, fmaf(v3, v3, n1));
            t[2 * j] = h16 ? pack2h(v0, v1) : pack2(v0, v1); t[2 * j + 1] = h16 ? pack2h(v2, v3) : pack2(v2, v3);
          }
          nrm[0] = n0; nrm[1] = n1;
        };
        auto norm_group = [&](int gi, float sc, uint32_t (&t)[2][8], float (&nrm)[2][2]) { norm_tile(gi, 0, sc, t[0], nrm[0]); norm_tile(gi, 1, sc, t[1], nrm[1]); };
        uint32_t q[2][2][8];
        const uint32_t srow = (lane & 7) + ((lane >> 3) & 1) * 8;
        const uint32_t row0 = wg * 128 + w * 16;
        auto put_o = [&](int h, int m, const float (&o)[16], float i0, float i1) {
          IDS();
          bf16* op = g_os + (size_t)(bm * 256 + row0 + m * 64 + (lane >> 2)) * 1024 + h * 512 + bn * 32 + (lane & 3) * 8;
          *(uint4*)op = make_uint4(pack2(o[0] * i0, o[1] * i0), pack2(o[4] * i0, o[5] * i0), pack2(o[8] * i0, o[9] * i0), pack2(o[12] * i0, o[13] * i0));
          *(uint4*)(op + 8 * 1024) = make_uint4(pack2(o[2] * i1, o[3] * i1), pack2(o[6] * i1, o[7] * i1), pack2(o[10] * i1, o[11] * i1), pack2(o[14] * i1, o[15] * i1));
        };
        if (!(l & 1)) {
          auto put_kv = [&](int gi, uint32_t r0, const uint32_t (&t)[8]) {
            if (gi < 4) {
              const uint32_t r = r0 + srow;
#pragma unroll
              for (int jj = 0; jj < 2; jj++) stsm4(sb + KSC + r * 128 + (((4 * (gi - 2) + 2 * jj + (lane >> 4)) ^ (r & 7)) << 4), t[4 * jj], t[4 * jj + 1], t[4 * jj + 2], t[4 * jj + 3]);
            } else {
              const uint32_t r = r0 + g, ad = sb + VSC + r * 128 + (((4 * (gi - 4) + qd) ^ (r & 7)) << 4);
              sts128(ad, t[0], t[2], t[4], t[6]); sts128(ad + 1024, t[1], t[3], t[5], t[7]);
            }
          };
          const bool send = wg == 1 && w == 3 && bm < 7;
          unsigned long long* hp = g_halo + ((size_t)(l >> 1) * 128 + b) * 1024 + lane;
          uint32_t t[4][2][8];
#pragma unroll
          for (int mm = 0; mm < 2; mm++)
#pragma unroll
            for (int u = 0; u < 4; u++) {
              float nrm[2];
              norm_tile(2 + (u >> 1) + 2 * (u & 1), 1 - mm, 1.f, t[u][1 - mm], nrm);
              load_cs(u == 0 ? 4 : u == 1 ? 3 : u == 2 ? 5 : mm == 0 ? 2 : 0);
              if (mm == 0 && send) {
#pragma unroll
                for (int i = 0; i < 8; i++) st_tagged(hp + (u * 8 + i) * 32, t[u][1][i], ep1);
              }
            }
          mbar_wait(sb + B_QE + 24, 1);
#pragma unroll
          for (int u = 0; u < 4; u++) { put_kv(2 + (u >> 1) + 2 * (u & 1), 16 + row0, t[u][0]); put_kv(2 + (u >> 1) + 2 * (u & 1), 16 + row0 + 64, t[u][1]); }
          { float nrm[2][2]; norm_group(0, 1.f, q[0], nrm); }
          bar_sync(NB_SC, 256);
          const bool e = g & 1, sel = 2 * qd + (g & 1) >= g + 2, first = bm == 0 && row0 == 0;
#pragma unroll 1
          for (int h = 0; h < 2; h++) {
            if (row0 == 0) bar_sync(NB_HALO + h, 64);
            float s[2][4][4];
            uint32_t vf[2][4][4], pf[2][2][4];
#pragma unroll
            for (int m = 0; m < 2; m++)
#pragma unroll
              for (int nt = 0; nt < 4; nt++) {
                uint32_t kf[4];
                const uint32_t r = row0 + m * 64 + 8 * nt + (lane & 7), ch = 4 * h + (lane >> 3);
                ldsm4(sb + KSC + r * 128 + ((ch ^ (r & 7)) << 4), kf);
                s[m][nt][0] = s[m][nt][1] = s[m][nt][2] = s[m][nt][3] = 0.f;
                mma16816(s[m][nt], q[0][m][0], q[0][m][1], q[0][m][2], q[0][m][3], kf[0], kf[1]);
                mma16816(s[m][nt], q[0][m][4], q[0][m][5], q[0][m][6], q[0][m][7], kf[2], kf[3]);
              }
#pragma unroll
            for (int m = 0; m < 2; m++)
#pragma unroll
              for (int i = 0; i < 4; i++) {
                const uint32_t r = row0 + m * 64 + 16 * (i >> 1) + srow, ch = 4 * h + 2 * (i & 1) + (lane >> 4);
                ldsm4t(sb + VSC + r * 128 + ((ch ^ (r & 7)) << 4), vf[m][i]);
              }
            float va[4], vb[4], mx[4];
#pragma unroll
            for (int i = 0; i < 4; i++) {
              const int m = i >> 1, hh = i & 1;
              const float a = e ? s[m][hh + 1][2 * hh + 1] : s[m][hh + 1][2 * hh];
              const float lo = e ? s[m][hh][2 * hh + 1] : s[m][hh][2 * hh], hi = e ? s[m][hh + 2][2 * hh + 1] : s[m][hh + 2][2 * hh];
              const uint32_t t = pack2(a, sel ? lo : hi);
              const uint32_t u = pack2(bf_lo(t) * 0.17677669529663687f, bf_hi(t) * 0.17677669529663687f);
              va[i] = (m == 0 && hh == 0 && first) ? -INFINITY : bf_lo(u);
              vb[i] = (m == 0 && first && sel) ? -INFINITY : bf_hi(u);
              mx[i] = fmaxf(va[i], vb[i]);
            }
#pragma unroll
            for (int i = 0; i < 4; i++) mx[i] = fmaxf(mx[i], __shfl_xor_sync(~0u, mx[i], 1));
#pragma unroll
            for (int i = 0; i < 4; i++) mx[i] = fmaxf(mx[i], __shfl_xor_sync(~0u, mx[i], 2));
#pragma unroll
            for (int i = 0; i < 4; i++) {
              va[i] = ex2((va[i] - mx[i]) * 1.4426950408889634f); vb[i] = ex2((vb[i] - mx[i]) * 1.4426950408889634f);
              mx[i] = va[i] + vb[i];
            }
#pragma unroll
            for (int i = 0; i < 4; i++) mx[i] += __shfl_xor_sync(~0u, mx[i], 1);
#pragma unroll
            for (int i = 0; i < 4; i++) mx[i] += __shfl_xor_sync(~0u, mx[i], 2);
#pragma unroll
            for (int i = 0; i < 4; i++) {
              const int m = i >> 1, hh = i & 1;
              const float inv = rcp(mx[i]);
              const uint32_t t = pack2(va[i] * inv, vb[i] * inv);
              const uint32_t pa = e ? t << 16 : t & 0xFFFFu, pb = e ? t & 0xFFFF0000u : t >> 16;
              pf[m][hh][hh + 1] = pa; pf[m][hh][hh] = sel ? pb : 0u; pf[m][hh][hh + 2] = sel ? 0u : pb; pf[m][hh][3 - 3 * hh] = 0u;
            }
#pragma unroll
            for (int m = 0; m < 2; m++) {
              float o[4][4];
#pragma unroll
              for (int j = 0; j < 4; j++) o[j][0] = o[j][1] = o[j][2] = o[j][3] = 0.f;
#pragma unroll
              for (int i = 0; i < 4; i++) {
                const int kk = i >> 1, jj = 2 * (i & 1);
                mma16816(o[jj], pf[m][0][2 * kk], pf[m][1][2 * kk], pf[m][0][2 * kk + 1], pf[m][1][2 * kk + 1], vf[m][i][0], vf[m][i][1]);
                mma16816(o[jj + 1], pf[m][0][2 * kk], pf[m][1][2 * kk], pf[m][0][2 * kk + 1], pf[m][1][2 * kk + 1], vf[m][i][2], vf[m][i][3]);
              }
              const float of[16] = {o[0][0], o[0][1], o[0][2], o[0][3], o[1][0], o[1][1], o[1][2], o[1][3], o[2][0], o[2][1], o[2][2], o[2][3], o[3][0], o[3][1], o[3][2], o[3][3]};
              put_o(h, m, of, 1.f, 1.f);
            }
            bar_arrive(NB_SIG + 2 * h + wg, 160);
            if (h == 0) {
              float nrm[2][2];
              load_cs(1);
              norm_group(1, 1.f, q[0], nrm);
            }
          }
        } else {
          float qn[2];
          auto esc_ptr = [&](int gi) { IDS(); return g_esc + (size_t)(((l & 2) + (gi >> 1)) * 65536 + (2 * bn + (gi & 1)) * 2048) * 16; };
          auto norm_half = [&](int gi, float sc, uint32_t (&t)[2][8], float (&nrm)[2][2]) {
            norm_tile(gi, 0, sc, t[0], nrm[0], true); norm_tile(gi, 1, sc, t[1], nrm[1], true);
            if (!((nrm[0][0] + nrm[0][1]) + (nrm[1][0] + nrm[1][1]) <= 4e9f)) {
              uint32_t* p = esc_ptr(gi) + (bm * 256 + row0 + g) * 16 + qd;
#pragma unroll
              for (int m = 0; m < 2; m++) {
                uint32_t u[8]; float d[2];
                norm_tile(gi, m, sc, u, d);
#pragma unroll
                for (int i = 0; i < 8; i++) p[(m * 64 + (i & 1) * 8) * 16 + (i >> 1) * 4] = u[i];
              }
            }
            __syncwarp();
          };
          {
            auto max_norm = [&](const float (&nrm)[2][2]) {
              const bool o1 = qd & 1, o2 = qd & 2;
              const float a = (o1 ? nrm[1][0] : nrm[0][0]) + __shfl_xor_sync(~0u, o1 ? nrm[0][0] : nrm[1][0], 1);
              const float c = (o1 ? nrm[1][1] : nrm[0][1]) + __shfl_xor_sync(~0u, o1 ? nrm[0][1] : nrm[1][1], 1);
              const float d = (o2 ? c : a) + __shfl_xor_sync(~0u, o2 ? a : c, 2);
              return __uint_as_float(__reduce_max_sync(~0u, __float_as_uint(d)));
            };
#pragma unroll
            for (int h = 0; h < 2; h++) {
              uint32_t t[2][8]; float nrm[2][2];
              const uint32_t kb = sb + (h ? 0 : T0);
              if (h) load_cs(3);
              uint32_t tv[2][8];
              norm_half(2 + h, 1.f, t, nrm);
              load_cs(4 + h);
              float nv[2][2];
              if (h == 1) { const float kn = max_norm(nrm); if (lane == 0) g_kn[((l >> 1) * 128 + bn * 8 + bm) * 16 + 8 + wg * 4 + w] = kn; }
              norm_group(4 + h, 1.f, tv, nv);
              load_cs(h);
              if (h == 0) mbar_wait(sb + B_QE + 24, 1);
#pragma unroll
              for (int i = 0; i < 4; i++) {
                const uint32_t r = row0 + (i >> 1) * 64 + srow;
                stsm4(kb + r * 64 + (((2 * (i & 1) + (lane >> 4)) ^ ((r >> 1) & 3)) << 4), t[i >> 1][4 * (i & 1)], t[i >> 1][4 * (i & 1) + 1], t[i >> 1][4 * (i & 1) + 2], t[i >> 1][4 * (i & 1) + 3]);
              }
#pragma unroll
              for (int m = 0; m < 2; m++) {
                const uint32_t r = row0 + m * 64 + g, ad = kb + 16384 + r * 64 + ((qd ^ ((r >> 1) & 3)) << 4);
                sts128(ad, tv[m][0], tv[m][2], tv[m][4], tv[m][6]); sts128(ad + 512, tv[m][1], tv[m][3], tv[m][5], tv[m][7]);
              }
              fence_async_smem();
              bar_arrive(NB_KV + 12 * h, 288);
              if (h == 0) { const float kn = max_norm(nrm); if (lane == 0) g_kn[((l >> 1) * 128 + bn * 8 + bm) * 16 + wg * 4 + w] = kn; }
              norm_half(h, QSCALE, q[h], nrm);
#pragma unroll
              for (int i = 0; i < 4; i++) sts128(sb + QPARK + h * 16384 + (wg * 128 + w * 32 + lane) * 16 + i * 4096, q[h][i >> 1][4 * (i & 1)], q[h][i >> 1][4 * (i & 1) + 1], q[h][i >> 1][4 * (i & 1) + 2], q[h][i >> 1][4 * (i & 1) + 3]);
              qn[h] = max_norm(nrm);
            }
          }
          const bool elected = w == 0 && lane == 0;
          constexpr uint64_t VSTEP = 64 - (64ull << 16);
          constexpr int SK = 2;
          const uint32_t c_nsig = 0xB8A0B8A0u + (lane_id() & zero), c_half = 0x3F003F00u + (lane_id() & zero), c_lsb = 0x00010001u + (lane_id() & zero);
          float o[2][20], S[2][32], e[2 * SK];
          uint32_t H[2][16], P0[4] = {}, P1[4] = {};
#pragma unroll
          for (int m = 0; m < 2; m++) {
#pragma unroll
            for (int i = 0; i < 20; i++) o[m][i] = 0.f;
            fence_regs(o[m]);
          }
          auto qk = [&](int b, int ks, uint64_t d) {
            wg_n64_rs_nb_f16_f32(S[b], q[0][0][4 * ks], q[0][0][4 * ks + 1], q[0][0][4 * ks + 2], q[0][0][4 * ks + 3], d, ks ? 1 : zero);
            wg_n64_rs_nb_f16_f16(H[b], q[0][1][4 * ks], q[0][1][4 * ks + 1], q[0][1][4 * ks + 2], q[0][1][4 * ks + 3], d, ks ? 1 : zero);
          };
          auto pv = [&](uint64_t d) {
            wgmma_m64n40k16_rs_tb(o[0], P0[0], P0[1], P0[2], P0[3], d, 1);
            wgmma_m64n40k16_rs_tb(o[1], P1[0], P1[1], P1[2], P1[3], d, 1);
          };
          auto start = [&](int h) {
#pragma unroll
            for (int i = 0; i < 2 * SK; i++) e[i] = ex2(S[(h >> 2) & 1][8 * (h & 3) + i]);
            fence_regs(e);
          };
          auto finish = [&](int h) {
            const int b = (h >> 2) & 1, c = h & 3;
#pragma unroll
            for (int i = 0; i < 4; i++) {
              const float s0 = S[b][8 * c + 2 * i], s1 = S[b][8 * c + 2 * i + 1];
              P0[i] = i < SK ? pack2(e[2 * i], e[2 * i + 1]) : i < 3 ? pack2(ex2(s0), ex2(s1)) : exp2_pair(s0, s1, c_half, c_lsb);
              P1[i] = exp2_h2(H[b][4 * c + i], c_nsig);
            }
            fence_regs(P0); fence_regs(P1);
          };
          uint64_t kd = prm.kv[0].kd;
          mbar_wait(sb + B_TF, 0);
          wg_fence();
#pragma unroll
          for (int b = 0; b < 2; b++) {
            wg_n64_rs_nb_f16_f32_z(S[b], q[0][0][0], q[0][0][1], q[0][0][2], q[0][0][3], kd + 256 * b, 0);
            wg_n64_rs_nb_f16_f16_z(H[b], q[0][1][0], q[0][1][1], q[0][1][2], q[0][1][3], kd + 256 * b, 0);
            if (b == 0) qk(0, 1, kd + 2);
            wg_commit();
          }
          wg_wait<1>(); fence_regs(S[0]); fence_regs(H[0]);
          start(0); finish(0); start(1);
          wg_wait<0>();
          const int jlag = JLAG - wg;
          int redo = 0;
#pragma unroll 1
          for (int pass = 0, j = 1; pass < 2; pass++) {
#pragma unroll 1
           do {
            const uint64_t vd = prm.kv[j].vd;
            bool go = false;
#pragma unroll
            for (int h = 2; h < 18; h++) {
              const int px = (h >> 2) + 1, c = h & 3;
              wg_fence();
              if (h == 13) kd = prm.kv[j].kd;
              if (h == 2) qk(1, 0, kd + 256);
              else if ((c == 1 || c == 2) && h < 17) qk(px & 1, c - 1, kd + (px & 3) * 256 + 2 * (c - 1));
              pv(vd + (h - 2) * VSTEP);
              if (h == 2) qk(1, 1, kd + 258);
              wg_commit();
              if (h == 11) go = mbar_test(sb + B_TF + 8 * (j & 3), (j >> 2) & 1) && j != jlag && j != 8;
              finish(h - 1); start(h);
              if (h != 12 && h != 17) sched_fence();
              if (h == 12 && !go) {
                if (j < 16) mbar_wait(sb + B_TF + 8 * (j & 3), (j >> 2) & 1);
                if (j == jlag) { if (wg) bar_sync(NB_HALO, 256); else bar_arrive(NB_HALO, 256); }
                if (j == 8) {
#pragma unroll
                  for (int i = 0; i < 4; i++) lds128(sb + QPARK + 16384 + (wg * 128 + w * 32 + lane_id()) * 16 + i * 4096, &q[0][i >> 1][4 * (i & 1)]);
                }
              }
              if (h == 17) wg_wait<0>(); else if (h & 1) wg_wait<1>();
              if (c == 3) { fence_regs(S[px & 1]); fence_regs(H[px & 1]); }
            }
            if (elected) mbar_arrive(sb + B_TE + 8 * ((j + 3) & 3));
           } while (j++ & 7);
            fence_regs(o[0]); fence_regs(o[1]);
            if (pass == 0) bar_sync(NB_KN + wg, 160);
            const float kmax = *(volatile float*)(smem + ROWST + 4 * pass);
            const bool wide = !(qn[0] <= 1.6e7f && kmax <= 1.6e7f && qn[0] * kmax <= 112.f * 112.f);
            uint32_t pk[2][8];
            auto norm_o = [&](uint32_t (&u)[8], const float (&a)[20]) {
              const float i0 = rcp(a[16]), i1 = rcp(a[18]);
#pragma unroll
              for (int i = 0; i < 4; i++) { u[i] = pack2(a[4 * i] * i0, a[4 * i + 1] * i0); u[4 + i] = pack2(a[4 * i + 2] * i1, a[4 * i + 3] * i1); }
            };
            int badm = 0;
#pragma unroll
            for (int m = 0; m < 2; m++) {
              norm_o(pk[m], o[m]);
              uint32_t chk[2] = {0u, 0u};
#pragma unroll
              for (int i = 0; i < 8; i++) asm("fma.rn.bf16x2 %0, %1, %2, %0;" : "+r"(chk[i & 1]) : "r"(pk[m][i]), "r"(0u));
              const bool bad = wide | !(fminf(o[m][16], o[m][18]) >= 9.3e-10f) | !(o[m][16] + o[m][18] <= 1e36f) | (((chk[0] | chk[1]) & 0x7FFF7FFFu) != 0);
              badm |= __any_sync(~0u, bad) << m;
            }
            if (badm) {
              redo |= badm << 2 * pass;
              uint32_t* p = esc_ptr(pass) + ((cta_id() >> 4) * 256 + row0 + (lane_id() >> 2)) * 16 + (lane_id() & 3);
#pragma unroll
              for (int i = 0; i < 4; i++) {
                uint32_t u[4] = {q[0][i >> 1][4 * (i & 1)], q[0][i >> 1][4 * (i & 1) + 1], q[0][i >> 1][4 * (i & 1) + 2], q[0][i >> 1][4 * (i & 1) + 3]};
                if (pass == 0) lds128(sb + QPARK + (wg * 128 + w * 32 + lane_id()) * 16 + i * 4096, u);
#pragma unroll
                for (int k = 0; k < 4; k++) { uint32_t* a = p + ((i >> 1) * 64 + (k & 1) * 8) * 16 + (2 * (i & 1) + (k >> 1)) * 4; *a = unesc(u[k], a); }
              }
              __syncwarp();
            }
            {
              IDS();
              bf16* op = g_os + (size_t)(bm * 256 + row0 + (lane >> 2)) * 1024 + pass * 512 + bn * 32 + (lane & 3) * 8;
#pragma unroll
              for (int i = 0; i < 4; i++) *(uint4*)(op + ((i >> 1) * 64 + (i & 1) * 8) * 1024) = make_uint4(pk[i >> 1][4 * (i & 1)], pk[i >> 1][4 * (i & 1) + 1], pk[i >> 1][4 * (i & 1) + 2], pk[i >> 1][4 * (i & 1) + 3]);
            }
            if (!badm) bar_arrive(NB_SIG + 2 * pass + wg, 160);
            qn[0] = qn[1];
#pragma unroll
            for (int m = 0; m < 2; m++) {
#pragma unroll
              for (int i = 0; i < 20; i++) o[m][i] = 0.f;
              fence_regs(o[m]);
            }
          }
          if (redo) {
#pragma unroll 1
            for (int t = 0; t < 4; t++) {
              const int pass = t >> 1, m = t & 1;
              if ((redo >> t) & 1) {
                uint32_t qq[8]; float res[20];
                const uint32_t* p = esc_ptr(pass) + ((cta_id() >> 4) * 256 + row0 + m * 64 + (lane_id() >> 2)) * 16 + (lane_id() & 3);
#pragma unroll
                for (int i = 0; i < 8; i++) qq[i] = __ldcg(p + (i & 1) * 128 + (i >> 1) * 4);
                attn_slow(qq, 2 * (cta_id() & 15) + pass, esc_ptr(2 + pass), res, lane_id());
                const float of[16] = {res[0], res[1], res[2], res[3], res[4], res[5], res[6], res[7], res[8], res[9], res[10], res[11], res[12], res[13], res[14], res[15]};
                put_o(pass, m, of, rcp(res[16]), rcp(res[18]));
              }
              if (m && ((redo >> 2 * pass) & 3)) bar_arrive(NB_SIG + 2 * pass + wg, 160);
            }
          }
        }
      }
      {
        float acc[64];
#pragma unroll
        for (int i = 0; i < 64; i++) acc[i] = 0.f;
        fence_regs(acc);
        uint32_t s = 0, lap = 0;
#pragma unroll 1
        for (int kt = 0; kt < 16; kt++) {
          mbar_wait(sb + B_PF + 8 * s, ((s < 4 ? l : 0) + lap) & 1);
          const uint64_t da = mkdesc(sb + pslot_a(s, l) + wg * 8192, 16, 1024, 1), db = mkdesc(sb + pslot_b(s), 8192, 1024, 1);
          wg_fence();
#pragma unroll
          for (int k = 0; k < 4; k++) wgmma_m64n128k16_ss_tb(acc, da + k * 2, db + k * 128, 1);
          wg_commit();
          wg_wait<1>();
          if (kt > 0 && w == 0) e_arrive_both(sb + B_PE + 8 * (s ? s - 1 : 5));
          if (++s == 6) { s = 0; lap++; }
        }
        IDS();
        const int g = lane >> 2, qd = lane & 3;
        const int r0 = wg * 64 + w * 16;
        const uint32_t r = r0 + (lane & 7) + ((lane >> 3) & 1) * 8;
        uint32_t x[8][4];
        mbar_wait(sb + B_RF, l & 1);
#pragma unroll
        for (int jj = 0; jj < 8; jj++) ldsm4(sb + RES + (jj >> 2) * 16384 + r * 128 + ((((2 * jj + (lane >> 4)) & 7) ^ (r & 7)) << 4), x[jj]);
        wg_wait<0>();
        fence_regs(acc);
        if (w == 0) e_arrive_both(sb + B_PE + 8 * 3);
        bar_sync(NB_SC, 256);
        const CUtensorMap* mo = &prm.m[l == 3 ? M_OUT : M_XST];
#pragma unroll
        for (int jj = 0; jj < 8; jj++) {
#pragma unroll
          for (int i = 0; i < 4; i++) x[jj][i] = add_bf16x2(x[jj][i], pack2(acc[8 * jj + 2 * i], acc[8 * jj + 2 * i + 1]));
          stsm4(sb + (jj >> 2) * QSTG + po * 16384 + r * 128 + ((((2 * jj + (lane >> 4)) & 7) ^ (r & 7)) << 4), x[jj][0], x[jj][1], x[jj][2], x[jj][3]);
          if ((jj & 3) == 3) { fence_async_smem(); __syncwarp(); tma_st(mo, pn * 128 + (jj >> 2) * 64, pm * 128 + r0, sb + (jj >> 2) * QSTG + po * 16384 + r0 * 128); }
        }
        bulk_commit();
        if (l < 3) {
          bar_arrive(NB_X, 288);
          float s1[4] = {0.f, 0.f, 0.f, 0.f}, sa[4] = {0.f, 0.f, 0.f, 0.f}, sc[4] = {0.f, 0.f, 0.f, 0.f};
#pragma unroll
          for (int jj = 0; jj < 8; jj++) {
            mma16816(s1, x[jj][0], x[jj][1], x[jj][2], x[jj][3], 0x3f803f80u, 0x3f803f80u);
            mma16816(sa, x[jj][0], x[jj][1], x[jj][2], x[jj][3], x[jj][0], x[jj][2]);
            mma16816(sc, x[jj][0], x[jj][1], x[jj][2], x[jj][3], x[jj][1], x[jj][3]);
          }
          if (qd == g >> 1) {
            float2* p = g_stats + pn * 2048 + pm * 128 + r0 + g;
            p[0] = make_float2(s1[0], g & 1 ? sa[1] : sa[0]);
            p[8] = make_float2(s1[2], g & 1 ? sc[3] : sc[2]);
          }
        }
        bulk_wait_n<0>();
        if (l < 3) bar_arrive(NB_X0, 288);
      }
    }
  }
  asm volatile("barrier.cluster.arrive.relaxed.aligned;\nbarrier.cluster.wait.aligned;" ::: "memory");
}

typedef CUresult (*EncodeFn)(CUtensorMap*, CUtensorMapDataType, cuuint32_t, void*, const cuuint64_t*, const cuuint64_t*, const cuuint32_t*,
                             const cuuint32_t*, CUtensorMapInterleave, CUtensorMapSwizzle, CUtensorMapL2promotion, CUtensorMapFloatOOBfill);

static void make_map(EncodeFn fn, CUtensorMap* m, const void* ptr, int rank, const uint64_t* dims, const uint64_t* strides, const uint32_t* box, CUtensorMapSwizzle sw) {
  cuuint64_t d[5], st[4];
  cuuint32_t bx[5], es[5];
  for (int i = 0; i < rank; i++) { d[i] = dims[i]; bx[i] = box[i]; es[i] = 1; if (i) st[i - 1] = strides[i - 1] * 2; }
  fn(m, CU_TENSOR_MAP_DATA_TYPE_BFLOAT16, rank, (void*)ptr, d, st, bx, es, CU_TENSOR_MAP_INTERLEAVE_NONE, sw,
     CU_TENSOR_MAP_L2_PROMOTION_L2_128B, CU_TENSOR_MAP_FLOAT_OOB_FILL_NONE);
}
static void map2(EncodeFn fn, CUtensorMap* m, const void* ptr, uint64_t inner, uint64_t outer, uint32_t bi, uint32_t bo, CUtensorMapSwizzle sw) {
  const uint64_t d[2] = {inner, outer}, st[1] = {inner};
  const uint32_t bx[2] = {bi, bo};
  make_map(fn, m, ptr, 2, d, st, bx, sw);
}

extern "C" void kernel_launch(void* const* d_in, const int* in_sizes, int n_in, void* d_out, int out_size) {
  (void)in_sizes; (void)n_in; (void)out_size;
  static EncodeFn enc = nullptr;
  static void *xs, *os, *kk, *vv;
  static int sbase = 1024;
  if (!enc) {
    void* p = nullptr;
    cudaDriverEntryPointQueryResult qr;
    cudaGetDriverEntryPoint("cuTensorMapEncodeTiled", &p, cudaEnableDefault, &qr);
    enc = (EncodeFn)p;
    cudaGetSymbolAddress(&xs, g_xs); cudaGetSymbolAddress(&os, g_os); cudaGetSymbolAddress(&kk, g_k); cudaGetSymbolAddress(&vv, g_v);
    int dev = 0;
    cudaGetDevice(&dev);
    cudaDeviceGetAttribute(&sbase, cudaDevAttrReservedSharedMemoryPerBlock, dev);
    cudaFuncSetAttribute(fused_kernel, cudaFuncAttributeMaxDynamicSharedMemorySize, SMEM_BYTES);
  }
  Params prm;
  const CUtensorMapSwizzle S128 = CU_TENSOR_MAP_SWIZZLE_128B, S64 = CU_TENSOR_MAP_SWIZZLE_64B;
  map2(enc, &prm.m[M_X0A], d_in[0], 1024, 2048, 64, 256, S128);
  map2(enc, &prm.m[M_XSA], xs, 1024, 2048, 64, 256, S128);
  for (int t = 0; t < 2; t++) {
    const uint64_t d3[3] = {1024, 1024, 3}, s3[2] = {3072, 1024};
    const uint32_t b3[3] = {64, 64, 3};
    make_map(enc, &prm.m[M_WQA + t], d_in[1 + 3 * t], 3, d3, s3, b3, S128);
    const uint64_t d5[5] = {64, 32, 2, 16, 16}, s5[4] = {1024, 32 * 1024, 64 * 1024, 64};
    const uint32_t b5[5] = {64, 32, 1, 2, 2};
    make_map(enc, &prm.m[M_WOA + t], d_in[2 + 3 * t], 5, d5, s5, b5, S128);
    const uint64_t dr[3] = {64, 2048, 16}, sr[2] = {1024, 64};
    const uint32_t br[3] = {64, 128, 2};
    make_map(enc, &prm.m[M_X0R + t], t ? xs : d_in[0], 3, dr, sr, br, S128);
  }
  map2(enc, &prm.m[M_OS], os, 1024, 2048, 64, 64, S128);
  map2(enc, &prm.m[M_K], kk, 32, 65536, 32, 256, S64);
  map2(enc, &prm.m[M_V], vv, 32, 65536, 32, 256, S64);
  map2(enc, &prm.m[M_XSO], xs, 1024, 2048, 64, 128, S128);
  map2(enc, &prm.m[M_X0H], d_in[0], 1024, 2048, 64, 128, S128);
  map2(enc, &prm.m[M_XST], xs, 1024, 2048, 64, 16, S128);
  map2(enc, &prm.m[M_OUT], d_out, 1024, 2048, 64, 16, S128);
  prm.x0 = (const bf16*)d_in[0];
  prm.wq[0] = (const bf16*)d_in[1]; prm.wq[1] = (const bf16*)d_in[4];
  prm.zero = 0;
  for (int i = 0; i < 128; i++) prm.map[i] = remap(i);
  {
    const uint64_t hi = 0x80000020ull << 32, k0 = sbase + T0, v0 = k0 + 16384, vstep = 64 - (64ull << 16);
    for (int j = 0; j < 17; j++) {
      prm.kv[j].kd = (hi | 1u << 16 | k0 >> 4) + 2048 * ((j < 16 ? j : 15) & 3);
      prm.kv[j].vd = (hi | (uint64_t)(ONES - T0 - 16384) >> 4 << 16 | v0 >> 4) + 32 * vstep * ((j ? j - 1 : 0) & 3);
    }
  }
  fused_kernel<<<128, 384, SMEM_BYTES>>>(prm);
}
```

```cpp
#include <cuda_runtime.h>
#include <cuda_bf16.h>
#include <cuda.h>
#include <stdint.h>

typedef __nv_bfloat16 bf16;

__device__ __forceinline__ void wgmma_m64n192k16_ss_tb(float (&d)[96], uint64_t da, uint64_t db, int scale_d) {
  asm volatile("{\n.reg .pred p;\nsetp.ne.b32 p, %98, 0;\n"
    "wgmma.mma_async.sync.aligned.m64n192k16.f32.bf16.bf16 "
    "{%0, %1, %2, %3, %4, %5, %6, %7, %8, %9, %10, %11, %12, %13, %14, %15, "
    "%16, %17, %18, %19, %20, %21, %22, %23, %24, %25, %26, %27, %28, %29, %30, %31, "
    "%32, %33, %34, %35, %36, %37, %38, %39, %40, %41, %42, %43, %44, %45, %46, %47, "
    "%48, %49, %50, %51, %52, %53, %54, %55, %56, %57, %58, %59, %60, %61, %62, %63, "
    "%64, %65, %66, %67, %68, %69, %70, %71, %72, %73, %74, %75, %76, %77, %78, %79, "
    "%80, %81, %82, %83, %84, %85, %86, %87, %88, %89, %90, %91, %92, %93, %94, %95}, "
    "%96, %97, p, 1, 1, 0, 1;\n}\n"
    : "+f"(d[0]), "+f"(d[1]), "+f"(d[2]), "+f"(d[3]), "+f"(d[4]), "+f"(d[5]), "+f"(d[6]), "+f"(d[7]),
      "+f"(d[8]), "+f"(d[9]), "+f"(d[10]), "+f"(d[11]), "+f"(d[12]), "+f"(d[13]), "+f"(d[14]), "+f"(d[15]),
      "+f"(d[16]), "+f"(d[17]), "+f"(d[18]), "+f"(d[19]), "+f"(d[20]), "+f"(d[21]), "+f"(d[22]), "+f"(d[23]),
      "+f"(d[24]), "+f"(d[25]), "+f"(d[26]), "+f"(d[27]), "+f"(d[28]), "+f"(d[29]), "+f"(d[30]), "+f"(d[31]),
      "+f"(d[32]), "+f"(d[33]), "+f"(d[34]), "+f"(d[35]), "+f"(d[36]), "+f"(d[37]), "+f"(d[38]), "+f"(d[39]),
      "+f"(d[40]), "+f"(d[41]), "+f"(d[42]), "+f"(d[43]), "+f"(d[44]), "+f"(d[45]), "+f"(d[46]), "+f"(d[47]),
      "+f"(d[48]), "+f"(d[49]), "+f"(d[50]), "+f"(d[51]), "+f"(d[52]), "+f"(d[53]), "+f"(d[54]), "+f"(d[55]),
      "+f"(d[56]), "+f"(d[57]), "+f"(d[58]), "+f"(d[59]), "+f"(d[60]), "+f"(d[61]), "+f"(d[62]), "+f"(d[63]),
      "+f"(d[64]), "+f"(d[65]), "+f"(d[66]), "+f"(d[67]), "+f"(d[68]), "+f"(d[69]), "+f"(d[70]), "+f"(d[71]),
      "+f"(d[72]), "+f"(d[73]), "+f"(d[74]), "+f"(d[75]), "+f"(d[76]), "+f"(d[77]), "+f"(d[78]), "+f"(d[79]),
      "+f"(d[80]), "+f"(d[81]), "+f"(d[82]), "+f"(d[83]), "+f"(d[84]), "+f"(d[85]), "+f"(d[86]), "+f"(d[87]),
      "+f"(d[88]), "+f"(d[89]), "+f"(d[90]), "+f"(d[91]), "+f"(d[92]), "+f"(d[93]), "+f"(d[94]), "+f"(d[95])
    : "l"(da), "l"(db), "r"(scale_d));
}

__device__ __forceinline__ void wgmma_m64n128k16_ss_tb(float (&d)[64], uint64_t da, uint64_t db, int scale_d) {
  asm volatile("{\n.reg .pred p;\nsetp.ne.b32 p, %66, 0;\n"
    "wgmma.mma_async.sync.aligned.m64n128k16.f32.bf16.bf16 "
    "{%0, %1, %2, %3, %4, %5, %6, %7, %8, %9, %10, %11, %12, %13, %14, %15, "
    "%16, %17, %18, %19, %20, %21, %22, %23, %24, %25, %26, %27, %28, %29, %30, %31, "
    "%32, %33, %34, %35, %36, %37, %38, %39, %40, %41, %42, %43, %44, %45, %46, %47, "
    "%48, %49, %50, %51, %52, %53, %54, %55, %56, %57, %58, %59, %60, %61, %62, %63}, "
    "%64, %65, p, 1, 1, 0, 1;\n}\n"
    : "+f"(d[0]), "+f"(d[1]), "+f"(d[2]), "+f"(d[3]), "+f"(d[4]), "+f"(d[5]), "+f"(d[6]), "+f"(d[7]),
      "+f"(d[8]), "+f"(d[9]), "+f"(d[10]), "+f"(d[11]), "+f"(d[12]), "+f"(d[13]), "+f"(d[14]), "+f"(d[15]),
      "+f"(d[16]), "+f"(d[17]), "+f"(d[18]), "+f"(d[19]), "+f"(d[20]), "+f"(d[21]), "+f"(d[22]), "+f"(d[23]),
      "+f"(d[24]), "+f"(d[25]), "+f"(d[26]), "+f"(d[27]), "+f"(d[28]), "+f"(d[29]), "+f"(d[30]), "+f"(d[31]),
      "+f"(d[32]), "+f"(d[33]), "+f"(d[34]), "+f"(d[35]), "+f"(d[36]), "+f"(d[37]), "+f"(d[38]), "+f"(d[39]),
      "+f"(d[40]), "+f"(d[41]), "+f"(d[42]), "+f"(d[43]), "+f"(d[44]), "+f"(d[45]), "+f"(d[46]), "+f"(d[47]),
      "+f"(d[48]), "+f"(d[49]), "+f"(d[50]), "+f"(d[51]), "+f"(d[52]), "+f"(d[53]), "+f"(d[54]), "+f"(d[55]),
      "+f"(d[56]), "+f"(d[57]), "+f"(d[58]), "+f"(d[59]), "+f"(d[60]), "+f"(d[61]), "+f"(d[62]), "+f"(d[63])
    : "l"(da), "l"(db), "r"(scale_d));
}

__device__ __forceinline__ void wgmma_m64n40k16_rs_tb(float (&d)[20], uint32_t a0, uint32_t a1, uint32_t a2, uint32_t a3, uint64_t db, int scale_d) {
  asm volatile("{\n.reg .pred p;\nsetp.ne.b32 p, %25, 0;\n"
    "wgmma.mma_async.sync.aligned.m64n40k16.f32.bf16.bf16 "
    "{%0, %1, %2, %3, %4, %5, %6, %7, %8, %9, %10, %11, %12, %13, %14, %15, "
    "%16, %17, %18, %19}, "
    "{%20, %21, %22, %23}, %24, p, 1, 1, 1;\n}\n"
    : "+f"(d[0]), "+f"(d[1]), "+f"(d[2]), "+f"(d[3]), "+f"(d[4]), "+f"(d[5]), "+f"(d[6]), "+f"(d[7]),
      "+f"(d[8]), "+f"(d[9]), "+f"(d[10]), "+f"(d[11]), "+f"(d[12]), "+f"(d[13]), "+f"(d[14]), "+f"(d[15]),
      "+f"(d[16]), "+f"(d[17]), "+f"(d[18]), "+f"(d[19])
    : "r"(a0), "r"(a1), "r"(a2), "r"(a3), "l"(db), "r"(scale_d));
}

__device__ __forceinline__ void wg_n64_rs_nb_f16_f32(float (&d)[32], uint32_t a0, uint32_t a1, uint32_t a2, uint32_t a3, uint64_t db, int scale_d) {
  asm volatile("{\n.reg .pred p;\nsetp.ne.b32 p, %37, 0;\n"
    "wgmma.mma_async.sync.aligned.m64n64k16.f32.f16.f16 "
    "{%0, %1, %2, %3, %4, %5, %6, %7, %8, %9, %10, %11, %12, %13, %14, %15, "
    "%16, %17, %18, %19, %20, %21, %22, %23, %24, %25, %26, %27, %28, %29, %30, %31}, "
    "{%32, %33, %34, %35}, %36, p, 1, 1, 0;\n}\n"
    : "+f"(d[0]), "+f"(d[1]), "+f"(d[2]), "+f"(d[3]), "+f"(d[4]), "+f"(d[5]), "+f"(d[6]), "+f"(d[7]),
      "+f"(d[8]), "+f"(d[9]), "+f"(d[10]), "+f"(d[11]), "+f"(d[12]), "+f"(d[13]), "+f"(d[14]), "+f"(d[15]),
      "+f"(d[16]), "+f"(d[17]), "+f"(d[18]), "+f"(d[19]), "+f"(d[20]), "+f"(d[21]), "+f"(d[22]), "+f"(d[23]),
      "+f"(d[24]), "+f"(d[25]), "+f"(d[26]), "+f"(d[27]), "+f"(d[28]), "+f"(d[29]), "+f"(d[30]), "+f"(d[31])
    : "r"(a0), "r"(a1), "r"(a2), "r"(a3), "l"(db), "r"(scale_d));
}

__device__ __forceinline__ void wg_n64_rs_nb_f16_f16(uint32_t (&d)[16], uint32_t a0, uint32_t a1, uint32_t a2, uint32_t a3, uint64_t db, int scale_d) {
  asm volatile("{\n.reg .pred p;\nsetp.ne.b32 p, %21, 0;\n"
    "wgmma.mma_async.sync.aligned.m64n64k16.f16.f16.f16 "
    "{%0, %1, %2, %3, %4, %5, %6, %7, %8, %9, %10, %11, %12, %13, %14, %15}, "
    "{%16, %17, %18, %19}, %20, p, 1, 1, 0;\n}\n"
    : "+r"(d[0]), "+r"(d[1]), "+r"(d[2]), "+r"(d[3]), "+r"(d[4]), "+r"(d[5]), "+r"(d[6]), "+r"(d[7]),
      "+r"(d[8]), "+r"(d[9]), "+r"(d[10]), "+r"(d[11]), "+r"(d[12]), "+r"(d[13]), "+r"(d[14]), "+r"(d[15])
    : "r"(a0), "r"(a1), "r"(a2), "r"(a3), "l"(db), "r"(scale_d));
}

__device__ __forceinline__ void wg_n64_rs_nb_f16_f32_z(float (&d)[32], uint32_t a0, uint32_t a1, uint32_t a2, uint32_t a3, uint64_t db, int scale_d) {
  asm volatile("{\n.reg .pred p;\nsetp.ne.b32 p, %37, 0;\n"
    "wgmma.mma_async.sync.aligned.m64n64k16.f32.f16.f16 "
    "{%0, %1, %2, %3, %4, %5, %6, %7, %8, %9, %10, %11, %12, %13, %14, %15, "
    "%16, %17, %18, %19, %20, %21, %22, %23, %24, %25, %26, %27, %28, %29, %30, %31}, "
    "{%32, %33, %34, %35}, %36, p, 1, 1, 0;\n}\n"
    : "=f"(d[0]), "=f"(d[1]), "=f"(d[2]), "=f"(d[3]), "=f"(d[4]), "=f"(d[5]), "=f"(d[6]), "=f"(d[7]),
      "=f"(d[8]), "=f"(d[9]), "=f"(d[10]), "=f"(d[11]), "=f"(d[12]), "=f"(d[13]), "=f"(d[14]), "=f"(d[15]),
      "=f"(d[16]), "=f"(d[17]), "=f"(d[18]), "=f"(d[19]), "=f"(d[20]), "=f"(d[21]), "=f"(d[22]), "=f"(d[23]),
      "=f"(d[24]), "=f"(d[25]), "=f"(d[26]), "=f"(d[27]), "=f"(d[28]), "=f"(d[29]), "=f"(d[30]), "=f"(d[31])
    : "r"(a0), "r"(a1), "r"(a2), "r"(a3), "l"(db), "r"(scale_d));
}

__device__ __forceinline__ void wg_n64_rs_nb_f16_f16_z(uint32_t (&d)[16], uint32_t a0, uint32_t a1, uint32_t a2, uint32_t a3, uint64_t db, int scale_d) {
  asm volatile("{\n.reg .pred p;\nsetp.ne.b32 p, %21, 0;\n"
    "wgmma.mma_async.sync.aligned.m64n64k16.f16.f16.f16 "
    "{%0, %1, %2, %3, %4, %5, %6, %7, %8, %9, %10, %11, %12, %13, %14, %15}, "
    "{%16, %17, %18, %19}, %20, p, 1, 1, 0;\n}\n"
    : "=r"(d[0]), "=r"(d[1]), "=r"(d[2]), "=r"(d[3]), "=r"(d[4]), "=r"(d[5]), "=r"(d[6]), "=r"(d[7]),
      "=r"(d[8]), "=r"(d[9]), "=r"(d[10]), "=r"(d[11]), "=r"(d[12]), "=r"(d[13]), "=r"(d[14]), "=r"(d[15])
    : "r"(a0), "r"(a1), "r"(a2), "r"(a3), "l"(db), "r"(scale_d));
}

#define DEVINL __device__ __forceinline__
DEVINL void wg_fence() { asm volatile("wgmma.fence.sync.aligned;" ::: "memory"); }
DEVINL void wg_commit() { asm volatile("wgmma.commit_group.sync.aligned;" ::: "memory"); }
template <int N> DEVINL void wg_wait() { asm volatile("wgmma.wait_group.sync.aligned %0;" ::"n"(N) : "memory"); }
DEVINL uint64_t mkdesc(uint32_t addr, uint32_t lbo, uint32_t sbo, int sw) {
  return (uint64_t)((addr & 0x3FFFF) >> 4) | ((uint64_t)(lbo >> 4) << 16) | ((uint64_t)(sbo >> 4) << 32) | ((uint64_t)sw << 62);
}
DEVINL void mbar_init(uint32_t bar, uint32_t cnt) { asm volatile("mbarrier.init.shared::cta.b64 [%0], %1;" ::"r"(bar), "r"(cnt) : "memory"); }
DEVINL void mbar_arrive(uint32_t bar) { asm volatile("mbarrier.arrive.shared::cta.b64 _, [%0];" ::"r"(bar) : "memory"); }
DEVINL bool mbar_try(uint32_t bar, uint32_t parity) {
  uint32_t ok;
  asm volatile("{\n.reg .pred p;\nmbarrier.try_wait.parity.shared::cta.b64 p, [%1], %2;\nselp.u32 %0, 1, 0, p;\n}" : "=r"(ok) : "r"(bar), "r"(parity) : "memory");
  return ok;
}
DEVINL bool mbar_test(uint32_t bar, uint32_t parity) {
  uint32_t ok;
  asm volatile("{\n.reg .pred p;\nmbarrier.test_wait.parity.shared::cta.b64 p, [%1], %2;\nselp.u32 %0, 1, 0, p;\n}" : "=r"(ok) : "r"(bar), "r"(parity) : "memory");
  return ok;
}
DEVINL void mbar_hint(uint32_t bar, uint32_t parity) {
#pragma unroll 1
  for (uint32_t n = 0; n < 16u; n++) if (mbar_try(bar, parity)) break;
}
DEVINL void mbar_wait(uint32_t bar, uint32_t parity) {
#pragma unroll 1
  for (uint32_t n = 0; n < 100000u; n++) if (mbar_try(bar, parity)) break;
}
#define EL(txt) "{\n.reg .pred pe;\nelect.sync _|pe, 0xffffffff;\n@pe " txt "\n}"
DEVINL void e_expect_tx(uint32_t bar, uint32_t bytes) { asm volatile(EL("mbarrier.arrive.expect_tx.shared::cta.b64 _, [%0], %1;") ::"r"(bar), "r"(bytes) : "memory"); }
DEVINL void e_arrive(uint32_t bar) { asm volatile(EL("mbarrier.arrive.shared::cta.b64 _, [%0];") ::"r"(bar) : "memory"); }
DEVINL void e_red(uint32_t* p) { asm volatile(EL("red.release.gpu.global.add.u32 [%0], 1;") ::"l"(p) : "memory"); }
DEVINL void e_red_relaxed(uint32_t* p) { asm volatile(EL("red.relaxed.gpu.global.add.u32 [%0], 1;") ::"l"(p) : "memory"); }
DEVINL void tma_ld(uint32_t dst, const CUtensorMap* m, int c0, int c1, uint32_t bar) {
  asm volatile(EL("cp.async.bulk.tensor.2d.shared::cluster.global.mbarrier::complete_tx::bytes [%0], [%1, {%3, %4}], [%2];")
               ::"r"(dst), "l"(m), "r"(bar), "r"(c0), "r"(c1) : "memory");
}
DEVINL void tma_ld3(uint32_t dst, const CUtensorMap* m, int c0, int c1, int c2, uint32_t bar) {
  asm volatile(EL("cp.async.bulk.tensor.3d.shared::cluster.global.mbarrier::complete_tx::bytes [%0], [%1, {%3, %4, %5}], [%2];")
               ::"r"(dst), "l"(m), "r"(bar), "r"(c0), "r"(c1), "r"(c2) : "memory");
}
DEVINL void tma_ld5(uint32_t dst, const CUtensorMap* m, int c2, int c3, int c4, uint32_t bar) {
  asm volatile(EL("cp.async.bulk.tensor.5d.shared::cluster.global.mbarrier::complete_tx::bytes [%0], [%1, {0, 0, %3, %4, %5}], [%2];")
               ::"r"(dst), "l"(m), "r"(bar), "r"(c2), "r"(c3), "r"(c4) : "memory");
}
DEVINL void tma_ld_mc(uint32_t dst, const CUtensorMap* m, int c0, int c1, uint32_t bar) {
  asm volatile(EL("cp.async.bulk.tensor.2d.shared::cluster.global.mbarrier::complete_tx::bytes.multicast::cluster [%0], [%1, {%3, %4}], [%2], %5;")
               ::"r"(dst), "l"(m), "r"(bar), "r"(c0), "r"(c1), "h"((uint16_t)3) : "memory");
}
DEVINL void e_arrive_both(uint32_t bar) {
  asm volatile("{\n.reg .pred pe;\n.reg .b32 r0, r1;\nelect.sync _|pe, 0xffffffff;\nmapa.shared::cluster.u32 r0, %0, 0;\nmapa.shared::cluster.u32 r1, %0, 1;\n"
               "@pe mbarrier.arrive.shared::cluster.b64 _, [r0];\n@pe mbarrier.arrive.shared::cluster.b64 _, [r1];\n}" ::"r"(bar) : "memory");
}
DEVINL void tma_st(const CUtensorMap* m, int c0, int c1, uint32_t src) {
  asm volatile(EL("cp.async.bulk.tensor.2d.global.shared::cta.bulk_group [%0, {%2, %3}], [%1];") ::"l"(m), "r"(src), "r"(c0), "r"(c1) : "memory");
}
DEVINL void bulk_commit() { asm volatile("cp.async.bulk.commit_group;" ::: "memory"); }
template <int N> DEVINL void bulk_wait_n() { asm volatile("cp.async.bulk.wait_group %0;\nbar.warp.sync 0xffffffff;" ::"n"(N) : "memory"); }
DEVINL void l2_prefetch(const void* g, uint32_t bytes) { asm volatile(EL("cp.async.bulk.prefetch.L2.global [%0], %1;") ::"l"(g), "r"(bytes) : "memory"); }
DEVINL void fence_async_smem() { asm volatile("fence.proxy.async.shared::cta;" ::: "memory"); }
DEVINL void fence_async_gl() { asm volatile("fence.proxy.async.global;" ::: "memory"); }
DEVINL void cluster_wait() { asm volatile("barrier.cluster.wait.aligned;" ::: "memory"); }
DEVINL void bar_sync(int id, int n) { asm volatile("bar.sync %0, %1;" ::"r"(id), "r"(n) : "memory"); }
DEVINL void bar_arrive(int id, int n) { asm volatile("bar.arrive %0, %1;" ::"r"(id), "r"(n) : "memory"); }
DEVINL uint32_t ld_acquire(const uint32_t* p) { uint32_t v; asm volatile("ld.acquire.gpu.global.u32 %0, [%1];" : "=r"(v) : "l"(p) : "memory"); return v; }
DEVINL void watch(const uint32_t* p, uint32_t target, uint32_t all, uint32_t tag, uint32_t slot) {
  uint32_t seen = 0;
#pragma unroll 1
  for (uint32_t n = 0; n < 200000u && seen != all; n++) {
    const uint32_t m = __ballot_sync(~0u, (int)(ld_acquire(p) - target) >= 0) & all;
    if (m != seen) { seen = m; asm volatile("st.release.cta.shared.u32 [%0], %1;" ::"r"(slot), "r"(tag << 16 | m) : "memory"); }
  }
}
template <bool RELAXED = false> DEVINL void await_bit(uint32_t slot, uint32_t tag, int j, uint32_t& rdy) {
  if ((rdy >> j) & 1) return;
#pragma unroll 1
  for (uint32_t n = 0; n < 8000000u; n++) {
    uint32_t v;
    asm volatile("ld.acquire.cta.shared.u32 %0, [%1];" : "=r"(v) : "r"(slot) : "memory");
    if ((v >> 16) == tag && ((v >> j) & 1)) { rdy = v; break; }
    if (RELAXED) __nanosleep(200);
  }
  asm volatile("fence.proxy.async.global;" ::: "memory");
}
DEVINL void poll_ge(const uint32_t* p, uint32_t target) {
#pragma unroll 1
  for (uint32_t n = 0; n < 200000u; n++) if (__all_sync(~0u, (int)(ld_acquire(p) - target) >= 0)) break;
}
DEVINL int lane_id() { int v; asm volatile("mov.u32 %0, %%laneid;" : "=r"(v)); return v; }
__host__ DEVINL int remap(int v) {
  const int c = v >> 1, u = c - 36, r = (u * 37) >> 8;
  const int L = c < 4 ? 32 + 8 * c : c < 36 ? c - 4 : 33 + u + r;
  return 2 * L + (v & 1);
}
DEVINL int block_id() { int v; asm volatile("mov.u32 %0, %%ctaid.x;" : "=r"(v)); return v; }
#define cta_id() prm.map[block_id()]
#define IDS() const int lane = lane_id(), b = cta_id(), bm = b >> 4, bn = b & 15, rank = b & 1, pm = 2 * bm + (bn >> 3), pn = bn & 7, po = pm & 1; \
  (void)lane; (void)bm; (void)bn; (void)rank; (void)pm; (void)pn; (void)po
DEVINL void st_tagged(uint4* p, uint32_t a, uint32_t b, uint32_t c, uint32_t tag) {
  asm volatile("{\n.reg .b64 u, v;\n.reg .b128 t;\nmov.b64 u, {%1, %2};\nmov.b64 v, {%3, %4};\nmov.b128 t, {u, v};\nst.relaxed.gpu.global.b128 [%0], t;\n}"
               ::"l"(p), "r"(a), "r"(b), "r"(c), "r"(tag) : "memory");
}
DEVINL uint32_t ld_tagged(const uint4* p, uint32_t* r) {
  uint32_t tag;
  asm volatile("{\n.reg .b64 u, v;\n.reg .b128 t;\nld.relaxed.gpu.global.b128 t, [%4];\nmov.b128 {u, v}, t;\nmov.b64 {%0, %1}, u;\nmov.b64 {%2, %3}, v;\n}"
               : "=r"(r[0]), "=r"(r[1]), "=r"(r[2]), "=r"(tag) : "l"(p) : "memory");
  return tag;
}
DEVINL float ex2(float x) { float y; asm("ex2.approx.ftz.f32 %0, %1;" : "=f"(y) : "f"(x)); return y; }
DEVINL float rcp(float x) { float y; asm("rcp.approx.ftz.f32 %0, %1;" : "=f"(y) : "f"(x)); return y; }
DEVINL uint32_t pack2(float lo, float hi) { uint32_t r; asm("cvt.rn.bf16x2.f32 %0, %1, %2;" : "=r"(r) : "f"(hi), "f"(lo)); return r; }
DEVINL uint32_t pack2h(float lo, float hi) { uint32_t r; asm("cvt.rn.f16x2.f32 %0, %1, %2;" : "=r"(r) : "f"(hi), "f"(lo)); return r; }
DEVINL uint32_t hadd2(uint32_t a, uint32_t b) { uint32_t r; asm("add.rn.f16x2 %0, %1, %2;" : "=r"(r) : "r"(a), "r"(b)); return r; }
DEVINL uint32_t hfma2(uint32_t a, uint32_t b, uint32_t c) { uint32_t r; asm("fma.rn.f16x2 %0, %1, %2, %3;" : "=r"(r) : "r"(a), "r"(b), "r"(c)); return r; }
DEVINL float bf_lo(uint32_t w) { return __uint_as_float(w << 16); }
DEVINL float bf_hi(uint32_t w) { return __uint_as_float(w & 0xFFFF0000u); }
DEVINL float bf_round(float x) { return bf_lo(pack2(x, 0.f)); }
DEVINL uint32_t add_bf16x2(uint32_t a, uint32_t b) { uint32_t r; asm("add.rn.bf16x2 %0, %1, %2;" : "=r"(r) : "r"(a), "r"(b)); return r; }
DEVINL void stsm4(uint32_t addr, uint32_t a, uint32_t b, uint32_t c, uint32_t d) {
  asm volatile("stmatrix.sync.aligned.m8n8.x4.shared.b16 [%0], {%1, %2, %3, %4};" ::"r"(addr), "r"(a), "r"(b), "r"(c), "r"(d) : "memory");
}
DEVINL void ldsm4(uint32_t addr, uint32_t (&r)[4]) {
  asm volatile("ldmatrix.sync.aligned.m8n8.x4.shared.b16 {%0, %1, %2, %3}, [%4];" : "=r"(r[0]), "=r"(r[1]), "=r"(r[2]), "=r"(r[3]) : "r"(addr) : "memory");
}
DEVINL void ldsm4t(uint32_t addr, uint32_t (&r)[4]) {
  asm volatile("ldmatrix.sync.aligned.m8n8.x4.trans.shared.b16 {%0, %1, %2, %3}, [%4];" : "=r"(r[0]), "=r"(r[1]), "=r"(r[2]), "=r"(r[3]) : "r"(addr) : "memory");
}
DEVINL void sts128(uint32_t addr, uint32_t a, uint32_t b, uint32_t c, uint32_t d) {
  asm volatile("st.shared.v4.b32 [%0], {%1, %2, %3, %4};" ::"r"(addr), "r"(a), "r"(b), "r"(c), "r"(d) : "memory");
}
DEVINL float2 lds64f(uint32_t addr) { float2 v; asm volatile("ld.shared.v2.f32 {%0, %1}, [%2];" : "=f"(v.x), "=f"(v.y) : "r"(addr) : "memory"); return v; }
DEVINL void mma16816(float (&d)[4], uint32_t a0, uint32_t a1, uint32_t a2, uint32_t a3, uint32_t b0, uint32_t b1) {
  asm("mma.sync.aligned.m16n8k16.row.col.f32.bf16.bf16.f32 {%0, %1, %2, %3}, {%4, %5, %6, %7}, {%8, %9}, {%0, %1, %2, %3};"
               : "+f"(d[0]), "+f"(d[1]), "+f"(d[2]), "+f"(d[3]) : "r"(a0), "r"(a1), "r"(a2), "r"(a3), "r"(b0), "r"(b1));
}
template <int N> DEVINL void fence_regs(float (&d)[N]) {
#pragma unroll
  for (int i = 0; i < N; i++) asm volatile("" : "+f"(d[i])::"memory");
}
template <int N> DEVINL void fence_regs(uint32_t (&d)[N]) {
#pragma unroll
  for (int i = 0; i < N; i++) asm volatile("" : "+r"(d[i])::"memory");
}
DEVINL void lds128(uint32_t addr, uint32_t* r) {
  asm volatile("ld.shared.v4.b32 {%0, %1, %2, %3}, [%4];" : "=r"(r[0]), "=r"(r[1]), "=r"(r[2]), "=r"(r[3]) : "r"(addr) : "memory");
}
DEVINL void sched_fence() { asm volatile("griddepcontrol.launch_dependents;" ::: "memory"); }

__device__ __align__(1024) bf16 g_xs[2048 * 1024];
__device__ __align__(1024) bf16 g_os[2048 * 1024];
__device__ __align__(1024) bf16 g_k[32 * 2048 * 32];
__device__ __align__(1024) bf16 g_v[32 * 2048 * 32];
__device__ __align__(16) uint32_t g_esc[4 * 65536 * 16];
__device__ __align__(128) float2 g_stats[8 * 2048];
__device__ __align__(16) float g_csp[2 * 16 * 8 * 192];
__device__ __align__(128) float g_kn[2 * 128 * 16];
__device__ __align__(128) uint4 g_halo[2 * 128 * 12 * 32];
__device__ __align__(128) uint32_t g_cnt[256 * 32];
__device__ uint32_t g_epoch;

DEVINL uint32_t* cnt_x(int l, int bm) { return g_cnt + (l * 8 + bm) * 32; }
DEVINL uint32_t* cnt_o(int l, int pm, int h) { return g_cnt + (32 + (l * 16 + pm) * 2 + h) * 32; }
DEVINL uint32_t* cnt_kv(int lb, int bn) { return g_cnt + (160 + lb * 16 + bn) * 32; }
DEVINL uint32_t* cnt_ad(int bn) { return g_cnt + (192 + bn) * 32; }
DEVINL uint32_t* cnt_cs(int t, int bn) { return g_cnt + (208 + t * 16 + bn) * 32; }

DEVINL int qord(int i, int l, int pn) { return l == 0 ? i : i < 4 ? ((2 * pn) ^ (i & 2)) + (i & 1) : i - 4 < 2 * (pn & 6) ? i - 4 : i; }
struct Params {
  CUtensorMap m[17];
  const bf16* x0;
  const bf16* wq[2];
  uint32_t zero;
  int map[128];
  struct { uint64_t kd, vd; } kv[17];
};
enum { M_X0A = 0, M_XSA, M_WQA, M_WQB, M_WOA, M_WOB, M_OS, M_K, M_V, M_X0R, M_XSR, M_XSO, M_OUT, M_XST, M_X0H, M_K16, M_V16, M_COUNT };

constexpr uint32_t QSTG = 57344;
constexpr uint32_t T0 = 65536, TSTG = 32768;
constexpr uint32_t ONES = 230400;
constexpr uint32_t PSTG = 32768, RES = 196608;
constexpr uint32_t KSC = 98304, VSC = 133120, HRS = 167936;
constexpr uint32_t ROWST = 229376, COLS = 231424, BARS = 232192, SMEM_BYTES = 232448;
constexpr uint32_t B_QF = BARS, B_QE = BARS + 32, B_TF = BARS + 64, B_TE = BARS + 96, B_PF = BARS + 128, B_PE = BARS + 176,
                   B_RF = BARS + 224, W_X = BARS + 232, W_O = BARS + 236, B_QL = BARS + 240, B_PA = BARS + 248;
enum { NB_ST = 1, NB_KV = 2  , NB_DONE = 3, NB_SC = 4, NB_SIG = 5  , NB_KN = 9  , NB_X = 11, NB_HALO = 12  , NB_X0 = 15 };

DEVINL uint32_t pslot_b(uint32_t s) { return ((0x320415u >> (4 * s)) & 7) * 16384u; }
DEVINL uint32_t pslot_a(uint32_t s, int l) { return 98304u + ((((l & 1) ? 0x541230u : 0x041235u) >> (4 * s)) & 7) * 16384u; }

constexpr float QSCALE = 0.17677669529663687f * 1.4426950408889634f;
#define JLAG 4
constexpr uint32_t QPARK = 32768;

DEVINL uint32_t exp2_pair(float s0, float s1, uint32_t half, uint32_t lsb) {
  constexpr float M = 383.f - 0.591914f + 0.00390625f;
  const uint32_t B = __byte_perm(__float_as_uint(s0 + M), __float_as_uint(s1 + M), 0x6521);
  uint32_t w, E, r;
  asm("lop3.b32 %0, %1, 0x807F807F, %2, 0xEA;" : "=r"(w) : "r"(B), "r"(half));
  asm("lop3.b32 %0, %1, 0x7F807F80, %2, 0xEA;" : "=r"(E) : "r"(B), "r"(lsb));
  asm("fma.rn.bf16x2 %0, %1, %2, %3;" : "=r"(r) : "r"(B), "r"(w), "r"(E));
  return r;
}
DEVINL uint32_t exp2_h2(uint32_t s, uint32_t nsig) {
  uint32_t r = hadd2(s, 0x65F565F5u), d;
  asm("{.reg .b64 t; cvt.u64.u32 t, %0; cvt.u32.u64 %0, t;}" : "+r"(r));
  const uint32_t w = hfma2(s, 0x38A038A0u, hfma2(r, nsig, 0x62E562E5u));
  const uint32_t m = hfma2(w, w, 0x48244833u);
  asm("{.reg .b32 t; shf.l.clamp.b32 t, %2, %1, 7; add.u32 %0, t, %2;}" : "=r"(d) : "r"(r), "r"(m));
  return d;
}
DEVINL uint32_t unesc(uint32_t u, const uint32_t* esc) {
  if ((u & 0x7C00u) == 0x7C00u || (u & 0x7C000000u) == 0x7C000000u) return __ldcg(esc);
  float lo, hi;
  asm("{.reg .f16 a, b; mov.b32 {a, b}, %2; cvt.f32.f16 %0, a; cvt.f32.f16 %1, b;}" : "=f"(lo), "=f"(hi) : "r"(u));
  return pack2(lo, hi);
}

DEVINL void attn_slow(const uint32_t (&q)[8], int head, const uint32_t* kesc, float (&res)[20], int lane) {
  const int g = lane >> 2, qd = lane & 3;
  const bf16* kb = g_k + (size_t)head * 2048 * 32;
  const bf16* vb = g_v + (size_t)head * 2048 * 32;
  float o[4][4], m0 = -INFINITY, m1 = -INFINITY, l0 = 0.f, l1 = 0.f;
#pragma unroll
  for (int j = 0; j < 4; j++) { o[j][0] = o[j][1] = o[j][2] = o[j][3] = 0.f; }
#pragma unroll 1
  for (int k0 = 0; k0 < 2048; k0 += 16) {
    float s[2][4];
#pragma unroll
    for (int nt = 0; nt < 2; nt++) {
      s[nt][0] = s[nt][1] = s[nt][2] = s[nt][3] = 0.f;
      const uint32_t* kp = (const uint32_t*)(kb + (size_t)(k0 + nt * 8 + g) * 32) + qd;
      const uint32_t* ke = kesc + (k0 + nt * 8 + g) * 16 + qd;
      const uint32_t k0r = unesc(__ldcg(kp), ke), k1r = unesc(__ldcg(kp + 4), ke + 4), k2r = unesc(__ldcg(kp + 8), ke + 8), k3r = unesc(__ldcg(kp + 12), ke + 12);
      __syncwarp();
      mma16816(s[nt], q[0], q[1], q[2], q[3], k0r, k1r);
      mma16816(s[nt], q[4], q[5], q[6], q[7], k2r, k3r);
    }
    float a0 = fmaxf(fmaxf(s[0][0], s[0][1]), fmaxf(s[1][0], s[1][1]));
    float a1 = fmaxf(fmaxf(s[0][2], s[0][3]), fmaxf(s[1][2], s[1][3]));
    a0 = fmaxf(a0, __shfl_xor_sync(~0u, a0, 1)); a0 = fmaxf(a0, __shfl_xor_sync(~0u, a0, 2));
    a1 = fmaxf(a1, __shfl_xor_sync(~0u, a1, 1)); a1 = fmaxf(a1, __shfl_xor_sync(~0u, a1, 2));
    const float n0 = fmaxf(m0, a0), n1 = fmaxf(m1, a1);
    const float c0 = (m0 == n0) ? 1.f : ex2(m0 - n0), c1 = (m1 == n1) ? 1.f : ex2(m1 - n1);
    m0 = n0; m1 = n1;
    const uint32_t p0 = pack2(ex2(s[0][0] - n0), ex2(s[0][1] - n0)), p1 = pack2(ex2(s[0][2] - n1), ex2(s[0][3] - n1));
    const uint32_t p2 = pack2(ex2(s[1][0] - n0), ex2(s[1][1] - n0)), p3 = pack2(ex2(s[1][2] - n1), ex2(s[1][3] - n1));
    l0 = l0 * c0 + bf_lo(p0) + bf_hi(p0) + bf_lo(p2) + bf_hi(p2);
    l1 = l1 * c1 + bf_lo(p1) + bf_hi(p1) + bf_lo(p3) + bf_hi(p3);
#pragma unroll
    for (int j = 0; j < 4; j++) {
      o[j][0] *= c0; o[j][1] *= c0; o[j][2] *= c1; o[j][3] *= c1;
      const unsigned short* vp = (const unsigned short*)(vb + (size_t)(k0 + 2 * qd) * 32 + j * 8 + g);
      const uint32_t b0 = (uint32_t)__ldcg(vp) | ((uint32_t)__ldcg(vp + 32) << 16);
      const uint32_t b1 = (uint32_t)__ldcg(vp + 256) | ((uint32_t)__ldcg(vp + 288) << 16);
      mma16816(o[j], p0, p1, p2, p3, b0, b1);
    }
  }
  l0 += __shfl_xor_sync(~0u, l0, 1); l0 += __shfl_xor_sync(~0u, l0, 2);
  l1 += __shfl_xor_sync(~0u, l1, 1); l1 += __shfl_xor_sync(~0u, l1, 2);
#pragma unroll
  for (int j = 0; j < 4; j++) { res[4 * j] = o[j][0]; res[4 * j + 1] = o[j][1]; res[4 * j + 2] = o[j][2]; res[4 * j + 3] = o[j][3]; }
  res[16] = l0; res[18] = l1;
}

__global__ void __cluster_dims__(2, 1, 1) __launch_bounds__(384, 1) fused_kernel(const __grid_constant__ Params prm) {
  extern __shared__ __align__(1024) char smem[];
  const uint32_t sb = (uint32_t)__cvta_generic_to_shared(smem);
  const int tid = threadIdx.x, lane = tid & 31;
  const int wg = __shfl_sync(0xffffffffu, tid >> 7, 0);
  const int w = __shfl_sync(0xffffffffu, (tid >> 5) & 3, 0);
  const int bm = remap(blockIdx.x) >> 4, bn = remap(blockIdx.x) & 15;

  auto first_tile = [&](int kt) {
    e_expect_tx(sb + B_QF + 8 * kt, QSTG);
    tma_ld(sb + kt * QSTG, &prm.m[M_X0A], kt * 64, bm * 256, sb + B_QF + 8 * kt);
    tma_ld3(sb + kt * QSTG + 32768, &prm.m[M_WQA], bn * 64, kt * 64, 0, sb + B_QF + 8 * kt);
  };
  auto init4 = [&](uint32_t bar, uint32_t c0, uint32_t c1, uint32_t c2, uint32_t c3) {
    asm volatile("{\n.reg .pred pe;\nelect.sync _|pe, 0xffffffff;\n@pe mbarrier.init.shared::cta.b64 [%0], %1;\n@pe mbarrier.init.shared::cta.b64 [%0+8], %2;\n"
                 "@pe mbarrier.init.shared::cta.b64 [%0+16], %3;\n@pe mbarrier.init.shared::cta.b64 [%0+24], %4;\n@pe fence.mbarrier_init.release.cluster;\n}"
                 ::"r"(bar), "r"(c0), "r"(c1), "r"(c2), "r"(c3) : "memory");
  };
  if (wg < 2) {
    const uint32_t k = wg * 4 + w, lo = (0x1411214u >> (4 * k)) & 7, hi = (0x1441214u >> (4 * k)) & 7;
    if (tid < 32) asm volatile("prefetch.global.L2 [%0];" ::"l"(prm.x0 + (size_t)(bm * 256 + bn * 16 + (tid & 15)) * 1024 + (tid >> 4) * 64));
    else if (tid < 80) asm volatile("prefetch.global.L2 [%0];" ::"l"(prm.wq[0] + (bm * 16 + (tid & 15)) * 3072 + ((tid >> 4) - 2) * 1024 + bn * 64));
    __syncwarp();
    if (k < 7) init4(sb + B_QE + 32 * k, lo, lo, hi, k == 6 ? 2 : hi);
    __syncwarp();
    if (k == 6 && lane == 0) *(volatile unsigned long long*)(smem + W_X) = 0ull;
  } else if (w == 0) {
    init4(sb + B_QF, 1, 1, 1, 1);
    __syncwarp();
    first_tile(0);
  } else if (lane < 6 && 6 * (w - 1) + lane < M_COUNT) {
    asm volatile("prefetch.tensormap [%0];" ::"l"(&prm.m[6 * (w - 1) + lane]) : "memory");
  }
  __syncthreads();
  asm volatile("barrier.cluster.arrive.relaxed.aligned;" ::: "memory");

  if (wg == 2) {
    asm volatile("setmaxnreg.dec.sync.aligned.u32 56;");
    const uint32_t ep1 = *(volatile uint32_t*)&g_epoch + 1;
    if (w == 0) {
      first_tile(1);
      mbar_wait(sb + B_QF, 0);
      first_tile(2); first_tile(3);
#pragma unroll 1
      for (int kt = 4; kt < 16; kt++) l2_prefetch(prm.wq[0] + kt * 196608 + blockIdx.x * 1536, 3072);
      cluster_wait();
#pragma unroll 1
      for (int l = 0; l < 4; l++) {
        IDS();
        const CUtensorMap* mw = &prm.m[M_WQA + (l & 1)];
        const CUtensorMap* mx = &prm.m[l == 0 ? M_X0A : M_XSA];
        const CUtensorMap* mh = &prm.m[l == 0 ? M_X0H : M_XSO];
        const CUtensorMap* mo = &prm.m[M_WOA + (l & 1)];
        auto q_b = [&](int i) {
          const int s = i & 3;
          mbar_wait(sb + B_QE + 8 * s, ((i >> 2) & 1) ^ 1);
          e_expect_tx(sb + B_QF + 8 * s, QSTG);
          tma_ld3(sb + s * QSTG + 32768, mw, bn * 64, qord(i, l, pn) * 64, 0, sb + B_QF + 8 * s);
        };
        uint32_t rdy = l ? 0u : ~0u;
        auto q_a = [&](int i) {
          const int kt = qord(i, l, pn);
          await_bit(sb + W_X, l, kt >> 1, rdy);
          if (i < 4) tma_ld(sb + i * QSTG, mx, kt * 64, bm * 256, sb + B_QF + 8 * i);
          else tma_ld_mc(sb + (i & 3) * QSTG + rank * 16384, mh, kt * 64, bm * 256 + rank * 128, sb + B_QF + 8 * (i & 3));
        };
        if (l > 0) {
          await_bit(sb + W_X, l, pn, rdy);
#pragma unroll 1
          for (int i = 0; i < 2; i++) {
            e_expect_tx(sb + B_QF + 8 * i, 16384);
            tma_ld(sb + i * QSTG + (po ^ 1) * 16384, &prm.m[M_XSO], (2 * pn + i) * 64, (pm ^ 1) * 128, sb + B_QF + 8 * i);
          }
          mbar_wait(sb + B_QF, 0);
          q_a(2);
          mbar_wait(sb + B_QF + 8, 0);
        }
#pragma unroll 1
        for (int i = l ? 3 : 4; i < 16; i++) {
          if (l == 3 && i == 12) poll_ge(cnt_ad(bn), ep1 * 16);
          q_b(i); q_a(i);
        }
        if (l & 1) {
          bar_sync(NB_KV, 288);
          sts128(sb + ONES + lane * 32, 0x3f803f80u, 0x3f803f80u, 0x3f803f80u, 0x3f803f80u);
          sts128(sb + ONES + lane * 32 + 16, 0x3f803f80u, 0x3f803f80u, 0x3f803f80u, 0x3f803f80u);
          fence_async_smem();
          __syncwarp();
          e_arrive(sb + B_TF);
          const int krow = 2 * bn * 2048 + bm * 256;
          uint32_t* kvc = cnt_kv(l >> 1, bn);
          bar_sync(NB_DONE, 288);
          e_red(kvc + bm);
          uint32_t seen = 0;
#pragma unroll 1
          for (int it = 1; it < 16; it++) {
            const int s = it & 3, blk = it;
            if (it == 4) {
              bar_sync(NB_KV + 12, 288);
              mbar_wait(sb + B_TF + 24, 0);
              tma_st(&prm.m[M_K], 0, krow + 2048, sb);
              tma_st(&prm.m[M_V], 0, krow + 2048, sb + 16384);
              bulk_commit();
            }
            if (it == 5) { bulk_wait_n<0>(); e_red(kvc + bm); }
            if (it == 12) { e_expect_tx(sb + B_RF, 32768); tma_ld3(sb + RES, &prm.m[M_XSR], 0, pm * 128, 2 * pn, sb + B_RF); }
            if (it == 2 || it == 3) mbar_wait(sb + B_TF + 8 * (it - 1), 0);
            mbar_wait(sb + B_TE + 8 * s, ((it >> 2) & 1) ^ 1);
            if (it < 8) {
#pragma unroll 1
              for (uint32_t n = 0; n < 200000u && !((seen >> it) & 1); n++)
                seen = __ballot_sync(~0u, (int)(ld_acquire(kvc + ((bm + lane) & 7)) - (ep1 * 2 - 1)) >= 0);
              fence_async_gl();
            } else if (it == 8) { poll_ge(kvc + (lane & 7), ep1 * 2); fence_async_gl(); }
            const int row = (2 * bn + (it >> 3)) * 2048 + ((bm + blk) & 7) * 256;
            e_expect_tx(sb + B_TF + 8 * s, 32768);
            tma_ld(sb + T0 + s * TSTG, &prm.m[M_K], 0, row, sb + B_TF + 8 * s);
            tma_ld(sb + T0 + s * TSTG + 16384, &prm.m[M_V], 0, row, sb + B_TF + 8 * s);
          }
        }
        auto p_b = [&](int i, uint32_t s, uint32_t par) {
          mbar_wait(sb + B_PE + 8 * s, par ^ 1);
          e_expect_tx(sb + B_PF + 8 * s, PSTG);
          tma_ld5(sb + pslot_b(s), mo, i >> 3, 2 * (i & 7), 2 * pn, sb + B_PF + 8 * s);
        };
        auto p_a = [&](int i, uint32_t s) {
          await_bit(sb + W_O, l + 1, i, rdy);
          tma_ld_mc(sb + pslot_a(s, l) + rank * 8192, &prm.m[M_OS], i * 64, pm * 128 + rank * 64, sb + B_PF + 8 * s);
        };
        auto p_a2 = [&](int i) {
          await_bit(sb + W_O, l + 1, i, rdy);
          tma_ld(sb + pslot_a(i, l), &prm.m[M_OS], i * 64, pm * 128, sb + B_PF + 8 * i);
          tma_ld(sb + pslot_a(i, l) + 8192, &prm.m[M_OS], i * 64, pm * 128 + 64, sb + B_PF + 8 * i);
        };
        rdy = 0;
        if (l & 1) {
#pragma unroll 1
          for (int u = 0; u < 6; u++) { const int i = (0x205413 >> (4 * u)) & 7; if (u == 4) mbar_wait(sb + B_TE, 1); p_b(i, i, i < 4 ? 1 : 0); }
#pragma unroll 1
          for (int u = 0; u < 6; u++) {
            const int i = (0x542130 >> (4 * u)) & 7;
            if (!(u & 1)) mbar_wait(sb + B_TE + 8 + 4 * u, 1);
            if (u == 4) bar_sync(NB_ST, 64);
            p_a2(i);
          }
        } else {
#pragma unroll 1
          for (int u = 0; u < 6; u++) { const int i = (0x025413 >> (4 * u)) & 7; if (u == 0 || u == 3) mbar_wait(sb + B_QE + 8 * (u / 3), 1); p_b(i, i, 0); }
          mbar_wait(sb + B_QE + 24, 1);
          e_expect_tx(sb + B_RF, 32768);
          tma_ld3(sb + RES, &prm.m[l == 0 ? M_X0R : M_XSR], 0, pm * 128, 2 * pn, sb + B_RF);
          p_a2(0);
          bar_sync(NB_DONE, 64);
          e_arrive_both(sb + B_PA);
          p_a2(1);
          mbar_wait(sb + B_PA, (l >> 1) & 1);
#pragma unroll 1
          for (int i = 2; i < 6; i++) { if (i > 2) mbar_wait(sb + B_PF + 8 * (i - 3), 0); p_a(i, i); }
        }
        uint32_t s = 0, lap = 1;
#pragma unroll 1
        for (int i = 6; i < 16; i++) {
          p_b(i, s, ((s < 4 ? l : 0) + lap) & 1);
          p_a(i, s);
          if (++s == 6) { s = 0; lap++; }
        }
        const CUtensorMap* mn = &prm.m[M_WQA + ((l + 1) & 1)];
        if (l < 3) {
          mbar_wait(sb + B_PE + 8 * 4, 1); mbar_wait(sb + B_PE + 8 * 5, 1);
          tma_ld3(sb + 32768, mn, bn * 64, 2 * pn * 64, 0, sb + B_QL);
          mbar_wait(sb + B_PE + 8 * 0, l & 1);
          tma_ld3(sb + QSTG + 32768, mn, bn * 64, (2 * pn + 1) * 64, 0, sb + B_QL);
          mbar_wait(sb + B_PE + 8 * 1, l & 1);
          e_expect_tx(sb + B_QF + 16, QSTG);
          tma_ld3(sb + 2 * QSTG + 32768, mn, bn * 64, ((2 * pn) ^ 2) * 64, 0, sb + B_QF + 16);
        }
        if (l < 3) { bar_sync(NB_X, 288); e_expect_tx(sb + B_QL, 49152); }
      }
      if (blockIdx.x == 0 && lane_id() == 0) *(volatile uint32_t*)&g_epoch = ep1;
    } else {
      const int hw = w - 1;
      cluster_wait();
      mbar_wait(sb + B_QF, 0);
#pragma unroll 1
      for (int l = 0; l < 4; l++) {
        IDS();
        if (hw == 2 && l > 0) watch(cnt_x(l, bm) + (lane & 7), ep1 * 2, 0xFFu, l, sb + W_X);
        if (l == 0) {
#pragma unroll 1
          for (int r = 2 * hw; r < 16; r += 6) {
            const uint4* p = (const uint4*)(prm.x0 + (size_t)(b * 16 + r) * 1024) + lane;
            float s1[2] = {0.f, 0.f}, s2[2] = {0.f, 0.f};
#pragma unroll
            for (int i = 0; i < 8; i++) {
              const uint4 v = __ldg(p + 32 * i);
              const uint32_t u[4] = {v.x, v.y, v.z, v.w};
#pragma unroll
              for (int k = 0; k < 4; k++) { const float a = bf_lo(u[k]), c = bf_hi(u[k]); s1[i >> 2] += a + c; s2[i >> 2] = fmaf(a, a, fmaf(c, c, s2[i >> 2])); }
            }
#pragma unroll
            for (int o = 16; o; o >>= 1)
#pragma unroll
              for (int rr = 0; rr < 2; rr++) { s1[rr] += __shfl_xor_sync(~0u, s1[rr], o); s2[rr] += __shfl_xor_sync(~0u, s2[rr], o); }
            if (lane == 0) *(float4*)&g_stats[b * 16 + r] = make_float4(s1[0], s2[0], s1[1], s2[1]);
          }
        }
        if (l == 1) { uint32_t rdy = 0; await_bit<true>(sb + W_X, 1, pn, rdy); mbar_hint(sb + B_QF + 8, 0); }
        if (l < 2) {
          float cs[8];
#pragma unroll
          for (int i = 0; i < 8; i++) cs[i] = 0.f;
          const uint4* wp = (const uint4*)(prm.wq[l] + (size_t)(bm * 128 + (lane >> 3)) * 3072 + hw * 1024 + bn * 64) + (lane & 7);
#pragma unroll 8
          for (int i = 0; i < 32; i++) {
            const uint4 v = __ldg(wp + (size_t)i * 4 * 384);
            cs[0] += bf_lo(v.x); cs[1] += bf_hi(v.x); cs[2] += bf_lo(v.y); cs[3] += bf_hi(v.y);
            cs[4] += bf_lo(v.z); cs[5] += bf_hi(v.z); cs[6] += bf_lo(v.w); cs[7] += bf_hi(v.w);
          }
#pragma unroll
          for (int i = 0; i < 8; i++) { cs[i] += __shfl_xor_sync(~0u, cs[i], 8); cs[i] += __shfl_xor_sync(~0u, cs[i], 16); }
          if (lane < 8) {
            float4* d = (float4*)(g_csp + ((l * 16 + bn) * 8 + bm) * 192 + hw * 64 + lane * 8);
            d[0] = make_float4(cs[0], cs[1], cs[2], cs[3]); d[1] = make_float4(cs[4], cs[5], cs[6], cs[7]);
          }
          __syncwarp();
          asm volatile("fence.acq_rel.gpu;" ::: "memory");
          e_red_relaxed(cnt_cs(l, bn));
          if (l == 0) e_red_relaxed(cnt_x(0, bm) + pn);
          poll_ge(lane < 8 && l == 0 ? cnt_x(0, bm) + lane : cnt_cs(l, bn), ep1 * (lane < 8 && l == 0 ? 6 : 24));
        }
        if (l > 0) {
          uint32_t rdy = 0;
#pragma unroll 1
          for (int j = 0; j < 8; j++) await_bit<true>(sb + W_X, l, j, rdy);
        }
#pragma unroll 1
        for (int it = hw * 32 + lane; it < 176; it += 96) {
          const bool rows = it < 128;
          const float4* p = rows ? (const float4*)(g_stats + bm * 256) + it : (const float4*)(g_csp + ((l & 1) * 16 + bn) * 8 * 192) + (it - 128);
          const int stride = rows ? 1024 : 48, np = rows && l == 0 ? 1 : 8;
          float4 a = make_float4(0.f, 0.f, 0.f, 0.f);
#pragma unroll
          for (int k = 0; k < 8; k++) if (k < np) { const float4 v = __ldcg(p + k * stride); a.x += v.x; a.y += v.y; a.z += v.z; a.w += v.w; }
          if (rows) {
            const float m0 = a.x * (1.f / 1024.f), m1 = a.z * (1.f / 1024.f);
            const float v0 = fmaxf(a.y * (1.f / 1024.f) - m0 * m0, 0.f), v1 = fmaxf(a.w * (1.f / 1024.f) - m1 * m1, 0.f);
            const float r0 = __fdividef(1.f, bf_round(sqrtf(bf_round(bf_round(v0) + 1e-5f)))), r1 = __fdividef(1.f, bf_round(sqrtf(bf_round(bf_round(v1) + 1e-5f))));
            a = make_float4(r0, -bf_round(m0) * (l & 1 ? r0 : 1.f), r1, -bf_round(m1) * (l & 1 ? r1 : 1.f));
          }
          *(float4*)(smem + ROWST + it * 16) = a;
        }
        __syncwarp();
        if (lane == 0) asm volatile("red.release.cta.shared.add.u32 [%0], 0x100;" ::"r"(sb + W_X) : "memory");
        if (hw == 2) {
          if (!(l & 1)) {
            bar_sync(NB_ST, 288);
            const uint4* hp = g_halo + ((l >> 1) * 128 + b - 16) * 384 + lane;
#pragma unroll 1
            for (int h = 0; h < 2; h++) {
              uint32_t t[18];
#pragma unroll
              for (int i = 0; i < 18; i++) t[i] = 0;
#pragma unroll 1
              for (uint32_t n = bm ? 0 : 100000u; n < 100000u; n++) {
                uint32_t miss = 0;
#pragma unroll
                for (int i = 0; i < 6; i++) miss |= ld_tagged(hp + h * 192 + i * 32, &t[3 * i]) ^ ep1;
                if (__all_sync(~0u, !miss)) break;
              }
              mbar_wait(sb + B_QE + 16, 1);
              const uint32_t r = (lane & 7) + ((lane >> 3) & 1) * 8, rv = lane >> 2;
#pragma unroll
              for (int jj = 0; jj < 2; jj++) stsm4(sb + KSC + r * 128 + (((4 * h + 2 * jj + (lane >> 4)) ^ (r & 7)) << 4), t[4 * jj], t[4 * jj + 1], t[4 * jj + 2], t[4 * jj + 3]);
              const uint32_t ad = sb + VSC + rv * 128 + (((4 * h + (lane & 3)) ^ (rv & 7)) << 4);
              sts128(ad, t[8], t[10], t[12], t[14]); sts128(ad + 1024, t[9], t[11], t[13], t[15]);
              if (h == 0 && !(lane & 2)) *(uint32_t*)(smem + HRS + ((lane >> 2) + 8 * (lane & 1)) * 8) = t[16];
              bar_arrive(NB_HALO + h, 64);
            }
          } else {
            mbar_wait(sb + B_TF + 16, 0); mbar_wait(sb + B_TF + 16, 1);
            poll_ge(cnt_kv(l >> 1, bn) + (lane & 7), ep1 * 2);
            const uint4 v = __ldcg((const uint4*)(g_kn + ((l >> 1) * 128 + bn * 8) * 16) + lane);
            const uint32_t mx = max(max(v.x, v.y), max(v.z, v.w));
            const uint32_t m0 = __reduce_max_sync(~0u, (lane & 2) ? 0u : mx), m1 = __reduce_max_sync(~0u, (lane & 2) ? mx : 0u);
            if (lane == 0) *(uint2*)(smem + ROWST) = make_uint2(m0, m1);
            __syncwarp();
            bar_arrive(NB_KN, 160); bar_arrive(NB_KN + 1, 160);
            mbar_wait(sb + B_TF + 16, 0); mbar_wait(sb + B_TF + 16, 1);
          }
        } else {
#pragma unroll 1
          for (int i = 0; i < 2; i++) {
            const int h = l & 1 ? i : hw, g = l & 1 ? hw : i;
            bar_sync(NB_SIG + 2 * h + g, 160);
            if (!(l & 1) && i == 0) continue;
            if (i == 1 && hw == 1) bar_arrive(l & 1 ? NB_ST : NB_DONE, 64);
            asm volatile("fence.acq_rel.gpu;" ::: "memory");
            e_red_relaxed(cnt_o(l, 2 * bm + g, h) + (bn >> 1));
            if (!(l & 1)) e_red_relaxed(cnt_o(l, 2 * bm, h) + (bn >> 1));
            if (h == 1 && l == 1) e_red_relaxed(cnt_ad(bn));
          }
        }
        if (hw == 2) watch(cnt_o(l, pm, (lane >> 3) & 1) + (lane & 7), ep1 * 2, 0xFFFFu, l + 1, sb + W_O);
        if (hw == 0 && l < 3) {
          bar_sync(NB_X0, 288);
          e_red(cnt_x(l + 1, bm) + pn);
        }
      }
    }
  } else {
    asm volatile("setmaxnreg.inc.sync.aligned.u32 224;");
    const uint32_t zero = prm.zero;
    cluster_wait();
#pragma unroll 1
    for (int l = 0; l < 4; l++) {
      {
        float acc[2][96];
#pragma unroll
        for (int i = 0; i < 96; i++) { acc[0][i] = 0.f; acc[1][i] = 0.f; }
        fence_regs(acc[0]); fence_regs(acc[1]);
        const bool early = l > 0 && wg == ((cta_id() >> 3) & 1);
        uint32_t ep1 = 0;
#pragma unroll 1
        for (int kt = 0; kt < 16; kt++) {
          const int s = kt & 3;
          if (l > 0 && kt == 0) mbar_wait(sb + B_QL, (l + 1) & 1);
          if (!(early && kt < 2)) mbar_wait(sb + B_QF + 8 * s, (kt >> 2) & 1);
          const uint64_t da = mkdesc(sb + s * QSTG + wg * 16384, 16, 1024, 1), db = mkdesc(sb + s * QSTG + 32768, 8192, 1024, 1);
          wg_fence();
#pragma unroll
          for (int m = 1; m >= 0; m--) {
#pragma unroll
            for (int k = 0; k < 4; k++) wgmma_m64n192k16_ss_tb(acc[m], da + m * 512 + k * 2, db + k * 128, 1);
            wg_commit();
          }
          if (kt == 15 && !(l & 1)) bar_arrive(NB_ST, 288);
          if (kt == 4) ep1 = *(volatile uint32_t*)&g_epoch + 1;
          wg_wait<2>();
          if (early && (kt == 1 || kt == 2)) mbar_wait(sb + B_QF + 8 * (kt - 1), 0);
          if (kt > 0 && w == 0) e_arrive_both(sb + B_QE + 8 * ((kt - 1) & 3));
        }
#pragma unroll 1
        for (uint32_t n = 0; n < 4000000u; n++) {
          uint32_t v;
          asm volatile("ld.acquire.cta.shared.u32 %0, [%1];" : "=r"(v) : "r"(sb + W_X) : "memory");
          if ((v >> 8) == (uint32_t)(l * 256 + 3)) break;
        }
        IDS();
        const int g = lane >> 2, qd = lane & 3;
        float2 st[2][2];
#pragma unroll
        for (int m = 0; m < 2; m++)
#pragma unroll
          for (int hh = 0; hh < 2; hh++) st[m][hh] = lds64f(sb + ROWST + (wg * 128 + m * 64 + w * 16 + g + 8 * hh) * 8);
        float2 cs[4];
        auto load_cs = [&](int gi) {
#pragma unroll
          for (int j = 0; j < 4; j++) cs[j] = lds64f(sb + COLS + (gi * 32 + j * 8 + 2 * qd) * 4);
        };
        load_cs(2);
        auto drain = [&]() {
          wg_wait<0>(); fence_regs(acc[0]);
          if (w == 0) e_arrive_both(sb + B_QE + 8 * 3);
        };
        wg_wait<1>(); fence_regs(acc[1]);
        auto norm_tile = [&](int gi, int m, float sc, uint32_t (&t)[8], float (&nrm)[2], bool h16 = false) {
          const float r0 = st[m][0].x * sc, s0 = st[m][0].y * sc, r1 = st[m][1].x * sc, s1 = st[m][1].y * sc;
          float n0 = 0.f, n1 = 0.f;
#pragma unroll
          for (int j = 0; j < 4; j++) {
            const float* a = &acc[m][16 * gi + 4 * j];
            const float v0 = fmaf(a[0], r0, s0 * cs[j].x), v1 = fmaf(a[1], r0, s0 * cs[j].y);
            const float v2 = fmaf(a[2], r1, s1 * cs[j].x), v3 = fmaf(a[3], r1, s1 * cs[j].y);
            n0 = fmaf(v0, v0, fmaf(v1, v1, n0)); n1 = fmaf(v2, v2, fmaf(v3, v3, n1));
            t[2 * j] = h16 ? pack2h(v0, v1) : pack2(v0, v1); t[2 * j + 1] = h16 ? pack2h(v2, v3) : pack2(v2, v3);
          }
          nrm[0] = n0; nrm[1] = n1;
        };
        auto norm_group = [&](int gi, float sc, uint32_t (&t)[2][8], float (&nrm)[2][2]) { norm_tile(gi, 0, sc, t[0], nrm[0]); norm_tile(gi, 1, sc, t[1], nrm[1]); };
        uint32_t q[2][2][8];
        const uint32_t srow = (lane & 7) + ((lane >> 3) & 1) * 8;
        const uint32_t row0 = wg * 128 + w * 16;
        auto put_o = [&](int h, int m, const float (&o)[16], float i0, float i1) {
          IDS();
          bf16* op = g_os + (size_t)(bm * 256 + row0 + m * 64 + (lane >> 2)) * 1024 + h * 512 + bn * 32 + (lane & 3) * 8;
          *(uint4*)op = make_uint4(pack2(o[0] * i0, o[1] * i0), pack2(o[4] * i0, o[5] * i0), pack2(o[8] * i0, o[9] * i0), pack2(o[12] * i0, o[13] * i0));
          *(uint4*)(op + 8 * 1024) = make_uint4(pack2(o[2] * i1, o[3] * i1), pack2(o[6] * i1, o[7] * i1), pack2(o[10] * i1, o[11] * i1), pack2(o[14] * i1, o[15] * i1));
        };
        if (!(l & 1)) {
          auto put_kv = [&](int gi, uint32_t r0, const uint32_t (&t)[8]) {
            if (gi < 4) {
              const uint32_t r = r0 + srow;
#pragma unroll
              for (int jj = 0; jj < 2; jj++) stsm4(sb + KSC + r * 128 + (((4 * (gi - 2) + 2 * jj + (lane >> 4)) ^ (r & 7)) << 4), t[4 * jj], t[4 * jj + 1], t[4 * jj + 2], t[4 * jj + 3]);
            } else {
              const uint32_t r = r0 + g, ad = sb + VSC + r * 128 + (((4 * (gi - 4) + qd) ^ (r & 7)) << 4);
              sts128(ad, t[0], t[2], t[4], t[6]); sts128(ad + 1024, t[1], t[3], t[5], t[7]);
            }
          };
          auto cen_tile = [&](int gi, int m, uint32_t (&t)[8]) {
#pragma unroll
            for (int j = 0; j < 4; j++) {
              const float* a = &acc[m][16 * gi + 4 * j];
              t[2 * j] = pack2(fmaf(st[m][0].y, cs[j].x, a[0]), fmaf(st[m][0].y, cs[j].y, a[1]));
              t[2 * j + 1] = pack2(fmaf(st[m][1].y, cs[j].x, a[2]), fmaf(st[m][1].y, cs[j].y, a[3]));
            }
          };
          const bool send = wg == 1 && w == 3 && bm < 7;
          uint4* hp = g_halo + ((l >> 1) * 128 + b) * 384 + lane;
          mbar_wait(sb + B_QE + 16, 1);
          float2 cn[4];
          auto next_cs = [&](int gi) {
#pragma unroll
            for (int j = 0; j < 4; j++) { cs[j] = cn[j]; cn[j] = lds64f(sb + COLS + (gi * 32 + j * 8 + 2 * qd) * 4); }
          };
#pragma unroll
          for (int j = 0; j < 4; j++) cn[j] = cs[j];
#pragma unroll
          for (int h = 0; h < 2; h++) {
            uint32_t k[8], v[8];
            next_cs(4 + h);
            cen_tile(2 + h, 1, k); put_kv(2 + h, 16 + row0 + 64, k);
            next_cs(h ? 2 : 3);
            cen_tile(4 + h, 1, v); put_kv(4 + h, 16 + row0 + 64, v);
            if (send) {
              uint4* p = hp + h * 192;
              st_tagged(p, k[0], k[1], k[2], ep1); st_tagged(p + 32, k[3], k[4], k[5], ep1); st_tagged(p + 64, k[6], k[7], v[0], ep1);
              st_tagged(p + 96, v[1], v[2], v[3], ep1); st_tagged(p + 128, v[4], v[5], v[6], ep1);
              st_tagged(p + 160, v[7], __float_as_uint(qd & 1 ? st[1][1].x : st[1][0].x), 0u, ep1);
            }
            sched_fence();
          }
          drain();
          {
            uint32_t t[8];
            next_cs(4); cen_tile(2, 0, t); put_kv(2, 16 + row0, t);
            next_cs(0); cen_tile(4, 0, t); put_kv(4, 16 + row0, t);
            next_cs(3); cen_tile(0, 0, q[0][0]); cen_tile(0, 1, q[0][1]);
          }
          bar_sync(NB_SC, 256);
          const bool e = g & 1, sel = 2 * qd + (g & 1) >= g + 2, first = bm == 0 && row0 == 0;
          if (row0 == 0) bar_sync(NB_HALO, 64);
          float ra[4], rb[4], ca[4], cb[4];
#pragma unroll
          for (int m = 0; m < 2; m++) {
            float rk[3];
#pragma unroll
            for (int u = 0; u < 3; u++) {
              const int r = row0 + m * 64 + 8 * u + 2 * qd + e - (sel ? 16 : 8);
              rk[u] = lds64f(sb + (m == 0 && r < 0 ? HRS + 128 : ROWST) + r * 8).x;
            }
            ra[2 * m] = sel ? rk[1] : rk[0]; ra[2 * m + 1] = sel ? rk[2] : rk[1];
            rb[2 * m] = sel ? rk[0] : rk[1]; rb[2 * m + 1] = sel ? rk[1] : rk[2];
          }
#pragma unroll
          for (int i = 0; i < 4; i++) { const float rq = st[i >> 1][i & 1].x * QSCALE; ca[i] = rq * ra[i]; cb[i] = rq * rb[i]; }
#pragma unroll 1
          for (int h = 0; h < 2; h++) {
            float s[2][4][4];
            uint32_t vf[2][4][4], pf[2][2][4];
#pragma unroll
            for (int m = 0; m < 2; m++)
#pragma unroll
              for (int nt = 0; nt < 4; nt++) {
                uint32_t kf[4];
                const uint32_t r = row0 + m * 64 + 8 * nt + (lane & 7), ch = 4 * h + (lane >> 3);
                ldsm4(sb + KSC + r * 128 + ((ch ^ (r & 7)) << 4), kf);
                s[m][nt][0] = s[m][nt][1] = s[m][nt][2] = s[m][nt][3] = 0.f;
                mma16816(s[m][nt], q[0][m][0], q[0][m][1], q[0][m][2], q[0][m][3], kf[0], kf[1]);
                mma16816(s[m][nt], q[0][m][4], q[0][m][5], q[0][m][6], q[0][m][7], kf[2], kf[3]);
              }
#pragma unroll
            for (int m = 0; m < 2; m++)
#pragma unroll
              for (int i = 0; i < 4; i++) {
                const uint32_t r = row0 + m * 64 + 16 * (i >> 1) + srow, ch = 4 * h + 2 * (i & 1) + (lane >> 4);
                ldsm4t(sb + VSC + r * 128 + ((ch ^ (r & 7)) << 4), vf[m][i]);
              }
            float va[4], vb[4], mx[4];
#pragma unroll
            for (int i = 0; i < 4; i++) {
              const int m = i >> 1, hh = i & 1;
              const float a = e ? s[m][hh + 1][2 * hh + 1] : s[m][hh + 1][2 * hh];
              const float lo = e ? s[m][hh][2 * hh + 1] : s[m][hh][2 * hh], hi = e ? s[m][hh + 2][2 * hh + 1] : s[m][hh + 2][2 * hh];
              va[i] = (m == 0 && hh == 0 && first) ? -INFINITY : a * ca[i];
              vb[i] = (m == 0 && first && sel) ? -INFINITY : (sel ? lo : hi) * cb[i];
              mx[i] = fmaxf(va[i], vb[i]);
            }
#pragma unroll
            for (int i = 0; i < 4; i++) mx[i] = fmaxf(mx[i], __shfl_xor_sync(~0u, mx[i], 1));
#pragma unroll
            for (int i = 0; i < 4; i++) mx[i] = fmaxf(mx[i], __shfl_xor_sync(~0u, mx[i], 2));
#pragma unroll
            for (int i = 0; i < 4; i++) {
              va[i] = ex2(va[i] - mx[i]); vb[i] = ex2(vb[i] - mx[i]);
              mx[i] = va[i] + vb[i];
              va[i] *= ra[i]; vb[i] *= rb[i];
            }
#pragma unroll
            for (int i = 0; i < 4; i++) mx[i] += __shfl_xor_sync(~0u, mx[i], 1);
#pragma unroll
            for (int i = 0; i < 4; i++) mx[i] += __shfl_xor_sync(~0u, mx[i], 2);
#pragma unroll
            for (int i = 0; i < 4; i++) {
              const int m = i >> 1, hh = i & 1;
              const float inv = rcp(mx[i]);
              const uint32_t t = pack2(va[i] * inv, vb[i] * inv);
              const uint32_t pa = e ? t << 16 : t & 0xFFFFu, pb = e ? t & 0xFFFF0000u : t >> 16;
              pf[m][hh][hh + 1] = pa; pf[m][hh][hh] = sel ? pb : 0u; pf[m][hh][hh + 2] = sel ? 0u : pb; pf[m][hh][3 - 3 * hh] = 0u;
            }
#pragma unroll
            for (int m = 0; m < 2; m++) {
              float o[4][4];
#pragma unroll
              for (int j = 0; j < 4; j++) o[j][0] = o[j][1] = o[j][2] = o[j][3] = 0.f;
#pragma unroll
              for (int i = 0; i < 4; i++) {
                const int kk = i >> 1, jj = 2 * (i & 1);
                mma16816(o[jj], pf[m][0][2 * kk], pf[m][1][2 * kk], pf[m][0][2 * kk + 1], pf[m][1][2 * kk + 1], vf[m][i][0], vf[m][i][1]);
                mma16816(o[jj + 1], pf[m][0][2 * kk], pf[m][1][2 * kk], pf[m][0][2 * kk + 1], pf[m][1][2 * kk + 1], vf[m][i][2], vf[m][i][3]);
              }
              const float of[16] = {o[0][0], o[0][1], o[0][2], o[0][3], o[1][0], o[1][1], o[1][2], o[1][3], o[2][0], o[2][1], o[2][2], o[2][3], o[3][0], o[3][1], o[3][2], o[3][3]};
              put_o(h, m, of, 1.f, 1.f);
            }
            bar_arrive(NB_SIG + 2 * h + wg, 160);
            if (h == 0) {
              uint32_t t[8];
              next_cs(5); cen_tile(3, 0, t); put_kv(3, 16 + row0, t);
              next_cs(1); cen_tile(5, 0, t); put_kv(5, 16 + row0, t);
#pragma unroll
              for (int j = 0; j < 4; j++) cs[j] = cn[j];
              cen_tile(1, 0, q[0][0]); cen_tile(1, 1, q[0][1]);
              bar_sync(NB_SC, 256);
              if (row0 == 0) bar_sync(NB_HALO + 1, 64);
            }
          }
        } else {
          float qn[2];
          drain();
          auto esc_ptr = [&](int gi) { IDS(); return g_esc + (size_t)(((l & 2) + (gi >> 1)) * 65536 + (2 * bn + (gi & 1)) * 2048) * 16; };
          auto norm_half = [&](int gi, float sc, uint32_t (&t)[2][8], float (&nrm)[2][2]) {
            norm_tile(gi, 0, sc, t[0], nrm[0], true); norm_tile(gi, 1, sc, t[1], nrm[1], true);
            if (!((nrm[0][0] + nrm[0][1]) + (nrm[1][0] + nrm[1][1]) <= 4e9f)) {
              uint32_t* p = esc_ptr(gi) + (bm * 256 + row0 + g) * 16 + qd;
#pragma unroll
              for (int m = 0; m < 2; m++) {
                uint32_t u[8]; float d[2];
                norm_tile(gi, m, sc, u, d);
#pragma unroll
                for (int i = 0; i < 8; i++) p[(m * 64 + (i & 1) * 8) * 16 + (i >> 1) * 4] = u[i];
              }
            }
            __syncwarp();
          };
          {
            auto max_norm = [&](const float (&nrm)[2][2]) {
              const bool o1 = qd & 1, o2 = qd & 2;
              const float a = (o1 ? nrm[1][0] : nrm[0][0]) + __shfl_xor_sync(~0u, o1 ? nrm[0][0] : nrm[1][0], 1);
              const float c = (o1 ? nrm[1][1] : nrm[0][1]) + __shfl_xor_sync(~0u, o1 ? nrm[0][1] : nrm[1][1], 1);
              const float d = (o2 ? c : a) + __shfl_xor_sync(~0u, o2 ? a : c, 2);
              return __uint_as_float(__reduce_max_sync(~0u, __float_as_uint(d)));
            };
#pragma unroll
            for (int h = 0; h < 2; h++) {
              uint32_t t[2][8]; float nrm[2][2];
              const uint32_t kb = sb + (h ? 0 : T0);
              if (h) load_cs(3);
              uint32_t tv[2][8];
              norm_half(2 + h, 1.f, t, nrm);
              load_cs(4 + h);
              float nv[2][2];
              if (h == 1) { const float kn = max_norm(nrm); if (lane == 0) g_kn[((l >> 1) * 128 + bn * 8 + bm) * 16 + 8 + wg * 4 + w] = kn; }
              if (h == 0) mbar_wait(sb + B_QE + 8, 1);
#pragma unroll
              for (int i = 0; i < 4; i++) {
                const uint32_t r = row0 + (i >> 1) * 64 + srow;
                stsm4(kb + r * 64 + (((2 * (i & 1) + (lane >> 4)) ^ ((r >> 1) & 3)) << 4), t[i >> 1][4 * (i & 1)], t[i >> 1][4 * (i & 1) + 1], t[i >> 1][4 * (i & 1) + 2], t[i >> 1][4 * (i & 1) + 3]);
              }
              const int krow = 2 * bn * 2048 + bm * 256 + row0;
              if (h == 0) {
                fence_async_smem(); __syncwarp();
                tma_st(&prm.m[M_K16], 0, krow, kb + row0 * 64); tma_st(&prm.m[M_K16], 0, krow + 64, kb + row0 * 64 + 4096);
              }
              norm_group(4 + h, 1.f, tv, nv);
              load_cs(h);
#pragma unroll
              for (int m = 0; m < 2; m++) {
                const uint32_t r = row0 + m * 64 + g, ad = kb + 16384 + r * 64 + ((qd ^ ((r >> 1) & 3)) << 4);
                sts128(ad, tv[m][0], tv[m][2], tv[m][4], tv[m][6]); sts128(ad + 512, tv[m][1], tv[m][3], tv[m][5], tv[m][7]);
              }
              fence_async_smem();
              bar_arrive(NB_KV + 12 * h, 288);
              if (h == 0) {
                __syncwarp();
                tma_st(&prm.m[M_V16], 0, krow, kb + 16384 + row0 * 64); tma_st(&prm.m[M_V16], 0, krow + 64, kb + 16384 + row0 * 64 + 4096);
                bulk_commit();
              }
              if (h == 0) { const float kn = max_norm(nrm); if (lane == 0) g_kn[((l >> 1) * 128 + bn * 8 + bm) * 16 + wg * 4 + w] = kn; }
              norm_half(h, QSCALE, q[h], nrm);
#pragma unroll
              for (int i = 0; i < 4; i++) sts128(sb + QPARK + h * 16384 + (wg * 128 + w * 32 + lane) * 16 + i * 4096, q[h][i >> 1][4 * (i & 1)], q[h][i >> 1][4 * (i & 1) + 1], q[h][i >> 1][4 * (i & 1) + 2], q[h][i >> 1][4 * (i & 1) + 3]);
              qn[h] = max_norm(nrm);
              if (h == 0) { bulk_wait_n<0>(); bar_arrive(NB_DONE, 288); }
            }
          }
          const bool elected = w == 0 && lane == 0;
          constexpr uint64_t VSTEP = 64 - (64ull << 16);
          constexpr int SK = 2;
          const uint32_t c_nsig = 0xB8A0B8A0u + (lane_id() & zero), c_half = 0x3F003F00u + (lane_id() & zero), c_lsb = 0x00010001u + (lane_id() & zero);
          float o[2][20], S[2][32], e[2 * SK];
          uint32_t H[2][16], P0[4] = {}, P1[4] = {};
#pragma unroll
          for (int m = 0; m < 2; m++) {
#pragma unroll
            for (int i = 0; i < 20; i++) o[m][i] = 0.f;
            fence_regs(o[m]);
          }
          auto qk = [&](int b, int ks, uint64_t d) {
            wg_n64_rs_nb_f16_f32(S[b], q[0][0][4 * ks], q[0][0][4 * ks + 1], q[0][0][4 * ks + 2], q[0][0][4 * ks + 3], d, ks ? 1 : zero);
            wg_n64_rs_nb_f16_f16(H[b], q[0][1][4 * ks], q[0][1][4 * ks + 1], q[0][1][4 * ks + 2], q[0][1][4 * ks + 3], d, ks ? 1 : zero);
          };
          auto pv = [&](uint64_t d) {
            wgmma_m64n40k16_rs_tb(o[0], P0[0], P0[1], P0[2], P0[3], d, 1);
            wgmma_m64n40k16_rs_tb(o[1], P1[0], P1[1], P1[2], P1[3], d, 1);
          };
          auto start = [&](int h) {
#pragma unroll
            for (int i = 0; i < 2 * SK; i++) e[i] = ex2(S[(h >> 2) & 1][8 * (h & 3) + i]);
            fence_regs(e);
          };
          auto finish = [&](int h) {
            const int b = (h >> 2) & 1, c = h & 3;
#pragma unroll
            for (int i = 0; i < 4; i++) {
              const float s0 = S[b][8 * c + 2 * i], s1 = S[b][8 * c + 2 * i + 1];
              P0[i] = i < SK ? pack2(e[2 * i], e[2 * i + 1]) : i < 3 ? pack2(ex2(s0), ex2(s1)) : exp2_pair(s0, s1, c_half, c_lsb);
              P1[i] = exp2_h2(H[b][4 * c + i], c_nsig);
            }
            fence_regs(P0); fence_regs(P1);
          };
          uint64_t kd = prm.kv[0].kd;
          mbar_wait(sb + B_TF, 0);
          wg_fence();
#pragma unroll
          for (int b = 0; b < 2; b++) {
            wg_n64_rs_nb_f16_f32_z(S[b], q[0][0][0], q[0][0][1], q[0][0][2], q[0][0][3], kd + 256 * b, 0);
            wg_n64_rs_nb_f16_f16_z(H[b], q[0][1][0], q[0][1][1], q[0][1][2], q[0][1][3], kd + 256 * b, 0);
            if (b == 0) qk(0, 1, kd + 2);
            wg_commit();
          }
          wg_wait<1>(); fence_regs(S[0]); fence_regs(H[0]);
          start(0); finish(0); start(1);
          wg_wait<0>();
          const int jlag = JLAG - wg;
          int redo = 0;
#pragma unroll 1
          for (int pass = 0, j = 1; pass < 2; pass++) {
#pragma unroll 1
           do {
            const uint64_t vd = prm.kv[j].vd;
            bool go = false;
#pragma unroll
            for (int h = 2; h < 18; h++) {
              const int px = (h >> 2) + 1, c = h & 3;
              wg_fence();
              if (h == 13) kd = prm.kv[j].kd;
              if (h == 2) qk(1, 0, kd + 256);
              else if ((c == 1 || c == 2) && h < 17) qk(px & 1, c - 1, kd + (px & 3) * 256 + 2 * (c - 1));
              pv(vd + (h - 2) * VSTEP);
              if (h == 2) qk(1, 1, kd + 258);
              wg_commit();
              if (h == 11) go = mbar_test(sb + B_TF + 8 * (j & 3), (j >> 2) & 1) && j != jlag && j != 8;
              finish(h - 1); start(h);
              if (h != 12 && h != 17) sched_fence();
              if (h == 12 && !go) {
                if (j < 16) mbar_wait(sb + B_TF + 8 * (j & 3), (j >> 2) & 1);
                if (j == jlag) { if (wg) bar_sync(NB_HALO, 256); else bar_arrive(NB_HALO, 256); }
                if (j == 8) {
#pragma unroll
                  for (int i = 0; i < 4; i++) lds128(sb + QPARK + 16384 + (wg * 128 + w * 32 + lane_id()) * 16 + i * 4096, &q[0][i >> 1][4 * (i & 1)]);
                }
              }
              if (h == 17) wg_wait<0>(); else if (h & 1) wg_wait<1>();
              if (c == 3) { fence_regs(S[px & 1]); fence_regs(H[px & 1]); }
            }
            if (elected) mbar_arrive(sb + B_TE + 8 * ((j + 3) & 3));
           } while (j++ & 7);
            fence_regs(o[0]); fence_regs(o[1]);
            if (pass == 0) bar_sync(NB_KN + wg, 160);
            const float kmax = *(volatile float*)(smem + ROWST + 4 * pass);
            const bool wide = !(qn[0] <= 1.6e7f && kmax <= 1.6e7f && qn[0] * kmax <= 112.f * 112.f);
            uint32_t pk[2][8];
            auto norm_o = [&](uint32_t (&u)[8], const float (&a)[20]) {
              const float i0 = rcp(a[16]), i1 = rcp(a[18]);
#pragma unroll
              for (int i = 0; i < 4; i++) { u[i] = pack2(a[4 * i] * i0, a[4 * i + 1] * i0); u[4 + i] = pack2(a[4 * i + 2] * i1, a[4 * i + 3] * i1); }
            };
            int badm = 0;
#pragma unroll
            for (int m = 0; m < 2; m++) {
              norm_o(pk[m], o[m]);
              uint32_t chk[2] = {0u, 0u};
#pragma unroll
              for (int i = 0; i < 8; i++) asm("fma.rn.bf16x2 %0, %1, %2, %0;" : "+r"(chk[i & 1]) : "r"(pk[m][i]), "r"(0u));
              const bool bad = wide | !(fminf(o[m][16], o[m][18]) >= 9.3e-10f) | !(o[m][16] + o[m][18] <= 1e36f) | (((chk[0] | chk[1]) & 0x7FFF7FFFu) != 0);
              badm |= __any_sync(~0u, bad) << m;
            }
            if (badm) {
              redo |= badm << 2 * pass;
              uint32_t* p = esc_ptr(pass) + ((cta_id() >> 4) * 256 + row0 + (lane_id() >> 2)) * 16 + (lane_id() & 3);
#pragma unroll
              for (int i = 0; i < 4; i++) {
                uint32_t u[4] = {q[0][i >> 1][4 * (i & 1)], q[0][i >> 1][4 * (i & 1) + 1], q[0][i >> 1][4 * (i & 1) + 2], q[0][i >> 1][4 * (i & 1) + 3]};
                if (pass == 0) lds128(sb + QPARK + (wg * 128 + w * 32 + lane_id()) * 16 + i * 4096, u);
#pragma unroll
                for (int k = 0; k < 4; k++) { uint32_t* a = p + ((i >> 1) * 64 + (k & 1) * 8) * 16 + (2 * (i & 1) + (k >> 1)) * 4; *a = unesc(u[k], a); }
              }
              __syncwarp();
            }
            {
              IDS();
              bf16* op = g_os + (size_t)(bm * 256 + row0 + (lane >> 2)) * 1024 + pass * 512 + bn * 32 + (lane & 3) * 8;
#pragma unroll
              for (int i = 0; i < 4; i++) *(uint4*)(op + ((i >> 1) * 64 + (i & 1) * 8) * 1024) = make_uint4(pk[i >> 1][4 * (i & 1)], pk[i >> 1][4 * (i & 1) + 1], pk[i >> 1][4 * (i & 1) + 2], pk[i >> 1][4 * (i & 1) + 3]);
            }
            if (!badm) bar_arrive(NB_SIG + 2 * pass + wg, 160);
            qn[0] = qn[1];
#pragma unroll
            for (int m = 0; m < 2; m++) {
#pragma unroll
              for (int i = 0; i < 20; i++) o[m][i] = 0.f;
              fence_regs(o[m]);
            }
          }
          if (redo) {
#pragma unroll 1
            for (int t = 0; t < 4; t++) {
              const int pass = t >> 1, m = t & 1;
              if ((redo >> t) & 1) {
                uint32_t qq[8]; float res[20];
                const uint32_t* p = esc_ptr(pass) + ((cta_id() >> 4) * 256 + row0 + m * 64 + (lane_id() >> 2)) * 16 + (lane_id() & 3);
#pragma unroll
                for (int i = 0; i < 8; i++) qq[i] = __ldcg(p + (i & 1) * 128 + (i >> 1) * 4);
                attn_slow(qq, 2 * (cta_id() & 15) + pass, esc_ptr(2 + pass), res, lane_id());
                const float of[16] = {res[0], res[1], res[2], res[3], res[4], res[5], res[6], res[7], res[8], res[9], res[10], res[11], res[12], res[13], res[14], res[15]};
                put_o(pass, m, of, rcp(res[16]), rcp(res[18]));
              }
              if (m && ((redo >> 2 * pass) & 3)) bar_arrive(NB_SIG + 2 * pass + wg, 160);
            }
          }
        }
      }
      {
        float acc[64];
#pragma unroll
        for (int i = 0; i < 64; i++) acc[i] = 0.f;
        fence_regs(acc);
        uint32_t s = 0, lap = 0;
#pragma unroll 1
        for (int kt = 0; kt < 16; kt++) {
          mbar_wait(sb + B_PF + 8 * s, ((s < 4 ? l : 0) + lap) & 1);
          const uint64_t da = mkdesc(sb + pslot_a(s, l) + wg * 8192, 16, 1024, 1), db = mkdesc(sb + pslot_b(s), 8192, 1024, 1);
          wg_fence();
#pragma unroll
          for (int k = 0; k < 4; k++) wgmma_m64n128k16_ss_tb(acc, da + k * 2, db + k * 128, 1);
          wg_commit();
          wg_wait<1>();
          if (kt > 0 && w == 0) e_arrive_both(sb + B_PE + 8 * (s ? s - 1 : 5));
          if (++s == 6) { s = 0; lap++; }
        }
        IDS();
        const int g = lane >> 2, qd = lane & 3;
        const int r0 = wg * 64 + w * 16;
        const uint32_t r = r0 + (lane & 7) + ((lane >> 3) & 1) * 8;
        uint32_t x[8][4];
        mbar_wait(sb + B_RF, l & 1);
#pragma unroll
        for (int jj = 0; jj < 8; jj++) ldsm4(sb + RES + (jj >> 2) * 16384 + r * 128 + ((((2 * jj + (lane >> 4)) & 7) ^ (r & 7)) << 4), x[jj]);
        wg_wait<0>();
        fence_regs(acc);
        if (w == 0) e_arrive_both(sb + B_PE + 8 * 3);
        bar_sync(NB_SC, 256);
        const CUtensorMap* mo = &prm.m[l == 3 ? M_OUT : M_XST];
#pragma unroll
        for (int jj = 0; jj < 8; jj++) {
#pragma unroll
          for (int i = 0; i < 4; i++) x[jj][i] = add_bf16x2(x[jj][i], pack2(acc[8 * jj + 2 * i], acc[8 * jj + 2 * i + 1]));
          stsm4(sb + (jj >> 2) * QSTG + po * 16384 + r * 128 + ((((2 * jj + (lane >> 4)) & 7) ^ (r & 7)) << 4), x[jj][0], x[jj][1], x[jj][2], x[jj][3]);
          if ((jj & 3) == 3) { fence_async_smem(); __syncwarp(); tma_st(mo, pn * 128 + (jj >> 2) * 64, pm * 128 + r0, sb + (jj >> 2) * QSTG + po * 16384 + r0 * 128); }
        }
        bulk_commit();
        if (l < 3) {
          bar_arrive(NB_X, 288);
          float s1[4] = {0.f, 0.f, 0.f, 0.f}, sa[4] = {0.f, 0.f, 0.f, 0.f}, sc[4] = {0.f, 0.f, 0.f, 0.f};
#pragma unroll
          for (int jj = 0; jj < 8; jj++) {
            mma16816(s1, x[jj][0], x[jj][1], x[jj][2], x[jj][3], 0x3f803f80u, 0x3f803f80u);
            mma16816(sa, x[jj][0], x[jj][1], x[jj][2], x[jj][3], x[jj][0], x[jj][2]);
            mma16816(sc, x[jj][0], x[jj][1], x[jj][2], x[jj][3], x[jj][1], x[jj][3]);
          }
          if (qd == g >> 1) {
            float2* p = g_stats + pn * 2048 + pm * 128 + r0 + g;
            p[0] = make_float2(s1[0], g & 1 ? sa[1] : sa[0]);
            p[8] = make_float2(s1[2], g & 1 ? sc[3] : sc[2]);
          }
        }
        bulk_wait_n<0>();
        if (l < 3) bar_arrive(NB_X0, 288);
      }
    }
  }
  asm volatile("barrier.cluster.arrive.relaxed.aligned;\nbarrier.cluster.wait.aligned;" ::: "memory");
}

typedef CUresult (*EncodeFn)(CUtensorMap*, CUtensorMapDataType, cuuint32_t, void*, const cuuint64_t*, const cuuint64_t*, const cuuint32_t*,
                             const cuuint32_t*, CUtensorMapInterleave, CUtensorMapSwizzle, CUtensorMapL2promotion, CUtensorMapFloatOOBfill);

static void make_map(EncodeFn fn, CUtensorMap* m, const void* ptr, int rank, const uint64_t* dims, const uint64_t* strides, const uint32_t* box, CUtensorMapSwizzle sw) {
  cuuint64_t d[5], st[4];
  cuuint32_t bx[5], es[5];
  for (int i = 0; i < rank; i++) { d[i] = dims[i]; bx[i] = box[i]; es[i] = 1; if (i) st[i - 1] = strides[i - 1] * 2; }
  fn(m, CU_TENSOR_MAP_DATA_TYPE_BFLOAT16, rank, (void*)ptr, d, st, bx, es, CU_TENSOR_MAP_INTERLEAVE_NONE, sw,
     CU_TENSOR_MAP_L2_PROMOTION_L2_128B, CU_TENSOR_MAP_FLOAT_OOB_FILL_NONE);
}
static void map2(EncodeFn fn, CUtensorMap* m, const void* ptr, uint64_t inner, uint64_t outer, uint32_t bi, uint32_t bo, CUtensorMapSwizzle sw) {
  const uint64_t d[2] = {inner, outer}, st[1] = {inner};
  const uint32_t bx[2] = {bi, bo};
  make_map(fn, m, ptr, 2, d, st, bx, sw);
}

extern "C" void kernel_launch(void* const* d_in, const int* in_sizes, int n_in, void* d_out, int out_size) {
  (void)in_sizes; (void)n_in; (void)out_size;
  static EncodeFn enc = nullptr;
  static void *xs, *os, *kk, *vv;
  static int sbase = 1024;
  if (!enc) {
    void* p = nullptr;
    cudaDriverEntryPointQueryResult qr;
    cudaGetDriverEntryPoint("cuTensorMapEncodeTiled", &p, cudaEnableDefault, &qr);
    enc = (EncodeFn)p;
    cudaGetSymbolAddress(&xs, g_xs); cudaGetSymbolAddress(&os, g_os); cudaGetSymbolAddress(&kk, g_k); cudaGetSymbolAddress(&vv, g_v);
    int dev = 0;
    cudaGetDevice(&dev);
    cudaDeviceGetAttribute(&sbase, cudaDevAttrReservedSharedMemoryPerBlock, dev);
    cudaFuncSetAttribute(fused_kernel, cudaFuncAttributeMaxDynamicSharedMemorySize, SMEM_BYTES);
  }
  Params prm;
  const CUtensorMapSwizzle S128 = CU_TENSOR_MAP_SWIZZLE_128B, S64 = CU_TENSOR_MAP_SWIZZLE_64B;
  map2(enc, &prm.m[M_X0A], d_in[0], 1024, 2048, 64, 256, S128);
  map2(enc, &prm.m[M_XSA], xs, 1024, 2048, 64, 256, S128);
  for (int t = 0; t < 2; t++) {
    const uint64_t d3[3] = {1024, 1024, 3}, s3[2] = {3072, 1024};
    const uint32_t b3[3] = {64, 64, 3};
    make_map(enc, &prm.m[M_WQA + t], d_in[1 + 3 * t], 3, d3, s3, b3, S128);
    const uint64_t d5[5] = {64, 32, 2, 16, 16}, s5[4] = {1024, 32 * 1024, 64 * 1024, 64};
    const uint32_t b5[5] = {64, 32, 1, 2, 2};
    make_map(enc, &prm.m[M_WOA + t], d_in[2 + 3 * t], 5, d5, s5, b5, S128);
    const uint64_t dr[3] = {64, 2048, 16}, sr[2] = {1024, 64};
    const uint32_t br[3] = {64, 128, 2};
    make_map(enc, &prm.m[M_X0R + t], t ? xs : d_in[0], 3, dr, sr, br, S128);
  }
  map2(enc, &prm.m[M_OS], os, 1024, 2048, 64, 64, S128);
  map2(enc, &prm.m[M_K], kk, 32, 65536, 32, 256, S64);
  map2(enc, &prm.m[M_V], vv, 32, 65536, 32, 256, S64);
  map2(enc, &prm.m[M_K16], kk, 32, 65536, 32, 16, S64);
  map2(enc, &prm.m[M_V16], vv, 32, 65536, 32, 16, S64);
  map2(enc, &prm.m[M_XSO], xs, 1024, 2048, 64, 128, S128);
  map2(enc, &prm.m[M_X0H], d_in[0], 1024, 2048, 64, 128, S128);
  map2(enc, &prm.m[M_XST], xs, 1024, 2048, 64, 16, S128);
  map2(enc, &prm.m[M_OUT], d_out, 1024, 2048, 64, 16, S128);
  prm.x0 = (const bf16*)d_in[0];
  prm.wq[0] = (const bf16*)d_in[1]; prm.wq[1] = (const bf16*)d_in[4];
  prm.zero = 0;
  for (int i = 0; i < 128; i++) prm.map[i] = remap(i);
  {
    const uint64_t hi = 0x80000020ull << 32, k0 = sbase + T0, v0 = k0 + 16384, vstep = 64 - (64ull << 16);
    for (int j = 0; j < 17; j++) {
      prm.kv[j].kd = (hi | 1u << 16 | k0 >> 4) + 2048 * ((j < 16 ? j : 15) & 3);
      prm.kv[j].vd = (hi | (uint64_t)(ONES - T0 - 16384) >> 4 << 16 | v0 >> 4) + 32 * vstep * ((j ? j - 1 : 0) & 3);
    }
  }
  fused_kernel<<<128, 384, SMEM_BYTES>>>(prm);
}
```

```cpp
#include <cuda_runtime.h>
#include <cuda_bf16.h>
#include <cuda.h>
#include <stdint.h>

typedef __nv_bfloat16 bf16;

__device__ __forceinline__ void wgmma_m64n192k16_ss_tb(float (&d)[96], uint64_t da, uint64_t db, int scale_d) {
  asm volatile("{\n.reg .pred p;\nsetp.ne.b32 p, %98, 0;\n"
    "wgmma.mma_async.sync.aligned.m64n192k16.f32.bf16.bf16 "
    "{%0, %1, %2, %3, %4, %5, %6, %7, %8, %9, %10, %11, %12, %13, %14, %15, "
    "%16, %17, %18, %19, %20, %21, %22, %23, %24, %25, %26, %27, %28, %29, %30, %31, "
    "%32, %33, %34, %35, %36, %37, %38, %39, %40, %41, %42, %43, %44, %45, %46, %47, "
    "%48, %49, %50, %51, %52, %53, %54, %55, %56, %57, %58, %59, %60, %61, %62, %63, "
    "%64, %65, %66, %67, %68, %69, %70, %71, %72, %73, %74, %75, %76, %77, %78, %79, "
    "%80, %81, %82, %83, %84, %85, %86, %87, %88, %89, %90, %91, %92, %93, %94, %95}, "
    "%96, %97, p, 1, 1, 0, 1;\n}\n"
    : "+f"(d[0]), "+f"(d[1]), "+f"(d[2]), "+f"(d[3]), "+f"(d[4]), "+f"(d[5]), "+f"(d[6]), "+f"(d[7]),
      "+f"(d[8]), "+f"(d[9]), "+f"(d[10]), "+f"(d[11]), "+f"(d[12]), "+f"(d[13]), "+f"(d[14]), "+f"(d[15]),
      "+f"(d[16]), "+f"(d[17]), "+f"(d[18]), "+f"(d[19]), "+f"(d[20]), "+f"(d[21]), "+f"(d[22]), "+f"(d[23]),
      "+f"(d[24]), "+f"(d[25]), "+f"(d[26]), "+f"(d[27]), "+f"(d[28]), "+f"(d[29]), "+f"(d[30]), "+f"(d[31]),
      "+f"(d[32]), "+f"(d[33]), "+f"(d[34]), "+f"(d[35]), "+f"(d[36]), "+f"(d[37]), "+f"(d[38]), "+f"(d[39]),
      "+f"(d[40]), "+f"(d[41]), "+f"(d[42]), "+f"(d[43]), "+f"(d[44]), "+f"(d[45]), "+f"(d[46]), "+f"(d[47]),
      "+f"(d[48]), "+f"(d[49]), "+f"(d[50]), "+f"(d[51]), "+f"(d[52]), "+f"(d[53]), "+f"(d[54]), "+f"(d[55]),
      "+f"(d[56]), "+f"(d[57]), "+f"(d[58]), "+f"(d[59]), "+f"(d[60]), "+f"(d[61]), "+f"(d[62]), "+f"(d[63]),
      "+f"(d[64]), "+f"(d[65]), "+f"(d[66]), "+f"(d[67]), "+f"(d[68]), "+f"(d[69]), "+f"(d[70]), "+f"(d[71]),
      "+f"(d[72]), "+f"(d[73]), "+f"(d[74]), "+f"(d[75]), "+f"(d[76]), "+f"(d[77]), "+f"(d[78]), "+f"(d[79]),
      "+f"(d[80]), "+f"(d[81]), "+f"(d[82]), "+f"(d[83]), "+f"(d[84]), "+f"(d[85]), "+f"(d[86]), "+f"(d[87]),
      "+f"(d[88]), "+f"(d[89]), "+f"(d[90]), "+f"(d[91]), "+f"(d[92]), "+f"(d[93]), "+f"(d[94]), "+f"(d[95])
    : "l"(da), "l"(db), "r"(scale_d));
}

__device__ __forceinline__ void wgmma_m64n128k16_ss_tb(float (&d)[64], uint64_t da, uint64_t db, int scale_d) {
  asm volatile("{\n.reg .pred p;\nsetp.ne.b32 p, %66, 0;\n"
    "wgmma.mma_async.sync.aligned.m64n128k16.f32.bf16.bf16 "
    "{%0, %1, %2, %3, %4, %5, %6, %7, %8, %9, %10, %11, %12, %13, %14, %15, "
    "%16, %17, %18, %19, %20, %21, %22, %23, %24, %25, %26, %27, %28, %29, %30, %31, "
    "%32, %33, %34, %35, %36, %37, %38, %39, %40, %41, %42, %43, %44, %45, %46, %47, "
    "%48, %49, %50, %51, %52, %53, %54, %55, %56, %57, %58, %59, %60, %61, %62, %63}, "
    "%64, %65, p, 1, 1, 0, 1;\n}\n"
    : "+f"(d[0]), "+f"(d[1]), "+f"(d[2]), "+f"(d[3]), "+f"(d[4]), "+f"(d[5]), "+f"(d[6]), "+f"(d[7]),
      "+f"(d[8]), "+f"(d[9]), "+f"(d[10]), "+f"(d[11]), "+f"(d[12]), "+f"(d[13]), "+f"(d[14]), "+f"(d[15]),
      "+f"(d[16]), "+f"(d[17]), "+f"(d[18]), "+f"(d[19]), "+f"(d[20]), "+f"(d[21]), "+f"(d[22]), "+f"(d[23]),
      "+f"(d[24]), "+f"(d[25]), "+f"(d[26]), "+f"(d[27]), "+f"(d[28]), "+f"(d[29]), "+f"(d[30]), "+f"(d[31]),
      "+f"(d[32]), "+f"(d[33]), "+f"(d[34]), "+f"(d[35]), "+f"(d[36]), "+f"(d[37]), "+f"(d[38]), "+f"(d[39]),
      "+f"(d[40]), "+f"(d[41]), "+f"(d[42]), "+f"(d[43]), "+f"(d[44]), "+f"(d[45]), "+f"(d[46]), "+f"(d[47]),
      "+f"(d[48]), "+f"(d[49]), "+f"(d[50]), "+f"(d[51]), "+f"(d[52]), "+f"(d[53]), "+f"(d[54]), "+f"(d[55]),
      "+f"(d[56]), "+f"(d[57]), "+f"(d[58]), "+f"(d[59]), "+f"(d[60]), "+f"(d[61]), "+f"(d[62]), "+f"(d[63])
    : "l"(da), "l"(db), "r"(scale_d));
}

__device__ __forceinline__ void wgmma_m64n40k16_rs_tb(float (&d)[20], uint32_t a0, uint32_t a1, uint32_t a2, uint32_t a3, uint64_t db, int scale_d) {
  asm volatile("{\n.reg .pred p;\nsetp.ne.b32 p, %25, 0;\n"
    "wgmma.mma_async.sync.aligned.m64n40k16.f32.bf16.bf16 "
    "{%0, %1, %2, %3, %4, %5, %6, %7, %8, %9, %10, %11, %12, %13, %14, %15, "
    "%16, %17, %18, %19}, "
    "{%20, %21, %22, %23}, %24, p, 1, 1, 1;\n}\n"
    : "+f"(d[0]), "+f"(d[1]), "+f"(d[2]), "+f"(d[3]), "+f"(d[4]), "+f"(d[5]), "+f"(d[6]), "+f"(d[7]),
      "+f"(d[8]), "+f"(d[9]), "+f"(d[10]), "+f"(d[11]), "+f"(d[12]), "+f"(d[13]), "+f"(d[14]), "+f"(d[15]),
      "+f"(d[16]), "+f"(d[17]), "+f"(d[18]), "+f"(d[19])
    : "r"(a0), "r"(a1), "r"(a2), "r"(a3), "l"(db), "r"(scale_d));
}

__device__ __forceinline__ void wg_n64_rs_nb_f16_f32(float (&d)[32], uint32_t a0, uint32_t a1, uint32_t a2, uint32_t a3, uint64_t db, int scale_d) {
  asm volatile("{\n.reg .pred p;\nsetp.ne.b32 p, %37, 0;\n"
    "wgmma.mma_async.sync.aligned.m64n64k16.f32.f16.f16 "
    "{%0, %1, %2, %3, %4, %5, %6, %7, %8, %9, %10, %11, %12, %13, %14, %15, "
    "%16, %17, %18, %19, %20, %21, %22, %23, %24, %25, %26, %27, %28, %29, %30, %31}, "
    "{%32, %33, %34, %35}, %36, p, 1, 1, 0;\n}\n"
    : "+f"(d[0]), "+f"(d[1]), "+f"(d[2]), "+f"(d[3]), "+f"(d[4]), "+f"(d[5]), "+f"(d[6]), "+f"(d[7]),
      "+f"(d[8]), "+f"(d[9]), "+f"(d[10]), "+f"(d[11]), "+f"(d[12]), "+f"(d[13]), "+f"(d[14]), "+f"(d[15]),
      "+f"(d[16]), "+f"(d[17]), "+f"(d[18]), "+f"(d[19]), "+f"(d[20]), "+f"(d[21]), "+f"(d[22]), "+f"(d[23]),
      "+f"(d[24]), "+f"(d[25]), "+f"(d[26]), "+f"(d[27]), "+f"(d[28]), "+f"(d[29]), "+f"(d[30]), "+f"(d[31])
    : "r"(a0), "r"(a1), "r"(a2), "r"(a3), "l"(db), "r"(scale_d));
}

__device__ __forceinline__ void wg_n64_rs_nb_f16_f16(uint32_t (&d)[16], uint32_t a0, uint32_t a1, uint32_t a2, uint32_t a3, uint64_t db, int scale_d) {
  asm volatile("{\n.reg .pred p;\nsetp.ne.b32 p, %21, 0;\n"
    "wgmma.mma_async.sync.aligned.m64n64k16.f16.f16.f16 "
    "{%0, %1, %2, %3, %4, %5, %6, %7, %8, %9, %10, %11, %12, %13, %14, %15}, "
    "{%16, %17, %18, %19}, %20, p, 1, 1, 0;\n}\n"
    : "+r"(d[0]), "+r"(d[1]), "+r"(d[2]), "+r"(d[3]), "+r"(d[4]), "+r"(d[5]), "+r"(d[6]), "+r"(d[7]),
      "+r"(d[8]), "+r"(d[9]), "+r"(d[10]), "+r"(d[11]), "+r"(d[12]), "+r"(d[13]), "+r"(d[14]), "+r"(d[15])
    : "r"(a0), "r"(a1), "r"(a2), "r"(a3), "l"(db), "r"(scale_d));
}

__device__ __forceinline__ void wg_n64_rs_nb_f16_f32_z(float (&d)[32], uint32_t a0, uint32_t a1, uint32_t a2, uint32_t a3, uint64_t db, int scale_d) {
  asm volatile("{\n.reg .pred p;\nsetp.ne.b32 p, %37, 0;\n"
    "wgmma.mma_async.sync.aligned.m64n64k16.f32.f16.f16 "
    "{%0, %1, %2, %3, %4, %5, %6, %7, %8, %9, %10, %11, %12, %13, %14, %15, "
    "%16, %17, %18, %19, %20, %21, %22, %23, %24, %25, %26, %27, %28, %29, %30, %31}, "
    "{%32, %33, %34, %35}, %36, p, 1, 1, 0;\n}\n"
    : "=f"(d[0]), "=f"(d[1]), "=f"(d[2]), "=f"(d[3]), "=f"(d[4]), "=f"(d[5]), "=f"(d[6]), "=f"(d[7]),
      "=f"(d[8]), "=f"(d[9]), "=f"(d[10]), "=f"(d[11]), "=f"(d[12]), "=f"(d[13]), "=f"(d[14]), "=f"(d[15]),
      "=f"(d[16]), "=f"(d[17]), "=f"(d[18]), "=f"(d[19]), "=f"(d[20]), "=f"(d[21]), "=f"(d[22]), "=f"(d[23]),
      "=f"(d[24]), "=f"(d[25]), "=f"(d[26]), "=f"(d[27]), "=f"(d[28]), "=f"(d[29]), "=f"(d[30]), "=f"(d[31])
    : "r"(a0), "r"(a1), "r"(a2), "r"(a3), "l"(db), "r"(scale_d));
}

__device__ __forceinline__ void wg_n64_rs_nb_f16_f16_z(uint32_t (&d)[16], uint32_t a0, uint32_t a1, uint32_t a2, uint32_t a3, uint64_t db, int scale_d) {
  asm volatile("{\n.reg .pred p;\nsetp.ne.b32 p, %21, 0;\n"
    "wgmma.mma_async.sync.aligned.m64n64k16.f16.f16.f16 "
    "{%0, %1, %2, %3, %4, %5, %6, %7, %8, %9, %10, %11, %12, %13, %14, %15}, "
    "{%16, %17, %18, %19}, %20, p, 1, 1, 0;\n}\n"
    : "=r"(d[0]), "=r"(d[1]), "=r"(d[2]), "=r"(d[3]), "=r"(d[4]), "=r"(d[5]), "=r"(d[6]), "=r"(d[7]),
      "=r"(d[8]), "=r"(d[9]), "=r"(d[10]), "=r"(d[11]), "=r"(d[12]), "=r"(d[13]), "=r"(d[14]), "=r"(d[15])
    : "r"(a0), "r"(a1), "r"(a2), "r"(a3), "l"(db), "r"(scale_d));
}

#define DEVINL __device__ __forceinline__
DEVINL void wg_fence() { asm volatile("wgmma.fence.sync.aligned;" ::: "memory"); }
DEVINL void wg_commit() { asm volatile("wgmma.commit_group.sync.aligned;" ::: "memory"); }
template <int N> DEVINL void wg_wait() { asm volatile("wgmma.wait_group.sync.aligned %0;" ::"n"(N) : "memory"); }
DEVINL uint64_t mkdesc(uint32_t addr, uint32_t lbo, uint32_t sbo, int sw) {
  return (uint64_t)((addr & 0x3FFFF) >> 4) | ((uint64_t)(lbo >> 4) << 16) | ((uint64_t)(sbo >> 4) << 32) | ((uint64_t)sw << 62);
}
DEVINL void mbar_init(uint32_t bar, uint32_t cnt) { asm volatile("mbarrier.init.shared::cta.b64 [%0], %1;" ::"r"(bar), "r"(cnt) : "memory"); }
DEVINL void mbar_arrive(uint32_t bar) { asm volatile("mbarrier.arrive.shared::cta.b64 _, [%0];" ::"r"(bar) : "memory"); }
DEVINL bool mbar_try(uint32_t bar, uint32_t parity) {
  uint32_t ok;
  asm volatile("{\n.reg .pred p;\nmbarrier.try_wait.parity.shared::cta.b64 p, [%1], %2;\nselp.u32 %0, 1, 0, p;\n}" : "=r"(ok) : "r"(bar), "r"(parity) : "memory");
  return ok;
}
DEVINL bool mbar_test(uint32_t bar, uint32_t parity) {
  uint32_t ok;
  asm volatile("{\n.reg .pred p;\nmbarrier.test_wait.parity.shared::cta.b64 p, [%1], %2;\nselp.u32 %0, 1, 0, p;\n}" : "=r"(ok) : "r"(bar), "r"(parity) : "memory");
  return ok;
}
DEVINL void mbar_hint(uint32_t bar, uint32_t parity) {
#pragma unroll 1
  for (uint32_t n = 0; n < 16u; n++) if (mbar_try(bar, parity)) break;
}
DEVINL void mbar_wait(uint32_t bar, uint32_t parity) {
#pragma unroll 1
  for (uint32_t n = 0; n < 100000u; n++) if (mbar_try(bar, parity)) break;
}
#define EL(txt) "{\n.reg .pred pe;\nelect.sync _|pe, 0xffffffff;\n@pe " txt "\n}"
DEVINL void e_expect_tx(uint32_t bar, uint32_t bytes) { asm volatile(EL("mbarrier.arrive.expect_tx.shared::cta.b64 _, [%0], %1;") ::"r"(bar), "r"(bytes) : "memory"); }
DEVINL void e_arrive(uint32_t bar) { asm volatile(EL("mbarrier.arrive.shared::cta.b64 _, [%0];") ::"r"(bar) : "memory"); }
DEVINL void e_arrive_if(uint32_t bar, int c) {
  asm volatile("{\n.reg .pred pe;\nelect.sync _|pe, 0xffffffff;\nsetp.ne.and.b32 pe, %1, 0, pe;\n@pe mbarrier.arrive.shared::cta.b64 _, [%0];\n}" ::"r"(bar), "r"(c) : "memory");
}
DEVINL void e_red(uint32_t* p) { asm volatile(EL("red.release.gpu.global.add.u32 [%0], 1;") ::"l"(p) : "memory"); }
DEVINL void e_red_relaxed(uint32_t* p) { asm volatile(EL("red.relaxed.gpu.global.add.u32 [%0], 1;") ::"l"(p) : "memory"); }
DEVINL void tma_ld(uint32_t dst, const CUtensorMap* m, int c0, int c1, uint32_t bar) {
  asm volatile(EL("cp.async.bulk.tensor.2d.shared::cluster.global.mbarrier::complete_tx::bytes [%0], [%1, {%3, %4}], [%2];")
               ::"r"(dst), "l"(m), "r"(bar), "r"(c0), "r"(c1) : "memory");
}
DEVINL void tma_ld3(uint32_t dst, const CUtensorMap* m, int c0, int c1, int c2, uint32_t bar) {
  asm volatile(EL("cp.async.bulk.tensor.3d.shared::cluster.global.mbarrier::complete_tx::bytes [%0], [%1, {%3, %4, %5}], [%2];")
               ::"r"(dst), "l"(m), "r"(bar), "r"(c0), "r"(c1), "r"(c2) : "memory");
}
DEVINL void tma_ld5(uint32_t dst, const CUtensorMap* m, int c2, int c3, int c4, uint32_t bar) {
  asm volatile(EL("cp.async.bulk.tensor.5d.shared::cluster.global.mbarrier::complete_tx::bytes [%0], [%1, {0, 0, %3, %4, %5}], [%2];")
               ::"r"(dst), "l"(m), "r"(bar), "r"(c2), "r"(c3), "r"(c4) : "memory");
}
DEVINL void tma_ld_mc(uint32_t dst, const CUtensorMap* m, int c0, int c1, uint32_t bar) {
  asm volatile(EL("cp.async.bulk.tensor.2d.shared::cluster.global.mbarrier::complete_tx::bytes.multicast::cluster [%0], [%1, {%3, %4}], [%2], %5;")
               ::"r"(dst), "l"(m), "r"(bar), "r"(c0), "r"(c1), "h"((uint16_t)3) : "memory");
}
DEVINL void e_arrive_both(uint32_t bar) {
  asm volatile("{\n.reg .pred pe;\n.reg .b32 r0, r1;\nelect.sync _|pe, 0xffffffff;\nmapa.shared::cluster.u32 r0, %0, 0;\nmapa.shared::cluster.u32 r1, %0, 1;\n"
               "@pe mbarrier.arrive.shared::cluster.b64 _, [r0];\n@pe mbarrier.arrive.shared::cluster.b64 _, [r1];\n}" ::"r"(bar) : "memory");
}
DEVINL void tma_st(const CUtensorMap* m, int c0, int c1, uint32_t src) {
  asm volatile(EL("cp.async.bulk.tensor.2d.global.shared::cta.bulk_group [%0, {%2, %3}], [%1];") ::"l"(m), "r"(src), "r"(c0), "r"(c1) : "memory");
}
DEVINL void bulk_commit() { asm volatile("cp.async.bulk.commit_group;" ::: "memory"); }
template <int N> DEVINL void bulk_wait_n() { asm volatile("cp.async.bulk.wait_group %0;\nbar.warp.sync 0xffffffff;" ::"n"(N) : "memory"); }
DEVINL void l2_prefetch(const void* g, uint32_t bytes) { asm volatile(EL("cp.async.bulk.prefetch.L2.global [%0], %1;") ::"l"(g), "r"(bytes) : "memory"); }
DEVINL void fence_async_smem() { asm volatile("fence.proxy.async.shared::cta;" ::: "memory"); }
DEVINL void fence_async_gl() { asm volatile("fence.proxy.async.global;" ::: "memory"); }
DEVINL void cluster_wait() { asm volatile("barrier.cluster.wait.aligned;" ::: "memory"); }
DEVINL void bar_sync(int id, int n) { asm volatile("bar.sync %0, %1;" ::"r"(id), "r"(n) : "memory"); }
DEVINL void bar_arrive(int id, int n) { asm volatile("bar.arrive %0, %1;" ::"r"(id), "r"(n) : "memory"); }
DEVINL uint32_t ld_acquire(const uint32_t* p) { uint32_t v; asm volatile("ld.acquire.gpu.global.u32 %0, [%1];" : "=r"(v) : "l"(p) : "memory"); return v; }
DEVINL void watch(const uint32_t* p, uint32_t target, uint32_t all, uint32_t tag, uint32_t slot) {
  uint32_t seen = 0;
#pragma unroll 1
  for (uint32_t n = 0; n < 200000u && seen != all; n++) {
    const uint32_t m = __ballot_sync(~0u, (int)(ld_acquire(p) - target) >= 0) & all;
    if (m != seen) { seen = m; asm volatile("st.release.cta.shared.u32 [%0], %1;" ::"r"(slot), "r"(tag << 16 | m) : "memory"); }
  }
}
template <bool RELAXED = false> DEVINL void await_bit(uint32_t slot, uint32_t tag, int j, uint32_t& rdy) {
  if ((rdy >> j) & 1) return;
#pragma unroll 1
  for (uint32_t n = 0; n < 8000000u; n++) {
    uint32_t v;
    asm volatile("ld.acquire.cta.shared.u32 %0, [%1];" : "=r"(v) : "r"(slot) : "memory");
    if ((v >> 16) == tag && ((v >> j) & 1)) { rdy = v; break; }
    if (RELAXED) __nanosleep(200);
  }
  asm volatile("fence.proxy.async.global;" ::: "memory");
}
DEVINL void poll_ge(const uint32_t* p, uint32_t target) {
#pragma unroll 1
  for (uint32_t n = 0; n < 200000u; n++) if (__all_sync(~0u, (int)(ld_acquire(p) - target) >= 0)) break;
}
DEVINL int lane_id() { int v; asm volatile("mov.u32 %0, %%laneid;" : "=r"(v)); return v; }
__host__ DEVINL int remap(int v) {
  const int c = v >> 1, u = c - 36, r = (u * 37) >> 8;
  const int L = c < 4 ? 32 + 8 * c : c < 36 ? c - 4 : 33 + u + r;
  return 2 * L + (v & 1);
}
DEVINL int block_id() { int v; asm volatile("mov.u32 %0, %%ctaid.x;" : "=r"(v)); return v; }
#define cta_id() prm.map[block_id()]
#define IDS() const int lane = lane_id(), b = cta_id(), bm = b >> 4, bn = b & 15, rank = b & 1, pm = 2 * bm + (bn >> 3), pn = bn & 7, po = pm & 1; \
  (void)lane; (void)bm; (void)bn; (void)rank; (void)pm; (void)pn; (void)po
DEVINL void st_tagged(uint4* p, uint32_t a, uint32_t b, uint32_t c, uint32_t tag) {
  asm volatile("{\n.reg .b64 u, v;\n.reg .b128 t;\nmov.b64 u, {%1, %2};\nmov.b64 v, {%3, %4};\nmov.b128 t, {u, v};\nst.relaxed.gpu.global.b128 [%0], t;\n}"
               ::"l"(p), "r"(a), "r"(b), "r"(c), "r"(tag) : "memory");
}
DEVINL uint32_t ld_tagged(const uint4* p, uint32_t* r) {
  uint32_t tag;
  asm volatile("{\n.reg .b64 u, v;\n.reg .b128 t;\nld.relaxed.gpu.global.b128 t, [%4];\nmov.b128 {u, v}, t;\nmov.b64 {%0, %1}, u;\nmov.b64 {%2, %3}, v;\n}"
               : "=r"(r[0]), "=r"(r[1]), "=r"(r[2]), "=r"(tag) : "l"(p) : "memory");
  return tag;
}
DEVINL float ex2(float x) { float y; asm("ex2.approx.ftz.f32 %0, %1;" : "=f"(y) : "f"(x)); return y; }
DEVINL float rcp(float x) { float y; asm("rcp.approx.ftz.f32 %0, %1;" : "=f"(y) : "f"(x)); return y; }
DEVINL uint32_t pack2(float lo, float hi) { uint32_t r; asm("cvt.rn.bf16x2.f32 %0, %1, %2;" : "=r"(r) : "f"(hi), "f"(lo)); return r; }
DEVINL uint32_t pack2h(float lo, float hi) { uint32_t r; asm("cvt.rn.f16x2.f32 %0, %1, %2;" : "=r"(r) : "f"(hi), "f"(lo)); return r; }
DEVINL uint32_t hadd2(uint32_t a, uint32_t b) { uint32_t r; asm("add.rn.f16x2 %0, %1, %2;" : "=r"(r) : "r"(a), "r"(b)); return r; }
DEVINL uint32_t hfma2(uint32_t a, uint32_t b, uint32_t c) { uint32_t r; asm("fma.rn.f16x2 %0, %1, %2, %3;" : "=r"(r) : "r"(a), "r"(b), "r"(c)); return r; }
DEVINL float bf_lo(uint32_t w) { return __uint_as_float(w << 16); }
DEVINL float bf_hi(uint32_t w) { return __uint_as_float(w & 0xFFFF0000u); }
DEVINL float bf_round(float x) { return bf_lo(pack2(x, 0.f)); }
DEVINL uint32_t add_bf16x2(uint32_t a, uint32_t b) { uint32_t r; asm("add.rn.bf16x2 %0, %1, %2;" : "=r"(r) : "r"(a), "r"(b)); return r; }
DEVINL void stsm4(uint32_t addr, uint32_t a, uint32_t b, uint32_t c, uint32_t d) {
  asm volatile("stmatrix.sync.aligned.m8n8.x4.shared.b16 [%0], {%1, %2, %3, %4};" ::"r"(addr), "r"(a), "r"(b), "r"(c), "r"(d) : "memory");
}
DEVINL void ldsm4(uint32_t addr, uint32_t (&r)[4]) {
  asm volatile("ldmatrix.sync.aligned.m8n8.x4.shared.b16 {%0, %1, %2, %3}, [%4];" : "=r"(r[0]), "=r"(r[1]), "=r"(r[2]), "=r"(r[3]) : "r"(addr) : "memory");
}
DEVINL void ldsm4t(uint32_t addr, uint32_t (&r)[4]) {
  asm volatile("ldmatrix.sync.aligned.m8n8.x4.trans.shared.b16 {%0, %1, %2, %3}, [%4];" : "=r"(r[0]), "=r"(r[1]), "=r"(r[2]), "=r"(r[3]) : "r"(addr) : "memory");
}
DEVINL void sts128(uint32_t addr, uint32_t a, uint32_t b, uint32_t c, uint32_t d) {
  asm volatile("st.shared.v4.b32 [%0], {%1, %2, %3, %4};" ::"r"(addr), "r"(a), "r"(b), "r"(c), "r"(d) : "memory");
}
DEVINL float2 lds64f(uint32_t addr) { float2 v; asm volatile("ld.shared.v2.f32 {%0, %1}, [%2];" : "=f"(v.x), "=f"(v.y) : "r"(addr) : "memory"); return v; }
DEVINL void mma16816(float (&d)[4], uint32_t a0, uint32_t a1, uint32_t a2, uint32_t a3, uint32_t b0, uint32_t b1) {
  asm("mma.sync.aligned.m16n8k16.row.col.f32.bf16.bf16.f32 {%0, %1, %2, %3}, {%4, %5, %6, %7}, {%8, %9}, {%0, %1, %2, %3};"
               : "+f"(d[0]), "+f"(d[1]), "+f"(d[2]), "+f"(d[3]) : "r"(a0), "r"(a1), "r"(a2), "r"(a3), "r"(b0), "r"(b1));
}
template <int N> DEVINL void fence_regs(float (&d)[N]) {
#pragma unroll
  for (int i = 0; i < N; i++) asm volatile("" : "+f"(d[i])::"memory");
}
template <int N> DEVINL void fence_regs(uint32_t (&d)[N]) {
#pragma unroll
  for (int i = 0; i < N; i++) asm volatile("" : "+r"(d[i])::"memory");
}
DEVINL void lds128(uint32_t addr, uint32_t* r) {
  asm volatile("ld.shared.v4.b32 {%0, %1, %2, %3}, [%4];" : "=r"(r[0]), "=r"(r[1]), "=r"(r[2]), "=r"(r[3]) : "r"(addr) : "memory");
}
DEVINL void sched_fence() { asm volatile("griddepcontrol.launch_dependents;" ::: "memory"); }

__device__ __align__(1024) bf16 g_xs[2048 * 1024];
__device__ __align__(1024) bf16 g_os[2048 * 1024];
__device__ __align__(1024) bf16 g_k[32 * 2048 * 32];
__device__ __align__(1024) bf16 g_v[32 * 2048 * 32];
__device__ __align__(16) uint32_t g_esc[4 * 65536 * 16];
__device__ __align__(128) float2 g_stats[8 * 2048];
__device__ __align__(16) float g_csp[2 * 16 * 8 * 192];
__device__ __align__(128) float g_kn[2 * 128 * 16];
__device__ __align__(128) uint4 g_halo[2 * 128 * 12 * 32];
__device__ __align__(128) uint32_t g_cnt[256 * 32];
__device__ uint32_t g_epoch;

DEVINL uint32_t* cnt_x(int l, int bm) { return g_cnt + (l * 8 + bm) * 32; }
DEVINL uint32_t* cnt_o(int l, int pm, int h) { return g_cnt + (32 + (l * 16 + pm) * 2 + h) * 32; }
DEVINL uint32_t* cnt_kv(int lb, int bn) { return g_cnt + (160 + lb * 16 + bn) * 32; }
DEVINL uint32_t* cnt_ad(int bn) { return g_cnt + (192 + bn) * 32; }
DEVINL uint32_t* cnt_cs(int t, int bn) { return g_cnt + (208 + t * 16 + bn) * 32; }

DEVINL int qord(int i, int l, int pn) { return l == 0 ? i : i < 4 ? ((2 * pn) ^ (i & 2)) + (i & 1) : i - 4 < 2 * (pn & 6) ? i - 4 : i; }
struct Params {
  CUtensorMap m[17];
  const bf16* x0;
  const bf16* wq[2];
  uint32_t zero;
  int map[128];
  struct { uint64_t kd, vd; } kv[17];
};
enum { M_X0A = 0, M_XSA, M_WQA, M_WQB, M_WOA, M_WOB, M_OS, M_K, M_V, M_X0R, M_XSR, M_XSO, M_OUT, M_XST, M_X0H, M_K16, M_V16, M_COUNT };

constexpr uint32_t QSTG = 57344;
constexpr uint32_t T0 = 65536, TSTG = 32768;
constexpr uint32_t ONES = 230400;
constexpr uint32_t PSTG = 32768, RES = 196608;
constexpr uint32_t KSC = 98304, VSC = 133120, HRS = 167936;
constexpr uint32_t ROWST = 229376, COLS = 231424, BARS = 232192, SMEM_BYTES = 232448;
constexpr uint32_t B_QF = BARS, B_QE = BARS + 32, B_TF = BARS + 64, B_TE = BARS + 96, B_PF = BARS + 128, B_PE = BARS + 176,
                   B_RF = BARS + 224, W_X = BARS + 232, W_O = BARS + 236, B_QL = BARS + 240, B_PA = BARS + 248;
enum { NB_ST = 1, NB_KV = 2  , NB_DONE = 3, NB_SC = 4, NB_SIG = 5  , NB_KN = 9  , NB_X = 11, NB_HALO = 12  , NB_X0 = 15 };

DEVINL uint32_t pslot_b(uint32_t s) { return ((0x320415u >> (4 * s)) & 7) * 16384u; }
DEVINL uint32_t pslot_a(uint32_t s, int l) { return 98304u + ((((l & 1) ? 0x541230u : 0x041235u) >> (4 * s)) & 7) * 16384u; }

constexpr float QSCALE = 0.17677669529663687f * 1.4426950408889634f;
constexpr uint32_t QPARK = 32768;

DEVINL uint32_t exp2_pair(float s0, float s1, uint32_t half, uint32_t lsb) {
  constexpr float M = 383.f - 0.591914f + 0.00390625f;
  const uint32_t B = __byte_perm(__float_as_uint(s0 + M), __float_as_uint(s1 + M), 0x6521);
  uint32_t w, E, r;
  asm("lop3.b32 %0, %1, 0x807F807F, %2, 0xEA;" : "=r"(w) : "r"(B), "r"(half));
  asm("lop3.b32 %0, %1, 0x7F807F80, %2, 0xEA;" : "=r"(E) : "r"(B), "r"(lsb));
  asm("fma.rn.bf16x2 %0, %1, %2, %3;" : "=r"(r) : "r"(B), "r"(w), "r"(E));
  return r;
}
DEVINL uint32_t exp2_h2(uint32_t s, uint32_t nsig) {
  uint32_t r = hadd2(s, 0x65F565F5u), d;
  asm("{.reg .b64 t; cvt.u64.u32 t, %0; cvt.u32.u64 %0, t;}" : "+r"(r));
  const uint32_t w = hfma2(s, 0x38A038A0u, hfma2(r, 0xB8A0B8A0u, nsig));
  const uint32_t m = hfma2(w, w, 0x48244833u);
  asm("{.reg .b32 t; shf.l.clamp.b32 t, %2, %1, 7; add.u32 %0, t, %2;}" : "=r"(d) : "r"(r), "r"(m));
  return d;
}
DEVINL uint32_t unesc(uint32_t u, const uint32_t* esc) {
  if ((u & 0x7C00u) == 0x7C00u || (u & 0x7C000000u) == 0x7C000000u) return __ldcg(esc);
  float lo, hi;
  asm("{.reg .f16 a, b; mov.b32 {a, b}, %2; cvt.f32.f16 %0, a; cvt.f32.f16 %1, b;}" : "=f"(lo), "=f"(hi) : "r"(u));
  return pack2(lo, hi);
}

DEVINL void attn_slow(const uint32_t (&q)[8], int head, const uint32_t* kesc, float (&res)[20], int lane) {
  const int g = lane >> 2, qd = lane & 3;
  const bf16* kb = g_k + (size_t)head * 2048 * 32;
  const bf16* vb = g_v + (size_t)head * 2048 * 32;
  float o[4][4], m0 = -INFINITY, m1 = -INFINITY, l0 = 0.f, l1 = 0.f;
#pragma unroll
  for (int j = 0; j < 4; j++) { o[j][0] = o[j][1] = o[j][2] = o[j][3] = 0.f; }
#pragma unroll 1
  for (int k0 = 0; k0 < 2048; k0 += 16) {
    float s[2][4];
#pragma unroll
    for (int nt = 0; nt < 2; nt++) {
      s[nt][0] = s[nt][1] = s[nt][2] = s[nt][3] = 0.f;
      const uint32_t* kp = (const uint32_t*)(kb + (size_t)(k0 + nt * 8 + g) * 32) + qd;
      const uint32_t* ke = kesc + (k0 + nt * 8 + g) * 16 + qd;
      const uint32_t k0r = unesc(__ldcg(kp), ke), k1r = unesc(__ldcg(kp + 4), ke + 4), k2r = unesc(__ldcg(kp + 8), ke + 8), k3r = unesc(__ldcg(kp + 12), ke + 12);
      __syncwarp();
      mma16816(s[nt], q[0], q[1], q[2], q[3], k0r, k1r);
      mma16816(s[nt], q[4], q[5], q[6], q[7], k2r, k3r);
    }
    float a0 = fmaxf(fmaxf(s[0][0], s[0][1]), fmaxf(s[1][0], s[1][1]));
    float a1 = fmaxf(fmaxf(s[0][2], s[0][3]), fmaxf(s[1][2], s[1][3]));
    a0 = fmaxf(a0, __shfl_xor_sync(~0u, a0, 1)); a0 = fmaxf(a0, __shfl_xor_sync(~0u, a0, 2));
    a1 = fmaxf(a1, __shfl_xor_sync(~0u, a1, 1)); a1 = fmaxf(a1, __shfl_xor_sync(~0u, a1, 2));
    const float n0 = fmaxf(m0, a0), n1 = fmaxf(m1, a1);
    const float c0 = (m0 == n0) ? 1.f : ex2(m0 - n0), c1 = (m1 == n1) ? 1.f : ex2(m1 - n1);
    m0 = n0; m1 = n1;
    const uint32_t p0 = pack2(ex2(s[0][0] - n0), ex2(s[0][1] - n0)), p1 = pack2(ex2(s[0][2] - n1), ex2(s[0][3] - n1));
    const uint32_t p2 = pack2(ex2(s[1][0] - n0), ex2(s[1][1] - n0)), p3 = pack2(ex2(s[1][2] - n1), ex2(s[1][3] - n1));
    l0 = l0 * c0 + bf_lo(p0) + bf_hi(p0) + bf_lo(p2) + bf_hi(p2);
    l1 = l1 * c1 + bf_lo(p1) + bf_hi(p1) + bf_lo(p3) + bf_hi(p3);
#pragma unroll
    for (int j = 0; j < 4; j++) {
      o[j][0] *= c0; o[j][1] *= c0; o[j][2] *= c1; o[j][3] *= c1;
      const unsigned short* vp = (const unsigned short*)(vb + (size_t)(k0 + 2 * qd) * 32 + j * 8 + g);
      const uint32_t b0 = (uint32_t)__ldcg(vp) | ((uint32_t)__ldcg(vp + 32) << 16);
      const uint32_t b1 = (uint32_t)__ldcg(vp + 256) | ((uint32_t)__ldcg(vp + 288) << 16);
      mma16816(o[j], p0, p1, p2, p3, b0, b1);
    }
  }
  l0 += __shfl_xor_sync(~0u, l0, 1); l0 += __shfl_xor_sync(~0u, l0, 2);
  l1 += __shfl_xor_sync(~0u, l1, 1); l1 += __shfl_xor_sync(~0u, l1, 2);
#pragma unroll
  for (int j = 0; j < 4; j++) { res[4 * j] = o[j][0]; res[4 * j + 1] = o[j][1]; res[4 * j + 2] = o[j][2]; res[4 * j + 3] = o[j][3]; }
  res[16] = l0; res[18] = l1;
}

__global__ void __cluster_dims__(2, 1, 1) __launch_bounds__(384, 1) fused_kernel(const __grid_constant__ Params prm) {
  extern __shared__ __align__(1024) char smem[];
  const uint32_t sb = (uint32_t)__cvta_generic_to_shared(smem);
  const int tid = threadIdx.x, lane = tid & 31;
  const int wg = __shfl_sync(0xffffffffu, tid >> 7, 0);
  const int w = __shfl_sync(0xffffffffu, (tid >> 5) & 3, 0);
  const int bm = remap(blockIdx.x) >> 4, bn = remap(blockIdx.x) & 15;

  auto first_tile = [&](int kt) {
    e_expect_tx(sb + B_QF + 8 * kt, QSTG);
    tma_ld(sb + kt * QSTG, &prm.m[M_X0A], kt * 64, bm * 256, sb + B_QF + 8 * kt);
    tma_ld3(sb + kt * QSTG + 32768, &prm.m[M_WQA], bn * 64, kt * 64, 0, sb + B_QF + 8 * kt);
  };
  auto init4 = [&](uint32_t bar, uint32_t c0, uint32_t c1, uint32_t c2, uint32_t c3) {
    asm volatile("{\n.reg .pred pe;\nelect.sync _|pe, 0xffffffff;\n@pe mbarrier.init.shared::cta.b64 [%0], %1;\n@pe mbarrier.init.shared::cta.b64 [%0+8], %2;\n"
                 "@pe mbarrier.init.shared::cta.b64 [%0+16], %3;\n@pe mbarrier.init.shared::cta.b64 [%0+24], %4;\n@pe fence.mbarrier_init.release.cluster;\n}"
                 ::"r"(bar), "r"(c0), "r"(c1), "r"(c2), "r"(c3) : "memory");
  };
  if (wg < 2) {
    const uint32_t k = wg * 4 + w, lo = (0x1411814u >> (4 * k)) & 15, hi = (0x1441814u >> (4 * k)) & 15;
    if (tid < 32) asm volatile("prefetch.global.L2 [%0];" ::"l"(prm.x0 + (size_t)(bm * 256 + bn * 16 + (tid & 15)) * 1024 + (tid >> 4) * 64));
    else if (tid < 80) asm volatile("prefetch.global.L2 [%0];" ::"l"(prm.wq[0] + (bm * 16 + (tid & 15)) * 3072 + ((tid >> 4) - 2) * 1024 + bn * 64));
    __syncwarp();
    if (k < 7) init4(sb + B_QE + 32 * k, lo, lo, hi, k == 6 ? 2 : hi);
    __syncwarp();
    if (k == 6 && lane == 0) *(volatile unsigned long long*)(smem + W_X) = 0ull;
  } else if (w == 0) {
    init4(sb + B_QF, 1, 1, 1, 1);
    __syncwarp();
    first_tile(0);
  }
  __syncthreads();
  asm volatile("barrier.cluster.arrive.relaxed.aligned;" ::: "memory");

  if (wg == 2) {
    asm volatile("setmaxnreg.dec.sync.aligned.u32 56;");
    const uint32_t ep1 = *(volatile uint32_t*)&g_epoch + 1;
    if (w == 0) {
      first_tile(1);
      mbar_wait(sb + B_QF, 0);
      first_tile(2); first_tile(3);
#pragma unroll 1
      for (int kt = 4; kt < 16; kt++) l2_prefetch(prm.wq[0] + kt * 196608 + blockIdx.x * 1536, 3072);
      cluster_wait();
#pragma unroll 1
      for (int l = 0; l < 4; l++) {
        IDS();
        const CUtensorMap* mw = &prm.m[M_WQA + (l & 1)];
        const CUtensorMap* mx = &prm.m[l == 0 ? M_X0A : M_XSA];
        const CUtensorMap* mh = &prm.m[l == 0 ? M_X0H : M_XSO];
        const CUtensorMap* mo = &prm.m[M_WOA + (l & 1)];
        auto q_b = [&](int i) {
          const int s = i & 3;
          mbar_wait(sb + B_QE + 8 * s, ((i >> 2) & 1) ^ 1);
          e_expect_tx(sb + B_QF + 8 * s, QSTG);
          tma_ld3(sb + s * QSTG + 32768, mw, bn * 64, qord(i, l, pn) * 64, 0, sb + B_QF + 8 * s);
        };
        uint32_t rdy = l ? 0u : ~0u;
        auto q_a = [&](int i) {
          const int kt = qord(i, l, pn);
          await_bit(sb + W_X, l, kt >> 1, rdy);
          if (i < 4) tma_ld(sb + i * QSTG, mx, kt * 64, bm * 256, sb + B_QF + 8 * i);
          else tma_ld_mc(sb + (i & 3) * QSTG + rank * 16384, mh, kt * 64, bm * 256 + rank * 128, sb + B_QF + 8 * (i & 3));
        };
        if (l > 0) {
          await_bit(sb + W_X, l, pn, rdy);
#pragma unroll 1
          for (int i = 0; i < 2; i++) {
            e_expect_tx(sb + B_QF + 8 * i, 16384);
            tma_ld(sb + i * QSTG + (po ^ 1) * 16384, &prm.m[M_XSO], (2 * pn + i) * 64, (pm ^ 1) * 128, sb + B_QF + 8 * i);
          }
          mbar_wait(sb + B_QF, 0);
          q_a(2);
          mbar_wait(sb + B_QF + 8, 0);
        }
#pragma unroll 1
        for (int i = l ? 3 : 4; i < 16; i++) {
          if (l == 3 && i == 12) poll_ge(cnt_ad(bn), ep1 * 16);
          q_b(i); q_a(i);
        }
        if (l & 1) {
          bar_sync(NB_KV, 288);
          sts128(sb + ONES + lane * 32, 0x3f803f80u, 0x3f803f80u, 0x3f803f80u, 0x3f803f80u);
          sts128(sb + ONES + lane * 32 + 16, 0x3f803f80u, 0x3f803f80u, 0x3f803f80u, 0x3f803f80u);
          fence_async_smem();
          __syncwarp();
          e_arrive(sb + B_TF);
          const int krow = 2 * bn * 2048 + bm * 256;
          uint32_t* kvc = cnt_kv(l >> 1, bn);
          bar_sync(NB_DONE, 288);
          e_red(kvc + bm);
          uint32_t seen = 0;
#pragma unroll 1
          for (int it = 1; it < 16; it++) {
            const int s = it & 3, blk = it;
            if (it == 4) {
              bar_sync(NB_KV + 12, 288);
              mbar_wait(sb + B_TF + 24, 0);
              tma_st(&prm.m[M_K], 0, krow + 2048, sb);
              tma_st(&prm.m[M_V], 0, krow + 2048, sb + 16384);
              bulk_commit();
            }
            if (it == 5) { bulk_wait_n<0>(); e_red(kvc + bm); }
            if (it == 12) { e_expect_tx(sb + B_RF, 32768); tma_ld3(sb + RES, &prm.m[M_XSR], 0, pm * 128, 2 * pn, sb + B_RF); }
            if (it == 2 || it == 3) mbar_wait(sb + B_TF + 8 * (it - 1), 0);
            mbar_wait(sb + B_TE + 8 * s, ((it >> 2) & 1) ^ 1);
            if (it < 8) {
#pragma unroll 1
              for (uint32_t n = 0; n < 200000u && !((seen >> it) & 1); n++)
                seen = __ballot_sync(~0u, (int)(ld_acquire(kvc + ((bm + lane) & 7)) - (ep1 * 2 - 1)) >= 0);
              fence_async_gl();
            } else if (it == 8) { poll_ge(kvc + (lane & 7), ep1 * 2); fence_async_gl(); }
            const int row = (2 * bn + (it >> 3)) * 2048 + ((bm + blk) & 7) * 256;
            e_expect_tx(sb + B_TF + 8 * s, 32768);
            tma_ld(sb + T0 + s * TSTG, &prm.m[M_K], 0, row, sb + B_TF + 8 * s);
            tma_ld(sb + T0 + s * TSTG + 16384, &prm.m[M_V], 0, row, sb + B_TF + 8 * s);
          }
        }
        auto p_b = [&](int i, uint32_t s, uint32_t par) {
          mbar_wait(sb + B_PE + 8 * s, par ^ 1);
          e_expect_tx(sb + B_PF + 8 * s, PSTG);
          tma_ld5(sb + pslot_b(s), mo, i >> 3, 2 * (i & 7), 2 * pn, sb + B_PF + 8 * s);
        };
        auto p_a = [&](int i, uint32_t s) {
          await_bit(sb + W_O, l + 1, i, rdy);
          tma_ld_mc(sb + pslot_a(s, l) + rank * 8192, &prm.m[M_OS], i * 64, pm * 128 + rank * 64, sb + B_PF + 8 * s);
        };
        auto p_a2 = [&](int i) {
          await_bit(sb + W_O, l + 1, i, rdy);
          tma_ld(sb + pslot_a(i, l), &prm.m[M_OS], i * 64, pm * 128, sb + B_PF + 8 * i);
          tma_ld(sb + pslot_a(i, l) + 8192, &prm.m[M_OS], i * 64, pm * 128 + 64, sb + B_PF + 8 * i);
        };
        rdy = 0;
        if (l & 1) {
#pragma unroll 1
          for (int u = 0; u < 6; u++) { const int i = (0x205413 >> (4 * u)) & 7; if (u == 4) mbar_wait(sb + B_TE, 1); p_b(i, i, i < 4 ? 1 : 0); }
#pragma unroll 1
          for (int u = 0; u < 6; u++) {
            const int i = (0x542130 >> (4 * u)) & 7;
            if (!(u & 1)) mbar_wait(sb + B_TE + 8 + 4 * u, 1);
            if (u == 4) bar_sync(NB_ST, 64);
            p_a2(i);
          }
        } else {
#pragma unroll 1
          for (int u = 0; u < 6; u++) { const int i = (0x025413 >> (4 * u)) & 7; if (u == 0 || u == 3) mbar_wait(sb + B_QE + 8 * (u / 3), 1); p_b(i, i, 0); }
          mbar_wait(sb + B_QE + 24, 1);
          e_expect_tx(sb + B_RF, 32768);
          tma_ld3(sb + RES, &prm.m[l == 0 ? M_X0R : M_XSR], 0, pm * 128, 2 * pn, sb + B_RF);
          p_a2(0);
          bar_sync(NB_DONE, 64);
          e_arrive_both(sb + B_PA);
          p_a2(1);
          mbar_wait(sb + B_PA, (l >> 1) & 1);
#pragma unroll 1
          for (int i = 2; i < 6; i++) { if (i > 2) mbar_wait(sb + B_PF + 8 * (i - 3), 0); p_a(i, i); }
        }
        uint32_t s = 0, lap = 1;
#pragma unroll 1
        for (int i = 6; i < 16; i++) {
          p_b(i, s, ((s < 4 ? l : 0) + lap) & 1);
          p_a(i, s);
          if (++s == 6) { s = 0; lap++; }
        }
        const CUtensorMap* mn = &prm.m[M_WQA + ((l + 1) & 1)];
        if (l < 3) {
          mbar_wait(sb + B_PE + 8 * 4, 1); mbar_wait(sb + B_PE + 8 * 5, 1);
          tma_ld3(sb + 32768, mn, bn * 64, 2 * pn * 64, 0, sb + B_QL);
          mbar_wait(sb + B_PE + 8 * 0, l & 1);
          tma_ld3(sb + QSTG + 32768, mn, bn * 64, (2 * pn + 1) * 64, 0, sb + B_QL);
          mbar_wait(sb + B_PE + 8 * 1, l & 1);
          e_expect_tx(sb + B_QF + 16, QSTG);
          tma_ld3(sb + 2 * QSTG + 32768, mn, bn * 64, ((2 * pn) ^ 2) * 64, 0, sb + B_QF + 16);
        }
        if (l < 3) { bar_sync(NB_X, 288); e_expect_tx(sb + B_QL, 49152); }
      }
      if (blockIdx.x == 0 && lane_id() == 0) *(volatile uint32_t*)&g_epoch = ep1;
    } else {
      const int hw = w - 1;
      if (lane < 6 && 6 * hw + lane < M_COUNT) asm volatile("prefetch.tensormap [%0];" ::"l"(&prm.m[6 * hw + lane]) : "memory");
      __syncwarp();
      cluster_wait();
      mbar_wait(sb + B_QF, 0);
#pragma unroll 1
      for (int l = 0; l < 4; l++) {
        IDS();
        if (hw == 2 && l > 0) watch(cnt_x(l, bm) + (lane & 7), ep1 * 2, 0xFFu, l, sb + W_X);
        if (l == 0) {
#pragma unroll 1
          for (int r = 2 * hw; r < 16; r += 6) {
            const uint4* p = (const uint4*)(prm.x0 + (size_t)(b * 16 + r) * 1024) + lane;
            float s1[2] = {0.f, 0.f}, s2[2] = {0.f, 0.f};
#pragma unroll
            for (int i = 0; i < 8; i++) {
              const uint4 v = __ldg(p + 32 * i);
              const uint32_t u[4] = {v.x, v.y, v.z, v.w};
#pragma unroll
              for (int k = 0; k < 4; k++) { const float a = bf_lo(u[k]), c = bf_hi(u[k]); s1[i >> 2] += a + c; s2[i >> 2] = fmaf(a, a, fmaf(c, c, s2[i >> 2])); }
            }
#pragma unroll
            for (int o = 16; o; o >>= 1)
#pragma unroll
              for (int rr = 0; rr < 2; rr++) { s1[rr] += __shfl_xor_sync(~0u, s1[rr], o); s2[rr] += __shfl_xor_sync(~0u, s2[rr], o); }
            if (lane == 0) *(float4*)&g_stats[b * 16 + r] = make_float4(s1[0], s2[0], s1[1], s2[1]);
          }
        }
        if (l == 1) { uint32_t rdy = 0; await_bit<true>(sb + W_X, 1, pn, rdy); mbar_hint(sb + B_QF + 8, 0); }
        if (l < 2) {
          float cs[8];
#pragma unroll
          for (int i = 0; i < 8; i++) cs[i] = 0.f;
          const uint4* wp = (const uint4*)(prm.wq[l] + (size_t)(bm * 128 + (lane >> 3)) * 3072 + hw * 1024 + bn * 64) + (lane & 7);
#pragma unroll 8
          for (int i = 0; i < 32; i++) {
            const uint4 v = __ldg(wp + (size_t)i * 4 * 384);
            cs[0] += bf_lo(v.x); cs[1] += bf_hi(v.x); cs[2] += bf_lo(v.y); cs[3] += bf_hi(v.y);
            cs[4] += bf_lo(v.z); cs[5] += bf_hi(v.z); cs[6] += bf_lo(v.w); cs[7] += bf_hi(v.w);
          }
#pragma unroll
          for (int i = 0; i < 8; i++) { cs[i] += __shfl_xor_sync(~0u, cs[i], 8); cs[i] += __shfl_xor_sync(~0u, cs[i], 16); }
          if (lane < 8) {
            float4* d = (float4*)(g_csp + ((l * 16 + bn) * 8 + bm) * 192 + hw * 64 + lane * 8);
            d[0] = make_float4(cs[0], cs[1], cs[2], cs[3]); d[1] = make_float4(cs[4], cs[5], cs[6], cs[7]);
          }
          __syncwarp();
          asm volatile("fence.acq_rel.gpu;" ::: "memory");
          e_red_relaxed(cnt_cs(l, bn));
          if (l == 0) e_red_relaxed(cnt_x(0, bm) + pn);
          poll_ge(lane < 8 && l == 0 ? cnt_x(0, bm) + lane : cnt_cs(l, bn), ep1 * (lane < 8 && l == 0 ? 6 : 24));
        }
        if (l > 0) {
          uint32_t rdy = 0;
#pragma unroll 1
          for (int j = 0; j < 8; j++) await_bit<true>(sb + W_X, l, j, rdy);
        }
#pragma unroll 1
        for (int it = hw * 32 + lane; it < 176; it += 96) {
          const bool rows = it < 128;
          const float4* p = rows ? (const float4*)(g_stats + bm * 256) + it : (const float4*)(g_csp + ((l & 1) * 16 + bn) * 8 * 192) + (it - 128);
          const int stride = rows ? 1024 : 48, np = rows && l == 0 ? 1 : 8;
          float4 a = make_float4(0.f, 0.f, 0.f, 0.f);
#pragma unroll
          for (int k = 0; k < 8; k++) if (k < np) { const float4 v = __ldcg(p + k * stride); a.x += v.x; a.y += v.y; a.z += v.z; a.w += v.w; }
          if (rows) {
            const float m0 = a.x * (1.f / 1024.f), m1 = a.z * (1.f / 1024.f);
            const float v0 = fmaxf(a.y * (1.f / 1024.f) - m0 * m0, 0.f), v1 = fmaxf(a.w * (1.f / 1024.f) - m1 * m1, 0.f);
            const float r0 = __fdividef(1.f, bf_round(sqrtf(bf_round(bf_round(v0) + 1e-5f)))), r1 = __fdividef(1.f, bf_round(sqrtf(bf_round(bf_round(v1) + 1e-5f))));
            a = make_float4(r0, -bf_round(m0) * (l & 1 ? r0 : 1.f), r1, -bf_round(m1) * (l & 1 ? r1 : 1.f));
          }
          *(float4*)(smem + ROWST + it * 16) = a;
        }
        __syncwarp();
        if (lane == 0) asm volatile("red.release.cta.shared.add.u32 [%0], 0x100;" ::"r"(sb + W_X) : "memory");
        if (hw == 2) {
          if (!(l & 1)) {
            bar_sync(NB_ST, 288);
            const uint4* hp = g_halo + ((l >> 1) * 128 + b - 16) * 384 + lane;
#pragma unroll 1
            for (int h = 0; h < 2; h++) {
              uint32_t t[18];
#pragma unroll
              for (int i = 0; i < 18; i++) t[i] = 0;
#pragma unroll 1
              for (uint32_t n = bm ? 0 : 100000u; n < 100000u; n++) {
                uint32_t miss = 0;
#pragma unroll
                for (int i = 0; i < 6; i++) miss |= ld_tagged(hp + h * 192 + i * 32, &t[3 * i]) ^ ep1;
                if (__all_sync(~0u, !miss)) break;
              }
              mbar_wait(sb + B_QE + 16, 1);
              const uint32_t r = (lane & 7) + ((lane >> 3) & 1) * 8, rv = lane >> 2;
#pragma unroll
              for (int jj = 0; jj < 2; jj++) stsm4(sb + KSC + r * 128 + (((4 * h + 2 * jj + (lane >> 4)) ^ (r & 7)) << 4), t[4 * jj], t[4 * jj + 1], t[4 * jj + 2], t[4 * jj + 3]);
              const uint32_t ad = sb + VSC + rv * 128 + (((4 * h + (lane & 3)) ^ (rv & 7)) << 4);
              sts128(ad, t[8], t[10], t[12], t[14]); sts128(ad + 1024, t[9], t[11], t[13], t[15]);
              if (h == 0 && !(lane & 2)) *(uint32_t*)(smem + HRS + ((lane >> 2) + 8 * (lane & 1)) * 8) = t[16];
              bar_arrive(NB_HALO + h, 64);
            }
          } else {
            mbar_wait(sb + B_TF + 16, 0); mbar_wait(sb + B_TF + 16, 1);
            poll_ge(cnt_kv(l >> 1, bn) + (lane & 7), ep1 * 2);
            const uint4 v = __ldcg((const uint4*)(g_kn + ((l >> 1) * 128 + bn * 8) * 16) + lane);
            const uint32_t mx = max(max(v.x, v.y), max(v.z, v.w));
            const uint32_t m0 = __reduce_max_sync(~0u, (lane & 2) ? 0u : mx), m1 = __reduce_max_sync(~0u, (lane & 2) ? mx : 0u);
            if (lane == 0) *(uint2*)(smem + ROWST) = make_uint2(m0, m1);
            __syncwarp();
            bar_arrive(NB_KN, 160); bar_arrive(NB_KN + 1, 160);
            mbar_wait(sb + B_TF + 16, 0); mbar_wait(sb + B_TF + 16, 1);
          }
        } else {
#pragma unroll 1
          for (int i = 0; i < 2; i++) {
            const int h = l & 1 ? i : hw, g = l & 1 ? hw : i;
            bar_sync(NB_SIG + 2 * h + g, 160);
            if (!(l & 1) && i == 0) continue;
            if (i == 1 && hw == 1) bar_arrive(l & 1 ? NB_ST : NB_DONE, 64);
            asm volatile("fence.acq_rel.gpu;" ::: "memory");
            e_red_relaxed(cnt_o(l, 2 * bm + g, h) + (bn >> 1));
            if (!(l & 1)) e_red_relaxed(cnt_o(l, 2 * bm, h) + (bn >> 1));
            if (h == 1 && l == 1) e_red_relaxed(cnt_ad(bn));
          }
        }
        if (hw == 2) watch(cnt_o(l, pm, (lane >> 3) & 1) + (lane & 7), ep1 * 2, 0xFFFFu, l + 1, sb + W_O);
        if (hw == 0 && l < 3) {
          bar_sync(NB_X0, 288);
          e_red(cnt_x(l + 1, bm) + pn);
        }
      }
    }
  } else {
    asm volatile("setmaxnreg.inc.sync.aligned.u32 224;");
    const uint32_t zero = prm.zero;
    cluster_wait();
#pragma unroll 1
    for (int l = 0; l < 4; l++) {
      {
        float acc[2][96];
#pragma unroll
        for (int i = 0; i < 96; i++) { acc[0][i] = 0.f; acc[1][i] = 0.f; }
        fence_regs(acc[0]); fence_regs(acc[1]);
        const bool early = l > 0 && wg == ((cta_id() >> 3) & 1);
        uint32_t ep1 = 0;
#pragma unroll 1
        for (int kt = 0; kt < 16; kt++) {
          const int s = kt & 3;
          if (l > 0 && kt == 0) mbar_wait(sb + B_QL, (l + 1) & 1);
          if (!(early && kt < 2)) mbar_wait(sb + B_QF + 8 * s, (kt >> 2) & 1);
          const uint64_t da = mkdesc(sb + s * QSTG + wg * 16384, 16, 1024, 1), db = mkdesc(sb + s * QSTG + 32768, 8192, 1024, 1);
          wg_fence();
#pragma unroll
          for (int m = 1; m >= 0; m--) {
#pragma unroll
            for (int k = 0; k < 4; k++) wgmma_m64n192k16_ss_tb(acc[m], da + m * 512 + k * 2, db + k * 128, 1);
            wg_commit();
          }
          if (kt == 15 && !(l & 1)) bar_arrive(NB_ST, 288);
          if (kt == 4) ep1 = *(volatile uint32_t*)&g_epoch + 1;
          wg_wait<2>();
          if (early && (kt == 1 || kt == 2)) mbar_wait(sb + B_QF + 8 * (kt - 1), 0);
          if (kt > 0 && w == 0) e_arrive_both(sb + B_QE + 8 * ((kt - 1) & 3));
        }
#pragma unroll 1
        for (uint32_t n = 0; n < 4000000u; n++) {
          uint32_t v;
          asm volatile("ld.acquire.cta.shared.u32 %0, [%1];" : "=r"(v) : "r"(sb + W_X) : "memory");
          if ((v >> 8) == (uint32_t)(l * 256 + 3)) break;
        }
        IDS();
        const int g = lane >> 2, qd = lane & 3;
        float2 st[2][2];
#pragma unroll
        for (int m = 0; m < 2; m++)
#pragma unroll
          for (int hh = 0; hh < 2; hh++) st[m][hh] = lds64f(sb + ROWST + (wg * 128 + m * 64 + w * 16 + g + 8 * hh) * 8);
        float2 cs[4];
        auto load_cs = [&](int gi) {
#pragma unroll
          for (int j = 0; j < 4; j++) cs[j] = lds64f(sb + COLS + (gi * 32 + j * 8 + 2 * qd) * 4);
        };
        load_cs(2);
        auto drain = [&]() {
          wg_wait<0>(); fence_regs(acc[0]);
          if (w == 0) e_arrive_both(sb + B_QE + 8 * 3);
        };
        wg_wait<1>(); fence_regs(acc[1]);
        auto norm_tile = [&](int gi, int m, float sc, uint32_t (&t)[8], float (&nrm)[2], bool h16 = false) {
          const float r0 = st[m][0].x * sc, s0 = st[m][0].y * sc, r1 = st[m][1].x * sc, s1 = st[m][1].y * sc;
          float n0 = 0.f, n1 = 0.f;
#pragma unroll
          for (int j = 0; j < 4; j++) {
            const float* a = &acc[m][16 * gi + 4 * j];
            const float v0 = fmaf(a[0], r0, s0 * cs[j].x), v1 = fmaf(a[1], r0, s0 * cs[j].y);
            const float v2 = fmaf(a[2], r1, s1 * cs[j].x), v3 = fmaf(a[3], r1, s1 * cs[j].y);
            n0 = fmaf(v0, v0, fmaf(v1, v1, n0)); n1 = fmaf(v2, v2, fmaf(v3, v3, n1));
            t[2 * j] = h16 ? pack2h(v0, v1) : pack2(v0, v1); t[2 * j + 1] = h16 ? pack2h(v2, v3) : pack2(v2, v3);
          }
          nrm[0] = n0; nrm[1] = n1;
        };
        auto norm_group = [&](int gi, float sc, uint32_t (&t)[2][8], float (&nrm)[2][2]) { norm_tile(gi, 0, sc, t[0], nrm[0]); norm_tile(gi, 1, sc, t[1], nrm[1]); };
        uint32_t q[2][2][8];
        const uint32_t srow = (lane & 7) + ((lane >> 3) & 1) * 8;
        const uint32_t row0 = wg * 128 + w * 16;
        auto put_o = [&](int h, int m, const float (&o)[16], float i0, float i1) {
          IDS();
          bf16* op = g_os + (size_t)(bm * 256 + row0 + m * 64 + (lane >> 2)) * 1024 + h * 512 + bn * 32 + (lane & 3) * 8;
          *(uint4*)op = make_uint4(pack2(o[0] * i0, o[1] * i0), pack2(o[4] * i0, o[5] * i0), pack2(o[8] * i0, o[9] * i0), pack2(o[12] * i0, o[13] * i0));
          *(uint4*)(op + 8 * 1024) = make_uint4(pack2(o[2] * i1, o[3] * i1), pack2(o[6] * i1, o[7] * i1), pack2(o[10] * i1, o[11] * i1), pack2(o[14] * i1, o[15] * i1));
        };
        if (!(l & 1)) {
          auto put_kv = [&](int gi, uint32_t r0, const uint32_t (&t)[8]) {
            if (gi < 4) {
              const uint32_t r = r0 + srow;
#pragma unroll
              for (int jj = 0; jj < 2; jj++) stsm4(sb + KSC + r * 128 + (((4 * (gi - 2) + 2 * jj + (lane >> 4)) ^ (r & 7)) << 4), t[4 * jj], t[4 * jj + 1], t[4 * jj + 2], t[4 * jj + 3]);
            } else {
              const uint32_t r = r0 + g, ad = sb + VSC + r * 128 + (((4 * (gi - 4) + qd) ^ (r & 7)) << 4);
              sts128(ad, t[0], t[2], t[4], t[6]); sts128(ad + 1024, t[1], t[3], t[5], t[7]);
            }
          };
          auto cen_tile = [&](int gi, int m, uint32_t (&t)[8]) {
#pragma unroll
            for (int j = 0; j < 4; j++) {
              const float* a = &acc[m][16 * gi + 4 * j];
              t[2 * j] = pack2(fmaf(st[m][0].y, cs[j].x, a[0]), fmaf(st[m][0].y, cs[j].y, a[1]));
              t[2 * j + 1] = pack2(fmaf(st[m][1].y, cs[j].x, a[2]), fmaf(st[m][1].y, cs[j].y, a[3]));
            }
          };
          const bool send = wg == 1 && w == 3 && bm < 7;
          uint4* hp = g_halo + ((l >> 1) * 128 + b) * 384 + lane;
          mbar_wait(sb + B_QE + 16, 1);
          float2 cn[4];
          auto next_cs = [&](int gi) {
#pragma unroll
            for (int j = 0; j < 4; j++) { cs[j] = cn[j]; cn[j] = lds64f(sb + COLS + (gi * 32 + j * 8 + 2 * qd) * 4); }
          };
#pragma unroll
          for (int j = 0; j < 4; j++) cn[j] = cs[j];
#pragma unroll
          for (int h = 0; h < 2; h++) {
            uint32_t k[8], v[8];
            next_cs(4 + h);
            cen_tile(2 + h, 1, k); put_kv(2 + h, 16 + row0 + 64, k);
            next_cs(h ? 2 : 3);
            cen_tile(4 + h, 1, v); put_kv(4 + h, 16 + row0 + 64, v);
            if (send) {
              uint4* p = hp + h * 192;
              st_tagged(p, k[0], k[1], k[2], ep1); st_tagged(p + 32, k[3], k[4], k[5], ep1); st_tagged(p + 64, k[6], k[7], v[0], ep1);
              st_tagged(p + 96, v[1], v[2], v[3], ep1); st_tagged(p + 128, v[4], v[5], v[6], ep1);
              st_tagged(p + 160, v[7], __float_as_uint(qd & 1 ? st[1][1].x : st[1][0].x), 0u, ep1);
            }
            sched_fence();
          }
          drain();
          {
            uint32_t t[8];
            next_cs(4); cen_tile(2, 0, t); put_kv(2, 16 + row0, t);
            next_cs(0); cen_tile(4, 0, t); put_kv(4, 16 + row0, t);
            next_cs(3); cen_tile(0, 0, q[0][0]); cen_tile(0, 1, q[0][1]);
          }
          bar_sync(NB_SC, 256);
          const bool e = g & 1, sel = 2 * qd + (g & 1) >= g + 2, first = bm == 0 && row0 == 0;
          if (row0 == 0) bar_sync(NB_HALO, 64);
          float ra[4], rb[4], ca[4], cb[4];
#pragma unroll
          for (int m = 0; m < 2; m++) {
            float rk[3];
#pragma unroll
            for (int u = 0; u < 3; u++) {
              const int r = row0 + m * 64 + 8 * u + 2 * qd + e - (sel ? 16 : 8);
              rk[u] = lds64f(sb + (m == 0 && r < 0 ? HRS + 128 : ROWST) + r * 8).x;
            }
            ra[2 * m] = sel ? rk[1] : rk[0]; ra[2 * m + 1] = sel ? rk[2] : rk[1];
            rb[2 * m] = sel ? rk[0] : rk[1]; rb[2 * m + 1] = sel ? rk[1] : rk[2];
          }
#pragma unroll
          for (int i = 0; i < 4; i++) { const float rq = st[i >> 1][i & 1].x * QSCALE; ca[i] = rq * ra[i]; cb[i] = rq * rb[i]; }
#pragma unroll 1
          for (int h = 0; h < 2; h++) {
            float s[2][4][4];
            uint32_t vf[2][4][4], pf[2][2][4];
#pragma unroll
            for (int m = 0; m < 2; m++)
#pragma unroll
              for (int nt = 0; nt < 4; nt++) {
                uint32_t kf[4];
                const uint32_t r = row0 + m * 64 + 8 * nt + (lane & 7), ch = 4 * h + (lane >> 3);
                ldsm4(sb + KSC + r * 128 + ((ch ^ (r & 7)) << 4), kf);
                s[m][nt][0] = s[m][nt][1] = s[m][nt][2] = s[m][nt][3] = 0.f;
                mma16816(s[m][nt], q[0][m][0], q[0][m][1], q[0][m][2], q[0][m][3], kf[0], kf[1]);
                mma16816(s[m][nt], q[0][m][4], q[0][m][5], q[0][m][6], q[0][m][7], kf[2], kf[3]);
              }
#pragma unroll
            for (int m = 0; m < 2; m++)
#pragma unroll
              for (int i = 0; i < 4; i++) {
                const uint32_t r = row0 + m * 64 + 16 * (i >> 1) + srow, ch = 4 * h + 2 * (i & 1) + (lane >> 4);
                ldsm4t(sb + VSC + r * 128 + ((ch ^ (r & 7)) << 4), vf[m][i]);
              }
            float va[4], vb[4], mx[4];
#pragma unroll
            for (int i = 0; i < 4; i++) {
              const int m = i >> 1, hh = i & 1;
              const float a = e ? s[m][hh + 1][2 * hh + 1] : s[m][hh + 1][2 * hh];
              const float lo = e ? s[m][hh][2 * hh + 1] : s[m][hh][2 * hh], hi = e ? s[m][hh + 2][2 * hh + 1] : s[m][hh + 2][2 * hh];
              va[i] = (m == 0 && hh == 0 && first) ? -INFINITY : a * ca[i];
              vb[i] = (m == 0 && first && sel) ? -INFINITY : (sel ? lo : hi) * cb[i];
              mx[i] = fmaxf(va[i], vb[i]);
            }
#pragma unroll
            for (int i = 0; i < 4; i++) mx[i] = fmaxf(mx[i], __shfl_xor_sync(~0u, mx[i], 1));
#pragma unroll
            for (int i = 0; i < 4; i++) mx[i] = fmaxf(mx[i], __shfl_xor_sync(~0u, mx[i], 2));
#pragma unroll
            for (int i = 0; i < 4; i++) {
              va[i] = ex2(va[i] - mx[i]); vb[i] = ex2(vb[i] - mx[i]);
              mx[i] = va[i] + vb[i];
              va[i] *= ra[i]; vb[i] *= rb[i];
            }
#pragma unroll
            for (int i = 0; i < 4; i++) mx[i] += __shfl_xor_sync(~0u, mx[i], 1);
#pragma unroll
            for (int i = 0; i < 4; i++) mx[i] += __shfl_xor_sync(~0u, mx[i], 2);
#pragma unroll
            for (int i = 0; i < 4; i++) {
              const int m = i >> 1, hh = i & 1;
              const float inv = rcp(mx[i]);
              const uint32_t t = pack2(va[i] * inv, vb[i] * inv);
              const uint32_t pa = e ? t << 16 : t & 0xFFFFu, pb = e ? t & 0xFFFF0000u : t >> 16;
              pf[m][hh][hh + 1] = pa; pf[m][hh][hh] = sel ? pb : 0u; pf[m][hh][hh + 2] = sel ? 0u : pb; pf[m][hh][3 - 3 * hh] = 0u;
            }
#pragma unroll
            for (int m = 0; m < 2; m++) {
              float o[4][4];
#pragma unroll
              for (int j = 0; j < 4; j++) o[j][0] = o[j][1] = o[j][2] = o[j][3] = 0.f;
#pragma unroll
              for (int i = 0; i < 4; i++) {
                const int kk = i >> 1, jj = 2 * (i & 1);
                mma16816(o[jj], pf[m][0][2 * kk], pf[m][1][2 * kk], pf[m][0][2 * kk + 1], pf[m][1][2 * kk + 1], vf[m][i][0], vf[m][i][1]);
                mma16816(o[jj + 1], pf[m][0][2 * kk], pf[m][1][2 * kk], pf[m][0][2 * kk + 1], pf[m][1][2 * kk + 1], vf[m][i][2], vf[m][i][3]);
              }
              const float of[16] = {o[0][0], o[0][1], o[0][2], o[0][3], o[1][0], o[1][1], o[1][2], o[1][3], o[2][0], o[2][1], o[2][2], o[2][3], o[3][0], o[3][1], o[3][2], o[3][3]};
              put_o(h, m, of, 1.f, 1.f);
            }
            bar_arrive(NB_SIG + 2 * h + wg, 160);
            if (h == 0) {
              uint32_t t[8];
              next_cs(5); cen_tile(3, 0, t); put_kv(3, 16 + row0, t);
              next_cs(1); cen_tile(5, 0, t); put_kv(5, 16 + row0, t);
#pragma unroll
              for (int j = 0; j < 4; j++) cs[j] = cn[j];
              cen_tile(1, 0, q[0][0]); cen_tile(1, 1, q[0][1]);
              bar_sync(NB_SC, 256);
              if (row0 == 0) bar_sync(NB_HALO + 1, 64);
            }
          }
        } else {
          float qn[2];
          drain();
          auto esc_ptr = [&](int gi) { IDS(); return g_esc + (size_t)(((l & 2) + (gi >> 1)) * 65536 + (2 * bn + (gi & 1)) * 2048) * 16; };
          auto norm_half = [&](int gi, float sc, uint32_t (&t)[2][8], float (&nrm)[2][2]) {
            norm_tile(gi, 0, sc, t[0], nrm[0], true); norm_tile(gi, 1, sc, t[1], nrm[1], true);
            if (!((nrm[0][0] + nrm[0][1]) + (nrm[1][0] + nrm[1][1]) <= 4e9f)) {
              uint32_t* p = esc_ptr(gi) + (bm * 256 + row0 + g) * 16 + qd;
#pragma unroll
              for (int m = 0; m < 2; m++) {
                uint32_t u[8]; float d[2];
                norm_tile(gi, m, sc, u, d);
#pragma unroll
                for (int i = 0; i < 8; i++) p[(m * 64 + (i & 1) * 8) * 16 + (i >> 1) * 4] = u[i];
              }
            }
            __syncwarp();
          };
          {
            auto max_norm = [&](const float (&nrm)[2][2]) {
              const bool o1 = qd & 1, o2 = qd & 2;
              const float a = (o1 ? nrm[1][0] : nrm[0][0]) + __shfl_xor_sync(~0u, o1 ? nrm[0][0] : nrm[1][0], 1);
              const float c = (o1 ? nrm[1][1] : nrm[0][1]) + __shfl_xor_sync(~0u, o1 ? nrm[0][1] : nrm[1][1], 1);
              const float d = (o2 ? c : a) + __shfl_xor_sync(~0u, o2 ? a : c, 2);
              return __uint_as_float(__reduce_max_sync(~0u, __float_as_uint(d)));
            };
#pragma unroll
            for (int h = 0; h < 2; h++) {
              uint32_t t[2][8]; float nrm[2][2];
              const uint32_t kb = sb + (h ? 0 : T0);
              if (h) load_cs(3);
              uint32_t tv[2][8];
              norm_half(2 + h, 1.f, t, nrm);
              load_cs(4 + h);
              float nv[2][2];
              if (h == 1) { const float kn = max_norm(nrm); if (lane == 0) g_kn[((l >> 1) * 128 + bn * 8 + bm) * 16 + 8 + wg * 4 + w] = kn; }
              if (h == 0) mbar_wait(sb + B_QE + 8, 1);
#pragma unroll
              for (int i = 0; i < 4; i++) {
                const uint32_t r = row0 + (i >> 1) * 64 + srow;
                stsm4(kb + r * 64 + (((2 * (i & 1) + (lane >> 4)) ^ ((r >> 1) & 3)) << 4), t[i >> 1][4 * (i & 1)], t[i >> 1][4 * (i & 1) + 1], t[i >> 1][4 * (i & 1) + 2], t[i >> 1][4 * (i & 1) + 3]);
              }
              const int krow = 2 * bn * 2048 + bm * 256 + row0;
              if (h == 0) {
                fence_async_smem(); __syncwarp();
                tma_st(&prm.m[M_K16], 0, krow, kb + row0 * 64); tma_st(&prm.m[M_K16], 0, krow + 64, kb + row0 * 64 + 4096);
              }
              norm_group(4 + h, 1.f, tv, nv);
              load_cs(h);
#pragma unroll
              for (int m = 0; m < 2; m++) {
                const uint32_t r = row0 + m * 64 + g, ad = kb + 16384 + r * 64 + ((qd ^ ((r >> 1) & 3)) << 4);
                sts128(ad, tv[m][0], tv[m][2], tv[m][4], tv[m][6]); sts128(ad + 512, tv[m][1], tv[m][3], tv[m][5], tv[m][7]);
              }
              fence_async_smem();
              bar_arrive(NB_KV + 12 * h, 288);
              if (h == 0) {
                __syncwarp();
                tma_st(&prm.m[M_V16], 0, krow, kb + 16384 + row0 * 64); tma_st(&prm.m[M_V16], 0, krow + 64, kb + 16384 + row0 * 64 + 4096);
                bulk_commit();
                if (wg) { bulk_wait_n<0>(); bar_arrive(NB_DONE, 288); bar_sync(NB_HALO + 1, 256); }
              }
              if (h == 0) { const float kn = max_norm(nrm); if (lane == 0) g_kn[((l >> 1) * 128 + bn * 8 + bm) * 16 + wg * 4 + w] = kn; }
              norm_half(h, QSCALE, q[h], nrm);
#pragma unroll
              for (int i = 0; i < 4; i++) sts128(sb + QPARK + h * 16384 + (wg * 128 + w * 32 + lane) * 16 + i * 4096, q[h][i >> 1][4 * (i & 1)], q[h][i >> 1][4 * (i & 1) + 1], q[h][i >> 1][4 * (i & 1) + 2], q[h][i >> 1][4 * (i & 1) + 3]);
              qn[h] = max_norm(nrm);
              if (h == 0 && !wg) { bulk_wait_n<0>(); bar_arrive(NB_DONE, 288); }
            }
            if (!wg) bar_arrive(NB_HALO + 1, 256);
          }
          constexpr uint64_t VSTEP = 64 - (64ull << 16);
          constexpr int SK = 2;
          const uint32_t c_nsig = 0x62E562E5u + (lane_id() & zero), c_half = 0x3F003F00u + (lane_id() & zero), c_lsb = 0x00010001u + (lane_id() & zero);
          float o[2][20], S[2][32], e[2 * SK];
          uint32_t H[2][16], P0[4] = {}, P1[4] = {};
#pragma unroll
          for (int m = 0; m < 2; m++) {
#pragma unroll
            for (int i = 0; i < 20; i++) o[m][i] = 0.f;
            fence_regs(o[m]);
          }
          auto qk = [&](int b, int ks, uint64_t d) {
            wg_n64_rs_nb_f16_f32(S[b], q[0][0][4 * ks], q[0][0][4 * ks + 1], q[0][0][4 * ks + 2], q[0][0][4 * ks + 3], d, ks ? 1 : zero);
            wg_n64_rs_nb_f16_f16(H[b], q[0][1][4 * ks], q[0][1][4 * ks + 1], q[0][1][4 * ks + 2], q[0][1][4 * ks + 3], d, ks ? 1 : zero);
          };
          auto pv = [&](uint64_t d) {
            wgmma_m64n40k16_rs_tb(o[0], P0[0], P0[1], P0[2], P0[3], d, 1);
            wgmma_m64n40k16_rs_tb(o[1], P1[0], P1[1], P1[2], P1[3], d, 1);
          };
          auto start = [&](int h) {
#pragma unroll
            for (int i = 0; i < 2 * SK; i++) e[i] = ex2(S[(h >> 2) & 1][8 * (h & 3) + i]);
            fence_regs(e);
          };
          auto finish = [&](int h) {
            const int b = (h >> 2) & 1, c = h & 3;
#pragma unroll
            for (int i = 0; i < 4; i++) {
              const float s0 = S[b][8 * c + 2 * i], s1 = S[b][8 * c + 2 * i + 1];
              P1[3 - i] = exp2_h2(H[b][4 * c + 3 - i], c_nsig);
              P0[i] = i < SK ? pack2(e[2 * i], e[2 * i + 1]) : i < 3 ? pack2(ex2(s0), ex2(s1)) : exp2_pair(s0, s1, c_half, c_lsb);
            }
            fence_regs(P0); fence_regs(P1);
          };
          uint64_t kd = prm.kv[0].kd;
          mbar_wait(sb + B_TF, 0);
          wg_fence();
#pragma unroll
          for (int b = 0; b < 2; b++) {
            wg_n64_rs_nb_f16_f32_z(S[b], q[0][0][0], q[0][0][1], q[0][0][2], q[0][0][3], kd + 256 * b, 0);
            wg_n64_rs_nb_f16_f16_z(H[b], q[0][1][0], q[0][1][1], q[0][1][2], q[0][1][3], kd + 256 * b, 0);
            if (b == 0) qk(0, 1, kd + 2);
            wg_commit();
          }
          wg_wait<1>(); fence_regs(S[0]); fence_regs(H[0]);
          start(0); finish(0); start(1);
          wg_wait<0>();
          int redo = 0;
#pragma unroll 1
          for (int pass = 0, j = 1; pass < 2; pass++) {
#pragma unroll 1
           do {
            const uint64_t vd = prm.kv[j].vd;
            bool go = false;
#pragma unroll
            for (int h = 2; h < 18; h++) {
              const int px = (h >> 2) + 1, c = h & 3;
              wg_fence();
              if (h == 13) kd = prm.kv[j].kd;
              if (h == 2) qk(1, 0, kd + 256);
              else if ((c == 1 || c == 2) && h < 17) qk(px & 1, c - 1, kd + (px & 3) * 256 + 2 * (c - 1));
              pv(vd + (h - 2) * VSTEP);
              if (h == 2) qk(1, 1, kd + 258);
              wg_commit();
              if (h == 3) e_arrive_if(sb + B_TE + 8 * ((j + 2) & 3), j > 1);
              if (h == 11) go = mbar_test(sb + B_TF + 8 * (j & 3), (j >> 2) & 1) && j != 8;
              finish(h - 1); start(h);
              if (h != 12 && h != 17) sched_fence();
              if (h == 12 && !go) {
                if (j == 16) {
#pragma unroll
                  for (int t = 13; t < 18; t++) {
                    wg_fence(); pv(vd + (t - 2) * VSTEP); wg_commit();
                    if (t < 17) finish(t - 1);
                    if (t < 16) { start(t); sched_fence(); }
                    if (t & 1) { if (t == 17) wg_wait<0>(); else wg_wait<1>(); }
                  }
                  e_arrive(sb + B_TE + 24);
                  goto head_done;
                }
                mbar_wait(sb + B_TF + 8 * (j & 3), (j >> 2) & 1);
                if (j == 8) {
#pragma unroll
                  for (int i = 0; i < 4; i++) lds128(sb + QPARK + 16384 + (wg * 128 + w * 32 + lane_id()) * 16 + i * 4096, &q[0][i >> 1][4 * (i & 1)]);
                }
              }
              if (h == 17) wg_wait<0>(); else if (h & 1) wg_wait<1>();
              if (c == 3) { fence_regs(S[px & 1]); fence_regs(H[px & 1]); }
            }
           } while (j++ & 7);
           head_done:
            fence_regs(o[0]); fence_regs(o[1]);
            if (pass == 0) bar_sync(NB_KN + wg, 160);
            const float kmax = *(volatile float*)(smem + ROWST + 4 * pass);
            const bool wide = !(qn[0] <= 1.6e7f && kmax <= 1.6e7f && qn[0] * kmax <= 112.f * 112.f);
            uint32_t pk[2][8];
            auto norm_o = [&](uint32_t (&u)[8], const float (&a)[20]) {
              const float i0 = rcp(a[16]), i1 = rcp(a[18]);
#pragma unroll
              for (int i = 0; i < 4; i++) { u[i] = pack2(a[4 * i] * i0, a[4 * i + 1] * i0); u[4 + i] = pack2(a[4 * i + 2] * i1, a[4 * i + 3] * i1); }
            };
            int badm = 0;
#pragma unroll
            for (int m = 0; m < 2; m++) {
              norm_o(pk[m], o[m]);
              uint32_t chk[2] = {0u, 0u};
#pragma unroll
              for (int i = 0; i < 8; i++) asm("fma.rn.bf16x2 %0, %1, %2, %0;" : "+r"(chk[i & 1]) : "r"(pk[m][i]), "r"(0u));
              const bool bad = wide | !(fminf(o[m][16], o[m][18]) >= 9.3e-10f) | !(o[m][16] + o[m][18] <= 1e36f) | (((chk[0] | chk[1]) & 0x7FFF7FFFu) != 0);
              badm |= __any_sync(~0u, bad) << m;
            }
            if (badm) {
              redo |= badm << 2 * pass;
              uint32_t* p = esc_ptr(pass) + ((cta_id() >> 4) * 256 + row0 + (lane_id() >> 2)) * 16 + (lane_id() & 3);
#pragma unroll
              for (int i = 0; i < 4; i++) {
                uint32_t u[4] = {q[0][i >> 1][4 * (i & 1)], q[0][i >> 1][4 * (i & 1) + 1], q[0][i >> 1][4 * (i & 1) + 2], q[0][i >> 1][4 * (i & 1) + 3]};
                if (pass == 0) lds128(sb + QPARK + (wg * 128 + w * 32 + lane_id()) * 16 + i * 4096, u);
#pragma unroll
                for (int k = 0; k < 4; k++) { uint32_t* a = p + ((i >> 1) * 64 + (k & 1) * 8) * 16 + (2 * (i & 1) + (k >> 1)) * 4; *a = unesc(u[k], a); }
              }
              __syncwarp();
            }
            {
              IDS();
              bf16* op = g_os + (size_t)(bm * 256 + row0 + (lane >> 2)) * 1024 + pass * 512 + bn * 32 + (lane & 3) * 8;
#pragma unroll
              for (int i = 0; i < 4; i++) *(uint4*)(op + ((i >> 1) * 64 + (i & 1) * 8) * 1024) = make_uint4(pk[i >> 1][4 * (i & 1)], pk[i >> 1][4 * (i & 1) + 1], pk[i >> 1][4 * (i & 1) + 2], pk[i >> 1][4 * (i & 1) + 3]);
            }
            if (!badm) bar_arrive(NB_SIG + 2 * pass + wg, 160);
            qn[0] = qn[1];
#pragma unroll
            for (int m = 0; m < 2; m++) {
#pragma unroll
              for (int i = 0; i < 20; i++) o[m][i] = 0.f;
              fence_regs(o[m]);
            }
          }
          if (redo) {
#pragma unroll 1
            for (int t = 0; t < 4; t++) {
              const int pass = t >> 1, m = t & 1;
              if ((redo >> t) & 1) {
                uint32_t qq[8]; float res[20];
                const uint32_t* p = esc_ptr(pass) + ((cta_id() >> 4) * 256 + row0 + m * 64 + (lane_id() >> 2)) * 16 + (lane_id() & 3);
#pragma unroll
                for (int i = 0; i < 8; i++) qq[i] = __ldcg(p + (i & 1) * 128 + (i >> 1) * 4);
                attn_slow(qq, 2 * (cta_id() & 15) + pass, esc_ptr(2 + pass), res, lane_id());
                const float of[16] = {res[0], res[1], res[2], res[3], res[4], res[5], res[6], res[7], res[8], res[9], res[10], res[11], res[12], res[13], res[14], res[15]};
                put_o(pass, m, of, rcp(res[16]), rcp(res[18]));
              }
              if (m && ((redo >> 2 * pass) & 3)) bar_arrive(NB_SIG + 2 * pass + wg, 160);
            }
          }
        }
      }
      {
        float acc[64];
#pragma unroll
        for (int i = 0; i < 64; i++) acc[i] = 0.f;
        fence_regs(acc);
        uint32_t s = 0, lap = 0;
#pragma unroll 1
        for (int kt = 0; kt < 16; kt++) {
          mbar_wait(sb + B_PF + 8 * s, ((s < 4 ? l : 0) + lap) & 1);
          const uint64_t da = mkdesc(sb + pslot_a(s, l) + wg * 8192, 16, 1024, 1), db = mkdesc(sb + pslot_b(s), 8192, 1024, 1);
          wg_fence();
#pragma unroll
          for (int k = 0; k < 4; k++) wgmma_m64n128k16_ss_tb(acc, da + k * 2, db + k * 128, 1);
          wg_commit();
          wg_wait<1>();
          if (kt > 0 && w == 0) e_arrive_both(sb + B_PE + 8 * (s ? s - 1 : 5));
          if (++s == 6) { s = 0; lap++; }
        }
        IDS();
        const int g = lane >> 2, qd = lane & 3;
        const int r0 = wg * 64 + w * 16;
        const uint32_t r = r0 + (lane & 7) + ((lane >> 3) & 1) * 8;
        uint32_t x[8][4];
        mbar_wait(sb + B_RF, l & 1);
#pragma unroll
        for (int jj = 0; jj < 8; jj++) ldsm4(sb + RES + (jj >> 2) * 16384 + r * 128 + ((((2 * jj + (lane >> 4)) & 7) ^ (r & 7)) << 4), x[jj]);
        wg_wait<0>();
        fence_regs(acc);
        if (w == 0) e_arrive_both(sb + B_PE + 8 * 3);
        const CUtensorMap* mo = &prm.m[l == 3 ? M_OUT : M_XST];
#pragma unroll
        for (int jj = 0; jj < 8; jj++) {
#pragma unroll
          for (int i = 0; i < 4; i++) x[jj][i] = add_bf16x2(x[jj][i], pack2(acc[8 * jj + 2 * i], acc[8 * jj + 2 * i + 1]));
          stsm4(sb + RES + (jj >> 2) * 16384 + r * 128 + ((((2 * jj + (lane >> 4)) & 7) ^ (r & 7)) << 4), x[jj][0], x[jj][1], x[jj][2], x[jj][3]);
          if ((jj & 3) == 3) { fence_async_smem(); __syncwarp(); tma_st(mo, pn * 128 + (jj >> 2) * 64, pm * 128 + r0, sb + RES + (jj >> 2) * 16384 + r0 * 128); }
        }
        bulk_commit();
        if (l < 3) {
          bar_sync(NB_SC, 256);
#pragma unroll
          for (int jj = 0; jj < 8; jj++)
            stsm4(sb + (jj >> 2) * QSTG + po * 16384 + r * 128 + ((((2 * jj + (lane >> 4)) & 7) ^ (r & 7)) << 4), x[jj][0], x[jj][1], x[jj][2], x[jj][3]);
          fence_async_smem();
          bar_arrive(NB_X, 288);
          float s1[4] = {0.f, 0.f, 0.f, 0.f}, sa[4] = {0.f, 0.f, 0.f, 0.f}, sc[4] = {0.f, 0.f, 0.f, 0.f};
#pragma unroll
          for (int jj = 0; jj < 8; jj++) {
            mma16816(s1, x[jj][0], x[jj][1], x[jj][2], x[jj][3], 0x3f803f80u, 0x3f803f80u);
            mma16816(sa, x[jj][0], x[jj][1], x[jj][2], x[jj][3], x[jj][0], x[jj][2]);
            mma16816(sc, x[jj][0], x[jj][1], x[jj][2], x[jj][3], x[jj][1], x[jj][3]);
          }
          if (qd == g >> 1) {
            float2* p = g_stats + pn * 2048 + pm * 128 + r0 + g;
            p[0] = make_float2(s1[0], g & 1 ? sa[1] : sa[0]);
            p[8] = make_float2(s1[2], g & 1 ? sc[3] : sc[2]);
          }
        }
        bulk_wait_n<0>();
        if (l < 3) bar_arrive(NB_X0, 288);
      }
    }
  }
  asm volatile("barrier.cluster.arrive.relaxed.aligned;\nbarrier.cluster.wait.aligned;" ::: "memory");
}

typedef CUresult (*EncodeFn)(CUtensorMap*, CUtensorMapDataType, cuuint32_t, void*, const cuuint64_t*, const cuuint64_t*, const cuuint32_t*,
                             const cuuint32_t*, CUtensorMapInterleave, CUtensorMapSwizzle, CUtensorMapL2promotion, CUtensorMapFloatOOBfill);

static void make_map(EncodeFn fn, CUtensorMap* m, const void* ptr, int rank, const uint64_t* dims, const uint64_t* strides, const uint32_t* box, CUtensorMapSwizzle sw) {
  cuuint64_t d[5], st[4];
  cuuint32_t bx[5], es[5];
  for (int i = 0; i < rank; i++) { d[i] = dims[i]; bx[i] = box[i]; es[i] = 1; if (i) st[i - 1] = strides[i - 1] * 2; }
  fn(m, CU_TENSOR_MAP_DATA_TYPE_BFLOAT16, rank, (void*)ptr, d, st, bx, es, CU_TENSOR_MAP_INTERLEAVE_NONE, sw,
     CU_TENSOR_MAP_L2_PROMOTION_L2_128B, CU_TENSOR_MAP_FLOAT_OOB_FILL_NONE);
}
static void map2(EncodeFn fn, CUtensorMap* m, const void* ptr, uint64_t inner, uint64_t outer, uint32_t bi, uint32_t bo, CUtensorMapSwizzle sw) {
  const uint64_t d[2] = {inner, outer}, st[1] = {inner};
  const uint32_t bx[2] = {bi, bo};
  make_map(fn, m, ptr, 2, d, st, bx, sw);
}

extern "C" void kernel_launch(void* const* d_in, const int* in_sizes, int n_in, void* d_out, int out_size) {
  (void)in_sizes; (void)n_in; (void)out_size;
  static EncodeFn enc = nullptr;
  static void *xs, *os, *kk, *vv;
  static int sbase = 1024;
  if (!enc) {
    void* p = nullptr;
    cudaDriverEntryPointQueryResult qr;
    cudaGetDriverEntryPoint("cuTensorMapEncodeTiled", &p, cudaEnableDefault, &qr);
    enc = (EncodeFn)p;
    cudaGetSymbolAddress(&xs, g_xs); cudaGetSymbolAddress(&os, g_os); cudaGetSymbolAddress(&kk, g_k); cudaGetSymbolAddress(&vv, g_v);
    int dev = 0;
    cudaGetDevice(&dev);
    cudaDeviceGetAttribute(&sbase, cudaDevAttrReservedSharedMemoryPerBlock, dev);
    cudaFuncSetAttribute(fused_kernel, cudaFuncAttributeMaxDynamicSharedMemorySize, SMEM_BYTES);
  }
  Params prm;
  const CUtensorMapSwizzle S128 = CU_TENSOR_MAP_SWIZZLE_128B, S64 = CU_TENSOR_MAP_SWIZZLE_64B;
  map2(enc, &prm.m[M_X0A], d_in[0], 1024, 2048, 64, 256, S128);
  map2(enc, &prm.m[M_XSA], xs, 1024, 2048, 64, 256, S128);
  for (int t = 0; t < 2; t++) {
    const uint64_t d3[3] = {1024, 1024, 3}, s3[2] = {3072, 1024};
    const uint32_t b3[3] = {64, 64, 3};
    make_map(enc, &prm.m[M_WQA + t], d_in[1 + 3 * t], 3, d3, s3, b3, S128);
    const uint64_t d5[5] = {64, 32, 2, 16, 16}, s5[4] = {1024, 32 * 1024, 64 * 1024, 64};
    const uint32_t b5[5] = {64, 32, 1, 2, 2};
    make_map(enc, &prm.m[M_WOA + t], d_in[2 + 3 * t], 5, d5, s5, b5, S128);
    const uint64_t dr[3] = {64, 2048, 16}, sr[2] = {1024, 64};
    const uint32_t br[3] = {64, 128, 2};
    make_map(enc, &prm.m[M_X0R + t], t ? xs : d_in[0], 3, dr, sr, br, S128);
  }
  map2(enc, &prm.m[M_OS], os, 1024, 2048, 64, 64, S128);
  map2(enc, &prm.m[M_K], kk, 32, 65536, 32, 256, S64);
  map2(enc, &prm.m[M_V], vv, 32, 65536, 32, 256, S64);
  map2(enc, &prm.m[M_K16], kk, 32, 65536, 32, 16, S64);
  map2(enc, &prm.m[M_V16], vv, 32, 65536, 32, 16, S64);
  map2(enc, &prm.m[M_XSO], xs, 1024, 2048, 64, 128, S128);
  map2(enc, &prm.m[M_X0H], d_in[0], 1024, 2048, 64, 128, S128);
  map2(enc, &prm.m[M_XST], xs, 1024, 2048, 64, 16, S128);
  map2(enc, &prm.m[M_OUT], d_out, 1024, 2048, 64, 16, S128);
  prm.x0 = (const bf16*)d_in[0];
  prm.wq[0] = (const bf16*)d_in[1]; prm.wq[1] = (const bf16*)d_in[4];
  prm.zero = 0;
  for (int i = 0; i < 128; i++) prm.map[i] = remap(i);
  {
    const uint64_t hi = 0x80000020ull << 32, k0 = sbase + T0, v0 = k0 + 16384, vstep = 64 - (64ull << 16);
    for (int j = 0; j < 17; j++) {
      prm.kv[j].kd = (hi | 1u << 16 | k0 >> 4) + 2048 * ((j < 16 ? j : 15) & 3);
      prm.kv[j].vd = (hi | (uint64_t)(ONES - T0 - 16384) >> 4 << 16 | v0 >> 4) + 32 * vstep * ((j ? j - 1 : 0) & 3);
    }
  }
  fused_kernel<<<128, 384, SMEM_BYTES>>>(prm);
}
```

```cpp
#include <cuda_runtime.h>
#include <cuda_bf16.h>
#include <cuda.h>
#include <stdint.h>

typedef __nv_bfloat16 bf16;

__device__ __forceinline__ void wgmma_m64n192k16_ss_tb(float (&d)[96], uint64_t da, uint64_t db, int scale_d) {
  asm volatile("{\n.reg .pred p;\nsetp.ne.b32 p, %98, 0;\n"
    "wgmma.mma_async.sync.aligned.m64n192k16.f32.bf16.bf16 "
    "{%0, %1, %2, %3, %4, %5, %6, %7, %8, %9, %10, %11, %12, %13, %14, %15, "
    "%16, %17, %18, %19, %20, %21, %22, %23, %24, %25, %26, %27, %28, %29, %30, %31, "
    "%32, %33, %34, %35, %36, %37, %38, %39, %40, %41, %42, %43, %44, %45, %46, %47, "
    "%48, %49, %50, %51, %52, %53, %54, %55, %56, %57, %58, %59, %60, %61, %62, %63, "
    "%64, %65, %66, %67, %68, %69, %70, %71, %72, %73, %74, %75, %76, %77, %78, %79, "
    "%80, %81, %82, %83, %84, %85, %86, %87, %88, %89, %90, %91, %92, %93, %94, %95}, "
    "%96, %97, p, 1, 1, 0, 1;\n}\n"
    : "+f"(d[0]), "+f"(d[1]), "+f"(d[2]), "+f"(d[3]), "+f"(d[4]), "+f"(d[5]), "+f"(d[6]), "+f"(d[7]),
      "+f"(d[8]), "+f"(d[9]), "+f"(d[10]), "+f"(d[11]), "+f"(d[12]), "+f"(d[13]), "+f"(d[14]), "+f"(d[15]),
      "+f"(d[16]), "+f"(d[17]), "+f"(d[18]), "+f"(d[19]), "+f"(d[20]), "+f"(d[21]), "+f"(d[22]), "+f"(d[23]),
      "+f"(d[24]), "+f"(d[25]), "+f"(d[26]), "+f"(d[27]), "+f"(d[28]), "+f"(d[29]), "+f"(d[30]), "+f"(d[31]),
      "+f"(d[32]), "+f"(d[33]), "+f"(d[34]), "+f"(d[35]), "+f"(d[36]), "+f"(d[37]), "+f"(d[38]), "+f"(d[39]),
      "+f"(d[40]), "+f"(d[41]), "+f"(d[42]), "+f"(d[43]), "+f"(d[44]), "+f"(d[45]), "+f"(d[46]), "+f"(d[47]),
      "+f"(d[48]), "+f"(d[49]), "+f"(d[50]), "+f"(d[51]), "+f"(d[52]), "+f"(d[53]), "+f"(d[54]), "+f"(d[55]),
      "+f"(d[56]), "+f"(d[57]), "+f"(d[58]), "+f"(d[59]), "+f"(d[60]), "+f"(d[61]), "+f"(d[62]), "+f"(d[63]),
      "+f"(d[64]), "+f"(d[65]), "+f"(d[66]), "+f"(d[67]), "+f"(d[68]), "+f"(d[69]), "+f"(d[70]), "+f"(d[71]),
      "+f"(d[72]), "+f"(d[73]), "+f"(d[74]), "+f"(d[75]), "+f"(d[76]), "+f"(d[77]), "+f"(d[78]), "+f"(d[79]),
      "+f"(d[80]), "+f"(d[81]), "+f"(d[82]), "+f"(d[83]), "+f"(d[84]), "+f"(d[85]), "+f"(d[86]), "+f"(d[87]),
      "+f"(d[88]), "+f"(d[89]), "+f"(d[90]), "+f"(d[91]), "+f"(d[92]), "+f"(d[93]), "+f"(d[94]), "+f"(d[95])
    : "l"(da), "l"(db), "r"(scale_d));
}

__device__ __forceinline__ void wgmma_m64n128k16_ss_tb(float (&d)[64], uint64_t da, uint64_t db, int scale_d) {
  asm volatile("{\n.reg .pred p;\nsetp.ne.b32 p, %66, 0;\n"
    "wgmma.mma_async.sync.aligned.m64n128k16.f32.bf16.bf16 "
    "{%0, %1, %2, %3, %4, %5, %6, %7, %8, %9, %10, %11, %12, %13, %14, %15, "
    "%16, %17, %18, %19, %20, %21, %22, %23, %24, %25, %26, %27, %28, %29, %30, %31, "
    "%32, %33, %34, %35, %36, %37, %38, %39, %40, %41, %42, %43, %44, %45, %46, %47, "
    "%48, %49, %50, %51, %52, %53, %54, %55, %56, %57, %58, %59, %60, %61, %62, %63}, "
    "%64, %65, p, 1, 1, 0, 1;\n}\n"
    : "+f"(d[0]), "+f"(d[1]), "+f"(d[2]), "+f"(d[3]), "+f"(d[4]), "+f"(d[5]), "+f"(d[6]), "+f"(d[7]),
      "+f"(d[8]), "+f"(d[9]), "+f"(d[10]), "+f"(d[11]), "+f"(d[12]), "+f"(d[13]), "+f"(d[14]), "+f"(d[15]),
      "+f"(d[16]), "+f"(d[17]), "+f"(d[18]), "+f"(d[19]), "+f"(d[20]), "+f"(d[21]), "+f"(d[22]), "+f"(d[23]),
      "+f"(d[24]), "+f"(d[25]), "+f"(d[26]), "+f"(d[27]), "+f"(d[28]), "+f"(d[29]), "+f"(d[30]), "+f"(d[31]),
      "+f"(d[32]), "+f"(d[33]), "+f"(d[34]), "+f"(d[35]), "+f"(d[36]), "+f"(d[37]), "+f"(d[38]), "+f"(d[39]),
      "+f"(d[40]), "+f"(d[41]), "+f"(d[42]), "+f"(d[43]), "+f"(d[44]), "+f"(d[45]), "+f"(d[46]), "+f"(d[47]),
      "+f"(d[48]), "+f"(d[49]), "+f"(d[50]), "+f"(d[51]), "+f"(d[52]), "+f"(d[53]), "+f"(d[54]), "+f"(d[55]),
      "+f"(d[56]), "+f"(d[57]), "+f"(d[58]), "+f"(d[59]), "+f"(d[60]), "+f"(d[61]), "+f"(d[62]), "+f"(d[63])
    : "l"(da), "l"(db), "r"(scale_d));
}

__device__ __forceinline__ void wgmma_m64n40k16_rs_tb(float (&d)[20], uint32_t a0, uint32_t a1, uint32_t a2, uint32_t a3, uint64_t db, int scale_d) {
  asm volatile("{\n.reg .pred p;\nsetp.ne.b32 p, %25, 0;\n"
    "wgmma.mma_async.sync.aligned.m64n40k16.f32.bf16.bf16 "
    "{%0, %1, %2, %3, %4, %5, %6, %7, %8, %9, %10, %11, %12, %13, %14, %15, "
    "%16, %17, %18, %19}, "
    "{%20, %21, %22, %23}, %24, p, 1, 1, 1;\n}\n"
    : "+f"(d[0]), "+f"(d[1]), "+f"(d[2]), "+f"(d[3]), "+f"(d[4]), "+f"(d[5]), "+f"(d[6]), "+f"(d[7]),
      "+f"(d[8]), "+f"(d[9]), "+f"(d[10]), "+f"(d[11]), "+f"(d[12]), "+f"(d[13]), "+f"(d[14]), "+f"(d[15]),
      "+f"(d[16]), "+f"(d[17]), "+f"(d[18]), "+f"(d[19])
    : "r"(a0), "r"(a1), "r"(a2), "r"(a3), "l"(db), "r"(scale_d));
}

__device__ __forceinline__ void wg_n64_rs_nb_f16_f32(float (&d)[32], uint32_t a0, uint32_t a1, uint32_t a2, uint32_t a3, uint64_t db, int scale_d) {
  asm volatile("{\n.reg .pred p;\nsetp.ne.b32 p, %37, 0;\n"
    "wgmma.mma_async.sync.aligned.m64n64k16.f32.f16.f16 "
    "{%0, %1, %2, %3, %4, %5, %6, %7, %8, %9, %10, %11, %12, %13, %14, %15, "
    "%16, %17, %18, %19, %20, %21, %22, %23, %24, %25, %26, %27, %28, %29, %30, %31}, "
    "{%32, %33, %34, %35}, %36, p, 1, 1, 0;\n}\n"
    : "+f"(d[0]), "+f"(d[1]), "+f"(d[2]), "+f"(d[3]), "+f"(d[4]), "+f"(d[5]), "+f"(d[6]), "+f"(d[7]),
      "+f"(d[8]), "+f"(d[9]), "+f"(d[10]), "+f"(d[11]), "+f"(d[12]), "+f"(d[13]), "+f"(d[14]), "+f"(d[15]),
      "+f"(d[16]), "+f"(d[17]), "+f"(d[18]), "+f"(d[19]), "+f"(d[20]), "+f"(d[21]), "+f"(d[22]), "+f"(d[23]),
      "+f"(d[24]), "+f"(d[25]), "+f"(d[26]), "+f"(d[27]), "+f"(d[28]), "+f"(d[29]), "+f"(d[30]), "+f"(d[31])
    : "r"(a0), "r"(a1), "r"(a2), "r"(a3), "l"(db), "r"(scale_d));
}

__device__ __forceinline__ void wg_n64_rs_nb_f16_f16(uint32_t (&d)[16], uint32_t a0, uint32_t a1, uint32_t a2, uint32_t a3, uint64_t db, int scale_d) {
  asm volatile("{\n.reg .pred p;\nsetp.ne.b32 p, %21, 0;\n"
    "wgmma.mma_async.sync.aligned.m64n64k16.f16.f16.f16 "
    "{%0, %1, %2, %3, %4, %5, %6, %7, %8, %9, %10, %11, %12, %13, %14, %15}, "
    "{%16, %17, %18, %19}, %20, p, 1, 1, 0;\n}\n"
    : "+r"(d[0]), "+r"(d[1]), "+r"(d[2]), "+r"(d[3]), "+r"(d[4]), "+r"(d[5]), "+r"(d[6]), "+r"(d[7]),
      "+r"(d[8]), "+r"(d[9]), "+r"(d[10]), "+r"(d[11]), "+r"(d[12]), "+r"(d[13]), "+r"(d[14]), "+r"(d[15])
    : "r"(a0), "r"(a1), "r"(a2), "r"(a3), "l"(db), "r"(scale_d));
}

__device__ __forceinline__ void wg_n64_rs_nb_f16_f32_z(float (&d)[32], uint32_t a0, uint32_t a1, uint32_t a2, uint32_t a3, uint64_t db, int scale_d) {
  asm volatile("{\n.reg .pred p;\nsetp.ne.b32 p, %37, 0;\n"
    "wgmma.mma_async.sync.aligned.m64n64k16.f32.f16.f16 "
    "{%0, %1, %2, %3, %4, %5, %6, %7, %8, %9, %10, %11, %12, %13, %14, %15, "
    "%16, %17, %18, %19, %20, %21, %22, %23, %24, %25, %26, %27, %28, %29, %30, %31}, "
    "{%32, %33, %34, %35}, %36, p, 1, 1, 0;\n}\n"
    : "=f"(d[0]), "=f"(d[1]), "=f"(d[2]), "=f"(d[3]), "=f"(d[4]), "=f"(d[5]), "=f"(d[6]), "=f"(d[7]),
      "=f"(d[8]), "=f"(d[9]), "=f"(d[10]), "=f"(d[11]), "=f"(d[12]), "=f"(d[13]), "=f"(d[14]), "=f"(d[15]),
      "=f"(d[16]), "=f"(d[17]), "=f"(d[18]), "=f"(d[19]), "=f"(d[20]), "=f"(d[21]), "=f"(d[22]), "=f"(d[23]),
      "=f"(d[24]), "=f"(d[25]), "=f"(d[26]), "=f"(d[27]), "=f"(d[28]), "=f"(d[29]), "=f"(d[30]), "=f"(d[31])
    : "r"(a0), "r"(a1), "r"(a2), "r"(a3), "l"(db), "r"(scale_d));
}

__device__ __forceinline__ void wg_n64_rs_nb_f16_f16_z(uint32_t (&d)[16], uint32_t a0, uint32_t a1, uint32_t a2, uint32_t a3, uint64_t db, int scale_d) {
  asm volatile("{\n.reg .pred p;\nsetp.ne.b32 p, %21, 0;\n"
    "wgmma.mma_async.sync.aligned.m64n64k16.f16.f16.f16 "
    "{%0, %1, %2, %3, %4, %5, %6, %7, %8, %9, %10, %11, %12, %13, %14, %15}, "
    "{%16, %17, %18, %19}, %20, p, 1, 1, 0;\n}\n"
    : "=r"(d[0]), "=r"(d[1]), "=r"(d[2]), "=r"(d[3]), "=r"(d[4]), "=r"(d[5]), "=r"(d[6]), "=r"(d[7]),
      "=r"(d[8]), "=r"(d[9]), "=r"(d[10]), "=r"(d[11]), "=r"(d[12]), "=r"(d[13]), "=r"(d[14]), "=r"(d[15])
    : "r"(a0), "r"(a1), "r"(a2), "r"(a3), "l"(db), "r"(scale_d));
}

#define DEVINL __device__ __forceinline__
DEVINL void wg_fence() { asm volatile("wgmma.fence.sync.aligned;" ::: "memory"); }
DEVINL void wg_commit() { asm volatile("wgmma.commit_group.sync.aligned;" ::: "memory"); }
template <int N> DEVINL void wg_wait() { asm volatile("wgmma.wait_group.sync.aligned %0;" ::"n"(N) : "memory"); }
DEVINL uint64_t mkdesc(uint32_t addr, uint32_t lbo, uint32_t sbo, int sw) {
  return (uint64_t)((addr & 0x3FFFF) >> 4) | ((uint64_t)(lbo >> 4) << 16) | ((uint64_t)(sbo >> 4) << 32) | ((uint64_t)sw << 62);
}
DEVINL void mbar_init(uint32_t bar, uint32_t cnt) { asm volatile("mbarrier.init.shared::cta.b64 [%0], %1;" ::"r"(bar), "r"(cnt) : "memory"); }
DEVINL void mbar_arrive(uint32_t bar) { asm volatile("mbarrier.arrive.shared::cta.b64 _, [%0];" ::"r"(bar) : "memory"); }
DEVINL bool mbar_try(uint32_t bar, uint32_t parity) {
  uint32_t ok;
  asm volatile("{\n.reg .pred p;\nmbarrier.try_wait.parity.shared::cta.b64 p, [%1], %2;\nselp.u32 %0, 1, 0, p;\n}" : "=r"(ok) : "r"(bar), "r"(parity) : "memory");
  return ok;
}
DEVINL bool mbar_test(uint32_t bar, uint32_t parity) {
  uint32_t ok;
  asm volatile("{\n.reg .pred p;\nmbarrier.test_wait.parity.shared::cta.b64 p, [%1], %2;\nselp.u32 %0, 1, 0, p;\n}" : "=r"(ok) : "r"(bar), "r"(parity) : "memory");
  return ok;
}
DEVINL void mbar_hint(uint32_t bar, uint32_t parity) {
#pragma unroll 1
  for (uint32_t n = 0; n < 16u; n++) if (mbar_try(bar, parity)) break;
}
DEVINL void mbar_wait(uint32_t bar, uint32_t parity) {
#pragma unroll 1
  for (uint32_t n = 0; n < 100000u; n++) if (mbar_try(bar, parity)) break;
}
#define EL(txt) "{\n.reg .pred pe;\nelect.sync _|pe, 0xffffffff;\n@pe " txt "\n}"
DEVINL void e_expect_tx(uint32_t bar, uint32_t bytes) { asm volatile(EL("mbarrier.arrive.expect_tx.shared::cta.b64 _, [%0], %1;") ::"r"(bar), "r"(bytes) : "memory"); }
DEVINL void e_arrive(uint32_t bar) { asm volatile(EL("mbarrier.arrive.shared::cta.b64 _, [%0];") ::"r"(bar) : "memory"); }
DEVINL void e_arrive_if(uint32_t bar, int c) {
  asm volatile("{\n.reg .pred pe;\nelect.sync _|pe, 0xffffffff;\nsetp.ne.and.b32 pe, %1, 0, pe;\n@pe mbarrier.arrive.shared::cta.b64 _, [%0];\n}" ::"r"(bar), "r"(c) : "memory");
}
DEVINL void e_red(uint32_t* p) { asm volatile(EL("red.release.gpu.global.add.u32 [%0], 1;") ::"l"(p) : "memory"); }
DEVINL void e_red_relaxed(uint32_t* p) { asm volatile(EL("red.relaxed.gpu.global.add.u32 [%0], 1;") ::"l"(p) : "memory"); }
DEVINL void tma_ld(uint32_t dst, const CUtensorMap* m, int c0, int c1, uint32_t bar) {
  asm volatile(EL("cp.async.bulk.tensor.2d.shared::cluster.global.mbarrier::complete_tx::bytes [%0], [%1, {%3, %4}], [%2];")
               ::"r"(dst), "l"(m), "r"(bar), "r"(c0), "r"(c1) : "memory");
}
DEVINL void tma_ld3(uint32_t dst, const CUtensorMap* m, int c0, int c1, int c2, uint32_t bar) {
  asm volatile(EL("cp.async.bulk.tensor.3d.shared::cluster.global.mbarrier::complete_tx::bytes [%0], [%1, {%3, %4, %5}], [%2];")
               ::"r"(dst), "l"(m), "r"(bar), "r"(c0), "r"(c1), "r"(c2) : "memory");
}
DEVINL void tma_ld5(uint32_t dst, const CUtensorMap* m, int c2, int c3, int c4, uint32_t bar) {
  asm volatile(EL("cp.async.bulk.tensor.5d.shared::cluster.global.mbarrier::complete_tx::bytes [%0], [%1, {0, 0, %3, %4, %5}], [%2];")
               ::"r"(dst), "l"(m), "r"(bar), "r"(c2), "r"(c3), "r"(c4) : "memory");
}
DEVINL void tma_ld_mc(uint32_t dst, const CUtensorMap* m, int c0, int c1, uint32_t bar) {
  asm volatile(EL("cp.async.bulk.tensor.2d.shared::cluster.global.mbarrier::complete_tx::bytes.multicast::cluster [%0], [%1, {%3, %4}], [%2], %5;")
               ::"r"(dst), "l"(m), "r"(bar), "r"(c0), "r"(c1), "h"((uint16_t)3) : "memory");
}
DEVINL void e_arrive_both(uint32_t bar) {
  asm volatile("{\n.reg .pred pe;\n.reg .b32 r0, r1;\nelect.sync _|pe, 0xffffffff;\nmapa.shared::cluster.u32 r0, %0, 0;\nmapa.shared::cluster.u32 r1, %0, 1;\n"
               "@pe mbarrier.arrive.shared::cluster.b64 _, [r0];\n@pe mbarrier.arrive.shared::cluster.b64 _, [r1];\n}" ::"r"(bar) : "memory");
}
DEVINL void tma_st(const CUtensorMap* m, int c0, int c1, uint32_t src) {
  asm volatile(EL("cp.async.bulk.tensor.2d.global.shared::cta.bulk_group [%0, {%2, %3}], [%1];") ::"l"(m), "r"(src), "r"(c0), "r"(c1) : "memory");
}
DEVINL void bulk_commit() { asm volatile("cp.async.bulk.commit_group;" ::: "memory"); }
template <int N> DEVINL void bulk_wait_n() { asm volatile("cp.async.bulk.wait_group %0;\nbar.warp.sync 0xffffffff;" ::"n"(N) : "memory"); }
DEVINL void l2_prefetch(const void* g, uint32_t bytes) { asm volatile(EL("cp.async.bulk.prefetch.L2.global [%0], %1;") ::"l"(g), "r"(bytes) : "memory"); }
DEVINL void fence_async_smem() { asm volatile("fence.proxy.async.shared::cta;" ::: "memory"); }
DEVINL void fence_async_gl() { asm volatile("fence.proxy.async.global;" ::: "memory"); }
DEVINL void cluster_wait() { asm volatile("barrier.cluster.wait.aligned;" ::: "memory"); }
DEVINL void bar_sync(int id, int n) { asm volatile("bar.sync %0, %1;" ::"r"(id), "r"(n) : "memory"); }
DEVINL void bar_arrive(int id, int n) { asm volatile("bar.arrive %0, %1;" ::"r"(id), "r"(n) : "memory"); }
DEVINL uint32_t ld_acquire(const uint32_t* p) { uint32_t v; asm volatile("ld.acquire.gpu.global.u32 %0, [%1];" : "=r"(v) : "l"(p) : "memory"); return v; }
DEVINL void watch(const uint32_t* p, uint32_t target, uint32_t all, uint32_t tag, uint32_t slot) {
  uint32_t seen = 0;
#pragma unroll 1
  for (uint32_t n = 0; n < 200000u && seen != all; n++) {
    const uint32_t m = __ballot_sync(~0u, (int)(ld_acquire(p) - target) >= 0) & all;
    if (m != seen) { seen = m; asm volatile("st.release.cta.shared.u32 [%0], %1;" ::"r"(slot), "r"(tag << 16 | m) : "memory"); }
  }
}
template <bool RELAXED = false> DEVINL void await_bit(uint32_t slot, uint32_t tag, int j, uint32_t& rdy) {
  if ((rdy >> j) & 1) return;
#pragma unroll 1
  for (uint32_t n = 0; n < 8000000u; n++) {
    uint32_t v;
    asm volatile("ld.acquire.cta.shared.u32 %0, [%1];" : "=r"(v) : "r"(slot) : "memory");
    if ((v >> 16) == tag && ((v >> j) & 1)) { rdy = v; break; }
    if (RELAXED) __nanosleep(200);
  }
  asm volatile("fence.proxy.async.global;" ::: "memory");
}
DEVINL void poll_ge(const uint32_t* p, uint32_t target) {
#pragma unroll 1
  for (uint32_t n = 0; n < 200000u; n++) if (__all_sync(~0u, (int)(ld_acquire(p) - target) >= 0)) break;
}
DEVINL int lane_id() { int v; asm volatile("mov.u32 %0, %%laneid;" : "=r"(v)); return v; }
__host__ DEVINL int remap(int v) {
  const int c = v >> 1, u = c - 36, r = (u * 37) >> 8;
  const int L = c < 4 ? 32 + 8 * c : c < 36 ? c - 4 : 33 + u + r;
  return 2 * L + (v & 1);
}
DEVINL int block_id() { int v; asm volatile("mov.u32 %0, %%ctaid.x;" : "=r"(v)); return v; }
#define cta_id() prm.map[block_id()]
#define IDS() const int lane = lane_id(), b = cta_id(), bm = b >> 4, bn = b & 15, rank = b & 1, pm = 2 * bm + (bn >> 3), pn = bn & 7, po = pm & 1; \
  (void)lane; (void)bm; (void)bn; (void)rank; (void)pm; (void)pn; (void)po
DEVINL void st_tagged(uint4* p, uint32_t a, uint32_t b, uint32_t c, uint32_t tag) {
  asm volatile("{\n.reg .b64 u, v;\n.reg .b128 t;\nmov.b64 u, {%1, %2};\nmov.b64 v, {%3, %4};\nmov.b128 t, {u, v};\nst.relaxed.gpu.global.b128 [%0], t;\n}"
               ::"l"(p), "r"(a), "r"(b), "r"(c), "r"(tag) : "memory");
}
DEVINL uint32_t ld_tagged(const uint4* p, uint32_t* r) {
  uint32_t tag;
  asm volatile("{\n.reg .b64 u, v;\n.reg .b128 t;\nld.relaxed.gpu.global.b128 t, [%4];\nmov.b128 {u, v}, t;\nmov.b64 {%0, %1}, u;\nmov.b64 {%2, %3}, v;\n}"
               : "=r"(r[0]), "=r"(r[1]), "=r"(r[2]), "=r"(tag) : "l"(p) : "memory");
  return tag;
}
DEVINL float ex2(float x) { float y; asm("ex2.approx.ftz.f32 %0, %1;" : "=f"(y) : "f"(x)); return y; }
DEVINL float rcp(float x) { float y; asm("rcp.approx.ftz.f32 %0, %1;" : "=f"(y) : "f"(x)); return y; }
DEVINL uint32_t pack2(float lo, float hi) { uint32_t r; asm("cvt.rn.bf16x2.f32 %0, %1, %2;" : "=r"(r) : "f"(hi), "f"(lo)); return r; }
DEVINL uint32_t pack2h(float lo, float hi) { uint32_t r; asm("cvt.rn.f16x2.f32 %0, %1, %2;" : "=r"(r) : "f"(hi), "f"(lo)); return r; }
DEVINL float bf_lo(uint32_t w) { return __uint_as_float(w << 16); }
DEVINL float bf_hi(uint32_t w) { return __uint_as_float(w & 0xFFFF0000u); }
DEVINL float bf_round(float x) { return bf_lo(pack2(x, 0.f)); }
DEVINL uint32_t add_bf16x2(uint32_t a, uint32_t b) { uint32_t r; asm("add.rn.bf16x2 %0, %1, %2;" : "=r"(r) : "r"(a), "r"(b)); return r; }
DEVINL void stsm4(uint32_t addr, uint32_t a, uint32_t b, uint32_t c, uint32_t d) {
  asm volatile("stmatrix.sync.aligned.m8n8.x4.shared.b16 [%0], {%1, %2, %3, %4};" ::"r"(addr), "r"(a), "r"(b), "r"(c), "r"(d) : "memory");
}
DEVINL void ldsm4(uint32_t addr, uint32_t (&r)[4]) {
  asm volatile("ldmatrix.sync.aligned.m8n8.x4.shared.b16 {%0, %1, %2, %3}, [%4];" : "=r"(r[0]), "=r"(r[1]), "=r"(r[2]), "=r"(r[3]) : "r"(addr) : "memory");
}
DEVINL void ldsm4t(uint32_t addr, uint32_t (&r)[4]) {
  asm volatile("ldmatrix.sync.aligned.m8n8.x4.trans.shared.b16 {%0, %1, %2, %3}, [%4];" : "=r"(r[0]), "=r"(r[1]), "=r"(r[2]), "=r"(r[3]) : "r"(addr) : "memory");
}
DEVINL void sts128(uint32_t addr, uint32_t a, uint32_t b, uint32_t c, uint32_t d) {
  asm volatile("st.shared.v4.b32 [%0], {%1, %2, %3, %4};" ::"r"(addr), "r"(a), "r"(b), "r"(c), "r"(d) : "memory");
}
DEVINL float2 lds64f(uint32_t addr) { float2 v; asm volatile("ld.shared.v2.f32 {%0, %1}, [%2];" : "=f"(v.x), "=f"(v.y) : "r"(addr) : "memory"); return v; }
DEVINL void mma16816(float (&d)[4], uint32_t a0, uint32_t a1, uint32_t a2, uint32_t a3, uint32_t b0, uint32_t b1) {
  asm("mma.sync.aligned.m16n8k16.row.col.f32.bf16.bf16.f32 {%0, %1, %2, %3}, {%4, %5, %6, %7}, {%8, %9}, {%0, %1, %2, %3};"
               : "+f"(d[0]), "+f"(d[1]), "+f"(d[2]), "+f"(d[3]) : "r"(a0), "r"(a1), "r"(a2), "r"(a3), "r"(b0), "r"(b1));
}
template <int N> DEVINL void fence_regs(float (&d)[N]) {
#pragma unroll
  for (int i = 0; i < N; i++) asm volatile("" : "+f"(d[i])::"memory");
}
template <int N> DEVINL void fence_regs(uint32_t (&d)[N]) {
#pragma unroll
  for (int i = 0; i < N; i++) asm volatile("" : "+r"(d[i])::"memory");
}
DEVINL void lds128(uint32_t addr, uint32_t* r) {
  asm volatile("ld.shared.v4.b32 {%0, %1, %2, %3}, [%4];" : "=r"(r[0]), "=r"(r[1]), "=r"(r[2]), "=r"(r[3]) : "r"(addr) : "memory");
}
DEVINL void sched_fence() { asm volatile("griddepcontrol.launch_dependents;" ::: "memory"); }

__device__ __align__(1024) bf16 g_xs[2048 * 1024];
__device__ __align__(1024) bf16 g_os[2048 * 1024];
__device__ __align__(1024) bf16 g_k[32 * 2048 * 32];
__device__ __align__(1024) bf16 g_v[32 * 2048 * 32];
__device__ __align__(16) uint32_t g_esc[4 * 65536 * 16];
__device__ __align__(128) float2 g_stats[8 * 2048];
__device__ __align__(16) float g_csp[2 * 16 * 8 * 192];
__device__ __align__(128) float g_kn[2 * 128 * 16];
__device__ __align__(128) uint4 g_halo[2 * 128 * 12 * 32];
__device__ __align__(128) uint32_t g_cnt[256 * 32];
__device__ uint32_t g_epoch;

DEVINL uint32_t* cnt_x(int l, int bm) { return g_cnt + (l * 8 + bm) * 32; }
DEVINL uint32_t* cnt_o(int l, int pm, int h) { return g_cnt + (32 + (l * 16 + pm) * 2 + h) * 32; }
DEVINL uint32_t* cnt_kv(int lb, int bn) { return g_cnt + (160 + lb * 16 + bn) * 32; }
DEVINL uint32_t* cnt_ad(int bn) { return g_cnt + (192 + bn) * 32; }
DEVINL uint32_t* cnt_cs(int t, int bn) { return g_cnt + (208 + t * 16 + bn) * 32; }

DEVINL int qord(int i, int l, int pn) { return l == 0 ? i : i < 4 ? ((2 * pn) ^ (i & 2)) + (i & 1) : i - 4 < 2 * (pn & 6) ? i - 4 : i; }
struct Params {
  CUtensorMap m[17];
  const bf16* x0;
  const bf16* wq[2];
  uint32_t zero;
  int map[128];
  struct { uint64_t kd, vd; } kv[17];
};
enum { M_X0A = 0, M_XSA, M_WQA, M_WQB, M_WOA, M_WOB, M_OS, M_K, M_V, M_X0R, M_XSR, M_XSO, M_OUT, M_XST, M_X0H, M_K16, M_V16, M_COUNT };

constexpr uint32_t QSTG = 57344;
constexpr uint32_t T0 = 65536, TSTG = 32768;
constexpr uint32_t ONES = 230400;
constexpr uint32_t PSTG = 32768, RES = 196608;
constexpr uint32_t KSC = 98304, VSC = 133120, HRS = 167936;
constexpr uint32_t ROWST = 229376, COLS = 231424, BARS = 232192, SMEM_BYTES = 232448;
constexpr uint32_t B_QF = BARS, B_QE = BARS + 32, B_TF = BARS + 64, B_TE = BARS + 96, B_PF = BARS + 128, B_PE = BARS + 176,
                   B_RF = BARS + 224, W_X = BARS + 232, W_O = BARS + 236, B_QL = BARS + 240, B_PA = BARS + 248;
enum { NB_ST = 1, NB_KV = 2  , NB_DONE = 3, NB_SC = 4, NB_SIG = 5  , NB_KN = 9  , NB_X = 11, NB_HALO = 12  , NB_X0 = 15 };

DEVINL uint32_t pslot_b(uint32_t s) { return ((0x320415u >> (4 * s)) & 7) * 16384u; }
DEVINL uint32_t pslot_a(uint32_t s, int l) { return 98304u + ((((l & 1) ? 0x541230u : 0x041235u) >> (4 * s)) & 7) * 16384u; }

constexpr float QSCALE = 0.17677669529663687f * 1.4426950408889634f;
constexpr uint32_t QPARK = 32768;

DEVINL uint32_t exp2_h2(uint32_t s, uint32_t c882) {
  uint32_t r, t, w, m, d;
  asm volatile("{.reg .b64 t; add.rn.f16x2 %0, %1, %2; cvt.u64.u32 t, %0; cvt.u32.u64 %0, t;}" : "=r"(r) : "r"(s), "r"(0x65F565F5u));
  asm volatile("fma.rn.f16x2 %0, %1, %2, %3;" : "=r"(t) : "r"(r), "r"(0xB8A0B8A0u), "r"(c882));
  asm volatile("fma.rn.f16x2 %0, %1, %2, %3;" : "=r"(w) : "r"(s), "r"(0x38A038A0u), "r"(t));
  asm volatile("fma.rn.f16x2 %0, %1, %1, %2;" : "=r"(m) : "r"(w), "r"(0x48244833u));
  asm volatile("{.reg .b32 t; shf.l.clamp.b32 t, %2, %1, 7; add.u32 %0, t, %2;}" : "=r"(d) : "r"(r), "r"(m));
  return d;
}
DEVINL float exp2_fix(float s) { float z; asm volatile("add.rn.f32 %0, %1, 0f43BF34BC;" : "=f"(z) : "f"(s)); return z; }
DEVINL uint32_t exp2_base(float z0, float z1) { uint32_t B; asm volatile("prmt.b32 %0, %1, %2, 0x6521;" : "=r"(B) : "r"(__float_as_uint(z0)), "r"(__float_as_uint(z1))); return B; }
template <uint32_t MASK> DEVINL uint32_t and_or(uint32_t a, uint32_t c) { uint32_t r; asm volatile("lop3.b32 %0, %1, %3, %2, 0xEA;" : "=r"(r) : "r"(a), "r"(c), "n"(MASK)); return r; }
DEVINL uint32_t fma_bf2(uint32_t a, uint32_t b, uint32_t c) { uint32_t r; asm volatile("fma.rn.bf16x2 %0, %1, %2, %3;" : "=r"(r) : "r"(a), "r"(b), "r"(c)); return r; }
DEVINL float ex2v(float x) { float y; asm volatile("ex2.approx.ftz.f32 %0, %1;" : "=f"(y) : "f"(x)); return y; }
DEVINL uint32_t pack2v(float lo, float hi) { uint32_t r; asm volatile("cvt.rn.bf16x2.f32 %0, %1, %2;" : "=r"(r) : "f"(hi), "f"(lo)); return r; }
DEVINL uint32_t unesc(uint32_t u, const uint32_t* esc) {
  if ((u & 0x7C00u) == 0x7C00u || (u & 0x7C000000u) == 0x7C000000u) return __ldcg(esc);
  float lo, hi;
  asm("{.reg .f16 a, b; mov.b32 {a, b}, %2; cvt.f32.f16 %0, a; cvt.f32.f16 %1, b;}" : "=f"(lo), "=f"(hi) : "r"(u));
  return pack2(lo, hi);
}

DEVINL void attn_slow(const uint32_t (&q)[8], int head, const uint32_t* kesc, float (&res)[20], int lane) {
  const int g = lane >> 2, qd = lane & 3;
  const bf16* kb = g_k + (size_t)head * 2048 * 32;
  const bf16* vb = g_v + (size_t)head * 2048 * 32;
  float o[4][4], m0 = -INFINITY, m1 = -INFINITY, l0 = 0.f, l1 = 0.f;
#pragma unroll
  for (int j = 0; j < 4; j++) { o[j][0] = o[j][1] = o[j][2] = o[j][3] = 0.f; }
#pragma unroll 1
  for (int k0 = 0; k0 < 2048; k0 += 16) {
    float s[2][4];
#pragma unroll
    for (int nt = 0; nt < 2; nt++) {
      s[nt][0] = s[nt][1] = s[nt][2] = s[nt][3] = 0.f;
      const uint32_t* kp = (const uint32_t*)(kb + (size_t)(k0 + nt * 8 + g) * 32) + qd;
      const uint32_t* ke = kesc + (k0 + nt * 8 + g) * 16 + qd;
      const uint32_t k0r = unesc(__ldcg(kp), ke), k1r = unesc(__ldcg(kp + 4), ke + 4), k2r = unesc(__ldcg(kp + 8), ke + 8), k3r = unesc(__ldcg(kp + 12), ke + 12);
      __syncwarp();
      mma16816(s[nt], q[0], q[1], q[2], q[3], k0r, k1r);
      mma16816(s[nt], q[4], q[5], q[6], q[7], k2r, k3r);
    }
    float a0 = fmaxf(fmaxf(s[0][0], s[0][1]), fmaxf(s[1][0], s[1][1]));
    float a1 = fmaxf(fmaxf(s[0][2], s[0][3]), fmaxf(s[1][2], s[1][3]));
    a0 = fmaxf(a0, __shfl_xor_sync(~0u, a0, 1)); a0 = fmaxf(a0, __shfl_xor_sync(~0u, a0, 2));
    a1 = fmaxf(a1, __shfl_xor_sync(~0u, a1, 1)); a1 = fmaxf(a1, __shfl_xor_sync(~0u, a1, 2));
    const float n0 = fmaxf(m0, a0), n1 = fmaxf(m1, a1);
    const float c0 = (m0 == n0) ? 1.f : ex2(m0 - n0), c1 = (m1 == n1) ? 1.f : ex2(m1 - n1);
    m0 = n0; m1 = n1;
    const uint32_t p0 = pack2(ex2(s[0][0] - n0), ex2(s[0][1] - n0)), p1 = pack2(ex2(s[0][2] - n1), ex2(s[0][3] - n1));
    const uint32_t p2 = pack2(ex2(s[1][0] - n0), ex2(s[1][1] - n0)), p3 = pack2(ex2(s[1][2] - n1), ex2(s[1][3] - n1));
    l0 = l0 * c0 + bf_lo(p0) + bf_hi(p0) + bf_lo(p2) + bf_hi(p2);
    l1 = l1 * c1 + bf_lo(p1) + bf_hi(p1) + bf_lo(p3) + bf_hi(p3);
#pragma unroll
    for (int j = 0; j < 4; j++) {
      o[j][0] *= c0; o[j][1] *= c0; o[j][2] *= c1; o[j][3] *= c1;
      const unsigned short* vp = (const unsigned short*)(vb + (size_t)(k0 + 2 * qd) * 32 + j * 8 + g);
      const uint32_t b0 = (uint32_t)__ldcg(vp) | ((uint32_t)__ldcg(vp + 32) << 16);
      const uint32_t b1 = (uint32_t)__ldcg(vp + 256) | ((uint32_t)__ldcg(vp + 288) << 16);
      mma16816(o[j], p0, p1, p2, p3, b0, b1);
    }
  }
  l0 += __shfl_xor_sync(~0u, l0, 1); l0 += __shfl_xor_sync(~0u, l0, 2);
  l1 += __shfl_xor_sync(~0u, l1, 1); l1 += __shfl_xor_sync(~0u, l1, 2);
#pragma unroll
  for (int j = 0; j < 4; j++) { res[4 * j] = o[j][0]; res[4 * j + 1] = o[j][1]; res[4 * j + 2] = o[j][2]; res[4 * j + 3] = o[j][3]; }
  res[16] = l0; res[18] = l1;
}

__global__ void __cluster_dims__(2, 1, 1) __launch_bounds__(384, 1) fused_kernel(const __grid_constant__ Params prm) {
  extern __shared__ __align__(1024) char smem[];
  const uint32_t sb = (uint32_t)__cvta_generic_to_shared(smem);
  const int tid = threadIdx.x, lane = tid & 31;
  const int wg = __shfl_sync(0xffffffffu, tid >> 7, 0);
  const int w = __shfl_sync(0xffffffffu, (tid >> 5) & 3, 0);
  const int bm = remap(blockIdx.x) >> 4, bn = remap(blockIdx.x) & 15;

  auto first_tile = [&](int kt) {
    e_expect_tx(sb + B_QF + 8 * kt, QSTG);
    tma_ld(sb + kt * QSTG, &prm.m[M_X0A], kt * 64, bm * 256, sb + B_QF + 8 * kt);
    tma_ld3(sb + kt * QSTG + 32768, &prm.m[M_WQA], bn * 64, kt * 64, 0, sb + B_QF + 8 * kt);
  };
  auto init4 = [&](uint32_t bar, uint32_t c0, uint32_t c1, uint32_t c2, uint32_t c3) {
    asm volatile("{\n.reg .pred pe;\nelect.sync _|pe, 0xffffffff;\n@pe mbarrier.init.shared::cta.b64 [%0], %1;\n@pe mbarrier.init.shared::cta.b64 [%0+8], %2;\n"
                 "@pe mbarrier.init.shared::cta.b64 [%0+16], %3;\n@pe mbarrier.init.shared::cta.b64 [%0+24], %4;\n@pe fence.mbarrier_init.release.cluster;\n}"
                 ::"r"(bar), "r"(c0), "r"(c1), "r"(c2), "r"(c3) : "memory");
  };
  if (wg < 2) {
    const uint32_t k = wg * 4 + w, lo = (0x1411814u >> (4 * k)) & 15, hi = (0x1441814u >> (4 * k)) & 15;
    if (tid < 32) asm volatile("prefetch.global.L2 [%0];" ::"l"(prm.x0 + (size_t)(bm * 256 + bn * 16 + (tid & 15)) * 1024 + (tid >> 4) * 64));
    else if (tid < 80) asm volatile("prefetch.global.L2 [%0];" ::"l"(prm.wq[0] + (bm * 16 + (tid & 15)) * 3072 + ((tid >> 4) - 2) * 1024 + bn * 64));
    __syncwarp();
    if (k < 7) init4(sb + B_QE + 32 * k, lo, lo, hi, k == 6 ? 2 : hi);
    __syncwarp();
    if (k == 6 && lane == 0) *(volatile unsigned long long*)(smem + W_X) = 0ull;
  } else if (w == 0) {
    init4(sb + B_QF, 1, 1, 1, 1);
    __syncwarp();
    first_tile(0);
  }
  __syncthreads();
  asm volatile("barrier.cluster.arrive.relaxed.aligned;" ::: "memory");

  if (wg == 2) {
    asm volatile("setmaxnreg.dec.sync.aligned.u32 56;");
    const uint32_t ep1 = *(volatile uint32_t*)&g_epoch + 1;
    if (w == 0) {
      first_tile(1);
      mbar_wait(sb + B_QF, 0);
      first_tile(2); first_tile(3);
#pragma unroll 1
      for (int kt = 4; kt < 16; kt++) l2_prefetch(prm.wq[0] + kt * 196608 + blockIdx.x * 1536, 3072);
      cluster_wait();
#pragma unroll 1
      for (int l = 0; l < 4; l++) {
        IDS();
        const CUtensorMap* mw = &prm.m[M_WQA + (l & 1)];
        const CUtensorMap* mx = &prm.m[l == 0 ? M_X0A : M_XSA];
        const CUtensorMap* mh = &prm.m[l == 0 ? M_X0H : M_XSO];
        const CUtensorMap* mo = &prm.m[M_WOA + (l & 1)];
        auto q_b = [&](int i) {
          const int s = i & 3;
          mbar_wait(sb + B_QE + 8 * s, ((i >> 2) & 1) ^ 1);
          e_expect_tx(sb + B_QF + 8 * s, QSTG);
          tma_ld3(sb + s * QSTG + 32768, mw, bn * 64, qord(i, l, pn) * 64, 0, sb + B_QF + 8 * s);
        };
        uint32_t rdy = l ? 0u : ~0u;
        auto q_a = [&](int i) {
          const int kt = qord(i, l, pn);
          await_bit(sb + W_X, l, kt >> 1, rdy);
          if (i < 4) tma_ld(sb + i * QSTG, mx, kt * 64, bm * 256, sb + B_QF + 8 * i);
          else tma_ld_mc(sb + (i & 3) * QSTG + rank * 16384, mh, kt * 64, bm * 256 + rank * 128, sb + B_QF + 8 * (i & 3));
        };
        if (l > 0) {
          await_bit(sb + W_X, l, pn, rdy);
#pragma unroll 1
          for (int i = 0; i < 2; i++) {
            e_expect_tx(sb + B_QF + 8 * i, 16384);
            tma_ld(sb + i * QSTG + (po ^ 1) * 16384, &prm.m[M_XSO], (2 * pn + i) * 64, (pm ^ 1) * 128, sb + B_QF + 8 * i);
          }
          mbar_wait(sb + B_QF, 0);
          q_a(2);
          mbar_wait(sb + B_QF + 8, 0);
        }
#pragma unroll 1
        for (int i = l ? 3 : 4; i < 16; i++) {
          if (l == 3 && i == 12) poll_ge(cnt_ad(bn), ep1 * 16);
          q_b(i); q_a(i);
        }
        if (l & 1) {
          bar_sync(NB_KV, 288);
          sts128(sb + ONES + lane * 32, 0x3f803f80u, 0x3f803f80u, 0x3f803f80u, 0x3f803f80u);
          sts128(sb + ONES + lane * 32 + 16, 0x3f803f80u, 0x3f803f80u, 0x3f803f80u, 0x3f803f80u);
          fence_async_smem();
          __syncwarp();
          e_arrive(sb + B_TF);
          const int krow = 2 * bn * 2048 + bm * 256;
          uint32_t* kvc = cnt_kv(l >> 1, bn);
          bar_sync(NB_DONE, 288);
          e_red(kvc + bm);
          uint32_t seen = 0;
#pragma unroll 1
          for (int it = 1; it < 16; it++) {
            const int s = it & 3, blk = it;
            if (it == 4) {
              bar_sync(NB_KV + 12, 288);
              mbar_wait(sb + B_TF + 24, 0);
              tma_st(&prm.m[M_K], 0, krow + 2048, sb);
              tma_st(&prm.m[M_V], 0, krow + 2048, sb + 16384);
              bulk_commit();
            }
            if (it == 5) { bulk_wait_n<0>(); e_red(kvc + bm); }
            if (it == 12) { e_expect_tx(sb + B_RF, 32768); tma_ld3(sb + RES, &prm.m[M_XSR], 0, pm * 128, 2 * pn, sb + B_RF); }
            if (it == 2 || it == 3) mbar_wait(sb + B_TF + 8 * (it - 1), 0);
            mbar_wait(sb + B_TE + 8 * s, ((it >> 2) & 1) ^ 1);
            if (it < 8) {
#pragma unroll 1
              for (uint32_t n = 0; n < 200000u && !((seen >> it) & 1); n++)
                seen = __ballot_sync(~0u, (int)(ld_acquire(kvc + ((bm + lane) & 7)) - (ep1 * 2 - 1)) >= 0);
              fence_async_gl();
            } else if (it == 8) { poll_ge(kvc + (lane & 7), ep1 * 2); fence_async_gl(); }
            const int row = (2 * bn + (it >> 3)) * 2048 + ((bm + blk) & 7) * 256;
            e_expect_tx(sb + B_TF + 8 * s, 32768);
            tma_ld(sb + T0 + s * TSTG, &prm.m[M_K], 0, row, sb + B_TF + 8 * s);
            tma_ld(sb + T0 + s * TSTG + 16384, &prm.m[M_V], 0, row, sb + B_TF + 8 * s);
          }
        }
        auto p_b = [&](int i, uint32_t s, uint32_t par) {
          mbar_wait(sb + B_PE + 8 * s, par ^ 1);
          e_expect_tx(sb + B_PF + 8 * s, PSTG);
          tma_ld5(sb + pslot_b(s), mo, i >> 3, 2 * (i & 7), 2 * pn, sb + B_PF + 8 * s);
        };
        auto p_a = [&](int i, uint32_t s) {
          await_bit(sb + W_O, l + 1, i, rdy);
          tma_ld_mc(sb + pslot_a(s, l) + rank * 8192, &prm.m[M_OS], i * 64, pm * 128 + rank * 64, sb + B_PF + 8 * s);
        };
        auto p_a2 = [&](int i) {
          await_bit(sb + W_O, l + 1, i, rdy);
          tma_ld(sb + pslot_a(i, l), &prm.m[M_OS], i * 64, pm * 128, sb + B_PF + 8 * i);
          tma_ld(sb + pslot_a(i, l) + 8192, &prm.m[M_OS], i * 64, pm * 128 + 64, sb + B_PF + 8 * i);
        };
        rdy = 0;
        if (l & 1) {
#pragma unroll 1
          for (int u = 0; u < 6; u++) { const int i = (0x205413 >> (4 * u)) & 7; if (u == 4) mbar_wait(sb + B_TE, 1); p_b(i, i, i < 4 ? 1 : 0); }
#pragma unroll 1
          for (int u = 0; u < 6; u++) {
            const int i = (0x542130 >> (4 * u)) & 7;
            if (!(u & 1)) mbar_wait(sb + B_TE + 8 + 4 * u, 1);
            if (u == 4) bar_sync(NB_ST, 64);
            p_a2(i);
          }
        } else {
#pragma unroll 1
          for (int u = 0; u < 6; u++) { const int i = (0x025413 >> (4 * u)) & 7; if (u == 0 || u == 3) mbar_wait(sb + B_QE + 8 * (u / 3), 1); p_b(i, i, 0); }
          mbar_wait(sb + B_QE + 24, 1);
          e_expect_tx(sb + B_RF, 32768);
          tma_ld3(sb + RES, &prm.m[l == 0 ? M_X0R : M_XSR], 0, pm * 128, 2 * pn, sb + B_RF);
          p_a2(0);
          bar_sync(NB_DONE, 64);
          e_arrive_both(sb + B_PA);
          p_a2(1);
          mbar_wait(sb + B_PA, (l >> 1) & 1);
#pragma unroll 1
          for (int i = 2; i < 6; i++) { if (i > 2) mbar_wait(sb + B_PF + 8 * (i - 3), 0); p_a(i, i); }
        }
        uint32_t s = 0, lap = 1;
#pragma unroll 1
        for (int i = 6; i < 16; i++) {
          p_b(i, s, ((s < 4 ? l : 0) + lap) & 1);
          p_a(i, s);
          if (++s == 6) { s = 0; lap++; }
        }
        const CUtensorMap* mn = &prm.m[M_WQA + ((l + 1) & 1)];
        if (l < 3) {
          mbar_wait(sb + B_PE + 8 * 4, 1); mbar_wait(sb + B_PE + 8 * 5, 1);
          tma_ld3(sb + 32768, mn, bn * 64, 2 * pn * 64, 0, sb + B_QL);
          mbar_wait(sb + B_PE + 8 * 0, l & 1);
          tma_ld3(sb + QSTG + 32768, mn, bn * 64, (2 * pn + 1) * 64, 0, sb + B_QL);
          mbar_wait(sb + B_PE + 8 * 1, l & 1);
          e_expect_tx(sb + B_QF + 16, QSTG);
          tma_ld3(sb + 2 * QSTG + 32768, mn, bn * 64, ((2 * pn) ^ 2) * 64, 0, sb + B_QF + 16);
        }
        if (l < 3) { bar_sync(NB_X, 288); e_expect_tx(sb + B_QL, 49152); }
      }
      if (blockIdx.x == 0 && lane_id() == 0) *(volatile uint32_t*)&g_epoch = ep1;
    } else {
      const int hw = w - 1;
      if (lane < 6 && 6 * hw + lane < M_COUNT) asm volatile("prefetch.tensormap [%0];" ::"l"(&prm.m[6 * hw + lane]) : "memory");
      __syncwarp();
      cluster_wait();
      mbar_wait(sb + B_QF, 0);
#pragma unroll 1
      for (int l = 0; l < 4; l++) {
        IDS();
        if (hw == 2 && l > 0) watch(cnt_x(l, bm) + (lane & 7), ep1 * 2, 0xFFu, l, sb + W_X);
        if (l == 0) {
#pragma unroll 1
          for (int r = 2 * hw; r < 16; r += 6) {
            const uint4* p = (const uint4*)(prm.x0 + (size_t)(b * 16 + r) * 1024) + lane;
            float s1[2] = {0.f, 0.f}, s2[2] = {0.f, 0.f};
#pragma unroll
            for (int i = 0; i < 8; i++) {
              const uint4 v = __ldg(p + 32 * i);
              const uint32_t u[4] = {v.x, v.y, v.z, v.w};
#pragma unroll
              for (int k = 0; k < 4; k++) { const float a = bf_lo(u[k]), c = bf_hi(u[k]); s1[i >> 2] += a + c; s2[i >> 2] = fmaf(a, a, fmaf(c, c, s2[i >> 2])); }
            }
#pragma unroll
            for (int o = 16; o; o >>= 1)
#pragma unroll
              for (int rr = 0; rr < 2; rr++) { s1[rr] += __shfl_xor_sync(~0u, s1[rr], o); s2[rr] += __shfl_xor_sync(~0u, s2[rr], o); }
            if (lane == 0) *(float4*)&g_stats[b * 16 + r] = make_float4(s1[0], s2[0], s1[1], s2[1]);
          }
        }
        if (l == 1) { uint32_t rdy = 0; await_bit<true>(sb + W_X, 1, pn, rdy); mbar_hint(sb + B_QF + 8, 0); }
        if (l < 2) {
          float cs[8];
#pragma unroll
          for (int i = 0; i < 8; i++) cs[i] = 0.f;
          const uint4* wp = (const uint4*)(prm.wq[l] + (size_t)(bm * 128 + (lane >> 3)) * 3072 + hw * 1024 + bn * 64) + (lane & 7);
#pragma unroll 8
          for (int i = 0; i < 32; i++) {
            const uint4 v = __ldg(wp + (size_t)i * 4 * 384);
            cs[0] += bf_lo(v.x); cs[1] += bf_hi(v.x); cs[2] += bf_lo(v.y); cs[3] += bf_hi(v.y);
            cs[4] += bf_lo(v.z); cs[5] += bf_hi(v.z); cs[6] += bf_lo(v.w); cs[7] += bf_hi(v.w);
          }
#pragma unroll
          for (int i = 0; i < 8; i++) { cs[i] += __shfl_xor_sync(~0u, cs[i], 8); cs[i] += __shfl_xor_sync(~0u, cs[i], 16); }
          if (lane < 8) {
            float4* d = (float4*)(g_csp + ((l * 16 + bn) * 8 + bm) * 192 + hw * 64 + lane * 8);
            d[0] = make_float4(cs[0], cs[1], cs[2], cs[3]); d[1] = make_float4(cs[4], cs[5], cs[6], cs[7]);
          }
          __syncwarp();
          asm volatile("fence.acq_rel.gpu;" ::: "memory");
          e_red_relaxed(cnt_cs(l, bn));
          if (l == 0) e_red_relaxed(cnt_x(0, bm) + pn);
          poll_ge(lane < 8 && l == 0 ? cnt_x(0, bm) + lane : cnt_cs(l, bn), ep1 * (lane < 8 && l == 0 ? 6 : 24));
        }
        if (l > 0) {
          uint32_t rdy = 0;
#pragma unroll 1
          for (int j = 0; j < 8; j++) await_bit<true>(sb + W_X, l, j, rdy);
        }
#pragma unroll 1
        for (int it = hw * 32 + lane; it < 176; it += 96) {
          const bool rows = it < 128;
          const float4* p = rows ? (const float4*)(g_stats + bm * 256) + it : (const float4*)(g_csp + ((l & 1) * 16 + bn) * 8 * 192) + (it - 128);
          const int stride = rows ? 1024 : 48, np = rows && l == 0 ? 1 : 8;
          float4 a = make_float4(0.f, 0.f, 0.f, 0.f);
#pragma unroll
          for (int k = 0; k < 8; k++) if (k < np) { const float4 v = __ldcg(p + k * stride); a.x += v.x; a.y += v.y; a.z += v.z; a.w += v.w; }
          if (rows) {
            const float m0 = a.x * (1.f / 1024.f), m1 = a.z * (1.f / 1024.f);
            const float v0 = fmaxf(a.y * (1.f / 1024.f) - m0 * m0, 0.f), v1 = fmaxf(a.w * (1.f / 1024.f) - m1 * m1, 0.f);
            const float r0 = __fdividef(1.f, bf_round(sqrtf(bf_round(bf_round(v0) + 1e-5f)))), r1 = __fdividef(1.f, bf_round(sqrtf(bf_round(bf_round(v1) + 1e-5f))));
            a = make_float4(r0, -bf_round(m0) * (l & 1 ? r0 : 1.f), r1, -bf_round(m1) * (l & 1 ? r1 : 1.f));
          }
          *(float4*)(smem + ROWST + it * 16) = a;
        }
        __syncwarp();
        if (lane == 0) asm volatile("red.release.cta.shared.add.u32 [%0], 0x100;" ::"r"(sb + W_X) : "memory");
        if (hw == 2) {
          if (!(l & 1)) {
            bar_sync(NB_ST, 288);
            const uint4* hp = g_halo + ((l >> 1) * 128 + b - 16) * 384 + lane;
#pragma unroll 1
            for (int h = 0; h < 2; h++) {
              uint32_t t[18];
#pragma unroll
              for (int i = 0; i < 18; i++) t[i] = 0;
#pragma unroll 1
              for (uint32_t n = bm ? 0 : 100000u; n < 100000u; n++) {
                uint32_t miss = 0;
#pragma unroll
                for (int i = 0; i < 6; i++) miss |= ld_tagged(hp + h * 192 + i * 32, &t[3 * i]) ^ ep1;
                if (__all_sync(~0u, !miss)) break;
              }
              mbar_wait(sb + B_QE + 16, 1);
              const uint32_t r = (lane & 7) + ((lane >> 3) & 1) * 8, rv = lane >> 2;
#pragma unroll
              for (int jj = 0; jj < 2; jj++) stsm4(sb + KSC + r * 128 + (((4 * h + 2 * jj + (lane >> 4)) ^ (r & 7)) << 4), t[4 * jj], t[4 * jj + 1], t[4 * jj + 2], t[4 * jj + 3]);
              const uint32_t ad = sb + VSC + rv * 128 + (((4 * h + (lane & 3)) ^ (rv & 7)) << 4);
              sts128(ad, t[8], t[10], t[12], t[14]); sts128(ad + 1024, t[9], t[11], t[13], t[15]);
              if (h == 0 && !(lane & 2)) *(uint32_t*)(smem + HRS + ((lane >> 2) + 8 * (lane & 1)) * 8) = t[16];
              bar_arrive(NB_HALO + h, 64);
            }
          } else {
            mbar_wait(sb + B_TF + 16, 0); mbar_wait(sb + B_TF + 16, 1);
            poll_ge(cnt_kv(l >> 1, bn) + (lane & 7), ep1 * 2);
            const uint4 v = __ldcg((const uint4*)(g_kn + ((l >> 1) * 128 + bn * 8) * 16) + lane);
            const uint32_t mx = max(max(v.x, v.y), max(v.z, v.w));
            const uint32_t m0 = __reduce_max_sync(~0u, (lane & 2) ? 0u : mx), m1 = __reduce_max_sync(~0u, (lane & 2) ? mx : 0u);
            if (lane == 0) *(uint2*)(smem + ROWST) = make_uint2(m0, m1);
            __syncwarp();
            bar_arrive(NB_KN, 160); bar_arrive(NB_KN + 1, 160);
            mbar_wait(sb + B_TF + 16, 0); mbar_wait(sb + B_TF + 16, 1);
          }
        } else {
#pragma unroll 1
          for (int i = 0; i < 2; i++) {
            const int h = l & 1 ? i : hw, g = l & 1 ? hw : i;
            bar_sync(NB_SIG + 2 * h + g, 160);
            if (!(l & 1) && i == 0) continue;
            if (i == 1 && hw == 1) bar_arrive(l & 1 ? NB_ST : NB_DONE, 64);
            asm volatile("fence.acq_rel.gpu;" ::: "memory");
            e_red_relaxed(cnt_o(l, 2 * bm + g, h) + (bn >> 1));
            if (!(l & 1)) e_red_relaxed(cnt_o(l, 2 * bm, h) + (bn >> 1));
            if (h == 1 && l == 1) e_red_relaxed(cnt_ad(bn));
          }
        }
        if (hw == 2) watch(cnt_o(l, pm, (lane >> 3) & 1) + (lane & 7), ep1 * 2, 0xFFFFu, l + 1, sb + W_O);
        if (hw == 0 && l < 3) {
          bar_sync(NB_X0, 288);
          e_red(cnt_x(l + 1, bm) + pn);
        }
      }
    }
  } else {
    asm volatile("setmaxnreg.inc.sync.aligned.u32 224;");
    const uint32_t zero = prm.zero;
    cluster_wait();
#pragma unroll 1
    for (int l = 0; l < 4; l++) {
      {
        float acc[2][96];
#pragma unroll
        for (int i = 0; i < 96; i++) { acc[0][i] = 0.f; acc[1][i] = 0.f; }
        fence_regs(acc[0]); fence_regs(acc[1]);
        const bool early = l > 0 && wg == ((cta_id() >> 3) & 1);
        uint32_t ep1 = 0;
#pragma unroll 1
        for (int kt = 0; kt < 16; kt++) {
          const int s = kt & 3;
          if (l > 0 && kt == 0) mbar_wait(sb + B_QL, (l + 1) & 1);
          if (!(early && kt < 2)) mbar_wait(sb + B_QF + 8 * s, (kt >> 2) & 1);
          const uint64_t da = mkdesc(sb + s * QSTG + wg * 16384, 16, 1024, 1), db = mkdesc(sb + s * QSTG + 32768, 8192, 1024, 1);
          wg_fence();
#pragma unroll
          for (int m = 1; m >= 0; m--) {
#pragma unroll
            for (int k = 0; k < 4; k++) wgmma_m64n192k16_ss_tb(acc[m], da + m * 512 + k * 2, db + k * 128, 1);
            wg_commit();
          }
          if (kt == 15 && !(l & 1)) bar_arrive(NB_ST, 288);
          if (kt == 4) ep1 = *(volatile uint32_t*)&g_epoch + 1;
          wg_wait<2>();
          if (early && (kt == 1 || kt == 2)) mbar_wait(sb + B_QF + 8 * (kt - 1), 0);
          if (kt > 0 && w == 0) e_arrive_both(sb + B_QE + 8 * ((kt - 1) & 3));
        }
#pragma unroll 1
        for (uint32_t n = 0; n < 4000000u; n++) {
          uint32_t v;
          asm volatile("ld.acquire.cta.shared.u32 %0, [%1];" : "=r"(v) : "r"(sb + W_X) : "memory");
          if ((v >> 8) == (uint32_t)(l * 256 + 3)) break;
        }
        IDS();
        const int g = lane >> 2, qd = lane & 3;
        float2 st[2][2];
#pragma unroll
        for (int m = 0; m < 2; m++)
#pragma unroll
          for (int hh = 0; hh < 2; hh++) st[m][hh] = lds64f(sb + ROWST + (wg * 128 + m * 64 + w * 16 + g + 8 * hh) * 8);
        float2 cs[4];
        auto load_cs = [&](int gi) {
#pragma unroll
          for (int j = 0; j < 4; j++) cs[j] = lds64f(sb + COLS + (gi * 32 + j * 8 + 2 * qd) * 4);
        };
        load_cs(2);
        auto drain = [&]() {
          wg_wait<0>(); fence_regs(acc[0]);
          if (w == 0) e_arrive_both(sb + B_QE + 8 * 3);
        };
        wg_wait<1>(); fence_regs(acc[1]);
        auto norm_tile = [&](int gi, int m, float sc, uint32_t (&t)[8], float (&nrm)[2], bool h16 = false) {
          const float r0 = st[m][0].x * sc, s0 = st[m][0].y * sc, r1 = st[m][1].x * sc, s1 = st[m][1].y * sc;
          float n0 = 0.f, n1 = 0.f;
#pragma unroll
          for (int j = 0; j < 4; j++) {
            const float* a = &acc[m][16 * gi + 4 * j];
            const float v0 = fmaf(a[0], r0, s0 * cs[j].x), v1 = fmaf(a[1], r0, s0 * cs[j].y);
            const float v2 = fmaf(a[2], r1, s1 * cs[j].x), v3 = fmaf(a[3], r1, s1 * cs[j].y);
            n0 = fmaf(v0, v0, fmaf(v1, v1, n0)); n1 = fmaf(v2, v2, fmaf(v3, v3, n1));
            t[2 * j] = h16 ? pack2h(v0, v1) : pack2(v0, v1); t[2 * j + 1] = h16 ? pack2h(v2, v3) : pack2(v2, v3);
          }
          nrm[0] = n0; nrm[1] = n1;
        };
        auto norm_group = [&](int gi, float sc, uint32_t (&t)[2][8], float (&nrm)[2][2]) { norm_tile(gi, 0, sc, t[0], nrm[0]); norm_tile(gi, 1, sc, t[1], nrm[1]); };
        uint32_t q[2][2][8];
        const uint32_t srow = (lane & 7) + ((lane >> 3) & 1) * 8;
        const uint32_t row0 = wg * 128 + w * 16;
        auto put_o = [&](int h, int m, const float (&o)[16], float i0, float i1) {
          IDS();
          bf16* op = g_os + (size_t)(bm * 256 + row0 + m * 64 + (lane >> 2)) * 1024 + h * 512 + bn * 32 + (lane & 3) * 8;
          *(uint4*)op = make_uint4(pack2(o[0] * i0, o[1] * i0), pack2(o[4] * i0, o[5] * i0), pack2(o[8] * i0, o[9] * i0), pack2(o[12] * i0, o[13] * i0));
          *(uint4*)(op + 8 * 1024) = make_uint4(pack2(o[2] * i1, o[3] * i1), pack2(o[6] * i1, o[7] * i1), pack2(o[10] * i1, o[11] * i1), pack2(o[14] * i1, o[15] * i1));
        };
        if (!(l & 1)) {
          auto put_kv = [&](int gi, uint32_t r0, const uint32_t (&t)[8]) {
            if (gi < 4) {
              const uint32_t r = r0 + srow;
#pragma unroll
              for (int jj = 0; jj < 2; jj++) stsm4(sb + KSC + r * 128 + (((4 * (gi - 2) + 2 * jj + (lane >> 4)) ^ (r & 7)) << 4), t[4 * jj], t[4 * jj + 1], t[4 * jj + 2], t[4 * jj + 3]);
            } else {
              const uint32_t r = r0 + g, ad = sb + VSC + r * 128 + (((4 * (gi - 4) + qd) ^ (r & 7)) << 4);
              sts128(ad, t[0], t[2], t[4], t[6]); sts128(ad + 1024, t[1], t[3], t[5], t[7]);
            }
          };
          auto cen_tile = [&](int gi, int m, uint32_t (&t)[8]) {
#pragma unroll
            for (int j = 0; j < 4; j++) {
              const float* a = &acc[m][16 * gi + 4 * j];
              t[2 * j] = pack2(fmaf(st[m][0].y, cs[j].x, a[0]), fmaf(st[m][0].y, cs[j].y, a[1]));
              t[2 * j + 1] = pack2(fmaf(st[m][1].y, cs[j].x, a[2]), fmaf(st[m][1].y, cs[j].y, a[3]));
            }
          };
          const bool send = wg == 1 && w == 3 && bm < 7;
          uint4* hp = g_halo + ((l >> 1) * 128 + b) * 384 + lane;
          mbar_wait(sb + B_QE + 16, 1);
          float2 cn[4];
          auto next_cs = [&](int gi) {
#pragma unroll
            for (int j = 0; j < 4; j++) { cs[j] = cn[j]; cn[j] = lds64f(sb + COLS + (gi * 32 + j * 8 + 2 * qd) * 4); }
          };
#pragma unroll
          for (int j = 0; j < 4; j++) cn[j] = cs[j];
#pragma unroll
          for (int h = 0; h < 2; h++) {
            uint32_t k[8], v[8];
            next_cs(4 + h);
            cen_tile(2 + h, 1, k); put_kv(2 + h, 16 + row0 + 64, k);
            next_cs(h ? 2 : 3);
            cen_tile(4 + h, 1, v); put_kv(4 + h, 16 + row0 + 64, v);
            if (send) {
              uint4* p = hp + h * 192;
              st_tagged(p, k[0], k[1], k[2], ep1); st_tagged(p + 32, k[3], k[4], k[5], ep1); st_tagged(p + 64, k[6], k[7], v[0], ep1);
              st_tagged(p + 96, v[1], v[2], v[3], ep1); st_tagged(p + 128, v[4], v[5], v[6], ep1);
              st_tagged(p + 160, v[7], __float_as_uint(qd & 1 ? st[1][1].x : st[1][0].x), 0u, ep1);
            }
            sched_fence();
          }
          drain();
          {
            uint32_t t[8];
            next_cs(4); cen_tile(2, 0, t); put_kv(2, 16 + row0, t);
            next_cs(0); cen_tile(4, 0, t); put_kv(4, 16 + row0, t);
            next_cs(3); cen_tile(0, 0, q[0][0]); cen_tile(0, 1, q[0][1]);
          }
          bar_sync(NB_SC, 256);
          const bool e = g & 1, sel = 2 * qd + (g & 1) >= g + 2, first = bm == 0 && row0 == 0;
          if (row0 == 0) bar_sync(NB_HALO, 64);
          float ra[4], rb[4], ca[4], cb[4];
#pragma unroll
          for (int m = 0; m < 2; m++) {
            float rk[3];
#pragma unroll
            for (int u = 0; u < 3; u++) {
              const int r = row0 + m * 64 + 8 * u + 2 * qd + e - (sel ? 16 : 8);
              rk[u] = lds64f(sb + (m == 0 && r < 0 ? HRS + 128 : ROWST) + r * 8).x;
            }
            ra[2 * m] = sel ? rk[1] : rk[0]; ra[2 * m + 1] = sel ? rk[2] : rk[1];
            rb[2 * m] = sel ? rk[0] : rk[1]; rb[2 * m + 1] = sel ? rk[1] : rk[2];
          }
#pragma unroll
          for (int i = 0; i < 4; i++) { const float rq = st[i >> 1][i & 1].x * QSCALE; ca[i] = rq * ra[i]; cb[i] = rq * rb[i]; }
#pragma unroll 1
          for (int h = 0; h < 2; h++) {
            float s[2][4][4];
            uint32_t vf[2][4][4], pf[2][2][4];
#pragma unroll
            for (int m = 0; m < 2; m++)
#pragma unroll
              for (int nt = 0; nt < 4; nt++) {
                uint32_t kf[4];
                const uint32_t r = row0 + m * 64 + 8 * nt + (lane & 7), ch = 4 * h + (lane >> 3);
                ldsm4(sb + KSC + r * 128 + ((ch ^ (r & 7)) << 4), kf);
                s[m][nt][0] = s[m][nt][1] = s[m][nt][2] = s[m][nt][3] = 0.f;
                mma16816(s[m][nt], q[0][m][0], q[0][m][1], q[0][m][2], q[0][m][3], kf[0], kf[1]);
                mma16816(s[m][nt], q[0][m][4], q[0][m][5], q[0][m][6], q[0][m][7], kf[2], kf[3]);
              }
#pragma unroll
            for (int m = 0; m < 2; m++)
#pragma unroll
              for (int i = 0; i < 4; i++) {
                const uint32_t r = row0 + m * 64 + 16 * (i >> 1) + srow, ch = 4 * h + 2 * (i & 1) + (lane >> 4);
                ldsm4t(sb + VSC + r * 128 + ((ch ^ (r & 7)) << 4), vf[m][i]);
              }
            float va[4], vb[4], mx[4];
#pragma unroll
            for (int i = 0; i < 4; i++) {
              const int m = i >> 1, hh = i & 1;
              const float a = e ? s[m][hh + 1][2 * hh + 1] : s[m][hh + 1][2 * hh];
              const float lo = e ? s[m][hh][2 * hh + 1] : s[m][hh][2 * hh], hi = e ? s[m][hh + 2][2 * hh + 1] : s[m][hh + 2][2 * hh];
              va[i] = (m == 0 && hh == 0 && first) ? -INFINITY : a * ca[i];
              vb[i] = (m == 0 && first && sel) ? -INFINITY : (sel ? lo : hi) * cb[i];
              mx[i] = fmaxf(va[i], vb[i]);
            }
#pragma unroll
            for (int i = 0; i < 4; i++) mx[i] = fmaxf(mx[i], __shfl_xor_sync(~0u, mx[i], 1));
#pragma unroll
            for (int i = 0; i < 4; i++) mx[i] = fmaxf(mx[i], __shfl_xor_sync(~0u, mx[i], 2));
#pragma unroll
            for (int i = 0; i < 4; i++) {
              va[i] = ex2(va[i] - mx[i]); vb[i] = ex2(vb[i] - mx[i]);
              mx[i] = va[i] + vb[i];
              va[i] *= ra[i]; vb[i] *= rb[i];
            }
#pragma unroll
            for (int i = 0; i < 4; i++) mx[i] += __shfl_xor_sync(~0u, mx[i], 1);
#pragma unroll
            for (int i = 0; i < 4; i++) mx[i] += __shfl_xor_sync(~0u, mx[i], 2);
#pragma unroll
            for (int i = 0; i < 4; i++) {
              const int m = i >> 1, hh = i & 1;
              const float inv = rcp(mx[i]);
              const uint32_t t = pack2(va[i] * inv, vb[i] * inv);
              const uint32_t pa = e ? t << 16 : t & 0xFFFFu, pb = e ? t & 0xFFFF0000u : t >> 16;
              pf[m][hh][hh + 1] = pa; pf[m][hh][hh] = sel ? pb : 0u; pf[m][hh][hh + 2] = sel ? 0u : pb; pf[m][hh][3 - 3 * hh] = 0u;
            }
#pragma unroll
            for (int m = 0; m < 2; m++) {
              float o[4][4];
#pragma unroll
              for (int j = 0; j < 4; j++) o[j][0] = o[j][1] = o[j][2] = o[j][3] = 0.f;
#pragma unroll
              for (int i = 0; i < 4; i++) {
                const int kk = i >> 1, jj = 2 * (i & 1);
                mma16816(o[jj], pf[m][0][2 * kk], pf[m][1][2 * kk], pf[m][0][2 * kk + 1], pf[m][1][2 * kk + 1], vf[m][i][0], vf[m][i][1]);
                mma16816(o[jj + 1], pf[m][0][2 * kk], pf[m][1][2 * kk], pf[m][0][2 * kk + 1], pf[m][1][2 * kk + 1], vf[m][i][2], vf[m][i][3]);
              }
              const float of[16] = {o[0][0], o[0][1], o[0][2], o[0][3], o[1][0], o[1][1], o[1][2], o[1][3], o[2][0], o[2][1], o[2][2], o[2][3], o[3][0], o[3][1], o[3][2], o[3][3]};
              put_o(h, m, of, 1.f, 1.f);
            }
            bar_arrive(NB_SIG + 2 * h + wg, 160);
            if (h == 0) {
              uint32_t t[8];
              next_cs(5); cen_tile(3, 0, t); put_kv(3, 16 + row0, t);
              next_cs(1); cen_tile(5, 0, t); put_kv(5, 16 + row0, t);
#pragma unroll
              for (int j = 0; j < 4; j++) cs[j] = cn[j];
              cen_tile(1, 0, q[0][0]); cen_tile(1, 1, q[0][1]);
              bar_sync(NB_SC, 256);
              if (row0 == 0) bar_sync(NB_HALO + 1, 64);
            }
          }
        } else {
          float qn[2];
          drain();
          auto esc_ptr = [&](int gi) { IDS(); return g_esc + (size_t)(((l & 2) + (gi >> 1)) * 65536 + (2 * bn + (gi & 1)) * 2048) * 16; };
          auto norm_half = [&](int gi, float sc, uint32_t (&t)[2][8], float (&nrm)[2][2]) {
            norm_tile(gi, 0, sc, t[0], nrm[0], true); norm_tile(gi, 1, sc, t[1], nrm[1], true);
            if (!((nrm[0][0] + nrm[0][1]) + (nrm[1][0] + nrm[1][1]) <= 4e9f)) {
              uint32_t* p = esc_ptr(gi) + (bm * 256 + row0 + g) * 16 + qd;
#pragma unroll
              for (int m = 0; m < 2; m++) {
                uint32_t u[8]; float d[2];
                norm_tile(gi, m, sc, u, d);
#pragma unroll
                for (int i = 0; i < 8; i++) p[(m * 64 + (i & 1) * 8) * 16 + (i >> 1) * 4] = u[i];
              }
            }
            __syncwarp();
          };
          {
            auto max_norm = [&](const float (&nrm)[2][2]) {
              const bool o1 = qd & 1, o2 = qd & 2;
              const float a = (o1 ? nrm[1][0] : nrm[0][0]) + __shfl_xor_sync(~0u, o1 ? nrm[0][0] : nrm[1][0], 1);
              const float c = (o1 ? nrm[1][1] : nrm[0][1]) + __shfl_xor_sync(~0u, o1 ? nrm[0][1] : nrm[1][1], 1);
              const float d = (o2 ? c : a) + __shfl_xor_sync(~0u, o2 ? a : c, 2);
              return __uint_as_float(__reduce_max_sync(~0u, __float_as_uint(d)));
            };
#pragma unroll
            for (int h = 0; h < 2; h++) {
              uint32_t t[2][8]; float nrm[2][2];
              const uint32_t kb = sb + (h ? 0 : T0);
              if (h) load_cs(3);
              uint32_t tv[2][8];
              norm_half(2 + h, 1.f, t, nrm);
              load_cs(4 + h);
              float nv[2][2];
              if (h == 1) { const float kn = max_norm(nrm); if (lane == 0) g_kn[((l >> 1) * 128 + bn * 8 + bm) * 16 + 8 + wg * 4 + w] = kn; }
              if (h == 0) mbar_wait(sb + B_QE + 8, 1);
#pragma unroll
              for (int i = 0; i < 4; i++) {
                const uint32_t r = row0 + (i >> 1) * 64 + srow;
                stsm4(kb + r * 64 + (((2 * (i & 1) + (lane >> 4)) ^ ((r >> 1) & 3)) << 4), t[i >> 1][4 * (i & 1)], t[i >> 1][4 * (i & 1) + 1], t[i >> 1][4 * (i & 1) + 2], t[i >> 1][4 * (i & 1) + 3]);
              }
              const int krow = 2 * bn * 2048 + bm * 256 + row0;
              if (h == 0) {
                fence_async_smem(); __syncwarp();
                tma_st(&prm.m[M_K16], 0, krow, kb + row0 * 64); tma_st(&prm.m[M_K16], 0, krow + 64, kb + row0 * 64 + 4096);
              }
              norm_group(4 + h, 1.f, tv, nv);
              load_cs(h);
#pragma unroll
              for (int m = 0; m < 2; m++) {
                const uint32_t r = row0 + m * 64 + g, ad = kb + 16384 + r * 64 + ((qd ^ ((r >> 1) & 3)) << 4);
                sts128(ad, tv[m][0], tv[m][2], tv[m][4], tv[m][6]); sts128(ad + 512, tv[m][1], tv[m][3], tv[m][5], tv[m][7]);
              }
              fence_async_smem();
              bar_arrive(NB_KV + 12 * h, 288);
              if (h == 0) {
                __syncwarp();
                tma_st(&prm.m[M_V16], 0, krow, kb + 16384 + row0 * 64); tma_st(&prm.m[M_V16], 0, krow + 64, kb + 16384 + row0 * 64 + 4096);
                bulk_commit();
                if (wg) { bulk_wait_n<0>(); bar_arrive(NB_DONE, 288); bar_sync(NB_HALO + 1, 256); }
              }
              if (h == 0) { const float kn = max_norm(nrm); if (lane == 0) g_kn[((l >> 1) * 128 + bn * 8 + bm) * 16 + wg * 4 + w] = kn; }
              norm_half(h, QSCALE, q[h], nrm);
#pragma unroll
              for (int i = 0; i < 4; i++) sts128(sb + QPARK + h * 16384 + (wg * 128 + w * 32 + lane) * 16 + i * 4096, q[h][i >> 1][4 * (i & 1)], q[h][i >> 1][4 * (i & 1) + 1], q[h][i >> 1][4 * (i & 1) + 2], q[h][i >> 1][4 * (i & 1) + 3]);
              qn[h] = max_norm(nrm);
              if (h == 0 && !wg) { bulk_wait_n<0>(); bar_arrive(NB_DONE, 288); }
            }
            if (!wg) bar_arrive(NB_HALO + 1, 256);
          }
          constexpr uint64_t VSTEP = 64 - (64ull << 16);
          const uint32_t c_882 = 0x62E562E5u + (lane_id() & zero), c_lsb = 0x00010001u + (lane_id() & zero), c_half = 0x3F003F00u + (lane_id() & zero);
          float o[2][20], S[2][32];
          uint32_t H[2][16], P0[4] = {}, P1[4] = {};
#pragma unroll
          for (int m = 0; m < 2; m++) {
#pragma unroll
            for (int i = 0; i < 20; i++) o[m][i] = 0.f;
            fence_regs(o[m]);
          }
          auto qkf = [&](int b, int ks, uint64_t d) { wg_n64_rs_nb_f16_f32(S[b], q[0][0][4 * ks], q[0][0][4 * ks + 1], q[0][0][4 * ks + 2], q[0][0][4 * ks + 3], d + 2 * ks, ks ? 1 : zero); };
          auto qkh = [&](int b, int ks, uint64_t d) { wg_n64_rs_nb_f16_f16(H[b], q[0][1][4 * ks], q[0][1][4 * ks + 1], q[0][1][4 * ks + 2], q[0][1][4 * ks + 3], d + 2 * ks, ks ? 1 : zero); };
          auto pv0 = [&](uint64_t d) { wgmma_m64n40k16_rs_tb(o[0], P0[0], P0[1], P0[2], P0[3], d, 1); };
          auto pv1 = [&](uint64_t d) { wgmma_m64n40k16_rs_tb(o[1], P1[0], P1[1], P1[2], P1[3], d, 1); };
          float e[4] = {};
          auto finish = [&](int h) {
            const float* s = &S[(h >> 2) & 1][8 * (h & 3)];
            const uint32_t* u = &H[(h >> 2) & 1][4 * (h & 3)];
            const float z0 = exp2_fix(s[6]), z1 = exp2_fix(s[7]);
            P0[0] = pack2v(e[0], e[1]);
            P1[0] = exp2_h2(u[0], c_882);
            P0[1] = pack2v(e[2], e[3]);
            P1[1] = exp2_h2(u[1], c_882);
            const uint32_t B = exp2_base(z0, z1), E = and_or<0x7F807F80u>(B, c_lsb);
            P1[3] = exp2_h2(u[3], c_882);
            P0[3] = fma_bf2(B, and_or<0x807F807Fu>(B, c_half), E);
            const float e4 = ex2v(s[4]), e5 = ex2v(s[5]);
            P1[2] = exp2_h2(u[2], c_882);
            P0[2] = pack2v(e4, e5);
          };
          auto start = [&](int h) {
            const float* s = &S[(h >> 2) & 1][8 * (h & 3)];
            e[0] = ex2v(s[0]); e[1] = ex2v(s[1]); e[3] = ex2v(s[3]); e[2] = ex2v(s[2]);
          };
          uint64_t kd = prm.kv[0].kd;
          mbar_wait(sb + B_TF, 0);
          wg_fence();
#pragma unroll
          for (int b = 0; b < 2; b++) {
            wg_n64_rs_nb_f16_f32_z(S[b], q[0][0][0], q[0][0][1], q[0][0][2], q[0][0][3], kd + 256 * b, 0);
            wg_n64_rs_nb_f16_f16_z(H[b], q[0][1][0], q[0][1][1], q[0][1][2], q[0][1][3], kd + 256 * b, 0);
            if (b == 0) { qkf(0, 1, kd); qkh(0, 1, kd); }
            wg_commit();
          }
          wg_wait<1>(); fence_regs(S[0]); fence_regs(H[0]);
          start(0); finish(0); start(1);
          wg_wait<0>();
          int redo = 0;
#pragma unroll 1
          for (int pass = 0, j = 1; pass < 2; pass++) {
#pragma unroll 1
           do {
            const uint64_t vd = prm.kv[j].vd;
            bool go = false;
#pragma unroll
            for (int h = 2; h < 18; h++) {
              const int px = (h >> 2) + 1, c = h & 3;
              wg_fence();
              if (h == 13) kd = prm.kv[j].kd;
              const uint64_t kx = kd + (px & 3) * 256, vx = vd + (h - 2) * VSTEP;
              if (h == 2) { qkh(1, 0, kx); qkf(1, 0, kx); pv0(vx); pv1(vx); qkh(1, 1, kx); qkf(1, 1, kx); }
              else if ((c == 1 || c == 2) && h < 17) { qkh(px & 1, c - 1, kx); pv1(vx); qkf(px & 1, c - 1, kx); pv0(vx); }
              else { pv0(vx); pv1(vx); }
              wg_commit();
              if (h == 3) e_arrive_if(sb + B_TE + 8 * ((j + 2) & 3), j > 1);
              if (h == 11) go = mbar_test(sb + B_TF + 8 * (j & 3), (j >> 2) & 1) && j != 8;
              finish(h - 1); start(h);
              if (h != 12 && h != 17) sched_fence();
              if (h == 12 && !go) {
                if (j == 16) {
#pragma unroll
                  for (int u = 13; u < 18; u++) {
                    wg_fence(); pv0(vd + (u - 2) * VSTEP); pv1(vd + (u - 2) * VSTEP); wg_commit();
                    if (u < 17) finish(u - 1);
                    if (u < 16) { start(u); sched_fence(); }
                    if (u & 1) { if (u == 17) wg_wait<0>(); else wg_wait<1>(); }
                  }
                  e_arrive(sb + B_TE + 24);
                  goto head_done;
                }
                mbar_wait(sb + B_TF + 8 * (j & 3), (j >> 2) & 1);
                if (j == 8) {
#pragma unroll
                  for (int i = 0; i < 4; i++) lds128(sb + QPARK + 16384 + (wg * 128 + w * 32 + lane_id()) * 16 + i * 4096, &q[0][i >> 1][4 * (i & 1)]);
                }
              }
              if (h == 17) wg_wait<0>(); else if (h & 1) wg_wait<1>();
              if (c == 3) { fence_regs(S[px & 1]); fence_regs(H[px & 1]); }
            }
           } while (j++ & 7);
           head_done:
            fence_regs(o[0]); fence_regs(o[1]);
            if (pass == 0) bar_sync(NB_KN + wg, 160);
            const float kmax = *(volatile float*)(smem + ROWST + 4 * pass);
            const bool wide = !(qn[0] <= 1.6e7f && kmax <= 1.6e7f && qn[0] * kmax <= 112.f * 112.f);
            uint32_t pk[2][8];
            auto norm_o = [&](uint32_t (&u)[8], const float (&a)[20]) {
              const float i0 = rcp(a[16]), i1 = rcp(a[18]);
#pragma unroll
              for (int i = 0; i < 4; i++) { u[i] = pack2(a[4 * i] * i0, a[4 * i + 1] * i0); u[4 + i] = pack2(a[4 * i + 2] * i1, a[4 * i + 3] * i1); }
            };
            int badm = 0;
#pragma unroll
            for (int m = 0; m < 2; m++) {
              norm_o(pk[m], o[m]);
              uint32_t chk[2] = {0u, 0u};
#pragma unroll
              for (int i = 0; i < 8; i++) asm("fma.rn.bf16x2 %0, %1, %2, %0;" : "+r"(chk[i & 1]) : "r"(pk[m][i]), "r"(0u));
              const bool bad = wide | !(fminf(o[m][16], o[m][18]) >= 9.3e-10f) | !(o[m][16] + o[m][18] <= 1e36f) | (((chk[0] | chk[1]) & 0x7FFF7FFFu) != 0);
              badm |= __any_sync(~0u, bad) << m;
            }
            if (badm) {
              redo |= badm << 2 * pass;
              uint32_t* p = esc_ptr(pass) + ((cta_id() >> 4) * 256 + row0 + (lane_id() >> 2)) * 16 + (lane_id() & 3);
#pragma unroll
              for (int i = 0; i < 4; i++) {
                uint32_t u[4] = {q[0][i >> 1][4 * (i & 1)], q[0][i >> 1][4 * (i & 1) + 1], q[0][i >> 1][4 * (i & 1) + 2], q[0][i >> 1][4 * (i & 1) + 3]};
                if (pass == 0) lds128(sb + QPARK + (wg * 128 + w * 32 + lane_id()) * 16 + i * 4096, u);
#pragma unroll
                for (int k = 0; k < 4; k++) { uint32_t* a = p + ((i >> 1) * 64 + (k & 1) * 8) * 16 + (2 * (i & 1) + (k >> 1)) * 4; *a = unesc(u[k], a); }
              }
              __syncwarp();
            }
            {
              IDS();
              bf16* op = g_os + (size_t)(bm * 256 + row0 + (lane >> 2)) * 1024 + pass * 512 + bn * 32 + (lane & 3) * 8;
#pragma unroll
              for (int i = 0; i < 4; i++) *(uint4*)(op + ((i >> 1) * 64 + (i & 1) * 8) * 1024) = make_uint4(pk[i >> 1][4 * (i & 1)], pk[i >> 1][4 * (i & 1) + 1], pk[i >> 1][4 * (i & 1) + 2], pk[i >> 1][4 * (i & 1) + 3]);
            }
            if (!badm) bar_arrive(NB_SIG + 2 * pass + wg, 160);
            qn[0] = qn[1];
#pragma unroll
            for (int m = 0; m < 2; m++) {
#pragma unroll
              for (int i = 0; i < 20; i++) o[m][i] = 0.f;
              fence_regs(o[m]);
            }
          }
          if (redo) {
#pragma unroll 1
            for (int t = 0; t < 4; t++) {
              const int pass = t >> 1, m = t & 1;
              if ((redo >> t) & 1) {
                uint32_t qq[8]; float res[20];
                const uint32_t* p = esc_ptr(pass) + ((cta_id() >> 4) * 256 + row0 + m * 64 + (lane_id() >> 2)) * 16 + (lane_id() & 3);
#pragma unroll
                for (int i = 0; i < 8; i++) qq[i] = __ldcg(p + (i & 1) * 128 + (i >> 1) * 4);
                attn_slow(qq, 2 * (cta_id() & 15) + pass, esc_ptr(2 + pass), res, lane_id());
                const float of[16] = {res[0], res[1], res[2], res[3], res[4], res[5], res[6], res[7], res[8], res[9], res[10], res[11], res[12], res[13], res[14], res[15]};
                put_o(pass, m, of, rcp(res[16]), rcp(res[18]));
              }
              if (m && ((redo >> 2 * pass) & 3)) bar_arrive(NB_SIG + 2 * pass + wg, 160);
            }
          }
        }
      }
      {
        float acc[64];
#pragma unroll
        for (int i = 0; i < 64; i++) acc[i] = 0.f;
        fence_regs(acc);
        uint32_t s = 0, lap = 0;
#pragma unroll 1
        for (int kt = 0; kt < 16; kt++) {
          mbar_wait(sb + B_PF + 8 * s, ((s < 4 ? l : 0) + lap) & 1);
          const uint64_t da = mkdesc(sb + pslot_a(s, l) + wg * 8192, 16, 1024, 1), db = mkdesc(sb + pslot_b(s), 8192, 1024, 1);
          wg_fence();
#pragma unroll
          for (int k = 0; k < 4; k++) wgmma_m64n128k16_ss_tb(acc, da + k * 2, db + k * 128, 1);
          wg_commit();
          wg_wait<1>();
          if (kt > 0 && w == 0) e_arrive_both(sb + B_PE + 8 * (s ? s - 1 : 5));
          if (++s == 6) { s = 0; lap++; }
        }
        IDS();
        const int g = lane >> 2, qd = lane & 3;
        const int r0 = wg * 64 + w * 16;
        const uint32_t r = r0 + (lane & 7) + ((lane >> 3) & 1) * 8;
        uint32_t x[8][4];
        mbar_wait(sb + B_RF, l & 1);
#pragma unroll
        for (int jj = 0; jj < 8; jj++) ldsm4(sb + RES + (jj >> 2) * 16384 + r * 128 + ((((2 * jj + (lane >> 4)) & 7) ^ (r & 7)) << 4), x[jj]);
        wg_wait<0>();
        fence_regs(acc);
        if (w == 0) e_arrive_both(sb + B_PE + 8 * 3);
        const CUtensorMap* mo = &prm.m[l == 3 ? M_OUT : M_XST];
#pragma unroll
        for (int jj = 0; jj < 8; jj++) {
#pragma unroll
          for (int i = 0; i < 4; i++) x[jj][i] = add_bf16x2(x[jj][i], pack2(acc[8 * jj + 2 * i], acc[8 * jj + 2 * i + 1]));
          stsm4(sb + RES + (jj >> 2) * 16384 + r * 128 + ((((2 * jj + (lane >> 4)) & 7) ^ (r & 7)) << 4), x[jj][0], x[jj][1], x[jj][2], x[jj][3]);
          if ((jj & 3) == 3) { fence_async_smem(); __syncwarp(); tma_st(mo, pn * 128 + (jj >> 2) * 64, pm * 128 + r0, sb + RES + (jj >> 2) * 16384 + r0 * 128); }
        }
        bulk_commit();
        if (l < 3) {
          bar_sync(NB_SC, 256);
#pragma unroll
          for (int jj = 0; jj < 8; jj++)
            stsm4(sb + (jj >> 2) * QSTG + po * 16384 + r * 128 + ((((2 * jj + (lane >> 4)) & 7) ^ (r & 7)) << 4), x[jj][0], x[jj][1], x[jj][2], x[jj][3]);
          fence_async_smem();
          bar_arrive(NB_X, 288);
          float s1[4] = {0.f, 0.f, 0.f, 0.f}, sa[4] = {0.f, 0.f, 0.f, 0.f}, sc[4] = {0.f, 0.f, 0.f, 0.f};
#pragma unroll
          for (int jj = 0; jj < 8; jj++) {
            mma16816(s1, x[jj][0], x[jj][1], x[jj][2], x[jj][3], 0x3f803f80u, 0x3f803f80u);
            mma16816(sa, x[jj][0], x[jj][1], x[jj][2], x[jj][3], x[jj][0], x[jj][2]);
            mma16816(sc, x[jj][0], x[jj][1], x[jj][2], x[jj][3], x[jj][1], x[jj][3]);
          }
          if (qd == g >> 1) {
            float2* p = g_stats + pn * 2048 + pm * 128 + r0 + g;
            p[0] = make_float2(s1[0], g & 1 ? sa[1] : sa[0]);
            p[8] = make_float2(s1[2], g & 1 ? sc[3] : sc[2]);
          }
        }
        bulk_wait_n<0>();
        if (l < 3) bar_arrive(NB_X0, 288);
      }
    }
  }
  asm volatile("barrier.cluster.arrive.relaxed.aligned;\nbarrier.cluster.wait.aligned;" ::: "memory");
}

typedef CUresult (*EncodeFn)(CUtensorMap*, CUtensorMapDataType, cuuint32_t, void*, const cuuint64_t*, const cuuint64_t*, const cuuint32_t*,
                             const cuuint32_t*, CUtensorMapInterleave, CUtensorMapSwizzle, CUtensorMapL2promotion, CUtensorMapFloatOOBfill);

static void make_map(EncodeFn fn, CUtensorMap* m, const void* ptr, int rank, const uint64_t* dims, const uint64_t* strides, const uint32_t* box, CUtensorMapSwizzle sw) {
  cuuint64_t d[5], st[4];
  cuuint32_t bx[5], es[5];
  for (int i = 0; i < rank; i++) { d[i] = dims[i]; bx[i] = box[i]; es[i] = 1; if (i) st[i - 1] = strides[i - 1] * 2; }
  fn(m, CU_TENSOR_MAP_DATA_TYPE_BFLOAT16, rank, (void*)ptr, d, st, bx, es, CU_TENSOR_MAP_INTERLEAVE_NONE, sw,
     CU_TENSOR_MAP_L2_PROMOTION_L2_128B, CU_TENSOR_MAP_FLOAT_OOB_FILL_NONE);
}
static void map2(EncodeFn fn, CUtensorMap* m, const void* ptr, uint64_t inner, uint64_t outer, uint32_t bi, uint32_t bo, CUtensorMapSwizzle sw) {
  const uint64_t d[2] = {inner, outer}, st[1] = {inner};
  const uint32_t bx[2] = {bi, bo};
  make_map(fn, m, ptr, 2, d, st, bx, sw);
}

extern "C" void kernel_launch(void* const* d_in, const int* in_sizes, int n_in, void* d_out, int out_size) {
  (void)in_sizes; (void)n_in; (void)out_size;
  static EncodeFn enc = nullptr;
  static void *xs, *os, *kk, *vv;
  static int sbase = 1024;
  if (!enc) {
    void* p = nullptr;
    cudaDriverEntryPointQueryResult qr;
    cudaGetDriverEntryPoint("cuTensorMapEncodeTiled", &p, cudaEnableDefault, &qr);
    enc = (EncodeFn)p;
    cudaGetSymbolAddress(&xs, g_xs); cudaGetSymbolAddress(&os, g_os); cudaGetSymbolAddress(&kk, g_k); cudaGetSymbolAddress(&vv, g_v);
    int dev = 0;
    cudaGetDevice(&dev);
    cudaDeviceGetAttribute(&sbase, cudaDevAttrReservedSharedMemoryPerBlock, dev);
    cudaFuncSetAttribute(fused_kernel, cudaFuncAttributeMaxDynamicSharedMemorySize, SMEM_BYTES);
  }
  Params prm;
  const CUtensorMapSwizzle S128 = CU_TENSOR_MAP_SWIZZLE_128B, S64 = CU_TENSOR_MAP_SWIZZLE_64B;
  map2(enc, &prm.m[M_X0A], d_in[0], 1024, 2048, 64, 256, S128);
  map2(enc, &prm.m[M_XSA], xs, 1024, 2048, 64, 256, S128);
  for (int t = 0; t < 2; t++) {
    const uint64_t d3[3] = {1024, 1024, 3}, s3[2] = {3072, 1024};
    const uint32_t b3[3] = {64, 64, 3};
    make_map(enc, &prm.m[M_WQA + t], d_in[1 + 3 * t], 3, d3, s3, b3, S128);
    const uint64_t d5[5] = {64, 32, 2, 16, 16}, s5[4] = {1024, 32 * 1024, 64 * 1024, 64};
    const uint32_t b5[5] = {64, 32, 1, 2, 2};
    make_map(enc, &prm.m[M_WOA + t], d_in[2 + 3 * t], 5, d5, s5, b5, S128);
    const uint64_t dr[3] = {64, 2048, 16}, sr[2] = {1024, 64};
    const uint32_t br[3] = {64, 128, 2};
    make_map(enc, &prm.m[M_X0R + t], t ? xs : d_in[0], 3, dr, sr, br, S128);
  }
  map2(enc, &prm.m[M_OS], os, 1024, 2048, 64, 64, S128);
  map2(enc, &prm.m[M_K], kk, 32, 65536, 32, 256, S64);
  map2(enc, &prm.m[M_V], vv, 32, 65536, 32, 256, S64);
  map2(enc, &prm.m[M_K16], kk, 32, 65536, 32, 16, S64);
  map2(enc, &prm.m[M_V16], vv, 32, 65536, 32, 16, S64);
  map2(enc, &prm.m[M_XSO], xs, 1024, 2048, 64, 128, S128);
  map2(enc, &prm.m[M_X0H], d_in[0], 1024, 2048, 64, 128, S128);
  map2(enc, &prm.m[M_XST], xs, 1024, 2048, 64, 16, S128);
  map2(enc, &prm.m[M_OUT], d_out, 1024, 2048, 64, 16, S128);
  prm.x0 = (const bf16*)d_in[0];
  prm.wq[0] = (const bf16*)d_in[1]; prm.wq[1] = (const bf16*)d_in[4];
  prm.zero = 0;
  for (int i = 0; i < 128; i++) prm.map[i] = remap(i);
  {
    const uint64_t hi = 0x80000020ull << 32, k0 = sbase + T0, v0 = k0 + 16384, vstep = 64 - (64ull << 16);
    for (int j = 0; j < 17; j++) {
      prm.kv[j].kd = (hi | 1u << 16 | k0 >> 4) + 2048 * ((j < 16 ? j : 15) & 3);
      prm.kv[j].vd = (hi | (uint64_t)(ONES - T0 - 16384) >> 4 << 16 | v0 >> 4) + 32 * vstep * ((j ? j - 1 : 0) & 3);
    }
  }
  fused_kernel<<<128, 384, SMEM_BYTES>>>(prm);
}
```

```cpp
#include <cuda_runtime.h>
#include <cuda_bf16.h>
#include <cuda.h>
#include <stdint.h>

typedef __nv_bfloat16 bf16;

__device__ __forceinline__ void wgmma_m64n192k16_ss_tb(float (&d)[96], uint64_t da, uint64_t db, int scale_d) {
  asm volatile("{\n.reg .pred p;\nsetp.ne.b32 p, %98, 0;\n"
    "wgmma.mma_async.sync.aligned.m64n192k16.f32.bf16.bf16 "
    "{%0, %1, %2, %3, %4, %5, %6, %7, %8, %9, %10, %11, %12, %13, %14, %15, "
    "%16, %17, %18, %19, %20, %21, %22, %23, %24, %25, %26, %27, %28, %29, %30, %31, "
    "%32, %33, %34, %35, %36, %37, %38, %39, %40, %41, %42, %43, %44, %45, %46, %47, "
    "%48, %49, %50, %51, %52, %53, %54, %55, %56, %57, %58, %59, %60, %61, %62, %63, "
    "%64, %65, %66, %67, %68, %69, %70, %71, %72, %73, %74, %75, %76, %77, %78, %79, "
    "%80, %81, %82, %83, %84, %85, %86, %87, %88, %89, %90, %91, %92, %93, %94, %95}, "
    "%96, %97, p, 1, 1, 0, 1;\n}\n"
    : "+f"(d[0]), "+f"(d[1]), "+f"(d[2]), "+f"(d[3]), "+f"(d[4]), "+f"(d[5]), "+f"(d[6]), "+f"(d[7]),
      "+f"(d[8]), "+f"(d[9]), "+f"(d[10]), "+f"(d[11]), "+f"(d[12]), "+f"(d[13]), "+f"(d[14]), "+f"(d[15]),
      "+f"(d[16]), "+f"(d[17]), "+f"(d[18]), "+f"(d[19]), "+f"(d[20]), "+f"(d[21]), "+f"(d[22]), "+f"(d[23]),
      "+f"(d[24]), "+f"(d[25]), "+f"(d[26]), "+f"(d[27]), "+f"(d[28]), "+f"(d[29]), "+f"(d[30]), "+f"(d[31]),
      "+f"(d[32]), "+f"(d[33]), "+f"(d[34]), "+f"(d[35]), "+f"(d[36]), "+f"(d[37]), "+f"(d[38]), "+f"(d[39]),
      "+f"(d[40]), "+f"(d[41]), "+f"(d[42]), "+f"(d[43]), "+f"(d[44]), "+f"(d[45]), "+f"(d[46]), "+f"(d[47]),
      "+f"(d[48]), "+f"(d[49]), "+f"(d[50]), "+f"(d[51]), "+f"(d[52]), "+f"(d[53]), "+f"(d[54]), "+f"(d[55]),
      "+f"(d[56]), "+f"(d[57]), "+f"(d[58]), "+f"(d[59]), "+f"(d[60]), "+f"(d[61]), "+f"(d[62]), "+f"(d[63]),
      "+f"(d[64]), "+f"(d[65]), "+f"(d[66]), "+f"(d[67]), "+f"(d[68]), "+f"(d[69]), "+f"(d[70]), "+f"(d[71]),
      "+f"(d[72]), "+f"(d[73]), "+f"(d[74]), "+f"(d[75]), "+f"(d[76]), "+f"(d[77]), "+f"(d[78]), "+f"(d[79]),
      "+f"(d[80]), "+f"(d[81]), "+f"(d[82]), "+f"(d[83]), "+f"(d[84]), "+f"(d[85]), "+f"(d[86]), "+f"(d[87]),
      "+f"(d[88]), "+f"(d[89]), "+f"(d[90]), "+f"(d[91]), "+f"(d[92]), "+f"(d[93]), "+f"(d[94]), "+f"(d[95])
    : "l"(da), "l"(db), "r"(scale_d));
}

__device__ __forceinline__ void wgmma_m64n128k16_ss_tb(float (&d)[64], uint64_t da, uint64_t db, int scale_d) {
  asm volatile("{\n.reg .pred p;\nsetp.ne.b32 p, %66, 0;\n"
    "wgmma.mma_async.sync.aligned.m64n128k16.f32.bf16.bf16 "
    "{%0, %1, %2, %3, %4, %5, %6, %7, %8, %9, %10, %11, %12, %13, %14, %15, "
    "%16, %17, %18, %19, %20, %21, %22, %23, %24, %25, %26, %27, %28, %29, %30, %31, "
    "%32, %33, %34, %35, %36, %37, %38, %39, %40, %41, %42, %43, %44, %45, %46, %47, "
    "%48, %49, %50, %51, %52, %53, %54, %55, %56, %57, %58, %59, %60, %61, %62, %63}, "
    "%64, %65, p, 1, 1, 0, 1;\n}\n"
    : "+f"(d[0]), "+f"(d[1]), "+f"(d[2]), "+f"(d[3]), "+f"(d[4]), "+f"(d[5]), "+f"(d[6]), "+f"(d[7]),
      "+f"(d[8]), "+f"(d[9]), "+f"(d[10]), "+f"(d[11]), "+f"(d[12]), "+f"(d[13]), "+f"(d[14]), "+f"(d[15]),
      "+f"(d[16]), "+f"(d[17]), "+f"(d[18]), "+f"(d[19]), "+f"(d[20]), "+f"(d[21]), "+f"(d[22]), "+f"(d[23]),
      "+f"(d[24]), "+f"(d[25]), "+f"(d[26]), "+f"(d[27]), "+f"(d[28]), "+f"(d[29]), "+f"(d[30]), "+f"(d[31]),
      "+f"(d[32]), "+f"(d[33]), "+f"(d[34]), "+f"(d[35]), "+f"(d[36]), "+f"(d[37]), "+f"(d[38]), "+f"(d[39]),
      "+f"(d[40]), "+f"(d[41]), "+f"(d[42]), "+f"(d[43]), "+f"(d[44]), "+f"(d[45]), "+f"(d[46]), "+f"(d[47]),
      "+f"(d[48]), "+f"(d[49]), "+f"(d[50]), "+f"(d[51]), "+f"(d[52]), "+f"(d[53]), "+f"(d[54]), "+f"(d[55]),
      "+f"(d[56]), "+f"(d[57]), "+f"(d[58]), "+f"(d[59]), "+f"(d[60]), "+f"(d[61]), "+f"(d[62]), "+f"(d[63])
    : "l"(da), "l"(db), "r"(scale_d));
}

__device__ __forceinline__ void wgmma_m64n40k16_rs_tb(float (&d)[20], uint32_t a0, uint32_t a1, uint32_t a2, uint32_t a3, uint64_t db, int scale_d) {
  asm volatile("{\n.reg .pred p;\nsetp.ne.b32 p, %25, 0;\n"
    "wgmma.mma_async.sync.aligned.m64n40k16.f32.bf16.bf16 "
    "{%0, %1, %2, %3, %4, %5, %6, %7, %8, %9, %10, %11, %12, %13, %14, %15, "
    "%16, %17, %18, %19}, "
    "{%20, %21, %22, %23}, %24, p, 1, 1, 1;\n}\n"
    : "+f"(d[0]), "+f"(d[1]), "+f"(d[2]), "+f"(d[3]), "+f"(d[4]), "+f"(d[5]), "+f"(d[6]), "+f"(d[7]),
      "+f"(d[8]), "+f"(d[9]), "+f"(d[10]), "+f"(d[11]), "+f"(d[12]), "+f"(d[13]), "+f"(d[14]), "+f"(d[15]),
      "+f"(d[16]), "+f"(d[17]), "+f"(d[18]), "+f"(d[19])
    : "r"(a0), "r"(a1), "r"(a2), "r"(a3), "l"(db), "r"(scale_d));
}

__device__ __forceinline__ void wg_n64_rs_nb_f16_f32(float (&d)[32], uint32_t a0, uint32_t a1, uint32_t a2, uint32_t a3, uint64_t db, int scale_d) {
  asm volatile("{\n.reg .pred p;\nsetp.ne.b32 p, %37, 0;\n"
    "wgmma.mma_async.sync.aligned.m64n64k16.f32.f16.f16 "
    "{%0, %1, %2, %3, %4, %5, %6, %7, %8, %9, %10, %11, %12, %13, %14, %15, "
    "%16, %17, %18, %19, %20, %21, %22, %23, %24, %25, %26, %27, %28, %29, %30, %31}, "
    "{%32, %33, %34, %35}, %36, p, 1, 1, 0;\n}\n"
    : "+f"(d[0]), "+f"(d[1]), "+f"(d[2]), "+f"(d[3]), "+f"(d[4]), "+f"(d[5]), "+f"(d[6]), "+f"(d[7]),
      "+f"(d[8]), "+f"(d[9]), "+f"(d[10]), "+f"(d[11]), "+f"(d[12]), "+f"(d[13]), "+f"(d[14]), "+f"(d[15]),
      "+f"(d[16]), "+f"(d[17]), "+f"(d[18]), "+f"(d[19]), "+f"(d[20]), "+f"(d[21]), "+f"(d[22]), "+f"(d[23]),
      "+f"(d[24]), "+f"(d[25]), "+f"(d[26]), "+f"(d[27]), "+f"(d[28]), "+f"(d[29]), "+f"(d[30]), "+f"(d[31])
    : "r"(a0), "r"(a1), "r"(a2), "r"(a3), "l"(db), "r"(scale_d));
}

__device__ __forceinline__ void wg_n64_rs_nb_f16_f16(uint32_t (&d)[16], uint32_t a0, uint32_t a1, uint32_t a2, uint32_t a3, uint64_t db, int scale_d) {
  asm volatile("{\n.reg .pred p;\nsetp.ne.b32 p, %21, 0;\n"
    "wgmma.mma_async.sync.aligned.m64n64k16.f16.f16.f16 "
    "{%0, %1, %2, %3, %4, %5, %6, %7, %8, %9, %10, %11, %12, %13, %14, %15}, "
    "{%16, %17, %18, %19}, %20, p, 1, 1, 0;\n}\n"
    : "+r"(d[0]), "+r"(d[1]), "+r"(d[2]), "+r"(d[3]), "+r"(d[4]), "+r"(d[5]), "+r"(d[6]), "+r"(d[7]),
      "+r"(d[8]), "+r"(d[9]), "+r"(d[10]), "+r"(d[11]), "+r"(d[12]), "+r"(d[13]), "+r"(d[14]), "+r"(d[15])
    : "r"(a0), "r"(a1), "r"(a2), "r"(a3), "l"(db), "r"(scale_d));
}

__device__ __forceinline__ void wg_n64_rs_nb_f16_f32_z(float (&d)[32], uint32_t a0, uint32_t a1, uint32_t a2, uint32_t a3, uint64_t db, int scale_d) {
  asm volatile("{\n.reg .pred p;\nsetp.ne.b32 p, %37, 0;\n"
    "wgmma.mma_async.sync.aligned.m64n64k16.f32.f16.f16 "
    "{%0, %1, %2, %3, %4, %5, %6, %7, %8, %9, %10, %11, %12, %13, %14, %15, "
    "%16, %17, %18, %19, %20, %21, %22, %23, %24, %25, %26, %27, %28, %29, %30, %31}, "
    "{%32, %33, %34, %35}, %36, p, 1, 1, 0;\n}\n"
    : "=f"(d[0]), "=f"(d[1]), "=f"(d[2]), "=f"(d[3]), "=f"(d[4]), "=f"(d[5]), "=f"(d[6]), "=f"(d[7]),
      "=f"(d[8]), "=f"(d[9]), "=f"(d[10]), "=f"(d[11]), "=f"(d[12]), "=f"(d[13]), "=f"(d[14]), "=f"(d[15]),
      "=f"(d[16]), "=f"(d[17]), "=f"(d[18]), "=f"(d[19]), "=f"(d[20]), "=f"(d[21]), "=f"(d[22]), "=f"(d[23]),
      "=f"(d[24]), "=f"(d[25]), "=f"(d[26]), "=f"(d[27]), "=f"(d[28]), "=f"(d[29]), "=f"(d[30]), "=f"(d[31])
    : "r"(a0), "r"(a1), "r"(a2), "r"(a3), "l"(db), "r"(scale_d));
}

__device__ __forceinline__ void wg_n64_rs_nb_f16_f16_z(uint32_t (&d)[16], uint32_t a0, uint32_t a1, uint32_t a2, uint32_t a3, uint64_t db, int scale_d) {
  asm volatile("{\n.reg .pred p;\nsetp.ne.b32 p, %21, 0;\n"
    "wgmma.mma_async.sync.aligned.m64n64k16.f16.f16.f16 "
    "{%0, %1, %2, %3, %4, %5, %6, %7, %8, %9, %10, %11, %12, %13, %14, %15}, "
    "{%16, %17, %18, %19}, %20, p, 1, 1, 0;\n}\n"
    : "=r"(d[0]), "=r"(d[1]), "=r"(d[2]), "=r"(d[3]), "=r"(d[4]), "=r"(d[5]), "=r"(d[6]), "=r"(d[7]),
      "=r"(d[8]), "=r"(d[9]), "=r"(d[10]), "=r"(d[11]), "=r"(d[12]), "=r"(d[13]), "=r"(d[14]), "=r"(d[15])
    : "r"(a0), "r"(a1), "r"(a2), "r"(a3), "l"(db), "r"(scale_d));
}

#define DEVINL __device__ __forceinline__
DEVINL void wg_fence() { asm volatile("wgmma.fence.sync.aligned;" ::: "memory"); }
DEVINL void wg_commit() { asm volatile("wgmma.commit_group.sync.aligned;" ::: "memory"); }
template <int N> DEVINL void wg_wait() { asm volatile("wgmma.wait_group.sync.aligned %0;" ::"n"(N) : "memory"); }
DEVINL uint64_t mkdesc(uint32_t addr, uint32_t lbo, uint32_t sbo, int sw) {
  return (uint64_t)((addr & 0x3FFFF) >> 4) | ((uint64_t)(lbo >> 4) << 16) | ((uint64_t)(sbo >> 4) << 32) | ((uint64_t)sw << 62);
}
DEVINL void mbar_init(uint32_t bar, uint32_t cnt) { asm volatile("mbarrier.init.shared::cta.b64 [%0], %1;" ::"r"(bar), "r"(cnt) : "memory"); }
DEVINL void mbar_arrive(uint32_t bar) { asm volatile("mbarrier.arrive.shared::cta.b64 _, [%0];" ::"r"(bar) : "memory"); }
DEVINL bool mbar_try(uint32_t bar, uint32_t parity) {
  uint32_t ok;
  asm volatile("{\n.reg .pred p;\nmbarrier.try_wait.parity.shared::cta.b64 p, [%1], %2;\nselp.u32 %0, 1, 0, p;\n}" : "=r"(ok) : "r"(bar), "r"(parity) : "memory");
  return ok;
}
DEVINL bool mbar_test(uint32_t bar, uint32_t parity) {
  uint32_t ok;
  asm volatile("{\n.reg .pred p;\nmbarrier.test_wait.parity.shared::cta.b64 p, [%1], %2;\nselp.u32 %0, 1, 0, p;\n}" : "=r"(ok) : "r"(bar), "r"(parity) : "memory");
  return ok;
}
DEVINL void mbar_hint(uint32_t bar, uint32_t parity) {
#pragma unroll 1
  for (uint32_t n = 0; n < 16u; n++) if (mbar_try(bar, parity)) break;
}
DEVINL void mbar_wait(uint32_t bar, uint32_t parity) {
#pragma unroll 1
  for (uint32_t n = 0; n < 100000u; n++) if (mbar_try(bar, parity)) break;
}
#define EL(txt) "{\n.reg .pred pe;\nelect.sync _|pe, 0xffffffff;\n@pe " txt "\n}"
DEVINL void e_expect_tx(uint32_t bar, uint32_t bytes) { asm volatile(EL("mbarrier.arrive.expect_tx.shared::cta.b64 _, [%0], %1;") ::"r"(bar), "r"(bytes) : "memory"); }
DEVINL void e_arrive(uint32_t bar) { asm volatile(EL("mbarrier.arrive.shared::cta.b64 _, [%0];") ::"r"(bar) : "memory"); }
DEVINL void e_arrive_if(uint32_t bar, int c) {
  asm volatile("{\n.reg .pred pe;\nelect.sync _|pe, 0xffffffff;\nsetp.ne.and.b32 pe, %1, 0, pe;\n@pe mbarrier.arrive.shared::cta.b64 _, [%0];\n}" ::"r"(bar), "r"(c) : "memory");
}
DEVINL void e_red(uint32_t* p) { asm volatile(EL("red.release.gpu.global.add.u32 [%0], 1;") ::"l"(p) : "memory"); }
DEVINL void e_red_relaxed(uint32_t* p) { asm volatile(EL("red.relaxed.gpu.global.add.u32 [%0], 1;") ::"l"(p) : "memory"); }
DEVINL void tma_ld(uint32_t dst, const CUtensorMap* m, int c0, int c1, uint32_t bar) {
  asm volatile(EL("cp.async.bulk.tensor.2d.shared::cluster.global.mbarrier::complete_tx::bytes [%0], [%1, {%3, %4}], [%2];")
               ::"r"(dst), "l"(m), "r"(bar), "r"(c0), "r"(c1) : "memory");
}
DEVINL void tma_ld3(uint32_t dst, const CUtensorMap* m, int c0, int c1, int c2, uint32_t bar) {
  asm volatile(EL("cp.async.bulk.tensor.3d.shared::cluster.global.mbarrier::complete_tx::bytes [%0], [%1, {%3, %4, %5}], [%2];")
               ::"r"(dst), "l"(m), "r"(bar), "r"(c0), "r"(c1), "r"(c2) : "memory");
}
DEVINL void tma_ld5(uint32_t dst, const CUtensorMap* m, int c2, int c3, int c4, uint32_t bar) {
  asm volatile(EL("cp.async.bulk.tensor.5d.shared::cluster.global.mbarrier::complete_tx::bytes [%0], [%1, {0, 0, %3, %4, %5}], [%2];")
               ::"r"(dst), "l"(m), "r"(bar), "r"(c2), "r"(c3), "r"(c4) : "memory");
}
DEVINL void tma_ld_mc(uint32_t dst, const CUtensorMap* m, int c0, int c1, uint32_t bar) {
  asm volatile(EL("cp.async.bulk.tensor.2d.shared::cluster.global.mbarrier::complete_tx::bytes.multicast::cluster [%0], [%1, {%3, %4}], [%2], %5;")
               ::"r"(dst), "l"(m), "r"(bar), "r"(c0), "r"(c1), "h"((uint16_t)3) : "memory");
}
DEVINL void e_arrive_both(uint32_t bar) {
  asm volatile("{\n.reg .pred pe;\n.reg .b32 r0, r1;\nelect.sync _|pe, 0xffffffff;\nmapa.shared::cluster.u32 r0, %0, 0;\nmapa.shared::cluster.u32 r1, %0, 1;\n"
               "@pe mbarrier.arrive.shared::cluster.b64 _, [r0];\n@pe mbarrier.arrive.shared::cluster.b64 _, [r1];\n}" ::"r"(bar) : "memory");
}
DEVINL void tma_st(const CUtensorMap* m, int c0, int c1, uint32_t src) {
  asm volatile(EL("cp.async.bulk.tensor.2d.global.shared::cta.bulk_group [%0, {%2, %3}], [%1];") ::"l"(m), "r"(src), "r"(c0), "r"(c1) : "memory");
}
DEVINL void bulk_commit() { asm volatile("cp.async.bulk.commit_group;" ::: "memory"); }
template <int N> DEVINL void bulk_wait_n() { asm volatile("cp.async.bulk.wait_group %0;\nbar.warp.sync 0xffffffff;" ::"n"(N) : "memory"); }
DEVINL void l2_prefetch(const void* g, uint32_t bytes) { asm volatile(EL("cp.async.bulk.prefetch.L2.global [%0], %1;") ::"l"(g), "r"(bytes) : "memory"); }
DEVINL void fence_async_smem() { asm volatile("fence.proxy.async.shared::cta;" ::: "memory"); }
DEVINL void fence_async_gl() { asm volatile("fence.proxy.async.global;" ::: "memory"); }
DEVINL void cluster_wait() { asm volatile("barrier.cluster.wait.aligned;" ::: "memory"); }
DEVINL void bar_sync(int id, int n) { asm volatile("bar.sync %0, %1;" ::"r"(id), "r"(n) : "memory"); }
DEVINL void bar_arrive(int id, int n) { asm volatile("bar.arrive %0, %1;" ::"r"(id), "r"(n) : "memory"); }
DEVINL uint32_t ld_acquire(const uint32_t* p) { uint32_t v; asm volatile("ld.acquire.gpu.global.u32 %0, [%1];" : "=r"(v) : "l"(p) : "memory"); return v; }
DEVINL void watch(const uint32_t* p, uint32_t target, uint32_t all, uint32_t tag, uint32_t slot) {
  uint32_t seen = 0;
#pragma unroll 1
  for (uint32_t n = 0; n < 200000u && seen != all; n++) {
    const uint32_t m = __ballot_sync(~0u, (int)(ld_acquire(p) - target) >= 0) & all;
    if (m != seen) { seen = m; asm volatile("st.release.cta.shared.u32 [%0], %1;" ::"r"(slot), "r"(tag << 16 | m) : "memory"); }
  }
}
template <bool RELAXED = false> DEVINL void await_bit(uint32_t slot, uint32_t tag, int j, uint32_t& rdy) {
  if ((rdy >> j) & 1) return;
#pragma unroll 1
  for (uint32_t n = 0; n < 8000000u; n++) {
    uint32_t v;
    asm volatile("ld.acquire.cta.shared.u32 %0, [%1];" : "=r"(v) : "r"(slot) : "memory");
    if ((v >> 16) == tag && ((v >> j) & 1)) { rdy = v; break; }
    if (RELAXED) __nanosleep(200);
  }
  asm volatile("fence.proxy.async.global;" ::: "memory");
}
DEVINL void poll_ge(const uint32_t* p, uint32_t target) {
#pragma unroll 1
  for (uint32_t n = 0; n < 200000u; n++) if (__all_sync(~0u, (int)(ld_acquire(p) - target) >= 0)) break;
}
DEVINL int lane_id() { int v; asm volatile("mov.u32 %0, %%laneid;" : "=r"(v)); return v; }
__host__ DEVINL int remap(int v) {
  const int c = v >> 1, u = c - 36, r = (u * 37) >> 8;
  const int L = c < 4 ? 32 + 8 * c : c < 36 ? c - 4 : 33 + u + r;
  return 2 * L + (v & 1);
}
DEVINL int block_id() { int v; asm volatile("mov.u32 %0, %%ctaid.x;" : "=r"(v)); return v; }
#define cta_id() prm.map[block_id()]
#define IDS() const int lane = lane_id(), b = cta_id(), bm = b >> 4, bn = b & 15, rank = b & 1, pm = 2 * bm + (bn >> 3), pn = bn & 7, po = pm & 1; \
  (void)lane; (void)bm; (void)bn; (void)rank; (void)pm; (void)pn; (void)po
DEVINL void st_tagged(uint4* p, uint32_t a, uint32_t b, uint32_t c, uint32_t tag) {
  asm volatile("{\n.reg .b64 u, v;\n.reg .b128 t;\nmov.b64 u, {%1, %2};\nmov.b64 v, {%3, %4};\nmov.b128 t, {u, v};\nst.relaxed.gpu.global.b128 [%0], t;\n}"
               ::"l"(p), "r"(a), "r"(b), "r"(c), "r"(tag) : "memory");
}
DEVINL uint32_t ld_tagged(const uint4* p, uint32_t* r) {
  uint32_t tag;
  asm volatile("{\n.reg .b64 u, v;\n.reg .b128 t;\nld.relaxed.gpu.global.b128 t, [%4];\nmov.b128 {u, v}, t;\nmov.b64 {%0, %1}, u;\nmov.b64 {%2, %3}, v;\n}"
               : "=r"(r[0]), "=r"(r[1]), "=r"(r[2]), "=r"(tag) : "l"(p) : "memory");
  return tag;
}
DEVINL float ex2(float x) { float y; asm("ex2.approx.ftz.f32 %0, %1;" : "=f"(y) : "f"(x)); return y; }
DEVINL float rcp(float x) { float y; asm("rcp.approx.ftz.f32 %0, %1;" : "=f"(y) : "f"(x)); return y; }
DEVINL uint32_t pack2(float lo, float hi) { uint32_t r; asm("cvt.rn.bf16x2.f32 %0, %1, %2;" : "=r"(r) : "f"(hi), "f"(lo)); return r; }
DEVINL uint32_t pack2h(float lo, float hi) { uint32_t r; asm("cvt.rn.f16x2.f32 %0, %1, %2;" : "=r"(r) : "f"(hi), "f"(lo)); return r; }
DEVINL float bf_lo(uint32_t w) { return __uint_as_float(w << 16); }
DEVINL float bf_hi(uint32_t w) { return __uint_as_float(w & 0xFFFF0000u); }
DEVINL float bf_round(float x) { return bf_lo(pack2(x, 0.f)); }
DEVINL uint32_t add_bf16x2(uint32_t a, uint32_t b) { uint32_t r; asm("add.rn.bf16x2 %0, %1, %2;" : "=r"(r) : "r"(a), "r"(b)); return r; }
DEVINL void stsm4(uint32_t addr, uint32_t a, uint32_t b, uint32_t c, uint32_t d) {
  asm volatile("stmatrix.sync.aligned.m8n8.x4.shared.b16 [%0], {%1, %2, %3, %4};" ::"r"(addr), "r"(a), "r"(b), "r"(c), "r"(d) : "memory");
}
DEVINL void ldsm4(uint32_t addr, uint32_t (&r)[4]) {
  asm volatile("ldmatrix.sync.aligned.m8n8.x4.shared.b16 {%0, %1, %2, %3}, [%4];" : "=r"(r[0]), "=r"(r[1]), "=r"(r[2]), "=r"(r[3]) : "r"(addr) : "memory");
}
DEVINL void ldsm4t(uint32_t addr, uint32_t (&r)[4]) {
  asm volatile("ldmatrix.sync.aligned.m8n8.x4.trans.shared.b16 {%0, %1, %2, %3}, [%4];" : "=r"(r[0]), "=r"(r[1]), "=r"(r[2]), "=r"(r[3]) : "r"(addr) : "memory");
}
DEVINL void sts128(uint32_t addr, uint32_t a, uint32_t b, uint32_t c, uint32_t d) {
  asm volatile("st.shared.v4.b32 [%0], {%1, %2, %3, %4};" ::"r"(addr), "r"(a), "r"(b), "r"(c), "r"(d) : "memory");
}
DEVINL float2 lds64f(uint32_t addr) { float2 v; asm volatile("ld.shared.v2.f32 {%0, %1}, [%2];" : "=f"(v.x), "=f"(v.y) : "r"(addr) : "memory"); return v; }
DEVINL void mma16816(float (&d)[4], uint32_t a0, uint32_t a1, uint32_t a2, uint32_t a3, uint32_t b0, uint32_t b1) {
  asm("mma.sync.aligned.m16n8k16.row.col.f32.bf16.bf16.f32 {%0, %1, %2, %3}, {%4, %5, %6, %7}, {%8, %9}, {%0, %1, %2, %3};"
               : "+f"(d[0]), "+f"(d[1]), "+f"(d[2]), "+f"(d[3]) : "r"(a0), "r"(a1), "r"(a2), "r"(a3), "r"(b0), "r"(b1));
}
template <int N> DEVINL void fence_regs(float (&d)[N]) {
#pragma unroll
  for (int i = 0; i < N; i++) asm volatile("" : "+f"(d[i])::"memory");
}
template <int N> DEVINL void fence_regs(uint32_t (&d)[N]) {
#pragma unroll
  for (int i = 0; i < N; i++) asm volatile("" : "+r"(d[i])::"memory");
}
DEVINL void lds128(uint32_t addr, uint32_t* r) {
  asm volatile("ld.shared.v4.b32 {%0, %1, %2, %3}, [%4];" : "=r"(r[0]), "=r"(r[1]), "=r"(r[2]), "=r"(r[3]) : "r"(addr) : "memory");
}
DEVINL void sched_fence() { asm volatile("griddepcontrol.launch_dependents;" ::: "memory"); }

struct Scratch {
  bf16 k[32 * 2048 * 32];
  bf16 xs[2048 * 1024];
  bf16 os[2048 * 1024];
  bf16 v[32 * 2048 * 32];
  float kn[2 * 128 * 16];
  uint32_t cnt[256 * 32];
  float2 stats[8 * 2048];
  uint4 halo[2 * 128 * 12 * 32];
  float csp[2 * 16 * 8 * 192];
  uint4 qsave[128 * 256 * 8];
  uint32_t esc[4 * 65536 * 16];
};
__device__ __align__(1024) Scratch g_s;
#define g_k g_s.k
#define g_xs g_s.xs
#define g_os g_s.os
#define g_v g_s.v
#define g_kn g_s.kn
#define g_cnt g_s.cnt
#define g_stats g_s.stats
#define g_halo g_s.halo
#define g_csp g_s.csp
#define g_qsave g_s.qsave
#define g_esc g_s.esc
#define g_epoch g_s.cnt[255 * 32]

DEVINL uint32_t* cnt_x(int l, int bm) { return g_cnt + (l * 8 + bm) * 32; }
DEVINL uint32_t* cnt_o(int l, int pm, int h) { return g_cnt + (32 + (l * 16 + pm) * 2 + h) * 32; }
DEVINL uint32_t* cnt_kv(int lb, int bn) { return g_cnt + (160 + lb * 16 + bn) * 32; }
DEVINL uint32_t* cnt_ad(int bn) { return g_cnt + (192 + bn) * 32; }
DEVINL uint32_t* cnt_cs(int t, int bn) { return g_cnt + (208 + t * 16 + bn) * 32; }

DEVINL int qord(int i, int l, int pn) { return l == 0 ? i : i < 4 ? ((2 * pn) ^ (i & 2)) + (i & 1) : i - 4 < 2 * (pn & 6) ? i - 4 : i; }
struct Params {
  CUtensorMap m[17];
  const bf16* x0;
  const bf16* wq[2];
  uint32_t zero;
  int map[128];
  struct { uint64_t kd, vd; } kv[17];
};
enum { M_X0A = 0, M_XSA, M_WQA, M_WQB, M_WOA, M_WOB, M_OS, M_K, M_V, M_X0R, M_XSR, M_XSO, M_OUT, M_XST, M_X0H, M_K16, M_V16, M_COUNT };

constexpr uint32_t QSTG = 57344;
constexpr uint32_t T0 = 65536, TSTG = 32768;
constexpr uint32_t ONES = 230400;
constexpr uint32_t PSTG = 32768, RES = 196608;
constexpr uint32_t KSC = 98304, VSC = 133120, HRS = 167936;
constexpr uint32_t ROWST = 229376, COLS = 231424, BARS = 232192, SMEM_BYTES = 232448;
constexpr uint32_t B_QF = BARS, B_QE = BARS + 32, B_TF = BARS + 64, B_TE = BARS + 96, B_PF = BARS + 128, B_PE = BARS + 176,
                   B_RF = BARS + 224, W_X = BARS + 232, W_O = BARS + 236, B_QL = BARS + 240, B_PA = BARS + 248;
enum { NB_ST = 1, NB_KV = 2  , NB_DONE = 3, NB_SC = 4, NB_SIG = 5  , NB_KN = 9  , NB_X = 11, NB_HALO = 12  , NB_X0 = 15 };

DEVINL uint32_t pslot_b(uint32_t s) { return ((0x320415u >> (4 * s)) & 7) * 16384u; }
DEVINL uint32_t pslot_a(uint32_t s, int l) { return 98304u + ((((l & 1) ? 0x541230u : 0x041235u) >> (4 * s)) & 7) * 16384u; }

constexpr float QSCALE = 0.17677669529663687f * 1.4426950408889634f;
constexpr uint32_t QPARK = 32768;

DEVINL uint32_t exp2_h2(uint32_t s, uint32_t c882) {
  uint32_t r, t, w, m, d;
  asm volatile("{.reg .b64 t; add.rn.f16x2 %0, %1, %2; cvt.u64.u32 t, %0; cvt.u32.u64 %0, t;}" : "=r"(r) : "r"(s), "r"(0x65F565F5u));
  asm volatile("fma.rn.f16x2 %0, %1, %2, %3;" : "=r"(t) : "r"(r), "r"(0xB8A0B8A0u), "r"(c882));
  asm volatile("fma.rn.f16x2 %0, %1, %2, %3;" : "=r"(w) : "r"(s), "r"(0x38A038A0u), "r"(t));
  asm volatile("fma.rn.f16x2 %0, %1, %1, %2;" : "=r"(m) : "r"(w), "r"(0x48244833u));
  asm volatile("{.reg .b32 t; shf.l.clamp.b32 t, %2, %1, 7; add.u32 %0, t, %2;}" : "=r"(d) : "r"(r), "r"(m));
  return d;
}
DEVINL float exp2_fix(float s) { float z; asm volatile("add.rn.f32 %0, %1, 0f43BF34BC;" : "=f"(z) : "f"(s)); return z; }
DEVINL uint32_t exp2_base(float z0, float z1) { uint32_t B; asm volatile("prmt.b32 %0, %1, %2, 0x6521;" : "=r"(B) : "r"(__float_as_uint(z0)), "r"(__float_as_uint(z1))); return B; }
template <uint32_t MASK> DEVINL uint32_t and_or(uint32_t a, uint32_t c) { uint32_t r; asm volatile("lop3.b32 %0, %1, %3, %2, 0xEA;" : "=r"(r) : "r"(a), "r"(c), "n"(MASK)); return r; }
DEVINL uint32_t fma_bf2(uint32_t a, uint32_t b, uint32_t c) { uint32_t r; asm volatile("fma.rn.bf16x2 %0, %1, %2, %3;" : "=r"(r) : "r"(a), "r"(b), "r"(c)); return r; }
DEVINL float ex2v(float x) { float y; asm volatile("ex2.approx.ftz.f32 %0, %1;" : "=f"(y) : "f"(x)); return y; }
DEVINL uint32_t pack2v(float lo, float hi) { uint32_t r; asm volatile("cvt.rn.bf16x2.f32 %0, %1, %2;" : "=r"(r) : "f"(hi), "f"(lo)); return r; }
DEVINL uint32_t unesc(uint32_t u, const uint32_t* esc) {
  if ((u & 0x7C00u) == 0x7C00u || (u & 0x7C000000u) == 0x7C000000u) return __ldcg(esc);
  float lo, hi;
  asm("{.reg .f16 a, b; mov.b32 {a, b}, %2; cvt.f32.f16 %0, a; cvt.f32.f16 %1, b;}" : "=f"(lo), "=f"(hi) : "r"(u));
  return pack2(lo, hi);
}

DEVINL void attn_slow(const uint32_t (&q)[8], int head, const uint32_t* kesc, float (&res)[20], int lane) {
  const int g = lane >> 2, qd = lane & 3;
  const bf16* kb = g_k + (size_t)head * 2048 * 32;
  const bf16* vb = g_v + (size_t)head * 2048 * 32;
  float o[4][4], m0 = -INFINITY, m1 = -INFINITY, l0 = 0.f, l1 = 0.f;
#pragma unroll
  for (int j = 0; j < 4; j++) { o[j][0] = o[j][1] = o[j][2] = o[j][3] = 0.f; }
#pragma unroll 1
  for (int k0 = 0; k0 < 2048; k0 += 16) {
    float s[2][4];
#pragma unroll
    for (int nt = 0; nt < 2; nt++) {
      s[nt][0] = s[nt][1] = s[nt][2] = s[nt][3] = 0.f;
      const uint32_t* kp = (const uint32_t*)(kb + (size_t)(k0 + nt * 8 + g) * 32) + qd;
      const uint32_t* ke = kesc + (k0 + nt * 8 + g) * 16 + qd;
      const uint32_t k0r = unesc(__ldcg(kp), ke), k1r = unesc(__ldcg(kp + 4), ke + 4), k2r = unesc(__ldcg(kp + 8), ke + 8), k3r = unesc(__ldcg(kp + 12), ke + 12);
      __syncwarp();
      mma16816(s[nt], q[0], q[1], q[2], q[3], k0r, k1r);
      mma16816(s[nt], q[4], q[5], q[6], q[7], k2r, k3r);
    }
    float a0 = fmaxf(fmaxf(s[0][0], s[0][1]), fmaxf(s[1][0], s[1][1]));
    float a1 = fmaxf(fmaxf(s[0][2], s[0][3]), fmaxf(s[1][2], s[1][3]));
    a0 = fmaxf(a0, __shfl_xor_sync(~0u, a0, 1)); a0 = fmaxf(a0, __shfl_xor_sync(~0u, a0, 2));
    a1 = fmaxf(a1, __shfl_xor_sync(~0u, a1, 1)); a1 = fmaxf(a1, __shfl_xor_sync(~0u, a1, 2));
    const float n0 = fmaxf(m0, a0), n1 = fmaxf(m1, a1);
    const float c0 = (m0 == n0) ? 1.f : ex2(m0 - n0), c1 = (m1 == n1) ? 1.f : ex2(m1 - n1);
    m0 = n0; m1 = n1;
    const uint32_t p0 = pack2(ex2(s[0][0] - n0), ex2(s[0][1] - n0)), p1 = pack2(ex2(s[0][2] - n1), ex2(s[0][3] - n1));
    const uint32_t p2 = pack2(ex2(s[1][0] - n0), ex2(s[1][1] - n0)), p3 = pack2(ex2(s[1][2] - n1), ex2(s[1][3] - n1));
    l0 = l0 * c0 + bf_lo(p0) + bf_hi(p0) + bf_lo(p2) + bf_hi(p2);
    l1 = l1 * c1 + bf_lo(p1) + bf_hi(p1) + bf_lo(p3) + bf_hi(p3);
#pragma unroll
    for (int j = 0; j < 4; j++) {
      o[j][0] *= c0; o[j][1] *= c0; o[j][2] *= c1; o[j][3] *= c1;
      const unsigned short* vp = (const unsigned short*)(vb + (size_t)(k0 + 2 * qd) * 32 + j * 8 + g);
      const uint32_t b0 = (uint32_t)__ldcg(vp) | ((uint32_t)__ldcg(vp + 32) << 16);
      const uint32_t b1 = (uint32_t)__ldcg(vp + 256) | ((uint32_t)__ldcg(vp + 288) << 16);
      mma16816(o[j], p0, p1, p2, p3, b0, b1);
    }
  }
  l0 += __shfl_xor_sync(~0u, l0, 1); l0 += __shfl_xor_sync(~0u, l0, 2);
  l1 += __shfl_xor_sync(~0u, l1, 1); l1 += __shfl_xor_sync(~0u, l1, 2);
#pragma unroll
  for (int j = 0; j < 4; j++) { res[4 * j] = o[j][0]; res[4 * j + 1] = o[j][1]; res[4 * j + 2] = o[j][2]; res[4 * j + 3] = o[j][3]; }
  res[16] = l0; res[18] = l1;
}

__device__ __noinline__ void attn_redo(int redo, int l, int b, int wg, int w) {
  const int lane = lane_id();
#pragma unroll 1
  for (int t = 0; t < 4; t++) {
    const int h = t >> 1, head = 2 * (b & 15) + h, row = (b >> 4) * 256 + wg * 128 + (t & 1) * 64 + w * 16 + (lane >> 2);
    if ((redo >> t) & 1) {
      const uint32_t* esc = g_esc + (size_t)((l & 2) * 65536 + head * 2048) * 16;
      const uint32_t* qs = (const uint32_t*)(g_qsave + (block_id() * 256 + wg * 128 + w * 32 + lane) * 8 + 2 * t);
      uint32_t q[8]; float o[20];
#pragma unroll
      for (int i = 0; i < 8; i++) q[i] = unesc(__ldcg(qs + i), esc + (row + (i & 1) * 8) * 16 + (i >> 1) * 4 + (lane & 3));
      __syncwarp();
      attn_slow(q, head, esc + 65536 * 16, o, lane);
      const float i0 = rcp(o[16]), i1 = rcp(o[18]);
      bf16* op = g_os + (size_t)row * 1024 + h * 512 + (b & 15) * 32 + (lane & 3) * 8;
      *(uint4*)op = make_uint4(pack2(o[0] * i0, o[1] * i0), pack2(o[4] * i0, o[5] * i0), pack2(o[8] * i0, o[9] * i0), pack2(o[12] * i0, o[13] * i0));
      *(uint4*)(op + 8 * 1024) = make_uint4(pack2(o[2] * i1, o[3] * i1), pack2(o[6] * i1, o[7] * i1), pack2(o[10] * i1, o[11] * i1), pack2(o[14] * i1, o[15] * i1));
    }
    if ((t & 1) && ((redo >> 2 * h) & 3)) bar_arrive(NB_SIG + 2 * h + wg, 160);
  }
}

__global__ void __cluster_dims__(2, 1, 1) __launch_bounds__(384, 1) fused_kernel(const __grid_constant__ Params prm) {
  extern __shared__ __align__(1024) char smem[];
  const uint32_t sb = (uint32_t)__cvta_generic_to_shared(smem);
  const int tid = threadIdx.x, lane = tid & 31;
  const int wg = __shfl_sync(0xffffffffu, tid >> 7, 0);
  const int w = __shfl_sync(0xffffffffu, (tid >> 5) & 3, 0);
  const int bm = remap(blockIdx.x) >> 4, bn = remap(blockIdx.x) & 15;

  auto first_tile = [&](int kt) {
    e_expect_tx(sb + B_QF + 8 * kt, QSTG);
    tma_ld(sb + kt * QSTG, &prm.m[M_X0A], kt * 64, bm * 256, sb + B_QF + 8 * kt);
    tma_ld3(sb + kt * QSTG + 32768, &prm.m[M_WQA], bn * 64, kt * 64, 0, sb + B_QF + 8 * kt);
  };
  auto init4 = [&](uint32_t bar, uint32_t c0, uint32_t c1, uint32_t c2, uint32_t c3) {
    asm volatile("{\n.reg .pred pe;\nelect.sync _|pe, 0xffffffff;\n@pe mbarrier.init.shared::cta.b64 [%0], %1;\n@pe mbarrier.init.shared::cta.b64 [%0+8], %2;\n"
                 "@pe mbarrier.init.shared::cta.b64 [%0+16], %3;\n@pe mbarrier.init.shared::cta.b64 [%0+24], %4;\n@pe fence.mbarrier_init.release.cluster;\n}"
                 ::"r"(bar), "r"(c0), "r"(c1), "r"(c2), "r"(c3) : "memory");
  };
  if (wg < 2) {
    const uint32_t k = wg * 4 + w, lo = (0x1411814u >> (4 * k)) & 15, hi = (0x1441814u >> (4 * k)) & 15;
    if (tid < 32) asm volatile("prefetch.global.L2 [%0];" ::"l"(prm.x0 + (size_t)(bm * 256 + bn * 16 + (tid & 15)) * 1024 + (tid >> 4) * 64));
    else if (tid < 80) asm volatile("prefetch.global.L2 [%0];" ::"l"(prm.wq[0] + (bm * 16 + (tid & 15)) * 3072 + ((tid >> 4) - 2) * 1024 + bn * 64));
    __syncwarp();
    if (k < 7) init4(sb + B_QE + 32 * k, lo, lo, hi, k == 6 ? 2 : hi);
    __syncwarp();
    if (k == 6 && lane == 0) *(volatile unsigned long long*)(smem + W_X) = 0ull;
  } else if (w == 0) {
    init4(sb + B_QF, 1, 1, 1, 1);
    __syncwarp();
    first_tile(0);
  }
  __syncthreads();
  asm volatile("barrier.cluster.arrive.relaxed.aligned;" ::: "memory");

  if (wg == 2) {
    asm volatile("setmaxnreg.dec.sync.aligned.u32 56;");
    const uint32_t ep1 = *(volatile uint32_t*)&g_epoch + 1;
    if (w == 0) {
      first_tile(1);
      mbar_wait(sb + B_QF, 0);
      first_tile(2); first_tile(3);
#pragma unroll 1
      for (int kt = 4; kt < 16; kt++) l2_prefetch(prm.wq[0] + kt * 196608 + blockIdx.x * 1536, 3072);
      cluster_wait();
#pragma unroll 1
      for (int l = 0; l < 4; l++) {
        IDS();
        const CUtensorMap* mw = &prm.m[M_WQA + (l & 1)];
        const CUtensorMap* mx = &prm.m[l == 0 ? M_X0A : M_XSA];
        const CUtensorMap* mh = &prm.m[l == 0 ? M_X0H : M_XSO];
        const CUtensorMap* mo = &prm.m[M_WOA + (l & 1)];
        auto q_b = [&](int i) {
          const int s = i & 3;
          mbar_wait(sb + B_QE + 8 * s, ((i >> 2) & 1) ^ 1);
          e_expect_tx(sb + B_QF + 8 * s, QSTG);
          tma_ld3(sb + s * QSTG + 32768, mw, bn * 64, qord(i, l, pn) * 64, 0, sb + B_QF + 8 * s);
        };
        uint32_t rdy = l ? 0u : ~0u;
        auto q_a = [&](int i) {
          const int kt = qord(i, l, pn);
          await_bit(sb + W_X, l, kt >> 1, rdy);
          if (i < 4) tma_ld(sb + i * QSTG, mx, kt * 64, bm * 256, sb + B_QF + 8 * i);
          else tma_ld_mc(sb + (i & 3) * QSTG + rank * 16384, mh, kt * 64, bm * 256 + rank * 128, sb + B_QF + 8 * (i & 3));
        };
        if (l > 0) {
          await_bit(sb + W_X, l, pn, rdy);
#pragma unroll 1
          for (int i = 0; i < 2; i++) {
            e_expect_tx(sb + B_QF + 8 * i, 16384);
            tma_ld(sb + i * QSTG + (po ^ 1) * 16384, &prm.m[M_XSO], (2 * pn + i) * 64, (pm ^ 1) * 128, sb + B_QF + 8 * i);
          }
          mbar_wait(sb + B_QF, 0);
          q_a(2);
          mbar_wait(sb + B_QF + 8, 0);
        }
#pragma unroll 1
        for (int i = l ? 3 : 4; i < 16; i++) {
          if (l == 3 && i == 12) poll_ge(cnt_ad(bn), ep1 * 16);
          q_b(i); q_a(i);
        }
        if (l & 1) {
          bar_sync(NB_KV, 288);
          sts128(sb + ONES + lane * 32, 0x3f803f80u, 0x3f803f80u, 0x3f803f80u, 0x3f803f80u);
          sts128(sb + ONES + lane * 32 + 16, 0x3f803f80u, 0x3f803f80u, 0x3f803f80u, 0x3f803f80u);
          fence_async_smem();
          __syncwarp();
          e_arrive(sb + B_TF);
          const int krow = 2 * bn * 2048 + bm * 256;
          uint32_t* kvc = cnt_kv(l >> 1, bn);
          bar_sync(NB_DONE, 288);
          e_red(kvc + bm);
          uint32_t seen = 0;
#pragma unroll 1
          for (int it = 1; it < 16; it++) {
            const int s = it & 3, blk = it;
            if (it == 4) {
              bar_sync(NB_KV + 12, 288);
              mbar_wait(sb + B_TF + 24, 0);
              tma_st(&prm.m[M_K], 0, krow + 2048, sb);
              tma_st(&prm.m[M_V], 0, krow + 2048, sb + 16384);
              bulk_commit();
            }
            if (it == 5) { bulk_wait_n<0>(); e_red(kvc + bm); }
            if (it == 12) { e_expect_tx(sb + B_RF, 32768); tma_ld3(sb + RES, &prm.m[M_XSR], 0, pm * 128, 2 * pn, sb + B_RF); }
            if (it == 2 || it == 3) mbar_wait(sb + B_TF + 8 * (it - 1), 0);
            mbar_wait(sb + B_TE + 8 * s, ((it >> 2) & 1) ^ 1);
            if (it < 8) {
#pragma unroll 1
              for (uint32_t n = 0; n < 200000u && !((seen >> it) & 1); n++)
                seen = __ballot_sync(~0u, (int)(ld_acquire(kvc + ((bm + lane) & 7)) - (ep1 * 2 - 1)) >= 0);
              fence_async_gl();
            } else if (it == 8) { poll_ge(kvc + (lane & 7), ep1 * 2); fence_async_gl(); }
            const int row = (2 * bn + (it >> 3)) * 2048 + ((bm + blk) & 7) * 256;
            e_expect_tx(sb + B_TF + 8 * s, 32768);
            tma_ld(sb + T0 + s * TSTG, &prm.m[M_K], 0, row, sb + B_TF + 8 * s);
            tma_ld(sb + T0 + s * TSTG + 16384, &prm.m[M_V], 0, row, sb + B_TF + 8 * s);
          }
        }
        auto p_b = [&](int i, uint32_t s, uint32_t par) {
          mbar_wait(sb + B_PE + 8 * s, par ^ 1);
          e_expect_tx(sb + B_PF + 8 * s, PSTG);
          tma_ld5(sb + pslot_b(s), mo, i >> 3, 2 * (i & 7), 2 * pn, sb + B_PF + 8 * s);
        };
        auto p_a = [&](int i, uint32_t s) {
          await_bit(sb + W_O, l + 1, i, rdy);
          tma_ld_mc(sb + pslot_a(s, l) + rank * 8192, &prm.m[M_OS], i * 64, pm * 128 + rank * 64, sb + B_PF + 8 * s);
        };
        auto p_a2 = [&](int i) {
          await_bit(sb + W_O, l + 1, i, rdy);
          tma_ld(sb + pslot_a(i, l), &prm.m[M_OS], i * 64, pm * 128, sb + B_PF + 8 * i);
          tma_ld(sb + pslot_a(i, l) + 8192, &prm.m[M_OS], i * 64, pm * 128 + 64, sb + B_PF + 8 * i);
        };
        rdy = 0;
        if (l & 1) {
#pragma unroll 1
          for (int u = 0; u < 6; u++) { const int i = (0x205413 >> (4 * u)) & 7; if (u == 4) mbar_wait(sb + B_TE, 1); p_b(i, i, i < 4 ? 1 : 0); }
#pragma unroll 1
          for (int u = 0; u < 6; u++) {
            const int i = (0x542130 >> (4 * u)) & 7;
            if (!(u & 1)) mbar_wait(sb + B_TE + 8 + 4 * u, 1);
            if (u == 4) bar_sync(NB_ST, 64);
            p_a2(i);
          }
        } else {
#pragma unroll 1
          for (int u = 0; u < 6; u++) { const int i = (0x025413 >> (4 * u)) & 7; if (u == 0 || u == 3) mbar_wait(sb + B_QE + 8 * (u / 3), 1); p_b(i, i, 0); }
          mbar_wait(sb + B_QE + 24, 1);
          e_expect_tx(sb + B_RF, 32768);
          tma_ld3(sb + RES, &prm.m[l == 0 ? M_X0R : M_XSR], 0, pm * 128, 2 * pn, sb + B_RF);
          p_a2(0);
          bar_sync(NB_DONE, 64);
          e_arrive_both(sb + B_PA);
          p_a2(1);
          mbar_wait(sb + B_PA, (l >> 1) & 1);
#pragma unroll 1
          for (int i = 2; i < 6; i++) { if (i > 2) mbar_wait(sb + B_PF + 8 * (i - 3), 0); p_a(i, i); }
        }
        uint32_t s = 0, lap = 1;
#pragma unroll 1
        for (int i = 6; i < 16; i++) {
          p_b(i, s, ((s < 4 ? l : 0) + lap) & 1);
          p_a(i, s);
          if (++s == 6) { s = 0; lap++; }
        }
        const CUtensorMap* mn = &prm.m[M_WQA + ((l + 1) & 1)];
        if (l < 3) {
          mbar_wait(sb + B_PE + 8 * 4, 1); mbar_wait(sb + B_PE + 8 * 5, 1);
          tma_ld3(sb + 32768, mn, bn * 64, 2 * pn * 64, 0, sb + B_QL);
          mbar_wait(sb + B_PE + 8 * 0, l & 1);
          tma_ld3(sb + QSTG + 32768, mn, bn * 64, (2 * pn + 1) * 64, 0, sb + B_QL);
          mbar_wait(sb + B_PE + 8 * 1, l & 1);
          e_expect_tx(sb + B_QF + 16, QSTG);
          tma_ld3(sb + 2 * QSTG + 32768, mn, bn * 64, ((2 * pn) ^ 2) * 64, 0, sb + B_QF + 16);
        }
        if (l < 3) { bar_sync(NB_X, 288); e_expect_tx(sb + B_QL, 49152); }
      }
      if (blockIdx.x == 0 && lane_id() == 0) *(volatile uint32_t*)&g_epoch = ep1;
    } else {
      const int hw = w - 1;
      if (lane < 6 && 6 * hw + lane < M_COUNT) asm volatile("prefetch.tensormap [%0];" ::"l"(&prm.m[6 * hw + lane]) : "memory");
      __syncwarp();
      cluster_wait();
      mbar_wait(sb + B_QF, 0);
#pragma unroll 1
      for (int l = 0; l < 4; l++) {
        IDS();
        if (hw == 2 && l > 0) watch(cnt_x(l, bm) + (lane & 7), ep1 * 2, 0xFFu, l, sb + W_X);
        if (l == 0) {
#pragma unroll 1
          for (int r = 2 * hw; r < 16; r += 6) {
            const uint4* p = (const uint4*)(prm.x0 + (size_t)(b * 16 + r) * 1024) + lane;
            float s1[2] = {0.f, 0.f}, s2[2] = {0.f, 0.f};
#pragma unroll
            for (int i = 0; i < 8; i++) {
              const uint4 v = __ldg(p + 32 * i);
              const uint32_t u[4] = {v.x, v.y, v.z, v.w};
#pragma unroll
              for (int k = 0; k < 4; k++) { const float a = bf_lo(u[k]), c = bf_hi(u[k]); s1[i >> 2] += a + c; s2[i >> 2] = fmaf(a, a, fmaf(c, c, s2[i >> 2])); }
            }
#pragma unroll
            for (int o = 16; o; o >>= 1)
#pragma unroll
              for (int rr = 0; rr < 2; rr++) { s1[rr] += __shfl_xor_sync(~0u, s1[rr], o); s2[rr] += __shfl_xor_sync(~0u, s2[rr], o); }
            if (lane == 0) *(float4*)&g_stats[b * 16 + r] = make_float4(s1[0], s2[0], s1[1], s2[1]);
          }
        }
        if (l == 1) { uint32_t rdy = 0; await_bit<true>(sb + W_X, 1, pn, rdy); mbar_hint(sb + B_QF + 8, 0); }
        if (l < 2) {
          float cs[8];
#pragma unroll
          for (int i = 0; i < 8; i++) cs[i] = 0.f;
          const uint4* wp = (const uint4*)(prm.wq[l] + (size_t)(bm * 128 + (lane >> 3)) * 3072 + hw * 1024 + bn * 64) + (lane & 7);
#pragma unroll 8
          for (int i = 0; i < 32; i++) {
            const uint4 v = __ldg(wp + (size_t)i * 4 * 384);
            cs[0] += bf_lo(v.x); cs[1] += bf_hi(v.x); cs[2] += bf_lo(v.y); cs[3] += bf_hi(v.y);
            cs[4] += bf_lo(v.z); cs[5] += bf_hi(v.z); cs[6] += bf_lo(v.w); cs[7] += bf_hi(v.w);
          }
#pragma unroll
          for (int i = 0; i < 8; i++) { cs[i] += __shfl_xor_sync(~0u, cs[i], 8); cs[i] += __shfl_xor_sync(~0u, cs[i], 16); }
          if (lane < 8) {
            float4* d = (float4*)(g_csp + ((l * 16 + bn) * 8 + bm) * 192 + hw * 64 + lane * 8);
            d[0] = make_float4(cs[0], cs[1], cs[2], cs[3]); d[1] = make_float4(cs[4], cs[5], cs[6], cs[7]);
          }
          __syncwarp();
          asm volatile("fence.acq_rel.gpu;" ::: "memory");
          e_red_relaxed(cnt_cs(l, bn));
          if (l == 0) e_red_relaxed(cnt_x(0, bm) + pn);
          poll_ge(lane < 8 && l == 0 ? cnt_x(0, bm) + lane : cnt_cs(l, bn), ep1 * (lane < 8 && l == 0 ? 6 : 24));
        }
        if (l > 0) {
          uint32_t rdy = 0;
#pragma unroll 1
          for (int j = 0; j < 8; j++) await_bit<true>(sb + W_X, l, j, rdy);
        }
#pragma unroll 1
        for (int it = hw * 32 + lane; it < 176; it += 96) {
          const bool rows = it < 128;
          const float4* p = rows ? (const float4*)(g_stats + bm * 256) + it : (const float4*)(g_csp + ((l & 1) * 16 + bn) * 8 * 192) + (it - 128);
          const int stride = rows ? 1024 : 48, np = rows && l == 0 ? 1 : 8;
          float4 a = make_float4(0.f, 0.f, 0.f, 0.f);
#pragma unroll
          for (int k = 0; k < 8; k++) if (k < np) { const float4 v = __ldcg(p + k * stride); a.x += v.x; a.y += v.y; a.z += v.z; a.w += v.w; }
          if (rows) {
            const float m0 = a.x * (1.f / 1024.f), m1 = a.z * (1.f / 1024.f);
            const float v0 = fmaxf(a.y * (1.f / 1024.f) - m0 * m0, 0.f), v1 = fmaxf(a.w * (1.f / 1024.f) - m1 * m1, 0.f);
            const float r0 = __fdividef(1.f, bf_round(sqrtf(bf_round(bf_round(v0) + 1e-5f)))), r1 = __fdividef(1.f, bf_round(sqrtf(bf_round(bf_round(v1) + 1e-5f))));
            a = make_float4(r0, -bf_round(m0) * (l & 1 ? r0 : 1.f), r1, -bf_round(m1) * (l & 1 ? r1 : 1.f));
          }
          *(float4*)(smem + ROWST + it * 16) = a;
        }
        __syncwarp();
        if (lane == 0) asm volatile("red.release.cta.shared.add.u32 [%0], 0x100;" ::"r"(sb + W_X) : "memory");
        if (hw == 2) {
          if (!(l & 1)) {
            bar_sync(NB_ST, 288);
            const uint4* hp = g_halo + ((l >> 1) * 128 + b - 16) * 384 + lane;
#pragma unroll 1
            for (int h = 0; h < 2; h++) {
              uint32_t t[18];
#pragma unroll
              for (int i = 0; i < 18; i++) t[i] = 0;
#pragma unroll 1
              for (uint32_t n = bm ? 0 : 100000u; n < 100000u; n++) {
                uint32_t miss = 0;
#pragma unroll
                for (int i = 0; i < 6; i++) miss |= ld_tagged(hp + h * 192 + i * 32, &t[3 * i]) ^ ep1;
                if (__all_sync(~0u, !miss)) break;
              }
              mbar_wait(sb + B_QE + 16, 1);
              const uint32_t r = (lane & 7) + ((lane >> 3) & 1) * 8, rv = lane >> 2;
#pragma unroll
              for (int jj = 0; jj < 2; jj++) stsm4(sb + KSC + r * 128 + (((4 * h + 2 * jj + (lane >> 4)) ^ (r & 7)) << 4), t[4 * jj], t[4 * jj + 1], t[4 * jj + 2], t[4 * jj + 3]);
              const uint32_t ad = sb + VSC + rv * 128 + (((4 * h + (lane & 3)) ^ (rv & 7)) << 4);
              sts128(ad, t[8], t[10], t[12], t[14]); sts128(ad + 1024, t[9], t[11], t[13], t[15]);
              if (h == 0 && !(lane & 2)) *(uint32_t*)(smem + HRS + ((lane >> 2) + 8 * (lane & 1)) * 8) = t[16];
              bar_arrive(NB_HALO + h, 64);
            }
          } else {
            mbar_wait(sb + B_TF + 16, 0); mbar_wait(sb + B_TF + 16, 1);
            poll_ge(cnt_kv(l >> 1, bn) + (lane & 7), ep1 * 2);
            const uint4 v = __ldcg((const uint4*)(g_kn + ((l >> 1) * 128 + bn * 8) * 16) + lane);
            const uint32_t mx = max(max(v.x, v.y), max(v.z, v.w));
            const uint32_t m0 = __reduce_max_sync(~0u, (lane & 2) ? 0u : mx), m1 = __reduce_max_sync(~0u, (lane & 2) ? mx : 0u);
            if (lane == 0) *(uint2*)(smem + ROWST) = make_uint2(m0, m1);
            __syncwarp();
            bar_arrive(NB_KN, 160); bar_arrive(NB_KN + 1, 160);
            mbar_wait(sb + B_TF + 16, 0); mbar_wait(sb + B_TF + 16, 1);
          }
        } else {
#pragma unroll 1
          for (int i = 0; i < 2; i++) {
            const int h = l & 1 ? i : hw, g = l & 1 ? hw : i;
            bar_sync(NB_SIG + 2 * h + g, 160);
            if (!(l & 1) && i == 0) continue;
            if (i == 1 && hw == 1) bar_arrive(l & 1 ? NB_ST : NB_DONE, 64);
            asm volatile("fence.acq_rel.gpu;" ::: "memory");
            e_red_relaxed(cnt_o(l, 2 * bm + g, h) + (bn >> 1));
            if (!(l & 1)) e_red_relaxed(cnt_o(l, 2 * bm, h) + (bn >> 1));
            if (h == 1 && l == 1) e_red_relaxed(cnt_ad(bn));
          }
        }
        if (hw == 2) watch(cnt_o(l, pm, (lane >> 3) & 1) + (lane & 7), ep1 * 2, 0xFFFFu, l + 1, sb + W_O);
        if (hw == 0 && l < 3) {
          bar_sync(NB_X0, 288);
          e_red(cnt_x(l + 1, bm) + pn);
        }
      }
    }
  } else {
    asm volatile("setmaxnreg.inc.sync.aligned.u32 224;");
    const uint32_t zero = prm.zero;
    cluster_wait();
#pragma unroll 1
    for (int l = 0; l < 4; l++) {
      {
        float acc[2][96];
#pragma unroll
        for (int i = 0; i < 96; i++) { acc[0][i] = 0.f; acc[1][i] = 0.f; }
        fence_regs(acc[0]); fence_regs(acc[1]);
        const bool early = l > 0 && wg == ((cta_id() >> 3) & 1);
        uint32_t ep1 = 0;
#pragma unroll 1
        for (int kt = 0; kt < 16; kt++) {
          const int s = kt & 3;
          if (l > 0 && kt == 0) mbar_wait(sb + B_QL, (l + 1) & 1);
          if (!(early && kt < 2)) mbar_wait(sb + B_QF + 8 * s, (kt >> 2) & 1);
          const uint64_t da = mkdesc(sb + s * QSTG + wg * 16384, 16, 1024, 1), db = mkdesc(sb + s * QSTG + 32768, 8192, 1024, 1);
          wg_fence();
#pragma unroll
          for (int m = 1; m >= 0; m--) {
#pragma unroll
            for (int k = 0; k < 4; k++) wgmma_m64n192k16_ss_tb(acc[m], da + m * 512 + k * 2, db + k * 128, 1);
            wg_commit();
          }
          if (kt == 15 && !(l & 1)) bar_arrive(NB_ST, 288);
          if (kt == 4) ep1 = *(volatile uint32_t*)&g_epoch + 1;
          wg_wait<2>();
          if (early && (kt == 1 || kt == 2)) mbar_wait(sb + B_QF + 8 * (kt - 1), 0);
          if (kt > 0 && w == 0) e_arrive_both(sb + B_QE + 8 * ((kt - 1) & 3));
        }
#pragma unroll 1
        for (uint32_t n = 0; n < 4000000u; n++) {
          uint32_t v;
          asm volatile("ld.acquire.cta.shared.u32 %0, [%1];" : "=r"(v) : "r"(sb + W_X) : "memory");
          if ((v >> 8) == (uint32_t)(l * 256 + 3)) break;
        }
        IDS();
        const int g = lane >> 2, qd = lane & 3;
        float2 st[2][2];
#pragma unroll
        for (int m = 0; m < 2; m++)
#pragma unroll
          for (int hh = 0; hh < 2; hh++) st[m][hh] = lds64f(sb + ROWST + (wg * 128 + m * 64 + w * 16 + g + 8 * hh) * 8);
        float2 cs[4];
        auto load_cs = [&](int gi) {
#pragma unroll
          for (int j = 0; j < 4; j++) cs[j] = lds64f(sb + COLS + (gi * 32 + j * 8 + 2 * qd) * 4);
        };
        load_cs(2);
        auto drain = [&]() {
          wg_wait<0>(); fence_regs(acc[0]);
          if (w == 0) e_arrive_both(sb + B_QE + 8 * 3);
        };
        wg_wait<1>(); fence_regs(acc[1]);
        auto norm_tile = [&](int gi, int m, float sc, uint32_t (&t)[8], float (&nrm)[2], bool h16 = false) {
          const float r0 = st[m][0].x * sc, s0 = st[m][0].y * sc, r1 = st[m][1].x * sc, s1 = st[m][1].y * sc;
          float n0 = 0.f, n1 = 0.f;
#pragma unroll
          for (int j = 0; j < 4; j++) {
            const float* a = &acc[m][16 * gi + 4 * j];
            const float v0 = fmaf(a[0], r0, s0 * cs[j].x), v1 = fmaf(a[1], r0, s0 * cs[j].y);
            const float v2 = fmaf(a[2], r1, s1 * cs[j].x), v3 = fmaf(a[3], r1, s1 * cs[j].y);
            n0 = fmaf(v0, v0, fmaf(v1, v1, n0)); n1 = fmaf(v2, v2, fmaf(v3, v3, n1));
            t[2 * j] = h16 ? pack2h(v0, v1) : pack2(v0, v1); t[2 * j + 1] = h16 ? pack2h(v2, v3) : pack2(v2, v3);
          }
          nrm[0] = n0; nrm[1] = n1;
        };
        auto norm_group = [&](int gi, float sc, uint32_t (&t)[2][8], float (&nrm)[2][2]) { norm_tile(gi, 0, sc, t[0], nrm[0]); norm_tile(gi, 1, sc, t[1], nrm[1]); };
        uint32_t q[2][2][8];
        const uint32_t srow = (lane & 7) + ((lane >> 3) & 1) * 8;
        const uint32_t row0 = wg * 128 + w * 16;
        auto put_o = [&](int h, int m, const float (&o)[16], float i0, float i1) {
          IDS();
          bf16* op = g_os + (size_t)(bm * 256 + row0 + m * 64 + (lane >> 2)) * 1024 + h * 512 + bn * 32 + (lane & 3) * 8;
          *(uint4*)op = make_uint4(pack2(o[0] * i0, o[1] * i0), pack2(o[4] * i0, o[5] * i0), pack2(o[8] * i0, o[9] * i0), pack2(o[12] * i0, o[13] * i0));
          *(uint4*)(op + 8 * 1024) = make_uint4(pack2(o[2] * i1, o[3] * i1), pack2(o[6] * i1, o[7] * i1), pack2(o[10] * i1, o[11] * i1), pack2(o[14] * i1, o[15] * i1));
        };
        if (!(l & 1)) {
          auto put_kv = [&](int gi, uint32_t r0, const uint32_t (&t)[8]) {
            if (gi < 4) {
              const uint32_t r = r0 + srow;
#pragma unroll
              for (int jj = 0; jj < 2; jj++) stsm4(sb + KSC + r * 128 + (((4 * (gi - 2) + 2 * jj + (lane >> 4)) ^ (r & 7)) << 4), t[4 * jj], t[4 * jj + 1], t[4 * jj + 2], t[4 * jj + 3]);
            } else {
              const uint32_t r = r0 + g, ad = sb + VSC + r * 128 + (((4 * (gi - 4) + qd) ^ (r & 7)) << 4);
              sts128(ad, t[0], t[2], t[4], t[6]); sts128(ad + 1024, t[1], t[3], t[5], t[7]);
            }
          };
          auto cen_tile = [&](int gi, int m, uint32_t (&t)[8]) {
#pragma unroll
            for (int j = 0; j < 4; j++) {
              const float* a = &acc[m][16 * gi + 4 * j];
              t[2 * j] = pack2(fmaf(st[m][0].y, cs[j].x, a[0]), fmaf(st[m][0].y, cs[j].y, a[1]));
              t[2 * j + 1] = pack2(fmaf(st[m][1].y, cs[j].x, a[2]), fmaf(st[m][1].y, cs[j].y, a[3]));
            }
          };
          const bool send = wg == 1 && w == 3 && bm < 7;
          uint4* hp = g_halo + ((l >> 1) * 128 + b) * 384 + lane;
          mbar_wait(sb + B_QE + 16, 1);
          float2 cn[4];
          auto next_cs = [&](int gi) {
#pragma unroll
            for (int j = 0; j < 4; j++) { cs[j] = cn[j]; cn[j] = lds64f(sb + COLS + (gi * 32 + j * 8 + 2 * qd) * 4); }
          };
#pragma unroll
          for (int j = 0; j < 4; j++) cn[j] = cs[j];
#pragma unroll
          for (int h = 0; h < 2; h++) {
            uint32_t k[8], v[8];
            next_cs(4 + h);
            cen_tile(2 + h, 1, k); put_kv(2 + h, 16 + row0 + 64, k);
            next_cs(h ? 2 : 3);
            cen_tile(4 + h, 1, v); put_kv(4 + h, 16 + row0 + 64, v);
            if (send) {
              uint4* p = hp + h * 192;
              st_tagged(p, k[0], k[1], k[2], ep1); st_tagged(p + 32, k[3], k[4], k[5], ep1); st_tagged(p + 64, k[6], k[7], v[0], ep1);
              st_tagged(p + 96, v[1], v[2], v[3], ep1); st_tagged(p + 128, v[4], v[5], v[6], ep1);
              st_tagged(p + 160, v[7], __float_as_uint(qd & 1 ? st[1][1].x : st[1][0].x), 0u, ep1);
            }
            sched_fence();
          }
          drain();
          {
            uint32_t t[8];
            next_cs(4); cen_tile(2, 0, t); put_kv(2, 16 + row0, t);
            next_cs(0); cen_tile(4, 0, t); put_kv(4, 16 + row0, t);
            next_cs(3); cen_tile(0, 0, q[0][0]); cen_tile(0, 1, q[0][1]);
          }
          bar_sync(NB_SC, 256);
          const bool e = g & 1, sel = 2 * qd + (g & 1) >= g + 2, first = bm == 0 && row0 == 0;
          if (row0 == 0) bar_sync(NB_HALO, 64);
          float ra[4], rb[4], ca[4], cb[4];
#pragma unroll
          for (int m = 0; m < 2; m++) {
            float rk[3];
#pragma unroll
            for (int u = 0; u < 3; u++) {
              const int r = row0 + m * 64 + 8 * u + 2 * qd + e - (sel ? 16 : 8);
              rk[u] = lds64f(sb + (m == 0 && r < 0 ? HRS + 128 : ROWST) + r * 8).x;
            }
            ra[2 * m] = sel ? rk[1] : rk[0]; ra[2 * m + 1] = sel ? rk[2] : rk[1];
            rb[2 * m] = sel ? rk[0] : rk[1]; rb[2 * m + 1] = sel ? rk[1] : rk[2];
          }
#pragma unroll
          for (int i = 0; i < 4; i++) { const float rq = st[i >> 1][i & 1].x * QSCALE; ca[i] = rq * ra[i]; cb[i] = rq * rb[i]; }
#pragma unroll 1
          for (int h = 0; h < 2; h++) {
            float s[2][4][4];
            uint32_t vf[2][4][4], pf[2][2][4];
#pragma unroll
            for (int m = 0; m < 2; m++)
#pragma unroll
              for (int nt = 0; nt < 4; nt++) {
                uint32_t kf[4];
                const uint32_t r = row0 + m * 64 + 8 * nt + (lane & 7), ch = 4 * h + (lane >> 3);
                ldsm4(sb + KSC + r * 128 + ((ch ^ (r & 7)) << 4), kf);
                s[m][nt][0] = s[m][nt][1] = s[m][nt][2] = s[m][nt][3] = 0.f;
                mma16816(s[m][nt], q[0][m][0], q[0][m][1], q[0][m][2], q[0][m][3], kf[0], kf[1]);
                mma16816(s[m][nt], q[0][m][4], q[0][m][5], q[0][m][6], q[0][m][7], kf[2], kf[3]);
              }
#pragma unroll
            for (int m = 0; m < 2; m++)
#pragma unroll
              for (int i = 0; i < 4; i++) {
                const uint32_t r = row0 + m * 64 + 16 * (i >> 1) + srow, ch = 4 * h + 2 * (i & 1) + (lane >> 4);
                ldsm4t(sb + VSC + r * 128 + ((ch ^ (r & 7)) << 4), vf[m][i]);
              }
            float va[4], vb[4], mx[4];
#pragma unroll
            for (int i = 0; i < 4; i++) {
              const int m = i >> 1, hh = i & 1;
              const float a = e ? s[m][hh + 1][2 * hh + 1] : s[m][hh + 1][2 * hh];
              const float lo = e ? s[m][hh][2 * hh + 1] : s[m][hh][2 * hh], hi = e ? s[m][hh + 2][2 * hh + 1] : s[m][hh + 2][2 * hh];
              va[i] = (m == 0 && hh == 0 && first) ? -INFINITY : a * ca[i];
              vb[i] = (m == 0 && first && sel) ? -INFINITY : (sel ? lo : hi) * cb[i];
              mx[i] = fmaxf(va[i], vb[i]);
            }
#pragma unroll
            for (int i = 0; i < 4; i++) mx[i] = fmaxf(mx[i], __shfl_xor_sync(~0u, mx[i], 1));
#pragma unroll
            for (int i = 0; i < 4; i++) mx[i] = fmaxf(mx[i], __shfl_xor_sync(~0u, mx[i], 2));
#pragma unroll
            for (int i = 0; i < 4; i++) {
              va[i] = ex2(va[i] - mx[i]); vb[i] = ex2(vb[i] - mx[i]);
              mx[i] = va[i] + vb[i];
              va[i] *= ra[i]; vb[i] *= rb[i];
            }
#pragma unroll
            for (int i = 0; i < 4; i++) mx[i] += __shfl_xor_sync(~0u, mx[i], 1);
#pragma unroll
            for (int i = 0; i < 4; i++) mx[i] += __shfl_xor_sync(~0u, mx[i], 2);
#pragma unroll
            for (int i = 0; i < 4; i++) {
              const int m = i >> 1, hh = i & 1;
              const float inv = rcp(mx[i]);
              const uint32_t t = pack2(va[i] * inv, vb[i] * inv);
              const uint32_t pa = e ? t << 16 : t & 0xFFFFu, pb = e ? t & 0xFFFF0000u : t >> 16;
              pf[m][hh][hh + 1] = pa; pf[m][hh][hh] = sel ? pb : 0u; pf[m][hh][hh + 2] = sel ? 0u : pb; pf[m][hh][3 - 3 * hh] = 0u;
            }
#pragma unroll
            for (int m = 0; m < 2; m++) {
              float o[4][4];
#pragma unroll
              for (int j = 0; j < 4; j++) o[j][0] = o[j][1] = o[j][2] = o[j][3] = 0.f;
#pragma unroll
              for (int i = 0; i < 4; i++) {
                const int kk = i >> 1, jj = 2 * (i & 1);
                mma16816(o[jj], pf[m][0][2 * kk], pf[m][1][2 * kk], pf[m][0][2 * kk + 1], pf[m][1][2 * kk + 1], vf[m][i][0], vf[m][i][1]);
                mma16816(o[jj + 1], pf[m][0][2 * kk], pf[m][1][2 * kk], pf[m][0][2 * kk + 1], pf[m][1][2 * kk + 1], vf[m][i][2], vf[m][i][3]);
              }
              const float of[16] = {o[0][0], o[0][1], o[0][2], o[0][3], o[1][0], o[1][1], o[1][2], o[1][3], o[2][0], o[2][1], o[2][2], o[2][3], o[3][0], o[3][1], o[3][2], o[3][3]};
              put_o(h, m, of, 1.f, 1.f);
            }
            bar_arrive(NB_SIG + 2 * h + wg, 160);
            if (h == 0) {
              uint32_t t[8];
              next_cs(5); cen_tile(3, 0, t); put_kv(3, 16 + row0, t);
              next_cs(1); cen_tile(5, 0, t); put_kv(5, 16 + row0, t);
#pragma unroll
              for (int j = 0; j < 4; j++) cs[j] = cn[j];
              cen_tile(1, 0, q[0][0]); cen_tile(1, 1, q[0][1]);
              bar_sync(NB_SC, 256);
              if (row0 == 0) bar_sync(NB_HALO + 1, 64);
            }
          }
        } else {
          float qn[2];
          drain();
          auto esc_ptr = [&](int gi) { IDS(); return g_esc + (size_t)(((l & 2) + (gi >> 1)) * 65536 + (2 * bn + (gi & 1)) * 2048) * 16; };
          auto norm_half = [&](int gi, float sc, uint32_t (&t)[2][8], float (&nrm)[2][2]) {
            norm_tile(gi, 0, sc, t[0], nrm[0], true); norm_tile(gi, 1, sc, t[1], nrm[1], true);
            if (!((nrm[0][0] + nrm[0][1]) + (nrm[1][0] + nrm[1][1]) <= 4e9f)) {
              uint32_t* p = esc_ptr(gi) + (bm * 256 + row0 + g) * 16 + qd;
#pragma unroll
              for (int m = 0; m < 2; m++) {
                uint32_t u[8]; float d[2];
                norm_tile(gi, m, sc, u, d);
#pragma unroll
                for (int i = 0; i < 8; i++) p[(m * 64 + (i & 1) * 8) * 16 + (i >> 1) * 4] = u[i];
              }
            }
            __syncwarp();
          };
          {
            auto max_norm = [&](const float (&nrm)[2][2]) {
              const bool o1 = qd & 1, o2 = qd & 2;
              const float a = (o1 ? nrm[1][0] : nrm[0][0]) + __shfl_xor_sync(~0u, o1 ? nrm[0][0] : nrm[1][0], 1);
              const float c = (o1 ? nrm[1][1] : nrm[0][1]) + __shfl_xor_sync(~0u, o1 ? nrm[0][1] : nrm[1][1], 1);
              const float d = (o2 ? c : a) + __shfl_xor_sync(~0u, o2 ? a : c, 2);
              return __uint_as_float(__reduce_max_sync(~0u, __float_as_uint(d)));
            };
#pragma unroll
            for (int h = 0; h < 2; h++) {
              uint32_t t[2][8]; float nrm[2][2];
              const uint32_t kb = sb + (h ? 0 : T0);
              if (h) load_cs(3);
              uint32_t tv[2][8];
              norm_half(2 + h, 1.f, t, nrm);
              load_cs(4 + h);
              float nv[2][2];
              if (h == 1) { const float kn = max_norm(nrm); if (lane == 0) g_kn[((l >> 1) * 128 + bn * 8 + bm) * 16 + 8 + wg * 4 + w] = kn; }
              if (h == 0) mbar_wait(sb + B_QE + 8, 1);
#pragma unroll
              for (int i = 0; i < 4; i++) {
                const uint32_t r = row0 + (i >> 1) * 64 + srow;
                stsm4(kb + r * 64 + (((2 * (i & 1) + (lane >> 4)) ^ ((r >> 1) & 3)) << 4), t[i >> 1][4 * (i & 1)], t[i >> 1][4 * (i & 1) + 1], t[i >> 1][4 * (i & 1) + 2], t[i >> 1][4 * (i & 1) + 3]);
              }
              const int krow = 2 * bn * 2048 + bm * 256 + row0;
              if (h == 0) {
                fence_async_smem(); __syncwarp();
                tma_st(&prm.m[M_K16], 0, krow, kb + row0 * 64); tma_st(&prm.m[M_K16], 0, krow + 64, kb + row0 * 64 + 4096);
              }
              norm_group(4 + h, 1.f, tv, nv);
              load_cs(h);
#pragma unroll
              for (int m = 0; m < 2; m++) {
                const uint32_t r = row0 + m * 64 + g, ad = kb + 16384 + r * 64 + ((qd ^ ((r >> 1) & 3)) << 4);
                sts128(ad, tv[m][0], tv[m][2], tv[m][4], tv[m][6]); sts128(ad + 512, tv[m][1], tv[m][3], tv[m][5], tv[m][7]);
              }
              fence_async_smem();
              bar_arrive(NB_KV + 12 * h, 288);
              if (h == 0) {
                __syncwarp();
                tma_st(&prm.m[M_V16], 0, krow, kb + 16384 + row0 * 64); tma_st(&prm.m[M_V16], 0, krow + 64, kb + 16384 + row0 * 64 + 4096);
                bulk_commit();
                if (wg) { bulk_wait_n<0>(); bar_arrive(NB_DONE, 288); bar_sync(NB_HALO + 1, 256); }
              }
              if (h == 0) { const float kn = max_norm(nrm); if (lane == 0) g_kn[((l >> 1) * 128 + bn * 8 + bm) * 16 + wg * 4 + w] = kn; }
              norm_half(h, QSCALE, q[h], nrm);
#pragma unroll
              for (int i = 0; i < 4; i++) sts128(sb + QPARK + h * 16384 + (wg * 128 + w * 32 + lane) * 16 + i * 4096, q[h][i >> 1][4 * (i & 1)], q[h][i >> 1][4 * (i & 1) + 1], q[h][i >> 1][4 * (i & 1) + 2], q[h][i >> 1][4 * (i & 1) + 3]);
              qn[h] = max_norm(nrm);
              if (h == 0 && !wg) { bulk_wait_n<0>(); bar_arrive(NB_DONE, 288); }
            }
            if (!wg) bar_arrive(NB_HALO + 1, 256);
          }
          constexpr uint64_t VSTEP = 64 - (64ull << 16);
          const uint32_t c_882 = 0x62E562E5u + (lane_id() & zero), c_lsb = 0x00010001u + (lane_id() & zero), c_half = 0x3F003F00u + (lane_id() & zero);
          float o[2][20], S[2][32];
          uint32_t H[2][16], P0[4] = {}, P1[4] = {};
#pragma unroll
          for (int m = 0; m < 2; m++) {
#pragma unroll
            for (int i = 0; i < 20; i++) o[m][i] = 0.f;
            fence_regs(o[m]);
          }
          auto qkf = [&](int b, int ks, uint64_t d) { wg_n64_rs_nb_f16_f32(S[b], q[0][0][4 * ks], q[0][0][4 * ks + 1], q[0][0][4 * ks + 2], q[0][0][4 * ks + 3], d + 2 * ks, ks ? 1 : zero); };
          auto qkh = [&](int b, int ks, uint64_t d) { wg_n64_rs_nb_f16_f16(H[b], q[0][1][4 * ks], q[0][1][4 * ks + 1], q[0][1][4 * ks + 2], q[0][1][4 * ks + 3], d + 2 * ks, ks ? 1 : zero); };
          auto pv0 = [&](uint64_t d) { wgmma_m64n40k16_rs_tb(o[0], P0[0], P0[1], P0[2], P0[3], d, 1); };
          auto pv1 = [&](uint64_t d) { wgmma_m64n40k16_rs_tb(o[1], P1[0], P1[1], P1[2], P1[3], d, 1); };
          float e[4] = {};
          auto finish = [&](int h) {
            const float* s = &S[(h >> 2) & 1][8 * (h & 3)];
            const uint32_t* u = &H[(h >> 2) & 1][4 * (h & 3)];
            const float z0 = exp2_fix(s[6]), z1 = exp2_fix(s[7]);
            P0[0] = pack2v(e[0], e[1]);
            P1[0] = exp2_h2(u[0], c_882);
            P0[1] = pack2v(e[2], e[3]);
            P1[1] = exp2_h2(u[1], c_882);
            const uint32_t B = exp2_base(z0, z1), E = and_or<0x7F807F80u>(B, c_lsb);
            P1[3] = exp2_h2(u[3], c_882);
            P0[3] = fma_bf2(B, and_or<0x807F807Fu>(B, c_half), E);
            const float e4 = ex2v(s[4]), e5 = ex2v(s[5]);
            P1[2] = exp2_h2(u[2], c_882);
            P0[2] = pack2v(e4, e5);
          };
          auto start = [&](int h) {
            const float* s = &S[(h >> 2) & 1][8 * (h & 3)];
            e[0] = ex2v(s[0]); e[1] = ex2v(s[1]); e[3] = ex2v(s[3]); e[2] = ex2v(s[2]);
          };
          uint64_t kd = prm.kv[0].kd;
          mbar_wait(sb + B_TF, 0);
          wg_fence();
#pragma unroll
          for (int b = 0; b < 2; b++) {
            wg_n64_rs_nb_f16_f32_z(S[b], q[0][0][0], q[0][0][1], q[0][0][2], q[0][0][3], kd + 256 * b, 0);
            wg_n64_rs_nb_f16_f16_z(H[b], q[0][1][0], q[0][1][1], q[0][1][2], q[0][1][3], kd + 256 * b, 0);
            if (b == 0) { qkf(0, 1, kd); qkh(0, 1, kd); }
            wg_commit();
          }
          wg_wait<1>(); fence_regs(S[0]); fence_regs(H[0]);
          start(0); finish(0); start(1);
          wg_wait<0>();
          int redo = 0;
#pragma unroll 1
          for (int pass = 0, j = 1; pass < 2; pass++) {
#pragma unroll 1
           do {
            const uint64_t vd = prm.kv[j].vd;
            bool go = false;
#pragma unroll
            for (int h = 2; h < 18; h++) {
              const int px = (h >> 2) + 1, c = h & 3;
              wg_fence();
              if (h == 13) kd = prm.kv[j].kd;
              const uint64_t kx = kd + (px & 3) * 256, vx = vd + (h - 2) * VSTEP;
              if (h == 2) { qkh(1, 0, kx); qkf(1, 0, kx); pv0(vx); pv1(vx); qkh(1, 1, kx); qkf(1, 1, kx); }
              else if ((c == 1 || c == 2) && h < 17) { qkh(px & 1, c - 1, kx); pv1(vx); qkf(px & 1, c - 1, kx); pv0(vx); }
              else { pv0(vx); pv1(vx); }
              wg_commit();
              if (h == 3) e_arrive_if(sb + B_TE + 8 * ((j + 2) & 3), j > 1);
              if (h == 11) go = mbar_test(sb + B_TF + 8 * (j & 3), (j >> 2) & 1) && j != 8;
              finish(h - 1); start(h);
              if (h != 12 && h != 17) sched_fence();
              if (h == 12 && !go) {
                if (j == 16) {
#pragma unroll
                  for (int u = 13; u < 18; u++) {
                    wg_fence(); pv0(vd + (u - 2) * VSTEP); pv1(vd + (u - 2) * VSTEP); wg_commit();
                    if (u < 17) finish(u - 1);
                    if (u < 16) { start(u); sched_fence(); }
                    if (u & 1) { if (u == 17) wg_wait<0>(); else wg_wait<1>(); }
                  }
                  e_arrive(sb + B_TE + 24);
                  goto head_done;
                }
                mbar_wait(sb + B_TF + 8 * (j & 3), (j >> 2) & 1);
                if (j == 8) {
#pragma unroll
                  for (int i = 0; i < 4; i++) lds128(sb + QPARK + 16384 + (wg * 128 + w * 32 + lane_id()) * 16 + i * 4096, &q[0][i >> 1][4 * (i & 1)]);
                }
              }
              if (h == 17) wg_wait<0>(); else if (h & 1) wg_wait<1>();
              if (c == 3) { fence_regs(S[px & 1]); fence_regs(H[px & 1]); }
            }
           } while (j++ & 7);
           head_done:
            fence_regs(o[0]); fence_regs(o[1]);
            uint32_t pk[2][8];
            {
              IDS();
              bf16* op = g_os + (size_t)(bm * 256 + row0 + (lane >> 2)) * 1024 + pass * 512 + bn * 32 + (lane & 3) * 8;
#pragma unroll
              for (int i = 0; i < 4; i++) {
                const float* a = &o[i >> 1][2 * (i & 1)];
                const float inv = rcp(a[16]);
                uint32_t* u = &pk[i >> 1][4 * (i & 1)];
#pragma unroll
                for (int k = 0; k < 4; k++) u[k] = pack2(a[4 * k] * inv, a[4 * k + 1] * inv);
                *(uint4*)(op + ((i >> 1) * 64 + (i & 1) * 8) * 1024) = make_uint4(u[0], u[1], u[2], u[3]);
              }
            }
            sched_fence();
            if (pass == 0) bar_sync(NB_KN + wg, 160);
            const float kmax = *(volatile float*)(smem + ROWST + 4 * pass);
            const bool wide = !(qn[0] <= 1.6e7f) | !(kmax <= 1.6e7f) | !(qn[0] * kmax <= 112.f * 112.f);
            int badm = 0;
#pragma unroll
            for (int m = 0; m < 2; m++) {
              uint32_t chk[2] = {0u, 0u};
#pragma unroll
              for (int i = 0; i < 8; i++) asm("fma.rn.bf16x2 %0, %1, %2, %0;" : "+r"(chk[i & 1]) : "r"(pk[m][i]), "r"(0u));
              const bool bad = wide | !(fminf(o[m][16], o[m][18]) >= 9.3e-10f) | !(o[m][16] + o[m][18] <= 1e36f) | (((chk[0] | chk[1]) & 0x7FFF7FFFu) != 0);
              badm |= __any_sync(~0u, bad) << m;
            }
            if (!badm) bar_arrive(NB_SIG + 2 * pass + wg, 160);
            qn[0] = qn[1];
#pragma unroll
            for (int m = 0; m < 2; m++) {
#pragma unroll
              for (int i = 0; i < 20; i++) o[m][i] = 0.f;
              fence_regs(o[m]);
            }
            if (badm) {
              redo |= badm << 2 * pass;
              const int tx = wg * 128 + w * 32 + lane_id();
              uint4* p = g_qsave + (block_id() * 256 + tx) * 8 + pass * 4;
#pragma unroll
              for (int i = 0; i < 4; i++) {
                uint32_t u[4] = {q[0][i >> 1][4 * (i & 1)], q[0][i >> 1][4 * (i & 1) + 1], q[0][i >> 1][4 * (i & 1) + 2], q[0][i >> 1][4 * (i & 1) + 3]};
                if (pass == 0) lds128(sb + QPARK + tx * 16 + i * 4096, u);
                p[i] = make_uint4(u[0], u[1], u[2], u[3]);
              }
            }
          }
          if (redo) attn_redo(redo, l, cta_id(), wg, w);
        }
      }
      {
        float acc[64];
#pragma unroll
        for (int i = 0; i < 64; i++) acc[i] = 0.f;
        fence_regs(acc);
        uint32_t s = 0, lap = 0;
#pragma unroll 1
        for (int kt = 0; kt < 16; kt++) {
          mbar_wait(sb + B_PF + 8 * s, ((s < 4 ? l : 0) + lap) & 1);
          const uint64_t da = mkdesc(sb + pslot_a(s, l) + wg * 8192, 16, 1024, 1), db = mkdesc(sb + pslot_b(s), 8192, 1024, 1);
          wg_fence();
#pragma unroll
          for (int k = 0; k < 4; k++) wgmma_m64n128k16_ss_tb(acc, da + k * 2, db + k * 128, 1);
          wg_commit();
          wg_wait<1>();
          if (kt > 0 && w == 0) e_arrive_both(sb + B_PE + 8 * (s ? s - 1 : 5));
          if (++s == 6) { s = 0; lap++; }
        }
        IDS();
        const int g = lane >> 2, qd = lane & 3;
        const int r0 = wg * 64 + w * 16;
        const uint32_t r = r0 + (lane & 7) + ((lane >> 3) & 1) * 8;
        uint32_t x[8][4];
        mbar_wait(sb + B_RF, l & 1);
#pragma unroll
        for (int jj = 0; jj < 8; jj++) ldsm4(sb + RES + (jj >> 2) * 16384 + r * 128 + ((((2 * jj + (lane >> 4)) & 7) ^ (r & 7)) << 4), x[jj]);
        wg_wait<0>();
        fence_regs(acc);
        if (w == 0) e_arrive_both(sb + B_PE + 8 * 3);
        const CUtensorMap* mo = &prm.m[l == 3 ? M_OUT : M_XST];
#pragma unroll
        for (int jj = 0; jj < 8; jj++) {
#pragma unroll
          for (int i = 0; i < 4; i++) x[jj][i] = add_bf16x2(x[jj][i], pack2(acc[8 * jj + 2 * i], acc[8 * jj + 2 * i + 1]));
          stsm4(sb + RES + (jj >> 2) * 16384 + r * 128 + ((((2 * jj + (lane >> 4)) & 7) ^ (r & 7)) << 4), x[jj][0], x[jj][1], x[jj][2], x[jj][3]);
          if ((jj & 3) == 3) { fence_async_smem(); __syncwarp(); tma_st(mo, pn * 128 + (jj >> 2) * 64, pm * 128 + r0, sb + RES + (jj >> 2) * 16384 + r0 * 128); }
        }
        bulk_commit();
        if (l < 3) {
          bar_sync(NB_SC, 256);
#pragma unroll
          for (int jj = 0; jj < 8; jj++)
            stsm4(sb + (jj >> 2) * QSTG + po * 16384 + r * 128 + ((((2 * jj + (lane >> 4)) & 7) ^ (r & 7)) << 4), x[jj][0], x[jj][1], x[jj][2], x[jj][3]);
          fence_async_smem();
          bar_arrive(NB_X, 288);
          float s1[4] = {0.f, 0.f, 0.f, 0.f}, sa[4] = {0.f, 0.f, 0.f, 0.f}, sc[4] = {0.f, 0.f, 0.f, 0.f};
#pragma unroll
          for (int jj = 0; jj < 8; jj++) {
            mma16816(s1, x[jj][0], x[jj][1], x[jj][2], x[jj][3], 0x3f803f80u, 0x3f803f80u);
            mma16816(sa, x[jj][0], x[jj][1], x[jj][2], x[jj][3], x[jj][0], x[jj][2]);
            mma16816(sc, x[jj][0], x[jj][1], x[jj][2], x[jj][3], x[jj][1], x[jj][3]);
          }
          if (qd == g >> 1) {
            float2* p = g_stats + pn * 2048 + pm * 128 + r0 + g;
            p[0] = make_float2(s1[0], g & 1 ? sa[1] : sa[0]);
            p[8] = make_float2(s1[2], g & 1 ? sc[3] : sc[2]);
          }
        }
        bulk_wait_n<0>();
        if (l < 3) bar_arrive(NB_X0, 288);
      }
    }
  }
  asm volatile("barrier.cluster.arrive.relaxed.aligned;\nbarrier.cluster.wait.aligned;" ::: "memory");
}

typedef CUresult (*EncodeFn)(CUtensorMap*, CUtensorMapDataType, cuuint32_t, void*, const cuuint64_t*, const cuuint64_t*, const cuuint32_t*,
                             const cuuint32_t*, CUtensorMapInterleave, CUtensorMapSwizzle, CUtensorMapL2promotion, CUtensorMapFloatOOBfill);

static void make_map(EncodeFn fn, CUtensorMap* m, const void* ptr, int rank, const uint64_t* dims, const uint64_t* strides, const uint32_t* box, CUtensorMapSwizzle sw) {
  cuuint64_t d[5], st[4];
  cuuint32_t bx[5], es[5];
  for (int i = 0; i < rank; i++) { d[i] = dims[i]; bx[i] = box[i]; es[i] = 1; if (i) st[i - 1] = strides[i - 1] * 2; }
  fn(m, CU_TENSOR_MAP_DATA_TYPE_BFLOAT16, rank, (void*)ptr, d, st, bx, es, CU_TENSOR_MAP_INTERLEAVE_NONE, sw,
     CU_TENSOR_MAP_L2_PROMOTION_L2_128B, CU_TENSOR_MAP_FLOAT_OOB_FILL_NONE);
}
static void map2(EncodeFn fn, CUtensorMap* m, const void* ptr, uint64_t inner, uint64_t outer, uint32_t bi, uint32_t bo, CUtensorMapSwizzle sw) {
  const uint64_t d[2] = {inner, outer}, st[1] = {inner};
  const uint32_t bx[2] = {bi, bo};
  make_map(fn, m, ptr, 2, d, st, bx, sw);
}

extern "C" void kernel_launch(void* const* d_in, const int* in_sizes, int n_in, void* d_out, int out_size) {
  (void)in_sizes; (void)n_in; (void)out_size;
  static EncodeFn enc = nullptr;
  static void *xs, *os, *kk, *vv;
  static int sbase = 1024;
  if (!enc) {
    void* p = nullptr;
    cudaDriverEntryPointQueryResult qr;
    cudaGetDriverEntryPoint("cuTensorMapEncodeTiled", &p, cudaEnableDefault, &qr);
    enc = (EncodeFn)p;
    Scratch* sc = nullptr;
    cudaGetSymbolAddress((void**)&sc, g_s);
    xs = sc->xs; os = sc->os; kk = sc->k; vv = sc->v;
    int dev = 0;
    cudaGetDevice(&dev);
    cudaDeviceGetAttribute(&sbase, cudaDevAttrReservedSharedMemoryPerBlock, dev);
    cudaFuncSetAttribute(fused_kernel, cudaFuncAttributeMaxDynamicSharedMemorySize, SMEM_BYTES);
  }
  Params prm;
  const CUtensorMapSwizzle S128 = CU_TENSOR_MAP_SWIZZLE_128B, S64 = CU_TENSOR_MAP_SWIZZLE_64B;
  map2(enc, &prm.m[M_X0A], d_in[0], 1024, 2048, 64, 256, S128);
  map2(enc, &prm.m[M_XSA], xs, 1024, 2048, 64, 256, S128);
  for (int t = 0; t < 2; t++) {
    const uint64_t d3[3] = {1024, 1024, 3}, s3[2] = {3072, 1024};
    const uint32_t b3[3] = {64, 64, 3};
    make_map(enc, &prm.m[M_WQA + t], d_in[1 + 3 * t], 3, d3, s3, b3, S128);
    const uint64_t d5[5] = {64, 32, 2, 16, 16}, s5[4] = {1024, 32 * 1024, 64 * 1024, 64};
    const uint32_t b5[5] = {64, 32, 1, 2, 2};
    make_map(enc, &prm.m[M_WOA + t], d_in[2 + 3 * t], 5, d5, s5, b5, S128);
    const uint64_t dr[3] = {64, 2048, 16}, sr[2] = {1024, 64};
    const uint32_t br[3] = {64, 128, 2};
    make_map(enc, &prm.m[M_X0R + t], t ? xs : d_in[0], 3, dr, sr, br, S128);
  }
  map2(enc, &prm.m[M_OS], os, 1024, 2048, 64, 64, S128);
  map2(enc, &prm.m[M_K], kk, 32, 65536, 32, 256, S64);
  map2(enc, &prm.m[M_V], vv, 32, 65536, 32, 256, S64);
  map2(enc, &prm.m[M_K16], kk, 32, 65536, 32, 16, S64);
  map2(enc, &prm.m[M_V16], vv, 32, 65536, 32, 16, S64);
  map2(enc, &prm.m[M_XSO], xs, 1024, 2048, 64, 128, S128);
  map2(enc, &prm.m[M_X0H], d_in[0], 1024, 2048, 64, 128, S128);
  map2(enc, &prm.m[M_XST], xs, 1024, 2048, 64, 16, S128);
  map2(enc, &prm.m[M_OUT], d_out, 1024, 2048, 64, 16, S128);
  prm.x0 = (const bf16*)d_in[0];
  prm.wq[0] = (const bf16*)d_in[1]; prm.wq[1] = (const bf16*)d_in[4];
  prm.zero = 0;
  for (int i = 0; i < 128; i++) prm.map[i] = remap(i);
  {
    const uint64_t hi = 0x80000020ull << 32, k0 = sbase + T0, v0 = k0 + 16384, vstep = 64 - (64ull << 16);
    for (int j = 0; j < 17; j++) {
      prm.kv[j].kd = (hi | 1u << 16 | k0 >> 4) + 2048 * ((j < 16 ? j : 15) & 3);
      prm.kv[j].vd = (hi | (uint64_t)(ONES - T0 - 16384) >> 4 << 16 | v0 >> 4) + 32 * vstep * ((j ? j - 1 : 0) & 3);
    }
  }
  fused_kernel<<<128, 384, SMEM_BYTES>>>(prm);
}
```

```cpp
#include <cuda_runtime.h>
#include <cuda_bf16.h>
#include <cuda.h>
#include <stdint.h>

typedef __nv_bfloat16 bf16;

__device__ __forceinline__ void wgmma_m64n192k16_ss_tb(float (&d)[96], uint64_t da, uint64_t db, int scale_d) {
  asm volatile("{\n.reg .pred p;\nsetp.ne.b32 p, %98, 0;\n"
    "wgmma.mma_async.sync.aligned.m64n192k16.f32.bf16.bf16 "
    "{%0, %1, %2, %3, %4, %5, %6, %7, %8, %9, %10, %11, %12, %13, %14, %15, "
    "%16, %17, %18, %19, %20, %21, %22, %23, %24, %25, %26, %27, %28, %29, %30, %31, "
    "%32, %33, %34, %35, %36, %37, %38, %39, %40, %41, %42, %43, %44, %45, %46, %47, "
    "%48, %49, %50, %51, %52, %53, %54, %55, %56, %57, %58, %59, %60, %61, %62, %63, "
    "%64, %65, %66, %67, %68, %69, %70, %71, %72, %73, %74, %75, %76, %77, %78, %79, "
    "%80, %81, %82, %83, %84, %85, %86, %87, %88, %89, %90, %91, %92, %93, %94, %95}, "
    "%96, %97, p, 1, 1, 0, 1;\n}\n"
    : "+f"(d[0]), "+f"(d[1]), "+f"(d[2]), "+f"(d[3]), "+f"(d[4]), "+f"(d[5]), "+f"(d[6]), "+f"(d[7]),
      "+f"(d[8]), "+f"(d[9]), "+f"(d[10]), "+f"(d[11]), "+f"(d[12]), "+f"(d[13]), "+f"(d[14]), "+f"(d[15]),
      "+f"(d[16]), "+f"(d[17]), "+f"(d[18]), "+f"(d[19]), "+f"(d[20]), "+f"(d[21]), "+f"(d[22]), "+f"(d[23]),
      "+f"(d[24]), "+f"(d[25]), "+f"(d[26]), "+f"(d[27]), "+f"(d[28]), "+f"(d[29]), "+f"(d[30]), "+f"(d[31]),
      "+f"(d[32]), "+f"(d[33]), "+f"(d[34]), "+f"(d[35]), "+f"(d[36]), "+f"(d[37]), "+f"(d[38]), "+f"(d[39]),
      "+f"(d[40]), "+f"(d[41]), "+f"(d[42]), "+f"(d[43]), "+f"(d[44]), "+f"(d[45]), "+f"(d[46]), "+f"(d[47]),
      "+f"(d[48]), "+f"(d[49]), "+f"(d[50]), "+f"(d[51]), "+f"(d[52]), "+f"(d[53]), "+f"(d[54]), "+f"(d[55]),
      "+f"(d[56]), "+f"(d[57]), "+f"(d[58]), "+f"(d[59]), "+f"(d[60]), "+f"(d[61]), "+f"(d[62]), "+f"(d[63]),
      "+f"(d[64]), "+f"(d[65]), "+f"(d[66]), "+f"(d[67]), "+f"(d[68]), "+f"(d[69]), "+f"(d[70]), "+f"(d[71]),
      "+f"(d[72]), "+f"(d[73]), "+f"(d[74]), "+f"(d[75]), "+f"(d[76]), "+f"(d[77]), "+f"(d[78]), "+f"(d[79]),
      "+f"(d[80]), "+f"(d[81]), "+f"(d[82]), "+f"(d[83]), "+f"(d[84]), "+f"(d[85]), "+f"(d[86]), "+f"(d[87]),
      "+f"(d[88]), "+f"(d[89]), "+f"(d[90]), "+f"(d[91]), "+f"(d[92]), "+f"(d[93]), "+f"(d[94]), "+f"(d[95])
    : "l"(da), "l"(db), "r"(scale_d));
}

__device__ __forceinline__ void wgmma_m64n128k16_ss_tb(float (&d)[64], uint64_t da, uint64_t db, int scale_d) {
  asm volatile("{\n.reg .pred p;\nsetp.ne.b32 p, %66, 0;\n"
    "wgmma.mma_async.sync.aligned.m64n128k16.f32.bf16.bf16 "
    "{%0, %1, %2, %3, %4, %5, %6, %7, %8, %9, %10, %11, %12, %13, %14, %15, "
    "%16, %17, %18, %19, %20, %21, %22, %23, %24, %25, %26, %27, %28, %29, %30, %31, "
    "%32, %33, %34, %35, %36, %37, %38, %39, %40, %41, %42, %43, %44, %45, %46, %47, "
    "%48, %49, %50, %51, %52, %53, %54, %55, %56, %57, %58, %59, %60, %61, %62, %63}, "
    "%64, %65, p, 1, 1, 0, 1;\n}\n"
    : "+f"(d[0]), "+f"(d[1]), "+f"(d[2]), "+f"(d[3]), "+f"(d[4]), "+f"(d[5]), "+f"(d[6]), "+f"(d[7]),
      "+f"(d[8]), "+f"(d[9]), "+f"(d[10]), "+f"(d[11]), "+f"(d[12]), "+f"(d[13]), "+f"(d[14]), "+f"(d[15]),
      "+f"(d[16]), "+f"(d[17]), "+f"(d[18]), "+f"(d[19]), "+f"(d[20]), "+f"(d[21]), "+f"(d[22]), "+f"(d[23]),
      "+f"(d[24]), "+f"(d[25]), "+f"(d[26]), "+f"(d[27]), "+f"(d[28]), "+f"(d[29]), "+f"(d[30]), "+f"(d[31]),
      "+f"(d[32]), "+f"(d[33]), "+f"(d[34]), "+f"(d[35]), "+f"(d[36]), "+f"(d[37]), "+f"(d[38]), "+f"(d[39]),
      "+f"(d[40]), "+f"(d[41]), "+f"(d[42]), "+f"(d[43]), "+f"(d[44]), "+f"(d[45]), "+f"(d[46]), "+f"(d[47]),
      "+f"(d[48]), "+f"(d[49]), "+f"(d[50]), "+f"(d[51]), "+f"(d[52]), "+f"(d[53]), "+f"(d[54]), "+f"(d[55]),
      "+f"(d[56]), "+f"(d[57]), "+f"(d[58]), "+f"(d[59]), "+f"(d[60]), "+f"(d[61]), "+f"(d[62]), "+f"(d[63])
    : "l"(da), "l"(db), "r"(scale_d));
}

__device__ __forceinline__ void wgmma_m64n40k16_rs_tb(float (&d)[20], uint32_t a0, uint32_t a1, uint32_t a2, uint32_t a3, uint64_t db, int scale_d) {
  asm volatile("{\n.reg .pred p;\nsetp.ne.b32 p, %25, 0;\n"
    "wgmma.mma_async.sync.aligned.m64n40k16.f32.bf16.bf16 "
    "{%0, %1, %2, %3, %4, %5, %6, %7, %8, %9, %10, %11, %12, %13, %14, %15, "
    "%16, %17, %18, %19}, "
    "{%20, %21, %22, %23}, %24, p, 1, 1, 1;\n}\n"
    : "+f"(d[0]), "+f"(d[1]), "+f"(d[2]), "+f"(d[3]), "+f"(d[4]), "+f"(d[5]), "+f"(d[6]), "+f"(d[7]),
      "+f"(d[8]), "+f"(d[9]), "+f"(d[10]), "+f"(d[11]), "+f"(d[12]), "+f"(d[13]), "+f"(d[14]), "+f"(d[15]),
      "+f"(d[16]), "+f"(d[17]), "+f"(d[18]), "+f"(d[19])
    : "r"(a0), "r"(a1), "r"(a2), "r"(a3), "l"(db), "r"(scale_d));
}

__device__ __forceinline__ void wg_n64_rs_nb_f16_f32(float (&d)[32], uint32_t a0, uint32_t a1, uint32_t a2, uint32_t a3, uint64_t db, int scale_d) {
  asm volatile("{\n.reg .pred p;\nsetp.ne.b32 p, %37, 0;\n"
    "wgmma.mma_async.sync.aligned.m64n64k16.f32.f16.f16 "
    "{%0, %1, %2, %3, %4, %5, %6, %7, %8, %9, %10, %11, %12, %13, %14, %15, "
    "%16, %17, %18, %19, %20, %21, %22, %23, %24, %25, %26, %27, %28, %29, %30, %31}, "
    "{%32, %33, %34, %35}, %36, p, 1, 1, 0;\n}\n"
    : "+f"(d[0]), "+f"(d[1]), "+f"(d[2]), "+f"(d[3]), "+f"(d[4]), "+f"(d[5]), "+f"(d[6]), "+f"(d[7]),
      "+f"(d[8]), "+f"(d[9]), "+f"(d[10]), "+f"(d[11]), "+f"(d[12]), "+f"(d[13]), "+f"(d[14]), "+f"(d[15]),
      "+f"(d[16]), "+f"(d[17]), "+f"(d[18]), "+f"(d[19]), "+f"(d[20]), "+f"(d[21]), "+f"(d[22]), "+f"(d[23]),
      "+f"(d[24]), "+f"(d[25]), "+f"(d[26]), "+f"(d[27]), "+f"(d[28]), "+f"(d[29]), "+f"(d[30]), "+f"(d[31])
    : "r"(a0), "r"(a1), "r"(a2), "r"(a3), "l"(db), "r"(scale_d));
}

__device__ __forceinline__ void wg_n64_rs_nb_f16_f16(uint32_t (&d)[16], uint32_t a0, uint32_t a1, uint32_t a2, uint32_t a3, uint64_t db, int scale_d) {
  asm volatile("{\n.reg .pred p;\nsetp.ne.b32 p, %21, 0;\n"
    "wgmma.mma_async.sync.aligned.m64n64k16.f16.f16.f16 "
    "{%0, %1, %2, %3, %4, %5, %6, %7, %8, %9, %10, %11, %12, %13, %14, %15}, "
    "{%16, %17, %18, %19}, %20, p, 1, 1, 0;\n}\n"
    : "+r"(d[0]), "+r"(d[1]), "+r"(d[2]), "+r"(d[3]), "+r"(d[4]), "+r"(d[5]), "+r"(d[6]), "+r"(d[7]),
      "+r"(d[8]), "+r"(d[9]), "+r"(d[10]), "+r"(d[11]), "+r"(d[12]), "+r"(d[13]), "+r"(d[14]), "+r"(d[15])
    : "r"(a0), "r"(a1), "r"(a2), "r"(a3), "l"(db), "r"(scale_d));
}

__device__ __forceinline__ void wg_n64_rs_nb_f16_f32_z(float (&d)[32], uint32_t a0, uint32_t a1, uint32_t a2, uint32_t a3, uint64_t db, int scale_d) {
  asm volatile("{\n.reg .pred p;\nsetp.ne.b32 p, %37, 0;\n"
    "wgmma.mma_async.sync.aligned.m64n64k16.f32.f16.f16 "
    "{%0, %1, %2, %3, %4, %5, %6, %7, %8, %9, %10, %11, %12, %13, %14, %15, "
    "%16, %17, %18, %19, %20, %21, %22, %23, %24, %25, %26, %27, %28, %29, %30, %31}, "
    "{%32, %33, %34, %35}, %36, p, 1, 1, 0;\n}\n"
    : "=f"(d[0]), "=f"(d[1]), "=f"(d[2]), "=f"(d[3]), "=f"(d[4]), "=f"(d[5]), "=f"(d[6]), "=f"(d[7]),
      "=f"(d[8]), "=f"(d[9]), "=f"(d[10]), "=f"(d[11]), "=f"(d[12]), "=f"(d[13]), "=f"(d[14]), "=f"(d[15]),
      "=f"(d[16]), "=f"(d[17]), "=f"(d[18]), "=f"(d[19]), "=f"(d[20]), "=f"(d[21]), "=f"(d[22]), "=f"(d[23]),
      "=f"(d[24]), "=f"(d[25]), "=f"(d[26]), "=f"(d[27]), "=f"(d[28]), "=f"(d[29]), "=f"(d[30]), "=f"(d[31])
    : "r"(a0), "r"(a1), "r"(a2), "r"(a3), "l"(db), "r"(scale_d));
}

__device__ __forceinline__ void wg_n64_rs_nb_f16_f16_z(uint32_t (&d)[16], uint32_t a0, uint32_t a1, uint32_t a2, uint32_t a3, uint64_t db, int scale_d) {
  asm volatile("{\n.reg .pred p;\nsetp.ne.b32 p, %21, 0;\n"
    "wgmma.mma_async.sync.aligned.m64n64k16.f16.f16.f16 "
    "{%0, %1, %2, %3, %4, %5, %6, %7, %8, %9, %10, %11, %12, %13, %14, %15}, "
    "{%16, %17, %18, %19}, %20, p, 1, 1, 0;\n}\n"
    : "=r"(d[0]), "=r"(d[1]), "=r"(d[2]), "=r"(d[3]), "=r"(d[4]), "=r"(d[5]), "=r"(d[6]), "=r"(d[7]),
      "=r"(d[8]), "=r"(d[9]), "=r"(d[10]), "=r"(d[11]), "=r"(d[12]), "=r"(d[13]), "=r"(d[14]), "=r"(d[15])
    : "r"(a0), "r"(a1), "r"(a2), "r"(a3), "l"(db), "r"(scale_d));
}

#define DEVINL __device__ __forceinline__
DEVINL void wg_fence() { asm volatile("wgmma.fence.sync.aligned;" ::: "memory"); }
DEVINL void wg_commit() { asm volatile("wgmma.commit_group.sync.aligned;" ::: "memory"); }
template <int N> DEVINL void wg_wait() { asm volatile("wgmma.wait_group.sync.aligned %0;" ::"n"(N) : "memory"); }
__host__ DEVINL uint64_t mkdesc(uint32_t addr, uint32_t lbo, uint32_t sbo, int sw) {
  return (uint64_t)((addr & 0x3FFFF) >> 4) | ((uint64_t)(lbo >> 4) << 16) | ((uint64_t)(sbo >> 4) << 32) | ((uint64_t)sw << 62);
}
DEVINL void mbar_init(uint32_t bar, uint32_t cnt) { asm volatile("mbarrier.init.shared::cta.b64 [%0], %1;" ::"r"(bar), "r"(cnt) : "memory"); }
DEVINL void mbar_arrive(uint32_t bar) { asm volatile("mbarrier.arrive.shared::cta.b64 _, [%0];" ::"r"(bar) : "memory"); }
DEVINL bool mbar_try(uint32_t bar, uint32_t parity) {
  uint32_t ok;
  asm volatile("{\n.reg .pred p;\nmbarrier.try_wait.parity.shared::cta.b64 p, [%1], %2;\nselp.u32 %0, 1, 0, p;\n}" : "=r"(ok) : "r"(bar), "r"(parity) : "memory");
  return ok;
}
DEVINL bool mbar_test(uint32_t bar, uint32_t parity) {
  uint32_t ok;
  asm volatile("{\n.reg .pred p;\nmbarrier.test_wait.parity.shared::cta.b64 p, [%1], %2;\nselp.u32 %0, 1, 0, p;\n}" : "=r"(ok) : "r"(bar), "r"(parity) : "memory");
  return ok;
}
DEVINL void mbar_hint(uint32_t bar, uint32_t parity) {
#pragma unroll 1
  for (uint32_t n = 0; n < 16u; n++) if (mbar_try(bar, parity)) break;
}
DEVINL void mbar_wait(uint32_t bar, uint32_t parity) {
#pragma unroll 1
  for (uint32_t n = 0; n < 100000u; n++) if (mbar_try(bar, parity)) break;
}
#define EL(txt) "{\n.reg .pred pe;\nelect.sync _|pe, 0xffffffff;\n@pe " txt "\n}"
DEVINL void e_expect_tx(uint32_t bar, uint32_t bytes) { asm volatile(EL("mbarrier.arrive.expect_tx.shared::cta.b64 _, [%0], %1;") ::"r"(bar), "r"(bytes) : "memory"); }
DEVINL void e_arrive(uint32_t bar) { asm volatile(EL("mbarrier.arrive.shared::cta.b64 _, [%0];") ::"r"(bar) : "memory"); }
DEVINL void e_arrive_if(uint32_t bar, int c) {
  asm volatile("{\n.reg .pred pe;\nelect.sync _|pe, 0xffffffff;\nsetp.ne.and.b32 pe, %1, 0, pe;\n@pe mbarrier.arrive.shared::cta.b64 _, [%0];\n}" ::"r"(bar), "r"(c) : "memory");
}
DEVINL void e_red(uint32_t* p) { asm volatile(EL("red.release.gpu.global.add.u32 [%0], 1;") ::"l"(p) : "memory"); }
DEVINL void e_red_relaxed(uint32_t* p) { asm volatile(EL("red.relaxed.gpu.global.add.u32 [%0], 1;") ::"l"(p) : "memory"); }
DEVINL void tma_ld(uint32_t dst, const CUtensorMap* m, int c0, int c1, uint32_t bar) {
  asm volatile(EL("cp.async.bulk.tensor.2d.shared::cluster.global.mbarrier::complete_tx::bytes [%0], [%1, {%3, %4}], [%2];")
               ::"r"(dst), "l"(m), "r"(bar), "r"(c0), "r"(c1) : "memory");
}
DEVINL void tma_ld3(uint32_t dst, const CUtensorMap* m, int c0, int c1, int c2, uint32_t bar) {
  asm volatile(EL("cp.async.bulk.tensor.3d.shared::cluster.global.mbarrier::complete_tx::bytes [%0], [%1, {%3, %4, %5}], [%2];")
               ::"r"(dst), "l"(m), "r"(bar), "r"(c0), "r"(c1), "r"(c2) : "memory");
}
DEVINL void tma_ld5(uint32_t dst, const CUtensorMap* m, int c2, int c3, int c4, uint32_t bar) {
  asm volatile(EL("cp.async.bulk.tensor.5d.shared::cluster.global.mbarrier::complete_tx::bytes [%0], [%1, {0, 0, %3, %4, %5}], [%2];")
               ::"r"(dst), "l"(m), "r"(bar), "r"(c2), "r"(c3), "r"(c4) : "memory");
}
DEVINL void tma_ld_mc(uint32_t dst, const CUtensorMap* m, int c0, int c1, uint32_t bar) {
  asm volatile(EL("cp.async.bulk.tensor.2d.shared::cluster.global.mbarrier::complete_tx::bytes.multicast::cluster [%0], [%1, {%3, %4}], [%2], %5;")
               ::"r"(dst), "l"(m), "r"(bar), "r"(c0), "r"(c1), "h"((uint16_t)3) : "memory");
}
DEVINL void e_arrive_both(uint32_t bar) {
  asm volatile("{\n.reg .pred pe;\n.reg .b32 r0, r1;\nelect.sync _|pe, 0xffffffff;\nmapa.shared::cluster.u32 r0, %0, 0;\nmapa.shared::cluster.u32 r1, %0, 1;\n"
               "@pe mbarrier.arrive.shared::cluster.b64 _, [r0];\n@pe mbarrier.arrive.shared::cluster.b64 _, [r1];\n}" ::"r"(bar) : "memory");
}
DEVINL void tma_st(const CUtensorMap* m, int c0, int c1, uint32_t src) {
  asm volatile(EL("cp.async.bulk.tensor.2d.global.shared::cta.bulk_group [%0, {%2, %3}], [%1];") ::"l"(m), "r"(src), "r"(c0), "r"(c1) : "memory");
}
DEVINL void bulk_commit() { asm volatile("cp.async.bulk.commit_group;" ::: "memory"); }
template <int N> DEVINL void bulk_wait_n() { asm volatile("cp.async.bulk.wait_group %0;\nbar.warp.sync 0xffffffff;" ::"n"(N) : "memory"); }
DEVINL void l2_prefetch(const void* g, uint32_t bytes) { asm volatile(EL("cp.async.bulk.prefetch.L2.global [%0], %1;") ::"l"(g), "r"(bytes) : "memory"); }
DEVINL void fence_async_smem() { asm volatile("fence.proxy.async.shared::cta;" ::: "memory"); }
DEVINL void fence_async_gl() { asm volatile("fence.proxy.async.global;" ::: "memory"); }
DEVINL void cluster_wait() { asm volatile("barrier.cluster.wait.aligned;" ::: "memory"); }
DEVINL void bar_sync(int id, int n) { asm volatile("bar.sync %0, %1;" ::"r"(id), "r"(n) : "memory"); }
DEVINL void bar_arrive(int id, int n) { asm volatile("bar.arrive %0, %1;" ::"r"(id), "r"(n) : "memory"); }
DEVINL uint32_t ld_acquire(const uint32_t* p) { uint32_t v; asm volatile("ld.acquire.gpu.global.u32 %0, [%1];" : "=r"(v) : "l"(p) : "memory"); return v; }
DEVINL void watch(const uint32_t* p, uint32_t target, uint32_t all, uint32_t tag, uint32_t slot) {
  uint32_t seen = 0;
#pragma unroll 1
  for (uint32_t n = 0; n < 200000u && seen != all; n++) {
    const uint32_t m = __ballot_sync(~0u, (int)(ld_acquire(p) - target) >= 0) & all;
    if (m != seen) { seen = m; asm volatile("st.release.cta.shared.u32 [%0], %1;" ::"r"(slot), "r"(tag << 16 | m) : "memory"); }
  }
}
template <bool RELAXED = false> DEVINL void await_bit(uint32_t slot, uint32_t tag, int j, uint32_t& rdy) {
  if ((rdy >> j) & 1) return;
#pragma unroll 1
  for (uint32_t n = 0; n < 8000000u; n++) {
    uint32_t v;
    asm volatile("ld.acquire.cta.shared.u32 %0, [%1];" : "=r"(v) : "r"(slot) : "memory");
    if ((v >> 16) == tag && ((v >> j) & 1)) { rdy = v; break; }
    if (RELAXED) __nanosleep(200);
  }
  asm volatile("fence.proxy.async.global;" ::: "memory");
}
DEVINL void poll_ge(const uint32_t* p, uint32_t target) {
#pragma unroll 1
  for (uint32_t n = 0; n < 200000u; n++) if (__all_sync(~0u, (int)(ld_acquire(p) - target) >= 0)) break;
}
DEVINL int lane_id() { int v; asm volatile("mov.u32 %0, %%laneid;" : "=r"(v)); return v; }
__host__ DEVINL int remap(int v) {
  const int c = v >> 1, u = c - 36, r = (u * 37) >> 8;
  const int L = c < 4 ? 32 + 8 * c : c < 36 ? c - 4 : 33 + u + r;
  return 2 * L + (v & 1);
}
DEVINL int block_id() { int v; asm volatile("mov.u32 %0, %%ctaid.x;" : "=r"(v)); return v; }
#define cta_id() prm.map[block_id()]
#define IDS() const int lane = lane_id(), b = cta_id(), bm = b >> 4, bn = b & 15, rank = b & 1, pm = 2 * bm + (bn >> 3), pn = bn & 7, po = pm & 1; \
  (void)lane; (void)bm; (void)bn; (void)rank; (void)pm; (void)pn; (void)po
DEVINL void st_tagged(uint4* p, uint32_t a, uint32_t b, uint32_t c, uint32_t tag) {
  asm volatile("{\n.reg .b64 u, v;\n.reg .b128 t;\nmov.b64 u, {%1, %2};\nmov.b64 v, {%3, %4};\nmov.b128 t, {u, v};\nst.relaxed.gpu.global.b128 [%0], t;\n}"
               ::"l"(p), "r"(a), "r"(b), "r"(c), "r"(tag) : "memory");
}
DEVINL uint32_t ld_tagged(const uint4* p, uint32_t* r) {
  uint32_t tag;
  asm volatile("{\n.reg .b64 u, v;\n.reg .b128 t;\nld.relaxed.gpu.global.b128 t, [%4];\nmov.b128 {u, v}, t;\nmov.b64 {%0, %1}, u;\nmov.b64 {%2, %3}, v;\n}"
               : "=r"(r[0]), "=r"(r[1]), "=r"(r[2]), "=r"(tag) : "l"(p) : "memory");
  return tag;
}
DEVINL float ex2(float x) { float y; asm("ex2.approx.ftz.f32 %0, %1;" : "=f"(y) : "f"(x)); return y; }
DEVINL float rcp(float x) { float y; asm("rcp.approx.ftz.f32 %0, %1;" : "=f"(y) : "f"(x)); return y; }
DEVINL uint32_t pack2(float lo, float hi) { uint32_t r; asm("cvt.rn.bf16x2.f32 %0, %1, %2;" : "=r"(r) : "f"(hi), "f"(lo)); return r; }
DEVINL uint32_t pack2h(float lo, float hi) { uint32_t r; asm("cvt.rn.f16x2.f32 %0, %1, %2;" : "=r"(r) : "f"(hi), "f"(lo)); return r; }
DEVINL float bf_lo(uint32_t w) { return __uint_as_float(w << 16); }
DEVINL float bf_hi(uint32_t w) { return __uint_as_float(w & 0xFFFF0000u); }
DEVINL float bf_round(float x) { return bf_lo(pack2(x, 0.f)); }
DEVINL uint32_t add_bf16x2(uint32_t a, uint32_t b) { uint32_t r; asm("add.rn.bf16x2 %0, %1, %2;" : "=r"(r) : "r"(a), "r"(b)); return r; }
DEVINL void stsm4(uint32_t addr, uint32_t a, uint32_t b, uint32_t c, uint32_t d) {
  asm volatile("stmatrix.sync.aligned.m8n8.x4.shared.b16 [%0], {%1, %2, %3, %4};" ::"r"(addr), "r"(a), "r"(b), "r"(c), "r"(d) : "memory");
}
DEVINL void ldsm4(uint32_t addr, uint32_t (&r)[4]) {
  asm volatile("ldmatrix.sync.aligned.m8n8.x4.shared.b16 {%0, %1, %2, %3}, [%4];" : "=r"(r[0]), "=r"(r[1]), "=r"(r[2]), "=r"(r[3]) : "r"(addr) : "memory");
}
DEVINL void ldsm4t(uint32_t addr, uint32_t (&r)[4]) {
  asm volatile("ldmatrix.sync.aligned.m8n8.x4.trans.shared.b16 {%0, %1, %2, %3}, [%4];" : "=r"(r[0]), "=r"(r[1]), "=r"(r[2]), "=r"(r[3]) : "r"(addr) : "memory");
}
DEVINL void sts128(uint32_t addr, uint32_t a, uint32_t b, uint32_t c, uint32_t d) {
  asm volatile("st.shared.v4.b32 [%0], {%1, %2, %3, %4};" ::"r"(addr), "r"(a), "r"(b), "r"(c), "r"(d) : "memory");
}
DEVINL float2 lds64f(uint32_t addr) { float2 v; asm volatile("ld.shared.v2.f32 {%0, %1}, [%2];" : "=f"(v.x), "=f"(v.y) : "r"(addr) : "memory"); return v; }
DEVINL void mma16816(float (&d)[4], uint32_t a0, uint32_t a1, uint32_t a2, uint32_t a3, uint32_t b0, uint32_t b1) {
  asm("mma.sync.aligned.m16n8k16.row.col.f32.bf16.bf16.f32 {%0, %1, %2, %3}, {%4, %5, %6, %7}, {%8, %9}, {%0, %1, %2, %3};"
               : "+f"(d[0]), "+f"(d[1]), "+f"(d[2]), "+f"(d[3]) : "r"(a0), "r"(a1), "r"(a2), "r"(a3), "r"(b0), "r"(b1));
}
template <int N> DEVINL void fence_regs(float (&d)[N]) {
#pragma unroll
  for (int i = 0; i < N; i++) asm volatile("" : "+f"(d[i])::"memory");
}
template <int N> DEVINL void fence_regs(uint32_t (&d)[N]) {
#pragma unroll
  for (int i = 0; i < N; i++) asm volatile("" : "+r"(d[i])::"memory");
}
DEVINL void lds128(uint32_t addr, uint32_t* r) {
  asm volatile("ld.shared.v4.b32 {%0, %1, %2, %3}, [%4];" : "=r"(r[0]), "=r"(r[1]), "=r"(r[2]), "=r"(r[3]) : "r"(addr) : "memory");
}
DEVINL void sched_fence() { asm volatile("griddepcontrol.launch_dependents;" ::: "memory"); }

struct Scratch {
  bf16 k[32 * 2048 * 32];
  bf16 xs[2048 * 1024];
  bf16 os[2048 * 1024];
  bf16 v[32 * 2048 * 32];
  float kn[2 * 128 * 16];
  uint32_t cnt[256 * 32];
  float2 stats[8 * 2048];
  uint4 halo[2 * 128 * 12 * 32];
  float csp[2 * 16 * 8 * 192];
  uint4 qsave[128 * 256 * 8];
  uint32_t esc[4 * 65536 * 16];
};
__device__ __align__(1024) Scratch g_s;
#define g_k g_s.k
#define g_xs g_s.xs
#define g_os g_s.os
#define g_v g_s.v
#define g_kn g_s.kn
#define g_cnt g_s.cnt
#define g_stats g_s.stats
#define g_halo g_s.halo
#define g_csp g_s.csp
#define g_qsave g_s.qsave
#define g_esc g_s.esc
#define g_epoch g_s.cnt[255 * 32]

DEVINL uint32_t* cnt_x(int l, int bm) { return g_cnt + (l * 8 + bm) * 32; }
DEVINL uint32_t* cnt_o(int l, int pm, int h) { return g_cnt + (32 + (l * 16 + pm) * 2 + h) * 32; }
DEVINL uint32_t* cnt_kv(int lb, int bn) { return g_cnt + (160 + lb * 16 + bn) * 32; }
DEVINL uint32_t* cnt_ad(int bn) { return g_cnt + (192 + bn) * 32; }
DEVINL uint32_t* cnt_cs(int t, int bn) { return g_cnt + (208 + t * 16 + bn) * 32; }

DEVINL int qord(int i, int l, int pn) { return l == 0 ? i : i < 4 ? ((2 * pn) ^ (i & 2)) + (i & 1) : i - 4 < 2 * (pn & 6) ? i - 4 : i; }
struct Params {
  CUtensorMap m[15];
  const bf16* x0;
  const bf16* wq[2];
  uint32_t zero;
  int map[128];
  uint64_t wd, xd;
  struct { uint64_t kd, vd; } kv[17];
};
enum { M_X0A = 0, M_XSA, M_WQA, M_WQB, M_WOA, M_WOB, M_OS, M_K, M_V, M_X0R, M_XSR, M_XSO, M_OUT, M_XST, M_X0H, M_COUNT };

constexpr uint32_t QSTG = 57344;
constexpr uint32_t T0 = 65536, TSTG = 32768;
constexpr uint32_t ONES = 230400;
constexpr uint32_t PSTG = 32768, RES = 196608;
constexpr uint32_t KSC = 98304, VSC = 133120, HRS = 167936;
constexpr uint32_t ROWST = 229376, COLS = 231424, BARS = 232192, SMEM_BYTES = 232448;
constexpr uint32_t B_QF = BARS, B_QE = BARS + 32, B_TF = BARS + 64, B_TE = BARS + 96, B_PF = BARS + 128, B_PE = BARS + 176,
                   B_RF = BARS + 224, W_X = BARS + 232, W_O = BARS + 236, B_QL = BARS + 240, B_PA = BARS + 248;
enum { NB_ST = 1, NB_KV = 2  , NB_DONE = 3, NB_SC = 4, NB_SIG = 5  , NB_KN = 9  , NB_X = 11, NB_HALO = 12  , NB_X0 = 15 };

DEVINL uint32_t pslot_b(uint32_t s) { return ((0x320415u >> (4 * s)) & 7) * 16384u; }
DEVINL uint32_t pslot_a(uint32_t s, int l) { return 98304u + ((((l & 1) ? 0x541230u : 0x041235u) >> (4 * s)) & 7) * 16384u; }

constexpr float QSCALE = 0.17677669529663687f * 1.4426950408889634f;
constexpr uint32_t QPARK = 32768;

DEVINL uint32_t exp2_h2(uint32_t s, uint32_t c882) {
  uint32_t r, t, w, m, d;
  asm volatile("{.reg .b64 t; add.rn.f16x2 %0, %1, %2; cvt.u64.u32 t, %0; cvt.u32.u64 %0, t;}" : "=r"(r) : "r"(s), "r"(0x65F565F5u));
  asm volatile("fma.rn.f16x2 %0, %1, %2, %3;" : "=r"(t) : "r"(r), "r"(0xB8A0B8A0u), "r"(c882));
  asm volatile("fma.rn.f16x2 %0, %1, %2, %3;" : "=r"(w) : "r"(s), "r"(0x38A038A0u), "r"(t));
  asm volatile("fma.rn.f16x2 %0, %1, %1, %2;" : "=r"(m) : "r"(w), "r"(0x48244833u));
  asm volatile("{.reg .b32 t; shf.l.clamp.b32 t, %2, %1, 7; add.u32 %0, t, %2;}" : "=r"(d) : "r"(r), "r"(m));
  return d;
}
DEVINL float exp2_fix(float s) { float z; asm volatile("add.rn.f32 %0, %1, 0f43BF34BC;" : "=f"(z) : "f"(s)); return z; }
DEVINL uint32_t exp2_base(float z0, float z1) { uint32_t B; asm volatile("prmt.b32 %0, %1, %2, 0x6521;" : "=r"(B) : "r"(__float_as_uint(z0)), "r"(__float_as_uint(z1))); return B; }
template <uint32_t MASK> DEVINL uint32_t and_or(uint32_t a, uint32_t c) { uint32_t r; asm volatile("lop3.b32 %0, %1, %3, %2, 0xEA;" : "=r"(r) : "r"(a), "r"(c), "n"(MASK)); return r; }
DEVINL uint32_t fma_bf2(uint32_t a, uint32_t b, uint32_t c) { uint32_t r; asm volatile("fma.rn.bf16x2 %0, %1, %2, %3;" : "=r"(r) : "r"(a), "r"(b), "r"(c)); return r; }
DEVINL float ex2v(float x) { float y; asm volatile("ex2.approx.ftz.f32 %0, %1;" : "=f"(y) : "f"(x)); return y; }
DEVINL uint32_t pack2v(float lo, float hi) { uint32_t r; asm volatile("cvt.rn.bf16x2.f32 %0, %1, %2;" : "=r"(r) : "f"(hi), "f"(lo)); return r; }
DEVINL uint32_t unesc(uint32_t u, const uint32_t* esc) {
  if ((u & 0x7C00u) == 0x7C00u || (u & 0x7C000000u) == 0x7C000000u) return __ldcg(esc);
  float lo, hi;
  asm("{.reg .f16 a, b; mov.b32 {a, b}, %2; cvt.f32.f16 %0, a; cvt.f32.f16 %1, b;}" : "=f"(lo), "=f"(hi) : "r"(u));
  return pack2(lo, hi);
}

DEVINL void attn_slow(const uint32_t (&q)[8], int head, const uint32_t* kesc, float (&res)[20], int lane) {
  const int g = lane >> 2, qd = lane & 3;
  const bf16* kb = g_k + (size_t)head * 2048 * 32;
  const bf16* vb = g_v + (size_t)head * 2048 * 32;
  float o[4][4], m0 = -INFINITY, m1 = -INFINITY, l0 = 0.f, l1 = 0.f;
#pragma unroll
  for (int j = 0; j < 4; j++) { o[j][0] = o[j][1] = o[j][2] = o[j][3] = 0.f; }
#pragma unroll 1
  for (int k0 = 0; k0 < 2048; k0 += 16) {
    float s[2][4];
#pragma unroll
    for (int nt = 0; nt < 2; nt++) {
      s[nt][0] = s[nt][1] = s[nt][2] = s[nt][3] = 0.f;
      const uint32_t* kp = (const uint32_t*)(kb + (size_t)(k0 + nt * 8 + g) * 32) + qd;
      const uint32_t* ke = kesc + (k0 + nt * 8 + g) * 16 + qd;
      const uint32_t k0r = unesc(__ldcg(kp), ke), k1r = unesc(__ldcg(kp + 4), ke + 4), k2r = unesc(__ldcg(kp + 8), ke + 8), k3r = unesc(__ldcg(kp + 12), ke + 12);
      __syncwarp();
      mma16816(s[nt], q[0], q[1], q[2], q[3], k0r, k1r);
      mma16816(s[nt], q[4], q[5], q[6], q[7], k2r, k3r);
    }
    float a0 = fmaxf(fmaxf(s[0][0], s[0][1]), fmaxf(s[1][0], s[1][1]));
    float a1 = fmaxf(fmaxf(s[0][2], s[0][3]), fmaxf(s[1][2], s[1][3]));
    a0 = fmaxf(a0, __shfl_xor_sync(~0u, a0, 1)); a0 = fmaxf(a0, __shfl_xor_sync(~0u, a0, 2));
    a1 = fmaxf(a1, __shfl_xor_sync(~0u, a1, 1)); a1 = fmaxf(a1, __shfl_xor_sync(~0u, a1, 2));
    const float n0 = fmaxf(m0, a0), n1 = fmaxf(m1, a1);
    const float c0 = (m0 == n0) ? 1.f : ex2(m0 - n0), c1 = (m1 == n1) ? 1.f : ex2(m1 - n1);
    m0 = n0; m1 = n1;
    const uint32_t p0 = pack2(ex2(s[0][0] - n0), ex2(s[0][1] - n0)), p1 = pack2(ex2(s[0][2] - n1), ex2(s[0][3] - n1));
    const uint32_t p2 = pack2(ex2(s[1][0] - n0), ex2(s[1][1] - n0)), p3 = pack2(ex2(s[1][2] - n1), ex2(s[1][3] - n1));
    l0 = l0 * c0 + bf_lo(p0) + bf_hi(p0) + bf_lo(p2) + bf_hi(p2);
    l1 = l1 * c1 + bf_lo(p1) + bf_hi(p1) + bf_lo(p3) + bf_hi(p3);
#pragma unroll
    for (int j = 0; j < 4; j++) {
      o[j][0] *= c0; o[j][1] *= c0; o[j][2] *= c1; o[j][3] *= c1;
      const unsigned short* vp = (const unsigned short*)(vb + (size_t)(k0 + 2 * qd) * 32 + j * 8 + g);
      const uint32_t b0 = (uint32_t)__ldcg(vp) | ((uint32_t)__ldcg(vp + 32) << 16);
      const uint32_t b1 = (uint32_t)__ldcg(vp + 256) | ((uint32_t)__ldcg(vp + 288) << 16);
      mma16816(o[j], p0, p1, p2, p3, b0, b1);
    }
  }
  l0 += __shfl_xor_sync(~0u, l0, 1); l0 += __shfl_xor_sync(~0u, l0, 2);
  l1 += __shfl_xor_sync(~0u, l1, 1); l1 += __shfl_xor_sync(~0u, l1, 2);
#pragma unroll
  for (int j = 0; j < 4; j++) { res[4 * j] = o[j][0]; res[4 * j + 1] = o[j][1]; res[4 * j + 2] = o[j][2]; res[4 * j + 3] = o[j][3]; }
  res[16] = l0; res[18] = l1;
}

__device__ __noinline__ void attn_redo(int redo, int l, int b, int wg, int w) {
  const int lane = lane_id();
#pragma unroll 1
  for (int t = 0; t < 4; t++) {
    const int h = t >> 1, head = 2 * (b & 15) + h, row = (b >> 4) * 256 + wg * 128 + (t & 1) * 64 + w * 16 + (lane >> 2);
    if ((redo >> t) & 1) {
      const uint32_t* esc = g_esc + (size_t)((l & 2) * 65536 + head * 2048) * 16;
      const uint32_t* qs = (const uint32_t*)(g_qsave + (block_id() * 256 + wg * 128 + w * 32 + lane) * 8 + 2 * t);
      uint32_t q[8]; float o[20];
#pragma unroll
      for (int i = 0; i < 8; i++) q[i] = unesc(__ldcg(qs + i), esc + (row + (i & 1) * 8) * 16 + (i >> 1) * 4 + (lane & 3));
      __syncwarp();
      attn_slow(q, head, esc + 65536 * 16, o, lane);
      const float i0 = rcp(o[16]), i1 = rcp(o[18]);
      bf16* op = g_os + (size_t)row * 1024 + h * 512 + (b & 15) * 32 + (lane & 3) * 8;
      *(uint4*)op = make_uint4(pack2(o[0] * i0, o[1] * i0), pack2(o[4] * i0, o[5] * i0), pack2(o[8] * i0, o[9] * i0), pack2(o[12] * i0, o[13] * i0));
      *(uint4*)(op + 8 * 1024) = make_uint4(pack2(o[2] * i1, o[3] * i1), pack2(o[6] * i1, o[7] * i1), pack2(o[10] * i1, o[11] * i1), pack2(o[14] * i1, o[15] * i1));
    }
    if ((t & 1) && ((redo >> 2 * h) & 3)) bar_arrive(NB_SIG + 2 * h + wg, 160);
  }
}

__global__ void __cluster_dims__(2, 1, 1) __launch_bounds__(384, 1) fused_kernel(const __grid_constant__ Params prm) {
  extern __shared__ __align__(1024) char smem[];
  const uint32_t sb = (uint32_t)__cvta_generic_to_shared(smem);
  const int tid = threadIdx.x, lane = tid & 31;
  const int wg = __shfl_sync(0xffffffffu, tid >> 7, 0);
  const int w = __shfl_sync(0xffffffffu, (tid >> 5) & 3, 0);
  const int bm = remap(blockIdx.x) >> 4, bn = remap(blockIdx.x) & 15;

  auto first_tile = [&](int kt) {
    e_expect_tx(sb + B_QF + 8 * kt, QSTG);
    tma_ld(sb + kt * QSTG, &prm.m[M_X0A], kt * 64, bm * 256, sb + B_QF + 8 * kt);
    tma_ld3(sb + kt * QSTG + 32768, &prm.m[M_WQA], bn * 64, kt * 64, 0, sb + B_QF + 8 * kt);
  };
  auto init4 = [&](uint32_t bar, uint32_t c0, uint32_t c1, uint32_t c2, uint32_t c3) {
    asm volatile("{\n.reg .pred pe;\nelect.sync _|pe, 0xffffffff;\n@pe mbarrier.init.shared::cta.b64 [%0], %1;\n@pe mbarrier.init.shared::cta.b64 [%0+8], %2;\n"
                 "@pe mbarrier.init.shared::cta.b64 [%0+16], %3;\n@pe mbarrier.init.shared::cta.b64 [%0+24], %4;\n@pe fence.mbarrier_init.release.cluster;\n}"
                 ::"r"(bar), "r"(c0), "r"(c1), "r"(c2), "r"(c3) : "memory");
  };
  if (wg < 2) {
    const uint32_t k = wg * 4 + w, lo = (0x1411814u >> (4 * k)) & 15, hi = (0x1441814u >> (4 * k)) & 15;
    if (tid < 32) asm volatile("prefetch.global.L2 [%0];" ::"l"(prm.x0 + (size_t)(bm * 256 + bn * 16 + (tid & 15)) * 1024 + (tid >> 4) * 64));
    else if (tid < 80) asm volatile("prefetch.global.L2 [%0];" ::"l"(prm.wq[0] + (bm * 16 + (tid & 15)) * 3072 + ((tid >> 4) - 2) * 1024 + bn * 64));
    __syncwarp();
    if (k < 7) init4(sb + B_QE + 32 * k, lo, lo, hi, k == 6 ? 2 : hi);
    __syncwarp();
    if (k == 6 && lane == 0) *(volatile unsigned long long*)(smem + W_X) = 0ull;
  } else if (w == 0) {
    init4(sb + B_QF, 1, 1, 1, 1);
    __syncwarp();
    first_tile(0);
  }
  __syncthreads();
  asm volatile("barrier.cluster.arrive.relaxed.aligned;" ::: "memory");

  if (wg == 2) {
    asm volatile("setmaxnreg.dec.sync.aligned.u32 56;");
    const uint32_t ep1 = *(volatile uint32_t*)&g_epoch + 1;
    if (w == 0) {
      first_tile(1);
      mbar_wait(sb + B_QF, 0);
      first_tile(2); first_tile(3);
#pragma unroll 1
      for (int kt = 4; kt < 16; kt++) l2_prefetch(prm.wq[0] + kt * 196608 + blockIdx.x * 1536, 3072);
      cluster_wait();
#pragma unroll 1
      for (int l = 0; l < 4; l++) {
        IDS();
        const CUtensorMap* mw = &prm.m[M_WQA + (l & 1)];
        const CUtensorMap* mx = &prm.m[l == 0 ? M_X0A : M_XSA];
        const CUtensorMap* mh = &prm.m[l == 0 ? M_X0H : M_XSO];
        const CUtensorMap* mo = &prm.m[M_WOA + (l & 1)];
        auto q_b = [&](int i) {
          const int s = i & 3;
          mbar_wait(sb + B_QE + 8 * s, ((i >> 2) & 1) ^ 1);
          e_expect_tx(sb + B_QF + 8 * s, QSTG);
          tma_ld3(sb + s * QSTG + 32768, mw, bn * 64, qord(i, l, pn) * 64, 0, sb + B_QF + 8 * s);
        };
        uint32_t rdy = l ? 0u : ~0u;
        auto q_a = [&](int i) {
          const int kt = qord(i, l, pn);
          await_bit(sb + W_X, l, kt >> 1, rdy);
          if (i < 4) tma_ld(sb + i * QSTG, mx, kt * 64, bm * 256, sb + B_QF + 8 * i);
          else tma_ld_mc(sb + (i & 3) * QSTG + rank * 16384, mh, kt * 64, bm * 256 + rank * 128, sb + B_QF + 8 * (i & 3));
        };
        if (l > 0) {
          await_bit(sb + W_X, l, pn, rdy);
#pragma unroll 1
          for (int i = 0; i < 2; i++) {
            e_expect_tx(sb + B_QF + 8 * i, 16384);
            tma_ld(sb + i * QSTG + (po ^ 1) * 16384, &prm.m[M_XSO], (2 * pn + i) * 64, (pm ^ 1) * 128, sb + B_QF + 8 * i);
          }
          mbar_wait(sb + B_QF, 0);
          q_a(2);
          mbar_wait(sb + B_QF + 8, 0);
        }
#pragma unroll 1
        for (int i = l ? 3 : 4; i < 16; i++) {
          if (l == 3 && i == 12) poll_ge(cnt_ad(bn), ep1 * 16);
          q_b(i); q_a(i);
        }
        if (l & 1) {
          bar_sync(NB_KV, 288);
          sts128(sb + ONES + lane * 32, 0x3f803f80u, 0x3f803f80u, 0x3f803f80u, 0x3f803f80u);
          sts128(sb + ONES + lane * 32 + 16, 0x3f803f80u, 0x3f803f80u, 0x3f803f80u, 0x3f803f80u);
          fence_async_smem();
          __syncwarp();
          e_arrive(sb + B_TF);
          const int krow = 2 * bn * 2048 + bm * 256;
          uint32_t* kvc = cnt_kv(l >> 1, bn);
          uint32_t seen = 0;
#pragma unroll 1
          for (int it = 1; it < 16; it++) {
            const int s = it & 3;
            if (it == 4) {
              bar_sync(NB_KV + 12, 288);
              mbar_wait(sb + B_TF + 24, 0);
#pragma unroll 1
              for (int i = 0; i < 4; i++) tma_st(&prm.m[M_K + (i >> 1)], 0, krow + 2048 + (i & 1) * 128, sb + i * 8192);
              bulk_commit();
            }
            if (it == 5) { bulk_wait_n<0>(); e_red(kvc + 16 + bm); }
            if (it == 12) { e_expect_tx(sb + B_RF, 32768); tma_ld3(sb + RES, &prm.m[M_XSR], 0, pm * 128, 2 * pn, sb + B_RF); }
            mbar_wait(sb + B_TE + 8 * s, ((it >> 2) & 1) ^ 1);
            if (it < 8) {
#pragma unroll 1
              for (uint32_t n = 0; n < 200000u && (~seen & (3u << (2 * it - 2) | (it == 4 ? 0xC000u : 0u))); n++)
                seen = __ballot_sync(~0u, (int)(ld_acquire(kvc + (lane < 7 || lane == 15 ? (bm + 1 + lane) & 7 : 8 + ((bm + 2 + lane) & 7))) - ep1) >= 0);
              fence_async_gl();
            } else if (it == 8) { poll_ge(kvc + 16 + (lane & 7), ep1); fence_async_gl(); }
            e_expect_tx(sb + B_TF + 8 * s, 32768);
#pragma unroll 1
            for (int i = 0; i < 2; i++) {
              const int u = 2 * it - 2 + i;
              const int row = 2 * bn * 2048 + (it > 7 ? 2048 + ((bm + it) & 7) * 256 + i * 128 : u < 7 ? ((bm + 1 + u) & 7) * 256 : ((bm + 2 + u) & 7) * 256 + 128);
              tma_ld(sb + T0 + s * TSTG + i * 8192, &prm.m[M_K], 0, row, sb + B_TF + 8 * s);
              tma_ld(sb + T0 + s * TSTG + 16384 + i * 8192, &prm.m[M_V], 0, row, sb + B_TF + 8 * s);
            }
          }
        }
        auto p_b = [&](int i, uint32_t s, uint32_t par) {
          mbar_wait(sb + B_PE + 8 * s, par ^ 1);
          e_expect_tx(sb + B_PF + 8 * s, PSTG);
          tma_ld5(sb + pslot_b(s), mo, i >> 3, 2 * (i & 7), 2 * pn, sb + B_PF + 8 * s);
        };
        auto p_a = [&](int i, uint32_t s) {
          await_bit(sb + W_O, l + 1, i, rdy);
          tma_ld_mc(sb + pslot_a(s, l) + rank * 8192, &prm.m[M_OS], i * 64, pm * 128 + rank * 64, sb + B_PF + 8 * s);
        };
        auto p_a2 = [&](int i) {
          await_bit(sb + W_O, l + 1, i, rdy);
          tma_ld(sb + pslot_a(i, l), &prm.m[M_OS], i * 64, pm * 128, sb + B_PF + 8 * i);
          tma_ld(sb + pslot_a(i, l) + 8192, &prm.m[M_OS], i * 64, pm * 128 + 64, sb + B_PF + 8 * i);
        };
        rdy = 0;
        if (l & 1) {
#pragma unroll 1
          for (int u = 0; u < 6; u++) { const int i = (0x205413 >> (4 * u)) & 7; if (u == 4) mbar_wait(sb + B_TE, 1); p_b(i, i, i < 4 ? 1 : 0); }
#pragma unroll 1
          for (int u = 0; u < 6; u++) {
            const int i = (0x542130 >> (4 * u)) & 7;
            if (!(u & 1)) mbar_wait(sb + B_TE + 8 + 4 * u, 1);
            if (u == 4) bar_sync(NB_ST, 64);
            p_a2(i);
          }
        } else {
#pragma unroll 1
          for (int u = 0; u < 6; u++) { const int i = (0x025413 >> (4 * u)) & 7; if (u == 0 || u == 3) mbar_wait(sb + B_QE + 8 * (u / 3), 1); p_b(i, i, 0); }
          mbar_wait(sb + B_QE + 24, 1);
          e_expect_tx(sb + B_RF, 32768);
          tma_ld3(sb + RES, &prm.m[l == 0 ? M_X0R : M_XSR], 0, pm * 128, 2 * pn, sb + B_RF);
          p_a2(0);
          bar_sync(NB_DONE, 64);
          e_arrive_both(sb + B_PA);
          p_a2(1);
          mbar_wait(sb + B_PA, (l >> 1) & 1);
#pragma unroll 1
          for (int i = 2; i < 6; i++) { if (i > 2) mbar_wait(sb + B_PF + 8 * (i - 3), 0); p_a(i, i); }
        }
        uint32_t s = 0, lap = 1;
#pragma unroll 1
        for (int i = 6; i < 16; i++) {
          p_b(i, s, ((s < 4 ? l : 0) + lap) & 1);
          p_a(i, s);
          if (++s == 6) { s = 0; lap++; }
        }
        const CUtensorMap* mn = &prm.m[M_WQA + ((l + 1) & 1)];
        if (l < 3) {
          mbar_wait(sb + B_PE + 8 * 4, 1); mbar_wait(sb + B_PE + 8 * 5, 1);
          tma_ld3(sb + 32768, mn, bn * 64, 2 * pn * 64, 0, sb + B_QL);
          mbar_wait(sb + B_PE + 8 * 0, l & 1);
          tma_ld3(sb + QSTG + 32768, mn, bn * 64, (2 * pn + 1) * 64, 0, sb + B_QL);
          mbar_wait(sb + B_PE + 8 * 1, l & 1);
          e_expect_tx(sb + B_QF + 16, QSTG);
          tma_ld3(sb + 2 * QSTG + 32768, mn, bn * 64, ((2 * pn) ^ 2) * 64, 0, sb + B_QF + 16);
        }
        if (l < 3) { bar_sync(NB_X, 288); e_expect_tx(sb + B_QL, 49152); }
      }
      if (blockIdx.x == 0 && lane_id() == 0) *(volatile uint32_t*)&g_epoch = ep1;
    } else {
      const int hw = w - 1;
      if (lane < 5) asm volatile("prefetch.tensormap [%0];" ::"l"(&prm.m[5 * hw + lane]) : "memory");
      __syncwarp();
      cluster_wait();
      mbar_wait(sb + B_QF, 0);
#pragma unroll 1
      for (int l = 0; l < 4; l++) {
        IDS();
        if (hw == 2 && l > 0) watch(cnt_x(l, bm) + (lane & 7), ep1 * 2, 0xFFu, l, sb + W_X);
        if (l == 0) {
#pragma unroll 1
          for (int r = 2 * hw; r < 16; r += 6) {
            const uint4* p = (const uint4*)(prm.x0 + (size_t)(b * 16 + r) * 1024) + lane;
            float s1[2] = {0.f, 0.f}, s2[2] = {0.f, 0.f};
#pragma unroll
            for (int i = 0; i < 8; i++) {
              const uint4 v = __ldg(p + 32 * i);
              const uint32_t u[4] = {v.x, v.y, v.z, v.w};
#pragma unroll
              for (int k = 0; k < 4; k++) { const float a = bf_lo(u[k]), c = bf_hi(u[k]); s1[i >> 2] += a + c; s2[i >> 2] = fmaf(a, a, fmaf(c, c, s2[i >> 2])); }
            }
#pragma unroll
            for (int o = 16; o; o >>= 1)
#pragma unroll
              for (int rr = 0; rr < 2; rr++) { s1[rr] += __shfl_xor_sync(~0u, s1[rr], o); s2[rr] += __shfl_xor_sync(~0u, s2[rr], o); }
            if (lane == 0) *(float4*)&g_stats[b * 16 + r] = make_float4(s1[0], s2[0], s1[1], s2[1]);
          }
        }
        if (l == 1) { uint32_t rdy = 0; await_bit<true>(sb + W_X, 1, pn, rdy); mbar_hint(sb + B_QF + 8, 0); }
        if (l < 2) {
          float cs[8];
#pragma unroll
          for (int i = 0; i < 8; i++) cs[i] = 0.f;
          const uint4* wp = (const uint4*)(prm.wq[l] + (size_t)(bm * 128 + (lane >> 3)) * 3072 + hw * 1024 + bn * 64) + (lane & 7);
#pragma unroll 8
          for (int i = 0; i < 32; i++) {
            const uint4 v = __ldg(wp + (size_t)i * 4 * 384);
            cs[0] += bf_lo(v.x); cs[1] += bf_hi(v.x); cs[2] += bf_lo(v.y); cs[3] += bf_hi(v.y);
            cs[4] += bf_lo(v.z); cs[5] += bf_hi(v.z); cs[6] += bf_lo(v.w); cs[7] += bf_hi(v.w);
          }
#pragma unroll
          for (int i = 0; i < 8; i++) { cs[i] += __shfl_xor_sync(~0u, cs[i], 8); cs[i] += __shfl_xor_sync(~0u, cs[i], 16); }
          if (lane < 8) {
            float4* d = (float4*)(g_csp + ((l * 16 + bn) * 8 + bm) * 192 + hw * 64 + lane * 8);
            d[0] = make_float4(cs[0], cs[1], cs[2], cs[3]); d[1] = make_float4(cs[4], cs[5], cs[6], cs[7]);
          }
          __syncwarp();
          asm volatile("fence.acq_rel.gpu;" ::: "memory");
          e_red_relaxed(cnt_cs(l, bn));
          if (l == 0) e_red_relaxed(cnt_x(0, bm) + pn);
          poll_ge(lane < 8 && l == 0 ? cnt_x(0, bm) + lane : cnt_cs(l, bn), ep1 * (lane < 8 && l == 0 ? 6 : 24));
        }
        if (l > 0) {
          uint32_t rdy = 0;
#pragma unroll 1
          for (int j = 0; j < 8; j++) await_bit<true>(sb + W_X, l, j, rdy);
        }
#pragma unroll 1
        for (int it = hw * 32 + lane; it < 176; it += 96) {
          const bool rows = it < 128;
          const float4* p = rows ? (const float4*)(g_stats + bm * 256) + it : (const float4*)(g_csp + ((l & 1) * 16 + bn) * 8 * 192) + (it - 128);
          const int stride = rows ? 1024 : 48, np = rows && l == 0 ? 1 : 8;
          float4 a = make_float4(0.f, 0.f, 0.f, 0.f);
#pragma unroll
          for (int k = 0; k < 8; k++) if (k < np) { const float4 v = __ldcg(p + k * stride); a.x += v.x; a.y += v.y; a.z += v.z; a.w += v.w; }
          if (rows) {
            const float m0 = a.x * (1.f / 1024.f), m1 = a.z * (1.f / 1024.f);
            const float v0 = fmaxf(a.y * (1.f / 1024.f) - m0 * m0, 0.f), v1 = fmaxf(a.w * (1.f / 1024.f) - m1 * m1, 0.f);
            const float r0 = __fdividef(1.f, bf_round(sqrtf(bf_round(bf_round(v0) + 1e-5f)))), r1 = __fdividef(1.f, bf_round(sqrtf(bf_round(bf_round(v1) + 1e-5f))));
            a = make_float4(r0, -bf_round(m0) * (l & 1 ? r0 : 1.f), r1, -bf_round(m1) * (l & 1 ? r1 : 1.f));
          }
          *(float4*)(smem + ROWST + it * 16) = a;
        }
        __syncwarp();
        if (lane == 0) asm volatile("red.release.cta.shared.add.u32 [%0], 0x100;" ::"r"(sb + W_X) : "memory");
        if (hw == 2) {
          if (!(l & 1)) {
            bar_sync(NB_ST, 288);
            const uint4* hp = g_halo + ((l >> 1) * 128 + b - 16) * 384 + lane;
#pragma unroll 1
            for (int h = 0; h < 2; h++) {
              uint32_t t[18];
#pragma unroll
              for (int i = 0; i < 18; i++) t[i] = 0;
#pragma unroll 1
              for (uint32_t n = bm ? 0 : 100000u; n < 100000u; n++) {
                uint32_t miss = 0;
#pragma unroll
                for (int i = 0; i < 6; i++) miss |= ld_tagged(hp + h * 192 + i * 32, &t[3 * i]) ^ ep1;
                if (__all_sync(~0u, !miss)) break;
              }
              mbar_wait(sb + B_QE + 16, 1);
              const uint32_t r = (lane & 7) + ((lane >> 3) & 1) * 8, rv = lane >> 2;
#pragma unroll
              for (int jj = 0; jj < 2; jj++) stsm4(sb + KSC + r * 128 + (((4 * h + 2 * jj + (lane >> 4)) ^ (r & 7)) << 4), t[4 * jj], t[4 * jj + 1], t[4 * jj + 2], t[4 * jj + 3]);
              const uint32_t ad = sb + VSC + rv * 128 + (((4 * h + (lane & 3)) ^ (rv & 7)) << 4);
              sts128(ad, t[8], t[10], t[12], t[14]); sts128(ad + 1024, t[9], t[11], t[13], t[15]);
              if (h == 0 && !(lane & 2)) *(uint32_t*)(smem + HRS + ((lane >> 2) + 8 * (lane & 1)) * 8) = t[16];
              bar_arrive(NB_HALO + h, 64);
            }
          } else {
            mbar_wait(sb + B_TF + 16, 0); mbar_wait(sb + B_TF + 16, 1);
            poll_ge(cnt_kv(l >> 1, bn) + 16 + (lane & 7), ep1);
            const uint4 v = __ldcg((const uint4*)(g_kn + ((l >> 1) * 128 + bn * 8) * 16) + lane);
            const uint32_t mx = max(max(v.x, v.y), max(v.z, v.w));
            const uint32_t m0 = __reduce_max_sync(~0u, (lane & 2) ? 0u : mx), m1 = __reduce_max_sync(~0u, (lane & 2) ? mx : 0u);
            if (lane == 0) *(uint2*)(smem + ROWST) = make_uint2(m0, m1);
            __syncwarp();
            bar_arrive(NB_KN, 160); bar_arrive(NB_KN + 1, 160);
            mbar_wait(sb + B_TF + 16, 0); mbar_wait(sb + B_TF + 16, 1);
          }
        } else {
          if (l & 1) {
            bar_sync(hw ? NB_HALO : NB_DONE, 160);
            tma_st(&prm.m[M_K], 0, 2 * bn * 2048 + bm * 256 + hw * 128, sb + T0 + hw * 8192);
            tma_st(&prm.m[M_V], 0, 2 * bn * 2048 + bm * 256 + hw * 128, sb + T0 + 16384 + hw * 8192);
            bulk_commit(); bulk_wait_n<0>();
            e_red(cnt_kv(l >> 1, bn) + 8 * hw + bm);
          }
#pragma unroll 1
          for (int i = 0; i < 2; i++) {
            const int h = l & 1 ? i : hw, g = l & 1 ? hw : i;
            bar_sync(NB_SIG + 2 * h + g, 160);
            if (!(l & 1) && i == 0) continue;
            if (i == 1 && hw == 1) bar_arrive(l & 1 ? NB_ST : NB_DONE, 64);
            asm volatile("fence.acq_rel.gpu;" ::: "memory");
            e_red_relaxed(cnt_o(l, 2 * bm + g, h) + (bn >> 1));
            if (!(l & 1)) e_red_relaxed(cnt_o(l, 2 * bm, h) + (bn >> 1));
            if (h == 1 && l == 1) e_red_relaxed(cnt_ad(bn));
          }
        }
        if (hw == 2) watch(cnt_o(l, pm, (lane >> 3) & 1) + (lane & 7), ep1 * 2, 0xFFFFu, l + 1, sb + W_O);
        if (hw == 0 && l < 3) {
          bar_sync(NB_X0, 288);
          e_red(cnt_x(l + 1, bm) + pn);
        }
      }
    }
  } else {
    asm volatile("setmaxnreg.inc.sync.aligned.u32 224;");
    const uint32_t zero = prm.zero;
    cluster_wait();
#pragma unroll 1
    for (int l = 0; l < 4; l++) {
      {
        float acc[2][96];
#pragma unroll
        for (int i = 0; i < 96; i++) { acc[0][i] = 0.f; acc[1][i] = 0.f; }
        fence_regs(acc[0]); fence_regs(acc[1]);
        const bool early = l > 0 && wg == ((cta_id() >> 3) & 1);
        uint32_t ep1 = 0;
#pragma unroll 1
        for (int kt = 0; kt < 14; kt++) {
          const int s = kt & 3;
          if (l > 0 && kt == 0) mbar_wait(sb + B_QL, (l + 1) & 1);
          if (!(early && kt < 2)) mbar_wait(sb + B_QF + 8 * s, (kt >> 2) & 1);
          const uint64_t da = prm.xd + wg * 1024 + s * (QSTG >> 4), db = prm.wd + s * (QSTG >> 4);
          wg_fence();
#pragma unroll
          for (int k = 0; k < 4; k++)
#pragma unroll
            for (int m = 0; m < 2; m++) wgmma_m64n192k16_ss_tb(acc[m], da + m * 512 + k * 2, db + k * 128, 1);
          wg_commit();
          if (kt == 4) ep1 = *(volatile uint32_t*)&g_epoch + 1;
          wg_wait<1>();
          if (early && (kt == 1 || kt == 2)) mbar_wait(sb + B_QF + 8 * (kt - 1), 0);
          if (kt > 0 && w == 0) e_arrive_both(sb + B_QE + 8 * ((kt - 1) & 3));
        }
        {
          const bool lag = (l & 1) && wg;
          const uint64_t da = prm.xd + wg * 1024 + 2 * (QSTG >> 4), db = prm.wd + 2 * (QSTG >> 4);
          mbar_wait(sb + B_QF + 16, 1);
          if (lag) {
            mbar_wait(sb + B_QF + 24, 1);
            wg_wait<0>();
            if (w == 0) e_arrive_both(sb + B_QE + 8);
            bar_sync(NB_SC, 256);
          }
          wg_fence();
#pragma unroll
          for (int k = 0; k < 4; k++)
#pragma unroll
            for (int m = 0; m < 2; m++) wgmma_m64n192k16_ss_tb(acc[m], da + m * 512 + k * 2, db + k * 128, 1);
          wg_commit();
          if (!lag) {
            wg_wait<1>();
            if (w == 0) e_arrive_both(sb + B_QE + 8);
            mbar_wait(sb + B_QF + 24, 1);
          }
          wg_fence();
#pragma unroll
          for (int m = 1; m >= 0; m--) {
#pragma unroll
            for (int k = 0; k < 4; k++) wgmma_m64n192k16_ss_tb(acc[m], da + (QSTG >> 4) + m * 512 + k * 2, db + (QSTG >> 4) + k * 128, 1);
            wg_commit();
          }
          if ((l & 1) && !wg) bar_arrive(NB_SC, 256);
          if (!(l & 1)) bar_arrive(NB_ST, 288);
          wg_wait<2>();
          if (w == 0) e_arrive_both(sb + B_QE + 16);
        }
#pragma unroll 1
        for (uint32_t n = 0; n < 4000000u; n++) {
          uint32_t v;
          asm volatile("ld.acquire.cta.shared.u32 %0, [%1];" : "=r"(v) : "r"(sb + W_X) : "memory");
          if ((v >> 8) == (uint32_t)(l * 256 + 3)) break;
        }
        IDS();
        const int g = lane >> 2, qd = lane & 3;
        float2 st[2][2];
#pragma unroll
        for (int m = 0; m < 2; m++)
#pragma unroll
          for (int hh = 0; hh < 2; hh++) st[m][hh] = lds64f(sb + ROWST + (wg * 128 + m * 64 + w * 16 + g + 8 * hh) * 8);
        float2 cs[4];
        auto load_cs = [&](int gi) {
#pragma unroll
          for (int j = 0; j < 4; j++) cs[j] = lds64f(sb + COLS + (gi * 32 + j * 8 + 2 * qd) * 4);
        };
        load_cs(2);
        auto drain = [&]() {
          wg_wait<0>(); fence_regs(acc[0]);
          if (w == 0) e_arrive_both(sb + B_QE + 8 * 3);
        };
        wg_wait<1>(); fence_regs(acc[1]);
        auto norm_tile = [&](int gi, int m, float sc, uint32_t (&t)[8], float (&nrm)[2], bool h16 = false) {
          const float r0 = st[m][0].x * sc, s0 = st[m][0].y * sc, r1 = st[m][1].x * sc, s1 = st[m][1].y * sc;
          float n0 = 0.f, n1 = 0.f;
#pragma unroll
          for (int j = 0; j < 4; j++) {
            const float* a = &acc[m][16 * gi + 4 * j];
            const float v0 = fmaf(a[0], r0, s0 * cs[j].x), v1 = fmaf(a[1], r0, s0 * cs[j].y);
            const float v2 = fmaf(a[2], r1, s1 * cs[j].x), v3 = fmaf(a[3], r1, s1 * cs[j].y);
            n0 = fmaf(v0, v0, fmaf(v1, v1, n0)); n1 = fmaf(v2, v2, fmaf(v3, v3, n1));
            t[2 * j] = h16 ? pack2h(v0, v1) : pack2(v0, v1); t[2 * j + 1] = h16 ? pack2h(v2, v3) : pack2(v2, v3);
          }
          nrm[0] = n0; nrm[1] = n1;
        };
        auto norm_group = [&](int gi, float sc, uint32_t (&t)[2][8], float (&nrm)[2][2]) { norm_tile(gi, 0, sc, t[0], nrm[0]); norm_tile(gi, 1, sc, t[1], nrm[1]); };
        uint32_t q[2][2][8];
        const uint32_t srow = (lane & 7) + ((lane >> 3) & 1) * 8;
        const uint32_t row0 = wg * 128 + w * 16;
        auto put_o = [&](int h, int m, const float (&o)[16], float i0, float i1) {
          IDS();
          bf16* op = g_os + (size_t)(bm * 256 + row0 + m * 64 + (lane >> 2)) * 1024 + h * 512 + bn * 32 + (lane & 3) * 8;
          *(uint4*)op = make_uint4(pack2(o[0] * i0, o[1] * i0), pack2(o[4] * i0, o[5] * i0), pack2(o[8] * i0, o[9] * i0), pack2(o[12] * i0, o[13] * i0));
          *(uint4*)(op + 8 * 1024) = make_uint4(pack2(o[2] * i1, o[3] * i1), pack2(o[6] * i1, o[7] * i1), pack2(o[10] * i1, o[11] * i1), pack2(o[14] * i1, o[15] * i1));
        };
        if (!(l & 1)) {
          auto put_kv = [&](int gi, uint32_t r0, const uint32_t (&t)[8]) {
            if (gi < 4) {
              const uint32_t r = r0 + srow;
#pragma unroll
              for (int jj = 0; jj < 2; jj++) stsm4(sb + KSC + r * 128 + (((4 * (gi - 2) + 2 * jj + (lane >> 4)) ^ (r & 7)) << 4), t[4 * jj], t[4 * jj + 1], t[4 * jj + 2], t[4 * jj + 3]);
            } else {
              const uint32_t r = r0 + g, ad = sb + VSC + r * 128 + (((4 * (gi - 4) + qd) ^ (r & 7)) << 4);
              sts128(ad, t[0], t[2], t[4], t[6]); sts128(ad + 1024, t[1], t[3], t[5], t[7]);
            }
          };
          auto cen_tile = [&](int gi, int m, uint32_t (&t)[8]) {
#pragma unroll
            for (int j = 0; j < 4; j++) {
              const float* a = &acc[m][16 * gi + 4 * j];
              t[2 * j] = pack2(fmaf(st[m][0].y, cs[j].x, a[0]), fmaf(st[m][0].y, cs[j].y, a[1]));
              t[2 * j + 1] = pack2(fmaf(st[m][1].y, cs[j].x, a[2]), fmaf(st[m][1].y, cs[j].y, a[3]));
            }
          };
          const bool send = wg == 1 && w == 3 && bm < 7;
          uint4* hp = g_halo + ((l >> 1) * 128 + b) * 384 + lane;
          mbar_wait(sb + B_QE + 16, 1);
          float2 cn[4];
          auto next_cs = [&](int gi) {
#pragma unroll
            for (int j = 0; j < 4; j++) { cs[j] = cn[j]; cn[j] = lds64f(sb + COLS + (gi * 32 + j * 8 + 2 * qd) * 4); }
          };
#pragma unroll
          for (int j = 0; j < 4; j++) cn[j] = cs[j];
#pragma unroll
          for (int h = 0; h < 2; h++) {
            uint32_t k[8], v[8];
            next_cs(4 + h);
            cen_tile(2 + h, 1, k); put_kv(2 + h, 16 + row0 + 64, k);
            next_cs(h ? 2 : 3);
            cen_tile(4 + h, 1, v); put_kv(4 + h, 16 + row0 + 64, v);
            if (send) {
              uint4* p = hp + h * 192;
              st_tagged(p, k[0], k[1], k[2], ep1); st_tagged(p + 32, k[3], k[4], k[5], ep1); st_tagged(p + 64, k[6], k[7], v[0], ep1);
              st_tagged(p + 96, v[1], v[2], v[3], ep1); st_tagged(p + 128, v[4], v[5], v[6], ep1);
              st_tagged(p + 160, v[7], __float_as_uint(qd & 1 ? st[1][1].x : st[1][0].x), 0u, ep1);
            }
            sched_fence();
          }
          drain();
          {
            uint32_t t[8];
            next_cs(4); cen_tile(2, 0, t); put_kv(2, 16 + row0, t);
            next_cs(0); cen_tile(4, 0, t); put_kv(4, 16 + row0, t);
            next_cs(3); cen_tile(0, 0, q[0][0]); cen_tile(0, 1, q[0][1]);
          }
          bar_sync(NB_SC, 256);
          const bool e = g & 1, sel = 2 * qd + (g & 1) >= g + 2, first = bm == 0 && row0 == 0;
          if (row0 == 0) bar_sync(NB_HALO, 64);
          float ra[4], rb[4], ca[4], cb[4];
#pragma unroll
          for (int m = 0; m < 2; m++) {
            float rk[3];
#pragma unroll
            for (int u = 0; u < 3; u++) {
              const int r = row0 + m * 64 + 8 * u + 2 * qd + e - (sel ? 16 : 8);
              rk[u] = lds64f(sb + (m == 0 && r < 0 ? HRS + 128 : ROWST) + r * 8).x;
            }
            ra[2 * m] = sel ? rk[1] : rk[0]; ra[2 * m + 1] = sel ? rk[2] : rk[1];
            rb[2 * m] = sel ? rk[0] : rk[1]; rb[2 * m + 1] = sel ? rk[1] : rk[2];
          }
#pragma unroll
          for (int i = 0; i < 4; i++) { const float rq = st[i >> 1][i & 1].x * QSCALE; ca[i] = rq * ra[i]; cb[i] = rq * rb[i]; }
#pragma unroll 1
          for (int h = 0; h < 2; h++) {
            float s[2][4][4];
            uint32_t vf[2][4][4], pf[2][2][4];
#pragma unroll
            for (int m = 0; m < 2; m++)
#pragma unroll
              for (int nt = 0; nt < 4; nt++) {
                uint32_t kf[4];
                const uint32_t r = row0 + m * 64 + 8 * nt + (lane & 7), ch = 4 * h + (lane >> 3);
                ldsm4(sb + KSC + r * 128 + ((ch ^ (r & 7)) << 4), kf);
                s[m][nt][0] = s[m][nt][1] = s[m][nt][2] = s[m][nt][3] = 0.f;
                mma16816(s[m][nt], q[0][m][0], q[0][m][1], q[0][m][2], q[0][m][3], kf[0], kf[1]);
                mma16816(s[m][nt], q[0][m][4], q[0][m][5], q[0][m][6], q[0][m][7], kf[2], kf[3]);
              }
#pragma unroll
            for (int m = 0; m < 2; m++)
#pragma unroll
              for (int i = 0; i < 4; i++) {
                const uint32_t r = row0 + m * 64 + 16 * (i >> 1) + srow, ch = 4 * h + 2 * (i & 1) + (lane >> 4);
                ldsm4t(sb + VSC + r * 128 + ((ch ^ (r & 7)) << 4), vf[m][i]);
              }
            float va[4], vb[4], mx[4];
#pragma unroll
            for (int i = 0; i < 4; i++) {
              const int m = i >> 1, hh = i & 1;
              const float a = e ? s[m][hh + 1][2 * hh + 1] : s[m][hh + 1][2 * hh];
              const float lo = e ? s[m][hh][2 * hh + 1] : s[m][hh][2 * hh], hi = e ? s[m][hh + 2][2 * hh + 1] : s[m][hh + 2][2 * hh];
              va[i] = (m == 0 && hh == 0 && first) ? -INFINITY : a * ca[i];
              vb[i] = (m == 0 && first && sel) ? -INFINITY : (sel ? lo : hi) * cb[i];
              mx[i] = fmaxf(va[i], vb[i]);
            }
#pragma unroll
            for (int i = 0; i < 4; i++) mx[i] = fmaxf(mx[i], __shfl_xor_sync(~0u, mx[i], 1));
#pragma unroll
            for (int i = 0; i < 4; i++) mx[i] = fmaxf(mx[i], __shfl_xor_sync(~0u, mx[i], 2));
#pragma unroll
            for (int i = 0; i < 4; i++) {
              va[i] = ex2(va[i] - mx[i]); vb[i] = ex2(vb[i] - mx[i]);
              mx[i] = va[i] + vb[i];
              va[i] *= ra[i]; vb[i] *= rb[i];
            }
#pragma unroll
            for (int i = 0; i < 4; i++) mx[i] += __shfl_xor_sync(~0u, mx[i], 1);
#pragma unroll
            for (int i = 0; i < 4; i++) mx[i] += __shfl_xor_sync(~0u, mx[i], 2);
#pragma unroll
            for (int i = 0; i < 4; i++) {
              const int m = i >> 1, hh = i & 1;
              const float inv = rcp(mx[i]);
              const uint32_t t = pack2(va[i] * inv, vb[i] * inv);
              const uint32_t pa = e ? t << 16 : t & 0xFFFFu, pb = e ? t & 0xFFFF0000u : t >> 16;
              pf[m][hh][hh + 1] = pa; pf[m][hh][hh] = sel ? pb : 0u; pf[m][hh][hh + 2] = sel ? 0u : pb; pf[m][hh][3 - 3 * hh] = 0u;
            }
#pragma unroll
            for (int m = 0; m < 2; m++) {
              float o[4][4];
#pragma unroll
              for (int j = 0; j < 4; j++) o[j][0] = o[j][1] = o[j][2] = o[j][3] = 0.f;
#pragma unroll
              for (int i = 0; i < 4; i++) {
                const int kk = i >> 1, jj = 2 * (i & 1);
                mma16816(o[jj], pf[m][0][2 * kk], pf[m][1][2 * kk], pf[m][0][2 * kk + 1], pf[m][1][2 * kk + 1], vf[m][i][0], vf[m][i][1]);
                mma16816(o[jj + 1], pf[m][0][2 * kk], pf[m][1][2 * kk], pf[m][0][2 * kk + 1], pf[m][1][2 * kk + 1], vf[m][i][2], vf[m][i][3]);
              }
              const float of[16] = {o[0][0], o[0][1], o[0][2], o[0][3], o[1][0], o[1][1], o[1][2], o[1][3], o[2][0], o[2][1], o[2][2], o[2][3], o[3][0], o[3][1], o[3][2], o[3][3]};
              put_o(h, m, of, 1.f, 1.f);
            }
            bar_arrive(NB_SIG + 2 * h + wg, 160);
            if (h == 0) {
              uint32_t t[8];
              next_cs(5); cen_tile(3, 0, t); put_kv(3, 16 + row0, t);
              next_cs(1); cen_tile(5, 0, t); put_kv(5, 16 + row0, t);
#pragma unroll
              for (int j = 0; j < 4; j++) cs[j] = cn[j];
              cen_tile(1, 0, q[0][0]); cen_tile(1, 1, q[0][1]);
              bar_sync(NB_SC, 256);
              if (row0 == 0) bar_sync(NB_HALO + 1, 64);
            }
          }
        } else {
          float qn[2];
          drain();
          auto esc_ptr = [&](int gi) { IDS(); return g_esc + (size_t)(((l & 2) + (gi >> 1)) * 65536 + (2 * bn + (gi & 1)) * 2048) * 16; };
          auto norm_half = [&](int gi, float sc, uint32_t (&t)[2][8], float (&nrm)[2][2]) {
            norm_tile(gi, 0, sc, t[0], nrm[0], true); norm_tile(gi, 1, sc, t[1], nrm[1], true);
            if (!((nrm[0][0] + nrm[0][1]) + (nrm[1][0] + nrm[1][1]) <= 4e9f)) {
              uint32_t* p = esc_ptr(gi) + (bm * 256 + row0 + g) * 16 + qd;
#pragma unroll
              for (int m = 0; m < 2; m++) {
                uint32_t u[8]; float d[2];
                norm_tile(gi, m, sc, u, d);
#pragma unroll
                for (int i = 0; i < 8; i++) p[(m * 64 + (i & 1) * 8) * 16 + (i >> 1) * 4] = u[i];
              }
            }
            __syncwarp();
          };
          {
            auto max_norm = [&](const float (&nrm)[2][2]) {
              const bool o1 = qd & 1, o2 = qd & 2;
              const float a = (o1 ? nrm[1][0] : nrm[0][0]) + __shfl_xor_sync(~0u, o1 ? nrm[0][0] : nrm[1][0], 1);
              const float c = (o1 ? nrm[1][1] : nrm[0][1]) + __shfl_xor_sync(~0u, o1 ? nrm[0][1] : nrm[1][1], 1);
              const float d = (o2 ? c : a) + __shfl_xor_sync(~0u, o2 ? a : c, 2);
              return __uint_as_float(__reduce_max_sync(~0u, __float_as_uint(d)));
            };
#pragma unroll
            for (int h = 0; h < 2; h++) {
              uint32_t t[2][8]; float nrm[2][2];
              const uint32_t kb = sb + (h ? 0 : T0);
              if (h) load_cs(3);
              uint32_t tv[2][8];
              norm_half(2 + h, 1.f, t, nrm);
              load_cs(4 + h);
              float nv[2][2];
              if (h == 1) { const float kn = max_norm(nrm); if (lane == 0) g_kn[((l >> 1) * 128 + bn * 8 + bm) * 16 + 8 + wg * 4 + w] = kn; }
              if (h == 0) mbar_wait(sb + B_QE + 8, 1);
#pragma unroll
              for (int i = 0; i < 4; i++) {
                const uint32_t r = row0 + (i >> 1) * 64 + srow;
                stsm4(kb + r * 64 + (((2 * (i & 1) + (lane >> 4)) ^ ((r >> 1) & 3)) << 4), t[i >> 1][4 * (i & 1)], t[i >> 1][4 * (i & 1) + 1], t[i >> 1][4 * (i & 1) + 2], t[i >> 1][4 * (i & 1) + 3]);
              }
              norm_group(4 + h, 1.f, tv, nv);
              load_cs(h);
#pragma unroll
              for (int m = 0; m < 2; m++) {
                const uint32_t r = row0 + m * 64 + g, ad = kb + 16384 + r * 64 + ((qd ^ ((r >> 1) & 3)) << 4);
                sts128(ad, tv[m][0], tv[m][2], tv[m][4], tv[m][6]); sts128(ad + 512, tv[m][1], tv[m][3], tv[m][5], tv[m][7]);
              }
              fence_async_smem();
              bar_arrive(NB_KV + 12 * h, 288);
              if (h == 0) {
                bar_arrive(wg ? NB_HALO : NB_DONE, 160);
                if (wg) bar_sync(NB_HALO + 1, 256);
              }
              if (h == 0) { const float kn = max_norm(nrm); if (lane == 0) g_kn[((l >> 1) * 128 + bn * 8 + bm) * 16 + wg * 4 + w] = kn; }
              norm_half(h, QSCALE, q[h], nrm);
#pragma unroll
              for (int i = 0; i < 4; i++) sts128(sb + QPARK + h * 16384 + (wg * 128 + w * 32 + lane) * 16 + i * 4096, q[h][i >> 1][4 * (i & 1)], q[h][i >> 1][4 * (i & 1) + 1], q[h][i >> 1][4 * (i & 1) + 2], q[h][i >> 1][4 * (i & 1) + 3]);
              qn[h] = max_norm(nrm);
            }
            if (!wg) bar_arrive(NB_HALO + 1, 256);
          }
          constexpr uint64_t VSTEP = 64 - (64ull << 16);
          const uint32_t c_882 = 0x62E562E5u + (lane_id() & zero), c_lsb = 0x00010001u + (lane_id() & zero), c_half = 0x3F003F00u + (lane_id() & zero);
          float o[2][20], S[2][32];
          uint32_t H[2][16], P0[4] = {}, P1[4] = {};
#pragma unroll
          for (int m = 0; m < 2; m++) {
#pragma unroll
            for (int i = 0; i < 20; i++) o[m][i] = 0.f;
            fence_regs(o[m]);
          }
          auto qkf = [&](int b, int ks, uint64_t d) { wg_n64_rs_nb_f16_f32(S[b], q[0][0][4 * ks], q[0][0][4 * ks + 1], q[0][0][4 * ks + 2], q[0][0][4 * ks + 3], d + 2 * ks, ks ? 1 : zero); };
          auto qkh = [&](int b, int ks, uint64_t d) { wg_n64_rs_nb_f16_f16(H[b], q[0][1][4 * ks], q[0][1][4 * ks + 1], q[0][1][4 * ks + 2], q[0][1][4 * ks + 3], d + 2 * ks, ks ? 1 : zero); };
          auto pv0 = [&](uint64_t d) { wgmma_m64n40k16_rs_tb(o[0], P0[0], P0[1], P0[2], P0[3], d, 1); };
          auto pv1 = [&](uint64_t d) { wgmma_m64n40k16_rs_tb(o[1], P1[0], P1[1], P1[2], P1[3], d, 1); };
          float e[4] = {};
          auto finish = [&](int h) {
            const float* s = &S[(h >> 2) & 1][8 * (h & 3)];
            const uint32_t* u = &H[(h >> 2) & 1][4 * (h & 3)];
            const float z0 = exp2_fix(s[6]), z1 = exp2_fix(s[7]);
            P0[0] = pack2v(e[0], e[1]);
            P1[0] = exp2_h2(u[0], c_882);
            P0[1] = pack2v(e[2], e[3]);
            P1[1] = exp2_h2(u[1], c_882);
            const uint32_t B = exp2_base(z0, z1), E = and_or<0x7F807F80u>(B, c_lsb);
            P1[3] = exp2_h2(u[3], c_882);
            P0[3] = fma_bf2(B, and_or<0x807F807Fu>(B, c_half), E);
            const float e4 = ex2v(s[4]), e5 = ex2v(s[5]);
            P1[2] = exp2_h2(u[2], c_882);
            P0[2] = pack2v(e4, e5);
          };
          auto start = [&](int h) {
            const float* s = &S[(h >> 2) & 1][8 * (h & 3)];
            e[0] = ex2v(s[0]); e[1] = ex2v(s[1]); e[3] = ex2v(s[3]); e[2] = ex2v(s[2]);
          };
          uint64_t kd = prm.kv[0].kd;
          mbar_wait(sb + B_TF, 0);
          wg_fence();
#pragma unroll
          for (int b = 0; b < 2; b++) {
            wg_n64_rs_nb_f16_f32_z(S[b], q[0][0][0], q[0][0][1], q[0][0][2], q[0][0][3], kd + 256 * b, 0);
            wg_n64_rs_nb_f16_f16_z(H[b], q[0][1][0], q[0][1][1], q[0][1][2], q[0][1][3], kd + 256 * b, 0);
            if (b == 0) { qkf(0, 1, kd); qkh(0, 1, kd); }
            wg_commit();
          }
          wg_wait<1>(); fence_regs(S[0]); fence_regs(H[0]);
          start(0); finish(0); start(1);
          wg_wait<0>();
          int redo = 0;
#pragma unroll 1
          for (int pass = 0, j = 1; pass < 2; pass++) {
#pragma unroll 1
           do {
            const uint64_t vd = prm.kv[j].vd;
            bool go = false;
#pragma unroll
            for (int h = 2; h < 18; h++) {
              const int px = (h >> 2) + 1, c = h & 3;
              wg_fence();
              if (h == 13) kd = prm.kv[j].kd;
              const uint64_t kx = kd + (px & 3) * 256, vx = vd + (h - 2) * VSTEP;
              if (h == 2) { qkh(1, 0, kx); qkf(1, 0, kx); pv0(vx); pv1(vx); qkh(1, 1, kx); qkf(1, 1, kx); }
              else if ((c == 1 || c == 2) && h < 17) { qkh(px & 1, c - 1, kx); pv1(vx); qkf(px & 1, c - 1, kx); pv0(vx); }
              else { pv0(vx); pv1(vx); }
              wg_commit();
              if (h == 3) e_arrive_if(sb + B_TE + 8 * ((j + 2) & 3), j > 1);
              if (h == 11) go = mbar_test(sb + B_TF + 8 * (j & 3), (j >> 2) & 1) && j != 8;
              finish(h - 1); start(h);
              if (h != 12 && h != 17) sched_fence();
              if (h == 12 && !go) {
                if (j == 16) {
#pragma unroll
                  for (int u = 13; u < 18; u++) {
                    wg_fence(); pv0(vd + (u - 2) * VSTEP); pv1(vd + (u - 2) * VSTEP); wg_commit();
                    if (u < 17) finish(u - 1);
                    if (u < 16) { start(u); sched_fence(); }
                    if (u & 1) { if (u == 17) wg_wait<0>(); else wg_wait<1>(); }
                  }
                  e_arrive(sb + B_TE + 24);
                  goto head_done;
                }
                mbar_wait(sb + B_TF + 8 * (j & 3), (j >> 2) & 1);
                if (j == 8) {
#pragma unroll
                  for (int i = 0; i < 4; i++) lds128(sb + QPARK + 16384 + (wg * 128 + w * 32 + lane_id()) * 16 + i * 4096, &q[0][i >> 1][4 * (i & 1)]);
                }
              }
              if (h == 17) wg_wait<0>(); else if (h & 1) wg_wait<1>();
              if (c == 3) { fence_regs(S[px & 1]); fence_regs(H[px & 1]); }
            }
           } while (j++ & 7);
           head_done:
            fence_regs(o[0]); fence_regs(o[1]);
            uint32_t pk[2][8];
            {
              IDS();
              bf16* op = g_os + (size_t)(bm * 256 + row0 + (lane >> 2)) * 1024 + pass * 512 + bn * 32 + (lane & 3) * 8;
#pragma unroll
              for (int i = 0; i < 4; i++) {
                const float* a = &o[i >> 1][2 * (i & 1)];
                const float inv = rcp(a[16]);
                uint32_t* u = &pk[i >> 1][4 * (i & 1)];
#pragma unroll
                for (int k = 0; k < 4; k++) u[k] = pack2(a[4 * k] * inv, a[4 * k + 1] * inv);
                *(uint4*)(op + ((i >> 1) * 64 + (i & 1) * 8) * 1024) = make_uint4(u[0], u[1], u[2], u[3]);
              }
            }
            sched_fence();
            if (pass == 0) bar_sync(NB_KN + wg, 160);
            const float kmax = *(volatile float*)(smem + ROWST + 4 * pass);
            const bool wide = !(qn[0] <= 1.6e7f) | !(kmax <= 1.6e7f) | !(qn[0] * kmax <= 112.f * 112.f);
            int badm = 0;
#pragma unroll
            for (int m = 0; m < 2; m++) {
              uint32_t chk[2] = {0u, 0u};
#pragma unroll
              for (int i = 0; i < 8; i++) asm("fma.rn.bf16x2 %0, %1, %2, %0;" : "+r"(chk[i & 1]) : "r"(pk[m][i]), "r"(0u));
              const bool bad = wide | !(fminf(o[m][16], o[m][18]) >= 9.3e-10f) | !(o[m][16] + o[m][18] <= 1e36f) | (((chk[0] | chk[1]) & 0x7FFF7FFFu) != 0);
              badm |= __any_sync(~0u, bad) << m;
            }
            if (!badm) bar_arrive(NB_SIG + 2 * pass + wg, 160);
            qn[0] = qn[1];
#pragma unroll
            for (int m = 0; m < 2; m++) {
#pragma unroll
              for (int i = 0; i < 20; i++) o[m][i] = 0.f;
              fence_regs(o[m]);
            }
            if (badm) {
              redo |= badm << 2 * pass;
              const int tx = wg * 128 + w * 32 + lane_id();
              uint4* p = g_qsave + (block_id() * 256 + tx) * 8 + pass * 4;
#pragma unroll
              for (int i = 0; i < 4; i++) {
                uint32_t u[4] = {q[0][i >> 1][4 * (i & 1)], q[0][i >> 1][4 * (i & 1) + 1], q[0][i >> 1][4 * (i & 1) + 2], q[0][i >> 1][4 * (i & 1) + 3]};
                if (pass == 0) lds128(sb + QPARK + tx * 16 + i * 4096, u);
                p[i] = make_uint4(u[0], u[1], u[2], u[3]);
              }
            }
          }
          if (redo) attn_redo(redo, l, cta_id(), wg, w);
        }
      }
      {
        float acc[64];
#pragma unroll
        for (int i = 0; i < 64; i++) acc[i] = 0.f;
        fence_regs(acc);
        uint32_t s = 0, lap = 0;
#pragma unroll 1
        for (int kt = 0; kt < 16; kt++) {
          mbar_wait(sb + B_PF + 8 * s, ((s < 4 ? l : 0) + lap) & 1);
          const uint64_t da = mkdesc(sb + pslot_a(s, l) + wg * 8192, 16, 1024, 1), db = mkdesc(sb + pslot_b(s), 8192, 1024, 1);
          wg_fence();
#pragma unroll
          for (int k = 0; k < 4; k++) wgmma_m64n128k16_ss_tb(acc, da + k * 2, db + k * 128, 1);
          wg_commit();
          wg_wait<1>();
          if (kt > 0 && w == 0) e_arrive_both(sb + B_PE + 8 * (s ? s - 1 : 5));
          if (++s == 6) { s = 0; lap++; }
        }
        IDS();
        const int g = lane >> 2, qd = lane & 3;
        const int r0 = wg * 64 + w * 16;
        const uint32_t r = r0 + (lane & 7) + ((lane >> 3) & 1) * 8;
        uint32_t x[8][4];
        mbar_wait(sb + B_RF, l & 1);
#pragma unroll
        for (int jj = 0; jj < 8; jj++) ldsm4(sb + RES + (jj >> 2) * 16384 + r * 128 + ((((2 * jj + (lane >> 4)) & 7) ^ (r & 7)) << 4), x[jj]);
        wg_wait<0>();
        fence_regs(acc);
        if (w == 0) e_arrive_both(sb + B_PE + 8 * 3);
        const CUtensorMap* mo = &prm.m[l == 3 ? M_OUT : M_XST];
#pragma unroll
        for (int jj = 0; jj < 8; jj++) {
#pragma unroll
          for (int i = 0; i < 4; i++) x[jj][i] = add_bf16x2(x[jj][i], pack2(acc[8 * jj + 2 * i], acc[8 * jj + 2 * i + 1]));
          stsm4(sb + RES + (jj >> 2) * 16384 + r * 128 + ((((2 * jj + (lane >> 4)) & 7) ^ (r & 7)) << 4), x[jj][0], x[jj][1], x[jj][2], x[jj][3]);
          if ((jj & 3) == 3) { fence_async_smem(); __syncwarp(); tma_st(mo, pn * 128 + (jj >> 2) * 64, pm * 128 + r0, sb + RES + (jj >> 2) * 16384 + r0 * 128); }
        }
        bulk_commit();
        if (l < 3) {
          bar_sync(NB_SC, 256);
#pragma unroll
          for (int jj = 0; jj < 8; jj++)
            stsm4(sb + (jj >> 2) * QSTG + po * 16384 + r * 128 + ((((2 * jj + (lane >> 4)) & 7) ^ (r & 7)) << 4), x[jj][0], x[jj][1], x[jj][2], x[jj][3]);
          fence_async_smem();
          bar_arrive(NB_X, 288);
          float s1[4] = {0.f, 0.f, 0.f, 0.f}, sa[4] = {0.f, 0.f, 0.f, 0.f}, sc[4] = {0.f, 0.f, 0.f, 0.f};
#pragma unroll
          for (int jj = 0; jj < 8; jj++) {
            mma16816(s1, x[jj][0], x[jj][1], x[jj][2], x[jj][3], 0x3f803f80u, 0x3f803f80u);
            mma16816(sa, x[jj][0], x[jj][1], x[jj][2], x[jj][3], x[jj][0], x[jj][2]);
            mma16816(sc, x[jj][0], x[jj][1], x[jj][2], x[jj][3], x[jj][1], x[jj][3]);
          }
          if (qd == g >> 1) {
            float2* p = g_stats + pn * 2048 + pm * 128 + r0 + g;
            p[0] = make_float2(s1[0], g & 1 ? sa[1] : sa[0]);
            p[8] = make_float2(s1[2], g & 1 ? sc[3] : sc[2]);
          }
        }
        bulk_wait_n<0>();
        if (l < 3) bar_arrive(NB_X0, 288);
      }
    }
  }
  asm volatile("barrier.cluster.arrive.relaxed.aligned;\nbarrier.cluster.wait.aligned;" ::: "memory");
}

typedef CUresult (*EncodeFn)(CUtensorMap*, CUtensorMapDataType, cuuint32_t, void*, const cuuint64_t*, const cuuint64_t*, const cuuint32_t*,
                             const cuuint32_t*, CUtensorMapInterleave, CUtensorMapSwizzle, CUtensorMapL2promotion, CUtensorMapFloatOOBfill);

static void make_map(EncodeFn fn, CUtensorMap* m, const void* ptr, int rank, const uint64_t* dims, const uint64_t* strides, const uint32_t* box, CUtensorMapSwizzle sw) {
  cuuint64_t d[5], st[4];
  cuuint32_t bx[5], es[5];
  for (int i = 0; i < rank; i++) { d[i] = dims[i]; bx[i] = box[i]; es[i] = 1; if (i) st[i - 1] = strides[i - 1] * 2; }
  fn(m, CU_TENSOR_MAP_DATA_TYPE_BFLOAT16, rank, (void*)ptr, d, st, bx, es, CU_TENSOR_MAP_INTERLEAVE_NONE, sw,
     CU_TENSOR_MAP_L2_PROMOTION_L2_128B, CU_TENSOR_MAP_FLOAT_OOB_FILL_NONE);
}
static void map2(EncodeFn fn, CUtensorMap* m, const void* ptr, uint64_t inner, uint64_t outer, uint32_t bi, uint32_t bo, CUtensorMapSwizzle sw) {
  const uint64_t d[2] = {inner, outer}, st[1] = {inner};
  const uint32_t bx[2] = {bi, bo};
  make_map(fn, m, ptr, 2, d, st, bx, sw);
}

extern "C" void kernel_launch(void* const* d_in, const int* in_sizes, int n_in, void* d_out, int out_size) {
  (void)in_sizes; (void)n_in; (void)out_size;
  static EncodeFn enc = nullptr;
  static void *xs, *os, *kk, *vv;
  static int sbase = 1024;
  if (!enc) {
    void* p = nullptr;
    cudaDriverEntryPointQueryResult qr;
    cudaGetDriverEntryPoint("cuTensorMapEncodeTiled", &p, cudaEnableDefault, &qr);
    enc = (EncodeFn)p;
    Scratch* sc = nullptr;
    cudaGetSymbolAddress((void**)&sc, g_s);
    xs = sc->xs; os = sc->os; kk = sc->k; vv = sc->v;
    int dev = 0;
    cudaGetDevice(&dev);
    cudaDeviceGetAttribute(&sbase, cudaDevAttrReservedSharedMemoryPerBlock, dev);
    cudaFuncSetAttribute(fused_kernel, cudaFuncAttributeMaxDynamicSharedMemorySize, SMEM_BYTES);
  }
  Params prm;
  const CUtensorMapSwizzle S128 = CU_TENSOR_MAP_SWIZZLE_128B, S64 = CU_TENSOR_MAP_SWIZZLE_64B;
  map2(enc, &prm.m[M_X0A], d_in[0], 1024, 2048, 64, 256, S128);
  map2(enc, &prm.m[M_XSA], xs, 1024, 2048, 64, 256, S128);
  for (int t = 0; t < 2; t++) {
    const uint64_t d3[3] = {1024, 1024, 3}, s3[2] = {3072, 1024};
    const uint32_t b3[3] = {64, 64, 3};
    make_map(enc, &prm.m[M_WQA + t], d_in[1 + 3 * t], 3, d3, s3, b3, S128);
    const uint64_t d5[5] = {64, 32, 2, 16, 16}, s5[4] = {1024, 32 * 1024, 64 * 1024, 64};
    const uint32_t b5[5] = {64, 32, 1, 2, 2};
    make_map(enc, &prm.m[M_WOA + t], d_in[2 + 3 * t], 5, d5, s5, b5, S128);
    const uint64_t dr[3] = {64, 2048, 16}, sr[2] = {1024, 64};
    const uint32_t br[3] = {64, 128, 2};
    make_map(enc, &prm.m[M_X0R + t], t ? xs : d_in[0], 3, dr, sr, br, S128);
  }
  map2(enc, &prm.m[M_OS], os, 1024, 2048, 64, 64, S128);
  map2(enc, &prm.m[M_K], kk, 32, 65536, 32, 128, S64);
  map2(enc, &prm.m[M_V], vv, 32, 65536, 32, 128, S64);
  map2(enc, &prm.m[M_XSO], xs, 1024, 2048, 64, 128, S128);
  map2(enc, &prm.m[M_X0H], d_in[0], 1024, 2048, 64, 128, S128);
  map2(enc, &prm.m[M_XST], xs, 1024, 2048, 64, 16, S128);
  map2(enc, &prm.m[M_OUT], d_out, 1024, 2048, 64, 16, S128);
  prm.x0 = (const bf16*)d_in[0];
  prm.wq[0] = (const bf16*)d_in[1]; prm.wq[1] = (const bf16*)d_in[4];
  prm.zero = 0;
  for (int i = 0; i < 128; i++) prm.map[i] = remap(i);
  {
    const uint64_t hi = 0x80000020ull << 32, k0 = sbase + T0, v0 = k0 + 16384, vstep = 64 - (64ull << 16);
    prm.wd = mkdesc(sbase + 32768, 8192, 1024, 1); prm.xd = mkdesc(sbase, 16, 1024, 1);
    for (int j = 0; j < 17; j++) {
      prm.kv[j].kd = (hi | 1u << 16 | k0 >> 4) + 2048 * ((j < 16 ? j : 15) & 3);
      prm.kv[j].vd = (hi | (uint64_t)(ONES - T0 - 16384) >> 4 << 16 | v0 >> 4) + 32 * vstep * ((j ? j - 1 : 0) & 3);
    }
  }
  fused_kernel<<<128, 384, SMEM_BYTES>>>(prm);
}
```

```cpp
#include <cuda_runtime.h>
#include <cuda_bf16.h>
#include <cuda.h>
#include <stdint.h>

typedef __nv_bfloat16 bf16;

__device__ __forceinline__ void wgmma_m64n192k16_ss_tb(float (&d)[96], uint64_t da, uint64_t db, int scale_d) {
  asm volatile("{\n.reg .pred p;\nsetp.ne.b32 p, %98, 0;\n"
    "wgmma.mma_async.sync.aligned.m64n192k16.f32.bf16.bf16 "
    "{%0, %1, %2, %3, %4, %5, %6, %7, %8, %9, %10, %11, %12, %13, %14, %15, "
    "%16, %17, %18, %19, %20, %21, %22, %23, %24, %25, %26, %27, %28, %29, %30, %31, "
    "%32, %33, %34, %35, %36, %37, %38, %39, %40, %41, %42, %43, %44, %45, %46, %47, "
    "%48, %49, %50, %51, %52, %53, %54, %55, %56, %57, %58, %59, %60, %61, %62, %63, "
    "%64, %65, %66, %67, %68, %69, %70, %71, %72, %73, %74, %75, %76, %77, %78, %79, "
    "%80, %81, %82, %83, %84, %85, %86, %87, %88, %89, %90, %91, %92, %93, %94, %95}, "
    "%96, %97, p, 1, 1, 0, 1;\n}\n"
    : "+f"(d[0]), "+f"(d[1]), "+f"(d[2]), "+f"(d[3]), "+f"(d[4]), "+f"(d[5]), "+f"(d[6]), "+f"(d[7]),
      "+f"(d[8]), "+f"(d[9]), "+f"(d[10]), "+f"(d[11]), "+f"(d[12]), "+f"(d[13]), "+f"(d[14]), "+f"(d[15]),
      "+f"(d[16]), "+f"(d[17]), "+f"(d[18]), "+f"(d[19]), "+f"(d[20]), "+f"(d[21]), "+f"(d[22]), "+f"(d[23]),
      "+f"(d[24]), "+f"(d[25]), "+f"(d[26]), "+f"(d[27]), "+f"(d[28]), "+f"(d[29]), "+f"(d[30]), "+f"(d[31]),
      "+f"(d[32]), "+f"(d[33]), "+f"(d[34]), "+f"(d[35]), "+f"(d[36]), "+f"(d[37]), "+f"(d[38]), "+f"(d[39]),
      "+f"(d[40]), "+f"(d[41]), "+f"(d[42]), "+f"(d[43]), "+f"(d[44]), "+f"(d[45]), "+f"(d[46]), "+f"(d[47]),
      "+f"(d[48]), "+f"(d[49]), "+f"(d[50]), "+f"(d[51]), "+f"(d[52]), "+f"(d[53]), "+f"(d[54]), "+f"(d[55]),
      "+f"(d[56]), "+f"(d[57]), "+f"(d[58]), "+f"(d[59]), "+f"(d[60]), "+f"(d[61]), "+f"(d[62]), "+f"(d[63]),
      "+f"(d[64]), "+f"(d[65]), "+f"(d[66]), "+f"(d[67]), "+f"(d[68]), "+f"(d[69]), "+f"(d[70]), "+f"(d[71]),
      "+f"(d[72]), "+f"(d[73]), "+f"(d[74]), "+f"(d[75]), "+f"(d[76]), "+f"(d[77]), "+f"(d[78]), "+f"(d[79]),
      "+f"(d[80]), "+f"(d[81]), "+f"(d[82]), "+f"(d[83]), "+f"(d[84]), "+f"(d[85]), "+f"(d[86]), "+f"(d[87]),
      "+f"(d[88]), "+f"(d[89]), "+f"(d[90]), "+f"(d[91]), "+f"(d[92]), "+f"(d[93]), "+f"(d[94]), "+f"(d[95])
    : "l"(da), "l"(db), "r"(scale_d));
}

__device__ __forceinline__ void wgmma_m64n128k16_ss_tb(float (&d)[64], uint64_t da, uint64_t db, int scale_d) {
  asm volatile("{\n.reg .pred p;\nsetp.ne.b32 p, %66, 0;\n"
    "wgmma.mma_async.sync.aligned.m64n128k16.f32.bf16.bf16 "
    "{%0, %1, %2, %3, %4, %5, %6, %7, %8, %9, %10, %11, %12, %13, %14, %15, "
    "%16, %17, %18, %19, %20, %21, %22, %23, %24, %25, %26, %27, %28, %29, %30, %31, "
    "%32, %33, %34, %35, %36, %37, %38, %39, %40, %41, %42, %43, %44, %45, %46, %47, "
    "%48, %49, %50, %51, %52, %53, %54, %55, %56, %57, %58, %59, %60, %61, %62, %63}, "
    "%64, %65, p, 1, 1, 0, 1;\n}\n"
    : "+f"(d[0]), "+f"(d[1]), "+f"(d[2]), "+f"(d[3]), "+f"(d[4]), "+f"(d[5]), "+f"(d[6]), "+f"(d[7]),
      "+f"(d[8]), "+f"(d[9]), "+f"(d[10]), "+f"(d[11]), "+f"(d[12]), "+f"(d[13]), "+f"(d[14]), "+f"(d[15]),
      "+f"(d[16]), "+f"(d[17]), "+f"(d[18]), "+f"(d[19]), "+f"(d[20]), "+f"(d[21]), "+f"(d[22]), "+f"(d[23]),
      "+f"(d[24]), "+f"(d[25]), "+f"(d[26]), "+f"(d[27]), "+f"(d[28]), "+f"(d[29]), "+f"(d[30]), "+f"(d[31]),
      "+f"(d[32]), "+f"(d[33]), "+f"(d[34]), "+f"(d[35]), "+f"(d[36]), "+f"(d[37]), "+f"(d[38]), "+f"(d[39]),
      "+f"(d[40]), "+f"(d[41]), "+f"(d[42]), "+f"(d[43]), "+f"(d[44]), "+f"(d[45]), "+f"(d[46]), "+f"(d[47]),
      "+f"(d[48]), "+f"(d[49]), "+f"(d[50]), "+f"(d[51]), "+f"(d[52]), "+f"(d[53]), "+f"(d[54]), "+f"(d[55]),
      "+f"(d[56]), "+f"(d[57]), "+f"(d[58]), "+f"(d[59]), "+f"(d[60]), "+f"(d[61]), "+f"(d[62]), "+f"(d[63])
    : "l"(da), "l"(db), "r"(scale_d));
}

__device__ __forceinline__ void wgmma_m64n40k16_rs_tb(float (&d)[20], uint32_t a0, uint32_t a1, uint32_t a2, uint32_t a3, uint64_t db, int scale_d) {
  asm volatile("{\n.reg .pred p;\nsetp.ne.b32 p, %25, 0;\n"
    "wgmma.mma_async.sync.aligned.m64n40k16.f32.bf16.bf16 "
    "{%0, %1, %2, %3, %4, %5, %6, %7, %8, %9, %10, %11, %12, %13, %14, %15, "
    "%16, %17, %18, %19}, "
    "{%20, %21, %22, %23}, %24, p, 1, 1, 1;\n}\n"
    : "+f"(d[0]), "+f"(d[1]), "+f"(d[2]), "+f"(d[3]), "+f"(d[4]), "+f"(d[5]), "+f"(d[6]), "+f"(d[7]),
      "+f"(d[8]), "+f"(d[9]), "+f"(d[10]), "+f"(d[11]), "+f"(d[12]), "+f"(d[13]), "+f"(d[14]), "+f"(d[15]),
      "+f"(d[16]), "+f"(d[17]), "+f"(d[18]), "+f"(d[19])
    : "r"(a0), "r"(a1), "r"(a2), "r"(a3), "l"(db), "r"(scale_d));
}

__device__ __forceinline__ void wg_n64_rs_nb_f16_f32(float (&d)[32], uint32_t a0, uint32_t a1, uint32_t a2, uint32_t a3, uint64_t db, int scale_d) {
  asm volatile("{\n.reg .pred p;\nsetp.ne.b32 p, %37, 0;\n"
    "wgmma.mma_async.sync.aligned.m64n64k16.f32.f16.f16 "
    "{%0, %1, %2, %3, %4, %5, %6, %7, %8, %9, %10, %11, %12, %13, %14, %15, "
    "%16, %17, %18, %19, %20, %21, %22, %23, %24, %25, %26, %27, %28, %29, %30, %31}, "
    "{%32, %33, %34, %35}, %36, p, 1, 1, 0;\n}\n"
    : "+f"(d[0]), "+f"(d[1]), "+f"(d[2]), "+f"(d[3]), "+f"(d[4]), "+f"(d[5]), "+f"(d[6]), "+f"(d[7]),
      "+f"(d[8]), "+f"(d[9]), "+f"(d[10]), "+f"(d[11]), "+f"(d[12]), "+f"(d[13]), "+f"(d[14]), "+f"(d[15]),
      "+f"(d[16]), "+f"(d[17]), "+f"(d[18]), "+f"(d[19]), "+f"(d[20]), "+f"(d[21]), "+f"(d[22]), "+f"(d[23]),
      "+f"(d[24]), "+f"(d[25]), "+f"(d[26]), "+f"(d[27]), "+f"(d[28]), "+f"(d[29]), "+f"(d[30]), "+f"(d[31])
    : "r"(a0), "r"(a1), "r"(a2), "r"(a3), "l"(db), "r"(scale_d));
}

__device__ __forceinline__ void wg_n64_rs_nb_f16_f16(uint32_t (&d)[16], uint32_t a0, uint32_t a1, uint32_t a2, uint32_t a3, uint64_t db, int scale_d) {
  asm volatile("{\n.reg .pred p;\nsetp.ne.b32 p, %21, 0;\n"
    "wgmma.mma_async.sync.aligned.m64n64k16.f16.f16.f16 "
    "{%0, %1, %2, %3, %4, %5, %6, %7, %8, %9, %10, %11, %12, %13, %14, %15}, "
    "{%16, %17, %18, %19}, %20, p, 1, 1, 0;\n}\n"
    : "+r"(d[0]), "+r"(d[1]), "+r"(d[2]), "+r"(d[3]), "+r"(d[4]), "+r"(d[5]), "+r"(d[6]), "+r"(d[7]),
      "+r"(d[8]), "+r"(d[9]), "+r"(d[10]), "+r"(d[11]), "+r"(d[12]), "+r"(d[13]), "+r"(d[14]), "+r"(d[15])
    : "r"(a0), "r"(a1), "r"(a2), "r"(a3), "l"(db), "r"(scale_d));
}

__device__ __forceinline__ void wg_n64_rs_nb_f16_f32_z(float (&d)[32], uint32_t a0, uint32_t a1, uint32_t a2, uint32_t a3, uint64_t db, int scale_d) {
  asm volatile("{\n.reg .pred p;\nsetp.ne.b32 p, %37, 0;\n"
    "wgmma.mma_async.sync.aligned.m64n64k16.f32.f16.f16 "
    "{%0, %1, %2, %3, %4, %5, %6, %7, %8, %9, %10, %11, %12, %13, %14, %15, "
    "%16, %17, %18, %19, %20, %21, %22, %23, %24, %25, %26, %27, %28, %29, %30, %31}, "
    "{%32, %33, %34, %35}, %36, p, 1, 1, 0;\n}\n"
    : "=f"(d[0]), "=f"(d[1]), "=f"(d[2]), "=f"(d[3]), "=f"(d[4]), "=f"(d[5]), "=f"(d[6]), "=f"(d[7]),
      "=f"(d[8]), "=f"(d[9]), "=f"(d[10]), "=f"(d[11]), "=f"(d[12]), "=f"(d[13]), "=f"(d[14]), "=f"(d[15]),
      "=f"(d[16]), "=f"(d[17]), "=f"(d[18]), "=f"(d[19]), "=f"(d[20]), "=f"(d[21]), "=f"(d[22]), "=f"(d[23]),
      "=f"(d[24]), "=f"(d[25]), "=f"(d[26]), "=f"(d[27]), "=f"(d[28]), "=f"(d[29]), "=f"(d[30]), "=f"(d[31])
    : "r"(a0), "r"(a1), "r"(a2), "r"(a3), "l"(db), "r"(scale_d));
}

__device__ __forceinline__ void wg_n64_rs_nb_f16_f16_z(uint32_t (&d)[16], uint32_t a0, uint32_t a1, uint32_t a2, uint32_t a3, uint64_t db, int scale_d) {
  asm volatile("{\n.reg .pred p;\nsetp.ne.b32 p, %21, 0;\n"
    "wgmma.mma_async.sync.aligned.m64n64k16.f16.f16.f16 "
    "{%0, %1, %2, %3, %4, %5, %6, %7, %8, %9, %10, %11, %12, %13, %14, %15}, "
    "{%16, %17, %18, %19}, %20, p, 1, 1, 0;\n}\n"
    : "=r"(d[0]), "=r"(d[1]), "=r"(d[2]), "=r"(d[3]), "=r"(d[4]), "=r"(d[5]), "=r"(d[6]), "=r"(d[7]),
      "=r"(d[8]), "=r"(d[9]), "=r"(d[10]), "=r"(d[11]), "=r"(d[12]), "=r"(d[13]), "=r"(d[14]), "=r"(d[15])
    : "r"(a0), "r"(a1), "r"(a2), "r"(a3), "l"(db), "r"(scale_d));
}

#define DEVINL __device__ __forceinline__
DEVINL void wg_fence() { asm volatile("wgmma.fence.sync.aligned;" ::: "memory"); }
DEVINL void wg_commit() { asm volatile("wgmma.commit_group.sync.aligned;" ::: "memory"); }
template <int N> DEVINL void wg_wait() { asm volatile("wgmma.wait_group.sync.aligned %0;" ::"n"(N) : "memory"); }
__host__ DEVINL uint64_t mkdesc(uint32_t addr, uint32_t lbo, uint32_t sbo, int sw) {
  return (uint64_t)((addr & 0x3FFFF) >> 4) | ((uint64_t)(lbo >> 4) << 16) | ((uint64_t)(sbo >> 4) << 32) | ((uint64_t)sw << 62);
}
DEVINL void mbar_init(uint32_t bar, uint32_t cnt) { asm volatile("mbarrier.init.shared::cta.b64 [%0], %1;" ::"r"(bar), "r"(cnt) : "memory"); }
DEVINL void mbar_arrive(uint32_t bar) { asm volatile("mbarrier.arrive.shared::cta.b64 _, [%0];" ::"r"(bar) : "memory"); }
DEVINL bool mbar_try(uint32_t bar, uint32_t parity) {
  uint32_t ok;
  asm volatile("{\n.reg .pred p;\nmbarrier.try_wait.parity.shared::cta.b64 p, [%1], %2;\nselp.u32 %0, 1, 0, p;\n}" : "=r"(ok) : "r"(bar), "r"(parity) : "memory");
  return ok;
}
DEVINL bool mbar_test(uint32_t bar, uint32_t parity) {
  uint32_t ok;
  asm volatile("{\n.reg .pred p;\nmbarrier.test_wait.parity.shared::cta.b64 p, [%1], %2;\nselp.u32 %0, 1, 0, p;\n}" : "=r"(ok) : "r"(bar), "r"(parity) : "memory");
  return ok;
}
DEVINL void mbar_hint(uint32_t bar, uint32_t parity) {
#pragma unroll 1
  for (uint32_t n = 0; n < 16u; n++) if (mbar_try(bar, parity)) break;
}
DEVINL void mbar_wait(uint32_t bar, uint32_t parity) {
#pragma unroll 1
  for (uint32_t n = 0; n < 100000u; n++) if (mbar_try(bar, parity)) break;
}
#define EL(txt) "{\n.reg .pred pe;\nelect.sync _|pe, 0xffffffff;\n@pe " txt "\n}"
DEVINL void e_expect_tx(uint32_t bar, uint32_t bytes) { asm volatile(EL("mbarrier.arrive.expect_tx.shared::cta.b64 _, [%0], %1;") ::"r"(bar), "r"(bytes) : "memory"); }
DEVINL void e_arrive(uint32_t bar) { asm volatile(EL("mbarrier.arrive.shared::cta.b64 _, [%0];") ::"r"(bar) : "memory"); }
DEVINL void e_arrive_if(uint32_t bar, int c) {
  asm volatile("{\n.reg .pred pe;\nelect.sync _|pe, 0xffffffff;\nsetp.ne.and.b32 pe, %1, 0, pe;\n@pe mbarrier.arrive.shared::cta.b64 _, [%0];\n}" ::"r"(bar), "r"(c) : "memory");
}
DEVINL void e_red(uint32_t* p) { asm volatile(EL("red.release.gpu.global.add.u32 [%0], 1;") ::"l"(p) : "memory"); }
DEVINL void e_red_relaxed(uint32_t* p) { asm volatile(EL("red.relaxed.gpu.global.add.u32 [%0], 1;") ::"l"(p) : "memory"); }
DEVINL void tma_ld(uint32_t dst, const CUtensorMap* m, int c0, int c1, uint32_t bar) {
  asm volatile(EL("cp.async.bulk.tensor.2d.shared::cluster.global.mbarrier::complete_tx::bytes [%0], [%1, {%3, %4}], [%2];")
               ::"r"(dst), "l"(m), "r"(bar), "r"(c0), "r"(c1) : "memory");
}
DEVINL void tma_ld3(uint32_t dst, const CUtensorMap* m, int c0, int c1, int c2, uint32_t bar) {
  asm volatile(EL("cp.async.bulk.tensor.3d.shared::cluster.global.mbarrier::complete_tx::bytes [%0], [%1, {%3, %4, %5}], [%2];")
               ::"r"(dst), "l"(m), "r"(bar), "r"(c0), "r"(c1), "r"(c2) : "memory");
}
DEVINL void tma_ld5(uint32_t dst, const CUtensorMap* m, int c2, int c3, int c4, uint32_t bar) {
  asm volatile(EL("cp.async.bulk.tensor.5d.shared::cluster.global.mbarrier::complete_tx::bytes [%0], [%1, {0, 0, %3, %4, %5}], [%2];")
               ::"r"(dst), "l"(m), "r"(bar), "r"(c2), "r"(c3), "r"(c4) : "memory");
}
DEVINL void tma_ld_mc(uint32_t dst, const CUtensorMap* m, int c0, int c1, uint32_t bar) {
  asm volatile(EL("cp.async.bulk.tensor.2d.shared::cluster.global.mbarrier::complete_tx::bytes.multicast::cluster [%0], [%1, {%3, %4}], [%2], %5;")
               ::"r"(dst), "l"(m), "r"(bar), "r"(c0), "r"(c1), "h"((uint16_t)3) : "memory");
}
DEVINL void e_arrive_both(uint32_t bar) {
  asm volatile("{\n.reg .pred pe;\n.reg .b32 r0, r1;\nelect.sync _|pe, 0xffffffff;\nmapa.shared::cluster.u32 r0, %0, 0;\nmapa.shared::cluster.u32 r1, %0, 1;\n"
               "@pe mbarrier.arrive.shared::cluster.b64 _, [r0];\n@pe mbarrier.arrive.shared::cluster.b64 _, [r1];\n}" ::"r"(bar) : "memory");
}
DEVINL void tma_st(const CUtensorMap* m, int c0, int c1, uint32_t src) {
  asm volatile(EL("cp.async.bulk.tensor.2d.global.shared::cta.bulk_group [%0, {%2, %3}], [%1];") ::"l"(m), "r"(src), "r"(c0), "r"(c1) : "memory");
}
DEVINL void bulk_commit() { asm volatile("cp.async.bulk.commit_group;" ::: "memory"); }
template <int N> DEVINL void bulk_wait_n() { asm volatile("cp.async.bulk.wait_group %0;\nbar.warp.sync 0xffffffff;" ::"n"(N) : "memory"); }
DEVINL void l2_prefetch(const void* g, uint32_t bytes) { asm volatile(EL("cp.async.bulk.prefetch.L2.global [%0], %1;") ::"l"(g), "r"(bytes) : "memory"); }
DEVINL void fence_async_smem() { asm volatile("fence.proxy.async.shared::cta;" ::: "memory"); }
DEVINL void fence_async_gl() { asm volatile("fence.proxy.async.global;" ::: "memory"); }
DEVINL void cluster_wait() { asm volatile("barrier.cluster.wait.aligned;" ::: "memory"); }
DEVINL void bar_sync(int id, int n) { asm volatile("bar.sync %0, %1;" ::"r"(id), "r"(n) : "memory"); }
DEVINL void bar_arrive(int id, int n) { asm volatile("bar.arrive %0, %1;" ::"r"(id), "r"(n) : "memory"); }
DEVINL uint32_t ld_acquire(const uint32_t* p) { uint32_t v; asm volatile("ld.acquire.gpu.global.u32 %0, [%1];" : "=r"(v) : "l"(p) : "memory"); return v; }
DEVINL void watch(const uint32_t* p, uint32_t target, uint32_t all, uint32_t tag, uint32_t slot) {
  uint32_t seen = 0;
#pragma unroll 1
  for (uint32_t n = 0; n < 200000u && seen != all; n++) {
    const uint32_t m = __ballot_sync(~0u, (int)(ld_acquire(p) - target) >= 0) & all;
    if (m != seen) { seen = m; asm volatile("st.release.cta.shared.u32 [%0], %1;" ::"r"(slot), "r"(tag << 16 | m) : "memory"); }
  }
}
template <bool RELAXED = false> DEVINL void await_bit(uint32_t slot, uint32_t tag, int j, uint32_t& rdy) {
  if ((rdy >> j) & 1) return;
#pragma unroll 1
  for (uint32_t n = 0; n < 8000000u; n++) {
    uint32_t v;
    asm volatile("ld.acquire.cta.shared.u32 %0, [%1];" : "=r"(v) : "r"(slot) : "memory");
    if ((v >> 16) == tag && ((v >> j) & 1)) { rdy = v; break; }
    if (RELAXED) __nanosleep(200);
  }
  asm volatile("fence.proxy.async.global;" ::: "memory");
}
DEVINL void poll_ge(const uint32_t* p, uint32_t target) {
#pragma unroll 1
  for (uint32_t n = 0; n < 200000u; n++) if (__all_sync(~0u, (int)(ld_acquire(p) - target) >= 0)) break;
}
DEVINL int lane_id() { int v; asm volatile("mov.u32 %0, %%laneid;" : "=r"(v)); return v; }
__host__ DEVINL int remap(int v) {
  const int c = v >> 1, u = c - 36, r = (u * 37) >> 8;
  const int L = c < 4 ? 32 + 8 * c : c < 36 ? c - 4 : 33 + u + r;
  return 2 * L + (v & 1);
}
DEVINL int block_id() { int v; asm volatile("mov.u32 %0, %%ctaid.x;" : "=r"(v)); return v; }
#define cta_id() prm.map[block_id()]
#define IDS() const int lane = lane_id(), b = cta_id(), bm = b >> 4, bn = b & 15, rank = b & 1, pm = 2 * bm + (bn >> 3), pn = bn & 7, po = pm & 1; \
  (void)lane; (void)bm; (void)bn; (void)rank; (void)pm; (void)pn; (void)po
DEVINL void st_tagged(uint4* p, uint32_t a, uint32_t b, uint32_t c, uint32_t tag) {
  asm volatile("{\n.reg .b64 u, v;\n.reg .b128 t;\nmov.b64 u, {%1, %2};\nmov.b64 v, {%3, %4};\nmov.b128 t, {u, v};\nst.relaxed.gpu.global.b128 [%0], t;\n}"
               ::"l"(p), "r"(a), "r"(b), "r"(c), "r"(tag) : "memory");
}
DEVINL uint32_t ld_tagged(const uint4* p, uint32_t* r) {
  uint32_t tag;
  asm volatile("{\n.reg .b64 u, v;\n.reg .b128 t;\nld.relaxed.gpu.global.b128 t, [%4];\nmov.b128 {u, v}, t;\nmov.b64 {%0, %1}, u;\nmov.b64 {%2, %3}, v;\n}"
               : "=r"(r[0]), "=r"(r[1]), "=r"(r[2]), "=r"(tag) : "l"(p) : "memory");
  return tag;
}
DEVINL float ex2(float x) { float y; asm("ex2.approx.ftz.f32 %0, %1;" : "=f"(y) : "f"(x)); return y; }
DEVINL float rcp(float x) { float y; asm("rcp.approx.ftz.f32 %0, %1;" : "=f"(y) : "f"(x)); return y; }
DEVINL uint32_t pack2(float lo, float hi) { uint32_t r; asm("cvt.rn.bf16x2.f32 %0, %1, %2;" : "=r"(r) : "f"(hi), "f"(lo)); return r; }
DEVINL uint32_t pack2h(float lo, float hi) { uint32_t r; asm("cvt.rn.f16x2.f32 %0, %1, %2;" : "=r"(r) : "f"(hi), "f"(lo)); return r; }
DEVINL float bf_lo(uint32_t w) { return __uint_as_float(w << 16); }
DEVINL float bf_hi(uint32_t w) { return __uint_as_float(w & 0xFFFF0000u); }
DEVINL float bf_round(float x) { return bf_lo(pack2(x, 0.f)); }
DEVINL uint32_t add_bf16x2(uint32_t a, uint32_t b) { uint32_t r; asm("add.rn.bf16x2 %0, %1, %2;" : "=r"(r) : "r"(a), "r"(b)); return r; }
DEVINL void stsm4(uint32_t addr, uint32_t a, uint32_t b, uint32_t c, uint32_t d) {
  asm volatile("stmatrix.sync.aligned.m8n8.x4.shared.b16 [%0], {%1, %2, %3, %4};" ::"r"(addr), "r"(a), "r"(b), "r"(c), "r"(d) : "memory");
}
DEVINL void ldsm4(uint32_t addr, uint32_t (&r)[4]) {
  asm volatile("ldmatrix.sync.aligned.m8n8.x4.shared.b16 {%0, %1, %2, %3}, [%4];" : "=r"(r[0]), "=r"(r[1]), "=r"(r[2]), "=r"(r[3]) : "r"(addr) : "memory");
}
DEVINL void ldsm4t(uint32_t addr, uint32_t (&r)[4]) {
  asm volatile("ldmatrix.sync.aligned.m8n8.x4.trans.shared.b16 {%0, %1, %2, %3}, [%4];" : "=r"(r[0]), "=r"(r[1]), "=r"(r[2]), "=r"(r[3]) : "r"(addr) : "memory");
}
DEVINL void sts128(uint32_t addr, uint32_t a, uint32_t b, uint32_t c, uint32_t d) {
  asm volatile("st.shared.v4.b32 [%0], {%1, %2, %3, %4};" ::"r"(addr), "r"(a), "r"(b), "r"(c), "r"(d) : "memory");
}
DEVINL float2 lds64f(uint32_t addr) { float2 v; asm volatile("ld.shared.v2.f32 {%0, %1}, [%2];" : "=f"(v.x), "=f"(v.y) : "r"(addr) : "memory"); return v; }
DEVINL void mma16816(float (&d)[4], uint32_t a0, uint32_t a1, uint32_t a2, uint32_t a3, uint32_t b0, uint32_t b1) {
  asm("mma.sync.aligned.m16n8k16.row.col.f32.bf16.bf16.f32 {%0, %1, %2, %3}, {%4, %5, %6, %7}, {%8, %9}, {%0, %1, %2, %3};"
               : "+f"(d[0]), "+f"(d[1]), "+f"(d[2]), "+f"(d[3]) : "r"(a0), "r"(a1), "r"(a2), "r"(a3), "r"(b0), "r"(b1));
}
template <int N> DEVINL void fence_regs(float (&d)[N]) {
#pragma unroll
  for (int i = 0; i < N; i++) asm volatile("" : "+f"(d[i])::"memory");
}
template <int N> DEVINL void fence_regs(uint32_t (&d)[N]) {
#pragma unroll
  for (int i = 0; i < N; i++) asm volatile("" : "+r"(d[i])::"memory");
}
DEVINL void lds128(uint32_t addr, uint32_t* r) {
  asm volatile("ld.shared.v4.b32 {%0, %1, %2, %3}, [%4];" : "=r"(r[0]), "=r"(r[1]), "=r"(r[2]), "=r"(r[3]) : "r"(addr) : "memory");
}
DEVINL void sched_fence() { asm volatile("griddepcontrol.launch_dependents;" ::: "memory"); }

struct Scratch {
  bf16 k[32 * 2048 * 32];
  bf16 xs[2048 * 1024];
  bf16 os[2048 * 1024];
  bf16 v[32 * 2048 * 32];
  float kn[2 * 128 * 16];
  uint32_t cnt[256 * 32];
  float2 stats[8 * 2048];
  uint4 halo[2 * 128 * 12 * 32];
  float csp[2 * 16 * 8 * 192];
  uint4 qsave[128 * 256 * 8];
  uint32_t esc[4 * 65536 * 20];
};
__device__ __align__(1024) Scratch g_s;
#define g_k g_s.k
#define g_xs g_s.xs
#define g_os g_s.os
#define g_v g_s.v
#define g_kn g_s.kn
#define g_cnt g_s.cnt
#define g_stats g_s.stats
#define g_halo g_s.halo
#define g_csp g_s.csp
#define g_qsave g_s.qsave
#define g_esc g_s.esc
#define g_epoch g_s.cnt[255 * 32]

DEVINL uint32_t* cnt_x(int l, int bm) { return g_cnt + (l * 8 + bm) * 32; }
DEVINL uint32_t* cnt_o(int l, int pm, int h) { return g_cnt + (32 + (l * 16 + pm) * 2 + h) * 32; }
DEVINL uint32_t* cnt_kv(int lb, int bn) { return g_cnt + (160 + lb * 16 + bn) * 32; }
DEVINL uint32_t* cnt_ad(int bn) { return g_cnt + (192 + bn) * 32; }
DEVINL uint32_t* cnt_cs(int t, int bn) { return g_cnt + (208 + t * 16 + bn) * 32; }

DEVINL int qord(int i, int l, int pn) { return l == 0 ? i : i < 4 ? ((2 * pn) ^ (i & 2)) + (i & 1) : i - 4 < 2 * (pn & 6) ? i - 4 : i; }
struct Params {
  CUtensorMap m[15];
  const bf16* x0;
  const bf16* wq[2];
  uint32_t zero;
  int map[128];
  uint64_t wd, xd;
  struct { uint64_t kd, vd; } kv[17];
};
enum { M_X0A = 0, M_XSA, M_WQA, M_WQB, M_WOA, M_WOB, M_OS, M_K, M_V, M_X0R, M_XSR, M_XSO, M_OUT, M_XST, M_X0H, M_COUNT };

constexpr uint32_t QSTG = 57344;
constexpr uint32_t T0 = 65536, TSTG = 32768;
constexpr uint32_t ONES = 230400;
constexpr uint32_t PSTG = 32768, RES = 196608;
constexpr uint32_t KSC = 98304, VSC = 133120, HRS = 167936;
constexpr uint32_t ROWST = 229376, COLS = 231424, BARS = 232192, SMEM_BYTES = 232448;
constexpr uint32_t B_QF = BARS, B_QE = BARS + 32, B_TF = BARS + 64, B_TE = BARS + 96, B_PF = BARS + 128, B_PE = BARS + 176,
                   B_RF = BARS + 224, W_X = BARS + 232, W_O = BARS + 236, B_QL = BARS + 240, B_PA = BARS + 248;
enum { NB_ST = 1, NB_KV = 2  , NB_DONE = 3, NB_SC = 4, NB_SIG = 5  , NB_KN = 9  , NB_X = 11, NB_HALO = 12  , NB_X0 = 15 };

DEVINL uint32_t pslot_b(uint32_t s) { return ((0x320415u >> (4 * s)) & 7) * 16384u; }
DEVINL uint32_t pslot_a(uint32_t s, int l) { return 98304u + ((((l & 1) ? 0x541230u : 0x041235u) >> (4 * s)) & 7) * 16384u; }

constexpr float QSCALE = 0.17677669529663687f * 1.4426950408889634f;
constexpr uint32_t QPARK = 32768;

DEVINL uint32_t exp2_h2(uint32_t s, uint32_t c882) {
  uint32_t r, t, w, m, d;
  asm volatile("{.reg .b64 t; add.rn.f16x2 %0, %1, %2; cvt.u64.u32 t, %0; cvt.u32.u64 %0, t;}" : "=r"(r) : "r"(s), "r"(0x65F565F5u));
  asm volatile("fma.rn.f16x2 %0, %1, %2, %3;" : "=r"(t) : "r"(r), "r"(0xB8A0B8A0u), "r"(c882));
  asm volatile("fma.rn.f16x2 %0, %1, %2, %3;" : "=r"(w) : "r"(s), "r"(0x38A038A0u), "r"(t));
  asm volatile("fma.rn.f16x2 %0, %1, %1, %2;" : "=r"(m) : "r"(w), "r"(0x48244833u));
  asm volatile("{.reg .b32 t; shf.l.clamp.b32 t, %2, %1, 7; add.u32 %0, t, %2;}" : "=r"(d) : "r"(r), "r"(m));
  return d;
}
DEVINL float exp2_fix(float s) { float z; asm volatile("add.rn.f32 %0, %1, 0f43BF34BC;" : "=f"(z) : "f"(s)); return z; }
DEVINL uint32_t exp2_base(float z0, float z1) { uint32_t B; asm volatile("prmt.b32 %0, %1, %2, 0x6521;" : "=r"(B) : "r"(__float_as_uint(z0)), "r"(__float_as_uint(z1))); return B; }
template <uint32_t MASK> DEVINL uint32_t and_or(uint32_t a, uint32_t c) { uint32_t r; asm volatile("lop3.b32 %0, %1, %3, %2, 0xEA;" : "=r"(r) : "r"(a), "r"(c), "n"(MASK)); return r; }
DEVINL uint32_t fma_bf2(uint32_t a, uint32_t b, uint32_t c) { uint32_t r; asm volatile("fma.rn.bf16x2 %0, %1, %2, %3;" : "=r"(r) : "r"(a), "r"(b), "r"(c)); return r; }
DEVINL float ex2v(float x) { float y; asm volatile("ex2.approx.ftz.f32 %0, %1;" : "=f"(y) : "f"(x)); return y; }
DEVINL uint32_t pack2v(float lo, float hi) { uint32_t r; asm volatile("cvt.rn.bf16x2.f32 %0, %1, %2;" : "=r"(r) : "f"(hi), "f"(lo)); return r; }
DEVINL void unesc(uint32_t (&u)[4], const uint32_t* esc, uint32_t tag) {
  const bool saved = __ldcg(esc + 16) == tag;
#pragma unroll
  for (int j = 0; j < 4; j++) {
    float lo, hi;
    asm("{.reg .f16 a, b; mov.b32 {a, b}, %2; cvt.f32.f16 %0, a; cvt.f32.f16 %1, b;}" : "=f"(lo), "=f"(hi) : "r"(u[j]));
    u[j] = saved ? __ldcg(esc + 4 * j) : pack2(lo, hi);
  }
}

DEVINL void attn_slow(const uint32_t (&q)[8], int head, const uint32_t* kesc, uint32_t tag, float (&res)[20], int lane) {
  const int g = lane >> 2, qd = lane & 3;
  const bf16* kb = g_k + (size_t)head * 2048 * 32;
  const bf16* vb = g_v + (size_t)head * 2048 * 32;
  float o[4][4], m0 = -INFINITY, m1 = -INFINITY, l0 = 0.f, l1 = 0.f;
#pragma unroll
  for (int j = 0; j < 4; j++) { o[j][0] = o[j][1] = o[j][2] = o[j][3] = 0.f; }
#pragma unroll 1
  for (int k0 = 0; k0 < 2048; k0 += 16) {
    float s[2][4];
#pragma unroll
    for (int nt = 0; nt < 2; nt++) {
      s[nt][0] = s[nt][1] = s[nt][2] = s[nt][3] = 0.f;
      const uint32_t* kp = (const uint32_t*)(kb + (size_t)(k0 + nt * 8 + g) * 32) + qd;
      uint32_t k[4] = {__ldcg(kp), __ldcg(kp + 4), __ldcg(kp + 8), __ldcg(kp + 12)};
      unesc(k, kesc + (k0 + nt * 8 + g) * 20 + qd, tag);
      __syncwarp();
      mma16816(s[nt], q[0], q[1], q[2], q[3], k[0], k[1]);
      mma16816(s[nt], q[4], q[5], q[6], q[7], k[2], k[3]);
    }
    float a0 = fmaxf(fmaxf(s[0][0], s[0][1]), fmaxf(s[1][0], s[1][1]));
    float a1 = fmaxf(fmaxf(s[0][2], s[0][3]), fmaxf(s[1][2], s[1][3]));
    a0 = fmaxf(a0, __shfl_xor_sync(~0u, a0, 1)); a0 = fmaxf(a0, __shfl_xor_sync(~0u, a0, 2));
    a1 = fmaxf(a1, __shfl_xor_sync(~0u, a1, 1)); a1 = fmaxf(a1, __shfl_xor_sync(~0u, a1, 2));
    const float n0 = fmaxf(m0, a0), n1 = fmaxf(m1, a1);
    const float c0 = (m0 == n0) ? 1.f : ex2(m0 - n0), c1 = (m1 == n1) ? 1.f : ex2(m1 - n1);
    m0 = n0; m1 = n1;
    const uint32_t p0 = pack2(ex2(s[0][0] - n0), ex2(s[0][1] - n0)), p1 = pack2(ex2(s[0][2] - n1), ex2(s[0][3] - n1));
    const uint32_t p2 = pack2(ex2(s[1][0] - n0), ex2(s[1][1] - n0)), p3 = pack2(ex2(s[1][2] - n1), ex2(s[1][3] - n1));
    l0 = l0 * c0 + bf_lo(p0) + bf_hi(p0) + bf_lo(p2) + bf_hi(p2);
    l1 = l1 * c1 + bf_lo(p1) + bf_hi(p1) + bf_lo(p3) + bf_hi(p3);
#pragma unroll
    for (int j = 0; j < 4; j++) {
      o[j][0] *= c0; o[j][1] *= c0; o[j][2] *= c1; o[j][3] *= c1;
      const unsigned short* vp = (const unsigned short*)(vb + (size_t)(k0 + 2 * qd) * 32 + j * 8 + g);
      const uint32_t b0 = (uint32_t)__ldcg(vp) | ((uint32_t)__ldcg(vp + 32) << 16);
      const uint32_t b1 = (uint32_t)__ldcg(vp + 256) | ((uint32_t)__ldcg(vp + 288) << 16);
      mma16816(o[j], p0, p1, p2, p3, b0, b1);
    }
  }
  l0 += __shfl_xor_sync(~0u, l0, 1); l0 += __shfl_xor_sync(~0u, l0, 2);
  l1 += __shfl_xor_sync(~0u, l1, 1); l1 += __shfl_xor_sync(~0u, l1, 2);
#pragma unroll
  for (int j = 0; j < 4; j++) { res[4 * j] = o[j][0]; res[4 * j + 1] = o[j][1]; res[4 * j + 2] = o[j][2]; res[4 * j + 3] = o[j][3]; }
  res[16] = l0; res[18] = l1;
}

__device__ __noinline__ void attn_redo(int redo, int l, int b, int wg, int w, uint32_t tag) {
  const int lane = lane_id();
#pragma unroll 1
  for (int t = 0; t < 4; t++) {
    const int h = t >> 1, head = 2 * (b & 15) + h, row = (b >> 4) * 256 + wg * 128 + (t & 1) * 64 + w * 16 + (lane >> 2);
    if ((redo >> t) & 1) {
      const uint32_t* esc = g_esc + (size_t)((l & 2) * 65536 + head * 2048) * 20;
      const uint32_t* qs = (const uint32_t*)(g_qsave + (block_id() * 256 + wg * 128 + w * 32 + lane) * 8 + 2 * t);
      uint32_t q[8]; float o[20];
#pragma unroll
      for (int i = 0; i < 2; i++) {
        uint32_t u[4] = {__ldcg(qs + i), __ldcg(qs + i + 2), __ldcg(qs + i + 4), __ldcg(qs + i + 6)};
        unesc(u, esc + (row + i * 8) * 20 + (lane & 3), tag);
        q[i] = u[0]; q[i + 2] = u[1]; q[i + 4] = u[2]; q[i + 6] = u[3];
      }
      __syncwarp();
      attn_slow(q, head, esc + 65536 * 20, tag, o, lane);
      const float i0 = rcp(o[16]), i1 = rcp(o[18]);
      bf16* op = g_os + (size_t)row * 1024 + h * 512 + (b & 15) * 32 + (lane & 3) * 8;
      *(uint4*)op = make_uint4(pack2(o[0] * i0, o[1] * i0), pack2(o[4] * i0, o[5] * i0), pack2(o[8] * i0, o[9] * i0), pack2(o[12] * i0, o[13] * i0));
      *(uint4*)(op + 8 * 1024) = make_uint4(pack2(o[2] * i1, o[3] * i1), pack2(o[6] * i1, o[7] * i1), pack2(o[10] * i1, o[11] * i1), pack2(o[14] * i1, o[15] * i1));
    }
    if ((t & 1) && ((redo >> 2 * h) & 3)) bar_arrive(NB_SIG + 2 * h + wg, 160);
  }
}

__global__ void __cluster_dims__(2, 1, 1) __launch_bounds__(384, 1) fused_kernel(const __grid_constant__ Params prm) {
  extern __shared__ __align__(1024) char smem[];
  const uint32_t sb = (uint32_t)__cvta_generic_to_shared(smem);
  const int tid = threadIdx.x, lane = tid & 31;
  const int wg = __shfl_sync(0xffffffffu, tid >> 7, 0);
  const int w = __shfl_sync(0xffffffffu, (tid >> 5) & 3, 0);
  const int bm = remap(blockIdx.x) >> 4, bn = remap(blockIdx.x) & 15;

  auto first_tile = [&](int kt) {
    e_expect_tx(sb + B_QF + 8 * kt, QSTG);
    tma_ld(sb + kt * QSTG, &prm.m[M_X0A], kt * 64, bm * 256, sb + B_QF + 8 * kt);
    tma_ld3(sb + kt * QSTG + 32768, &prm.m[M_WQA], bn * 64, kt * 64, 0, sb + B_QF + 8 * kt);
  };
  auto init4 = [&](uint32_t bar, uint32_t c0, uint32_t c1, uint32_t c2, uint32_t c3) {
    asm volatile("{\n.reg .pred pe;\nelect.sync _|pe, 0xffffffff;\n@pe mbarrier.init.shared::cta.b64 [%0], %1;\n@pe mbarrier.init.shared::cta.b64 [%0+8], %2;\n"
                 "@pe mbarrier.init.shared::cta.b64 [%0+16], %3;\n@pe mbarrier.init.shared::cta.b64 [%0+24], %4;\n@pe fence.mbarrier_init.release.cluster;\n}"
                 ::"r"(bar), "r"(c0), "r"(c1), "r"(c2), "r"(c3) : "memory");
  };
  if (wg < 2) {
    const uint32_t k = wg * 4 + w, lo = (0x1411814u >> (4 * k)) & 15, hi = (0x1441814u >> (4 * k)) & 15;
    if (tid < 32) asm volatile("prefetch.global.L2 [%0];" ::"l"(prm.x0 + (size_t)(bm * 256 + bn * 16 + (tid & 15)) * 1024 + (tid >> 4) * 64));
    else if (tid < 80) asm volatile("prefetch.global.L2 [%0];" ::"l"(prm.wq[0] + (bm * 16 + (tid & 15)) * 3072 + ((tid >> 4) - 2) * 1024 + bn * 64));
    __syncwarp();
    if (k < 7) init4(sb + B_QE + 32 * k, lo, lo, hi, k == 6 ? 2 : hi);
    __syncwarp();
    if (k == 6 && lane == 0) *(volatile unsigned long long*)(smem + W_X) = 0ull;
  } else if (w == 0) {
    init4(sb + B_QF, 1, 1, 1, 1);
    __syncwarp();
    first_tile(0);
  }
  __syncthreads();
  asm volatile("barrier.cluster.arrive.relaxed.aligned;" ::: "memory");

  if (wg == 2) {
    asm volatile("setmaxnreg.dec.sync.aligned.u32 56;");
    const uint32_t ep1 = *(volatile uint32_t*)&g_epoch + 1;
    if (w == 0) {
      first_tile(1);
      mbar_wait(sb + B_QF, 0);
      first_tile(2); first_tile(3);
#pragma unroll 1
      for (int kt = 4; kt < 16; kt++) l2_prefetch(prm.wq[0] + kt * 196608 + blockIdx.x * 1536, 3072);
      cluster_wait();
#pragma unroll 1
      for (int l = 0; l < 4; l++) {
        IDS();
        const CUtensorMap* mw = &prm.m[M_WQA + (l & 1)];
        const CUtensorMap* mx = &prm.m[l == 0 ? M_X0A : M_XSA];
        const CUtensorMap* mh = &prm.m[l == 0 ? M_X0H : M_XSO];
        const CUtensorMap* mo = &prm.m[M_WOA + (l & 1)];
        auto q_b = [&](int i) {
          const int s = i & 3;
          mbar_wait(sb + B_QE + 8 * s, ((i >> 2) & 1) ^ 1);
          e_expect_tx(sb + B_QF + 8 * s, QSTG);
          tma_ld3(sb + s * QSTG + 32768, mw, bn * 64, qord(i, l, pn) * 64, 0, sb + B_QF + 8 * s);
        };
        uint32_t rdy = l ? 0u : ~0u;
        auto q_a = [&](int i) {
          const int kt = qord(i, l, pn);
          await_bit(sb + W_X, l, kt >> 1, rdy);
          if (i < 4) tma_ld(sb + i * QSTG, mx, kt * 64, bm * 256, sb + B_QF + 8 * i);
          else tma_ld_mc(sb + (i & 3) * QSTG + rank * 16384, mh, kt * 64, bm * 256 + rank * 128, sb + B_QF + 8 * (i & 3));
        };
        if (l > 0) {
          await_bit(sb + W_X, l, pn, rdy);
#pragma unroll 1
          for (int i = 0; i < 2; i++) {
            e_expect_tx(sb + B_QF + 8 * i, 16384);
            tma_ld(sb + i * QSTG + (po ^ 1) * 16384, &prm.m[M_XSO], (2 * pn + i) * 64, (pm ^ 1) * 128, sb + B_QF + 8 * i);
          }
          mbar_wait(sb + B_QF, 0);
          q_a(2);
          mbar_wait(sb + B_QF + 8, 0);
        }
#pragma unroll 1
        for (int i = l ? 3 : 4; i < 16; i++) {
          if (l == 3 && i == 12) poll_ge(cnt_ad(bn), ep1 * 16);
          q_b(i); q_a(i);
        }
        if (l & 1) {
          bar_sync(NB_KV, 288);
          sts128(sb + ONES + lane * 32, 0x3f803f80u, 0x3f803f80u, 0x3f803f80u, 0x3f803f80u);
          sts128(sb + ONES + lane * 32 + 16, 0x3f803f80u, 0x3f803f80u, 0x3f803f80u, 0x3f803f80u);
          fence_async_smem();
          __syncwarp();
          e_arrive(sb + B_TF);
          const int krow = 2 * bn * 2048 + bm * 256;
          uint32_t* kvc = cnt_kv(l >> 1, bn);
          uint32_t seen = 0;
#pragma unroll 1
          for (int it = 1; it < 16; it++) {
            const int s = it & 3;
            if (it == 4) {
              bar_sync(NB_KV + 12, 288);
              mbar_wait(sb + B_TF + 24, 0);
#pragma unroll 1
              for (int i = 0; i < 4; i++) tma_st(&prm.m[M_K + (i >> 1)], 0, krow + 2048 + (i & 1) * 128, sb + i * 8192);
              bulk_commit();
            }
            if (it == 5) { bulk_wait_n<0>(); e_red(kvc + 16 + bm); }
            if (it == 12) { e_expect_tx(sb + B_RF, 32768); tma_ld3(sb + RES, &prm.m[M_XSR], 0, pm * 128, 2 * pn, sb + B_RF); }
            mbar_wait(sb + B_TE + 8 * s, ((it >> 2) & 1) ^ 1);
            if (it < 8) {
#pragma unroll 1
              for (uint32_t n = 0; n < 200000u && (~seen & (3u << (2 * it - 2) | (it == 4 ? 0xC000u : 0u))); n++)
                seen = __ballot_sync(~0u, (int)(ld_acquire(kvc + (lane < 7 || lane == 15 ? (bm + 1 + lane) & 7 : 8 + ((bm + 2 + lane) & 7))) - ep1) >= 0);
              fence_async_gl();
            } else if (it == 8) { poll_ge(kvc + 16 + (lane & 7), ep1); fence_async_gl(); }
            e_expect_tx(sb + B_TF + 8 * s, 32768);
#pragma unroll 1
            for (int i = 0; i < 2; i++) {
              const int u = 2 * it - 2 + i;
              const int row = 2 * bn * 2048 + (it > 7 ? 2048 + ((bm + it) & 7) * 256 + i * 128 : u < 7 ? ((bm + 1 + u) & 7) * 256 : ((bm + 2 + u) & 7) * 256 + 128);
              tma_ld(sb + T0 + s * TSTG + i * 8192, &prm.m[M_K], 0, row, sb + B_TF + 8 * s);
              tma_ld(sb + T0 + s * TSTG + 16384 + i * 8192, &prm.m[M_V], 0, row, sb + B_TF + 8 * s);
            }
          }
        }
        auto p_b = [&](int i, uint32_t s, uint32_t par) {
          mbar_wait(sb + B_PE + 8 * s, par ^ 1);
          e_expect_tx(sb + B_PF + 8 * s, PSTG);
          tma_ld5(sb + pslot_b(s), mo, i >> 3, 2 * (i & 7), 2 * pn, sb + B_PF + 8 * s);
        };
        auto p_a = [&](int i, uint32_t s) {
          await_bit(sb + W_O, l + 1, i, rdy);
          tma_ld_mc(sb + pslot_a(s, l) + rank * 8192, &prm.m[M_OS], i * 64, pm * 128 + rank * 64, sb + B_PF + 8 * s);
        };
        auto p_a2 = [&](int i) {
          await_bit(sb + W_O, l + 1, i, rdy);
          tma_ld(sb + pslot_a(i, l), &prm.m[M_OS], i * 64, pm * 128, sb + B_PF + 8 * i);
          tma_ld(sb + pslot_a(i, l) + 8192, &prm.m[M_OS], i * 64, pm * 128 + 64, sb + B_PF + 8 * i);
        };
        rdy = 0;
        if (l & 1) {
#pragma unroll 1
          for (int u = 0; u < 6; u++) { const int i = (0x205413 >> (4 * u)) & 7; if (u == 4) mbar_wait(sb + B_TE, 1); p_b(i, i, i < 4 ? 1 : 0); }
#pragma unroll 1
          for (int u = 0; u < 6; u++) {
            const int i = (0x542130 >> (4 * u)) & 7;
            if (!(u & 1)) mbar_wait(sb + B_TE + 8 + 4 * u, 1);
            if (u == 4) bar_sync(NB_ST, 64);
            p_a2(i);
          }
        } else {
#pragma unroll 1
          for (int u = 0; u < 6; u++) { const int i = (0x025413 >> (4 * u)) & 7; if (u == 0 || u == 3) mbar_wait(sb + B_QE + 8 * (u / 3), 1); p_b(i, i, 0); }
          mbar_wait(sb + B_QE + 24, 1);
          e_expect_tx(sb + B_RF, 32768);
          tma_ld3(sb + RES, &prm.m[l == 0 ? M_X0R : M_XSR], 0, pm * 128, 2 * pn, sb + B_RF);
          p_a2(0);
          bar_sync(NB_DONE, 64);
          e_arrive_both(sb + B_PA);
          p_a2(1);
          mbar_wait(sb + B_PA, (l >> 1) & 1);
#pragma unroll 1
          for (int i = 2; i < 6; i++) { if (i > 2) mbar_wait(sb + B_PF + 8 * (i - 3), 0); p_a(i, i); }
        }
        uint32_t s = 0, lap = 1;
#pragma unroll 1
        for (int i = 6; i < 16; i++) {
          p_b(i, s, ((s < 4 ? l : 0) + lap) & 1);
          p_a(i, s);
          if (++s == 6) { s = 0; lap++; }
        }
        const CUtensorMap* mn = &prm.m[M_WQA + ((l + 1) & 1)];
        if (l < 3) {
          mbar_wait(sb + B_PE + 8 * 4, 1); mbar_wait(sb + B_PE + 8 * 5, 1);
          tma_ld3(sb + 32768, mn, bn * 64, 2 * pn * 64, 0, sb + B_QL);
          mbar_wait(sb + B_PE + 8 * 0, l & 1);
          tma_ld3(sb + QSTG + 32768, mn, bn * 64, (2 * pn + 1) * 64, 0, sb + B_QL);
          mbar_wait(sb + B_PE + 8 * 1, l & 1);
          e_expect_tx(sb + B_QF + 16, QSTG);
          tma_ld3(sb + 2 * QSTG + 32768, mn, bn * 64, ((2 * pn) ^ 2) * 64, 0, sb + B_QF + 16);
        }
        if (l < 3) { bar_sync(NB_X, 288); e_expect_tx(sb + B_QL, 49152); }
      }
      if (blockIdx.x == 0 && lane_id() == 0) *(volatile uint32_t*)&g_epoch = ep1;
    } else {
      const int hw = w - 1;
      if (lane < 5) asm volatile("prefetch.tensormap [%0];" ::"l"(&prm.m[5 * hw + lane]) : "memory");
      __syncwarp();
      cluster_wait();
      mbar_wait(sb + B_QF, 0);
#pragma unroll 1
      for (int l = 0; l < 4; l++) {
        IDS();
        if (hw == 2 && l > 0) watch(cnt_x(l, bm) + (lane & 7), ep1 * 2, 0xFFu, l, sb + W_X);
        if (l == 0) {
#pragma unroll 1
          for (int r = 2 * hw; r < 16; r += 6) {
            const uint4* p = (const uint4*)(prm.x0 + (size_t)(b * 16 + r) * 1024) + lane;
            float s1[2] = {0.f, 0.f}, s2[2] = {0.f, 0.f};
#pragma unroll
            for (int i = 0; i < 8; i++) {
              const uint4 v = __ldg(p + 32 * i);
              const uint32_t u[4] = {v.x, v.y, v.z, v.w};
#pragma unroll
              for (int k = 0; k < 4; k++) { const float a = bf_lo(u[k]), c = bf_hi(u[k]); s1[i >> 2] += a + c; s2[i >> 2] = fmaf(a, a, fmaf(c, c, s2[i >> 2])); }
            }
#pragma unroll
            for (int o = 16; o; o >>= 1)
#pragma unroll
              for (int rr = 0; rr < 2; rr++) { s1[rr] += __shfl_xor_sync(~0u, s1[rr], o); s2[rr] += __shfl_xor_sync(~0u, s2[rr], o); }
            if (lane == 0) *(float4*)&g_stats[b * 16 + r] = make_float4(s1[0], s2[0], s1[1], s2[1]);
          }
        }
        if (l == 1) { uint32_t rdy = 0; await_bit<true>(sb + W_X, 1, pn, rdy); mbar_hint(sb + B_QF + 8, 0); }
        if (l < 2) {
          float cs[8];
#pragma unroll
          for (int i = 0; i < 8; i++) cs[i] = 0.f;
          const uint4* wp = (const uint4*)(prm.wq[l] + (size_t)(bm * 128 + (lane >> 3)) * 3072 + hw * 1024 + bn * 64) + (lane & 7);
#pragma unroll 8
          for (int i = 0; i < 32; i++) {
            const uint4 v = __ldg(wp + (size_t)i * 4 * 384);
            cs[0] += bf_lo(v.x); cs[1] += bf_hi(v.x); cs[2] += bf_lo(v.y); cs[3] += bf_hi(v.y);
            cs[4] += bf_lo(v.z); cs[5] += bf_hi(v.z); cs[6] += bf_lo(v.w); cs[7] += bf_hi(v.w);
          }
#pragma unroll
          for (int i = 0; i < 8; i++) { cs[i] += __shfl_xor_sync(~0u, cs[i], 8); cs[i] += __shfl_xor_sync(~0u, cs[i], 16); }
          if (lane < 8) {
            float4* d = (float4*)(g_csp + ((l * 16 + bn) * 8 + bm) * 192 + hw * 64 + lane * 8);
            d[0] = make_float4(cs[0], cs[1], cs[2], cs[3]); d[1] = make_float4(cs[4], cs[5], cs[6], cs[7]);
          }
          __syncwarp();
          asm volatile("fence.acq_rel.gpu;" ::: "memory");
          e_red_relaxed(cnt_cs(l, bn));
          if (l == 0) e_red_relaxed(cnt_x(0, bm) + pn);
          poll_ge(lane < 8 && l == 0 ? cnt_x(0, bm) + lane : cnt_cs(l, bn), ep1 * (lane < 8 && l == 0 ? 6 : 24));
        }
        if (l > 0) {
          uint32_t rdy = 0;
#pragma unroll 1
          for (int j = 0; j < 8; j++) await_bit<true>(sb + W_X, l, j, rdy);
        }
#pragma unroll 1
        for (int it = hw * 32 + lane; it < 176; it += 96) {
          const bool rows = it < 128;
          const float4* p = rows ? (const float4*)(g_stats + bm * 256) + it : (const float4*)(g_csp + ((l & 1) * 16 + bn) * 8 * 192) + (it - 128);
          const int stride = rows ? 1024 : 48, np = rows && l == 0 ? 1 : 8;
          float4 a = make_float4(0.f, 0.f, 0.f, 0.f);
#pragma unroll
          for (int k = 0; k < 8; k++) if (k < np) { const float4 v = __ldcg(p + k * stride); a.x += v.x; a.y += v.y; a.z += v.z; a.w += v.w; }
          if (rows) {
            const float m0 = a.x * (1.f / 1024.f), m1 = a.z * (1.f / 1024.f);
            const float v0 = fmaxf(a.y * (1.f / 1024.f) - m0 * m0, 0.f), v1 = fmaxf(a.w * (1.f / 1024.f) - m1 * m1, 0.f);
            const float r0 = __fdividef(1.f, bf_round(sqrtf(bf_round(bf_round(v0) + 1e-5f)))), r1 = __fdividef(1.f, bf_round(sqrtf(bf_round(bf_round(v1) + 1e-5f))));
            a = make_float4(r0, -bf_round(m0) * (l & 1 ? r0 : 1.f), r1, -bf_round(m1) * (l & 1 ? r1 : 1.f));
          }
          *(float4*)(smem + ROWST + it * 16) = a;
        }
        __syncwarp();
        if (lane == 0) asm volatile("red.release.cta.shared.add.u32 [%0], 0x100;" ::"r"(sb + W_X) : "memory");
        if (hw == 2) {
          if (!(l & 1)) {
            bar_sync(NB_ST, 288);
            const uint4* hp = g_halo + ((l >> 1) * 128 + b - 16) * 384 + lane;
#pragma unroll 1
            for (int h = 0; h < 2; h++) {
              uint32_t t[18];
#pragma unroll
              for (int i = 0; i < 18; i++) t[i] = 0;
#pragma unroll 1
              for (uint32_t n = bm ? 0 : 100000u; n < 100000u; n++) {
                uint32_t miss = 0;
#pragma unroll
                for (int i = 0; i < 6; i++) miss |= ld_tagged(hp + h * 192 + i * 32, &t[3 * i]) ^ ep1;
                if (__all_sync(~0u, !miss)) break;
              }
              mbar_wait(sb + B_QE + 16, 1);
              const uint32_t r = (lane & 7) + ((lane >> 3) & 1) * 8, rv = lane >> 2;
#pragma unroll
              for (int jj = 0; jj < 2; jj++) stsm4(sb + KSC + r * 128 + (((4 * h + 2 * jj + (lane >> 4)) ^ (r & 7)) << 4), t[4 * jj], t[4 * jj + 1], t[4 * jj + 2], t[4 * jj + 3]);
              const uint32_t ad = sb + VSC + rv * 128 + (((4 * h + (lane & 3)) ^ (rv & 7)) << 4);
              sts128(ad, t[8], t[10], t[12], t[14]); sts128(ad + 1024, t[9], t[11], t[13], t[15]);
              if (h == 0 && !(lane & 2)) *(uint32_t*)(smem + HRS + ((lane >> 2) + 8 * (lane & 1)) * 8) = t[16];
              bar_arrive(NB_HALO + h, 64);
            }
          } else {
            mbar_wait(sb + B_TF + 16, 0); mbar_wait(sb + B_TF + 16, 1);
            poll_ge(cnt_kv(l >> 1, bn) + 16 + (lane & 7), ep1);
            const uint4 v = __ldcg((const uint4*)(g_kn + ((l >> 1) * 128 + bn * 8) * 16) + lane);
            const uint32_t mx = max(max(v.x, v.y), max(v.z, v.w));
            const uint32_t m0 = __reduce_max_sync(~0u, (lane & 2) ? 0u : mx), m1 = __reduce_max_sync(~0u, (lane & 2) ? mx : 0u);
            if (lane == 0) *(uint2*)(smem + ROWST) = make_uint2(m0, m1);
            __syncwarp();
            bar_arrive(NB_KN, 160); bar_arrive(NB_KN + 1, 160);
            mbar_wait(sb + B_TF + 16, 0); mbar_wait(sb + B_TF + 16, 1);
          }
        } else {
          if (l & 1) {
            bar_sync(hw ? NB_HALO : NB_DONE, 160);
            tma_st(&prm.m[M_K], 0, 2 * bn * 2048 + bm * 256 + hw * 128, sb + T0 + hw * 8192);
            tma_st(&prm.m[M_V], 0, 2 * bn * 2048 + bm * 256 + hw * 128, sb + T0 + 16384 + hw * 8192);
            bulk_commit(); bulk_wait_n<0>();
            e_red(cnt_kv(l >> 1, bn) + 8 * hw + bm);
          }
#pragma unroll 1
          for (int i = 0; i < 2; i++) {
            const int h = l & 1 ? i : hw, g = l & 1 ? hw : i;
            bar_sync(NB_SIG + 2 * h + g, 160);
            if (!(l & 1) && i == 0) continue;
            if (i == 1 && hw == 1) bar_arrive(l & 1 ? NB_ST : NB_DONE, 64);
            asm volatile("fence.acq_rel.gpu;" ::: "memory");
            e_red_relaxed(cnt_o(l, 2 * bm + g, h) + (bn >> 1));
            if (!(l & 1)) e_red_relaxed(cnt_o(l, 2 * bm, h) + (bn >> 1));
            if (h == 1 && l == 1) e_red_relaxed(cnt_ad(bn));
          }
        }
        if (hw == 2) watch(cnt_o(l, pm, (lane >> 3) & 1) + (lane & 7), ep1 * 2, 0xFFFFu, l + 1, sb + W_O);
        if (hw == 0 && l < 3) {
          bar_sync(NB_X0, 288);
          e_red(cnt_x(l + 1, bm) + pn);
        }
      }
    }
  } else {
    asm volatile("setmaxnreg.inc.sync.aligned.u32 224;");
    const uint32_t zero = prm.zero;
    cluster_wait();
#pragma unroll 1
    for (int l = 0; l < 4; l++) {
      {
        float acc[2][96];
#pragma unroll
        for (int i = 0; i < 96; i++) { acc[0][i] = 0.f; acc[1][i] = 0.f; }
        fence_regs(acc[0]); fence_regs(acc[1]);
        const bool early = l > 0 && wg == ((cta_id() >> 3) & 1);
        uint32_t ep1 = 0;
#pragma unroll 1
        for (int kt = 0; kt < 14; kt++) {
          const int s = kt & 3;
          if (l > 0 && kt == 0) mbar_wait(sb + B_QL, (l + 1) & 1);
          if (!(early && kt < 2)) mbar_wait(sb + B_QF + 8 * s, (kt >> 2) & 1);
          const uint64_t da = prm.xd + wg * 1024 + s * (QSTG >> 4), db = prm.wd + s * (QSTG >> 4);
          wg_fence();
#pragma unroll
          for (int k = 0; k < 4; k++)
#pragma unroll
            for (int m = 0; m < 2; m++) wgmma_m64n192k16_ss_tb(acc[m], da + m * 512 + k * 2, db + k * 128, 1);
          wg_commit();
          if (kt == 4) ep1 = *(volatile uint32_t*)&g_epoch + 1;
          wg_wait<1>();
          if (early && (kt == 1 || kt == 2)) mbar_wait(sb + B_QF + 8 * (kt - 1), 0);
          if (kt > 0 && w == 0) e_arrive_both(sb + B_QE + 8 * ((kt - 1) & 3));
        }
        {
          const bool lag = (l & 1) && wg;
          const uint64_t da = prm.xd + wg * 1024 + 2 * (QSTG >> 4), db = prm.wd + 2 * (QSTG >> 4);
          mbar_wait(sb + B_QF + 16, 1);
          if (lag) {
            mbar_wait(sb + B_QF + 24, 1);
            wg_wait<0>();
            if (w == 0) e_arrive_both(sb + B_QE + 8);
            bar_sync(NB_SC, 256);
          }
          wg_fence();
#pragma unroll
          for (int k = 0; k < 4; k++)
#pragma unroll
            for (int m = 0; m < 2; m++) wgmma_m64n192k16_ss_tb(acc[m], da + m * 512 + k * 2, db + k * 128, 1);
          wg_commit();
          if (!lag) {
            wg_wait<1>();
            if (w == 0) e_arrive_both(sb + B_QE + 8);
            mbar_wait(sb + B_QF + 24, 1);
          }
          wg_fence();
#pragma unroll
          for (int m = 1; m >= 0; m--) {
#pragma unroll
            for (int k = 0; k < 4; k++) wgmma_m64n192k16_ss_tb(acc[m], da + (QSTG >> 4) + m * 512 + k * 2, db + (QSTG >> 4) + k * 128, 1);
            wg_commit();
          }
          if ((l & 1) && !wg) bar_arrive(NB_SC, 256);
          if (!(l & 1)) bar_arrive(NB_ST, 288);
          wg_wait<2>();
          if (w == 0) e_arrive_both(sb + B_QE + 16);
        }
#pragma unroll 1
        for (uint32_t n = 0; n < 4000000u; n++) {
          uint32_t v;
          asm volatile("ld.acquire.cta.shared.u32 %0, [%1];" : "=r"(v) : "r"(sb + W_X) : "memory");
          if ((v >> 8) == (uint32_t)(l * 256 + 3)) break;
        }
        IDS();
        const int g = lane >> 2, qd = lane & 3;
        float2 st[2][2];
#pragma unroll
        for (int m = 0; m < 2; m++)
#pragma unroll
          for (int hh = 0; hh < 2; hh++) st[m][hh] = lds64f(sb + ROWST + (wg * 128 + m * 64 + w * 16 + g + 8 * hh) * 8);
        float2 cs[4];
        auto load_cs = [&](int gi) {
#pragma unroll
          for (int j = 0; j < 4; j++) cs[j] = lds64f(sb + COLS + (gi * 32 + j * 8 + 2 * qd) * 4);
        };
        load_cs(2);
        auto drain = [&]() {
          wg_wait<0>(); fence_regs(acc[0]);
          if (w == 0) e_arrive_both(sb + B_QE + 8 * 3);
        };
        wg_wait<1>(); fence_regs(acc[1]);
        auto norm_tile = [&](int gi, int m, float sc, uint32_t (&t)[8], float (&nrm)[2], bool h16 = false) {
          const float r0 = st[m][0].x * sc, s0 = st[m][0].y * sc, r1 = st[m][1].x * sc, s1 = st[m][1].y * sc;
          float n0 = 0.f, n1 = 0.f;
#pragma unroll
          for (int j = 0; j < 4; j++) {
            const float* a = &acc[m][16 * gi + 4 * j];
            const float v0 = fmaf(a[0], r0, s0 * cs[j].x), v1 = fmaf(a[1], r0, s0 * cs[j].y);
            const float v2 = fmaf(a[2], r1, s1 * cs[j].x), v3 = fmaf(a[3], r1, s1 * cs[j].y);
            n0 = fmaf(v0, v0, fmaf(v1, v1, n0)); n1 = fmaf(v2, v2, fmaf(v3, v3, n1));
            t[2 * j] = h16 ? pack2h(v0, v1) : pack2(v0, v1); t[2 * j + 1] = h16 ? pack2h(v2, v3) : pack2(v2, v3);
          }
          nrm[0] = n0; nrm[1] = n1;
        };
        auto norm_group = [&](int gi, float sc, uint32_t (&t)[2][8], float (&nrm)[2][2]) { norm_tile(gi, 0, sc, t[0], nrm[0]); norm_tile(gi, 1, sc, t[1], nrm[1]); };
        uint32_t q[2][2][8];
        const uint32_t srow = (lane & 7) + ((lane >> 3) & 1) * 8;
        const uint32_t row0 = wg * 128 + w * 16;
        auto put_o = [&](int h, int m, const float (&o)[16], float i0, float i1) {
          IDS();
          bf16* op = g_os + (size_t)(bm * 256 + row0 + m * 64 + (lane >> 2)) * 1024 + h * 512 + bn * 32 + (lane & 3) * 8;
          *(uint4*)op = make_uint4(pack2(o[0] * i0, o[1] * i0), pack2(o[4] * i0, o[5] * i0), pack2(o[8] * i0, o[9] * i0), pack2(o[12] * i0, o[13] * i0));
          *(uint4*)(op + 8 * 1024) = make_uint4(pack2(o[2] * i1, o[3] * i1), pack2(o[6] * i1, o[7] * i1), pack2(o[10] * i1, o[11] * i1), pack2(o[14] * i1, o[15] * i1));
        };
        if (!(l & 1)) {
          auto put_kv = [&](int gi, uint32_t r0, const uint32_t (&t)[8]) {
            if (gi < 4) {
              const uint32_t r = r0 + srow;
#pragma unroll
              for (int jj = 0; jj < 2; jj++) stsm4(sb + KSC + r * 128 + (((4 * (gi - 2) + 2 * jj + (lane >> 4)) ^ (r & 7)) << 4), t[4 * jj], t[4 * jj + 1], t[4 * jj + 2], t[4 * jj + 3]);
            } else {
              const uint32_t r = r0 + g, ad = sb + VSC + r * 128 + (((4 * (gi - 4) + qd) ^ (r & 7)) << 4);
              sts128(ad, t[0], t[2], t[4], t[6]); sts128(ad + 1024, t[1], t[3], t[5], t[7]);
            }
          };
          auto cen_tile = [&](int gi, int m, uint32_t (&t)[8]) {
#pragma unroll
            for (int j = 0; j < 4; j++) {
              const float* a = &acc[m][16 * gi + 4 * j];
              t[2 * j] = pack2(fmaf(st[m][0].y, cs[j].x, a[0]), fmaf(st[m][0].y, cs[j].y, a[1]));
              t[2 * j + 1] = pack2(fmaf(st[m][1].y, cs[j].x, a[2]), fmaf(st[m][1].y, cs[j].y, a[3]));
            }
          };
          const bool send = wg == 1 && w == 3 && bm < 7;
          uint4* hp = g_halo + ((l >> 1) * 128 + b) * 384 + lane;
          mbar_wait(sb + B_QE + 16, 1);
          float2 cn[4];
          auto next_cs = [&](int gi) {
#pragma unroll
            for (int j = 0; j < 4; j++) { cs[j] = cn[j]; cn[j] = lds64f(sb + COLS + (gi * 32 + j * 8 + 2 * qd) * 4); }
          };
#pragma unroll
          for (int j = 0; j < 4; j++) cn[j] = cs[j];
#pragma unroll
          for (int h = 0; h < 2; h++) {
            uint32_t k[8], v[8];
            next_cs(4 + h);
            cen_tile(2 + h, 1, k); put_kv(2 + h, 16 + row0 + 64, k);
            next_cs(h ? 2 : 3);
            cen_tile(4 + h, 1, v); put_kv(4 + h, 16 + row0 + 64, v);
            if (send) {
              uint4* p = hp + h * 192;
              st_tagged(p, k[0], k[1], k[2], ep1); st_tagged(p + 32, k[3], k[4], k[5], ep1); st_tagged(p + 64, k[6], k[7], v[0], ep1);
              st_tagged(p + 96, v[1], v[2], v[3], ep1); st_tagged(p + 128, v[4], v[5], v[6], ep1);
              st_tagged(p + 160, v[7], __float_as_uint(qd & 1 ? st[1][1].x : st[1][0].x), 0u, ep1);
            }
            sched_fence();
          }
          drain();
          {
            uint32_t t[8];
            next_cs(4); cen_tile(2, 0, t); put_kv(2, 16 + row0, t);
            next_cs(0); cen_tile(4, 0, t); put_kv(4, 16 + row0, t);
            next_cs(3); cen_tile(0, 0, q[0][0]); cen_tile(0, 1, q[0][1]);
          }
          bar_sync(NB_SC, 256);
          const bool e = g & 1, sel = 2 * qd + (g & 1) >= g + 2, first = bm == 0 && row0 == 0;
          if (row0 == 0) bar_sync(NB_HALO, 64);
          float ra[4], rb[4], ca[4], cb[4];
#pragma unroll
          for (int m = 0; m < 2; m++) {
            float rk[3];
#pragma unroll
            for (int u = 0; u < 3; u++) {
              const int r = row0 + m * 64 + 8 * u + 2 * qd + e - (sel ? 16 : 8);
              rk[u] = lds64f(sb + (m == 0 && r < 0 ? HRS + 128 : ROWST) + r * 8).x;
            }
            ra[2 * m] = sel ? rk[1] : rk[0]; ra[2 * m + 1] = sel ? rk[2] : rk[1];
            rb[2 * m] = sel ? rk[0] : rk[1]; rb[2 * m + 1] = sel ? rk[1] : rk[2];
          }
#pragma unroll
          for (int i = 0; i < 4; i++) { const float rq = st[i >> 1][i & 1].x * QSCALE; ca[i] = rq * ra[i]; cb[i] = rq * rb[i]; }
#pragma unroll 1
          for (int h = 0; h < 2; h++) {
            float s[2][4][4];
            uint32_t vf[2][4][4], pf[2][2][4];
#pragma unroll
            for (int m = 0; m < 2; m++)
#pragma unroll
              for (int nt = 0; nt < 4; nt++) {
                uint32_t kf[4];
                const uint32_t r = row0 + m * 64 + 8 * nt + (lane & 7), ch = 4 * h + (lane >> 3);
                ldsm4(sb + KSC + r * 128 + ((ch ^ (r & 7)) << 4), kf);
                s[m][nt][0] = s[m][nt][1] = s[m][nt][2] = s[m][nt][3] = 0.f;
                mma16816(s[m][nt], q[0][m][0], q[0][m][1], q[0][m][2], q[0][m][3], kf[0], kf[1]);
                mma16816(s[m][nt], q[0][m][4], q[0][m][5], q[0][m][6], q[0][m][7], kf[2], kf[3]);
              }
#pragma unroll
            for (int m = 0; m < 2; m++)
#pragma unroll
              for (int i = 0; i < 4; i++) {
                const uint32_t r = row0 + m * 64 + 16 * (i >> 1) + srow, ch = 4 * h + 2 * (i & 1) + (lane >> 4);
                ldsm4t(sb + VSC + r * 128 + ((ch ^ (r & 7)) << 4), vf[m][i]);
              }
            float va[4], vb[4], mx[4];
#pragma unroll
            for (int i = 0; i < 4; i++) {
              const int m = i >> 1, hh = i & 1;
              const float a = e ? s[m][hh + 1][2 * hh + 1] : s[m][hh + 1][2 * hh];
              const float lo = e ? s[m][hh][2 * hh + 1] : s[m][hh][2 * hh], hi = e ? s[m][hh + 2][2 * hh + 1] : s[m][hh + 2][2 * hh];
              va[i] = (m == 0 && hh == 0 && first) ? -INFINITY : a * ca[i];
              vb[i] = (m == 0 && first && sel) ? -INFINITY : (sel ? lo : hi) * cb[i];
              mx[i] = fmaxf(va[i], vb[i]);
            }
#pragma unroll
            for (int i = 0; i < 4; i++) mx[i] = fmaxf(mx[i], __shfl_xor_sync(~0u, mx[i], 1));
#pragma unroll
            for (int i = 0; i < 4; i++) mx[i] = fmaxf(mx[i], __shfl_xor_sync(~0u, mx[i], 2));
#pragma unroll
            for (int i = 0; i < 4; i++) {
              va[i] = ex2(va[i] - mx[i]); vb[i] = ex2(vb[i] - mx[i]);
              mx[i] = va[i] + vb[i];
              va[i] *= ra[i]; vb[i] *= rb[i];
            }
#pragma unroll
            for (int i = 0; i < 4; i++) mx[i] += __shfl_xor_sync(~0u, mx[i], 1);
#pragma unroll
            for (int i = 0; i < 4; i++) mx[i] += __shfl_xor_sync(~0u, mx[i], 2);
#pragma unroll
            for (int i = 0; i < 4; i++) {
              const int m = i >> 1, hh = i & 1;
              const float inv = rcp(mx[i]);
              const uint32_t t = pack2(va[i] * inv, vb[i] * inv);
              const uint32_t pa = e ? t << 16 : t & 0xFFFFu, pb = e ? t & 0xFFFF0000u : t >> 16;
              pf[m][hh][hh + 1] = pa; pf[m][hh][hh] = sel ? pb : 0u; pf[m][hh][hh + 2] = sel ? 0u : pb; pf[m][hh][3 - 3 * hh] = 0u;
            }
#pragma unroll
            for (int m = 0; m < 2; m++) {
              float o[4][4];
#pragma unroll
              for (int j = 0; j < 4; j++) o[j][0] = o[j][1] = o[j][2] = o[j][3] = 0.f;
#pragma unroll
              for (int i = 0; i < 4; i++) {
                const int kk = i >> 1, jj = 2 * (i & 1);
                mma16816(o[jj], pf[m][0][2 * kk], pf[m][1][2 * kk], pf[m][0][2 * kk + 1], pf[m][1][2 * kk + 1], vf[m][i][0], vf[m][i][1]);
                mma16816(o[jj + 1], pf[m][0][2 * kk], pf[m][1][2 * kk], pf[m][0][2 * kk + 1], pf[m][1][2 * kk + 1], vf[m][i][2], vf[m][i][3]);
              }
              const float of[16] = {o[0][0], o[0][1], o[0][2], o[0][3], o[1][0], o[1][1], o[1][2], o[1][3], o[2][0], o[2][1], o[2][2], o[2][3], o[3][0], o[3][1], o[3][2], o[3][3]};
              put_o(h, m, of, 1.f, 1.f);
            }
            bar_arrive(NB_SIG + 2 * h + wg, 160);
            if (h == 0) {
              uint32_t t[8];
              next_cs(5); cen_tile(3, 0, t); put_kv(3, 16 + row0, t);
              next_cs(1); cen_tile(5, 0, t); put_kv(5, 16 + row0, t);
#pragma unroll
              for (int j = 0; j < 4; j++) cs[j] = cn[j];
              cen_tile(1, 0, q[0][0]); cen_tile(1, 1, q[0][1]);
              bar_sync(NB_SC, 256);
              if (row0 == 0) bar_sync(NB_HALO + 1, 64);
            }
          }
        } else {
          float qn[2];
          drain();
          auto esc_ptr = [&](int gi) { IDS(); return g_esc + (size_t)(((l & 2) + (gi >> 1)) * 65536 + (2 * bn + (gi & 1)) * 2048) * 20; };
          auto norm_half = [&](int gi, float sc, uint32_t (&t)[2][8], float (&nrm)[2][2]) {
            norm_tile(gi, 0, sc, t[0], nrm[0], true); norm_tile(gi, 1, sc, t[1], nrm[1], true);
            if (!((nrm[0][0] + nrm[0][1]) + (nrm[1][0] + nrm[1][1]) <= 4e9f) || fminf(fminf(nrm[0][0], nrm[0][1]), fminf(nrm[1][0], nrm[1][1])) < 1.5e-5f) {
              uint32_t* p = esc_ptr(gi) + (bm * 256 + row0 + g) * 20 + qd;
#pragma unroll
              for (int m = 0; m < 2; m++) {
                uint32_t u[8]; float d[2];
                norm_tile(gi, m, sc, u, d);
#pragma unroll
                for (int i = 0; i < 10; i++) p[(m * 64 + (i & 1) * 8) * 20 + (i >> 1) * 4] = i < 8 ? u[i] : ep1;
              }
            }
            __syncwarp();
          };
          {
            auto max_norm = [&](const float (&nrm)[2][2]) {
              const bool o1 = qd & 1, o2 = qd & 2;
              const float a = (o1 ? nrm[1][0] : nrm[0][0]) + __shfl_xor_sync(~0u, o1 ? nrm[0][0] : nrm[1][0], 1);
              const float c = (o1 ? nrm[1][1] : nrm[0][1]) + __shfl_xor_sync(~0u, o1 ? nrm[0][1] : nrm[1][1], 1);
              const float d = (o2 ? c : a) + __shfl_xor_sync(~0u, o2 ? a : c, 2);
              return __uint_as_float(__reduce_max_sync(~0u, __float_as_uint(d)));
            };
#pragma unroll
            for (int h = 0; h < 2; h++) {
              uint32_t t[2][8]; float nrm[2][2];
              const uint32_t kb = sb + (h ? 0 : T0);
              if (h) load_cs(3);
              uint32_t tv[2][8];
              norm_half(2 + h, 1.f, t, nrm);
              load_cs(4 + h);
              float nv[2][2];
              if (h == 1) { const float kn = max_norm(nrm); if (lane == 0) g_kn[((l >> 1) * 128 + bn * 8 + bm) * 16 + 8 + wg * 4 + w] = kn; }
              if (h == 0) mbar_wait(sb + B_QE + 8, 1);
#pragma unroll
              for (int i = 0; i < 4; i++) {
                const uint32_t r = row0 + (i >> 1) * 64 + srow;
                stsm4(kb + r * 64 + (((2 * (i & 1) + (lane >> 4)) ^ ((r >> 1) & 3)) << 4), t[i >> 1][4 * (i & 1)], t[i >> 1][4 * (i & 1) + 1], t[i >> 1][4 * (i & 1) + 2], t[i >> 1][4 * (i & 1) + 3]);
              }
              norm_group(4 + h, 1.f, tv, nv);
              load_cs(h);
#pragma unroll
              for (int m = 0; m < 2; m++) {
                const uint32_t r = row0 + m * 64 + g, ad = kb + 16384 + r * 64 + ((qd ^ ((r >> 1) & 3)) << 4);
                sts128(ad, tv[m][0], tv[m][2], tv[m][4], tv[m][6]); sts128(ad + 512, tv[m][1], tv[m][3], tv[m][5], tv[m][7]);
              }
              fence_async_smem();
              bar_arrive(NB_KV + 12 * h, 288);
              if (h == 0) {
                bar_arrive(wg ? NB_HALO : NB_DONE, 160);
                if (wg) bar_sync(NB_HALO + 1, 256);
              }
              if (h == 0) { const float kn = max_norm(nrm); if (lane == 0) g_kn[((l >> 1) * 128 + bn * 8 + bm) * 16 + wg * 4 + w] = kn; }
              norm_half(h, QSCALE, q[h], nrm);
#pragma unroll
              for (int i = 0; i < 4; i++) sts128(sb + QPARK + h * 16384 + (wg * 128 + w * 32 + lane) * 16 + i * 4096, q[h][i >> 1][4 * (i & 1)], q[h][i >> 1][4 * (i & 1) + 1], q[h][i >> 1][4 * (i & 1) + 2], q[h][i >> 1][4 * (i & 1) + 3]);
              qn[h] = max_norm(nrm);
            }
            if (!wg) bar_arrive(NB_HALO + 1, 256);
          }
          constexpr uint64_t VSTEP = 64 - (64ull << 16);
          const uint32_t c_882 = 0x62E562E5u + (lane_id() & zero), c_lsb = 0x00010001u + (lane_id() & zero), c_half = 0x3F003F00u + (lane_id() & zero);
          float o[2][20], S[2][32];
          uint32_t H[2][16], P0[4] = {}, P1[4] = {};
#pragma unroll
          for (int m = 0; m < 2; m++) {
#pragma unroll
            for (int i = 0; i < 20; i++) o[m][i] = 0.f;
            fence_regs(o[m]);
          }
          auto qkf = [&](int b, int ks, uint64_t d) { wg_n64_rs_nb_f16_f32(S[b], q[0][0][4 * ks], q[0][0][4 * ks + 1], q[0][0][4 * ks + 2], q[0][0][4 * ks + 3], d + 2 * ks, ks ? 1 : zero); };
          auto qkh = [&](int b, int ks, uint64_t d) { wg_n64_rs_nb_f16_f16(H[b], q[0][1][4 * ks], q[0][1][4 * ks + 1], q[0][1][4 * ks + 2], q[0][1][4 * ks + 3], d + 2 * ks, ks ? 1 : zero); };
          auto pv0 = [&](uint64_t d) { wgmma_m64n40k16_rs_tb(o[0], P0[0], P0[1], P0[2], P0[3], d, 1); };
          auto pv1 = [&](uint64_t d) { wgmma_m64n40k16_rs_tb(o[1], P1[0], P1[1], P1[2], P1[3], d, 1); };
          float e[4] = {};
          auto finish = [&](int h) {
            const float* s = &S[(h >> 2) & 1][8 * (h & 3)];
            const uint32_t* u = &H[(h >> 2) & 1][4 * (h & 3)];
            const float z0 = exp2_fix(s[6]), z1 = exp2_fix(s[7]);
            P0[0] = pack2v(e[0], e[1]);
            P1[0] = exp2_h2(u[0], c_882);
            P0[1] = pack2v(e[2], e[3]);
            P1[1] = exp2_h2(u[1], c_882);
            const uint32_t B = exp2_base(z0, z1), E = and_or<0x7F807F80u>(B, c_lsb);
            P1[3] = exp2_h2(u[3], c_882);
            P0[3] = fma_bf2(B, and_or<0x807F807Fu>(B, c_half), E);
            const float e4 = ex2v(s[4]), e5 = ex2v(s[5]);
            P1[2] = exp2_h2(u[2], c_882);
            P0[2] = pack2v(e4, e5);
          };
          auto start = [&](int h) {
            const float* s = &S[(h >> 2) & 1][8 * (h & 3)];
            e[0] = ex2v(s[0]); e[1] = ex2v(s[1]); e[3] = ex2v(s[3]); e[2] = ex2v(s[2]);
          };
          uint64_t kd = prm.kv[0].kd;
          mbar_wait(sb + B_TF, 0);
          wg_fence();
#pragma unroll
          for (int b = 0; b < 2; b++) {
            wg_n64_rs_nb_f16_f32_z(S[b], q[0][0][0], q[0][0][1], q[0][0][2], q[0][0][3], kd + 256 * b, 0);
            wg_n64_rs_nb_f16_f16_z(H[b], q[0][1][0], q[0][1][1], q[0][1][2], q[0][1][3], kd + 256 * b, 0);
            if (b == 0) { qkf(0, 1, kd); qkh(0, 1, kd); }
            wg_commit();
          }
          wg_wait<1>(); fence_regs(S[0]); fence_regs(H[0]);
          start(0); finish(0); start(1);
          wg_wait<0>();
          int redo = 0;
#pragma unroll 1
          for (int pass = 0, j = 1; pass < 2; pass++) {
#pragma unroll 1
           do {
            const uint64_t vd = prm.kv[j].vd;
            bool go = false;
#pragma unroll
            for (int h = 2; h < 18; h++) {
              const int px = (h >> 2) + 1, c = h & 3;
              wg_fence();
              if (h == 13) kd = prm.kv[j].kd;
              const uint64_t kx = kd + (px & 3) * 256, vx = vd + (h - 2) * VSTEP;
              if (h == 2) { qkh(1, 0, kx); qkf(1, 0, kx); pv0(vx); pv1(vx); qkh(1, 1, kx); qkf(1, 1, kx); }
              else if ((c == 1 || c == 2) && h < 17) { qkh(px & 1, c - 1, kx); pv1(vx); qkf(px & 1, c - 1, kx); pv0(vx); }
              else { pv0(vx); pv1(vx); }
              wg_commit();
              if (h == 3) e_arrive_if(sb + B_TE + 8 * ((j + 2) & 3), j > 1);
              if (h == 11) go = mbar_test(sb + B_TF + 8 * (j & 3), (j >> 2) & 1) && j != 8;
              finish(h - 1); start(h);
              if (h != 12 && h != 17) sched_fence();
              if (h == 12 && !go) {
                if (j == 16) {
#pragma unroll
                  for (int u = 13; u < 18; u++) {
                    wg_fence(); pv0(vd + (u - 2) * VSTEP); pv1(vd + (u - 2) * VSTEP); wg_commit();
                    if (u < 17) finish(u - 1);
                    if (u < 16) { start(u); sched_fence(); }
                    if (u & 1) { if (u == 17) wg_wait<0>(); else wg_wait<1>(); }
                  }
                  e_arrive(sb + B_TE + 24);
                  goto head_done;
                }
                mbar_wait(sb + B_TF + 8 * (j & 3), (j >> 2) & 1);
                if (j == 8) {
#pragma unroll
                  for (int i = 0; i < 4; i++) lds128(sb + QPARK + 16384 + (wg * 128 + w * 32 + lane_id()) * 16 + i * 4096, &q[0][i >> 1][4 * (i & 1)]);
                }
              }
              if (h == 17) wg_wait<0>(); else if (h & 1) wg_wait<1>();
              if (c == 3) { fence_regs(S[px & 1]); fence_regs(H[px & 1]); }
            }
           } while (j++ & 7);
           head_done:
            fence_regs(o[0]); fence_regs(o[1]);
            uint32_t pk[2][8];
            {
              IDS();
              bf16* op = g_os + (size_t)(bm * 256 + row0 + (lane >> 2)) * 1024 + pass * 512 + bn * 32 + (lane & 3) * 8;
#pragma unroll
              for (int i = 0; i < 4; i++) {
                const float* a = &o[i >> 1][2 * (i & 1)];
                const float inv = rcp(a[16]);
                uint32_t* u = &pk[i >> 1][4 * (i & 1)];
#pragma unroll
                for (int k = 0; k < 4; k++) u[k] = pack2(a[4 * k] * inv, a[4 * k + 1] * inv);
                *(uint4*)(op + ((i >> 1) * 64 + (i & 1) * 8) * 1024) = make_uint4(u[0], u[1], u[2], u[3]);
              }
            }
            sched_fence();
            if (pass == 0) bar_sync(NB_KN + wg, 160);
            const float kmax = *(volatile float*)(smem + ROWST + 4 * pass);
            const bool wide = !(qn[0] <= 1.6e7f) | !(kmax <= 1.6e7f) | !(qn[0] * kmax <= 112.f * 112.f);
            int badm = 0;
#pragma unroll
            for (int m = 0; m < 2; m++) {
              uint32_t chk[2] = {0u, 0u};
#pragma unroll
              for (int i = 0; i < 8; i++) asm("fma.rn.bf16x2 %0, %1, %2, %0;" : "+r"(chk[i & 1]) : "r"(pk[m][i]), "r"(0u));
              const bool bad = wide | !(fminf(o[m][16], o[m][18]) >= 9.3e-10f) | !(o[m][16] + o[m][18] <= 1e36f) | (((chk[0] | chk[1]) & 0x7FFF7FFFu) != 0);
              badm |= __any_sync(~0u, bad) << m;
            }
            if (!badm) bar_arrive(NB_SIG + 2 * pass + wg, 160);
            qn[0] = qn[1];
#pragma unroll
            for (int m = 0; m < 2; m++) {
#pragma unroll
              for (int i = 0; i < 20; i++) o[m][i] = 0.f;
              fence_regs(o[m]);
            }
            if (badm) {
              redo |= badm << 2 * pass;
              const int tx = wg * 128 + w * 32 + lane_id();
              uint4* p = g_qsave + (block_id() * 256 + tx) * 8 + pass * 4;
#pragma unroll
              for (int i = 0; i < 4; i++) {
                uint32_t u[4] = {q[0][i >> 1][4 * (i & 1)], q[0][i >> 1][4 * (i & 1) + 1], q[0][i >> 1][4 * (i & 1) + 2], q[0][i >> 1][4 * (i & 1) + 3]};
                if (pass == 0) lds128(sb + QPARK + tx * 16 + i * 4096, u);
                p[i] = make_uint4(u[0], u[1], u[2], u[3]);
              }
            }
          }
          if (redo) attn_redo(redo, l, cta_id(), wg, w, ep1);
        }
      }
      {
        float acc[64];
#pragma unroll
        for (int i = 0; i < 64; i++) acc[i] = 0.f;
        fence_regs(acc);
        uint32_t s = 0, lap = 0;
#pragma unroll 1
        for (int kt = 0; kt < 16; kt++) {
          mbar_wait(sb + B_PF + 8 * s, ((s < 4 ? l : 0) + lap) & 1);
          const uint64_t da = mkdesc(sb + pslot_a(s, l) + wg * 8192, 16, 1024, 1), db = mkdesc(sb + pslot_b(s), 8192, 1024, 1);
          wg_fence();
#pragma unroll
          for (int k = 0; k < 4; k++) wgmma_m64n128k16_ss_tb(acc, da + k * 2, db + k * 128, 1);
          wg_commit();
          wg_wait<1>();
          if (kt > 0 && w == 0) e_arrive_both(sb + B_PE + 8 * (s ? s - 1 : 5));
          if (++s == 6) { s = 0; lap++; }
        }
        IDS();
        const int g = lane >> 2, qd = lane & 3;
        const int r0 = wg * 64 + w * 16;
        const uint32_t r = r0 + (lane & 7) + ((lane >> 3) & 1) * 8;
        uint32_t x[8][4];
        mbar_wait(sb + B_RF, l & 1);
#pragma unroll
        for (int jj = 0; jj < 8; jj++) ldsm4(sb + RES + (jj >> 2) * 16384 + r * 128 + ((((2 * jj + (lane >> 4)) & 7) ^ (r & 7)) << 4), x[jj]);
        wg_wait<0>();
        fence_regs(acc);
        if (w == 0) e_arrive_both(sb + B_PE + 8 * 3);
        const CUtensorMap* mo = &prm.m[l == 3 ? M_OUT : M_XST];
#pragma unroll
        for (int jj = 0; jj < 8; jj++) {
#pragma unroll
          for (int i = 0; i < 4; i++) x[jj][i] = add_bf16x2(x[jj][i], pack2(acc[8 * jj + 2 * i], acc[8 * jj + 2 * i + 1]));
          stsm4(sb + RES + (jj >> 2) * 16384 + r * 128 + ((((2 * jj + (lane >> 4)) & 7) ^ (r & 7)) << 4), x[jj][0], x[jj][1], x[jj][2], x[jj][3]);
          if ((jj & 3) == 3) { fence_async_smem(); __syncwarp(); tma_st(mo, pn * 128 + (jj >> 2) * 64, pm * 128 + r0, sb + RES + (jj >> 2) * 16384 + r0 * 128); }
        }
        bulk_commit();
        if (l < 3) {
          bar_sync(NB_SC, 256);
#pragma unroll
          for (int jj = 0; jj < 8; jj++)
            stsm4(sb + (jj >> 2) * QSTG + po * 16384 + r * 128 + ((((2 * jj + (lane >> 4)) & 7) ^ (r & 7)) << 4), x[jj][0], x[jj][1], x[jj][2], x[jj][3]);
          fence_async_smem();
          bar_arrive(NB_X, 288);
          float s1[4] = {0.f, 0.f, 0.f, 0.f}, sa[4] = {0.f, 0.f, 0.f, 0.f}, sc[4] = {0.f, 0.f, 0.f, 0.f};
#pragma unroll
          for (int jj = 0; jj < 8; jj++) {
            mma16816(s1, x[jj][0], x[jj][1], x[jj][2], x[jj][3], 0x3f803f80u, 0x3f803f80u);
            mma16816(sa, x[jj][0], x[jj][1], x[jj][2], x[jj][3], x[jj][0], x[jj][2]);
            mma16816(sc, x[jj][0], x[jj][1], x[jj][2], x[jj][3], x[jj][1], x[jj][3]);
          }
          if (qd == g >> 1) {
            float2* p = g_stats + pn * 2048 + pm * 128 + r0 + g;
            p[0] = make_float2(s1[0], g & 1 ? sa[1] : sa[0]);
            p[8] = make_float2(s1[2], g & 1 ? sc[3] : sc[2]);
          }
        }
        bulk_wait_n<0>();
        if (l < 3) bar_arrive(NB_X0, 288);
      }
    }
  }
  asm volatile("barrier.cluster.arrive.relaxed.aligned;\nbarrier.cluster.wait.aligned;" ::: "memory");
}

typedef CUresult (*EncodeFn)(CUtensorMap*, CUtensorMapDataType, cuuint32_t, void*, const cuuint64_t*, const cuuint64_t*, const cuuint32_t*,
                             const cuuint32_t*, CUtensorMapInterleave, CUtensorMapSwizzle, CUtensorMapL2promotion, CUtensorMapFloatOOBfill);

static void make_map(EncodeFn fn, CUtensorMap* m, const void* ptr, int rank, const uint64_t* dims, const uint64_t* strides, const uint32_t* box, CUtensorMapSwizzle sw) {
  cuuint64_t d[5], st[4];
  cuuint32_t bx[5], es[5];
  for (int i = 0; i < rank; i++) { d[i] = dims[i]; bx[i] = box[i]; es[i] = 1; if (i) st[i - 1] = strides[i - 1] * 2; }
  fn(m, CU_TENSOR_MAP_DATA_TYPE_BFLOAT16, rank, (void*)ptr, d, st, bx, es, CU_TENSOR_MAP_INTERLEAVE_NONE, sw,
     CU_TENSOR_MAP_L2_PROMOTION_L2_128B, CU_TENSOR_MAP_FLOAT_OOB_FILL_NONE);
}
static void map2(EncodeFn fn, CUtensorMap* m, const void* ptr, uint64_t inner, uint64_t outer, uint32_t bi, uint32_t bo, CUtensorMapSwizzle sw) {
  const uint64_t d[2] = {inner, outer}, st[1] = {inner};
  const uint32_t bx[2] = {bi, bo};
  make_map(fn, m, ptr, 2, d, st, bx, sw);
}

extern "C" void kernel_launch(void* const* d_in, const int* in_sizes, int n_in, void* d_out, int out_size) {
  (void)in_sizes; (void)n_in; (void)out_size;
  static EncodeFn enc = nullptr;
  static void *xs, *os, *kk, *vv;
  static int sbase = 1024;
  if (!enc) {
    void* p = nullptr;
    cudaDriverEntryPointQueryResult qr;
    cudaGetDriverEntryPoint("cuTensorMapEncodeTiled", &p, cudaEnableDefault, &qr);
    enc = (EncodeFn)p;
    Scratch* sc = nullptr;
    cudaGetSymbolAddress((void**)&sc, g_s);
    xs = sc->xs; os = sc->os; kk = sc->k; vv = sc->v;
    int dev = 0;
    cudaGetDevice(&dev);
    cudaDeviceGetAttribute(&sbase, cudaDevAttrReservedSharedMemoryPerBlock, dev);
    cudaFuncSetAttribute(fused_kernel, cudaFuncAttributeMaxDynamicSharedMemorySize, SMEM_BYTES);
  }
  Params prm;
  const CUtensorMapSwizzle S128 = CU_TENSOR_MAP_SWIZZLE_128B, S64 = CU_TENSOR_MAP_SWIZZLE_64B;
  map2(enc, &prm.m[M_X0A], d_in[0], 1024, 2048, 64, 256, S128);
  map2(enc, &prm.m[M_XSA], xs, 1024, 2048, 64, 256, S128);
  for (int t = 0; t < 2; t++) {
    const uint64_t d3[3] = {1024, 1024, 3}, s3[2] = {3072, 1024};
    const uint32_t b3[3] = {64, 64, 3};
    make_map(enc, &prm.m[M_WQA + t], d_in[1 + 3 * t], 3, d3, s3, b3, S128);
    const uint64_t d5[5] = {64, 32, 2, 16, 16}, s5[4] = {1024, 32 * 1024, 64 * 1024, 64};
    const uint32_t b5[5] = {64, 32, 1, 2, 2};
    make_map(enc, &prm.m[M_WOA + t], d_in[2 + 3 * t], 5, d5, s5, b5, S128);
    const uint64_t dr[3] = {64, 2048, 16}, sr[2] = {1024, 64};
    const uint32_t br[3] = {64, 128, 2};
    make_map(enc, &prm.m[M_X0R + t], t ? xs : d_in[0], 3, dr, sr, br, S128);
  }
  map2(enc, &prm.m[M_OS], os, 1024, 2048, 64, 64, S128);
  map2(enc, &prm.m[M_K], kk, 32, 65536, 32, 128, S64);
  map2(enc, &prm.m[M_V], vv, 32, 65536, 32, 128, S64);
  map2(enc, &prm.m[M_XSO], xs, 1024, 2048, 64, 128, S128);
  map2(enc, &prm.m[M_X0H], d_in[0], 1024, 2048, 64, 128, S128);
  map2(enc, &prm.m[M_XST], xs, 1024, 2048, 64, 16, S128);
  map2(enc, &prm.m[M_OUT], d_out, 1024, 2048, 64, 16, S128);
  prm.x0 = (const bf16*)d_in[0];
  prm.wq[0] = (const bf16*)d_in[1]; prm.wq[1] = (const bf16*)d_in[4];
  prm.zero = 0;
  for (int i = 0; i < 128; i++) prm.map[i] = remap(i);
  {
    const uint64_t hi = 0x80000020ull << 32, k0 = sbase + T0, v0 = k0 + 16384, vstep = 64 - (64ull << 16);
    prm.wd = mkdesc(sbase + 32768, 8192, 1024, 1); prm.xd = mkdesc(sbase, 16, 1024, 1);
    for (int j = 0; j < 17; j++) {
      prm.kv[j].kd = (hi | 1u << 16 | k0 >> 4) + 2048 * ((j < 16 ? j : 15) & 3);
      prm.kv[j].vd = (hi | (uint64_t)(ONES - T0 - 16384) >> 4 << 16 | v0 >> 4) + 32 * vstep * ((j ? j - 1 : 0) & 3);
    }
  }
  fused_kernel<<<128, 384, SMEM_BYTES>>>(prm);
}
```

```cpp
#include <cuda_runtime.h>
#include <cuda_bf16.h>
#include <cuda.h>
#include <stdint.h>

typedef __nv_bfloat16 bf16;

__device__ __forceinline__ void wgmma_m64n192k16_ss_tb(float (&d)[96], uint64_t da, uint64_t db, int scale_d) {
  asm volatile("{\n.reg .pred p;\nsetp.ne.b32 p, %98, 0;\n"
    "wgmma.mma_async.sync.aligned.m64n192k16.f32.bf16.bf16 "
    "{%0, %1, %2, %3, %4, %5, %6, %7, %8, %9, %10, %11, %12, %13, %14, %15, "
    "%16, %17, %18, %19, %20, %21, %22, %23, %24, %25, %26, %27, %28, %29, %30, %31, "
    "%32, %33, %34, %35, %36, %37, %38, %39, %40, %41, %42, %43, %44, %45, %46, %47, "
    "%48, %49, %50, %51, %52, %53, %54, %55, %56, %57, %58, %59, %60, %61, %62, %63, "
    "%64, %65, %66, %67, %68, %69, %70, %71, %72, %73, %74, %75, %76, %77, %78, %79, "
    "%80, %81, %82, %83, %84, %85, %86, %87, %88, %89, %90, %91, %92, %93, %94, %95}, "
    "%96, %97, p, 1, 1, 0, 1;\n}\n"
    : "+f"(d[0]), "+f"(d[1]), "+f"(d[2]), "+f"(d[3]), "+f"(d[4]), "+f"(d[5]), "+f"(d[6]), "+f"(d[7]),
      "+f"(d[8]), "+f"(d[9]), "+f"(d[10]), "+f"(d[11]), "+f"(d[12]), "+f"(d[13]), "+f"(d[14]), "+f"(d[15]),
      "+f"(d[16]), "+f"(d[17]), "+f"(d[18]), "+f"(d[19]), "+f"(d[20]), "+f"(d[21]), "+f"(d[22]), "+f"(d[23]),
      "+f"(d[24]), "+f"(d[25]), "+f"(d[26]), "+f"(d[27]), "+f"(d[28]), "+f"(d[29]), "+f"(d[30]), "+f"(d[31]),
      "+f"(d[32]), "+f"(d[33]), "+f"(d[34]), "+f"(d[35]), "+f"(d[36]), "+f"(d[37]), "+f"(d[38]), "+f"(d[39]),
      "+f"(d[40]), "+f"(d[41]), "+f"(d[42]), "+f"(d[43]), "+f"(d[44]), "+f"(d[45]), "+f"(d[46]), "+f"(d[47]),
      "+f"(d[48]), "+f"(d[49]), "+f"(d[50]), "+f"(d[51]), "+f"(d[52]), "+f"(d[53]), "+f"(d[54]), "+f"(d[55]),
      "+f"(d[56]), "+f"(d[57]), "+f"(d[58]), "+f"(d[59]), "+f"(d[60]), "+f"(d[61]), "+f"(d[62]), "+f"(d[63]),
      "+f"(d[64]), "+f"(d[65]), "+f"(d[66]), "+f"(d[67]), "+f"(d[68]), "+f"(d[69]), "+f"(d[70]), "+f"(d[71]),
      "+f"(d[72]), "+f"(d[73]), "+f"(d[74]), "+f"(d[75]), "+f"(d[76]), "+f"(d[77]), "+f"(d[78]), "+f"(d[79]),
      "+f"(d[80]), "+f"(d[81]), "+f"(d[82]), "+f"(d[83]), "+f"(d[84]), "+f"(d[85]), "+f"(d[86]), "+f"(d[87]),
      "+f"(d[88]), "+f"(d[89]), "+f"(d[90]), "+f"(d[91]), "+f"(d[92]), "+f"(d[93]), "+f"(d[94]), "+f"(d[95])
    : "l"(da), "l"(db), "r"(scale_d));
}

__device__ __forceinline__ void wgmma_m64n128k16_ss_tb(float (&d)[64], uint64_t da, uint64_t db, int scale_d) {
  asm volatile("{\n.reg .pred p;\nsetp.ne.b32 p, %66, 0;\n"
    "wgmma.mma_async.sync.aligned.m64n128k16.f32.bf16.bf16 "
    "{%0, %1, %2, %3, %4, %5, %6, %7, %8, %9, %10, %11, %12, %13, %14, %15, "
    "%16, %17, %18, %19, %20, %21, %22, %23, %24, %25, %26, %27, %28, %29, %30, %31, "
    "%32, %33, %34, %35, %36, %37, %38, %39, %40, %41, %42, %43, %44, %45, %46, %47, "
    "%48, %49, %50, %51, %52, %53, %54, %55, %56, %57, %58, %59, %60, %61, %62, %63}, "
    "%64, %65, p, 1, 1, 0, 1;\n}\n"
    : "+f"(d[0]), "+f"(d[1]), "+f"(d[2]), "+f"(d[3]), "+f"(d[4]), "+f"(d[5]), "+f"(d[6]), "+f"(d[7]),
      "+f"(d[8]), "+f"(d[9]), "+f"(d[10]), "+f"(d[11]), "+f"(d[12]), "+f"(d[13]), "+f"(d[14]), "+f"(d[15]),
      "+f"(d[16]), "+f"(d[17]), "+f"(d[18]), "+f"(d[19]), "+f"(d[20]), "+f"(d[21]), "+f"(d[22]), "+f"(d[23]),
      "+f"(d[24]), "+f"(d[25]), "+f"(d[26]), "+f"(d[27]), "+f"(d[28]), "+f"(d[29]), "+f"(d[30]), "+f"(d[31]),
      "+f"(d[32]), "+f"(d[33]), "+f"(d[34]), "+f"(d[35]), "+f"(d[36]), "+f"(d[37]), "+f"(d[38]), "+f"(d[39]),
      "+f"(d[40]), "+f"(d[41]), "+f"(d[42]), "+f"(d[43]), "+f"(d[44]), "+f"(d[45]), "+f"(d[46]), "+f"(d[47]),
      "+f"(d[48]), "+f"(d[49]), "+f"(d[50]), "+f"(d[51]), "+f"(d[52]), "+f"(d[53]), "+f"(d[54]), "+f"(d[55]),
      "+f"(d[56]), "+f"(d[57]), "+f"(d[58]), "+f"(d[59]), "+f"(d[60]), "+f"(d[61]), "+f"(d[62]), "+f"(d[63])
    : "l"(da), "l"(db), "r"(scale_d));
}

__device__ __forceinline__ void wgmma_m64n40k16_rs_tb(float (&d)[20], uint32_t a0, uint32_t a1, uint32_t a2, uint32_t a3, uint64_t db, int scale_d) {
  asm volatile("{\n.reg .pred p;\nsetp.ne.b32 p, %25, 0;\n"
    "wgmma.mma_async.sync.aligned.m64n40k16.f32.bf16.bf16 "
    "{%0, %1, %2, %3, %4, %5, %6, %7, %8, %9, %10, %11, %12, %13, %14, %15, "
    "%16, %17, %18, %19}, "
    "{%20, %21, %22, %23}, %24, p, 1, 1, 1;\n}\n"
    : "+f"(d[0]), "+f"(d[1]), "+f"(d[2]), "+f"(d[3]), "+f"(d[4]), "+f"(d[5]), "+f"(d[6]), "+f"(d[7]),
      "+f"(d[8]), "+f"(d[9]), "+f"(d[10]), "+f"(d[11]), "+f"(d[12]), "+f"(d[13]), "+f"(d[14]), "+f"(d[15]),
      "+f"(d[16]), "+f"(d[17]), "+f"(d[18]), "+f"(d[19])
    : "r"(a0), "r"(a1), "r"(a2), "r"(a3), "l"(db), "r"(scale_d));
}

__device__ __forceinline__ void wg_n64_rs_nb_f16_f32(float (&d)[32], uint32_t a0, uint32_t a1, uint32_t a2, uint32_t a3, uint64_t db, int scale_d) {
  asm volatile("{\n.reg .pred p;\nsetp.ne.b32 p, %37, 0;\n"
    "wgmma.mma_async.sync.aligned.m64n64k16.f32.f16.f16 "
    "{%0, %1, %2, %3, %4, %5, %6, %7, %8, %9, %10, %11, %12, %13, %14, %15, "
    "%16, %17, %18, %19, %20, %21, %22, %23, %24, %25, %26, %27, %28, %29, %30, %31}, "
    "{%32, %33, %34, %35}, %36, p, 1, 1, 0;\n}\n"
    : "+f"(d[0]), "+f"(d[1]), "+f"(d[2]), "+f"(d[3]), "+f"(d[4]), "+f"(d[5]), "+f"(d[6]), "+f"(d[7]),
      "+f"(d[8]), "+f"(d[9]), "+f"(d[10]), "+f"(d[11]), "+f"(d[12]), "+f"(d[13]), "+f"(d[14]), "+f"(d[15]),
      "+f"(d[16]), "+f"(d[17]), "+f"(d[18]), "+f"(d[19]), "+f"(d[20]), "+f"(d[21]), "+f"(d[22]), "+f"(d[23]),
      "+f"(d[24]), "+f"(d[25]), "+f"(d[26]), "+f"(d[27]), "+f"(d[28]), "+f"(d[29]), "+f"(d[30]), "+f"(d[31])
    : "r"(a0), "r"(a1), "r"(a2), "r"(a3), "l"(db), "r"(scale_d));
}

__device__ __forceinline__ void wg_n64_rs_nb_f16_f16(uint32_t (&d)[16], uint32_t a0, uint32_t a1, uint32_t a2, uint32_t a3, uint64_t db, int scale_d) {
  asm volatile("{\n.reg .pred p;\nsetp.ne.b32 p, %21, 0;\n"
    "wgmma.mma_async.sync.aligned.m64n64k16.f16.f16.f16 "
    "{%0, %1, %2, %3, %4, %5, %6, %7, %8, %9, %10, %11, %12, %13, %14, %15}, "
    "{%16, %17, %18, %19}, %20, p, 1, 1, 0;\n}\n"
    : "+r"(d[0]), "+r"(d[1]), "+r"(d[2]), "+r"(d[3]), "+r"(d[4]), "+r"(d[5]), "+r"(d[6]), "+r"(d[7]),
      "+r"(d[8]), "+r"(d[9]), "+r"(d[10]), "+r"(d[11]), "+r"(d[12]), "+r"(d[13]), "+r"(d[14]), "+r"(d[15])
    : "r"(a0), "r"(a1), "r"(a2), "r"(a3), "l"(db), "r"(scale_d));
}

__device__ __forceinline__ void wg_n64_rs_nb_f16_f32_z(float (&d)[32], uint32_t a0, uint32_t a1, uint32_t a2, uint32_t a3, uint64_t db, int scale_d) {
  asm volatile("{\n.reg .pred p;\nsetp.ne.b32 p, %37, 0;\n"
    "wgmma.mma_async.sync.aligned.m64n64k16.f32.f16.f16 "
    "{%0, %1, %2, %3, %4, %5, %6, %7, %8, %9, %10, %11, %12, %13, %14, %15, "
    "%16, %17, %18, %19, %20, %21, %22, %23, %24, %25, %26, %27, %28, %29, %30, %31}, "
    "{%32, %33, %34, %35}, %36, p, 1, 1, 0;\n}\n"
    : "=f"(d[0]), "=f"(d[1]), "=f"(d[2]), "=f"(d[3]), "=f"(d[4]), "=f"(d[5]), "=f"(d[6]), "=f"(d[7]),
      "=f"(d[8]), "=f"(d[9]), "=f"(d[10]), "=f"(d[11]), "=f"(d[12]), "=f"(d[13]), "=f"(d[14]), "=f"(d[15]),
      "=f"(d[16]), "=f"(d[17]), "=f"(d[18]), "=f"(d[19]), "=f"(d[20]), "=f"(d[21]), "=f"(d[22]), "=f"(d[23]),
      "=f"(d[24]), "=f"(d[25]), "=f"(d[26]), "=f"(d[27]), "=f"(d[28]), "=f"(d[29]), "=f"(d[30]), "=f"(d[31])
    : "r"(a0), "r"(a1), "r"(a2), "r"(a3), "l"(db), "r"(scale_d));
}

__device__ __forceinline__ void wg_n64_rs_nb_f16_f16_z(uint32_t (&d)[16], uint32_t a0, uint32_t a1, uint32_t a2, uint32_t a3, uint64_t db, int scale_d) {
  asm volatile("{\n.reg .pred p;\nsetp.ne.b32 p, %21, 0;\n"
    "wgmma.mma_async.sync.aligned.m64n64k16.f16.f16.f16 "
    "{%0, %1, %2, %3, %4, %5, %6, %7, %8, %9, %10, %11, %12, %13, %14, %15}, "
    "{%16, %17, %18, %19}, %20, p, 1, 1, 0;\n}\n"
    : "=r"(d[0]), "=r"(d[1]), "=r"(d[2]), "=r"(d[3]), "=r"(d[4]), "=r"(d[5]), "=r"(d[6]), "=r"(d[7]),
      "=r"(d[8]), "=r"(d[9]), "=r"(d[10]), "=r"(d[11]), "=r"(d[12]), "=r"(d[13]), "=r"(d[14]), "=r"(d[15])
    : "r"(a0), "r"(a1), "r"(a2), "r"(a3), "l"(db), "r"(scale_d));
}

#define DEVINL __device__ __forceinline__
DEVINL void wg_fence() { asm volatile("wgmma.fence.sync.aligned;" ::: "memory"); }
DEVINL void wg_commit() { asm volatile("wgmma.commit_group.sync.aligned;" ::: "memory"); }
template <int N> DEVINL void wg_wait() { asm volatile("wgmma.wait_group.sync.aligned %0;" ::"n"(N) : "memory"); }
__host__ DEVINL uint64_t mkdesc(uint32_t addr, uint32_t lbo, uint32_t sbo, int sw) {
  return (uint64_t)((addr & 0x3FFFF) >> 4) | ((uint64_t)(lbo >> 4) << 16) | ((uint64_t)(sbo >> 4) << 32) | ((uint64_t)sw << 62);
}
DEVINL void mbar_init(uint32_t bar, uint32_t cnt) { asm volatile("mbarrier.init.shared::cta.b64 [%0], %1;" ::"r"(bar), "r"(cnt) : "memory"); }
DEVINL void mbar_arrive(uint32_t bar) { asm volatile("mbarrier.arrive.shared::cta.b64 _, [%0];" ::"r"(bar) : "memory"); }
DEVINL bool mbar_try(uint32_t bar, uint32_t parity) {
  uint32_t ok;
  asm volatile("{\n.reg .pred p;\nmbarrier.try_wait.parity.shared::cta.b64 p, [%1], %2;\nselp.u32 %0, 1, 0, p;\n}" : "=r"(ok) : "r"(bar), "r"(parity) : "memory");
  return ok;
}
DEVINL bool mbar_test(uint32_t bar, uint32_t parity) {
  uint32_t ok;
  asm volatile("{\n.reg .pred p;\nmbarrier.test_wait.parity.shared::cta.b64 p, [%1], %2;\nselp.u32 %0, 1, 0, p;\n}" : "=r"(ok) : "r"(bar), "r"(parity) : "memory");
  return ok;
}
DEVINL void mbar_wait(uint32_t bar, uint32_t parity) {
#pragma unroll 1
  for (uint32_t n = 0; n < 100000u; n++) if (mbar_try(bar, parity)) break;
}
#define EL(txt) "{\n.reg .pred pe;\nelect.sync _|pe, 0xffffffff;\n@pe " txt "\n}"
DEVINL void e_expect_tx(uint32_t bar, uint32_t bytes) { asm volatile(EL("mbarrier.arrive.expect_tx.shared::cta.b64 _, [%0], %1;") ::"r"(bar), "r"(bytes) : "memory"); }
DEVINL void e_arrive(uint32_t bar) { asm volatile(EL("mbarrier.arrive.shared::cta.b64 _, [%0];") ::"r"(bar) : "memory"); }
DEVINL void e_arrive_if(uint32_t bar, int c) {
  asm volatile("{\n.reg .pred pe;\nelect.sync _|pe, 0xffffffff;\nsetp.ne.and.b32 pe, %1, 0, pe;\n@pe mbarrier.arrive.shared::cta.b64 _, [%0];\n}" ::"r"(bar), "r"(c) : "memory");
}
DEVINL void e_red(uint32_t* p) { asm volatile(EL("red.release.gpu.global.add.u32 [%0], 1;") ::"l"(p) : "memory"); }
DEVINL void e_red_relaxed(uint32_t* p) { asm volatile(EL("red.relaxed.gpu.global.add.u32 [%0], 1;") ::"l"(p) : "memory"); }
DEVINL void tma_ld(uint32_t dst, const CUtensorMap* m, int c0, int c1, uint32_t bar) {
  asm volatile(EL("cp.async.bulk.tensor.2d.shared::cluster.global.mbarrier::complete_tx::bytes [%0], [%1, {%3, %4}], [%2];")
               ::"r"(dst), "l"(m), "r"(bar), "r"(c0), "r"(c1) : "memory");
}
DEVINL void tma_ld3(uint32_t dst, const CUtensorMap* m, int c0, int c1, int c2, uint32_t bar) {
  asm volatile(EL("cp.async.bulk.tensor.3d.shared::cluster.global.mbarrier::complete_tx::bytes [%0], [%1, {%3, %4, %5}], [%2];")
               ::"r"(dst), "l"(m), "r"(bar), "r"(c0), "r"(c1), "r"(c2) : "memory");
}
DEVINL void tma_ld5(uint32_t dst, const CUtensorMap* m, int c2, int c3, int c4, uint32_t bar) {
  asm volatile(EL("cp.async.bulk.tensor.5d.shared::cluster.global.mbarrier::complete_tx::bytes [%0], [%1, {0, 0, %3, %4, %5}], [%2];")
               ::"r"(dst), "l"(m), "r"(bar), "r"(c2), "r"(c3), "r"(c4) : "memory");
}
DEVINL void tma_ld_mc(uint32_t dst, const CUtensorMap* m, int c0, int c1, uint32_t bar) {
  asm volatile(EL("cp.async.bulk.tensor.2d.shared::cluster.global.mbarrier::complete_tx::bytes.multicast::cluster [%0], [%1, {%3, %4}], [%2], %5;")
               ::"r"(dst), "l"(m), "r"(bar), "r"(c0), "r"(c1), "h"((uint16_t)3) : "memory");
}
DEVINL void e_arrive_both(uint32_t bar) {
  asm volatile("{\n.reg .pred pe;\n.reg .b32 r0, r1;\nelect.sync _|pe, 0xffffffff;\nmapa.shared::cluster.u32 r0, %0, 0;\nmapa.shared::cluster.u32 r1, %0, 1;\n"
               "@pe mbarrier.arrive.shared::cluster.b64 _, [r0];\n@pe mbarrier.arrive.shared::cluster.b64 _, [r1];\n}" ::"r"(bar) : "memory");
}
DEVINL void tma_st(const CUtensorMap* m, int c0, int c1, uint32_t src) {
  asm volatile(EL("cp.async.bulk.tensor.2d.global.shared::cta.bulk_group [%0, {%2, %3}], [%1];") ::"l"(m), "r"(src), "r"(c0), "r"(c1) : "memory");
}
DEVINL void bulk_commit() { asm volatile("cp.async.bulk.commit_group;" ::: "memory"); }
template <int N> DEVINL void bulk_wait_n() { asm volatile("cp.async.bulk.wait_group %0;\nbar.warp.sync 0xffffffff;" ::"n"(N) : "memory"); }
DEVINL void l2_prefetch(const void* g, uint32_t bytes) { asm volatile(EL("cp.async.bulk.prefetch.L2.global [%0], %1;") ::"l"(g), "r"(bytes) : "memory"); }
DEVINL void fence_async_smem() { asm volatile("fence.proxy.async.shared::cta;" ::: "memory"); }
DEVINL void fence_async_gl() { asm volatile("fence.proxy.async.global;" ::: "memory"); }
DEVINL void cluster_wait() { asm volatile("barrier.cluster.wait.aligned;" ::: "memory"); }
DEVINL void bar_sync(int id, int n) { asm volatile("bar.sync %0, %1;" ::"r"(id), "r"(n) : "memory"); }
DEVINL void bar_arrive(int id, int n) { asm volatile("bar.arrive %0, %1;" ::"r"(id), "r"(n) : "memory"); }
DEVINL uint32_t ld_acquire(const uint32_t* p) { uint32_t v; asm volatile("ld.acquire.gpu.global.u32 %0, [%1];" : "=r"(v) : "l"(p) : "memory"); return v; }
DEVINL void await_flag(int j, uint32_t& rdy, const uint32_t* p, uint32_t target) {
  if ((rdy >> j) & 1) return;
#pragma unroll 1
  for (uint32_t n = 0; n < 200000u && !((rdy >> j) & 1); n++) rdy = __ballot_sync(~0u, (int)(ld_acquire(p) - target) >= 0);
  asm volatile("fence.proxy.async.global;" ::: "memory");
}
DEVINL void poll_ge(const uint32_t* p, uint32_t target) {
#pragma unroll 1
  for (uint32_t n = 0; n < 200000u; n++) if (__all_sync(~0u, (int)(ld_acquire(p) - target) >= 0)) break;
}
DEVINL int lane_id() { int v; asm volatile("mov.u32 %0, %%laneid;" : "=r"(v)); return v; }
__host__ DEVINL int remap(int v) {
  const int c = v >> 1, u = c - 36, r = (u * 37) >> 8;
  const int L = c < 4 ? 32 + 8 * c : c < 36 ? c - 4 : 33 + u + r;
  return 2 * L + (v & 1);
}
DEVINL int block_id() { int v; asm volatile("mov.u32 %0, %%ctaid.x;" : "=r"(v)); return v; }
#define cta_id() prm.map[block_id()]
#define IDS() const int lane = lane_id(), b = cta_id(), bm = b >> 4, bn = b & 15, rank = b & 1, pm = 2 * bm + (bn >> 3), pn = bn & 7, po = pm & 1; \
  (void)lane; (void)bm; (void)bn; (void)rank; (void)pm; (void)pn; (void)po
DEVINL void st_tagged(uint4* p, uint32_t a, uint32_t b, uint32_t c, uint32_t tag) {
  asm volatile("{\n.reg .b64 u, v;\n.reg .b128 t;\nmov.b64 u, {%1, %2};\nmov.b64 v, {%3, %4};\nmov.b128 t, {u, v};\nst.relaxed.gpu.global.b128 [%0], t;\n}"
               ::"l"(p), "r"(a), "r"(b), "r"(c), "r"(tag) : "memory");
}
DEVINL uint32_t ld_tagged(const uint4* p, uint32_t* r) {
  uint32_t tag;
  asm volatile("{\n.reg .b64 u, v;\n.reg .b128 t;\nld.relaxed.gpu.global.b128 t, [%4];\nmov.b128 {u, v}, t;\nmov.b64 {%0, %1}, u;\nmov.b64 {%2, %3}, v;\n}"
               : "=r"(r[0]), "=r"(r[1]), "=r"(r[2]), "=r"(tag) : "l"(p) : "memory");
  return tag;
}
DEVINL float ex2(float x) { float y; asm("ex2.approx.ftz.f32 %0, %1;" : "=f"(y) : "f"(x)); return y; }
DEVINL float rcp(float x) { float y; asm("rcp.approx.ftz.f32 %0, %1;" : "=f"(y) : "f"(x)); return y; }
DEVINL uint32_t pack2(float lo, float hi) { uint32_t r; asm("cvt.rn.bf16x2.f32 %0, %1, %2;" : "=r"(r) : "f"(hi), "f"(lo)); return r; }
DEVINL uint32_t pack2h(float lo, float hi) { uint32_t r; asm("cvt.rn.f16x2.f32 %0, %1, %2;" : "=r"(r) : "f"(hi), "f"(lo)); return r; }
DEVINL float bf_lo(uint32_t w) { return __uint_as_float(w << 16); }
DEVINL float bf_hi(uint32_t w) { return __uint_as_float(w & 0xFFFF0000u); }
DEVINL float bf_round(float x) { return bf_lo(pack2(x, 0.f)); }
DEVINL uint32_t add_bf16x2(uint32_t a, uint32_t b) { uint32_t r; asm("add.rn.bf16x2 %0, %1, %2;" : "=r"(r) : "r"(a), "r"(b)); return r; }
DEVINL void stsm4(uint32_t addr, uint32_t a, uint32_t b, uint32_t c, uint32_t d) {
  asm volatile("stmatrix.sync.aligned.m8n8.x4.shared.b16 [%0], {%1, %2, %3, %4};" ::"r"(addr), "r"(a), "r"(b), "r"(c), "r"(d) : "memory");
}
DEVINL void ldsm4(uint32_t addr, uint32_t (&r)[4]) {
  asm volatile("ldmatrix.sync.aligned.m8n8.x4.shared.b16 {%0, %1, %2, %3}, [%4];" : "=r"(r[0]), "=r"(r[1]), "=r"(r[2]), "=r"(r[3]) : "r"(addr) : "memory");
}
DEVINL void ldsm4t(uint32_t addr, uint32_t (&r)[4]) {
  asm volatile("ldmatrix.sync.aligned.m8n8.x4.trans.shared.b16 {%0, %1, %2, %3}, [%4];" : "=r"(r[0]), "=r"(r[1]), "=r"(r[2]), "=r"(r[3]) : "r"(addr) : "memory");
}
DEVINL void sts128(uint32_t addr, uint32_t a, uint32_t b, uint32_t c, uint32_t d) {
  asm volatile("st.shared.v4.b32 [%0], {%1, %2, %3, %4};" ::"r"(addr), "r"(a), "r"(b), "r"(c), "r"(d) : "memory");
}
DEVINL float2 lds64f(uint32_t addr) { float2 v; asm volatile("ld.shared.v2.f32 {%0, %1}, [%2];" : "=f"(v.x), "=f"(v.y) : "r"(addr) : "memory"); return v; }
DEVINL void mma16816(float (&d)[4], uint32_t a0, uint32_t a1, uint32_t a2, uint32_t a3, uint32_t b0, uint32_t b1) {
  asm("mma.sync.aligned.m16n8k16.row.col.f32.bf16.bf16.f32 {%0, %1, %2, %3}, {%4, %5, %6, %7}, {%8, %9}, {%0, %1, %2, %3};"
               : "+f"(d[0]), "+f"(d[1]), "+f"(d[2]), "+f"(d[3]) : "r"(a0), "r"(a1), "r"(a2), "r"(a3), "r"(b0), "r"(b1));
}
template <int N> DEVINL void fence_regs(float (&d)[N]) {
#pragma unroll
  for (int i = 0; i < N; i++) asm volatile("" : "+f"(d[i])::"memory");
}
template <int N> DEVINL void fence_regs(uint32_t (&d)[N]) {
#pragma unroll
  for (int i = 0; i < N; i++) asm volatile("" : "+r"(d[i])::"memory");
}
DEVINL void lds128(uint32_t addr, uint32_t* r) {
  asm volatile("ld.shared.v4.b32 {%0, %1, %2, %3}, [%4];" : "=r"(r[0]), "=r"(r[1]), "=r"(r[2]), "=r"(r[3]) : "r"(addr) : "memory");
}
DEVINL void sched_fence() { asm volatile("griddepcontrol.launch_dependents;" ::: "memory"); }

struct Scratch {
  bf16 k[32 * 2048 * 32];
  bf16 xs[2048 * 1024];
  bf16 os[2048 * 1024];
  bf16 v[32 * 2048 * 32];
  float kn[2 * 128 * 16];
  uint32_t cnt[256 * 32];
  float2 stats[8 * 2048];
  uint4 halo[2 * 128 * 12 * 32];
  float csp[2 * 16 * 8 * 192];
  uint4 qsave[128 * 256 * 8];
  uint32_t esc[4 * 65536 * 20];
};
__device__ __align__(1024) Scratch g_s;
#define g_k g_s.k
#define g_xs g_s.xs
#define g_os g_s.os
#define g_v g_s.v
#define g_kn g_s.kn
#define g_cnt g_s.cnt
#define g_stats g_s.stats
#define g_halo g_s.halo
#define g_csp g_s.csp
#define g_qsave g_s.qsave
#define g_esc g_s.esc
#define g_epoch g_s.cnt[255 * 32]

DEVINL uint32_t* cnt_x(int l, int bm) { return g_cnt + (l * 8 + bm) * 32; }
DEVINL uint32_t* cnt_o(int l, int pm, int h) { return g_cnt + (32 + (l * 16 + pm) * 2 + h) * 32; }
DEVINL uint32_t* cnt_kv(int lb, int bn) { return g_cnt + (160 + lb * 16 + bn) * 32; }
DEVINL uint32_t* cnt_ad(int bn) { return g_cnt + (192 + bn) * 32; }
DEVINL uint32_t* cnt_cs(int t, int bn) { return g_cnt + (208 + t * 16 + bn) * 32; }

DEVINL int qord(int i, int l, int pn) { return l == 0 ? i : i < 4 ? ((2 * pn) ^ (i & 2)) + (i & 1) : i - 4 < 2 * (pn & 6) ? i - 4 : i; }
struct Params {
  CUtensorMap m[15];
  const bf16* x0;
  const bf16* wq[2];
  uint32_t zero;
  int map[128];
  uint64_t wd, xd;
  struct __align__(16) { uint64_t kd, vd; } kv[4];
};
enum { M_X0A = 0, M_XSA, M_WQA, M_WQB, M_WOA, M_WOB, M_OS, M_K, M_V, M_X0R, M_XSR, M_XSO, M_OUT, M_XST, M_X0H, M_COUNT };

constexpr uint32_t QSTG = 57344;
constexpr uint32_t T0 = 65536, TSTG = 32768;
constexpr uint32_t ONES = 230400;
constexpr uint32_t PSTG = 32768, RES = 196608;
constexpr uint32_t KSC = 98304, VSC = 133120, HRS = 167936;
constexpr uint32_t ROWST = 229376, COLS = 231424, BARS = 232192, SMEM_BYTES = 232448;
constexpr uint32_t B_QF = BARS, B_QE = BARS + 32, B_TF = BARS + 64, B_TE = BARS + 96, B_PF = BARS + 128, B_PE = BARS + 176,
                   B_RF = BARS + 224, W_X = BARS + 232, B_QL = BARS + 240, B_PA = BARS + 248;
enum { NB_ST = 1, NB_KV = 2  , NB_DONE = 3, NB_SC = 4, NB_SIG = 5  , NB_KN = 9  , NB_X = 11, NB_HALO = 12  , NB_X0 = 15 };

DEVINL uint32_t pslot_b(uint32_t s) { return ((0x320415u >> (4 * s)) & 7) * 16384u; }
DEVINL uint32_t pslot_a(uint32_t s, int l) { return 98304u + ((((l & 1) ? 0x541230u : 0x041235u) >> (4 * s)) & 7) * 16384u; }

constexpr float QSCALE = 0.17677669529663687f * 1.4426950408889634f;
constexpr uint32_t QPARK = 32768;

DEVINL uint32_t exp2_h2(uint32_t s, uint32_t c882) {
  uint32_t r, t, w, m, d;
  asm volatile("{.reg .b64 t; add.rn.f16x2 %0, %1, %2; cvt.u64.u32 t, %0; cvt.u32.u64 %0, t;}" : "=r"(r) : "r"(s), "r"(0x65F565F5u));
  asm volatile("fma.rn.f16x2 %0, %1, %2, %3;" : "=r"(t) : "r"(r), "r"(0xB8A0B8A0u), "r"(c882));
  asm volatile("fma.rn.f16x2 %0, %1, %2, %3;" : "=r"(w) : "r"(s), "r"(0x38A038A0u), "r"(t));
  asm volatile("fma.rn.f16x2 %0, %1, %1, %2;" : "=r"(m) : "r"(w), "r"(0x48244833u));
  asm volatile("{.reg .b32 t; shf.l.clamp.b32 t, %2, %1, 7; add.u32 %0, t, %2;}" : "=r"(d) : "r"(r), "r"(m));
  return d;
}
DEVINL float exp2_fix(float s) { float z; asm volatile("add.rn.f32 %0, %1, 0f43BF34BC;" : "=f"(z) : "f"(s)); return z; }
DEVINL uint32_t exp2_base(float z0, float z1) { uint32_t B; asm volatile("prmt.b32 %0, %1, %2, 0x6521;" : "=r"(B) : "r"(__float_as_uint(z0)), "r"(__float_as_uint(z1))); return B; }
template <uint32_t MASK> DEVINL uint32_t and_or(uint32_t a, uint32_t c) { uint32_t r; asm volatile("lop3.b32 %0, %1, %3, %2, 0xEA;" : "=r"(r) : "r"(a), "r"(c), "n"(MASK)); return r; }
DEVINL uint32_t fma_bf2(uint32_t a, uint32_t b, uint32_t c) { uint32_t r; asm volatile("fma.rn.bf16x2 %0, %1, %2, %3;" : "=r"(r) : "r"(a), "r"(b), "r"(c)); return r; }
DEVINL float ex2v(float x) { float y; asm volatile("ex2.approx.ftz.f32 %0, %1;" : "=f"(y) : "f"(x)); return y; }
DEVINL uint32_t pack2v(float lo, float hi) { uint32_t r; asm volatile("cvt.rn.bf16x2.f32 %0, %1, %2;" : "=r"(r) : "f"(hi), "f"(lo)); return r; }
DEVINL void unesc(uint32_t (&u)[4], const uint32_t* esc, uint32_t tag) {
  const bool saved = __ldcg(esc + 16) == tag;
#pragma unroll
  for (int j = 0; j < 4; j++) {
    float lo, hi;
    asm("{.reg .f16 a, b; mov.b32 {a, b}, %2; cvt.f32.f16 %0, a; cvt.f32.f16 %1, b;}" : "=f"(lo), "=f"(hi) : "r"(u[j]));
    u[j] = saved ? __ldcg(esc + 4 * j) : pack2(lo, hi);
  }
}

DEVINL void attn_slow(const uint32_t (&q)[8], int head, const uint32_t* kesc, uint32_t tag, float (&res)[20], int lane) {
  const int g = lane >> 2, qd = lane & 3;
  const bf16* kb = g_k + (size_t)head * 2048 * 32;
  const bf16* vb = g_v + (size_t)head * 2048 * 32;
  float o[4][4], m0 = -INFINITY, m1 = -INFINITY, l0 = 0.f, l1 = 0.f;
#pragma unroll
  for (int j = 0; j < 4; j++) { o[j][0] = o[j][1] = o[j][2] = o[j][3] = 0.f; }
#pragma unroll 1
  for (int k0 = 0; k0 < 2048; k0 += 16) {
    float s[2][4];
#pragma unroll
    for (int nt = 0; nt < 2; nt++) {
      s[nt][0] = s[nt][1] = s[nt][2] = s[nt][3] = 0.f;
      const uint32_t* kp = (const uint32_t*)(kb + (size_t)(k0 + nt * 8 + g) * 32) + qd;
      uint32_t k[4] = {__ldcg(kp), __ldcg(kp + 4), __ldcg(kp + 8), __ldcg(kp + 12)};
      unesc(k, kesc + (k0 + nt * 8 + g) * 20 + qd, tag);
      __syncwarp();
      mma16816(s[nt], q[0], q[1], q[2], q[3], k[0], k[1]);
      mma16816(s[nt], q[4], q[5], q[6], q[7], k[2], k[3]);
    }
    float a0 = fmaxf(fmaxf(s[0][0], s[0][1]), fmaxf(s[1][0], s[1][1]));
    float a1 = fmaxf(fmaxf(s[0][2], s[0][3]), fmaxf(s[1][2], s[1][3]));
    a0 = fmaxf(a0, __shfl_xor_sync(~0u, a0, 1)); a0 = fmaxf(a0, __shfl_xor_sync(~0u, a0, 2));
    a1 = fmaxf(a1, __shfl_xor_sync(~0u, a1, 1)); a1 = fmaxf(a1, __shfl_xor_sync(~0u, a1, 2));
    const float n0 = fmaxf(m0, a0), n1 = fmaxf(m1, a1);
    const float c0 = (m0 == n0) ? 1.f : ex2(m0 - n0), c1 = (m1 == n1) ? 1.f : ex2(m1 - n1);
    m0 = n0; m1 = n1;
    const uint32_t p0 = pack2(ex2(s[0][0] - n0), ex2(s[0][1] - n0)), p1 = pack2(ex2(s[0][2] - n1), ex2(s[0][3] - n1));
    const uint32_t p2 = pack2(ex2(s[1][0] - n0), ex2(s[1][1] - n0)), p3 = pack2(ex2(s[1][2] - n1), ex2(s[1][3] - n1));
    l0 = l0 * c0 + bf_lo(p0) + bf_hi(p0) + bf_lo(p2) + bf_hi(p2);
    l1 = l1 * c1 + bf_lo(p1) + bf_hi(p1) + bf_lo(p3) + bf_hi(p3);
#pragma unroll
    for (int j = 0; j < 4; j++) {
      o[j][0] *= c0; o[j][1] *= c0; o[j][2] *= c1; o[j][3] *= c1;
      const unsigned short* vp = (const unsigned short*)(vb + (size_t)(k0 + 2 * qd) * 32 + j * 8 + g);
      const uint32_t b0 = (uint32_t)__ldcg(vp) | ((uint32_t)__ldcg(vp + 32) << 16);
      const uint32_t b1 = (uint32_t)__ldcg(vp + 256) | ((uint32_t)__ldcg(vp + 288) << 16);
      mma16816(o[j], p0, p1, p2, p3, b0, b1);
    }
  }
  l0 += __shfl_xor_sync(~0u, l0, 1); l0 += __shfl_xor_sync(~0u, l0, 2);
  l1 += __shfl_xor_sync(~0u, l1, 1); l1 += __shfl_xor_sync(~0u, l1, 2);
#pragma unroll
  for (int j = 0; j < 4; j++) { res[4 * j] = o[j][0]; res[4 * j + 1] = o[j][1]; res[4 * j + 2] = o[j][2]; res[4 * j + 3] = o[j][3]; }
  res[16] = l0; res[18] = l1;
}

__device__ __noinline__ void attn_redo(int redo, int l, int b, int wg, int w, uint32_t tag) {
  const int lane = lane_id();
#pragma unroll 1
  for (int t = 0; t < 4; t++) {
    const int h = t >> 1, head = 2 * (b & 15) + h, row = (b >> 4) * 256 + wg * 128 + (t & 1) * 64 + w * 16 + (lane >> 2);
    if ((redo >> t) & 1) {
      const uint32_t* esc = g_esc + (size_t)((l & 2) * 65536 + head * 2048) * 20;
      const uint32_t* qs = (const uint32_t*)(g_qsave + (block_id() * 256 + wg * 128 + w * 32 + lane) * 8 + 2 * t);
      uint32_t q[8]; float o[20];
#pragma unroll
      for (int i = 0; i < 2; i++) {
        uint32_t u[4] = {__ldcg(qs + i), __ldcg(qs + i + 2), __ldcg(qs + i + 4), __ldcg(qs + i + 6)};
        unesc(u, esc + (row + i * 8) * 20 + (lane & 3), tag);
        q[i] = u[0]; q[i + 2] = u[1]; q[i + 4] = u[2]; q[i + 6] = u[3];
      }
      __syncwarp();
      attn_slow(q, head, esc + 65536 * 20, tag, o, lane);
      const float i0 = rcp(o[16]), i1 = rcp(o[18]);
      bf16* op = g_os + (size_t)row * 1024 + h * 512 + (b & 15) * 32 + (lane & 3) * 8;
      *(uint4*)op = make_uint4(pack2(o[0] * i0, o[1] * i0), pack2(o[4] * i0, o[5] * i0), pack2(o[8] * i0, o[9] * i0), pack2(o[12] * i0, o[13] * i0));
      *(uint4*)(op + 8 * 1024) = make_uint4(pack2(o[2] * i1, o[3] * i1), pack2(o[6] * i1, o[7] * i1), pack2(o[10] * i1, o[11] * i1), pack2(o[14] * i1, o[15] * i1));
    }
    if ((t & 1) && ((redo >> 2 * h) & 3)) bar_arrive(NB_SIG + 2 * h + wg, 160);
  }
}

__global__ void __cluster_dims__(2, 1, 1) __launch_bounds__(384, 1) fused_kernel(const __grid_constant__ Params prm) {
  extern __shared__ __align__(1024) char smem[];
  const uint32_t sb = (uint32_t)__cvta_generic_to_shared(smem);
  const int tid = threadIdx.x, lane = tid & 31;
  const int wg = __shfl_sync(0xffffffffu, tid >> 7, 0);
  const int w = __shfl_sync(0xffffffffu, (tid >> 5) & 3, 0);
  const int bm = remap(blockIdx.x) >> 4, bn = remap(blockIdx.x) & 15;

  auto first_tile = [&](int kt) {
    e_expect_tx(sb + B_QF + 8 * kt, QSTG);
    tma_ld(sb + kt * QSTG, &prm.m[M_X0A], kt * 64, bm * 256, sb + B_QF + 8 * kt);
    tma_ld3(sb + kt * QSTG + 32768, &prm.m[M_WQA], bn * 64, kt * 64, 0, sb + B_QF + 8 * kt);
  };
  auto init4 = [&](uint32_t bar, uint32_t c0, uint32_t c1, uint32_t c2, uint32_t c3) {
    asm volatile("{\n.reg .pred pe;\nelect.sync _|pe, 0xffffffff;\n@pe mbarrier.init.shared::cta.b64 [%0], %1;\n@pe mbarrier.init.shared::cta.b64 [%0+8], %2;\n"
                 "@pe mbarrier.init.shared::cta.b64 [%0+16], %3;\n@pe mbarrier.init.shared::cta.b64 [%0+24], %4;\n@pe fence.mbarrier_init.release.cluster;\n}"
                 ::"r"(bar), "r"(c0), "r"(c1), "r"(c2), "r"(c3) : "memory");
  };
  if (wg < 2) {
    const uint32_t k = wg * 4 + w, lo = (0x1411814u >> (4 * k)) & 15, hi = (0x1441814u >> (4 * k)) & 15;
    if (tid < 32) asm volatile("prefetch.global.L2 [%0];" ::"l"(prm.x0 + (size_t)(bm * 256 + bn * 16 + (tid & 15)) * 1024 + (tid >> 4) * 64));
    else if (tid < 80) asm volatile("prefetch.global.L2 [%0];" ::"l"(prm.wq[0] + (bm * 16 + (tid & 15)) * 3072 + ((tid >> 4) - 2) * 1024 + bn * 64));
    __syncwarp();
    if (k < 7) init4(sb + B_QE + 32 * k, lo, lo, hi, k == 6 ? 2 : hi);
    __syncwarp();
    if (k == 6 && lane == 0) *(volatile unsigned long long*)(smem + W_X) = 0ull;
  } else if (w == 0) {
    init4(sb + B_QF, 1, 1, 1, 1);
    __syncwarp();
    first_tile(0);
  }
  __syncthreads();
  asm volatile("barrier.cluster.arrive.relaxed.aligned;" ::: "memory");

  if (wg == 2) {
    asm volatile("setmaxnreg.dec.sync.aligned.u32 56;");
    const uint32_t ep1 = *(volatile uint32_t*)&g_epoch + 1;
    if (w == 0) {
      first_tile(1);
      mbar_wait(sb + B_QF, 0);
      first_tile(2); first_tile(3);
#pragma unroll 1
      for (int kt = 4; kt < 16; kt++) l2_prefetch(prm.wq[0] + kt * 196608 + blockIdx.x * 1536, 3072);
      cluster_wait();
#pragma unroll 1
      for (int l = 0; l < 4; l++) {
        IDS();
        const CUtensorMap* mw = &prm.m[M_WQA + (l & 1)];
        const CUtensorMap* mx = &prm.m[l == 0 ? M_X0A : M_XSA];
        const CUtensorMap* mh = &prm.m[l == 0 ? M_X0H : M_XSO];
        const CUtensorMap* mo = &prm.m[M_WOA + (l & 1)];
        auto q_b = [&](int i) {
          const int s = i & 3;
          mbar_wait(sb + B_QE + 8 * s, ((i >> 2) & 1) ^ 1);
          e_expect_tx(sb + B_QF + 8 * s, QSTG);
          tma_ld3(sb + s * QSTG + 32768, mw, bn * 64, qord(i, l, pn) * 64, 0, sb + B_QF + 8 * s);
        };
        uint32_t rdy = l ? 0u : ~0u;
        auto q_a = [&](int i) {
          const int kt = qord(i, l, pn);
          await_flag(kt >> 1, rdy, cnt_x(l, bm) + (lane & 7), ep1 * 2);
          if (i < 4) tma_ld(sb + i * QSTG, mx, kt * 64, bm * 256, sb + B_QF + 8 * i);
          else tma_ld_mc(sb + (i & 3) * QSTG + rank * 16384, mh, kt * 64, bm * 256 + rank * 128, sb + B_QF + 8 * (i & 3));
        };
        if (l > 0) {
          await_flag(pn, rdy, cnt_x(l, bm) + (lane & 7), ep1 * 2);
#pragma unroll 1
          for (int i = 0; i < 2; i++) {
            e_expect_tx(sb + B_QF + 8 * i, 16384);
            tma_ld(sb + i * QSTG + (po ^ 1) * 16384, &prm.m[M_XSO], (2 * pn + i) * 64, (pm ^ 1) * 128, sb + B_QF + 8 * i);
          }
          mbar_wait(sb + B_QF, 0);
          q_a(2);
          mbar_wait(sb + B_QF + 8, 0);
        }
#pragma unroll 1
        for (int i = l ? 3 : 4; i < 16; i++) {
          if (l == 3 && i == 12) poll_ge(cnt_ad(bn), ep1 * 16);
          q_b(i); q_a(i);
        }
        if (l & 1) {
          bar_sync(NB_KV, 288);
          sts128(sb + ONES + lane * 32, 0x3f803f80u, 0x3f803f80u, 0x3f803f80u, 0x3f803f80u);
          sts128(sb + ONES + lane * 32 + 16, 0x3f803f80u, 0x3f803f80u, 0x3f803f80u, 0x3f803f80u);
          fence_async_smem();
          __syncwarp();
          e_arrive(sb + B_TF);
          const int krow = 2 * bn * 2048 + bm * 256;
          uint32_t* kvc = cnt_kv(l >> 1, bn);
          uint32_t seen = 0;
#pragma unroll 1
          for (int it = 1; it < 16; it++) {
            const int s = it & 3;
            if (it == 4) {
              bar_sync(NB_KV + 12, 288);
              mbar_wait(sb + B_TF + 24, 0);
#pragma unroll 1
              for (int i = 0; i < 4; i++) tma_st(&prm.m[M_K + (i >> 1)], 0, krow + 2048 + (i & 1) * 128, sb + i * 8192);
              bulk_commit();
            }
            if (it == 5) { bulk_wait_n<0>(); e_red(kvc + 16 + bm); }
            if (it == 12) { e_expect_tx(sb + B_RF, 32768); tma_ld3(sb + RES, &prm.m[M_XSR], 0, pm * 128, 2 * pn, sb + B_RF); }
            mbar_wait(sb + B_TE + 8 * s, ((it >> 2) & 1) ^ 1);
            if (it < 8) {
#pragma unroll 1
              for (uint32_t n = 0; n < 200000u && (~seen & (3u << (2 * it - 2) | (it == 4 ? 0xC000u : 0u))); n++)
                seen = __ballot_sync(~0u, (int)(ld_acquire(kvc + (lane < 7 || lane == 15 ? (bm + 1 + lane) & 7 : 8 + ((bm + 2 + lane) & 7))) - ep1) >= 0);
              fence_async_gl();
            } else if (it == 8) { poll_ge(kvc + 16 + (lane & 7), ep1); fence_async_gl(); }
            e_expect_tx(sb + B_TF + 8 * s, 32768);
#pragma unroll 1
            for (int i = 0; i < 2; i++) {
              const int u = 2 * it - 2 + i;
              const int row = 2 * bn * 2048 + (it > 7 ? 2048 + ((bm + it) & 7) * 256 + i * 128 : u < 7 ? ((bm + 1 + u) & 7) * 256 : ((bm + 2 + u) & 7) * 256 + 128);
              tma_ld(sb + T0 + s * TSTG + i * 8192, &prm.m[M_K], 0, row, sb + B_TF + 8 * s);
              tma_ld(sb + T0 + s * TSTG + 16384 + i * 8192, &prm.m[M_V], 0, row, sb + B_TF + 8 * s);
            }
          }
        }
        auto p_b = [&](int i, uint32_t s, uint32_t par) {
          mbar_wait(sb + B_PE + 8 * s, par ^ 1);
          e_expect_tx(sb + B_PF + 8 * s, PSTG);
          tma_ld5(sb + pslot_b(s), mo, i >> 3, 2 * (i & 7), 2 * pn, sb + B_PF + 8 * s);
        };
        auto p_a = [&](int i, uint32_t s) {
          await_flag(i, rdy, cnt_o(l, pm, (lane >> 3) & 1) + (lane & 7), ep1 * 2);
          tma_ld_mc(sb + pslot_a(s, l) + rank * 8192, &prm.m[M_OS], i * 64, pm * 128 + rank * 64, sb + B_PF + 8 * s);
        };
        auto p_a2 = [&](int i) {
          await_flag(i, rdy, cnt_o(l, pm, (lane >> 3) & 1) + (lane & 7), ep1 * 2);
          tma_ld(sb + pslot_a(i, l), &prm.m[M_OS], i * 64, pm * 128, sb + B_PF + 8 * i);
          tma_ld(sb + pslot_a(i, l) + 8192, &prm.m[M_OS], i * 64, pm * 128 + 64, sb + B_PF + 8 * i);
        };
        rdy = 0;
        if (l & 1) {
#pragma unroll 1
          for (int u = 0; u < 6; u++) { const int i = (0x205413 >> (4 * u)) & 7; if (u == 4) mbar_wait(sb + B_TE, 1); p_b(i, i, i < 4 ? 1 : 0); }
#pragma unroll 1
          for (int u = 0; u < 6; u++) {
            const int i = (0x542130 >> (4 * u)) & 7;
            if (!(u & 1)) mbar_wait(sb + B_TE + 8 + 4 * u, 1);
            if (u == 4) bar_sync(NB_ST, 64);
            p_a2(i);
          }
        } else {
#pragma unroll 1
          for (int u = 0; u < 6; u++) { const int i = (0x025413 >> (4 * u)) & 7; if (u == 0 || u == 3) mbar_wait(sb + B_QE + 8 * (u / 3), 1); p_b(i, i, 0); }
          mbar_wait(sb + B_QE + 24, 1);
          e_expect_tx(sb + B_RF, 32768);
          tma_ld3(sb + RES, &prm.m[l == 0 ? M_X0R : M_XSR], 0, pm * 128, 2 * pn, sb + B_RF);
          p_a2(0);
          bar_sync(NB_DONE, 64);
          e_arrive_both(sb + B_PA);
          p_a2(1);
          mbar_wait(sb + B_PA, (l >> 1) & 1);
#pragma unroll 1
          for (int i = 2; i < 6; i++) { if (i > 2) mbar_wait(sb + B_PF + 8 * (i - 3), 0); p_a(i, i); }
        }
        uint32_t s = 0, lap = 1;
#pragma unroll 1
        for (int i = 6; i < 16; i++) {
          p_b(i, s, ((s < 4 ? l : 0) + lap) & 1);
          p_a(i, s);
          if (++s == 6) { s = 0; lap++; }
        }
        const CUtensorMap* mn = &prm.m[M_WQA + ((l + 1) & 1)];
        if (l < 3) {
          mbar_wait(sb + B_PE + 8 * 4, 1); mbar_wait(sb + B_PE + 8 * 5, 1);
          tma_ld3(sb + 32768, mn, bn * 64, 2 * pn * 64, 0, sb + B_QL);
          mbar_wait(sb + B_PE + 8 * 0, l & 1);
          tma_ld3(sb + QSTG + 32768, mn, bn * 64, (2 * pn + 1) * 64, 0, sb + B_QL);
          mbar_wait(sb + B_PE + 8 * 1, l & 1);
          e_expect_tx(sb + B_QF + 16, QSTG);
          tma_ld3(sb + 2 * QSTG + 32768, mn, bn * 64, ((2 * pn) ^ 2) * 64, 0, sb + B_QF + 16);
        }
        if (l < 3) { bar_sync(NB_X, 288); e_expect_tx(sb + B_QL, 49152); }
      }
      if (blockIdx.x == 0 && lane_id() == 0) *(volatile uint32_t*)&g_epoch = ep1;
    } else {
      const int hw = w - 1;
      if (lane < 5) asm volatile("prefetch.tensormap [%0];" ::"l"(&prm.m[5 * hw + lane]) : "memory");
      __syncwarp();
      cluster_wait();
      mbar_wait(sb + B_QF, 0);
#pragma unroll 1
      for (int l = 0; l < 4; l++) {
        IDS();
        if (l > 0) { mbar_wait(sb + B_QL, (l + 1) & 1); mbar_wait(sb + B_QF + 8 * 3, 0); }
        if (l == 0) {
#pragma unroll 1
          for (int r = 2 * hw; r < 16; r += 6) {
            const uint4* p = (const uint4*)(prm.x0 + (size_t)(b * 16 + r) * 1024) + lane;
            float s1[2] = {0.f, 0.f}, s2[2] = {0.f, 0.f};
#pragma unroll
            for (int i = 0; i < 8; i++) {
              const uint4 v = __ldg(p + 32 * i);
              const uint32_t u[4] = {v.x, v.y, v.z, v.w};
#pragma unroll
              for (int k = 0; k < 4; k++) { const float a = bf_lo(u[k]), c = bf_hi(u[k]); s1[i >> 2] += a + c; s2[i >> 2] = fmaf(a, a, fmaf(c, c, s2[i >> 2])); }
            }
#pragma unroll
            for (int o = 16; o; o >>= 1)
#pragma unroll
              for (int rr = 0; rr < 2; rr++) { s1[rr] += __shfl_xor_sync(~0u, s1[rr], o); s2[rr] += __shfl_xor_sync(~0u, s2[rr], o); }
            if (lane == 0) *(float4*)&g_stats[b * 16 + r] = make_float4(s1[0], s2[0], s1[1], s2[1]);
          }
        }
        if (l < 2) {
          float cs[8];
#pragma unroll
          for (int i = 0; i < 8; i++) cs[i] = 0.f;
          const uint4* wp = (const uint4*)(prm.wq[l] + (size_t)(bm * 128 + (lane >> 3)) * 3072 + hw * 1024 + bn * 64) + (lane & 7);
#pragma unroll 8
          for (int i = 0; i < 32; i++) {
            const uint4 v = __ldg(wp + (size_t)i * 4 * 384);
            cs[0] += bf_lo(v.x); cs[1] += bf_hi(v.x); cs[2] += bf_lo(v.y); cs[3] += bf_hi(v.y);
            cs[4] += bf_lo(v.z); cs[5] += bf_hi(v.z); cs[6] += bf_lo(v.w); cs[7] += bf_hi(v.w);
          }
#pragma unroll
          for (int i = 0; i < 8; i++) { cs[i] += __shfl_xor_sync(~0u, cs[i], 8); cs[i] += __shfl_xor_sync(~0u, cs[i], 16); }
          if (lane < 8) {
            float4* d = (float4*)(g_csp + ((l * 16 + bn) * 8 + bm) * 192 + hw * 64 + lane * 8);
            d[0] = make_float4(cs[0], cs[1], cs[2], cs[3]); d[1] = make_float4(cs[4], cs[5], cs[6], cs[7]);
          }
          __syncwarp();
          asm volatile("fence.acq_rel.gpu;" ::: "memory");
          e_red_relaxed(cnt_cs(l, bn));
          if (l == 0) e_red_relaxed(cnt_x(0, bm) + pn);
          poll_ge(lane < 8 && l == 0 ? cnt_x(0, bm) + lane : cnt_cs(l, bn), ep1 * (lane < 8 && l == 0 ? 6 : 24));
        }
        if (l > 0) poll_ge(cnt_x(l, bm) + (lane & 7), ep1 * 2);
#pragma unroll 1
        for (int it = hw * 32 + lane; it < 176; it += 96) {
          const bool rows = it < 128;
          const float4* p = rows ? (const float4*)(g_stats + bm * 256) + it : (const float4*)(g_csp + ((l & 1) * 16 + bn) * 8 * 192) + (it - 128);
          const int stride = rows ? 1024 : 48, np = rows && l == 0 ? 1 : 8;
          float4 a = make_float4(0.f, 0.f, 0.f, 0.f);
#pragma unroll
          for (int k = 0; k < 8; k++) if (k < np) { const float4 v = __ldcg(p + k * stride); a.x += v.x; a.y += v.y; a.z += v.z; a.w += v.w; }
          if (rows) {
            const float m0 = a.x * (1.f / 1024.f), m1 = a.z * (1.f / 1024.f);
            const float v0 = fmaxf(a.y * (1.f / 1024.f) - m0 * m0, 0.f), v1 = fmaxf(a.w * (1.f / 1024.f) - m1 * m1, 0.f);
            const float r0 = __fdividef(1.f, bf_round(sqrtf(bf_round(bf_round(v0) + 1e-5f)))), r1 = __fdividef(1.f, bf_round(sqrtf(bf_round(bf_round(v1) + 1e-5f))));
            a = make_float4(r0, -bf_round(m0) * (l & 1 ? r0 : 1.f), r1, -bf_round(m1) * (l & 1 ? r1 : 1.f));
          }
          *(float4*)(smem + ROWST + it * 16) = a;
        }
        __syncwarp();
        if (lane == 0) asm volatile("red.release.cta.shared.add.u32 [%0], 1;" ::"r"(sb + W_X) : "memory");
        if (hw == 2) {
          if (!(l & 1)) {
            bar_sync(NB_ST, 288);
            const uint4* hp = g_halo + ((l >> 1) * 128 + b - 16) * 384 + lane;
#pragma unroll 1
            for (int h = 0; h < 2; h++) {
              uint32_t t[18];
#pragma unroll
              for (int i = 0; i < 18; i++) t[i] = 0;
#pragma unroll 1
              for (uint32_t n = bm ? 0 : 100000u; n < 100000u; n++) {
                uint32_t miss = 0;
#pragma unroll
                for (int i = 0; i < 6; i++) miss |= ld_tagged(hp + h * 192 + i * 32, &t[3 * i]) ^ ep1;
                if (__all_sync(~0u, !miss)) break;
              }
              mbar_wait(sb + B_QE + 16, 1);
              const uint32_t r = (lane & 7) + ((lane >> 3) & 1) * 8, rv = lane >> 2;
#pragma unroll
              for (int jj = 0; jj < 2; jj++) stsm4(sb + KSC + r * 128 + (((4 * h + 2 * jj + (lane >> 4)) ^ (r & 7)) << 4), t[4 * jj], t[4 * jj + 1], t[4 * jj + 2], t[4 * jj + 3]);
              const uint32_t ad = sb + VSC + rv * 128 + (((4 * h + (lane & 3)) ^ (rv & 7)) << 4);
              sts128(ad, t[8], t[10], t[12], t[14]); sts128(ad + 1024, t[9], t[11], t[13], t[15]);
              if (h == 0 && !(lane & 2)) *(uint32_t*)(smem + HRS + ((lane >> 2) + 8 * (lane & 1)) * 8) = t[16];
              bar_arrive(NB_HALO + h, 64);
            }
          } else {
            mbar_wait(sb + B_TF + 16, 0); mbar_wait(sb + B_TF + 16, 1);
            poll_ge(cnt_kv(l >> 1, bn) + 16 + (lane & 7), ep1);
            const uint4 v = __ldcg((const uint4*)(g_kn + ((l >> 1) * 128 + bn * 8) * 16) + lane);
            const uint32_t mx = max(max(v.x, v.y), max(v.z, v.w));
            const uint32_t m0 = __reduce_max_sync(~0u, (lane & 2) ? 0u : mx), m1 = __reduce_max_sync(~0u, (lane & 2) ? mx : 0u);
            if (lane == 0) *(uint2*)(smem + ROWST) = make_uint2(m0, m1);
            __syncwarp();
            bar_arrive(NB_KN, 160); bar_arrive(NB_KN + 1, 160);
          }
        } else {
          if (l & 1) {
            bar_sync(hw ? NB_HALO : NB_DONE, 160);
            tma_st(&prm.m[M_K], 0, 2 * bn * 2048 + bm * 256 + hw * 128, sb + T0 + hw * 8192);
            tma_st(&prm.m[M_V], 0, 2 * bn * 2048 + bm * 256 + hw * 128, sb + T0 + 16384 + hw * 8192);
            bulk_commit(); bulk_wait_n<0>();
            e_red(cnt_kv(l >> 1, bn) + 8 * hw + bm);
          }
#pragma unroll 1
          for (int i = 0; i < 2; i++) {
            const int h = l & 1 ? i : hw, g = l & 1 ? hw : i;
            bar_sync(NB_SIG + 2 * h + g, 160);
            if (!(l & 1) && i == 0) continue;
            if (i == 1 && hw == 1) bar_arrive(l & 1 ? NB_ST : NB_DONE, 64);
            asm volatile("fence.acq_rel.gpu;" ::: "memory");
            e_red_relaxed(cnt_o(l, 2 * bm + g, h) + (bn >> 1));
            if (!(l & 1)) e_red_relaxed(cnt_o(l, 2 * bm, h) + (bn >> 1));
            if (h == 1 && l == 1) e_red_relaxed(cnt_ad(bn));
          }
        }
        if (hw == 0 && l < 3) {
          bar_sync(NB_X0, 288);
          e_red(cnt_x(l + 1, bm) + pn);
        }
      }
    }
  } else {
    asm volatile("setmaxnreg.inc.sync.aligned.u32 224;");
    const uint32_t zero = prm.zero;
    cluster_wait();
#pragma unroll 1
    for (int l = 0; l < 4; l++) {
      {
        float acc[2][96];
#pragma unroll
        for (int i = 0; i < 96; i++) { acc[0][i] = 0.f; acc[1][i] = 0.f; }
        fence_regs(acc[0]); fence_regs(acc[1]);
        const bool early = l > 0 && wg == ((cta_id() >> 3) & 1);
        uint32_t ep1 = 0;
#pragma unroll 1
        for (int kt = 0; kt < 14; kt++) {
          const int s = kt & 3;
          if (l > 0 && kt == 0) mbar_wait(sb + B_QL, (l + 1) & 1);
          if (!(early && kt < 2)) mbar_wait(sb + B_QF + 8 * s, (kt >> 2) & 1);
          const uint64_t da = prm.xd + wg * 1024 + s * (QSTG >> 4), db = prm.wd + s * (QSTG >> 4);
          wg_fence();
#pragma unroll
          for (int k = 0; k < 4; k++)
#pragma unroll
            for (int m = 0; m < 2; m++) wgmma_m64n192k16_ss_tb(acc[m], da + m * 512 + k * 2, db + k * 128, 1);
          wg_commit();
          if (kt == 4) ep1 = *(volatile uint32_t*)&g_epoch + 1;
          wg_wait<1>();
          if (early && (kt == 1 || kt == 2)) mbar_wait(sb + B_QF + 8 * (kt - 1), 0);
          if (kt > 0 && w == 0) e_arrive_both(sb + B_QE + 8 * ((kt - 1) & 3));
        }
        {
          const bool lag = (l & 1) && wg;
          const uint64_t da = prm.xd + wg * 1024 + 2 * (QSTG >> 4), db = prm.wd + 2 * (QSTG >> 4);
          mbar_wait(sb + B_QF + 16, 1);
          if (lag) {
            mbar_wait(sb + B_QF + 24, 1);
            wg_wait<0>();
            if (w == 0) e_arrive_both(sb + B_QE + 8);
            bar_sync(NB_SC, 256);
          }
          wg_fence();
#pragma unroll
          for (int k = 0; k < 4; k++)
#pragma unroll
            for (int m = 0; m < 2; m++) wgmma_m64n192k16_ss_tb(acc[m], da + m * 512 + k * 2, db + k * 128, 1);
          wg_commit();
          if (!lag) {
            wg_wait<1>();
            if (w == 0) e_arrive_both(sb + B_QE + 8);
            mbar_wait(sb + B_QF + 24, 1);
          }
          wg_fence();
#pragma unroll
          for (int m = 1; m >= 0; m--) {
#pragma unroll
            for (int k = 0; k < 4; k++) wgmma_m64n192k16_ss_tb(acc[m], da + (QSTG >> 4) + m * 512 + k * 2, db + (QSTG >> 4) + k * 128, 1);
            wg_commit();
          }
          if ((l & 1) && !wg) bar_arrive(NB_SC, 256);
          if (!(l & 1)) bar_arrive(NB_ST, 288);
          wg_wait<2>();
          if (w == 0) e_arrive_both(sb + B_QE + 16);
        }
#pragma unroll 1
        for (uint32_t n = 0; n < 4000000u; n++) {
          uint32_t v;
          asm volatile("ld.acquire.cta.shared.u32 %0, [%1];" : "=r"(v) : "r"(sb + W_X) : "memory");
          if (v == (uint32_t)(3 * l + 3)) break;
        }
        IDS();
        const int g = lane >> 2, qd = lane & 3;
        float2 st[2][2];
#pragma unroll
        for (int m = 0; m < 2; m++)
#pragma unroll
          for (int hh = 0; hh < 2; hh++) st[m][hh] = lds64f(sb + ROWST + (wg * 128 + m * 64 + w * 16 + g + 8 * hh) * 8);
        float2 cs[4];
        auto load_cs = [&](int gi) {
#pragma unroll
          for (int j = 0; j < 4; j++) cs[j] = lds64f(sb + COLS + (gi * 32 + j * 8 + 2 * qd) * 4);
        };
        load_cs(2);
        auto drain = [&]() {
          wg_wait<0>(); fence_regs(acc[0]);
          if (w == 0) e_arrive_both(sb + B_QE + 8 * 3);
        };
        wg_wait<1>(); fence_regs(acc[1]);
        auto norm_tile = [&](int gi, int m, float sc, uint32_t (&t)[8], float (&nrm)[2], bool h16 = false) {
          const float r0 = st[m][0].x * sc, s0 = st[m][0].y * sc, r1 = st[m][1].x * sc, s1 = st[m][1].y * sc;
          float n0 = 0.f, n1 = 0.f;
#pragma unroll
          for (int j = 0; j < 4; j++) {
            const float* a = &acc[m][16 * gi + 4 * j];
            const float v0 = fmaf(a[0], r0, s0 * cs[j].x), v1 = fmaf(a[1], r0, s0 * cs[j].y);
            const float v2 = fmaf(a[2], r1, s1 * cs[j].x), v3 = fmaf(a[3], r1, s1 * cs[j].y);
            n0 = fmaf(v0, v0, fmaf(v1, v1, n0)); n1 = fmaf(v2, v2, fmaf(v3, v3, n1));
            t[2 * j] = h16 ? pack2h(v0, v1) : pack2(v0, v1); t[2 * j + 1] = h16 ? pack2h(v2, v3) : pack2(v2, v3);
          }
          nrm[0] = n0; nrm[1] = n1;
        };
        auto norm_group = [&](int gi, float sc, uint32_t (&t)[2][8], float (&nrm)[2][2]) { norm_tile(gi, 0, sc, t[0], nrm[0]); norm_tile(gi, 1, sc, t[1], nrm[1]); };
        uint32_t q[2][2][8];
        const uint32_t srow = (lane & 7) + ((lane >> 3) & 1) * 8;
        const uint32_t row0 = wg * 128 + w * 16;
        auto put_o = [&](int h, int m, const float (&o)[16], float i0, float i1) {
          IDS();
          bf16* op = g_os + (size_t)(bm * 256 + row0 + m * 64 + (lane >> 2)) * 1024 + h * 512 + bn * 32 + (lane & 3) * 8;
          *(uint4*)op = make_uint4(pack2(o[0] * i0, o[1] * i0), pack2(o[4] * i0, o[5] * i0), pack2(o[8] * i0, o[9] * i0), pack2(o[12] * i0, o[13] * i0));
          *(uint4*)(op + 8 * 1024) = make_uint4(pack2(o[2] * i1, o[3] * i1), pack2(o[6] * i1, o[7] * i1), pack2(o[10] * i1, o[11] * i1), pack2(o[14] * i1, o[15] * i1));
        };
        if (!(l & 1)) {
          auto put_kv = [&](int gi, uint32_t r0, const uint32_t (&t)[8]) {
            if (gi < 4) {
              const uint32_t r = r0 + srow;
#pragma unroll
              for (int jj = 0; jj < 2; jj++) stsm4(sb + KSC + r * 128 + (((4 * (gi - 2) + 2 * jj + (lane >> 4)) ^ (r & 7)) << 4), t[4 * jj], t[4 * jj + 1], t[4 * jj + 2], t[4 * jj + 3]);
            } else {
              const uint32_t r = r0 + g, ad = sb + VSC + r * 128 + (((4 * (gi - 4) + qd) ^ (r & 7)) << 4);
              sts128(ad, t[0], t[2], t[4], t[6]); sts128(ad + 1024, t[1], t[3], t[5], t[7]);
            }
          };
          auto cen_tile = [&](int gi, int m, uint32_t (&t)[8]) {
#pragma unroll
            for (int j = 0; j < 4; j++) {
              const float* a = &acc[m][16 * gi + 4 * j];
              t[2 * j] = pack2(fmaf(st[m][0].y, cs[j].x, a[0]), fmaf(st[m][0].y, cs[j].y, a[1]));
              t[2 * j + 1] = pack2(fmaf(st[m][1].y, cs[j].x, a[2]), fmaf(st[m][1].y, cs[j].y, a[3]));
            }
          };
          const bool send = wg == 1 && w == 3 && bm < 7;
          uint4* hp = g_halo + ((l >> 1) * 128 + b) * 384 + lane;
          mbar_wait(sb + B_QE + 16, 1);
          float2 cn[4];
          auto next_cs = [&](int gi) {
#pragma unroll
            for (int j = 0; j < 4; j++) { cs[j] = cn[j]; cn[j] = lds64f(sb + COLS + (gi * 32 + j * 8 + 2 * qd) * 4); }
          };
#pragma unroll
          for (int j = 0; j < 4; j++) cn[j] = cs[j];
#pragma unroll
          for (int h = 0; h < 2; h++) {
            uint32_t k[8], v[8];
            next_cs(4 + h);
            cen_tile(2 + h, 1, k); put_kv(2 + h, 16 + row0 + 64, k);
            next_cs(h ? 2 : 3);
            cen_tile(4 + h, 1, v); put_kv(4 + h, 16 + row0 + 64, v);
            if (send) {
              uint4* p = hp + h * 192;
              st_tagged(p, k[0], k[1], k[2], ep1); st_tagged(p + 32, k[3], k[4], k[5], ep1); st_tagged(p + 64, k[6], k[7], v[0], ep1);
              st_tagged(p + 96, v[1], v[2], v[3], ep1); st_tagged(p + 128, v[4], v[5], v[6], ep1);
              st_tagged(p + 160, v[7], __float_as_uint(qd & 1 ? st[1][1].x : st[1][0].x), 0u, ep1);
            }
            sched_fence();
          }
          drain();
          {
            uint32_t t[8];
            next_cs(4); cen_tile(2, 0, t); put_kv(2, 16 + row0, t);
            next_cs(0); cen_tile(4, 0, t); put_kv(4, 16 + row0, t);
            next_cs(3); cen_tile(0, 0, q[0][0]); cen_tile(0, 1, q[0][1]);
          }
          bar_sync(NB_SC, 256);
          const bool e = g & 1, sel = 2 * qd + (g & 1) >= g + 2, first = bm == 0 && row0 == 0;
          if (row0 == 0) bar_sync(NB_HALO, 64);
          float ra[4], rb[4], ca[4], cb[4];
#pragma unroll
          for (int m = 0; m < 2; m++) {
            float rk[3];
#pragma unroll
            for (int u = 0; u < 3; u++) {
              const int r = row0 + m * 64 + 8 * u + 2 * qd + e - (sel ? 16 : 8);
              rk[u] = lds64f(sb + (m == 0 && r < 0 ? HRS + 128 : ROWST) + r * 8).x;
            }
            ra[2 * m] = sel ? rk[1] : rk[0]; ra[2 * m + 1] = sel ? rk[2] : rk[1];
            rb[2 * m] = sel ? rk[0] : rk[1]; rb[2 * m + 1] = sel ? rk[1] : rk[2];
          }
#pragma unroll
          for (int i = 0; i < 4; i++) { const float rq = st[i >> 1][i & 1].x * QSCALE; ca[i] = rq * ra[i]; cb[i] = rq * rb[i]; }
#pragma unroll 1
          for (int h = 0; h < 2; h++) {
            float s[2][4][4];
            uint32_t vf[2][4][4], pf[2][2][4];
#pragma unroll
            for (int m = 0; m < 2; m++)
#pragma unroll
              for (int nt = 0; nt < 4; nt++) {
                uint32_t kf[4];
                const uint32_t r = row0 + m * 64 + 8 * nt + (lane & 7), ch = 4 * h + (lane >> 3);
                ldsm4(sb + KSC + r * 128 + ((ch ^ (r & 7)) << 4), kf);
                s[m][nt][0] = s[m][nt][1] = s[m][nt][2] = s[m][nt][3] = 0.f;
                mma16816(s[m][nt], q[0][m][0], q[0][m][1], q[0][m][2], q[0][m][3], kf[0], kf[1]);
                mma16816(s[m][nt], q[0][m][4], q[0][m][5], q[0][m][6], q[0][m][7], kf[2], kf[3]);
              }
#pragma unroll
            for (int m = 0; m < 2; m++)
#pragma unroll
              for (int i = 0; i < 4; i++) {
                const uint32_t r = row0 + m * 64 + 16 * (i >> 1) + srow, ch = 4 * h + 2 * (i & 1) + (lane >> 4);
                ldsm4t(sb + VSC + r * 128 + ((ch ^ (r & 7)) << 4), vf[m][i]);
              }
            float va[4], vb[4], mx[4];
#pragma unroll
            for (int i = 0; i < 4; i++) {
              const int m = i >> 1, hh = i & 1;
              const float a = e ? s[m][hh + 1][2 * hh + 1] : s[m][hh + 1][2 * hh];
              const float lo = e ? s[m][hh][2 * hh + 1] : s[m][hh][2 * hh], hi = e ? s[m][hh + 2][2 * hh + 1] : s[m][hh + 2][2 * hh];
              va[i] = (m == 0 && hh == 0 && first) ? -INFINITY : a * ca[i];
              vb[i] = (m == 0 && first && sel) ? -INFINITY : (sel ? lo : hi) * cb[i];
              mx[i] = fmaxf(va[i], vb[i]);
            }
#pragma unroll
            for (int i = 0; i < 4; i++) mx[i] = fmaxf(mx[i], __shfl_xor_sync(~0u, mx[i], 1));
#pragma unroll
            for (int i = 0; i < 4; i++) mx[i] = fmaxf(mx[i], __shfl_xor_sync(~0u, mx[i], 2));
#pragma unroll
            for (int i = 0; i < 4; i++) {
              va[i] = ex2(va[i] - mx[i]); vb[i] = ex2(vb[i] - mx[i]);
              mx[i] = va[i] + vb[i];
              va[i] *= ra[i]; vb[i] *= rb[i];
            }
#pragma unroll
            for (int i = 0; i < 4; i++) mx[i] += __shfl_xor_sync(~0u, mx[i], 1);
#pragma unroll
            for (int i = 0; i < 4; i++) mx[i] += __shfl_xor_sync(~0u, mx[i], 2);
#pragma unroll
            for (int i = 0; i < 4; i++) {
              const int m = i >> 1, hh = i & 1;
              const float inv = rcp(mx[i]);
              const uint32_t t = pack2(va[i] * inv, vb[i] * inv);
              const uint32_t pa = e ? t << 16 : t & 0xFFFFu, pb = e ? t & 0xFFFF0000u : t >> 16;
              pf[m][hh][hh + 1] = pa; pf[m][hh][hh] = sel ? pb : 0u; pf[m][hh][hh + 2] = sel ? 0u : pb; pf[m][hh][3 - 3 * hh] = 0u;
            }
#pragma unroll
            for (int m = 0; m < 2; m++) {
              float o[4][4];
#pragma unroll
              for (int j = 0; j < 4; j++) o[j][0] = o[j][1] = o[j][2] = o[j][3] = 0.f;
#pragma unroll
              for (int i = 0; i < 4; i++) {
                const int kk = i >> 1, jj = 2 * (i & 1);
                mma16816(o[jj], pf[m][0][2 * kk], pf[m][1][2 * kk], pf[m][0][2 * kk + 1], pf[m][1][2 * kk + 1], vf[m][i][0], vf[m][i][1]);
                mma16816(o[jj + 1], pf[m][0][2 * kk], pf[m][1][2 * kk], pf[m][0][2 * kk + 1], pf[m][1][2 * kk + 1], vf[m][i][2], vf[m][i][3]);
              }
              const float of[16] = {o[0][0], o[0][1], o[0][2], o[0][3], o[1][0], o[1][1], o[1][2], o[1][3], o[2][0], o[2][1], o[2][2], o[2][3], o[3][0], o[3][1], o[3][2], o[3][3]};
              put_o(h, m, of, 1.f, 1.f);
            }
            bar_arrive(NB_SIG + 2 * h + wg, 160);
            if (h == 0) {
              uint32_t t[8];
              next_cs(5); cen_tile(3, 0, t); put_kv(3, 16 + row0, t);
              next_cs(1); cen_tile(5, 0, t); put_kv(5, 16 + row0, t);
#pragma unroll
              for (int j = 0; j < 4; j++) cs[j] = cn[j];
              cen_tile(1, 0, q[0][0]); cen_tile(1, 1, q[0][1]);
              bar_sync(NB_SC, 256);
              if (row0 == 0) bar_sync(NB_HALO + 1, 64);
            }
          }
        } else {
          float qn[2];
          drain();
          auto esc_ptr = [&](int gi) { IDS(); return g_esc + (size_t)(((l & 2) + (gi >> 1)) * 65536 + (2 * bn + (gi & 1)) * 2048) * 20; };
          auto norm_half = [&](int gi, float sc, uint32_t (&t)[2][8], float (&nrm)[2][2]) {
            norm_tile(gi, 0, sc, t[0], nrm[0], true); norm_tile(gi, 1, sc, t[1], nrm[1], true);
            if (!((nrm[0][0] + nrm[0][1]) + (nrm[1][0] + nrm[1][1]) <= 4e9f) || fminf(fminf(nrm[0][0], nrm[0][1]), fminf(nrm[1][0], nrm[1][1])) < 1.5e-5f) {
              uint32_t* p = esc_ptr(gi) + (bm * 256 + row0 + g) * 20 + qd;
#pragma unroll
              for (int m = 0; m < 2; m++) {
                uint32_t u[8]; float d[2];
                norm_tile(gi, m, sc, u, d);
#pragma unroll
                for (int i = 0; i < 10; i++) p[(m * 64 + (i & 1) * 8) * 20 + (i >> 1) * 4] = i < 8 ? u[i] : ep1;
              }
            }
            __syncwarp();
          };
          {
            auto max_norm = [&](const float (&nrm)[2][2]) {
              const bool o1 = qd & 1, o2 = qd & 2;
              const float a = (o1 ? nrm[1][0] : nrm[0][0]) + __shfl_xor_sync(~0u, o1 ? nrm[0][0] : nrm[1][0], 1);
              const float c = (o1 ? nrm[1][1] : nrm[0][1]) + __shfl_xor_sync(~0u, o1 ? nrm[0][1] : nrm[1][1], 1);
              const float d = (o2 ? c : a) + __shfl_xor_sync(~0u, o2 ? a : c, 2);
              return __uint_as_float(__reduce_max_sync(~0u, __float_as_uint(d)));
            };
#pragma unroll
            for (int h = 0; h < 2; h++) {
              uint32_t t[2][8]; float nrm[2][2];
              const uint32_t kb = sb + (h ? 0 : T0);
              if (h) load_cs(3);
              uint32_t tv[2][8];
              norm_half(2 + h, 1.f, t, nrm);
              load_cs(4 + h);
              float nv[2][2];
              if (h == 1) { const float kn = max_norm(nrm); if (lane == 0) g_kn[((l >> 1) * 128 + bn * 8 + bm) * 16 + 8 + wg * 4 + w] = kn; }
              if (h == 0) mbar_wait(sb + B_QE + 8, 1);
#pragma unroll
              for (int i = 0; i < 4; i++) {
                const uint32_t r = row0 + (i >> 1) * 64 + srow;
                stsm4(kb + r * 64 + (((2 * (i & 1) + (lane >> 4)) ^ ((r >> 1) & 3)) << 4), t[i >> 1][4 * (i & 1)], t[i >> 1][4 * (i & 1) + 1], t[i >> 1][4 * (i & 1) + 2], t[i >> 1][4 * (i & 1) + 3]);
              }
              norm_group(4 + h, 1.f, tv, nv);
              load_cs(h);
#pragma unroll
              for (int m = 0; m < 2; m++) {
                const uint32_t r = row0 + m * 64 + g, ad = kb + 16384 + r * 64 + ((qd ^ ((r >> 1) & 3)) << 4);
                sts128(ad, tv[m][0], tv[m][2], tv[m][4], tv[m][6]); sts128(ad + 512, tv[m][1], tv[m][3], tv[m][5], tv[m][7]);
              }
              fence_async_smem();
              bar_arrive(NB_KV + 12 * h, 288);
              if (h == 0) {
                bar_arrive(wg ? NB_HALO : NB_DONE, 160);
                if (wg) bar_sync(NB_HALO + 1, 256);
              }
              if (h == 0) { const float kn = max_norm(nrm); if (lane == 0) g_kn[((l >> 1) * 128 + bn * 8 + bm) * 16 + wg * 4 + w] = kn; }
              norm_half(h, QSCALE, q[h], nrm);
#pragma unroll
              for (int i = 0; i < 4; i++) sts128(sb + QPARK + h * 16384 + (wg * 128 + w * 32 + lane) * 16 + i * 4096, q[h][i >> 1][4 * (i & 1)], q[h][i >> 1][4 * (i & 1) + 1], q[h][i >> 1][4 * (i & 1) + 2], q[h][i >> 1][4 * (i & 1) + 3]);
              qn[h] = max_norm(nrm);
            }
            if (!wg) bar_arrive(NB_HALO + 1, 256);
          }
          constexpr uint64_t VSTEP = 64 - (64ull << 16);
          const uint32_t c_882 = 0x62E562E5u + (lane_id() & zero), c_lsb = 0x00010001u + (lane_id() & zero), c_half = 0x3F003F00u + (lane_id() & zero);
          float o[2][20], S[2][32];
          uint32_t H[2][16], P0[4] = {}, P1[4] = {};
#pragma unroll
          for (int m = 0; m < 2; m++) {
#pragma unroll
            for (int i = 0; i < 20; i++) o[m][i] = 0.f;
            fence_regs(o[m]);
          }
          auto qkf = [&](int b, int ks, uint64_t d) { wg_n64_rs_nb_f16_f32(S[b], q[0][0][4 * ks], q[0][0][4 * ks + 1], q[0][0][4 * ks + 2], q[0][0][4 * ks + 3], d + 2 * ks, ks ? 1 : zero); };
          auto qkh = [&](int b, int ks, uint64_t d) { wg_n64_rs_nb_f16_f16(H[b], q[0][1][4 * ks], q[0][1][4 * ks + 1], q[0][1][4 * ks + 2], q[0][1][4 * ks + 3], d + 2 * ks, ks ? 1 : zero); };
          auto pv0 = [&](uint64_t d) { wgmma_m64n40k16_rs_tb(o[0], P0[0], P0[1], P0[2], P0[3], d, 1); };
          auto pv1 = [&](uint64_t d) { wgmma_m64n40k16_rs_tb(o[1], P1[0], P1[1], P1[2], P1[3], d, 1); };
          float e[4] = {};
          auto finish = [&](int h) {
            const float* s = &S[(h >> 2) & 1][8 * (h & 3)];
            const uint32_t* u = &H[(h >> 2) & 1][4 * (h & 3)];
            const float z0 = exp2_fix(s[6]), z1 = exp2_fix(s[7]);
            P0[0] = pack2v(e[0], e[1]);
            P1[0] = exp2_h2(u[0], c_882);
            P0[1] = pack2v(e[2], e[3]);
            P1[1] = exp2_h2(u[1], c_882);
            const uint32_t B = exp2_base(z0, z1), E = and_or<0x7F807F80u>(B, c_lsb);
            P1[3] = exp2_h2(u[3], c_882);
            P0[3] = fma_bf2(B, and_or<0x807F807Fu>(B, c_half), E);
            const float e4 = ex2v(s[4]), e5 = ex2v(s[5]);
            P1[2] = exp2_h2(u[2], c_882);
            P0[2] = pack2v(e4, e5);
          };
          auto start = [&](int h) {
            const float* s = &S[(h >> 2) & 1][8 * (h & 3)];
            e[0] = ex2v(s[0]); e[1] = ex2v(s[1]); e[3] = ex2v(s[3]); e[2] = ex2v(s[2]);
          };
          uint64_t kd = prm.kv[0].kd;
          mbar_wait(sb + B_TF, 0);
          wg_fence();
#pragma unroll
          for (int b = 0; b < 2; b++) {
            wg_n64_rs_nb_f16_f32_z(S[b], q[0][0][0], q[0][0][1], q[0][0][2], q[0][0][3], kd + 256 * b, 0);
            wg_n64_rs_nb_f16_f16_z(H[b], q[0][1][0], q[0][1][1], q[0][1][2], q[0][1][3], kd + 256 * b, 0);
            if (b == 0) { qkf(0, 1, kd); qkh(0, 1, kd); }
            wg_commit();
          }
          wg_wait<1>(); fence_regs(S[0]); fence_regs(H[0]);
          start(0); finish(0); start(1);
          wg_wait<0>();
          int redo = 0;
#pragma unroll 1
          for (int pass = 0, j = 1; pass < 2; pass++) {
#pragma unroll 1
           do {
            const uint64_t vd = prm.kv[j & 3].vd;
            bool go = false;
#pragma unroll
            for (int h = 2; h < 18; h++) {
              const int px = (h >> 2) + 1, c = h & 3;
              wg_fence();
              if (h == 13) kd = prm.kv[j & 3].kd;
              const uint64_t kx = kd + (px & 3) * 256, vx = vd + (h - 2) * VSTEP;
              if (h == 2) { qkh(1, 0, kx); qkf(1, 0, kx); pv0(vx); pv1(vx); qkh(1, 1, kx); qkf(1, 1, kx); }
              else if ((c == 1 || c == 2) && h < 17) { qkh(px & 1, c - 1, kx); pv1(vx); qkf(px & 1, c - 1, kx); pv0(vx); }
              else { pv0(vx); pv1(vx); }
              wg_commit();
              if (h == 3) e_arrive_if(sb + B_TE + 8 * ((j + 2) & 3), j > 1);
              if (h == 11) go = mbar_test(sb + B_TF + 8 * (j & 3), (j >> 2) & 1) && j != 8;
              finish(h - 1); start(h);
              if (h != 12 && h != 17) sched_fence();
              if (h == 12 && !go) {
                if (j == 16) {
#pragma unroll
                  for (int u = 13; u < 18; u++) {
                    wg_fence(); pv0(vd + (u - 2) * VSTEP); pv1(vd + (u - 2) * VSTEP); wg_commit();
                    if (u < 17) finish(u - 1);
                    if (u < 16) { start(u); sched_fence(); }
                    if (u & 1) { if (u == 17) wg_wait<0>(); else wg_wait<1>(); }
                  }
                  e_arrive(sb + B_TE + 24);
                  goto head_done;
                }
                mbar_wait(sb + B_TF + 8 * (j & 3), (j >> 2) & 1);
                if (j == 8) {
#pragma unroll
                  for (int i = 0; i < 4; i++) lds128(sb + QPARK + 16384 + (wg * 128 + w * 32 + lane_id()) * 16 + i * 4096, &q[0][i >> 1][4 * (i & 1)]);
                }
              }
              if (h == 17) wg_wait<0>(); else if (h & 1) wg_wait<1>();
              if (c == 3) { fence_regs(S[px & 1]); fence_regs(H[px & 1]); }
            }
           } while (j++ & 7);
           head_done:
            fence_regs(o[0]); fence_regs(o[1]);
            uint32_t pk[2][8];
            {
              IDS();
              bf16* op = g_os + (size_t)(bm * 256 + row0 + (lane >> 2)) * 1024 + pass * 512 + bn * 32 + (lane & 3) * 8;
#pragma unroll
              for (int i = 0; i < 4; i++) {
                const float* a = &o[i >> 1][2 * (i & 1)];
                const float inv = rcp(a[16]);
                uint32_t* u = &pk[i >> 1][4 * (i & 1)];
#pragma unroll
                for (int k = 0; k < 4; k++) u[k] = pack2(a[4 * k] * inv, a[4 * k + 1] * inv);
                *(uint4*)(op + ((i >> 1) * 64 + (i & 1) * 8) * 1024) = make_uint4(u[0], u[1], u[2], u[3]);
              }
            }
            sched_fence();
            if (pass == 0) bar_sync(NB_KN + wg, 160);
            const float kmax = *(volatile float*)(smem + ROWST + 4 * pass);
            const bool wide = !(qn[0] <= 1.6e7f) | !(kmax <= 1.6e7f) | !(qn[0] * kmax <= 112.f * 112.f);
            int badm = 0;
#pragma unroll
            for (int m = 0; m < 2; m++) {
              uint32_t chk[2] = {0u, 0u};
#pragma unroll
              for (int i = 0; i < 8; i++) asm("fma.rn.bf16x2 %0, %1, %2, %0;" : "+r"(chk[i & 1]) : "r"(pk[m][i]), "r"(0u));
              const bool bad = wide | !(fminf(o[m][16], o[m][18]) >= 9.3e-10f) | !(o[m][16] + o[m][18] <= 1e36f) | (((chk[0] | chk[1]) & 0x7FFF7FFFu) != 0);
              badm |= __any_sync(~0u, bad) << m;
            }
            if (!badm) bar_arrive(NB_SIG + 2 * pass + wg, 160);
            qn[0] = qn[1];
#pragma unroll
            for (int m = 0; m < 2; m++) {
#pragma unroll
              for (int i = 0; i < 20; i++) o[m][i] = 0.f;
              fence_regs(o[m]);
            }
            if (badm) {
              redo |= badm << 2 * pass;
              const int tx = wg * 128 + w * 32 + lane_id();
              uint4* p = g_qsave + (block_id() * 256 + tx) * 8 + pass * 4;
#pragma unroll
              for (int i = 0; i < 4; i++) {
                uint32_t u[4] = {q[0][i >> 1][4 * (i & 1)], q[0][i >> 1][4 * (i & 1) + 1], q[0][i >> 1][4 * (i & 1) + 2], q[0][i >> 1][4 * (i & 1) + 3]};
                if (pass == 0) lds128(sb + QPARK + tx * 16 + i * 4096, u);
                p[i] = make_uint4(u[0], u[1], u[2], u[3]);
              }
            }
          }
          if (redo) attn_redo(redo, l, cta_id(), wg, w, ep1);
        }
      }
      {
        float acc[64];
#pragma unroll
        for (int i = 0; i < 64; i++) acc[i] = 0.f;
        fence_regs(acc);
        uint32_t s = 0, lap = 0;
#pragma unroll 1
        for (int kt = 0; kt < 16; kt++) {
          mbar_wait(sb + B_PF + 8 * s, ((s < 4 ? l : 0) + lap) & 1);
          const uint64_t da = mkdesc(sb + pslot_a(s, l) + wg * 8192, 16, 1024, 1), db = mkdesc(sb + pslot_b(s), 8192, 1024, 1);
          wg_fence();
#pragma unroll
          for (int k = 0; k < 4; k++) wgmma_m64n128k16_ss_tb(acc, da + k * 2, db + k * 128, 1);
          wg_commit();
          wg_wait<1>();
          if (kt > 0 && w == 0) e_arrive_both(sb + B_PE + 8 * (s ? s - 1 : 5));
          if (++s == 6) { s = 0; lap++; }
        }
        IDS();
        const int g = lane >> 2, qd = lane & 3;
        const int r0 = wg * 64 + w * 16;
        const uint32_t r = r0 + (lane & 7) + ((lane >> 3) & 1) * 8;
        uint32_t x[8][4];
        mbar_wait(sb + B_RF, l & 1);
#pragma unroll
        for (int jj = 0; jj < 8; jj++) ldsm4(sb + RES + (jj >> 2) * 16384 + r * 128 + ((((2 * jj + (lane >> 4)) & 7) ^ (r & 7)) << 4), x[jj]);
        wg_wait<0>();
        fence_regs(acc);
        if (w == 0) e_arrive_both(sb + B_PE + 8 * 3);
        const CUtensorMap* mo = &prm.m[l == 3 ? M_OUT : M_XST];
#pragma unroll
        for (int jj = 0; jj < 8; jj++) {
#pragma unroll
          for (int i = 0; i < 4; i++) x[jj][i] = add_bf16x2(x[jj][i], pack2(acc[8 * jj + 2 * i], acc[8 * jj + 2 * i + 1]));
          stsm4(sb + RES + (jj >> 2) * 16384 + r * 128 + ((((2 * jj + (lane >> 4)) & 7) ^ (r & 7)) << 4), x[jj][0], x[jj][1], x[jj][2], x[jj][3]);
          if ((jj & 3) == 3) { fence_async_smem(); __syncwarp(); tma_st(mo, pn * 128 + (jj >> 2) * 64, pm * 128 + r0, sb + RES + (jj >> 2) * 16384 + r0 * 128); }
        }
        bulk_commit();
        if (l < 3) {
          bar_sync(NB_SC, 256);
#pragma unroll
          for (int jj = 0; jj < 8; jj++)
            stsm4(sb + (jj >> 2) * QSTG + po * 16384 + r * 128 + ((((2 * jj + (lane >> 4)) & 7) ^ (r & 7)) << 4), x[jj][0], x[jj][1], x[jj][2], x[jj][3]);
          fence_async_smem();
          bar_arrive(NB_X, 288);
          float s1[4] = {0.f, 0.f, 0.f, 0.f}, sa[4] = {0.f, 0.f, 0.f, 0.f}, sc[4] = {0.f, 0.f, 0.f, 0.f};
#pragma unroll
          for (int jj = 0; jj < 8; jj++) {
            mma16816(s1, x[jj][0], x[jj][1], x[jj][2], x[jj][3], 0x3f803f80u, 0x3f803f80u);
            mma16816(sa, x[jj][0], x[jj][1], x[jj][2], x[jj][3], x[jj][0], x[jj][2]);
            mma16816(sc, x[jj][0], x[jj][1], x[jj][2], x[jj][3], x[jj][1], x[jj][3]);
          }
          if (qd == g >> 1) {
            float2* p = g_stats + pn * 2048 + pm * 128 + r0 + g;
            p[0] = make_float2(s1[0], g & 1 ? sa[1] : sa[0]);
            p[8] = make_float2(s1[2], g & 1 ? sc[3] : sc[2]);
          }
        }
        bulk_wait_n<0>();
        if (l < 3) bar_arrive(NB_X0, 288);
      }
    }
  }
  asm volatile("barrier.cluster.arrive.relaxed.aligned;\nbarrier.cluster.wait.aligned;" ::: "memory");
}

typedef CUresult (*EncodeFn)(CUtensorMap*, CUtensorMapDataType, cuuint32_t, void*, const cuuint64_t*, const cuuint64_t*, const cuuint32_t*,
                             const cuuint32_t*, CUtensorMapInterleave, CUtensorMapSwizzle, CUtensorMapL2promotion, CUtensorMapFloatOOBfill);

static void make_map(EncodeFn fn, CUtensorMap* m, const void* ptr, int rank, const uint64_t* dims, const uint64_t* strides, const uint32_t* box, CUtensorMapSwizzle sw) {
  cuuint64_t d[5], st[4];
  cuuint32_t bx[5], es[5];
  for (int i = 0; i < rank; i++) { d[i] = dims[i]; bx[i] = box[i]; es[i] = 1; if (i) st[i - 1] = strides[i - 1] * 2; }
  fn(m, CU_TENSOR_MAP_DATA_TYPE_BFLOAT16, rank, (void*)ptr, d, st, bx, es, CU_TENSOR_MAP_INTERLEAVE_NONE, sw,
     CU_TENSOR_MAP_L2_PROMOTION_L2_128B, CU_TENSOR_MAP_FLOAT_OOB_FILL_NONE);
}
static void map2(EncodeFn fn, CUtensorMap* m, const void* ptr, uint64_t inner, uint64_t outer, uint32_t bi, uint32_t bo, CUtensorMapSwizzle sw) {
  const uint64_t d[2] = {inner, outer}, st[1] = {inner};
  const uint32_t bx[2] = {bi, bo};
  make_map(fn, m, ptr, 2, d, st, bx, sw);
}

extern "C" void kernel_launch(void* const* d_in, const int* in_sizes, int n_in, void* d_out, int out_size) {
  (void)in_sizes; (void)n_in; (void)out_size;
  static EncodeFn enc = nullptr;
  static void *xs, *os, *kk, *vv;
  static int sbase = 1024;
  if (!enc) {
    void* p = nullptr;
    cudaDriverEntryPointQueryResult qr;
    cudaGetDriverEntryPoint("cuTensorMapEncodeTiled", &p, cudaEnableDefault, &qr);
    enc = (EncodeFn)p;
    Scratch* sc = nullptr;
    cudaGetSymbolAddress((void**)&sc, g_s);
    xs = sc->xs; os = sc->os; kk = sc->k; vv = sc->v;
    int dev = 0;
    cudaGetDevice(&dev);
    cudaDeviceGetAttribute(&sbase, cudaDevAttrReservedSharedMemoryPerBlock, dev);
    cudaFuncSetAttribute(fused_kernel, cudaFuncAttributeMaxDynamicSharedMemorySize, SMEM_BYTES);
  }
  Params prm;
  const CUtensorMapSwizzle S128 = CU_TENSOR_MAP_SWIZZLE_128B, S64 = CU_TENSOR_MAP_SWIZZLE_64B;
  map2(enc, &prm.m[M_X0A], d_in[0], 1024, 2048, 64, 256, S128);
  map2(enc, &prm.m[M_XSA], xs, 1024, 2048, 64, 256, S128);
  for (int t = 0; t < 2; t++) {
    const uint64_t d3[3] = {1024, 1024, 3}, s3[2] = {3072, 1024};
    const uint32_t b3[3] = {64, 64, 3};
    make_map(enc, &prm.m[M_WQA + t], d_in[1 + 3 * t], 3, d3, s3, b3, S128);
    const uint64_t d5[5] = {64, 32, 2, 16, 16}, s5[4] = {1024, 32 * 1024, 64 * 1024, 64};
    const uint32_t b5[5] = {64, 32, 1, 2, 2};
    make_map(enc, &prm.m[M_WOA + t], d_in[2 + 3 * t], 5, d5, s5, b5, S128);
    const uint64_t dr[3] = {64, 2048, 16}, sr[2] = {1024, 64};
    const uint32_t br[3] = {64, 128, 2};
    make_map(enc, &prm.m[M_X0R + t], t ? xs : d_in[0], 3, dr, sr, br, S128);
  }
  map2(enc, &prm.m[M_OS], os, 1024, 2048, 64, 64, S128);
  map2(enc, &prm.m[M_K], kk, 32, 65536, 32, 128, S64);
  map2(enc, &prm.m[M_V], vv, 32, 65536, 32, 128, S64);
  map2(enc, &prm.m[M_XSO], xs, 1024, 2048, 64, 128, S128);
  map2(enc, &prm.m[M_X0H], d_in[0], 1024, 2048, 64, 128, S128);
  map2(enc, &prm.m[M_XST], xs, 1024, 2048, 64, 16, S128);
  map2(enc, &prm.m[M_OUT], d_out, 1024, 2048, 64, 16, S128);
  prm.x0 = (const bf16*)d_in[0];
  prm.wq[0] = (const bf16*)d_in[1]; prm.wq[1] = (const bf16*)d_in[4];
  prm.zero = 0;
  for (int i = 0; i < 128; i++) prm.map[i] = remap(i);
  {
    const uint64_t hi = 0x80000020ull << 32, k0 = sbase + T0, v0 = k0 + 16384, vstep = 64 - (64ull << 16);
    prm.wd = mkdesc(sbase + 32768, 8192, 1024, 1); prm.xd = mkdesc(sbase, 16, 1024, 1);
    for (int j = 0; j < 4; j++) {
      prm.kv[j].kd = (hi | 1u << 16 | k0 >> 4) + 2048 * ((j < 16 ? j : 15) & 3);
      prm.kv[j].vd = (hi | (uint64_t)(ONES - T0 - 16384) >> 4 << 16 | v0 >> 4) + 32 * vstep * ((j + 3) & 3);
    }
  }
  fused_kernel<<<128, 384, SMEM_BYTES>>>(prm);
}
```

```cpp
#include <cuda_runtime.h>
#include <cuda_bf16.h>
#include <cuda.h>
#include <stdint.h>

typedef __nv_bfloat16 bf16;

__device__ __forceinline__ void wgmma_m64n192k16_ss_tb(float (&d)[96], uint64_t da, uint64_t db, int scale_d) {
  asm volatile("{\n.reg .pred p;\nsetp.ne.b32 p, %98, 0;\n"
    "wgmma.mma_async.sync.aligned.m64n192k16.f32.bf16.bf16 "
    "{%0, %1, %2, %3, %4, %5, %6, %7, %8, %9, %10, %11, %12, %13, %14, %15, "
    "%16, %17, %18, %19, %20, %21, %22, %23, %24, %25, %26, %27, %28, %29, %30, %31, "
    "%32, %33, %34, %35, %36, %37, %38, %39, %40, %41, %42, %43, %44, %45, %46, %47, "
    "%48, %49, %50, %51, %52, %53, %54, %55, %56, %57, %58, %59, %60, %61, %62, %63, "
    "%64, %65, %66, %67, %68, %69, %70, %71, %72, %73, %74, %75, %76, %77, %78, %79, "
    "%80, %81, %82, %83, %84, %85, %86, %87, %88, %89, %90, %91, %92, %93, %94, %95}, "
    "%96, %97, p, 1, 1, 0, 1;\n}\n"
    : "+f"(d[0]), "+f"(d[1]), "+f"(d[2]), "+f"(d[3]), "+f"(d[4]), "+f"(d[5]), "+f"(d[6]), "+f"(d[7]),
      "+f"(d[8]), "+f"(d[9]), "+f"(d[10]), "+f"(d[11]), "+f"(d[12]), "+f"(d[13]), "+f"(d[14]), "+f"(d[15]),
      "+f"(d[16]), "+f"(d[17]), "+f"(d[18]), "+f"(d[19]), "+f"(d[20]), "+f"(d[21]), "+f"(d[22]), "+f"(d[23]),
      "+f"(d[24]), "+f"(d[25]), "+f"(d[26]), "+f"(d[27]), "+f"(d[28]), "+f"(d[29]), "+f"(d[30]), "+f"(d[31]),
      "+f"(d[32]), "+f"(d[33]), "+f"(d[34]), "+f"(d[35]), "+f"(d[36]), "+f"(d[37]), "+f"(d[38]), "+f"(d[39]),
      "+f"(d[40]), "+f"(d[41]), "+f"(d[42]), "+f"(d[43]), "+f"(d[44]), "+f"(d[45]), "+f"(d[46]), "+f"(d[47]),
      "+f"(d[48]), "+f"(d[49]), "+f"(d[50]), "+f"(d[51]), "+f"(d[52]), "+f"(d[53]), "+f"(d[54]), "+f"(d[55]),
      "+f"(d[56]), "+f"(d[57]), "+f"(d[58]), "+f"(d[59]), "+f"(d[60]), "+f"(d[61]), "+f"(d[62]), "+f"(d[63]),
      "+f"(d[64]), "+f"(d[65]), "+f"(d[66]), "+f"(d[67]), "+f"(d[68]), "+f"(d[69]), "+f"(d[70]), "+f"(d[71]),
      "+f"(d[72]), "+f"(d[73]), "+f"(d[74]), "+f"(d[75]), "+f"(d[76]), "+f"(d[77]), "+f"(d[78]), "+f"(d[79]),
      "+f"(d[80]), "+f"(d[81]), "+f"(d[82]), "+f"(d[83]), "+f"(d[84]), "+f"(d[85]), "+f"(d[86]), "+f"(d[87]),
      "+f"(d[88]), "+f"(d[89]), "+f"(d[90]), "+f"(d[91]), "+f"(d[92]), "+f"(d[93]), "+f"(d[94]), "+f"(d[95])
    : "l"(da), "l"(db), "r"(scale_d));
}

__device__ __forceinline__ void wgmma_m64n128k16_ss_tb(float (&d)[64], uint64_t da, uint64_t db, int scale_d) {
  asm volatile("{\n.reg .pred p;\nsetp.ne.b32 p, %66, 0;\n"
    "wgmma.mma_async.sync.aligned.m64n128k16.f32.bf16.bf16 "
    "{%0, %1, %2, %3, %4, %5, %6, %7, %8, %9, %10, %11, %12, %13, %14, %15, "
    "%16, %17, %18, %19, %20, %21, %22, %23, %24, %25, %26, %27, %28, %29, %30, %31, "
    "%32, %33, %34, %35, %36, %37, %38, %39, %40, %41, %42, %43, %44, %45, %46, %47, "
    "%48, %49, %50, %51, %52, %53, %54, %55, %56, %57, %58, %59, %60, %61, %62, %63}, "
    "%64, %65, p, 1, 1, 0, 1;\n}\n"
    : "+f"(d[0]), "+f"(d[1]), "+f"(d[2]), "+f"(d[3]), "+f"(d[4]), "+f"(d[5]), "+f"(d[6]), "+f"(d[7]),
      "+f"(d[8]), "+f"(d[9]), "+f"(d[10]), "+f"(d[11]), "+f"(d[12]), "+f"(d[13]), "+f"(d[14]), "+f"(d[15]),
      "+f"(d[16]), "+f"(d[17]), "+f"(d[18]), "+f"(d[19]), "+f"(d[20]), "+f"(d[21]), "+f"(d[22]), "+f"(d[23]),
      "+f"(d[24]), "+f"(d[25]), "+f"(d[26]), "+f"(d[27]), "+f"(d[28]), "+f"(d[29]), "+f"(d[30]), "+f"(d[31]),
      "+f"(d[32]), "+f"(d[33]), "+f"(d[34]), "+f"(d[35]), "+f"(d[36]), "+f"(d[37]), "+f"(d[38]), "+f"(d[39]),
      "+f"(d[40]), "+f"(d[41]), "+f"(d[42]), "+f"(d[43]), "+f"(d[44]), "+f"(d[45]), "+f"(d[46]), "+f"(d[47]),
      "+f"(d[48]), "+f"(d[49]), "+f"(d[50]), "+f"(d[51]), "+f"(d[52]), "+f"(d[53]), "+f"(d[54]), "+f"(d[55]),
      "+f"(d[56]), "+f"(d[57]), "+f"(d[58]), "+f"(d[59]), "+f"(d[60]), "+f"(d[61]), "+f"(d[62]), "+f"(d[63])
    : "l"(da), "l"(db), "r"(scale_d));
}

__device__ __forceinline__ void wgmma_m64n40k16_rs_tb(float (&d)[20], uint32_t a0, uint32_t a1, uint32_t a2, uint32_t a3, uint64_t db, int scale_d) {
  asm volatile("{\n.reg .pred p;\nsetp.ne.b32 p, %25, 0;\n"
    "wgmma.mma_async.sync.aligned.m64n40k16.f32.bf16.bf16 "
    "{%0, %1, %2, %3, %4, %5, %6, %7, %8, %9, %10, %11, %12, %13, %14, %15, "
    "%16, %17, %18, %19}, "
    "{%20, %21, %22, %23}, %24, p, 1, 1, 1;\n}\n"
    : "+f"(d[0]), "+f"(d[1]), "+f"(d[2]), "+f"(d[3]), "+f"(d[4]), "+f"(d[5]), "+f"(d[6]), "+f"(d[7]),
      "+f"(d[8]), "+f"(d[9]), "+f"(d[10]), "+f"(d[11]), "+f"(d[12]), "+f"(d[13]), "+f"(d[14]), "+f"(d[15]),
      "+f"(d[16]), "+f"(d[17]), "+f"(d[18]), "+f"(d[19])
    : "r"(a0), "r"(a1), "r"(a2), "r"(a3), "l"(db), "r"(scale_d));
}

__device__ __forceinline__ void wg_n64_rs_nb_f16_f32(float (&d)[32], uint32_t a0, uint32_t a1, uint32_t a2, uint32_t a3, uint64_t db, int scale_d) {
  asm volatile("{\n.reg .pred p;\nsetp.ne.b32 p, %37, 0;\n"
    "wgmma.mma_async.sync.aligned.m64n64k16.f32.f16.f16 "
    "{%0, %1, %2, %3, %4, %5, %6, %7, %8, %9, %10, %11, %12, %13, %14, %15, "
    "%16, %17, %18, %19, %20, %21, %22, %23, %24, %25, %26, %27, %28, %29, %30, %31}, "
    "{%32, %33, %34, %35}, %36, p, 1, 1, 0;\n}\n"
    : "+f"(d[0]), "+f"(d[1]), "+f"(d[2]), "+f"(d[3]), "+f"(d[4]), "+f"(d[5]), "+f"(d[6]), "+f"(d[7]),
      "+f"(d[8]), "+f"(d[9]), "+f"(d[10]), "+f"(d[11]), "+f"(d[12]), "+f"(d[13]), "+f"(d[14]), "+f"(d[15]),
      "+f"(d[16]), "+f"(d[17]), "+f"(d[18]), "+f"(d[19]), "+f"(d[20]), "+f"(d[21]), "+f"(d[22]), "+f"(d[23]),
      "+f"(d[24]), "+f"(d[25]), "+f"(d[26]), "+f"(d[27]), "+f"(d[28]), "+f"(d[29]), "+f"(d[30]), "+f"(d[31])
    : "r"(a0), "r"(a1), "r"(a2), "r"(a3), "l"(db), "r"(scale_d));
}

__device__ __forceinline__ void wg_n64_rs_nb_f16_f16(uint32_t (&d)[16], uint32_t a0, uint32_t a1, uint32_t a2, uint32_t a3, uint64_t db, int scale_d) {
  asm volatile("{\n.reg .pred p;\nsetp.ne.b32 p, %21, 0;\n"
    "wgmma.mma_async.sync.aligned.m64n64k16.f16.f16.f16 "
    "{%0, %1, %2, %3, %4, %5, %6, %7, %8, %9, %10, %11, %12, %13, %14, %15}, "
    "{%16, %17, %18, %19}, %20, p, 1, 1, 0;\n}\n"
    : "+r"(d[0]), "+r"(d[1]), "+r"(d[2]), "+r"(d[3]), "+r"(d[4]), "+r"(d[5]), "+r"(d[6]), "+r"(d[7]),
      "+r"(d[8]), "+r"(d[9]), "+r"(d[10]), "+r"(d[11]), "+r"(d[12]), "+r"(d[13]), "+r"(d[14]), "+r"(d[15])
    : "r"(a0), "r"(a1), "r"(a2), "r"(a3), "l"(db), "r"(scale_d));
}

__device__ __forceinline__ void wg_n64_rs_nb_f16_f32_z(float (&d)[32], uint32_t a0, uint32_t a1, uint32_t a2, uint32_t a3, uint64_t db, int scale_d) {
  asm volatile("{\n.reg .pred p;\nsetp.ne.b32 p, %37, 0;\n"
    "wgmma.mma_async.sync.aligned.m64n64k16.f32.f16.f16 "
    "{%0, %1, %2, %3, %4, %5, %6, %7, %8, %9, %10, %11, %12, %13, %14, %15, "
    "%16, %17, %18, %19, %20, %21, %22, %23, %24, %25, %26, %27, %28, %29, %30, %31}, "
    "{%32, %33, %34, %35}, %36, p, 1, 1, 0;\n}\n"
    : "=f"(d[0]), "=f"(d[1]), "=f"(d[2]), "=f"(d[3]), "=f"(d[4]), "=f"(d[5]), "=f"(d[6]), "=f"(d[7]),
      "=f"(d[8]), "=f"(d[9]), "=f"(d[10]), "=f"(d[11]), "=f"(d[12]), "=f"(d[13]), "=f"(d[14]), "=f"(d[15]),
      "=f"(d[16]), "=f"(d[17]), "=f"(d[18]), "=f"(d[19]), "=f"(d[20]), "=f"(d[21]), "=f"(d[22]), "=f"(d[23]),
      "=f"(d[24]), "=f"(d[25]), "=f"(d[26]), "=f"(d[27]), "=f"(d[28]), "=f"(d[29]), "=f"(d[30]), "=f"(d[31])
    : "r"(a0), "r"(a1), "r"(a2), "r"(a3), "l"(db), "r"(scale_d));
}

__device__ __forceinline__ void wg_n64_rs_nb_f16_f16_z(uint32_t (&d)[16], uint32_t a0, uint32_t a1, uint32_t a2, uint32_t a3, uint64_t db, int scale_d) {
  asm volatile("{\n.reg .pred p;\nsetp.ne.b32 p, %21, 0;\n"
    "wgmma.mma_async.sync.aligned.m64n64k16.f16.f16.f16 "
    "{%0, %1, %2, %3, %4, %5, %6, %7, %8, %9, %10, %11, %12, %13, %14, %15}, "
    "{%16, %17, %18, %19}, %20, p, 1, 1, 0;\n}\n"
    : "=r"(d[0]), "=r"(d[1]), "=r"(d[2]), "=r"(d[3]), "=r"(d[4]), "=r"(d[5]), "=r"(d[6]), "=r"(d[7]),
      "=r"(d[8]), "=r"(d[9]), "=r"(d[10]), "=r"(d[11]), "=r"(d[12]), "=r"(d[13]), "=r"(d[14]), "=r"(d[15])
    : "r"(a0), "r"(a1), "r"(a2), "r"(a3), "l"(db), "r"(scale_d));
}

#define DEVINL __device__ __forceinline__
DEVINL void wg_fence() { asm volatile("wgmma.fence.sync.aligned;" ::: "memory"); }
DEVINL void wg_commit() { asm volatile("wgmma.commit_group.sync.aligned;" ::: "memory"); }
template <int N> DEVINL void wg_wait() { asm volatile("wgmma.wait_group.sync.aligned %0;" ::"n"(N) : "memory"); }
__host__ DEVINL uint64_t mkdesc(uint32_t addr, uint32_t lbo, uint32_t sbo, int sw) {
  return (uint64_t)((addr & 0x3FFFF) >> 4) | ((uint64_t)(lbo >> 4) << 16) | ((uint64_t)(sbo >> 4) << 32) | ((uint64_t)sw << 62);
}
DEVINL void mbar_init(uint32_t bar, uint32_t cnt) { asm volatile("mbarrier.init.shared::cta.b64 [%0], %1;" ::"r"(bar), "r"(cnt) : "memory"); }
DEVINL void mbar_arrive(uint32_t bar) { asm volatile("mbarrier.arrive.shared::cta.b64 _, [%0];" ::"r"(bar) : "memory"); }
DEVINL bool mbar_try(uint32_t bar, uint32_t parity) {
  uint32_t ok;
  asm volatile("{\n.reg .pred p;\nmbarrier.try_wait.parity.shared::cta.b64 p, [%1], %2;\nselp.u32 %0, 1, 0, p;\n}" : "=r"(ok) : "r"(bar), "r"(parity) : "memory");
  return ok;
}
DEVINL bool mbar_test(uint32_t bar, uint32_t parity) {
  uint32_t ok;
  asm volatile("{\n.reg .pred p;\nmbarrier.test_wait.parity.shared::cta.b64 p, [%1], %2;\nselp.u32 %0, 1, 0, p;\n}" : "=r"(ok) : "r"(bar), "r"(parity) : "memory");
  return ok;
}
DEVINL void mbar_wait(uint32_t bar, uint32_t parity) {
#pragma unroll 1
  for (uint32_t n = 0; n < 100000u; n++) if (mbar_try(bar, parity)) break;
}
#define EL(txt) "{\n.reg .pred pe;\nelect.sync _|pe, 0xffffffff;\n@pe " txt "\n}"
DEVINL void e_expect_tx(uint32_t bar, uint32_t bytes) { asm volatile(EL("mbarrier.arrive.expect_tx.shared::cta.b64 _, [%0], %1;") ::"r"(bar), "r"(bytes) : "memory"); }
DEVINL void e_arrive(uint32_t bar) { asm volatile(EL("mbarrier.arrive.shared::cta.b64 _, [%0];") ::"r"(bar) : "memory"); }
DEVINL void e_arrive_if(uint32_t bar, int c) {
  asm volatile("{\n.reg .pred pe;\nelect.sync _|pe, 0xffffffff;\nsetp.ne.and.b32 pe, %1, 0, pe;\n@pe mbarrier.arrive.shared::cta.b64 _, [%0];\n}" ::"r"(bar), "r"(c) : "memory");
}
DEVINL void e_red(uint32_t* p) { asm volatile(EL("red.release.gpu.global.add.u32 [%0], 1;") ::"l"(p) : "memory"); }
DEVINL void e_red_relaxed(uint32_t* p) { asm volatile(EL("red.relaxed.gpu.global.add.u32 [%0], 1;") ::"l"(p) : "memory"); }
DEVINL void tma_ld(uint32_t dst, const CUtensorMap* m, int c0, int c1, uint32_t bar) {
  asm volatile(EL("cp.async.bulk.tensor.2d.shared::cluster.global.mbarrier::complete_tx::bytes [%0], [%1, {%3, %4}], [%2];")
               ::"r"(dst), "l"(m), "r"(bar), "r"(c0), "r"(c1) : "memory");
}
DEVINL void tma_ld3(uint32_t dst, const CUtensorMap* m, int c0, int c1, int c2, uint32_t bar) {
  asm volatile(EL("cp.async.bulk.tensor.3d.shared::cluster.global.mbarrier::complete_tx::bytes [%0], [%1, {%3, %4, %5}], [%2];")
               ::"r"(dst), "l"(m), "r"(bar), "r"(c0), "r"(c1), "r"(c2) : "memory");
}
DEVINL void tma_ld5(uint32_t dst, const CUtensorMap* m, int c2, int c3, int c4, uint32_t bar) {
  asm volatile(EL("cp.async.bulk.tensor.5d.shared::cluster.global.mbarrier::complete_tx::bytes [%0], [%1, {0, 0, %3, %4, %5}], [%2];")
               ::"r"(dst), "l"(m), "r"(bar), "r"(c2), "r"(c3), "r"(c4) : "memory");
}
DEVINL void tma_ld_mc(uint32_t dst, const CUtensorMap* m, int c0, int c1, uint32_t bar) {
  asm volatile(EL("cp.async.bulk.tensor.2d.shared::cluster.global.mbarrier::complete_tx::bytes.multicast::cluster [%0], [%1, {%3, %4}], [%2], %5;")
               ::"r"(dst), "l"(m), "r"(bar), "r"(c0), "r"(c1), "h"((uint16_t)3) : "memory");
}
DEVINL void e_arrive_both(uint32_t bar) {
  asm volatile("{\n.reg .pred pe;\n.reg .b32 r0, r1;\nelect.sync _|pe, 0xffffffff;\nmapa.shared::cluster.u32 r0, %0, 0;\nmapa.shared::cluster.u32 r1, %0, 1;\n"
               "@pe mbarrier.arrive.shared::cluster.b64 _, [r0];\n@pe mbarrier.arrive.shared::cluster.b64 _, [r1];\n}" ::"r"(bar) : "memory");
}
DEVINL void tma_st(const CUtensorMap* m, int c0, int c1, uint32_t src) {
  asm volatile(EL("cp.async.bulk.tensor.2d.global.shared::cta.bulk_group [%0, {%2, %3}], [%1];") ::"l"(m), "r"(src), "r"(c0), "r"(c1) : "memory");
}
DEVINL void bulk_commit() { asm volatile("cp.async.bulk.commit_group;" ::: "memory"); }
template <int N> DEVINL void bulk_wait_n() { asm volatile("cp.async.bulk.wait_group %0;\nbar.warp.sync 0xffffffff;" ::"n"(N) : "memory"); }
DEVINL void l2_prefetch(const void* g, uint32_t bytes) { asm volatile(EL("cp.async.bulk.prefetch.L2.global [%0], %1;") ::"l"(g), "r"(bytes) : "memory"); }
DEVINL void fence_async_smem() { asm volatile("fence.proxy.async.shared::cta;" ::: "memory"); }
DEVINL void fence_async_gl() { asm volatile("fence.proxy.async.global;" ::: "memory"); }
DEVINL void cluster_wait() { asm volatile("barrier.cluster.wait.aligned;" ::: "memory"); }
DEVINL void bar_sync(int id, int n) { asm volatile("bar.sync %0, %1;" ::"r"(id), "r"(n) : "memory"); }
DEVINL void bar_arrive(int id, int n) { asm volatile("bar.arrive %0, %1;" ::"r"(id), "r"(n) : "memory"); }
DEVINL uint32_t ld_acquire(const uint32_t* p) { uint32_t v; asm volatile("ld.acquire.gpu.global.u32 %0, [%1];" : "=r"(v) : "l"(p) : "memory"); return v; }
DEVINL void await_flag(int j, uint32_t& rdy, const uint32_t* p, uint32_t target) {
  if ((rdy >> j) & 1) return;
#pragma unroll 1
  for (uint32_t n = 0; n < 200000u && !((rdy >> j) & 1); n++) rdy = __ballot_sync(~0u, (int)(ld_acquire(p) - target) >= 0);
  asm volatile("fence.proxy.async.global;" ::: "memory");
}
DEVINL void poll_ge(const uint32_t* p, uint32_t target) {
#pragma unroll 1
  for (uint32_t n = 0; n < 200000u; n++) if (__all_sync(~0u, (int)(ld_acquire(p) - target) >= 0)) break;
}
DEVINL int lane_id() { int v; asm volatile("mov.u32 %0, %%laneid;" : "=r"(v)); return v; }
__host__ DEVINL int remap(int v) {
  const int c = v >> 1, u = c - 36, r = (u * 37) >> 8;
  const int L = c < 4 ? 32 + 8 * c : c < 36 ? c - 4 : 33 + u + r;
  return 2 * L + (v & 1);
}
DEVINL int block_id() { int v; asm volatile("mov.u32 %0, %%ctaid.x;" : "=r"(v)); return v; }
#define cta_id() prm.map[block_id()]
#define IDS() const int lane = lane_id(), b = cta_id(), bm = b >> 4, bn = b & 15, rank = b & 1, pm = 2 * bm + (bn >> 3), pn = bn & 7, po = pm & 1; \
  (void)lane; (void)bm; (void)bn; (void)rank; (void)pm; (void)pn; (void)po
DEVINL void st_tagged(uint4* p, uint32_t a, uint32_t b, uint32_t c, uint32_t tag) {
  asm volatile("{\n.reg .b64 u, v;\n.reg .b128 t;\nmov.b64 u, {%1, %2};\nmov.b64 v, {%3, %4};\nmov.b128 t, {u, v};\nst.relaxed.gpu.global.b128 [%0], t;\n}"
               ::"l"(p), "r"(a), "r"(b), "r"(c), "r"(tag) : "memory");
}
DEVINL uint32_t ld_tagged(const uint4* p, uint32_t* r) {
  uint32_t tag;
  asm volatile("{\n.reg .b64 u, v;\n.reg .b128 t;\nld.relaxed.gpu.global.b128 t, [%4];\nmov.b128 {u, v}, t;\nmov.b64 {%0, %1}, u;\nmov.b64 {%2, %3}, v;\n}"
               : "=r"(r[0]), "=r"(r[1]), "=r"(r[2]), "=r"(tag) : "l"(p) : "memory");
  return tag;
}
DEVINL float ex2(float x) { float y; asm("ex2.approx.ftz.f32 %0, %1;" : "=f"(y) : "f"(x)); return y; }
DEVINL float rcp(float x) { float y; asm("rcp.approx.ftz.f32 %0, %1;" : "=f"(y) : "f"(x)); return y; }
DEVINL uint32_t pack2(float lo, float hi) { uint32_t r; asm("cvt.rn.bf16x2.f32 %0, %1, %2;" : "=r"(r) : "f"(hi), "f"(lo)); return r; }
DEVINL uint32_t pack2h(float lo, float hi) { uint32_t r; asm("cvt.rn.f16x2.f32 %0, %1, %2;" : "=r"(r) : "f"(hi), "f"(lo)); return r; }
DEVINL float bf_lo(uint32_t w) { return __uint_as_float(w << 16); }
DEVINL float bf_hi(uint32_t w) { return __uint_as_float(w & 0xFFFF0000u); }
DEVINL float bf_round(float x) { return bf_lo(pack2(x, 0.f)); }
DEVINL uint32_t add_bf16x2(uint32_t a, uint32_t b) { uint32_t r; asm("add.rn.bf16x2 %0, %1, %2;" : "=r"(r) : "r"(a), "r"(b)); return r; }
DEVINL void stsm4(uint32_t addr, uint32_t a, uint32_t b, uint32_t c, uint32_t d) {
  asm volatile("stmatrix.sync.aligned.m8n8.x4.shared.b16 [%0], {%1, %2, %3, %4};" ::"r"(addr), "r"(a), "r"(b), "r"(c), "r"(d) : "memory");
}
DEVINL void ldsm4(uint32_t addr, uint32_t (&r)[4]) {
  asm volatile("ldmatrix.sync.aligned.m8n8.x4.shared.b16 {%0, %1, %2, %3}, [%4];" : "=r"(r[0]), "=r"(r[1]), "=r"(r[2]), "=r"(r[3]) : "r"(addr) : "memory");
}
DEVINL void ldsm4t(uint32_t addr, uint32_t (&r)[4]) {
  asm volatile("ldmatrix.sync.aligned.m8n8.x4.trans.shared.b16 {%0, %1, %2, %3}, [%4];" : "=r"(r[0]), "=r"(r[1]), "=r"(r[2]), "=r"(r[3]) : "r"(addr) : "memory");
}
DEVINL void sts128(uint32_t addr, uint32_t a, uint32_t b, uint32_t c, uint32_t d) {
  asm volatile("st.shared.v4.b32 [%0], {%1, %2, %3, %4};" ::"r"(addr), "r"(a), "r"(b), "r"(c), "r"(d) : "memory");
}
DEVINL float2 lds64f(uint32_t addr) { float2 v; asm volatile("ld.shared.v2.f32 {%0, %1}, [%2];" : "=f"(v.x), "=f"(v.y) : "r"(addr) : "memory"); return v; }
DEVINL void mma16816(float (&d)[4], uint32_t a0, uint32_t a1, uint32_t a2, uint32_t a3, uint32_t b0, uint32_t b1) {
  asm("mma.sync.aligned.m16n8k16.row.col.f32.bf16.bf16.f32 {%0, %1, %2, %3}, {%4, %5, %6, %7}, {%8, %9}, {%0, %1, %2, %3};"
               : "+f"(d[0]), "+f"(d[1]), "+f"(d[2]), "+f"(d[3]) : "r"(a0), "r"(a1), "r"(a2), "r"(a3), "r"(b0), "r"(b1));
}
template <int N> DEVINL void fence_regs(float (&d)[N]) {
#pragma unroll
  for (int i = 0; i < N; i++) asm volatile("" : "+f"(d[i])::"memory");
}
template <int N> DEVINL void fence_regs(uint32_t (&d)[N]) {
#pragma unroll
  for (int i = 0; i < N; i++) asm volatile("" : "+r"(d[i])::"memory");
}
DEVINL void lds128(uint32_t addr, uint32_t* r) {
  asm volatile("ld.shared.v4.b32 {%0, %1, %2, %3}, [%4];" : "=r"(r[0]), "=r"(r[1]), "=r"(r[2]), "=r"(r[3]) : "r"(addr) : "memory");
}
DEVINL void sched_fence() { asm volatile("griddepcontrol.launch_dependents;" ::: "memory"); }

struct Scratch {
  bf16 k[32 * 2048 * 32];
  bf16 xs[2048 * 1024];
  bf16 os[2048 * 1024];
  bf16 v[32 * 2048 * 32];
  float kn[2 * 128 * 16];
  uint32_t cnt[256 * 32];
  float2 stats[8 * 2048];
  uint4 halo[2 * 128 * 12 * 32];
  float csp[2 * 16 * 8 * 192];
  uint4 qsave[128 * 256 * 8];
  uint32_t esc[4 * 65536 * 20];
};
__device__ __align__(1024) Scratch g_s;
#define g_k g_s.k
#define g_xs g_s.xs
#define g_os g_s.os
#define g_v g_s.v
#define g_kn g_s.kn
#define g_cnt g_s.cnt
#define g_stats g_s.stats
#define g_halo g_s.halo
#define g_csp g_s.csp
#define g_qsave g_s.qsave
#define g_esc g_s.esc
#define g_epoch g_s.cnt[255 * 32]

DEVINL uint32_t* cnt_x(int l, int bm) { return g_cnt + (l * 8 + bm) * 32; }
DEVINL uint32_t* cnt_o(int l, int pm, int h) { return g_cnt + (32 + (l * 16 + pm) * 2 + h) * 32; }
DEVINL uint32_t* cnt_kv(int lb, int bn) { return g_cnt + (160 + lb * 16 + bn) * 32; }
DEVINL uint32_t* cnt_ad(int bn) { return g_cnt + (192 + bn) * 32; }
DEVINL uint32_t* cnt_cs(int t, int bn) { return g_cnt + (208 + t * 16 + bn) * 32; }

DEVINL int qord(int i, int l, int pn) { return l == 0 ? i : i < 4 ? ((2 * pn) ^ (i & 2)) + (i & 1) : i - 4 < 2 * (pn & 6) ? i - 4 : i; }
struct Params {
  CUtensorMap m[15];
  const bf16* x0;
  const bf16* wq[2];
  uint32_t zero;
  int map[128];
  uint64_t wd, xd;
  struct __align__(16) { uint64_t kd, vd; } kv[4];
};
enum { M_X0A = 0, M_XSA, M_WQA, M_WQB, M_WOA, M_WOB, M_OS, M_K, M_V, M_X0R, M_XSR, M_XSO, M_OUT, M_XST, M_X0H, M_COUNT };

constexpr uint32_t QSTG = 57344;
constexpr uint32_t T0 = 65536, TSTG = 32768;
constexpr uint32_t ONES = 230400;
constexpr uint32_t PSTG = 32768, RES = 196608;
constexpr uint32_t KSC = 98304, VSC = 133120, HRS = 167936;
constexpr uint32_t ROWST = 229376, COLS = 231424, BARS = 232192, SMEM_BYTES = 232448;
constexpr uint32_t B_QF = BARS, B_QE = BARS + 32, B_TF = BARS + 64, B_TE = BARS + 96, B_PF = BARS + 128, B_PE = BARS + 176,
                   B_RF = BARS + 224, W_X = BARS + 232, B_QL = BARS + 240, B_PA = BARS + 248;
enum { NB_ST = 1, NB_KV = 2  , NB_DONE = 3, NB_SC = 4, NB_SIG = 5  , NB_KN = 9  , NB_X = 11, NB_HALO = 12  , NB_X0 = 15 };

DEVINL uint32_t pslot_b(uint32_t s) { return ((0x320415u >> (4 * s)) & 7) * 16384u; }
DEVINL uint32_t pslot_a(uint32_t s, int l) { return 98304u + ((((l & 1) ? 0x541230u : 0x041235u) >> (4 * s)) & 7) * 16384u; }

constexpr float QSCALE = 0.17677669529663687f * 1.4426950408889634f;
constexpr uint32_t QPARK = 32768;

DEVINL uint32_t exp2_h2(uint32_t s, uint32_t c882) {
  uint32_t r, t, w, m, d;
  asm volatile("{.reg .b64 t; add.rn.f16x2 %0, %1, %2; cvt.u64.u32 t, %0; cvt.u32.u64 %0, t;}" : "=r"(r) : "r"(s), "r"(0x65F565F5u));
  asm volatile("fma.rn.f16x2 %0, %1, %2, %3;" : "=r"(t) : "r"(r), "r"(0xB8A0B8A0u), "r"(c882));
  asm volatile("fma.rn.f16x2 %0, %1, %2, %3;" : "=r"(w) : "r"(s), "r"(0x38A038A0u), "r"(t));
  asm volatile("fma.rn.f16x2 %0, %1, %1, %2;" : "=r"(m) : "r"(w), "r"(0x48244833u));
  asm volatile("{.reg .b32 t; shf.l.clamp.b32 t, %2, %1, 7; add.u32 %0, t, %2;}" : "=r"(d) : "r"(r), "r"(m));
  return d;
}
DEVINL float exp2_fix(float s) { float z; asm volatile("add.rn.f32 %0, %1, 0f43BF34BC;" : "=f"(z) : "f"(s)); return z; }
DEVINL uint32_t exp2_base(float z0, float z1) { uint32_t B; asm volatile("prmt.b32 %0, %1, %2, 0x6521;" : "=r"(B) : "r"(__float_as_uint(z0)), "r"(__float_as_uint(z1))); return B; }
template <uint32_t MASK> DEVINL uint32_t and_or(uint32_t a, uint32_t c) { uint32_t r; asm volatile("lop3.b32 %0, %1, %3, %2, 0xEA;" : "=r"(r) : "r"(a), "r"(c), "n"(MASK)); return r; }
DEVINL uint32_t fma_bf2(uint32_t a, uint32_t b, uint32_t c) { uint32_t r; asm volatile("fma.rn.bf16x2 %0, %1, %2, %3;" : "=r"(r) : "r"(a), "r"(b), "r"(c)); return r; }
DEVINL float ex2v(float x) { float y; asm volatile("ex2.approx.ftz.f32 %0, %1;" : "=f"(y) : "f"(x)); return y; }
DEVINL uint32_t pack2v(float lo, float hi) { uint32_t r; asm volatile("cvt.rn.bf16x2.f32 %0, %1, %2;" : "=r"(r) : "f"(hi), "f"(lo)); return r; }
DEVINL void unesc(uint32_t (&u)[4], const uint32_t* esc, uint32_t tag) {
  const bool saved = __ldcg(esc + 16) == tag;
#pragma unroll
  for (int j = 0; j < 4; j++) {
    float lo, hi;
    asm("{.reg .f16 a, b; mov.b32 {a, b}, %2; cvt.f32.f16 %0, a; cvt.f32.f16 %1, b;}" : "=f"(lo), "=f"(hi) : "r"(u[j]));
    u[j] = saved ? __ldcg(esc + 4 * j) : pack2(lo, hi);
  }
}

DEVINL void attn_slow(const uint32_t (&q)[8], int head, const uint32_t* kesc, uint32_t tag, float (&res)[20], int lane) {
  const int g = lane >> 2, qd = lane & 3;
  const bf16* kb = g_k + (size_t)head * 2048 * 32;
  const bf16* vb = g_v + (size_t)head * 2048 * 32;
  float o[4][4], m0 = -INFINITY, m1 = -INFINITY, l0 = 0.f, l1 = 0.f;
#pragma unroll
  for (int j = 0; j < 4; j++) { o[j][0] = o[j][1] = o[j][2] = o[j][3] = 0.f; }
#pragma unroll 1
  for (int k0 = 0; k0 < 2048; k0 += 16) {
    float s[2][4];
#pragma unroll
    for (int nt = 0; nt < 2; nt++) {
      s[nt][0] = s[nt][1] = s[nt][2] = s[nt][3] = 0.f;
      const uint32_t* kp = (const uint32_t*)(kb + (size_t)(k0 + nt * 8 + g) * 32) + qd;
      uint32_t k[4] = {__ldcg(kp), __ldcg(kp + 4), __ldcg(kp + 8), __ldcg(kp + 12)};
      unesc(k, kesc + (k0 + nt * 8 + g) * 20 + qd, tag);
      __syncwarp();
      mma16816(s[nt], q[0], q[1], q[2], q[3], k[0], k[1]);
      mma16816(s[nt], q[4], q[5], q[6], q[7], k[2], k[3]);
    }
    float a0 = fmaxf(fmaxf(s[0][0], s[0][1]), fmaxf(s[1][0], s[1][1]));
    float a1 = fmaxf(fmaxf(s[0][2], s[0][3]), fmaxf(s[1][2], s[1][3]));
    a0 = fmaxf(a0, __shfl_xor_sync(~0u, a0, 1)); a0 = fmaxf(a0, __shfl_xor_sync(~0u, a0, 2));
    a1 = fmaxf(a1, __shfl_xor_sync(~0u, a1, 1)); a1 = fmaxf(a1, __shfl_xor_sync(~0u, a1, 2));
    const float n0 = fmaxf(m0, a0), n1 = fmaxf(m1, a1);
    const float c0 = (m0 == n0) ? 1.f : ex2(m0 - n0), c1 = (m1 == n1) ? 1.f : ex2(m1 - n1);
    m0 = n0; m1 = n1;
    const uint32_t p0 = pack2(ex2(s[0][0] - n0), ex2(s[0][1] - n0)), p1 = pack2(ex2(s[0][2] - n1), ex2(s[0][3] - n1));
    const uint32_t p2 = pack2(ex2(s[1][0] - n0), ex2(s[1][1] - n0)), p3 = pack2(ex2(s[1][2] - n1), ex2(s[1][3] - n1));
    l0 = l0 * c0 + bf_lo(p0) + bf_hi(p0) + bf_lo(p2) + bf_hi(p2);
    l1 = l1 * c1 + bf_lo(p1) + bf_hi(p1) + bf_lo(p3) + bf_hi(p3);
#pragma unroll
    for (int j = 0; j < 4; j++) {
      o[j][0] *= c0; o[j][1] *= c0; o[j][2] *= c1; o[j][3] *= c1;
      const unsigned short* vp = (const unsigned short*)(vb + (size_t)(k0 + 2 * qd) * 32 + j * 8 + g);
      const uint32_t b0 = (uint32_t)__ldcg(vp) | ((uint32_t)__ldcg(vp + 32) << 16);
      const uint32_t b1 = (uint32_t)__ldcg(vp + 256) | ((uint32_t)__ldcg(vp + 288) << 16);
      mma16816(o[j], p0, p1, p2, p3, b0, b1);
    }
  }
  l0 += __shfl_xor_sync(~0u, l0, 1); l0 += __shfl_xor_sync(~0u, l0, 2);
  l1 += __shfl_xor_sync(~0u, l1, 1); l1 += __shfl_xor_sync(~0u, l1, 2);
#pragma unroll
  for (int j = 0; j < 4; j++) { res[4 * j] = o[j][0]; res[4 * j + 1] = o[j][1]; res[4 * j + 2] = o[j][2]; res[4 * j + 3] = o[j][3]; }
  res[16] = l0; res[18] = l1;
}

__device__ __noinline__ void attn_redo(int redo, int l, int b, int wg, int w, uint32_t tag) {
  const int lane = lane_id();
#pragma unroll 1
  for (int t = 0; t < 4; t++) {
    const int h = t >> 1, head = 2 * (b & 15) + h, row = (b >> 4) * 256 + wg * 128 + (t & 1) * 64 + w * 16 + (lane >> 2);
    if ((redo >> t) & 1) {
      const uint32_t* esc = g_esc + (size_t)((l & 2) * 65536 + head * 2048) * 20;
      const uint32_t* qs = (const uint32_t*)(g_qsave + (block_id() * 256 + wg * 128 + w * 32 + lane) * 8 + 2 * t);
      uint32_t q[8]; float o[20];
#pragma unroll
      for (int i = 0; i < 2; i++) {
        uint32_t u[4] = {__ldcg(qs + i), __ldcg(qs + i + 2), __ldcg(qs + i + 4), __ldcg(qs + i + 6)};
        unesc(u, esc + (row + i * 8) * 20 + (lane & 3), tag);
        q[i] = u[0]; q[i + 2] = u[1]; q[i + 4] = u[2]; q[i + 6] = u[3];
      }
      __syncwarp();
      attn_slow(q, head, esc + 65536 * 20, tag, o, lane);
      const float i0 = rcp(o[16]), i1 = rcp(o[18]);
      bf16* op = g_os + (size_t)row * 1024 + h * 512 + (b & 15) * 32 + (lane & 3) * 8;
      *(uint4*)op = make_uint4(pack2(o[0] * i0, o[1] * i0), pack2(o[4] * i0, o[5] * i0), pack2(o[8] * i0, o[9] * i0), pack2(o[12] * i0, o[13] * i0));
      *(uint4*)(op + 8 * 1024) = make_uint4(pack2(o[2] * i1, o[3] * i1), pack2(o[6] * i1, o[7] * i1), pack2(o[10] * i1, o[11] * i1), pack2(o[14] * i1, o[15] * i1));
    }
    if ((t & 1) && ((redo >> 2 * h) & 3)) bar_arrive(NB_SIG + 2 * h + wg, 160);
  }
}

__global__ void __cluster_dims__(2, 1, 1) __launch_bounds__(384, 1) fused_kernel(const __grid_constant__ Params prm) {
  extern __shared__ __align__(1024) char smem[];
  const uint32_t sb = (uint32_t)__cvta_generic_to_shared(smem);
  const int tid = threadIdx.x, lane = tid & 31;
  const int wg = __shfl_sync(0xffffffffu, tid >> 7, 0);
  const int w = __shfl_sync(0xffffffffu, (tid >> 5) & 3, 0);
  const int bm = remap(blockIdx.x) >> 4, bn = remap(blockIdx.x) & 15;

  auto first_tile = [&](int kt) {
    e_expect_tx(sb + B_QF + 8 * kt, QSTG);
    tma_ld(sb + kt * QSTG, &prm.m[M_X0A], kt * 64, bm * 256, sb + B_QF + 8 * kt);
    tma_ld3(sb + kt * QSTG + 32768, &prm.m[M_WQA], bn * 64, kt * 64, 0, sb + B_QF + 8 * kt);
  };
  auto init4 = [&](uint32_t bar, uint32_t c0, uint32_t c1, uint32_t c2, uint32_t c3) {
    asm volatile("{\n.reg .pred pe;\nelect.sync _|pe, 0xffffffff;\n@pe mbarrier.init.shared::cta.b64 [%0], %1;\n@pe mbarrier.init.shared::cta.b64 [%0+8], %2;\n"
                 "@pe mbarrier.init.shared::cta.b64 [%0+16], %3;\n@pe mbarrier.init.shared::cta.b64 [%0+24], %4;\n@pe fence.mbarrier_init.release.cluster;\n}"
                 ::"r"(bar), "r"(c0), "r"(c1), "r"(c2), "r"(c3) : "memory");
  };
  if (wg < 2) {
    const uint32_t k = wg * 4 + w, lo = (0x1411814u >> (4 * k)) & 15, hi = (0x1441814u >> (4 * k)) & 15;
    if (tid < 32) asm volatile("prefetch.global.L2 [%0];" ::"l"(prm.x0 + (size_t)(bm * 256 + bn * 16 + (tid & 15)) * 1024 + (tid >> 4) * 64));
    else if (tid < 80) asm volatile("prefetch.global.L2 [%0];" ::"l"(prm.wq[0] + (bm * 16 + (tid & 15)) * 3072 + ((tid >> 4) - 2) * 1024 + bn * 64));
    __syncwarp();
    if (k < 7) init4(sb + B_QE + 32 * k, lo, lo, hi, k == 6 ? 2 : hi);
    __syncwarp();
    if (k == 6 && lane == 0) *(volatile unsigned long long*)(smem + W_X) = 0ull;
  } else if (w == 0) {
    init4(sb + B_QF, 1, 1, 1, 1);
    __syncwarp();
    first_tile(0);
  }
  __syncthreads();
  asm volatile("barrier.cluster.arrive.relaxed.aligned;" ::: "memory");

  if (wg == 2) {
    asm volatile("setmaxnreg.dec.sync.aligned.u32 56;");
    const uint32_t ep1 = *(volatile uint32_t*)&g_epoch + 1;
    if (w == 0) {
      first_tile(1);
      mbar_wait(sb + B_QF, 0);
      first_tile(2); first_tile(3);
#pragma unroll 1
      for (int kt = 4; kt < 16; kt++) l2_prefetch(prm.wq[0] + kt * 196608 + blockIdx.x * 1536, 3072);
      cluster_wait();
#pragma unroll 1
      for (int l = 0; l < 4; l++) {
        IDS();
        const CUtensorMap* mw = &prm.m[M_WQA + (l & 1)];
        const CUtensorMap* mx = &prm.m[l == 0 ? M_X0A : M_XSA];
        const CUtensorMap* mh = &prm.m[l == 0 ? M_X0H : M_XSO];
        const CUtensorMap* mo = &prm.m[M_WOA + (l & 1)];
        auto q_b = [&](int i) {
          const int s = i & 3;
          mbar_wait(sb + B_QE + 8 * s, ((i >> 2) & 1) ^ 1);
          e_expect_tx(sb + B_QF + 8 * s, QSTG);
          tma_ld3(sb + s * QSTG + 32768, mw, bn * 64, qord(i, l, pn) * 64, 0, sb + B_QF + 8 * s);
        };
        uint32_t rdy = l ? 0u : ~0u;
        auto q_a = [&](int i) {
          const int kt = qord(i, l, pn);
          await_flag(kt, rdy, cnt_x(l, bm) + (lane & 15), ep1 * 2);
          if (i < 4) tma_ld(sb + i * QSTG, mx, kt * 64, bm * 256, sb + B_QF + 8 * i);
          else tma_ld_mc(sb + (i & 3) * QSTG + rank * 16384, mh, kt * 64, bm * 256 + rank * 128, sb + B_QF + 8 * (i & 3));
        };
        if (l > 0) {
#pragma unroll 1
          for (int i = 0; i < 2; i++) {
            await_flag(2 * pn + i, rdy, cnt_x(l, bm) + (lane & 15), ep1 * 2);
            e_expect_tx(sb + B_QF + 8 * i, 16384);
            tma_ld(sb + i * QSTG + (po ^ 1) * 16384, &prm.m[M_XSO], (2 * pn + i) * 64, (pm ^ 1) * 128, sb + B_QF + 8 * i);
            if (i == 0) {  q_a(2); }
          }
          mbar_wait(sb + B_QF + 8, 0);
        }
#pragma unroll 1
        for (int i = l ? 3 : 4; i < 16; i++) {
          if (l == 3 && i == 12) poll_ge(cnt_ad(bn), ep1 * 16);
          q_b(i); q_a(i);
        }
        if (l & 1) {
          bar_sync(NB_KV, 288);
          sts128(sb + ONES + lane * 32, 0x3f803f80u, 0x3f803f80u, 0x3f803f80u, 0x3f803f80u);
          sts128(sb + ONES + lane * 32 + 16, 0x3f803f80u, 0x3f803f80u, 0x3f803f80u, 0x3f803f80u);
          fence_async_smem();
          __syncwarp();
          e_arrive(sb + B_TF);
          const int krow = 2 * bn * 2048 + bm * 256;
          uint32_t* kvc = cnt_kv(l >> 1, bn);
          uint32_t seen = 0;
#pragma unroll 1
          for (int it = 1; it < 16; it++) {
            const int s = it & 3;
            if (it == 4) {
              bar_sync(NB_KV + 12, 288);
              mbar_wait(sb + B_TF + 24, 0);
#pragma unroll 1
              for (int i = 0; i < 4; i++) tma_st(&prm.m[M_K + (i >> 1)], 0, krow + 2048 + (i & 1) * 128, sb + i * 8192);
              bulk_commit();
            }
            if (it == 5) { bulk_wait_n<0>(); e_red(kvc + 16 + bm); }
            if (it == 12) { e_expect_tx(sb + B_RF, 32768); tma_ld3(sb + RES, &prm.m[M_XSR], 0, pm * 128, 2 * pn, sb + B_RF); }
            mbar_wait(sb + B_TE + 8 * s, ((it >> 2) & 1) ^ 1);
            if (it < 8) {
#pragma unroll 1
              for (uint32_t n = 0; n < 200000u && (~seen & (3u << (2 * it - 2) | (it == 4 ? 0xC000u : 0u))); n++)
                seen = __ballot_sync(~0u, (int)(ld_acquire(kvc + (lane < 7 || lane == 15 ? (bm + 1 + lane) & 7 : 8 + ((bm + 2 + lane) & 7))) - ep1) >= 0);
              fence_async_gl();
            } else if (it == 8) { poll_ge(kvc + 16 + (lane & 7), ep1); fence_async_gl(); }
            e_expect_tx(sb + B_TF + 8 * s, 32768);
#pragma unroll 1
            for (int i = 0; i < 2; i++) {
              const int u = 2 * it - 2 + i;
              const int row = 2 * bn * 2048 + (it > 7 ? 2048 + ((bm + it) & 7) * 256 + i * 128 : u < 7 ? ((bm + 1 + u) & 7) * 256 : ((bm + 2 + u) & 7) * 256 + 128);
              tma_ld(sb + T0 + s * TSTG + i * 8192, &prm.m[M_K], 0, row, sb + B_TF + 8 * s);
              tma_ld(sb + T0 + s * TSTG + 16384 + i * 8192, &prm.m[M_V], 0, row, sb + B_TF + 8 * s);
            }
          }
        }
        auto p_b = [&](int i, uint32_t s, uint32_t par) {
          mbar_wait(sb + B_PE + 8 * s, par ^ 1);
          e_expect_tx(sb + B_PF + 8 * s, PSTG);
          tma_ld5(sb + pslot_b(s), mo, i >> 3, 2 * (i & 7), 2 * pn, sb + B_PF + 8 * s);
        };
        auto p_a = [&](int i, uint32_t s) {
          await_flag(i, rdy, cnt_o(l, pm, (lane >> 3) & 1) + (lane & 7), ep1 * 2);
          tma_ld_mc(sb + pslot_a(s, l) + rank * 8192, &prm.m[M_OS], i * 64, pm * 128 + rank * 64, sb + B_PF + 8 * s);
        };
        auto p_a2 = [&](int i) {
          await_flag(i, rdy, cnt_o(l, pm, (lane >> 3) & 1) + (lane & 7), ep1 * 2);
          tma_ld(sb + pslot_a(i, l), &prm.m[M_OS], i * 64, pm * 128, sb + B_PF + 8 * i);
          tma_ld(sb + pslot_a(i, l) + 8192, &prm.m[M_OS], i * 64, pm * 128 + 64, sb + B_PF + 8 * i);
        };
        rdy = 0;
        if (l & 1) {
#pragma unroll 1
          for (int u = 0; u < 6; u++) { const int i = (0x205413 >> (4 * u)) & 7; if (u == 4) mbar_wait(sb + B_TE, 1); p_b(i, i, i < 4 ? 1 : 0); }
#pragma unroll 1
          for (int u = 0; u < 6; u++) {
            const int i = (0x542130 >> (4 * u)) & 7;
            if (!(u & 1)) mbar_wait(sb + B_TE + 8 + 4 * u, 1);
            if (u == 4) bar_sync(NB_ST, 64);
            p_a2(i);
          }
        } else {
#pragma unroll 1
          for (int u = 0; u < 6; u++) { const int i = (0x025413 >> (4 * u)) & 7; if (u == 0 || u == 3) mbar_wait(sb + B_QE + 8 * (u / 3), 1); p_b(i, i, 0); }
          mbar_wait(sb + B_QE + 24, 1);
          e_expect_tx(sb + B_RF, 32768);
          tma_ld3(sb + RES, &prm.m[l == 0 ? M_X0R : M_XSR], 0, pm * 128, 2 * pn, sb + B_RF);
          p_a2(0);
          bar_sync(NB_DONE, 64);
          e_arrive_both(sb + B_PA);
          p_a2(1);
          mbar_wait(sb + B_PA, (l >> 1) & 1);
#pragma unroll 1
          for (int i = 2; i < 6; i++) { if (i > 2) mbar_wait(sb + B_PF + 8 * (i - 3), 0); p_a(i, i); }
        }
        uint32_t s = 0, lap = 1;
#pragma unroll 1
        for (int i = 6; i < 16; i++) {
          p_b(i, s, ((s < 4 ? l : 0) + lap) & 1);
          p_a(i, s);
          if (++s == 6) { s = 0; lap++; }
        }
        const CUtensorMap* mn = &prm.m[M_WQA + ((l + 1) & 1)];
        if (l < 3) {
          mbar_wait(sb + B_PE + 8 * 4, 1); mbar_wait(sb + B_PE + 8 * 5, 1);
          tma_ld3(sb + 32768, mn, bn * 64, 2 * pn * 64, 0, sb + B_QL);
          mbar_wait(sb + B_PE + 8 * 0, l & 1);
          tma_ld3(sb + QSTG + 32768, mn, bn * 64, (2 * pn + 1) * 64, 0, sb + B_QL);
          mbar_wait(sb + B_PE + 8 * 1, l & 1);
          e_expect_tx(sb + B_QF + 16, QSTG);
          tma_ld3(sb + 2 * QSTG + 32768, mn, bn * 64, ((2 * pn) ^ 2) * 64, 0, sb + B_QF + 16);
        }
        if (l < 3) { bar_sync(NB_X, 320); e_expect_tx(sb + B_QL, 49152); }
      }
      if (blockIdx.x == 0 && lane_id() == 0) *(volatile uint32_t*)&g_epoch = ep1;
    } else {
      const int hw = w - 1;
      if (lane < 5) asm volatile("prefetch.tensormap [%0];" ::"l"(&prm.m[5 * hw + lane]) : "memory");
      __syncwarp();
      cluster_wait();
      mbar_wait(sb + B_QF, 0);
#pragma unroll 1
      for (int l = 0; l < 4; l++) {
        IDS();
        if (l > 0) { mbar_wait(sb + B_QL, (l + 1) & 1); mbar_wait(sb + B_QF + 8 * 3, 0); }
        if (l == 0) {
#pragma unroll 1
          for (int r = 2 * hw; r < 16; r += 6) {
            const uint4* p = (const uint4*)(prm.x0 + (size_t)(b * 16 + r) * 1024) + lane;
            float s1[2] = {0.f, 0.f}, s2[2] = {0.f, 0.f};
#pragma unroll
            for (int i = 0; i < 8; i++) {
              const uint4 v = __ldg(p + 32 * i);
              const uint32_t u[4] = {v.x, v.y, v.z, v.w};
#pragma unroll
              for (int k = 0; k < 4; k++) { const float a = bf_lo(u[k]), c = bf_hi(u[k]); s1[i >> 2] += a + c; s2[i >> 2] = fmaf(a, a, fmaf(c, c, s2[i >> 2])); }
            }
#pragma unroll
            for (int o = 16; o; o >>= 1)
#pragma unroll
              for (int rr = 0; rr < 2; rr++) { s1[rr] += __shfl_xor_sync(~0u, s1[rr], o); s2[rr] += __shfl_xor_sync(~0u, s2[rr], o); }
            if (lane == 0) *(float4*)&g_stats[b * 16 + r] = make_float4(s1[0], s2[0], s1[1], s2[1]);
          }
        }
        if (l < 2) {
          float cs[8];
#pragma unroll
          for (int i = 0; i < 8; i++) cs[i] = 0.f;
          const uint4* wp = (const uint4*)(prm.wq[l] + (size_t)(bm * 128 + (lane >> 3)) * 3072 + hw * 1024 + bn * 64) + (lane & 7);
#pragma unroll 8
          for (int i = 0; i < 32; i++) {
            const uint4 v = __ldg(wp + (size_t)i * 4 * 384);
            cs[0] += bf_lo(v.x); cs[1] += bf_hi(v.x); cs[2] += bf_lo(v.y); cs[3] += bf_hi(v.y);
            cs[4] += bf_lo(v.z); cs[5] += bf_hi(v.z); cs[6] += bf_lo(v.w); cs[7] += bf_hi(v.w);
          }
#pragma unroll
          for (int i = 0; i < 8; i++) { cs[i] += __shfl_xor_sync(~0u, cs[i], 8); cs[i] += __shfl_xor_sync(~0u, cs[i], 16); }
          if (lane < 8) {
            float4* d = (float4*)(g_csp + ((l * 16 + bn) * 8 + bm) * 192 + hw * 64 + lane * 8);
            d[0] = make_float4(cs[0], cs[1], cs[2], cs[3]); d[1] = make_float4(cs[4], cs[5], cs[6], cs[7]);
          }
          __syncwarp();
          asm volatile("fence.acq_rel.gpu;" ::: "memory");
          e_red_relaxed(cnt_cs(l, bn));
          if (l == 0) e_red_relaxed(cnt_x(0, bm) + pn);
          poll_ge(lane < 8 && l == 0 ? cnt_x(0, bm) + lane : cnt_cs(l, bn), ep1 * (lane < 8 && l == 0 ? 6 : 24));
        }
        if (l > 0) poll_ge(cnt_x(l, bm) + (lane & 15), ep1 * 2);
#pragma unroll 1
        for (int it = hw * 32 + lane; it < 176; it += 96) {
          const bool rows = it < 128;
          const float4* p = rows ? (const float4*)(g_stats + bm * 256) + it : (const float4*)(g_csp + ((l & 1) * 16 + bn) * 8 * 192) + (it - 128);
          const int stride = rows ? 1024 : 48, np = rows && l == 0 ? 1 : 8;
          float4 a = make_float4(0.f, 0.f, 0.f, 0.f);
#pragma unroll
          for (int k = 0; k < 8; k++) if (k < np) { const float4 v = __ldcg(p + k * stride); a.x += v.x; a.y += v.y; a.z += v.z; a.w += v.w; }
          if (rows) {
            const float m0 = a.x * (1.f / 1024.f), m1 = a.z * (1.f / 1024.f);
            const float v0 = fmaxf(a.y * (1.f / 1024.f) - m0 * m0, 0.f), v1 = fmaxf(a.w * (1.f / 1024.f) - m1 * m1, 0.f);
            const float r0 = __fdividef(1.f, bf_round(sqrtf(bf_round(bf_round(v0) + 1e-5f)))), r1 = __fdividef(1.f, bf_round(sqrtf(bf_round(bf_round(v1) + 1e-5f))));
            a = make_float4(r0, -bf_round(m0) * (l & 1 ? r0 : 1.f), r1, -bf_round(m1) * (l & 1 ? r1 : 1.f));
          }
          *(float4*)(smem + ROWST + it * 16) = a;
        }
        __syncwarp();
        if (lane == 0) asm volatile("red.release.cta.shared.add.u32 [%0], 1;" ::"r"(sb + W_X) : "memory");
        if (hw == 2) {
          if (!(l & 1)) {
            bar_sync(NB_ST, 288);
            const uint4* hp = g_halo + ((l >> 1) * 128 + b - 16) * 384 + lane;
#pragma unroll 1
            for (int h = 0; h < 2; h++) {
              uint32_t t[18];
#pragma unroll
              for (int i = 0; i < 18; i++) t[i] = 0;
#pragma unroll 1
              for (uint32_t n = bm ? 0 : 100000u; n < 100000u; n++) {
                uint32_t miss = 0;
#pragma unroll
                for (int i = 0; i < 6; i++) miss |= ld_tagged(hp + h * 192 + i * 32, &t[3 * i]) ^ ep1;
                if (__all_sync(~0u, !miss)) break;
              }
              mbar_wait(sb + B_QE + 16, 1);
              const uint32_t r = (lane & 7) + ((lane >> 3) & 1) * 8, rv = lane >> 2;
#pragma unroll
              for (int jj = 0; jj < 2; jj++) stsm4(sb + KSC + r * 128 + (((4 * h + 2 * jj + (lane >> 4)) ^ (r & 7)) << 4), t[4 * jj], t[4 * jj + 1], t[4 * jj + 2], t[4 * jj + 3]);
              const uint32_t ad = sb + VSC + rv * 128 + (((4 * h + (lane & 3)) ^ (rv & 7)) << 4);
              sts128(ad, t[8], t[10], t[12], t[14]); sts128(ad + 1024, t[9], t[11], t[13], t[15]);
              if (h == 0 && !(lane & 2)) *(uint32_t*)(smem + HRS + ((lane >> 2) + 8 * (lane & 1)) * 8) = t[16];
              bar_arrive(NB_HALO + h, 64);
            }
          } else {
            mbar_wait(sb + B_TF + 16, 0); mbar_wait(sb + B_TF + 16, 1);
            poll_ge(cnt_kv(l >> 1, bn) + 16 + (lane & 7), ep1);
            const uint4 v = __ldcg((const uint4*)(g_kn + ((l >> 1) * 128 + bn * 8) * 16) + lane);
            const uint32_t mx = max(max(v.x, v.y), max(v.z, v.w));
            const uint32_t m0 = __reduce_max_sync(~0u, (lane & 2) ? 0u : mx), m1 = __reduce_max_sync(~0u, (lane & 2) ? mx : 0u);
            if (lane == 0) *(uint2*)(smem + ROWST) = make_uint2(m0, m1);
            __syncwarp();
            bar_arrive(NB_KN, 160); bar_arrive(NB_KN + 1, 160);
          }
        } else {
          if (l & 1) {
            bar_sync(hw ? NB_HALO : NB_DONE, 160);
            tma_st(&prm.m[M_K], 0, 2 * bn * 2048 + bm * 256 + hw * 128, sb + T0 + hw * 8192);
            tma_st(&prm.m[M_V], 0, 2 * bn * 2048 + bm * 256 + hw * 128, sb + T0 + 16384 + hw * 8192);
            bulk_commit(); bulk_wait_n<0>();
            e_red(cnt_kv(l >> 1, bn) + 8 * hw + bm);
          }
#pragma unroll 1
          for (int i = 0; i < 2; i++) {
            const int h = l & 1 ? i : hw, g = l & 1 ? hw : i;
            bar_sync(NB_SIG + 2 * h + g, 160);
            if (!(l & 1) && i == 0) continue;
            if (i == 1 && hw == 1) bar_arrive(l & 1 ? NB_ST : NB_DONE, 64);
            asm volatile("fence.acq_rel.gpu;" ::: "memory");
            e_red_relaxed(cnt_o(l, 2 * bm + g, h) + (bn >> 1));
            if (!(l & 1)) e_red_relaxed(cnt_o(l, 2 * bm, h) + (bn >> 1));
            if (h == 1 && l == 1) e_red_relaxed(cnt_ad(bn));
          }
        }
        if (hw < 2 && l < 3) {
          if (hw) bar_sync(NB_X, 320); else bar_sync(NB_X0, 288);
          if (hw) {

            tma_st(&prm.m[M_XSO], pn * 128 + 64, pm * 128, sb + QSTG + po * 16384);
            bulk_commit();
            bar_sync(NB_KV, 288);
            bulk_wait_n<0>();
          }
          e_red(cnt_x(l + 1, bm) + 2 * pn + hw);
        }
      }
    }
  } else {
    asm volatile("setmaxnreg.inc.sync.aligned.u32 224;");
    const uint32_t zero = prm.zero;
    cluster_wait();
#pragma unroll 1
    for (int l = 0; l < 4; l++) {
      {
        float acc[2][96];
#pragma unroll
        for (int i = 0; i < 96; i++) { acc[0][i] = 0.f; acc[1][i] = 0.f; }
        fence_regs(acc[0]); fence_regs(acc[1]);
        const bool early = l > 0 && wg == ((cta_id() >> 3) & 1);
        uint32_t ep1 = 0;
#pragma unroll 1
        for (int kt = 0; kt < 14; kt++) {
          const int s = kt & 3;
          if (l > 0 && kt == 0) mbar_wait(sb + B_QL, (l + 1) & 1);
          if (!(early && kt < 2)) mbar_wait(sb + B_QF + 8 * s, (kt >> 2) & 1);
          const uint64_t da = prm.xd + wg * 1024 + s * (QSTG >> 4), db = prm.wd + s * (QSTG >> 4);
          wg_fence();
#pragma unroll
          for (int k = 0; k < 4; k++)
#pragma unroll
            for (int m = 0; m < 2; m++) wgmma_m64n192k16_ss_tb(acc[m], da + m * 512 + k * 2, db + k * 128, 1);
          wg_commit();
          if (kt == 4) ep1 = *(volatile uint32_t*)&g_epoch + 1;
          wg_wait<1>();
          if (early && (kt == 1 || kt == 2)) mbar_wait(sb + B_QF + 8 * (kt - 1), 0);
          if (kt > 0 && w == 0) e_arrive_both(sb + B_QE + 8 * ((kt - 1) & 3));
        }
        {
          const bool lag = (l & 1) && wg;
          const uint64_t da = prm.xd + wg * 1024 + 2 * (QSTG >> 4), db = prm.wd + 2 * (QSTG >> 4);
          mbar_wait(sb + B_QF + 16, 1);
          if (lag) {
            mbar_wait(sb + B_QF + 24, 1);
            wg_wait<0>();
            if (w == 0) e_arrive_both(sb + B_QE + 8);
            bar_sync(NB_SC, 256);
          }
          wg_fence();
#pragma unroll
          for (int k = 0; k < 4; k++)
#pragma unroll
            for (int m = 0; m < 2; m++) wgmma_m64n192k16_ss_tb(acc[m], da + m * 512 + k * 2, db + k * 128, 1);
          wg_commit();
          if (!lag) {
            wg_wait<1>();
            if (w == 0) e_arrive_both(sb + B_QE + 8);
            mbar_wait(sb + B_QF + 24, 1);
          }
          wg_fence();
#pragma unroll
          for (int m = 1; m >= 0; m--) {
#pragma unroll
            for (int k = 0; k < 4; k++) wgmma_m64n192k16_ss_tb(acc[m], da + (QSTG >> 4) + m * 512 + k * 2, db + (QSTG >> 4) + k * 128, 1);
            wg_commit();
          }
          if ((l & 1) && !wg) bar_arrive(NB_SC, 256);
          if (!(l & 1)) bar_arrive(NB_ST, 288);
          wg_wait<2>();
          if (w == 0) e_arrive_both(sb + B_QE + 16);
        }
#pragma unroll 1
        for (uint32_t n = 0; n < 4000000u; n++) {
          uint32_t v;
          asm volatile("ld.acquire.cta.shared.u32 %0, [%1];" : "=r"(v) : "r"(sb + W_X) : "memory");
          if (v == (uint32_t)(3 * l + 3)) break;
        }
        IDS();
        const int g = lane >> 2, qd = lane & 3;
        float2 st[2][2];
#pragma unroll
        for (int m = 0; m < 2; m++)
#pragma unroll
          for (int hh = 0; hh < 2; hh++) st[m][hh] = lds64f(sb + ROWST + (wg * 128 + m * 64 + w * 16 + g + 8 * hh) * 8);
        float2 cs[4];
        auto load_cs = [&](int gi) {
#pragma unroll
          for (int j = 0; j < 4; j++) cs[j] = lds64f(sb + COLS + (gi * 32 + j * 8 + 2 * qd) * 4);
        };
        load_cs(2);
        auto drain = [&]() {
          wg_wait<0>(); fence_regs(acc[0]);
          if (w == 0) e_arrive_both(sb + B_QE + 8 * 3);
        };
        wg_wait<1>(); fence_regs(acc[1]);
        auto norm_tile = [&](int gi, int m, float sc, uint32_t (&t)[8], float (&nrm)[2], bool h16 = false) {
          const float r0 = st[m][0].x * sc, s0 = st[m][0].y * sc, r1 = st[m][1].x * sc, s1 = st[m][1].y * sc;
          float n0 = 0.f, n1 = 0.f;
#pragma unroll
          for (int j = 0; j < 4; j++) {
            const float* a = &acc[m][16 * gi + 4 * j];
            const float v0 = fmaf(a[0], r0, s0 * cs[j].x), v1 = fmaf(a[1], r0, s0 * cs[j].y);
            const float v2 = fmaf(a[2], r1, s1 * cs[j].x), v3 = fmaf(a[3], r1, s1 * cs[j].y);
            n0 = fmaf(v0, v0, fmaf(v1, v1, n0)); n1 = fmaf(v2, v2, fmaf(v3, v3, n1));
            t[2 * j] = h16 ? pack2h(v0, v1) : pack2(v0, v1); t[2 * j + 1] = h16 ? pack2h(v2, v3) : pack2(v2, v3);
          }
          nrm[0] = n0; nrm[1] = n1;
        };
        auto norm_group = [&](int gi, float sc, uint32_t (&t)[2][8], float (&nrm)[2][2]) { norm_tile(gi, 0, sc, t[0], nrm[0]); norm_tile(gi, 1, sc, t[1], nrm[1]); };
        uint32_t q[2][2][8];
        const uint32_t srow = (lane & 7) + ((lane >> 3) & 1) * 8;
        const uint32_t row0 = wg * 128 + w * 16;
        auto put_o = [&](int h, int m, const float (&o)[16], float i0, float i1) {
          IDS();
          bf16* op = g_os + (size_t)(bm * 256 + row0 + m * 64 + (lane >> 2)) * 1024 + h * 512 + bn * 32 + (lane & 3) * 8;
          *(uint4*)op = make_uint4(pack2(o[0] * i0, o[1] * i0), pack2(o[4] * i0, o[5] * i0), pack2(o[8] * i0, o[9] * i0), pack2(o[12] * i0, o[13] * i0));
          *(uint4*)(op + 8 * 1024) = make_uint4(pack2(o[2] * i1, o[3] * i1), pack2(o[6] * i1, o[7] * i1), pack2(o[10] * i1, o[11] * i1), pack2(o[14] * i1, o[15] * i1));
        };
        if (!(l & 1)) {
          auto put_kv = [&](int gi, uint32_t r0, const uint32_t (&t)[8]) {
            if (gi < 4) {
              const uint32_t r = r0 + srow;
#pragma unroll
              for (int jj = 0; jj < 2; jj++) stsm4(sb + KSC + r * 128 + (((4 * (gi - 2) + 2 * jj + (lane >> 4)) ^ (r & 7)) << 4), t[4 * jj], t[4 * jj + 1], t[4 * jj + 2], t[4 * jj + 3]);
            } else {
              const uint32_t r = r0 + g, ad = sb + VSC + r * 128 + (((4 * (gi - 4) + qd) ^ (r & 7)) << 4);
              sts128(ad, t[0], t[2], t[4], t[6]); sts128(ad + 1024, t[1], t[3], t[5], t[7]);
            }
          };
          auto cen_tile = [&](int gi, int m, uint32_t (&t)[8]) {
#pragma unroll
            for (int j = 0; j < 4; j++) {
              const float* a = &acc[m][16 * gi + 4 * j];
              t[2 * j] = pack2(fmaf(st[m][0].y, cs[j].x, a[0]), fmaf(st[m][0].y, cs[j].y, a[1]));
              t[2 * j + 1] = pack2(fmaf(st[m][1].y, cs[j].x, a[2]), fmaf(st[m][1].y, cs[j].y, a[3]));
            }
          };
          const bool send = wg == 1 && w == 3 && bm < 7;
          uint4* hp = g_halo + ((l >> 1) * 128 + b) * 384 + lane;
          mbar_wait(sb + B_QE + 16, 1);
          float2 cn[4];
          auto next_cs = [&](int gi) {
#pragma unroll
            for (int j = 0; j < 4; j++) { cs[j] = cn[j]; cn[j] = lds64f(sb + COLS + (gi * 32 + j * 8 + 2 * qd) * 4); }
          };
#pragma unroll
          for (int j = 0; j < 4; j++) cn[j] = cs[j];
#pragma unroll
          for (int h = 0; h < 2; h++) {
            uint32_t k[8], v[8];
            next_cs(4 + h);
            cen_tile(2 + h, 1, k); put_kv(2 + h, 16 + row0 + 64, k);
            next_cs(h ? 2 : 3);
            cen_tile(4 + h, 1, v); put_kv(4 + h, 16 + row0 + 64, v);
            if (send) {
              uint4* p = hp + h * 192;
              st_tagged(p, k[0], k[1], k[2], ep1); st_tagged(p + 32, k[3], k[4], k[5], ep1); st_tagged(p + 64, k[6], k[7], v[0], ep1);
              st_tagged(p + 96, v[1], v[2], v[3], ep1); st_tagged(p + 128, v[4], v[5], v[6], ep1);
              st_tagged(p + 160, v[7], __float_as_uint(qd & 1 ? st[1][1].x : st[1][0].x), 0u, ep1);
            }
            sched_fence();
          }
          drain();
          {
            uint32_t t[8];
            next_cs(4); cen_tile(2, 0, t); put_kv(2, 16 + row0, t);
            next_cs(0); cen_tile(4, 0, t); put_kv(4, 16 + row0, t);
            next_cs(3); cen_tile(0, 0, q[0][0]); cen_tile(0, 1, q[0][1]);
          }
          bar_sync(NB_SC, 256);
          const bool e = g & 1, sel = 2 * qd + (g & 1) >= g + 2, first = bm == 0 && row0 == 0;
          if (row0 == 0) bar_sync(NB_HALO, 64);
          float ra[4], rb[4], ca[4], cb[4];
#pragma unroll
          for (int m = 0; m < 2; m++) {
            float rk[3];
#pragma unroll
            for (int u = 0; u < 3; u++) {
              const int r = row0 + m * 64 + 8 * u + 2 * qd + e - (sel ? 16 : 8);
              rk[u] = lds64f(sb + (m == 0 && r < 0 ? HRS + 128 : ROWST) + r * 8).x;
            }
            ra[2 * m] = sel ? rk[1] : rk[0]; ra[2 * m + 1] = sel ? rk[2] : rk[1];
            rb[2 * m] = sel ? rk[0] : rk[1]; rb[2 * m + 1] = sel ? rk[1] : rk[2];
          }
#pragma unroll
          for (int i = 0; i < 4; i++) { const float rq = st[i >> 1][i & 1].x * QSCALE; ca[i] = rq * ra[i]; cb[i] = rq * rb[i]; }
#pragma unroll 1
          for (int h = 0; h < 2; h++) {
            float s[2][4][4];
            uint32_t vf[2][4][4], pf[2][2][4];
#pragma unroll
            for (int m = 0; m < 2; m++)
#pragma unroll
              for (int nt = 0; nt < 4; nt++) {
                uint32_t kf[4];
                const uint32_t r = row0 + m * 64 + 8 * nt + (lane & 7), ch = 4 * h + (lane >> 3);
                ldsm4(sb + KSC + r * 128 + ((ch ^ (r & 7)) << 4), kf);
                s[m][nt][0] = s[m][nt][1] = s[m][nt][2] = s[m][nt][3] = 0.f;
                mma16816(s[m][nt], q[0][m][0], q[0][m][1], q[0][m][2], q[0][m][3], kf[0], kf[1]);
                mma16816(s[m][nt], q[0][m][4], q[0][m][5], q[0][m][6], q[0][m][7], kf[2], kf[3]);
              }
#pragma unroll
            for (int m = 0; m < 2; m++)
#pragma unroll
              for (int i = 0; i < 4; i++) {
                const uint32_t r = row0 + m * 64 + 16 * (i >> 1) + srow, ch = 4 * h + 2 * (i & 1) + (lane >> 4);
                ldsm4t(sb + VSC + r * 128 + ((ch ^ (r & 7)) << 4), vf[m][i]);
              }
            float va[4], vb[4], mx[4];
#pragma unroll
            for (int i = 0; i < 4; i++) {
              const int m = i >> 1, hh = i & 1;
              const float a = e ? s[m][hh + 1][2 * hh + 1] : s[m][hh + 1][2 * hh];
              const float lo = e ? s[m][hh][2 * hh + 1] : s[m][hh][2 * hh], hi = e ? s[m][hh + 2][2 * hh + 1] : s[m][hh + 2][2 * hh];
              va[i] = (m == 0 && hh == 0 && first) ? -INFINITY : a * ca[i];
              vb[i] = (m == 0 && first && sel) ? -INFINITY : (sel ? lo : hi) * cb[i];
              mx[i] = fmaxf(va[i], vb[i]);
            }
#pragma unroll
            for (int i = 0; i < 4; i++) mx[i] = fmaxf(mx[i], __shfl_xor_sync(~0u, mx[i], 1));
#pragma unroll
            for (int i = 0; i < 4; i++) mx[i] = fmaxf(mx[i], __shfl_xor_sync(~0u, mx[i], 2));
#pragma unroll
            for (int i = 0; i < 4; i++) {
              va[i] = ex2(va[i] - mx[i]); vb[i] = ex2(vb[i] - mx[i]);
              mx[i] = va[i] + vb[i];
              va[i] *= ra[i]; vb[i] *= rb[i];
            }
#pragma unroll
            for (int i = 0; i < 4; i++) mx[i] += __shfl_xor_sync(~0u, mx[i], 1);
#pragma unroll
            for (int i = 0; i < 4; i++) mx[i] += __shfl_xor_sync(~0u, mx[i], 2);
#pragma unroll
            for (int i = 0; i < 4; i++) {
              const int m = i >> 1, hh = i & 1;
              const float inv = rcp(mx[i]);
              const uint32_t t = pack2(va[i] * inv, vb[i] * inv);
              const uint32_t pa = e ? t << 16 : t & 0xFFFFu, pb = e ? t & 0xFFFF0000u : t >> 16;
              pf[m][hh][hh + 1] = pa; pf[m][hh][hh] = sel ? pb : 0u; pf[m][hh][hh + 2] = sel ? 0u : pb; pf[m][hh][3 - 3 * hh] = 0u;
            }
#pragma unroll
            for (int m = 0; m < 2; m++) {
              float o[4][4];
#pragma unroll
              for (int j = 0; j < 4; j++) o[j][0] = o[j][1] = o[j][2] = o[j][3] = 0.f;
#pragma unroll
              for (int i = 0; i < 4; i++) {
                const int kk = i >> 1, jj = 2 * (i & 1);
                mma16816(o[jj], pf[m][0][2 * kk], pf[m][1][2 * kk], pf[m][0][2 * kk + 1], pf[m][1][2 * kk + 1], vf[m][i][0], vf[m][i][1]);
                mma16816(o[jj + 1], pf[m][0][2 * kk], pf[m][1][2 * kk], pf[m][0][2 * kk + 1], pf[m][1][2 * kk + 1], vf[m][i][2], vf[m][i][3]);
              }
              const float of[16] = {o[0][0], o[0][1], o[0][2], o[0][3], o[1][0], o[1][1], o[1][2], o[1][3], o[2][0], o[2][1], o[2][2], o[2][3], o[3][0], o[3][1], o[3][2], o[3][3]};
              put_o(h, m, of, 1.f, 1.f);
            }
            bar_arrive(NB_SIG + 2 * h + wg, 160);
            if (h == 0) {
              uint32_t t[8];
              next_cs(5); cen_tile(3, 0, t); put_kv(3, 16 + row0, t);
              next_cs(1); cen_tile(5, 0, t); put_kv(5, 16 + row0, t);
#pragma unroll
              for (int j = 0; j < 4; j++) cs[j] = cn[j];
              cen_tile(1, 0, q[0][0]); cen_tile(1, 1, q[0][1]);
              bar_sync(NB_SC, 256);
              if (row0 == 0) bar_sync(NB_HALO + 1, 64);
            }
          }
        } else {
          float qn[2];
          drain();
          auto esc_ptr = [&](int gi) { IDS(); return g_esc + (size_t)(((l & 2) + (gi >> 1)) * 65536 + (2 * bn + (gi & 1)) * 2048) * 20; };
          auto norm_half = [&](int gi, float sc, uint32_t (&t)[2][8], float (&nrm)[2][2]) {
            norm_tile(gi, 0, sc, t[0], nrm[0], true); norm_tile(gi, 1, sc, t[1], nrm[1], true);
            if (!((nrm[0][0] + nrm[0][1]) + (nrm[1][0] + nrm[1][1]) <= 4e9f) || fminf(fminf(nrm[0][0], nrm[0][1]), fminf(nrm[1][0], nrm[1][1])) < 1.5e-5f) {
              uint32_t* p = esc_ptr(gi) + (bm * 256 + row0 + g) * 20 + qd;
#pragma unroll
              for (int m = 0; m < 2; m++) {
                uint32_t u[8]; float d[2];
                norm_tile(gi, m, sc, u, d);
#pragma unroll
                for (int i = 0; i < 10; i++) p[(m * 64 + (i & 1) * 8) * 20 + (i >> 1) * 4] = i < 8 ? u[i] : ep1;
              }
            }
            __syncwarp();
          };
          {
            auto max_norm = [&](const float (&nrm)[2][2]) {
              const bool o1 = qd & 1, o2 = qd & 2;
              const float a = (o1 ? nrm[1][0] : nrm[0][0]) + __shfl_xor_sync(~0u, o1 ? nrm[0][0] : nrm[1][0], 1);
              const float c = (o1 ? nrm[1][1] : nrm[0][1]) + __shfl_xor_sync(~0u, o1 ? nrm[0][1] : nrm[1][1], 1);
              const float d = (o2 ? c : a) + __shfl_xor_sync(~0u, o2 ? a : c, 2);
              return __uint_as_float(__reduce_max_sync(~0u, __float_as_uint(d)));
            };
#pragma unroll
            for (int h = 0; h < 2; h++) {
              uint32_t t[2][8]; float nrm[2][2];
              const uint32_t kb = sb + (h ? 0 : T0);
              if (h) load_cs(3);
              uint32_t tv[2][8];
              norm_half(2 + h, 1.f, t, nrm);
              load_cs(4 + h);
              float nv[2][2];
              if (h == 1) { const float kn = max_norm(nrm); if (lane == 0) g_kn[((l >> 1) * 128 + bn * 8 + bm) * 16 + 8 + wg * 4 + w] = kn; }
              if (h == 0) mbar_wait(sb + B_QE + 8, 1);
#pragma unroll
              for (int i = 0; i < 4; i++) {
                const uint32_t r = row0 + (i >> 1) * 64 + srow;
                stsm4(kb + r * 64 + (((2 * (i & 1) + (lane >> 4)) ^ ((r >> 1) & 3)) << 4), t[i >> 1][4 * (i & 1)], t[i >> 1][4 * (i & 1) + 1], t[i >> 1][4 * (i & 1) + 2], t[i >> 1][4 * (i & 1) + 3]);
              }
              norm_group(4 + h, 1.f, tv, nv);
              load_cs(h);
#pragma unroll
              for (int m = 0; m < 2; m++) {
                const uint32_t r = row0 + m * 64 + g, ad = kb + 16384 + r * 64 + ((qd ^ ((r >> 1) & 3)) << 4);
                sts128(ad, tv[m][0], tv[m][2], tv[m][4], tv[m][6]); sts128(ad + 512, tv[m][1], tv[m][3], tv[m][5], tv[m][7]);
              }
              fence_async_smem();
              bar_arrive(NB_KV + 12 * h, 288);
              if (h == 0) {
                bar_arrive(wg ? NB_HALO : NB_DONE, 160);
                if (wg) bar_sync(NB_HALO + 1, 256);
              }
              if (h == 0) { const float kn = max_norm(nrm); if (lane == 0) g_kn[((l >> 1) * 128 + bn * 8 + bm) * 16 + wg * 4 + w] = kn; }
              norm_half(h, QSCALE, q[h], nrm);
#pragma unroll
              for (int i = 0; i < 4; i++) sts128(sb + QPARK + h * 16384 + (wg * 128 + w * 32 + lane) * 16 + i * 4096, q[h][i >> 1][4 * (i & 1)], q[h][i >> 1][4 * (i & 1) + 1], q[h][i >> 1][4 * (i & 1) + 2], q[h][i >> 1][4 * (i & 1) + 3]);
              qn[h] = max_norm(nrm);
            }
            if (!wg) bar_arrive(NB_HALO + 1, 256);
          }
          constexpr uint64_t VSTEP = 64 - (64ull << 16);
          const uint32_t c_882 = 0x62E562E5u + (lane_id() & zero), c_lsb = 0x00010001u + (lane_id() & zero), c_half = 0x3F003F00u + (lane_id() & zero);
          float o[2][20], S[2][32];
          uint32_t H[2][16], P0[4] = {}, P1[4] = {};
#pragma unroll
          for (int m = 0; m < 2; m++) {
#pragma unroll
            for (int i = 0; i < 20; i++) o[m][i] = 0.f;
            fence_regs(o[m]);
          }
          auto qkf = [&](int b, int ks, uint64_t d) { wg_n64_rs_nb_f16_f32(S[b], q[0][0][4 * ks], q[0][0][4 * ks + 1], q[0][0][4 * ks + 2], q[0][0][4 * ks + 3], d + 2 * ks, ks ? 1 : zero); };
          auto qkh = [&](int b, int ks, uint64_t d) { wg_n64_rs_nb_f16_f16(H[b], q[0][1][4 * ks], q[0][1][4 * ks + 1], q[0][1][4 * ks + 2], q[0][1][4 * ks + 3], d + 2 * ks, ks ? 1 : zero); };
          auto pv0 = [&](uint64_t d) { wgmma_m64n40k16_rs_tb(o[0], P0[0], P0[1], P0[2], P0[3], d, 1); };
          auto pv1 = [&](uint64_t d) { wgmma_m64n40k16_rs_tb(o[1], P1[0], P1[1], P1[2], P1[3], d, 1); };
          float e[4] = {};
          auto finish = [&](int h) {
            const float* s = &S[(h >> 2) & 1][8 * (h & 3)];
            const uint32_t* u = &H[(h >> 2) & 1][4 * (h & 3)];
            const float z0 = exp2_fix(s[6]), z1 = exp2_fix(s[7]);
            P0[0] = pack2v(e[0], e[1]);
            P1[0] = exp2_h2(u[0], c_882);
            P0[1] = pack2v(e[2], e[3]);
            P1[1] = exp2_h2(u[1], c_882);
            const uint32_t B = exp2_base(z0, z1), E = and_or<0x7F807F80u>(B, c_lsb);
            P1[3] = exp2_h2(u[3], c_882);
            P0[3] = fma_bf2(B, and_or<0x807F807Fu>(B, c_half), E);
            const float e4 = ex2v(s[4]), e5 = ex2v(s[5]);
            P1[2] = exp2_h2(u[2], c_882);
            P0[2] = pack2v(e4, e5);
          };
          auto start = [&](int h) {
            const float* s = &S[(h >> 2) & 1][8 * (h & 3)];
            e[0] = ex2v(s[0]); e[1] = ex2v(s[1]); e[3] = ex2v(s[3]); e[2] = ex2v(s[2]);
          };
          uint64_t kd = prm.kv[0].kd;
          mbar_wait(sb + B_TF, 0);
          wg_fence();
#pragma unroll
          for (int b = 0; b < 2; b++) {
            wg_n64_rs_nb_f16_f32_z(S[b], q[0][0][0], q[0][0][1], q[0][0][2], q[0][0][3], kd + 256 * b, 0);
            wg_n64_rs_nb_f16_f16_z(H[b], q[0][1][0], q[0][1][1], q[0][1][2], q[0][1][3], kd + 256 * b, 0);
            if (b == 0) { qkf(0, 1, kd); qkh(0, 1, kd); }
            wg_commit();
          }
          wg_wait<1>(); fence_regs(S[0]); fence_regs(H[0]);
          start(0); finish(0); start(1);
          wg_wait<0>();
          int redo = 0;
#pragma unroll 1
          for (int pass = 0, j = 1; pass < 2; pass++) {
#pragma unroll 1
           do {
            const uint64_t vd = prm.kv[j & 3].vd;
            bool go = false;
#pragma unroll
            for (int h = 2; h < 18; h++) {
              const int px = (h >> 2) + 1, c = h & 3;
              wg_fence();
              if (h == 13) kd = prm.kv[j & 3].kd;
              const uint64_t kx = kd + (px & 3) * 256, vx = vd + (h - 2) * VSTEP;
              if (h == 2) { qkh(1, 0, kx); qkf(1, 0, kx); pv0(vx); pv1(vx); qkh(1, 1, kx); qkf(1, 1, kx); }
              else if ((c == 1 || c == 2) && h < 17) { qkh(px & 1, c - 1, kx); pv1(vx); qkf(px & 1, c - 1, kx); pv0(vx); }
              else { pv0(vx); pv1(vx); }
              wg_commit();
              if (h == 3) e_arrive_if(sb + B_TE + 8 * ((j + 2) & 3), j > 1);
              if (h == 11) go = mbar_test(sb + B_TF + 8 * (j & 3), (j >> 2) & 1) && j != 8;
              finish(h - 1); start(h);
              if (h != 12 && h != 17) sched_fence();
              if (h == 12 && !go) {
                if (j == 16) {
#pragma unroll
                  for (int u = 13; u < 18; u++) {
                    wg_fence(); pv0(vd + (u - 2) * VSTEP); pv1(vd + (u - 2) * VSTEP); wg_commit();
                    if (u < 17) finish(u - 1);
                    if (u < 16) { start(u); sched_fence(); }
                    if (u & 1) { if (u == 17) wg_wait<0>(); else wg_wait<1>(); }
                  }
                  e_arrive(sb + B_TE + 24);
                  goto head_done;
                }
                mbar_wait(sb + B_TF + 8 * (j & 3), (j >> 2) & 1);
                if (j == 8) {
#pragma unroll
                  for (int i = 0; i < 4; i++) lds128(sb + QPARK + 16384 + (wg * 128 + w * 32 + lane_id()) * 16 + i * 4096, &q[0][i >> 1][4 * (i & 1)]);
                }
              }
              if (h == 17) wg_wait<0>(); else if (h & 1) wg_wait<1>();
              if (c == 3) { fence_regs(S[px & 1]); fence_regs(H[px & 1]); }
            }
           } while (j++ & 7);
           head_done:
            fence_regs(o[0]); fence_regs(o[1]);
            uint32_t pk[2][8];
            {
              IDS();
              bf16* op = g_os + (size_t)(bm * 256 + row0 + (lane >> 2)) * 1024 + pass * 512 + bn * 32 + (lane & 3) * 8;
#pragma unroll
              for (int i = 0; i < 4; i++) {
                const float* a = &o[i >> 1][2 * (i & 1)];
                const float inv = rcp(a[16]);
                uint32_t* u = &pk[i >> 1][4 * (i & 1)];
#pragma unroll
                for (int k = 0; k < 4; k++) u[k] = pack2(a[4 * k] * inv, a[4 * k + 1] * inv);
                *(uint4*)(op + ((i >> 1) * 64 + (i & 1) * 8) * 1024) = make_uint4(u[0], u[1], u[2], u[3]);
              }
            }
            sched_fence();
            if (pass == 0) bar_sync(NB_KN + wg, 160);
            const float kmax = *(volatile float*)(smem + ROWST + 4 * pass);
            const bool wide = !(qn[0] <= 1.6e7f) | !(kmax <= 1.6e7f) | !(qn[0] * kmax <= 112.f * 112.f);
            int badm = 0;
#pragma unroll
            for (int m = 0; m < 2; m++) {
              uint32_t chk[2] = {0u, 0u};
#pragma unroll
              for (int i = 0; i < 8; i++) asm("fma.rn.bf16x2 %0, %1, %2, %0;" : "+r"(chk[i & 1]) : "r"(pk[m][i]), "r"(0u));
              const bool bad = wide | !(fminf(o[m][16], o[m][18]) >= 9.3e-10f) | !(o[m][16] + o[m][18] <= 1e36f) | (((chk[0] | chk[1]) & 0x7FFF7FFFu) != 0);
              badm |= __any_sync(~0u, bad) << m;
            }
            if (!badm) bar_arrive(NB_SIG + 2 * pass + wg, 160);
            qn[0] = qn[1];
#pragma unroll
            for (int m = 0; m < 2; m++) {
#pragma unroll
              for (int i = 0; i < 20; i++) o[m][i] = 0.f;
              fence_regs(o[m]);
            }
            if (badm) {
              redo |= badm << 2 * pass;
              const int tx = wg * 128 + w * 32 + lane_id();
              uint4* p = g_qsave + (block_id() * 256 + tx) * 8 + pass * 4;
#pragma unroll
              for (int i = 0; i < 4; i++) {
                uint32_t u[4] = {q[0][i >> 1][4 * (i & 1)], q[0][i >> 1][4 * (i & 1) + 1], q[0][i >> 1][4 * (i & 1) + 2], q[0][i >> 1][4 * (i & 1) + 3]};
                if (pass == 0) lds128(sb + QPARK + tx * 16 + i * 4096, u);
                p[i] = make_uint4(u[0], u[1], u[2], u[3]);
              }
            }
          }
          if (redo) attn_redo(redo, l, cta_id(), wg, w, ep1);
        }
      }
      {
        float acc[64];
#pragma unroll
        for (int i = 0; i < 64; i++) acc[i] = 0.f;
        fence_regs(acc);
        uint32_t s = 0, lap = 0;
#pragma unroll 1
        for (int kt = 0; kt < 16; kt++) {
          mbar_wait(sb + B_PF + 8 * s, ((s < 4 ? l : 0) + lap) & 1);
          const uint64_t da = mkdesc(sb + pslot_a(s, l) + wg * 8192, 16, 1024, 1), db = mkdesc(sb + pslot_b(s), 8192, 1024, 1);
          wg_fence();
#pragma unroll
          for (int k = 0; k < 4; k++) wgmma_m64n128k16_ss_tb(acc, da + k * 2, db + k * 128, 1);
          wg_commit();
          wg_wait<1>();
          if (kt > 0 && w == 0) e_arrive_both(sb + B_PE + 8 * (s ? s - 1 : 5));
          if (++s == 6) { s = 0; lap++; }
        }
        IDS();
        const int g = lane >> 2, qd = lane & 3;
        const int r0 = wg * 64 + w * 16;
        const uint32_t r = r0 + (lane & 7) + ((lane >> 3) & 1) * 8;
        uint32_t x[8][4];
        mbar_wait(sb + B_RF, l & 1);
#pragma unroll
        for (int jj = 0; jj < 8; jj++) ldsm4(sb + RES + (jj >> 2) * 16384 + r * 128 + ((((2 * jj + (lane >> 4)) & 7) ^ (r & 7)) << 4), x[jj]);
        wg_wait<0>();
        fence_regs(acc);
        if (w == 0) e_arrive_both(sb + B_PE + 8 * 3);
        const CUtensorMap* mo = &prm.m[l == 3 ? M_OUT : M_XST];
#pragma unroll
        for (int jj = 0; jj < 8; jj++) {
#pragma unroll
          for (int i = 0; i < 4; i++) x[jj][i] = add_bf16x2(x[jj][i], pack2(acc[8 * jj + 2 * i], acc[8 * jj + 2 * i + 1]));
          if (jj < 4) stsm4(sb + RES + r * 128 + ((((2 * jj + (lane >> 4)) & 7) ^ (r & 7)) << 4), x[jj][0], x[jj][1], x[jj][2], x[jj][3]);
          if (jj == 3) { fence_async_smem(); __syncwarp(); tma_st(mo, pn * 128, pm * 128 + r0, sb + RES + r0 * 128); bulk_commit(); sched_fence(); }
        }
        if (l == 3) {
#pragma unroll
          for (int jj = 4; jj < 8; jj++) stsm4(sb + RES + 16384 + r * 128 + ((((2 * jj + (lane >> 4)) & 7) ^ (r & 7)) << 4), x[jj][0], x[jj][1], x[jj][2], x[jj][3]);
          fence_async_smem(); __syncwarp();
          tma_st(mo, pn * 128 + 64, pm * 128 + r0, sb + RES + 16384 + r0 * 128);
          bulk_commit(); bulk_wait_n<0>();
        } else {
          bar_sync(NB_SC, 256);
#pragma unroll
          for (int jj = 0; jj < 8; jj++)
            stsm4(sb + (jj >> 2) * QSTG + po * 16384 + r * 128 + ((((2 * jj + (lane >> 4)) & 7) ^ (r & 7)) << 4), x[jj][0], x[jj][1], x[jj][2], x[jj][3]);
          bulk_wait_n<0>();
          bar_arrive(NB_X0, 288);
          fence_async_smem();
          bar_arrive(NB_X, 320);
          float s1[4] = {0.f, 0.f, 0.f, 0.f}, sa[4] = {0.f, 0.f, 0.f, 0.f}, sc[4] = {0.f, 0.f, 0.f, 0.f};
#pragma unroll
          for (int jj = 0; jj < 8; jj++) {
            mma16816(s1, x[jj][0], x[jj][1], x[jj][2], x[jj][3], 0x3f803f80u, 0x3f803f80u);
            mma16816(sa, x[jj][0], x[jj][1], x[jj][2], x[jj][3], x[jj][0], x[jj][2]);
            mma16816(sc, x[jj][0], x[jj][1], x[jj][2], x[jj][3], x[jj][1], x[jj][3]);
          }
          if (qd == g >> 1) {
            float2* p = g_stats + pn * 2048 + pm * 128 + r0 + g;
            p[0] = make_float2(s1[0], g & 1 ? sa[1] : sa[0]);
            p[8] = make_float2(s1[2], g & 1 ? sc[3] : sc[2]);
          }
          bar_arrive(NB_KV, 288);
        }
      }
    }
  }
  asm volatile("barrier.cluster.arrive.relaxed.aligned;\nbarrier.cluster.wait.aligned;" ::: "memory");
}

typedef CUresult (*EncodeFn)(CUtensorMap*, CUtensorMapDataType, cuuint32_t, void*, const cuuint64_t*, const cuuint64_t*, const cuuint32_t*,
                             const cuuint32_t*, CUtensorMapInterleave, CUtensorMapSwizzle, CUtensorMapL2promotion, CUtensorMapFloatOOBfill);

static void make_map(EncodeFn fn, CUtensorMap* m, const void* ptr, int rank, const uint64_t* dims, const uint64_t* strides, const uint32_t* box, CUtensorMapSwizzle sw) {
  cuuint64_t d[5], st[4];
  cuuint32_t bx[5], es[5];
  for (int i = 0; i < rank; i++) { d[i] = dims[i]; bx[i] = box[i]; es[i] = 1; if (i) st[i - 1] = strides[i - 1] * 2; }
  fn(m, CU_TENSOR_MAP_DATA_TYPE_BFLOAT16, rank, (void*)ptr, d, st, bx, es, CU_TENSOR_MAP_INTERLEAVE_NONE, sw,
     CU_TENSOR_MAP_L2_PROMOTION_L2_128B, CU_TENSOR_MAP_FLOAT_OOB_FILL_NONE);
}
static void map2(EncodeFn fn, CUtensorMap* m, const void* ptr, uint64_t inner, uint64_t outer, uint32_t bi, uint32_t bo, CUtensorMapSwizzle sw) {
  const uint64_t d[2] = {inner, outer}, st[1] = {inner};
  const uint32_t bx[2] = {bi, bo};
  make_map(fn, m, ptr, 2, d, st, bx, sw);
}

extern "C" void kernel_launch(void* const* d_in, const int* in_sizes, int n_in, void* d_out, int out_size) {
  (void)in_sizes; (void)n_in; (void)out_size;
  static EncodeFn enc = nullptr;
  static void *xs, *os, *kk, *vv;
  static int sbase = 1024;
  if (!enc) {
    void* p = nullptr;
    cudaDriverEntryPointQueryResult qr;
    cudaGetDriverEntryPoint("cuTensorMapEncodeTiled", &p, cudaEnableDefault, &qr);
    enc = (EncodeFn)p;
    Scratch* sc = nullptr;
    cudaGetSymbolAddress((void**)&sc, g_s);
    xs = sc->xs; os = sc->os; kk = sc->k; vv = sc->v;
    int dev = 0;
    cudaGetDevice(&dev);
    cudaDeviceGetAttribute(&sbase, cudaDevAttrReservedSharedMemoryPerBlock, dev);
    cudaFuncSetAttribute(fused_kernel, cudaFuncAttributeMaxDynamicSharedMemorySize, SMEM_BYTES);
  }
  Params prm;
  const CUtensorMapSwizzle S128 = CU_TENSOR_MAP_SWIZZLE_128B, S64 = CU_TENSOR_MAP_SWIZZLE_64B;
  map2(enc, &prm.m[M_X0A], d_in[0], 1024, 2048, 64, 256, S128);
  map2(enc, &prm.m[M_XSA], xs, 1024, 2048, 64, 256, S128);
  for (int t = 0; t < 2; t++) {
    const uint64_t d3[3] = {1024, 1024, 3}, s3[2] = {3072, 1024};
    const uint32_t b3[3] = {64, 64, 3};
    make_map(enc, &prm.m[M_WQA + t], d_in[1 + 3 * t], 3, d3, s3, b3, S128);
    const uint64_t d5[5] = {64, 32, 2, 16, 16}, s5[4] = {1024, 32 * 1024, 64 * 1024, 64};
    const uint32_t b5[5] = {64, 32, 1, 2, 2};
    make_map(enc, &prm.m[M_WOA + t], d_in[2 + 3 * t], 5, d5, s5, b5, S128);
    const uint64_t dr[3] = {64, 2048, 16}, sr[2] = {1024, 64};
    const uint32_t br[3] = {64, 128, 2};
    make_map(enc, &prm.m[M_X0R + t], t ? xs : d_in[0], 3, dr, sr, br, S128);
  }
  map2(enc, &prm.m[M_OS], os, 1024, 2048, 64, 64, S128);
  map2(enc, &prm.m[M_K], kk, 32, 65536, 32, 128, S64);
  map2(enc, &prm.m[M_V], vv, 32, 65536, 32, 128, S64);
  map2(enc, &prm.m[M_XSO], xs, 1024, 2048, 64, 128, S128);
  map2(enc, &prm.m[M_X0H], d_in[0], 1024, 2048, 64, 128, S128);
  map2(enc, &prm.m[M_XST], xs, 1024, 2048, 64, 16, S128);
  map2(enc, &prm.m[M_OUT], d_out, 1024, 2048, 64, 16, S128);
  prm.x0 = (const bf16*)d_in[0];
  prm.wq[0] = (const bf16*)d_in[1]; prm.wq[1] = (const bf16*)d_in[4];
  prm.zero = 0;
  for (int i = 0; i < 128; i++) prm.map[i] = remap(i);
  {
    const uint64_t hi = 0x80000020ull << 32, k0 = sbase + T0, v0 = k0 + 16384, vstep = 64 - (64ull << 16);
    prm.wd = mkdesc(sbase + 32768, 8192, 1024, 1); prm.xd = mkdesc(sbase, 16, 1024, 1);
    for (int j = 0; j < 4; j++) {
      prm.kv[j].kd = (hi | 1u << 16 | k0 >> 4) + 2048 * ((j < 16 ? j : 15) & 3);
      prm.kv[j].vd = (hi | (uint64_t)(ONES - T0 - 16384) >> 4 << 16 | v0 >> 4) + 32 * vstep * ((j + 3) & 3);
    }
  }
  fused_kernel<<<128, 384, SMEM_BYTES>>>(prm);
}
```

```cpp
#include <cuda_runtime.h>
#include <cuda_bf16.h>
#include <cuda.h>
#include <stdint.h>

typedef __nv_bfloat16 bf16;

__device__ __forceinline__ void wgmma_m64n192k16_ss_tb(float (&d)[96], uint64_t da, uint64_t db, int scale_d) {
  asm volatile("{\n.reg .pred p;\nsetp.ne.b32 p, %98, 0;\n"
    "wgmma.mma_async.sync.aligned.m64n192k16.f32.bf16.bf16 "
    "{%0, %1, %2, %3, %4, %5, %6, %7, %8, %9, %10, %11, %12, %13, %14, %15, "
    "%16, %17, %18, %19, %20, %21, %22, %23, %24, %25, %26, %27, %28, %29, %30, %31, "
    "%32, %33, %34, %35, %36, %37, %38, %39, %40, %41, %42, %43, %44, %45, %46, %47, "
    "%48, %49, %50, %51, %52, %53, %54, %55, %56, %57, %58, %59, %60, %61, %62, %63, "
    "%64, %65, %66, %67, %68, %69, %70, %71, %72, %73, %74, %75, %76, %77, %78, %79, "
    "%80, %81, %82, %83, %84, %85, %86, %87, %88, %89, %90, %91, %92, %93, %94, %95}, "
    "%96, %97, p, 1, 1, 0, 1;\n}\n"
    : "+f"(d[0]), "+f"(d[1]), "+f"(d[2]), "+f"(d[3]), "+f"(d[4]), "+f"(d[5]), "+f"(d[6]), "+f"(d[7]),
      "+f"(d[8]), "+f"(d[9]), "+f"(d[10]), "+f"(d[11]), "+f"(d[12]), "+f"(d[13]), "+f"(d[14]), "+f"(d[15]),
      "+f"(d[16]), "+f"(d[17]), "+f"(d[18]), "+f"(d[19]), "+f"(d[20]), "+f"(d[21]), "+f"(d[22]), "+f"(d[23]),
      "+f"(d[24]), "+f"(d[25]), "+f"(d[26]), "+f"(d[27]), "+f"(d[28]), "+f"(d[29]), "+f"(d[30]), "+f"(d[31]),
      "+f"(d[32]), "+f"(d[33]), "+f"(d[34]), "+f"(d[35]), "+f"(d[36]), "+f"(d[37]), "+f"(d[38]), "+f"(d[39]),
      "+f"(d[40]), "+f"(d[41]), "+f"(d[42]), "+f"(d[43]), "+f"(d[44]), "+f"(d[45]), "+f"(d[46]), "+f"(d[47]),
      "+f"(d[48]), "+f"(d[49]), "+f"(d[50]), "+f"(d[51]), "+f"(d[52]), "+f"(d[53]), "+f"(d[54]), "+f"(d[55]),
      "+f"(d[56]), "+f"(d[57]), "+f"(d[58]), "+f"(d[59]), "+f"(d[60]), "+f"(d[61]), "+f"(d[62]), "+f"(d[63]),
      "+f"(d[64]), "+f"(d[65]), "+f"(d[66]), "+f"(d[67]), "+f"(d[68]), "+f"(d[69]), "+f"(d[70]), "+f"(d[71]),
      "+f"(d[72]), "+f"(d[73]), "+f"(d[74]), "+f"(d[75]), "+f"(d[76]), "+f"(d[77]), "+f"(d[78]), "+f"(d[79]),
      "+f"(d[80]), "+f"(d[81]), "+f"(d[82]), "+f"(d[83]), "+f"(d[84]), "+f"(d[85]), "+f"(d[86]), "+f"(d[87]),
      "+f"(d[88]), "+f"(d[89]), "+f"(d[90]), "+f"(d[91]), "+f"(d[92]), "+f"(d[93]), "+f"(d[94]), "+f"(d[95])
    : "l"(da), "l"(db), "r"(scale_d));
}

__device__ __forceinline__ void wgmma_m64n128k16_ss_tb(float (&d)[64], uint64_t da, uint64_t db, int scale_d) {
  asm volatile("{\n.reg .pred p;\nsetp.ne.b32 p, %66, 0;\n"
    "wgmma.mma_async.sync.aligned.m64n128k16.f32.bf16.bf16 "
    "{%0, %1, %2, %3, %4, %5, %6, %7, %8, %9, %10, %11, %12, %13, %14, %15, "
    "%16, %17, %18, %19, %20, %21, %22, %23, %24, %25, %26, %27, %28, %29, %30, %31, "
    "%32, %33, %34, %35, %36, %37, %38, %39, %40, %41, %42, %43, %44, %45, %46, %47, "
    "%48, %49, %50, %51, %52, %53, %54, %55, %56, %57, %58, %59, %60, %61, %62, %63}, "
    "%64, %65, p, 1, 1, 0, 1;\n}\n"
    : "+f"(d[0]), "+f"(d[1]), "+f"(d[2]), "+f"(d[3]), "+f"(d[4]), "+f"(d[5]), "+f"(d[6]), "+f"(d[7]),
      "+f"(d[8]), "+f"(d[9]), "+f"(d[10]), "+f"(d[11]), "+f"(d[12]), "+f"(d[13]), "+f"(d[14]), "+f"(d[15]),
      "+f"(d[16]), "+f"(d[17]), "+f"(d[18]), "+f"(d[19]), "+f"(d[20]), "+f"(d[21]), "+f"(d[22]), "+f"(d[23]),
      "+f"(d[24]), "+f"(d[25]), "+f"(d[26]), "+f"(d[27]), "+f"(d[28]), "+f"(d[29]), "+f"(d[30]), "+f"(d[31]),
      "+f"(d[32]), "+f"(d[33]), "+f"(d[34]), "+f"(d[35]), "+f"(d[36]), "+f"(d[37]), "+f"(d[38]), "+f"(d[39]),
      "+f"(d[40]), "+f"(d[41]), "+f"(d[42]), "+f"(d[43]), "+f"(d[44]), "+f"(d[45]), "+f"(d[46]), "+f"(d[47]),
      "+f"(d[48]), "+f"(d[49]), "+f"(d[50]), "+f"(d[51]), "+f"(d[52]), "+f"(d[53]), "+f"(d[54]), "+f"(d[55]),
      "+f"(d[56]), "+f"(d[57]), "+f"(d[58]), "+f"(d[59]), "+f"(d[60]), "+f"(d[61]), "+f"(d[62]), "+f"(d[63])
    : "l"(da), "l"(db), "r"(scale_d));
}

__device__ __forceinline__ void wgmma_m64n40k16_rs_tb(float (&d)[20], uint32_t a0, uint32_t a1, uint32_t a2, uint32_t a3, uint64_t db, int scale_d) {
  asm volatile("{\n.reg .pred p;\nsetp.ne.b32 p, %25, 0;\n"
    "wgmma.mma_async.sync.aligned.m64n40k16.f32.bf16.bf16 "
    "{%0, %1, %2, %3, %4, %5, %6, %7, %8, %9, %10, %11, %12, %13, %14, %15, "
    "%16, %17, %18, %19}, "
    "{%20, %21, %22, %23}, %24, p, 1, 1, 1;\n}\n"
    : "+f"(d[0]), "+f"(d[1]), "+f"(d[2]), "+f"(d[3]), "+f"(d[4]), "+f"(d[5]), "+f"(d[6]), "+f"(d[7]),
      "+f"(d[8]), "+f"(d[9]), "+f"(d[10]), "+f"(d[11]), "+f"(d[12]), "+f"(d[13]), "+f"(d[14]), "+f"(d[15]),
      "+f"(d[16]), "+f"(d[17]), "+f"(d[18]), "+f"(d[19])
    : "r"(a0), "r"(a1), "r"(a2), "r"(a3), "l"(db), "r"(scale_d));
}

__device__ __forceinline__ void wg_n64_rs_nb_f16_f32(float (&d)[32], uint32_t a0, uint32_t a1, uint32_t a2, uint32_t a3, uint64_t db, int scale_d) {
  asm volatile("{\n.reg .pred p;\nsetp.ne.b32 p, %37, 0;\n"
    "wgmma.mma_async.sync.aligned.m64n64k16.f32.f16.f16 "
    "{%0, %1, %2, %3, %4, %5, %6, %7, %8, %9, %10, %11, %12, %13, %14, %15, "
    "%16, %17, %18, %19, %20, %21, %22, %23, %24, %25, %26, %27, %28, %29, %30, %31}, "
    "{%32, %33, %34, %35}, %36, p, 1, 1, 0;\n}\n"
    : "+f"(d[0]), "+f"(d[1]), "+f"(d[2]), "+f"(d[3]), "+f"(d[4]), "+f"(d[5]), "+f"(d[6]), "+f"(d[7]),
      "+f"(d[8]), "+f"(d[9]), "+f"(d[10]), "+f"(d[11]), "+f"(d[12]), "+f"(d[13]), "+f"(d[14]), "+f"(d[15]),
      "+f"(d[16]), "+f"(d[17]), "+f"(d[18]), "+f"(d[19]), "+f"(d[20]), "+f"(d[21]), "+f"(d[22]), "+f"(d[23]),
      "+f"(d[24]), "+f"(d[25]), "+f"(d[26]), "+f"(d[27]), "+f"(d[28]), "+f"(d[29]), "+f"(d[30]), "+f"(d[31])
    : "r"(a0), "r"(a1), "r"(a2), "r"(a3), "l"(db), "r"(scale_d));
}

__device__ __forceinline__ void wg_n64_rs_nb_f16_f16(uint32_t (&d)[16], uint32_t a0, uint32_t a1, uint32_t a2, uint32_t a3, uint64_t db, int scale_d) {
  asm volatile("{\n.reg .pred p;\nsetp.ne.b32 p, %21, 0;\n"
    "wgmma.mma_async.sync.aligned.m64n64k16.f16.f16.f16 "
    "{%0, %1, %2, %3, %4, %5, %6, %7, %8, %9, %10, %11, %12, %13, %14, %15}, "
    "{%16, %17, %18, %19}, %20, p, 1, 1, 0;\n}\n"
    : "+r"(d[0]), "+r"(d[1]), "+r"(d[2]), "+r"(d[3]), "+r"(d[4]), "+r"(d[5]), "+r"(d[6]), "+r"(d[7]),
      "+r"(d[8]), "+r"(d[9]), "+r"(d[10]), "+r"(d[11]), "+r"(d[12]), "+r"(d[13]), "+r"(d[14]), "+r"(d[15])
    : "r"(a0), "r"(a1), "r"(a2), "r"(a3), "l"(db), "r"(scale_d));
}

__device__ __forceinline__ void wg_n64_rs_nb_f16_f32_z(float (&d)[32], uint32_t a0, uint32_t a1, uint32_t a2, uint32_t a3, uint64_t db, int scale_d) {
  asm volatile("{\n.reg .pred p;\nsetp.ne.b32 p, %37, 0;\n"
    "wgmma.mma_async.sync.aligned.m64n64k16.f32.f16.f16 "
    "{%0, %1, %2, %3, %4, %5, %6, %7, %8, %9, %10, %11, %12, %13, %14, %15, "
    "%16, %17, %18, %19, %20, %21, %22, %23, %24, %25, %26, %27, %28, %29, %30, %31}, "
    "{%32, %33, %34, %35}, %36, p, 1, 1, 0;\n}\n"
    : "=f"(d[0]), "=f"(d[1]), "=f"(d[2]), "=f"(d[3]), "=f"(d[4]), "=f"(d[5]), "=f"(d[6]), "=f"(d[7]),
      "=f"(d[8]), "=f"(d[9]), "=f"(d[10]), "=f"(d[11]), "=f"(d[12]), "=f"(d[13]), "=f"(d[14]), "=f"(d[15]),
      "=f"(d[16]), "=f"(d[17]), "=f"(d[18]), "=f"(d[19]), "=f"(d[20]), "=f"(d[21]), "=f"(d[22]), "=f"(d[23]),
      "=f"(d[24]), "=f"(d[25]), "=f"(d[26]), "=f"(d[27]), "=f"(d[28]), "=f"(d[29]), "=f"(d[30]), "=f"(d[31])
    : "r"(a0), "r"(a1), "r"(a2), "r"(a3), "l"(db), "r"(scale_d));
}

__device__ __forceinline__ void wg_n64_rs_nb_f16_f16_z(uint32_t (&d)[16], uint32_t a0, uint32_t a1, uint32_t a2, uint32_t a3, uint64_t db, int scale_d) {
  asm volatile("{\n.reg .pred p;\nsetp.ne.b32 p, %21, 0;\n"
    "wgmma.mma_async.sync.aligned.m64n64k16.f16.f16.f16 "
    "{%0, %1, %2, %3, %4, %5, %6, %7, %8, %9, %10, %11, %12, %13, %14, %15}, "
    "{%16, %17, %18, %19}, %20, p, 1, 1, 0;\n}\n"
    : "=r"(d[0]), "=r"(d[1]), "=r"(d[2]), "=r"(d[3]), "=r"(d[4]), "=r"(d[5]), "=r"(d[6]), "=r"(d[7]),
      "=r"(d[8]), "=r"(d[9]), "=r"(d[10]), "=r"(d[11]), "=r"(d[12]), "=r"(d[13]), "=r"(d[14]), "=r"(d[15])
    : "r"(a0), "r"(a1), "r"(a2), "r"(a3), "l"(db), "r"(scale_d));
}

#define DEVINL __device__ __forceinline__
DEVINL void wg_fence() { asm volatile("wgmma.fence.sync.aligned;" ::: "memory"); }
DEVINL void wg_commit() { asm volatile("wgmma.commit_group.sync.aligned;" ::: "memory"); }
template <int N> DEVINL void wg_wait() { asm volatile("wgmma.wait_group.sync.aligned %0;" ::"n"(N) : "memory"); }
__host__ DEVINL uint64_t mkdesc(uint32_t addr, uint32_t lbo, uint32_t sbo, int sw) {
  return (uint64_t)((addr & 0x3FFFF) >> 4) | ((uint64_t)(lbo >> 4) << 16) | ((uint64_t)(sbo >> 4) << 32) | ((uint64_t)sw << 62);
}
DEVINL void mbar_init(uint32_t bar, uint32_t cnt) { asm volatile("mbarrier.init.shared::cta.b64 [%0], %1;" ::"r"(bar), "r"(cnt) : "memory"); }
DEVINL void mbar_arrive(uint32_t bar) { asm volatile("mbarrier.arrive.shared::cta.b64 _, [%0];" ::"r"(bar) : "memory"); }
DEVINL bool mbar_try(uint32_t bar, uint32_t parity) {
  uint32_t ok;
  asm volatile("{\n.reg .pred p;\nmbarrier.try_wait.parity.shared::cta.b64 p, [%1], %2;\nselp.u32 %0, 1, 0, p;\n}" : "=r"(ok) : "r"(bar), "r"(parity) : "memory");
  return ok;
}
DEVINL bool mbar_test(uint32_t bar, uint32_t parity) {
  uint32_t ok;
  asm volatile("{\n.reg .pred p;\nmbarrier.test_wait.parity.shared::cta.b64 p, [%1], %2;\nselp.u32 %0, 1, 0, p;\n}" : "=r"(ok) : "r"(bar), "r"(parity) : "memory");
  return ok;
}
DEVINL void mbar_wait(uint32_t bar, uint32_t parity) {
#pragma unroll 1
  for (uint32_t n = 0; n < 100000u; n++) if (mbar_try(bar, parity)) break;
}
#define EL(txt) "{\n.reg .pred pe;\nelect.sync _|pe, 0xffffffff;\n@pe " txt "\n}"
DEVINL void e_expect_tx(uint32_t bar, uint32_t bytes) { asm volatile(EL("mbarrier.arrive.expect_tx.shared::cta.b64 _, [%0], %1;") ::"r"(bar), "r"(bytes) : "memory"); }
DEVINL void e_arrive(uint32_t bar) { asm volatile(EL("mbarrier.arrive.shared::cta.b64 _, [%0];") ::"r"(bar) : "memory"); }
DEVINL void e_arrive_if(uint32_t bar, int c) {
  asm volatile("{\n.reg .pred pe;\nelect.sync _|pe, 0xffffffff;\nsetp.ne.and.b32 pe, %1, 0, pe;\n@pe mbarrier.arrive.shared::cta.b64 _, [%0];\n}" ::"r"(bar), "r"(c) : "memory");
}
DEVINL void e_red(uint32_t* p) { asm volatile(EL("red.release.gpu.global.add.u32 [%0], 1;") ::"l"(p) : "memory"); }
DEVINL void e_red_relaxed(uint32_t* p) { asm volatile(EL("red.relaxed.gpu.global.add.u32 [%0], 1;") ::"l"(p) : "memory"); }
DEVINL void tma_ld(uint32_t dst, const CUtensorMap* m, int c0, int c1, uint32_t bar) {
  asm volatile(EL("cp.async.bulk.tensor.2d.shared::cluster.global.mbarrier::complete_tx::bytes [%0], [%1, {%3, %4}], [%2];")
               ::"r"(dst), "l"(m), "r"(bar), "r"(c0), "r"(c1) : "memory");
}
DEVINL void tma_ld3(uint32_t dst, const CUtensorMap* m, int c0, int c1, int c2, uint32_t bar) {
  asm volatile(EL("cp.async.bulk.tensor.3d.shared::cluster.global.mbarrier::complete_tx::bytes [%0], [%1, {%3, %4, %5}], [%2];")
               ::"r"(dst), "l"(m), "r"(bar), "r"(c0), "r"(c1), "r"(c2) : "memory");
}
DEVINL void tma_ld5(uint32_t dst, const CUtensorMap* m, int c2, int c3, int c4, uint32_t bar) {
  asm volatile(EL("cp.async.bulk.tensor.5d.shared::cluster.global.mbarrier::complete_tx::bytes [%0], [%1, {0, 0, %3, %4, %5}], [%2];")
               ::"r"(dst), "l"(m), "r"(bar), "r"(c2), "r"(c3), "r"(c4) : "memory");
}
DEVINL void tma_ld_mc(uint32_t dst, const CUtensorMap* m, int c0, int c1, uint32_t bar) {
  asm volatile(EL("cp.async.bulk.tensor.2d.shared::cluster.global.mbarrier::complete_tx::bytes.multicast::cluster [%0], [%1, {%3, %4}], [%2], %5;")
               ::"r"(dst), "l"(m), "r"(bar), "r"(c0), "r"(c1), "h"((uint16_t)3) : "memory");
}
DEVINL void e_arrive_both(uint32_t bar) {
  asm volatile("{\n.reg .pred pe;\n.reg .b32 r0, r1;\nelect.sync _|pe, 0xffffffff;\nmapa.shared::cluster.u32 r0, %0, 0;\nmapa.shared::cluster.u32 r1, %0, 1;\n"
               "@pe mbarrier.arrive.shared::cluster.b64 _, [r0];\n@pe mbarrier.arrive.shared::cluster.b64 _, [r1];\n}" ::"r"(bar) : "memory");
}
DEVINL void tma_st(const CUtensorMap* m, int c0, int c1, uint32_t src) {
  asm volatile(EL("cp.async.bulk.tensor.2d.global.shared::cta.bulk_group [%0, {%2, %3}], [%1];") ::"l"(m), "r"(src), "r"(c0), "r"(c1) : "memory");
}
DEVINL void bulk_commit() { asm volatile("cp.async.bulk.commit_group;" ::: "memory"); }
template <int N> DEVINL void bulk_wait_n() { asm volatile("cp.async.bulk.wait_group %0;\nbar.warp.sync 0xffffffff;" ::"n"(N) : "memory"); }
DEVINL void l2_prefetch(const void* g, uint32_t bytes) { asm volatile(EL("cp.async.bulk.prefetch.L2.global [%0], %1;") ::"l"(g), "r"(bytes) : "memory"); }
DEVINL void fence_async_smem() { asm volatile("fence.proxy.async.shared::cta;" ::: "memory"); }
DEVINL void fence_async_gl() { asm volatile("fence.proxy.async.global;" ::: "memory"); }
DEVINL void cluster_wait() { asm volatile("barrier.cluster.wait.aligned;" ::: "memory"); }
DEVINL void bar_sync(int id, int n) { asm volatile("bar.sync %0, %1;" ::"r"(id), "r"(n) : "memory"); }
DEVINL void bar_arrive(int id, int n) { asm volatile("bar.arrive %0, %1;" ::"r"(id), "r"(n) : "memory"); }
DEVINL uint32_t ld_acquire(const uint32_t* p) { uint32_t v; asm volatile("ld.acquire.gpu.global.u32 %0, [%1];" : "=r"(v) : "l"(p) : "memory"); return v; }
DEVINL void await_flag(int j, uint32_t& rdy, const uint32_t* p, uint32_t target) {
  if ((rdy >> j) & 1) return;
#pragma unroll 1
  for (uint32_t n = 0; n < 200000u && !((rdy >> j) & 1); n++) rdy = __ballot_sync(~0u, (int)(ld_acquire(p) - target) >= 0);
  asm volatile("fence.proxy.async.global;" ::: "memory");
}
DEVINL void poll_ge(const uint32_t* p, uint32_t target) {
#pragma unroll 1
  for (uint32_t n = 0; n < 200000u; n++) if (__all_sync(~0u, (int)(ld_acquire(p) - target) >= 0)) break;
}
DEVINL int lane_id() { int v; asm volatile("mov.u32 %0, %%laneid;" : "=r"(v)); return v; }
__host__ DEVINL int remap(int v) {
  const int c = v >> 1, u = c - 36, r = (u * 37) >> 8;
  const int L = c < 4 ? 32 + 8 * c : c < 36 ? c - 4 : 33 + u + r;
  return 2 * L + (v & 1);
}
DEVINL int block_id() { int v; asm volatile("mov.u32 %0, %%ctaid.x;" : "=r"(v)); return v; }
#define cta_id() prm.map[block_id()]
#define IDS() const int lane = lane_id(), b = cta_id(), bm = b >> 4, bn = b & 15, rank = b & 1, pm = 2 * bm + (bn >> 3), pn = bn & 7, po = pm & 1; \
  (void)lane; (void)bm; (void)bn; (void)rank; (void)pm; (void)pn; (void)po
DEVINL void st_tagged(uint4* p, uint32_t a, uint32_t b, uint32_t c, uint32_t tag) {
  asm volatile("{\n.reg .b64 u, v;\n.reg .b128 t;\nmov.b64 u, {%1, %2};\nmov.b64 v, {%3, %4};\nmov.b128 t, {u, v};\nst.relaxed.gpu.global.b128 [%0], t;\n}"
               ::"l"(p), "r"(a), "r"(b), "r"(c), "r"(tag) : "memory");
}
DEVINL uint32_t ld_tagged(const uint4* p, uint32_t* r) {
  uint32_t tag;
  asm volatile("{\n.reg .b64 u, v;\n.reg .b128 t;\nld.relaxed.gpu.global.b128 t, [%4];\nmov.b128 {u, v}, t;\nmov.b64 {%0, %1}, u;\nmov.b64 {%2, %3}, v;\n}"
               : "=r"(r[0]), "=r"(r[1]), "=r"(r[2]), "=r"(tag) : "l"(p) : "memory");
  return tag;
}
DEVINL float ex2(float x) { float y; asm("ex2.approx.ftz.f32 %0, %1;" : "=f"(y) : "f"(x)); return y; }
DEVINL float rcp(float x) { float y; asm("rcp.approx.ftz.f32 %0, %1;" : "=f"(y) : "f"(x)); return y; }
DEVINL uint32_t pack2(float lo, float hi) { uint32_t r; asm("cvt.rn.bf16x2.f32 %0, %1, %2;" : "=r"(r) : "f"(hi), "f"(lo)); return r; }
DEVINL uint32_t pack2h(float lo, float hi) { uint32_t r; asm("cvt.rn.f16x2.f32 %0, %1, %2;" : "=r"(r) : "f"(hi), "f"(lo)); return r; }
DEVINL uint32_t prmt0(uint32_t a, uint32_t sel) { uint32_t r; asm("prmt.b32 %0, %1, 0, %2;" : "=r"(r) : "r"(a), "r"(sel)); return r; }
DEVINL void stg128(const void* p, uint32_t a, uint32_t b, uint32_t c, uint32_t d) {
  asm volatile("st.global.v4.b32 [%0], {%1, %2, %3, %4};" ::"l"(p), "r"(a), "r"(b), "r"(c), "r"(d) : "memory");
}
DEVINL float bf_lo(uint32_t w) { return __uint_as_float(w << 16); }
DEVINL float bf_hi(uint32_t w) { return __uint_as_float(w & 0xFFFF0000u); }
DEVINL float bf_round(float x) { return bf_lo(pack2(x, 0.f)); }
DEVINL uint32_t add_bf16x2(uint32_t a, uint32_t b) { uint32_t r; asm("add.rn.bf16x2 %0, %1, %2;" : "=r"(r) : "r"(a), "r"(b)); return r; }
DEVINL void stsm4(uint32_t addr, uint32_t a, uint32_t b, uint32_t c, uint32_t d) {
  asm volatile("stmatrix.sync.aligned.m8n8.x4.shared.b16 [%0], {%1, %2, %3, %4};" ::"r"(addr), "r"(a), "r"(b), "r"(c), "r"(d) : "memory");
}
DEVINL void ldsm4(uint32_t addr, uint32_t (&r)[4]) {
  asm volatile("ldmatrix.sync.aligned.m8n8.x4.shared.b16 {%0, %1, %2, %3}, [%4];" : "=r"(r[0]), "=r"(r[1]), "=r"(r[2]), "=r"(r[3]) : "r"(addr) : "memory");
}
DEVINL void ldsm4t(uint32_t addr, uint32_t (&r)[4]) {
  asm volatile("ldmatrix.sync.aligned.m8n8.x4.trans.shared.b16 {%0, %1, %2, %3}, [%4];" : "=r"(r[0]), "=r"(r[1]), "=r"(r[2]), "=r"(r[3]) : "r"(addr) : "memory");
}
DEVINL void sts128(uint32_t addr, uint32_t a, uint32_t b, uint32_t c, uint32_t d) {
  asm volatile("st.shared.v4.b32 [%0], {%1, %2, %3, %4};" ::"r"(addr), "r"(a), "r"(b), "r"(c), "r"(d) : "memory");
}
DEVINL float2 lds64f(uint32_t addr) { float2 v; asm volatile("ld.shared.v2.f32 {%0, %1}, [%2];" : "=f"(v.x), "=f"(v.y) : "r"(addr) : "memory"); return v; }
DEVINL void mma16816(float (&d)[4], uint32_t a0, uint32_t a1, uint32_t a2, uint32_t a3, uint32_t b0, uint32_t b1) {
  asm("mma.sync.aligned.m16n8k16.row.col.f32.bf16.bf16.f32 {%0, %1, %2, %3}, {%4, %5, %6, %7}, {%8, %9}, {%0, %1, %2, %3};"
               : "+f"(d[0]), "+f"(d[1]), "+f"(d[2]), "+f"(d[3]) : "r"(a0), "r"(a1), "r"(a2), "r"(a3), "r"(b0), "r"(b1));
}
template <int N> DEVINL void fence_regs(float (&d)[N]) {
#pragma unroll
  for (int i = 0; i < N; i++) asm volatile("" : "+f"(d[i])::"memory");
}
template <int N> DEVINL void fence_regs(uint32_t (&d)[N]) {
#pragma unroll
  for (int i = 0; i < N; i++) asm volatile("" : "+r"(d[i])::"memory");
}
DEVINL void lds128(uint32_t addr, uint32_t* r) {
  asm volatile("ld.shared.v4.b32 {%0, %1, %2, %3}, [%4];" : "=r"(r[0]), "=r"(r[1]), "=r"(r[2]), "=r"(r[3]) : "r"(addr) : "memory");
}
DEVINL void sched_fence() { asm volatile("griddepcontrol.launch_dependents;" ::: "memory"); }

struct Scratch {
  bf16 k[32 * 2048 * 32];
  bf16 xs[2048 * 1024];
  bf16 os[2048 * 1024];
  bf16 v[32 * 2048 * 32];
  float kn[2 * 128 * 16];
  uint32_t cnt[256 * 32];
  float2 stats[8 * 2048];
  uint4 halo[2 * 128 * 12 * 32];
  float csp[2 * 16 * 8 * 192];
  uint4 qsave[128 * 256 * 8];
  uint32_t esc[4 * 65536 * 20];
};
__device__ __align__(1024) Scratch g_s;
#define g_k g_s.k
#define g_xs g_s.xs
#define g_os g_s.os
#define g_v g_s.v
#define g_kn g_s.kn
#define g_cnt g_s.cnt
#define g_stats g_s.stats
#define g_halo g_s.halo
#define g_csp g_s.csp
#define g_qsave g_s.qsave
#define g_esc g_s.esc
#define g_epoch g_s.cnt[255 * 32]

DEVINL uint32_t* cnt_x(int l, int bm) { return g_cnt + (l * 8 + bm) * 32; }
DEVINL uint32_t* cnt_o(int l, int pm, int h) { return g_cnt + (32 + (l * 16 + pm) * 2 + h) * 32; }
DEVINL uint32_t* cnt_kv(int lb, int bn) { return g_cnt + (160 + lb * 16 + bn) * 32; }
DEVINL uint32_t* cnt_ad(int bn) { return g_cnt + (192 + bn) * 32; }
DEVINL uint32_t* cnt_cs(int t, int bn) { return g_cnt + (208 + t * 16 + bn) * 32; }

DEVINL int qord(int i, int l, int pn) { return l == 0 ? i : i < 4 ? ((2 * pn) ^ (i & 2)) + (i & 1) : i - 4 < 2 * (pn & 6) ? i - 4 : i; }
struct Params {
  CUtensorMap m[15];
  const bf16* x0;
  const bf16* wq[2];
  uint32_t zero;
  int map[128];
  uint64_t wd, xd;
  struct __align__(16) { uint64_t kd, vd; } kv[4];
};
enum { M_X0A = 0, M_XSA, M_WQA, M_WQB, M_WOA, M_WOB, M_OS, M_K, M_V, M_X0R, M_XSR, M_XSO, M_OUT, M_XST, M_X0H, M_COUNT };

constexpr uint32_t QSTG = 57344;
constexpr uint32_t T0 = 65536, TSTG = 32768;
constexpr uint32_t ONES = 230400;
constexpr uint32_t PSTG = 32768, RES = 196608;
constexpr uint32_t KSC = 98304, VSC = 133120, HRS = 167936;
constexpr uint32_t ROWST = 229376, COLS = 231424, BARS = 232192, SMEM_BYTES = 232448;
constexpr uint32_t B_QF = BARS, B_QE = BARS + 32, B_TF = BARS + 64, B_TE = BARS + 96, B_PF = BARS + 128, B_PE = BARS + 176,
                   B_RF = BARS + 224, W_X = BARS + 232, B_QL = BARS + 240, B_PA = BARS + 248;
enum { NB_ST = 1, NB_KV = 2  , NB_DONE = 3, NB_SC = 4, NB_SIG = 5  , NB_KN = 9  , NB_X = 11, NB_HALO = 12  , NB_X0 = 15 };

DEVINL uint32_t pslot_b(uint32_t s) { return ((0x320415u >> (4 * s)) & 7) * 16384u; }
DEVINL uint32_t pslot_a(uint32_t s, int l) { return 98304u + ((((l & 1) ? 0x541230u : 0x041235u) >> (4 * s)) & 7) * 16384u; }

constexpr float QSCALE = 0.17677669529663687f * 1.4426950408889634f;
constexpr uint32_t QPARK = 32768;

DEVINL uint32_t exp2_h2(uint32_t s, uint32_t c882) {
  uint32_t r, t, w, m, d;
  asm volatile("{.reg .b64 t; add.rn.f16x2 %0, %1, %2; cvt.u64.u32 t, %0; cvt.u32.u64 %0, t;}" : "=r"(r) : "r"(s), "r"(0x65F565F5u));
  asm volatile("fma.rn.f16x2 %0, %1, %2, %3;" : "=r"(t) : "r"(r), "r"(0xB8A0B8A0u), "r"(c882));
  asm volatile("fma.rn.f16x2 %0, %1, %2, %3;" : "=r"(w) : "r"(s), "r"(0x38A038A0u), "r"(t));
  asm volatile("fma.rn.f16x2 %0, %1, %1, %2;" : "=r"(m) : "r"(w), "r"(0x48244833u));
  asm volatile("{.reg .b32 t; shf.l.clamp.b32 t, %2, %1, 7; add.u32 %0, t, %2;}" : "=r"(d) : "r"(r), "r"(m));
  return d;
}
DEVINL float exp2_fix(float s) { float z; asm volatile("add.rn.f32 %0, %1, 0f43BF34BC;" : "=f"(z) : "f"(s)); return z; }
DEVINL uint32_t exp2_base(float z0, float z1) { uint32_t B; asm volatile("prmt.b32 %0, %1, %2, 0x6521;" : "=r"(B) : "r"(__float_as_uint(z0)), "r"(__float_as_uint(z1))); return B; }
template <uint32_t MASK> DEVINL uint32_t and_or(uint32_t a, uint32_t c) { uint32_t r; asm volatile("lop3.b32 %0, %1, %3, %2, 0xEA;" : "=r"(r) : "r"(a), "r"(c), "n"(MASK)); return r; }
DEVINL uint32_t fma_bf2(uint32_t a, uint32_t b, uint32_t c) { uint32_t r; asm volatile("fma.rn.bf16x2 %0, %1, %2, %3;" : "=r"(r) : "r"(a), "r"(b), "r"(c)); return r; }
DEVINL float ex2v(float x) { float y; asm volatile("ex2.approx.ftz.f32 %0, %1;" : "=f"(y) : "f"(x)); return y; }
DEVINL uint32_t pack2v(float lo, float hi) { uint32_t r; asm volatile("cvt.rn.bf16x2.f32 %0, %1, %2;" : "=r"(r) : "f"(hi), "f"(lo)); return r; }
DEVINL void unesc(uint32_t (&u)[4], const uint32_t* esc, uint32_t tag) {
  const bool saved = __ldcg(esc + 16) == tag;
#pragma unroll
  for (int j = 0; j < 4; j++) {
    float lo, hi;
    asm("{.reg .f16 a, b; mov.b32 {a, b}, %2; cvt.f32.f16 %0, a; cvt.f32.f16 %1, b;}" : "=f"(lo), "=f"(hi) : "r"(u[j]));
    u[j] = saved ? __ldcg(esc + 4 * j) : pack2(lo, hi);
  }
}

DEVINL void attn_slow(const uint32_t (&q)[8], int head, const uint32_t* kesc, uint32_t tag, float (&res)[20], int lane) {
  const int g = lane >> 2, qd = lane & 3;
  const bf16* kb = g_k + (size_t)head * 2048 * 32;
  const bf16* vb = g_v + (size_t)head * 2048 * 32;
  float o[4][4], m0 = -INFINITY, m1 = -INFINITY, l0 = 0.f, l1 = 0.f;
#pragma unroll
  for (int j = 0; j < 4; j++) { o[j][0] = o[j][1] = o[j][2] = o[j][3] = 0.f; }
#pragma unroll 1
  for (int k0 = 0; k0 < 2048; k0 += 16) {
    float s[2][4];
#pragma unroll
    for (int nt = 0; nt < 2; nt++) {
      s[nt][0] = s[nt][1] = s[nt][2] = s[nt][3] = 0.f;
      const uint32_t* kp = (const uint32_t*)(kb + (size_t)(k0 + nt * 8 + g) * 32) + qd;
      uint32_t k[4] = {__ldcg(kp), __ldcg(kp + 4), __ldcg(kp + 8), __ldcg(kp + 12)};
      unesc(k, kesc + (k0 + nt * 8 + g) * 20 + qd, tag);
      __syncwarp();
      mma16816(s[nt], q[0], q[1], q[2], q[3], k[0], k[1]);
      mma16816(s[nt], q[4], q[5], q[6], q[7], k[2], k[3]);
    }
    float a0 = fmaxf(fmaxf(s[0][0], s[0][1]), fmaxf(s[1][0], s[1][1]));
    float a1 = fmaxf(fmaxf(s[0][2], s[0][3]), fmaxf(s[1][2], s[1][3]));
    a0 = fmaxf(a0, __shfl_xor_sync(~0u, a0, 1)); a0 = fmaxf(a0, __shfl_xor_sync(~0u, a0, 2));
    a1 = fmaxf(a1, __shfl_xor_sync(~0u, a1, 1)); a1 = fmaxf(a1, __shfl_xor_sync(~0u, a1, 2));
    const float n0 = fmaxf(m0, a0), n1 = fmaxf(m1, a1);
    const float c0 = (m0 == n0) ? 1.f : ex2(m0 - n0), c1 = (m1 == n1) ? 1.f : ex2(m1 - n1);
    m0 = n0; m1 = n1;
    const uint32_t p0 = pack2(ex2(s[0][0] - n0), ex2(s[0][1] - n0)), p1 = pack2(ex2(s[0][2] - n1), ex2(s[0][3] - n1));
    const uint32_t p2 = pack2(ex2(s[1][0] - n0), ex2(s[1][1] - n0)), p3 = pack2(ex2(s[1][2] - n1), ex2(s[1][3] - n1));
    l0 = l0 * c0 + bf_lo(p0) + bf_hi(p0) + bf_lo(p2) + bf_hi(p2);
    l1 = l1 * c1 + bf_lo(p1) + bf_hi(p1) + bf_lo(p3) + bf_hi(p3);
#pragma unroll
    for (int j = 0; j < 4; j++) {
      o[j][0] *= c0; o[j][1] *= c0; o[j][2] *= c1; o[j][3] *= c1;
      const unsigned short* vp = (const unsigned short*)(vb + (size_t)(k0 + 2 * qd) * 32 + j * 8 + g);
      const uint32_t b0 = (uint32_t)__ldcg(vp) | ((uint32_t)__ldcg(vp + 32) << 16);
      const uint32_t b1 = (uint32_t)__ldcg(vp + 256) | ((uint32_t)__ldcg(vp + 288) << 16);
      mma16816(o[j], p0, p1, p2, p3, b0, b1);
    }
  }
  l0 += __shfl_xor_sync(~0u, l0, 1); l0 += __shfl_xor_sync(~0u, l0, 2);
  l1 += __shfl_xor_sync(~0u, l1, 1); l1 += __shfl_xor_sync(~0u, l1, 2);
#pragma unroll
  for (int j = 0; j < 4; j++) { res[4 * j] = o[j][0]; res[4 * j + 1] = o[j][1]; res[4 * j + 2] = o[j][2]; res[4 * j + 3] = o[j][3]; }
  res[16] = l0; res[18] = l1;
}

__device__ __noinline__ void attn_redo(int redo, int l, int b, int wg, int w, uint32_t tag) {
  const int lane = lane_id();
#pragma unroll 1
  for (int t = 0; t < 4; t++) {
    const int h = t >> 1, head = 2 * (b & 15) + h, row = (b >> 4) * 256 + wg * 128 + (t & 1) * 64 + w * 16 + (lane >> 2);
    if ((redo >> t) & 1) {
      const uint32_t* esc = g_esc + (size_t)((l & 2) * 65536 + head * 2048) * 20;
      const uint32_t* qs = (const uint32_t*)(g_qsave + (block_id() * 256 + wg * 128 + w * 32 + lane) * 8 + 2 * t);
      uint32_t q[8]; float o[20];
#pragma unroll
      for (int i = 0; i < 2; i++) {
        uint32_t u[4] = {__ldcg(qs + i), __ldcg(qs + i + 2), __ldcg(qs + i + 4), __ldcg(qs + i + 6)};
        unesc(u, esc + (row + i * 8) * 20 + (lane & 3), tag);
        q[i] = u[0]; q[i + 2] = u[1]; q[i + 4] = u[2]; q[i + 6] = u[3];
      }
      __syncwarp();
      attn_slow(q, head, esc + 65536 * 20, tag, o, lane);
      const float i0 = rcp(o[16]), i1 = rcp(o[18]);
      bf16* op = g_os + (size_t)row * 1024 + h * 512 + (b & 15) * 32 + (lane & 3) * 8;
      *(uint4*)op = make_uint4(pack2(o[0] * i0, o[1] * i0), pack2(o[4] * i0, o[5] * i0), pack2(o[8] * i0, o[9] * i0), pack2(o[12] * i0, o[13] * i0));
      *(uint4*)(op + 8 * 1024) = make_uint4(pack2(o[2] * i1, o[3] * i1), pack2(o[6] * i1, o[7] * i1), pack2(o[10] * i1, o[11] * i1), pack2(o[14] * i1, o[15] * i1));
    }
    if ((t & 1) && ((redo >> 2 * h) & 3)) bar_arrive(NB_SIG + 2 * h + wg, 160);
  }
}

__global__ void __cluster_dims__(2, 1, 1) __launch_bounds__(384, 1) fused_kernel(const __grid_constant__ Params prm) {
  extern __shared__ __align__(1024) char smem[];
  const uint32_t sb = (uint32_t)__cvta_generic_to_shared(smem);
  const int tid = threadIdx.x, lane = tid & 31;
  const int wg = __shfl_sync(0xffffffffu, tid >> 7, 0);
  const int w = __shfl_sync(0xffffffffu, (tid >> 5) & 3, 0);
  const int bm = remap(blockIdx.x) >> 4, bn = remap(blockIdx.x) & 15;

  auto first_tile = [&](int kt) {
    e_expect_tx(sb + B_QF + 8 * kt, QSTG);
    tma_ld(sb + kt * QSTG, &prm.m[M_X0A], kt * 64, bm * 256, sb + B_QF + 8 * kt);
    tma_ld3(sb + kt * QSTG + 32768, &prm.m[M_WQA], bn * 64, kt * 64, 0, sb + B_QF + 8 * kt);
  };
  auto init4 = [&](uint32_t bar, uint32_t c0, uint32_t c1, uint32_t c2, uint32_t c3) {
    asm volatile("{\n.reg .pred pe;\nelect.sync _|pe, 0xffffffff;\n@pe mbarrier.init.shared::cta.b64 [%0], %1;\n@pe mbarrier.init.shared::cta.b64 [%0+8], %2;\n"
                 "@pe mbarrier.init.shared::cta.b64 [%0+16], %3;\n@pe mbarrier.init.shared::cta.b64 [%0+24], %4;\n@pe fence.mbarrier_init.release.cluster;\n}"
                 ::"r"(bar), "r"(c0), "r"(c1), "r"(c2), "r"(c3) : "memory");
  };
  if (wg < 2) {
    const uint32_t k = wg * 4 + w, lo = (0x1411814u >> (4 * k)) & 15, hi = (0x1441814u >> (4 * k)) & 15;
    if (tid < 32) asm volatile("prefetch.global.L2 [%0];" ::"l"(prm.x0 + (size_t)(bm * 256 + bn * 16 + (tid & 15)) * 1024 + (tid >> 4) * 64));
    else if (tid < 80) asm volatile("prefetch.global.L2 [%0];" ::"l"(prm.wq[0] + (bm * 16 + (tid & 15)) * 3072 + ((tid >> 4) - 2) * 1024 + bn * 64));
    __syncwarp();
    if (k < 7) init4(sb + B_QE + 32 * k, lo, lo, hi, k == 6 ? 2 : hi);
    __syncwarp();
    if (k == 6 && lane == 0) *(volatile unsigned long long*)(smem + W_X) = 0ull;
  } else if (w == 0) {
    init4(sb + B_QF, 1, 1, 1, 1);
    __syncwarp();
    first_tile(0);
  }
  __syncthreads();
  asm volatile("barrier.cluster.arrive.relaxed.aligned;" ::: "memory");

  if (wg == 2) {
    asm volatile("setmaxnreg.dec.sync.aligned.u32 56;");
    const uint32_t ep1 = *(volatile uint32_t*)&g_epoch + 1;
    if (w == 0) {
      first_tile(1);
      mbar_wait(sb + B_QF, 0);
      first_tile(2); first_tile(3);
#pragma unroll 1
      for (int kt = 4; kt < 16; kt++) l2_prefetch(prm.wq[0] + kt * 196608 + blockIdx.x * 1536, 3072);
      cluster_wait();
#pragma unroll 1
      for (int l = 0; l < 4; l++) {
        IDS();
        const CUtensorMap* mw = &prm.m[M_WQA + (l & 1)];
        const CUtensorMap* mx = &prm.m[l == 0 ? M_X0A : M_XSA];
        const CUtensorMap* mh = &prm.m[l == 0 ? M_X0H : M_XSO];
        const CUtensorMap* mo = &prm.m[M_WOA + (l & 1)];
        auto q_b = [&](int i) {
          const int s = i & 3;
          mbar_wait(sb + B_QE + 8 * s, ((i >> 2) & 1) ^ 1);
          e_expect_tx(sb + B_QF + 8 * s, QSTG);
          tma_ld3(sb + s * QSTG + 32768, mw, bn * 64, qord(i, l, pn) * 64, 0, sb + B_QF + 8 * s);
        };
        uint32_t rdy = l ? 0u : ~0u;
        auto q_a = [&](int i) {
          const int kt = qord(i, l, pn);
          await_flag(kt, rdy, cnt_x(l, bm) + (lane & 15), ep1 * 2);
          if (i < 4) tma_ld(sb + i * QSTG, mx, kt * 64, bm * 256, sb + B_QF + 8 * i);
          else tma_ld_mc(sb + (i & 3) * QSTG + rank * 16384, mh, kt * 64, bm * 256 + rank * 128, sb + B_QF + 8 * (i & 3));
        };
        if (l > 0) {
#pragma unroll 1
          for (int i = 0; i < 2; i++) {
            await_flag(2 * pn + i, rdy, cnt_x(l, bm) + (lane & 15), ep1 * 2);
            e_expect_tx(sb + B_QF + 8 * i, 16384);
            tma_ld(sb + i * QSTG + (po ^ 1) * 16384, &prm.m[M_XSO], (2 * pn + i) * 64, (pm ^ 1) * 128, sb + B_QF + 8 * i);
            if (i == 0) {  q_a(2); }
          }
          mbar_wait(sb + B_QF + 8, 0);
        }
#pragma unroll 1
        for (int i = l ? 3 : 4; i < 16; i++) {
          if (l == 3 && i == 12) poll_ge(cnt_ad(bn), ep1 * 16);
          q_b(i); q_a(i);
        }
        if (l & 1) {
          bar_sync(NB_KV, 288);
          sts128(sb + ONES + lane * 32, 0x3f803f80u, 0x3f803f80u, 0x3f803f80u, 0x3f803f80u);
          sts128(sb + ONES + lane * 32 + 16, 0x3f803f80u, 0x3f803f80u, 0x3f803f80u, 0x3f803f80u);
          fence_async_smem();
          __syncwarp();
          e_arrive(sb + B_TF);
          const int krow = 2 * bn * 2048 + bm * 256;
          uint32_t* kvc = cnt_kv(l >> 1, bn);
          uint32_t seen = 0;
#pragma unroll 1
          for (int it = 1; it < 16; it++) {
            const int s = it & 3;
            if (it == 4) {
              bar_sync(NB_KV + 12, 288);
              mbar_wait(sb + B_TF + 24, 0);
#pragma unroll 1
              for (int i = 0; i < 4; i++) tma_st(&prm.m[M_K + (i >> 1)], 0, krow + 2048 + (i & 1) * 128, sb + i * 8192);
              bulk_commit();
            }
            if (it == 5) { bulk_wait_n<0>(); e_red(kvc + 16 + bm); }
            if (it == 12) { e_expect_tx(sb + B_RF, 32768); tma_ld3(sb + RES, &prm.m[M_XSR], 0, pm * 128, 2 * pn, sb + B_RF); }
            mbar_wait(sb + B_TE + 8 * s, ((it >> 2) & 1) ^ 1);
            if (it < 8) {
#pragma unroll 1
              for (uint32_t n = 0; n < 200000u && (~seen & (3u << (2 * it - 2) | (it == 4 ? 0xC000u : 0u))); n++)
                seen = __ballot_sync(~0u, (int)(ld_acquire(kvc + (lane < 7 || lane == 15 ? (bm + 1 + lane) & 7 : 8 + ((bm + 2 + lane) & 7))) - ep1) >= 0);
              fence_async_gl();
            } else if (it == 8) { poll_ge(kvc + 16 + (lane & 7), ep1); fence_async_gl(); }
            e_expect_tx(sb + B_TF + 8 * s, 32768);
#pragma unroll 1
            for (int i = 0; i < 2; i++) {
              const int u = 2 * it - 2 + i;
              const int row = 2 * bn * 2048 + (it > 7 ? 2048 + ((bm + it) & 7) * 256 + i * 128 : u < 7 ? ((bm + 1 + u) & 7) * 256 : ((bm + 2 + u) & 7) * 256 + 128);
              tma_ld(sb + T0 + s * TSTG + i * 8192, &prm.m[M_K], 0, row, sb + B_TF + 8 * s);
              tma_ld(sb + T0 + s * TSTG + 16384 + i * 8192, &prm.m[M_V], 0, row, sb + B_TF + 8 * s);
            }
          }
        }
        auto p_b = [&](int i, uint32_t s, uint32_t par) {
          mbar_wait(sb + B_PE + 8 * s, par ^ 1);
          e_expect_tx(sb + B_PF + 8 * s, PSTG);
          tma_ld5(sb + pslot_b(s), mo, i >> 3, 2 * (i & 7), 2 * pn, sb + B_PF + 8 * s);
        };
        auto p_a = [&](int i, uint32_t s) {
          await_flag(i, rdy, cnt_o(l, pm, (lane >> 3) & 1) + (lane & 7), ep1 * 2);
          tma_ld_mc(sb + pslot_a(s, l) + rank * 8192, &prm.m[M_OS], i * 64, pm * 128 + rank * 64, sb + B_PF + 8 * s);
        };
        auto p_a2 = [&](int i) {
          await_flag(i, rdy, cnt_o(l, pm, (lane >> 3) & 1) + (lane & 7), ep1 * 2);
          tma_ld(sb + pslot_a(i, l), &prm.m[M_OS], i * 64, pm * 128, sb + B_PF + 8 * i);
          tma_ld(sb + pslot_a(i, l) + 8192, &prm.m[M_OS], i * 64, pm * 128 + 64, sb + B_PF + 8 * i);
        };
        rdy = 0;
        if (l & 1) {
#pragma unroll 1
          for (int u = 0; u < 6; u++) { const int i = (0x205413 >> (4 * u)) & 7; if (u == 4) mbar_wait(sb + B_TE, 1); p_b(i, i, i < 4 ? 1 : 0); }
#pragma unroll 1
          for (int u = 0; u < 6; u++) {
            const int i = (0x542130 >> (4 * u)) & 7;
            if (!(u & 1)) mbar_wait(sb + B_TE + 8 + 4 * u, 1);
            if (u == 4) bar_sync(NB_ST, 64);
            p_a2(i);
          }
        } else {
#pragma unroll 1
          for (int u = 0; u < 6; u++) { const int i = (0x025413 >> (4 * u)) & 7; if (u == 0 || u == 3) mbar_wait(sb + B_QE + 8 * (u / 3), 1); p_b(i, i, 0); }
          mbar_wait(sb + B_QE + 24, 1);
          e_expect_tx(sb + B_RF, 32768);
          tma_ld3(sb + RES, &prm.m[l == 0 ? M_X0R : M_XSR], 0, pm * 128, 2 * pn, sb + B_RF);
          p_a2(0);
          bar_sync(NB_DONE, 64);
          e_arrive_both(sb + B_PA);
          p_a2(1);
          mbar_wait(sb + B_PA, (l >> 1) & 1);
#pragma unroll 1
          for (int i = 2; i < 6; i++) { if (i > 2) mbar_wait(sb + B_PF + 8 * (i - 3), 0); p_a(i, i); }
        }
        uint32_t s = 0, lap = 1;
#pragma unroll 1
        for (int i = 6; i < 16; i++) {
          p_b(i, s, ((s < 4 ? l : 0) + lap) & 1);
          p_a(i, s);
          if (++s == 6) { s = 0; lap++; }
        }
        const CUtensorMap* mn = &prm.m[M_WQA + ((l + 1) & 1)];
        if (l < 3) {
          mbar_wait(sb + B_PE + 8 * 4, 1); mbar_wait(sb + B_PE + 8 * 5, 1);
          tma_ld3(sb + 32768, mn, bn * 64, 2 * pn * 64, 0, sb + B_QL);
          mbar_wait(sb + B_PE + 8 * 0, l & 1);
          tma_ld3(sb + QSTG + 32768, mn, bn * 64, (2 * pn + 1) * 64, 0, sb + B_QL);
          mbar_wait(sb + B_PE + 8 * 1, l & 1);
          e_expect_tx(sb + B_QF + 16, QSTG);
          tma_ld3(sb + 2 * QSTG + 32768, mn, bn * 64, ((2 * pn) ^ 2) * 64, 0, sb + B_QF + 16);
        }
        if (l < 3) { bar_sync(NB_X, 320); e_expect_tx(sb + B_QL, 49152); }
      }
      if (blockIdx.x == 0 && lane_id() == 0) *(volatile uint32_t*)&g_epoch = ep1;
    } else {
      const int hw = w - 1;
      if (lane < 5) asm volatile("prefetch.tensormap [%0];" ::"l"(&prm.m[5 * hw + lane]) : "memory");
      __syncwarp();
      cluster_wait();
      mbar_wait(sb + B_QF, 0);
#pragma unroll 1
      for (int l = 0; l < 4; l++) {
        IDS();
        if (l > 0) { mbar_wait(sb + B_QL, (l + 1) & 1); mbar_wait(sb + B_QF + 8 * 3, 0); }
        if (l == 0) {
#pragma unroll 1
          for (int r = 2 * hw; r < 16; r += 6) {
            const uint4* p = (const uint4*)(prm.x0 + (size_t)(b * 16 + r) * 1024) + lane;
            float s1[2] = {0.f, 0.f}, s2[2] = {0.f, 0.f};
#pragma unroll
            for (int i = 0; i < 8; i++) {
              const uint4 v = __ldg(p + 32 * i);
              const uint32_t u[4] = {v.x, v.y, v.z, v.w};
#pragma unroll
              for (int k = 0; k < 4; k++) { const float a = bf_lo(u[k]), c = bf_hi(u[k]); s1[i >> 2] += a + c; s2[i >> 2] = fmaf(a, a, fmaf(c, c, s2[i >> 2])); }
            }
#pragma unroll
            for (int o = 16; o; o >>= 1)
#pragma unroll
              for (int rr = 0; rr < 2; rr++) { s1[rr] += __shfl_xor_sync(~0u, s1[rr], o); s2[rr] += __shfl_xor_sync(~0u, s2[rr], o); }
            if (lane == 0) *(float4*)&g_stats[b * 16 + r] = make_float4(s1[0], s2[0], s1[1], s2[1]);
          }
        }
        if (l < 2) {
          float cs[8];
#pragma unroll
          for (int i = 0; i < 8; i++) cs[i] = 0.f;
          const uint4* wp = (const uint4*)(prm.wq[l] + (size_t)(bm * 128 + (lane >> 3)) * 3072 + hw * 1024 + bn * 64) + (lane & 7);
#pragma unroll 8
          for (int i = 0; i < 32; i++) {
            const uint4 v = __ldg(wp + (size_t)i * 4 * 384);
            cs[0] += bf_lo(v.x); cs[1] += bf_hi(v.x); cs[2] += bf_lo(v.y); cs[3] += bf_hi(v.y);
            cs[4] += bf_lo(v.z); cs[5] += bf_hi(v.z); cs[6] += bf_lo(v.w); cs[7] += bf_hi(v.w);
          }
#pragma unroll
          for (int i = 0; i < 8; i++) { cs[i] += __shfl_xor_sync(~0u, cs[i], 8); cs[i] += __shfl_xor_sync(~0u, cs[i], 16); }
          if (lane < 8) {
            float4* d = (float4*)(g_csp + ((l * 16 + bn) * 8 + bm) * 192 + hw * 64 + lane * 8);
            d[0] = make_float4(cs[0], cs[1], cs[2], cs[3]); d[1] = make_float4(cs[4], cs[5], cs[6], cs[7]);
          }
          __syncwarp();
          asm volatile("fence.acq_rel.gpu;" ::: "memory");
          e_red_relaxed(cnt_cs(l, bn));
          if (l == 0) e_red_relaxed(cnt_x(0, bm) + pn);
          poll_ge(lane < 8 && l == 0 ? cnt_x(0, bm) + lane : cnt_cs(l, bn), ep1 * (lane < 8 && l == 0 ? 6 : 24));
        }
        if (l > 0) poll_ge(cnt_x(l, bm) + (lane & 15), ep1 * 2);
#pragma unroll 1
        for (int it = hw * 32 + lane; it < 176; it += 96) {
          const bool rows = it < 128;
          const float4* p = rows ? (const float4*)(g_stats + bm * 256) + it : (const float4*)(g_csp + ((l & 1) * 16 + bn) * 8 * 192) + (it - 128);
          const int stride = rows ? 1024 : 48, np = rows && l == 0 ? 1 : 8;
          float4 a = make_float4(0.f, 0.f, 0.f, 0.f);
#pragma unroll
          for (int k = 0; k < 8; k++) if (k < np) { const float4 v = __ldcg(p + k * stride); a.x += v.x; a.y += v.y; a.z += v.z; a.w += v.w; }
          if (rows) {
            const float m0 = a.x * (1.f / 1024.f), m1 = a.z * (1.f / 1024.f);
            const float v0 = fmaxf(a.y * (1.f / 1024.f) - m0 * m0, 0.f), v1 = fmaxf(a.w * (1.f / 1024.f) - m1 * m1, 0.f);
            const float r0 = __fdividef(1.f, bf_round(sqrtf(bf_round(bf_round(v0) + 1e-5f)))), r1 = __fdividef(1.f, bf_round(sqrtf(bf_round(bf_round(v1) + 1e-5f))));
            a = make_float4(r0, -bf_round(m0) * (l & 1 ? r0 : 1.f), r1, -bf_round(m1) * (l & 1 ? r1 : 1.f));
          }
          *(float4*)(smem + ROWST + it * 16) = a;
        }
        __syncwarp();
        if (lane == 0) asm volatile("red.release.cta.shared.add.u32 [%0], 1;" ::"r"(sb + W_X) : "memory");
        if (hw == 2) {
          if (!(l & 1)) {
            bar_sync(NB_ST, 288);
            const uint4* hp = g_halo + ((l >> 1) * 128 + b - 16) * 384 + lane;
#pragma unroll 1
            for (int h = 0; h < 2; h++) {
              uint32_t t[18];
#pragma unroll
              for (int i = 0; i < 18; i++) t[i] = 0;
#pragma unroll 1
              for (uint32_t n = bm ? 0 : 100000u; n < 100000u; n++) {
                uint32_t miss = 0;
#pragma unroll
                for (int i = 0; i < 6; i++) miss |= ld_tagged(hp + h * 192 + i * 32, &t[3 * i]) ^ ep1;
                if (__all_sync(~0u, !miss)) break;
              }
              mbar_wait(sb + B_QE + 16, 1);
              const uint32_t r = (lane & 7) + ((lane >> 3) & 1) * 8, rv = lane >> 2;
#pragma unroll
              for (int jj = 0; jj < 2; jj++) stsm4(sb + KSC + r * 128 + (((4 * h + 2 * jj + (lane >> 4)) ^ (r & 7)) << 4), t[4 * jj], t[4 * jj + 1], t[4 * jj + 2], t[4 * jj + 3]);
              const uint32_t ad = sb + VSC + rv * 128 + (((4 * h + (lane & 3)) ^ (rv & 7)) << 4);
              sts128(ad, t[8], t[10], t[12], t[14]); sts128(ad + 1024, t[9], t[11], t[13], t[15]);
              if (h == 0 && !(lane & 2)) *(uint32_t*)(smem + HRS + ((lane >> 2) + 8 * (lane & 1)) * 8) = t[16];
              bar_arrive(NB_HALO + h, 64);
            }
          } else {
            mbar_wait(sb + B_TF + 16, 0); mbar_wait(sb + B_TF + 16, 1);
            poll_ge(cnt_kv(l >> 1, bn) + 16 + (lane & 7), ep1);
            const uint4 v = __ldcg((const uint4*)(g_kn + ((l >> 1) * 128 + bn * 8) * 16) + lane);
            const uint32_t mx = max(max(v.x, v.y), max(v.z, v.w));
            const uint32_t m0 = __reduce_max_sync(~0u, (lane & 2) ? 0u : mx), m1 = __reduce_max_sync(~0u, (lane & 2) ? mx : 0u);
            if (lane == 0) *(uint2*)(smem + ROWST) = make_uint2(m0, m1);
            __syncwarp();
            bar_arrive(NB_KN, 160); bar_arrive(NB_KN + 1, 160);
          }
        } else {
          if (l & 1) {
            bar_sync(hw ? NB_HALO : NB_DONE, 160);
            tma_st(&prm.m[M_K], 0, 2 * bn * 2048 + bm * 256 + hw * 128, sb + T0 + hw * 8192);
            tma_st(&prm.m[M_V], 0, 2 * bn * 2048 + bm * 256 + hw * 128, sb + T0 + 16384 + hw * 8192);
            bulk_commit(); bulk_wait_n<0>();
            e_red(cnt_kv(l >> 1, bn) + 8 * hw + bm);
          }
#pragma unroll 1
          for (int i = 0; i < 2; i++) {
            const int h = l & 1 ? i : hw, g = l & 1 ? hw : i;
            bar_sync(NB_SIG + 2 * h + g, 160);
            if (!(l & 1) && i == 0) continue;
            if (i == 1 && hw == 1) bar_arrive(l & 1 ? NB_ST : NB_DONE, 64);
            asm volatile("fence.acq_rel.gpu;" ::: "memory");
            e_red_relaxed(cnt_o(l, 2 * bm + g, h) + (bn >> 1));
            if (!(l & 1)) e_red_relaxed(cnt_o(l, 2 * bm, h) + (bn >> 1));
            if (h == 1 && l == 1) e_red_relaxed(cnt_ad(bn));
          }
        }
        if (hw < 2 && l < 3) {
          if (hw) bar_sync(NB_X, 320); else bar_sync(NB_X0, 288);
          if (hw) {

            tma_st(&prm.m[M_XSO], pn * 128 + 64, pm * 128, sb + QSTG + po * 16384);
            bulk_commit();
            bar_sync(NB_KV, 288);
            bulk_wait_n<0>();
          }
          e_red(cnt_x(l + 1, bm) + 2 * pn + hw);
        }
      }
    }
  } else {
    asm volatile("setmaxnreg.inc.sync.aligned.u32 224;");
    const uint32_t zero = prm.zero;
    cluster_wait();
#pragma unroll 1
    for (int l = 0; l < 4; l++) {
      {
        float acc[2][96];
#pragma unroll
        for (int i = 0; i < 96; i++) { acc[0][i] = 0.f; acc[1][i] = 0.f; }
        fence_regs(acc[0]); fence_regs(acc[1]);
        const bool early = l > 0 && wg == ((cta_id() >> 3) & 1);
        uint32_t ep1 = 0;
#pragma unroll 1
        for (int kt = 0; kt < 14; kt++) {
          const int s = kt & 3;
          if (l > 0 && kt == 0) mbar_wait(sb + B_QL, (l + 1) & 1);
          if (!(early && kt < 2)) mbar_wait(sb + B_QF + 8 * s, (kt >> 2) & 1);
          const uint64_t da = prm.xd + wg * 1024 + s * (QSTG >> 4), db = prm.wd + s * (QSTG >> 4);
          wg_fence();
#pragma unroll
          for (int k = 0; k < 4; k++)
#pragma unroll
            for (int m = 0; m < 2; m++) wgmma_m64n192k16_ss_tb(acc[m], da + m * 512 + k * 2, db + k * 128, 1);
          wg_commit();
          if (kt == 4) ep1 = *(volatile uint32_t*)&g_epoch + 1;
          wg_wait<1>();
          if (early && (kt == 1 || kt == 2)) mbar_wait(sb + B_QF + 8 * (kt - 1), 0);
          if (kt > 0 && w == 0) e_arrive_both(sb + B_QE + 8 * ((kt - 1) & 3));
        }
        {
          const bool lag = (l & 1) && wg;
          const uint64_t da = prm.xd + wg * 1024 + 2 * (QSTG >> 4), db = prm.wd + 2 * (QSTG >> 4);
          mbar_wait(sb + B_QF + 16, 1);
          if (lag) {
            mbar_wait(sb + B_QF + 24, 1);
            wg_wait<0>();
            if (w == 0) e_arrive_both(sb + B_QE + 8);
            bar_sync(NB_SC, 256);
          }
          wg_fence();
#pragma unroll
          for (int k = 0; k < 4; k++)
#pragma unroll
            for (int m = 0; m < 2; m++) wgmma_m64n192k16_ss_tb(acc[m], da + m * 512 + k * 2, db + k * 128, 1);
          wg_commit();
          if (!lag) {
            wg_wait<1>();
            if (w == 0) e_arrive_both(sb + B_QE + 8);
            mbar_wait(sb + B_QF + 24, 1);
          }
          wg_fence();
#pragma unroll
          for (int m = 1; m >= 0; m--) {
#pragma unroll
            for (int k = 0; k < 4; k++) wgmma_m64n192k16_ss_tb(acc[m], da + (QSTG >> 4) + m * 512 + k * 2, db + (QSTG >> 4) + k * 128, 1);
            wg_commit();
          }
          if ((l & 1) && !wg) bar_arrive(NB_SC, 256);
          if (!(l & 1)) bar_arrive(NB_ST, 288);
          wg_wait<2>();
          if (w == 0) e_arrive_both(sb + B_QE + 16);
        }
#pragma unroll 1
        for (uint32_t n = 0; n < 4000000u; n++) {
          uint32_t v;
          asm volatile("ld.acquire.cta.shared.u32 %0, [%1];" : "=r"(v) : "r"(sb + W_X) : "memory");
          if (v == (uint32_t)(3 * l + 3)) break;
        }
        IDS();
        const int g = lane >> 2, qd = lane & 3;
        float2 st[2][2];
#pragma unroll
        for (int m = 0; m < 2; m++)
#pragma unroll
          for (int hh = 0; hh < 2; hh++) st[m][hh] = lds64f(sb + ROWST + (wg * 128 + m * 64 + w * 16 + g + 8 * hh) * 8);
        float2 cs[4];
        auto load_cs = [&](int gi) {
#pragma unroll
          for (int j = 0; j < 4; j++) cs[j] = lds64f(sb + COLS + (gi * 32 + j * 8 + 2 * qd) * 4);
        };
        load_cs(2);
        auto drain = [&]() {
          wg_wait<0>(); fence_regs(acc[0]);
          if (w == 0) e_arrive_both(sb + B_QE + 8 * 3);
        };
        wg_wait<1>(); fence_regs(acc[1]);
        auto norm_tile = [&](int gi, int m, float sc, uint32_t (&t)[8], float (&nrm)[2], bool h16 = false) {
          const float r0 = st[m][0].x * sc, s0 = st[m][0].y * sc, r1 = st[m][1].x * sc, s1 = st[m][1].y * sc;
          float n0 = 0.f, n1 = 0.f;
#pragma unroll
          for (int j = 0; j < 4; j++) {
            const float* a = &acc[m][16 * gi + 4 * j];
            const float v0 = fmaf(a[0], r0, s0 * cs[j].x), v1 = fmaf(a[1], r0, s0 * cs[j].y);
            const float v2 = fmaf(a[2], r1, s1 * cs[j].x), v3 = fmaf(a[3], r1, s1 * cs[j].y);
            n0 = fmaf(v0, v0, fmaf(v1, v1, n0)); n1 = fmaf(v2, v2, fmaf(v3, v3, n1));
            t[2 * j] = h16 ? pack2h(v0, v1) : pack2(v0, v1); t[2 * j + 1] = h16 ? pack2h(v2, v3) : pack2(v2, v3);
          }
          nrm[0] = n0; nrm[1] = n1;
        };
        auto norm_group = [&](int gi, float sc, uint32_t (&t)[2][8], float (&nrm)[2][2]) { norm_tile(gi, 0, sc, t[0], nrm[0]); norm_tile(gi, 1, sc, t[1], nrm[1]); };
        uint32_t q[2][2][8];
        const uint32_t srow = (lane & 7) + ((lane >> 3) & 1) * 8;
        const uint32_t row0 = wg * 128 + w * 16;
        if (!(l & 1)) {
          auto put_kv = [&](int gi, uint32_t r0, const uint32_t (&t)[8]) {
            if (gi < 4) {
              const uint32_t r = r0 + srow;
#pragma unroll
              for (int jj = 0; jj < 2; jj++) stsm4(sb + KSC + r * 128 + (((4 * (gi - 2) + 2 * jj + (lane >> 4)) ^ (r & 7)) << 4), t[4 * jj], t[4 * jj + 1], t[4 * jj + 2], t[4 * jj + 3]);
            } else {
              const uint32_t r = r0 + g, ad = sb + VSC + r * 128 + (((4 * (gi - 4) + qd) ^ (r & 7)) << 4);
              sts128(ad, t[0], t[2], t[4], t[6]); sts128(ad + 1024, t[1], t[3], t[5], t[7]);
            }
          };
          auto cen_tile = [&](int gi, int m, uint32_t (&t)[8]) {
#pragma unroll
            for (int j = 0; j < 4; j++) {
              const float* a = &acc[m][16 * gi + 4 * j];
              t[2 * j] = pack2(fmaf(st[m][0].y, cs[j].x, a[0]), fmaf(st[m][0].y, cs[j].y, a[1]));
              t[2 * j + 1] = pack2(fmaf(st[m][1].y, cs[j].x, a[2]), fmaf(st[m][1].y, cs[j].y, a[3]));
            }
          };
          const bool send = wg == 1 && w == 3 && bm < 7;
          uint4* hp = g_halo + ((l >> 1) * 128 + b) * 384 + lane;
          mbar_wait(sb + B_QE + 16, 1);
          float2 cn[4];
          auto next_cs = [&](int gi) {
#pragma unroll
            for (int j = 0; j < 4; j++) { cs[j] = cn[j]; cn[j] = lds64f(sb + COLS + (gi * 32 + j * 8 + 2 * qd) * 4); }
          };
#pragma unroll
          for (int j = 0; j < 4; j++) cn[j] = cs[j];
#pragma unroll
          for (int h = 0; h < 2; h++) {
            uint32_t k[8], v[8];
            next_cs(4 + h);
            cen_tile(2 + h, 1, k); put_kv(2 + h, 16 + row0 + 64, k);
            next_cs(h ? 2 : 3);
            cen_tile(4 + h, 1, v); put_kv(4 + h, 16 + row0 + 64, v);
            if (send) {
              uint4* p = hp + h * 192;
              st_tagged(p, k[0], k[1], k[2], ep1); st_tagged(p + 32, k[3], k[4], k[5], ep1); st_tagged(p + 64, k[6], k[7], v[0], ep1);
              st_tagged(p + 96, v[1], v[2], v[3], ep1); st_tagged(p + 128, v[4], v[5], v[6], ep1);
              st_tagged(p + 160, v[7], __float_as_uint(qd & 1 ? st[1][1].x : st[1][0].x), 0u, ep1);
            }
            sched_fence();
          }
          drain();
          {
            uint32_t t[8];
            next_cs(4); cen_tile(2, 0, t); put_kv(2, 16 + row0, t);
            next_cs(0); cen_tile(4, 0, t); put_kv(4, 16 + row0, t);
            next_cs(3); cen_tile(0, 0, q[0][0]); cen_tile(0, 1, q[0][1]);
          }
          const bool e = g & 1, sel = 2 * qd + (g & 1) >= g + 2, first = bm == 0 && row0 == 0;
          uint32_t ka = sb + KSC + (row0 + (lane & 7)) * 128 + (((lane >> 3) ^ (lane & 7)) << 4);
          uint32_t wa = sb + VSC + (row0 + srow) * 128 + (((lane >> 4) ^ (lane & 7)) << 4);
          uint32_t psel[3] = {e ? 0x1044u : 0x4410u, !sel ? 0x4444u : e ? 0x3244u : 0x4432u, sel ? 0x4444u : e ? 0x3244u : 0x4432u};
          bf16* op = g_os + (size_t)(bm * 256 + row0 + g) * 1024 + bn * 32 + qd * 8;
          asm volatile("" : "+r"(ka), "+r"(wa), "+l"(op));
          fence_regs(psel); fence_regs(q[0][0]); fence_regs(q[0][1]);
          sched_fence();
          bar_sync(NB_SC, 256);
          if (row0 == 0) bar_sync(NB_HALO, 64);
          float ra[4], rb[4], ca[4], cb[4];
#pragma unroll
          for (int m = 0; m < 2; m++) {
            float rk[3];
#pragma unroll
            for (int u = 0; u < 3; u++) {
              const int r = row0 + m * 64 + 8 * u + 2 * qd + e - (sel ? 16 : 8);
              rk[u] = lds64f(sb + (m == 0 && r < 0 ? HRS + 128 : ROWST) + r * 8).x;
            }
            ra[2 * m] = sel ? rk[1] : rk[0]; ra[2 * m + 1] = sel ? rk[2] : rk[1];
            rb[2 * m] = sel ? rk[0] : rk[1]; rb[2 * m + 1] = sel ? rk[1] : rk[2];
          }
#pragma unroll
          for (int i = 0; i < 4; i++) { const float rq = st[i >> 1][i & 1].x * QSCALE; ca[i] = rq * ra[i]; cb[i] = rq * rb[i]; }
#pragma unroll 1
          for (int h = 0; h < 2; h++) {
            float s[2][4][4];
            uint32_t vf[2][4][4], pf[2][2][4];
#pragma unroll
            for (int m = 0; m < 2; m++)
#pragma unroll
              for (int nt = 0; nt < 4; nt++) {
                uint32_t kf[4];
                ldsm4(ka + (m * 64 + 8 * nt) * 128, kf);
                s[m][nt][0] = s[m][nt][1] = s[m][nt][2] = s[m][nt][3] = 0.f;
                mma16816(s[m][nt], q[0][m][0], q[0][m][1], q[0][m][2], q[0][m][3], kf[0], kf[1]);
                mma16816(s[m][nt], q[0][m][4], q[0][m][5], q[0][m][6], q[0][m][7], kf[2], kf[3]);
              }
#pragma unroll
            for (int m = 0; m < 2; m++)
#pragma unroll
              for (int i = 0; i < 4; i++) {
                ldsm4t((wa ^ (32 * (i & 1))) + (m * 64 + 16 * (i >> 1)) * 128, vf[m][i]);
              }
            float va[4], vb[4], mx[4];
#pragma unroll
            for (int i = 0; i < 4; i++) {
              const int m = i >> 1, hh = i & 1;
              const float a = e ? s[m][hh + 1][2 * hh + 1] : s[m][hh + 1][2 * hh];
              const float lo = e ? s[m][hh][2 * hh + 1] : s[m][hh][2 * hh], hi = e ? s[m][hh + 2][2 * hh + 1] : s[m][hh + 2][2 * hh];
              va[i] = (m == 0 && hh == 0 && first) ? -INFINITY : a * ca[i];
              vb[i] = (m == 0 && first && sel) ? -INFINITY : (sel ? lo : hi) * cb[i];
              mx[i] = fmaxf(va[i], vb[i]);
            }
#pragma unroll
            for (int i = 0; i < 4; i++) mx[i] = fmaxf(mx[i], __shfl_xor_sync(~0u, mx[i], 1));
#pragma unroll
            for (int i = 0; i < 4; i++) mx[i] = fmaxf(mx[i], __shfl_xor_sync(~0u, mx[i], 2));
#pragma unroll
            for (int i = 0; i < 4; i++) {
              va[i] = ex2(va[i] - mx[i]); vb[i] = ex2(vb[i] - mx[i]);
              mx[i] = va[i] + vb[i];
              va[i] *= ra[i]; vb[i] *= rb[i];
            }
#pragma unroll
            for (int i = 0; i < 4; i++) mx[i] += __shfl_xor_sync(~0u, mx[i], 1);
#pragma unroll
            for (int i = 0; i < 4; i++) mx[i] += __shfl_xor_sync(~0u, mx[i], 2);
#pragma unroll
            for (int i = 0; i < 4; i++) {
              const int m = i >> 1, hh = i & 1;
              const float inv = rcp(mx[i]);
              const uint32_t t = pack2(va[i] * inv, vb[i] * inv);
              pf[m][hh][hh + 1] = prmt0(t, psel[0]); pf[m][hh][hh] = prmt0(t, psel[1]); pf[m][hh][hh + 2] = prmt0(t, psel[2]);
              pf[m][hh][3 - 3 * hh] = t & zero;
            }
#pragma unroll
            for (int m = 0; m < 2; m++) {
              float o[4][4];
#pragma unroll
              for (int j = 0; j < 4; j++) o[j][0] = o[j][1] = o[j][2] = o[j][3] = 0.f;
#pragma unroll
              for (int i = 0; i < 4; i++) {
                const int kk = i >> 1, jj = 2 * (i & 1);
                mma16816(o[jj], pf[m][0][2 * kk], pf[m][1][2 * kk], pf[m][0][2 * kk + 1], pf[m][1][2 * kk + 1], vf[m][i][0], vf[m][i][1]);
                mma16816(o[jj + 1], pf[m][0][2 * kk], pf[m][1][2 * kk], pf[m][0][2 * kk + 1], pf[m][1][2 * kk + 1], vf[m][i][2], vf[m][i][3]);
              }
              stg128(op + m * 65536, pack2(o[0][0], o[0][1]), pack2(o[1][0], o[1][1]), pack2(o[2][0], o[2][1]), pack2(o[3][0], o[3][1]));
              stg128(op + m * 65536 + 8192, pack2(o[0][2], o[0][3]), pack2(o[1][2], o[1][3]), pack2(o[2][2], o[2][3]), pack2(o[3][2], o[3][3]));
            }
            bar_arrive(NB_SIG + 2 * h + wg, 160);
            if (h == 0) {
              uint32_t t[8];
              next_cs(5); cen_tile(3, 0, t); put_kv(3, 16 + row0, t);
              next_cs(1); cen_tile(5, 0, t); put_kv(5, 16 + row0, t);
#pragma unroll
              for (int j = 0; j < 4; j++) cs[j] = cn[j];
              cen_tile(1, 0, q[0][0]); cen_tile(1, 1, q[0][1]);
              ka ^= 64; wa ^= 64; op += 512;
              bar_sync(NB_SC, 256);
              if (row0 == 0) bar_sync(NB_HALO + 1, 64);
            }
          }
        } else {
          float qn[2];
          drain();
          auto esc_ptr = [&](int gi) { IDS(); return g_esc + (size_t)(((l & 2) + (gi >> 1)) * 65536 + (2 * bn + (gi & 1)) * 2048) * 20; };
          auto norm_half = [&](int gi, float sc, uint32_t (&t)[2][8], float (&nrm)[2][2]) {
            norm_tile(gi, 0, sc, t[0], nrm[0], true); norm_tile(gi, 1, sc, t[1], nrm[1], true);
            if (!((nrm[0][0] + nrm[0][1]) + (nrm[1][0] + nrm[1][1]) <= 4e9f) || fminf(fminf(nrm[0][0], nrm[0][1]), fminf(nrm[1][0], nrm[1][1])) < 1.5e-5f) {
              uint32_t* p = esc_ptr(gi) + (bm * 256 + row0 + g) * 20 + qd;
#pragma unroll
              for (int m = 0; m < 2; m++) {
                uint32_t u[8]; float d[2];
                norm_tile(gi, m, sc, u, d);
#pragma unroll
                for (int i = 0; i < 10; i++) p[(m * 64 + (i & 1) * 8) * 20 + (i >> 1) * 4] = i < 8 ? u[i] : ep1;
              }
            }
            __syncwarp();
          };
          {
            auto max_norm = [&](const float (&nrm)[2][2]) {
              const bool o1 = qd & 1, o2 = qd & 2;
              const float a = (o1 ? nrm[1][0] : nrm[0][0]) + __shfl_xor_sync(~0u, o1 ? nrm[0][0] : nrm[1][0], 1);
              const float c = (o1 ? nrm[1][1] : nrm[0][1]) + __shfl_xor_sync(~0u, o1 ? nrm[0][1] : nrm[1][1], 1);
              const float d = (o2 ? c : a) + __shfl_xor_sync(~0u, o2 ? a : c, 2);
              return __uint_as_float(__reduce_max_sync(~0u, __float_as_uint(d)));
            };
#pragma unroll
            for (int h = 0; h < 2; h++) {
              uint32_t t[2][8]; float nrm[2][2];
              const uint32_t kb = sb + (h ? 0 : T0);
              if (h) load_cs(3);
              uint32_t tv[2][8];
              norm_half(2 + h, 1.f, t, nrm);
              load_cs(4 + h);
              float nv[2][2];
              if (h == 1) { const float kn = max_norm(nrm); if (lane == 0) g_kn[((l >> 1) * 128 + bn * 8 + bm) * 16 + 8 + wg * 4 + w] = kn; }
              if (h == 0) mbar_wait(sb + B_QE + 8, 1);
#pragma unroll
              for (int i = 0; i < 4; i++) {
                const uint32_t r = row0 + (i >> 1) * 64 + srow;
                stsm4(kb + r * 64 + (((2 * (i & 1) + (lane >> 4)) ^ ((r >> 1) & 3)) << 4), t[i >> 1][4 * (i & 1)], t[i >> 1][4 * (i & 1) + 1], t[i >> 1][4 * (i & 1) + 2], t[i >> 1][4 * (i & 1) + 3]);
              }
              norm_group(4 + h, 1.f, tv, nv);
              load_cs(h);
#pragma unroll
              for (int m = 0; m < 2; m++) {
                const uint32_t r = row0 + m * 64 + g, ad = kb + 16384 + r * 64 + ((qd ^ ((r >> 1) & 3)) << 4);
                sts128(ad, tv[m][0], tv[m][2], tv[m][4], tv[m][6]); sts128(ad + 512, tv[m][1], tv[m][3], tv[m][5], tv[m][7]);
              }
              fence_async_smem();
              bar_arrive(NB_KV + 12 * h, 288);
              if (h == 0) {
                bar_arrive(wg ? NB_HALO : NB_DONE, 160);
                if (wg) bar_sync(NB_HALO + 1, 256);
              }
              if (h == 0) { const float kn = max_norm(nrm); if (lane == 0) g_kn[((l >> 1) * 128 + bn * 8 + bm) * 16 + wg * 4 + w] = kn; }
              norm_half(h, QSCALE, q[h], nrm);
#pragma unroll
              for (int i = 0; i < 4; i++) sts128(sb + QPARK + h * 16384 + (wg * 128 + w * 32 + lane) * 16 + i * 4096, q[h][i >> 1][4 * (i & 1)], q[h][i >> 1][4 * (i & 1) + 1], q[h][i >> 1][4 * (i & 1) + 2], q[h][i >> 1][4 * (i & 1) + 3]);
              qn[h] = max_norm(nrm);
            }
            if (!wg) bar_arrive(NB_HALO + 1, 256);
          }
          constexpr uint64_t VSTEP = 64 - (64ull << 16);
          const uint32_t c_882 = 0x62E562E5u + (lane_id() & zero), c_lsb = 0x00010001u + (lane_id() & zero), c_half = 0x3F003F00u + (lane_id() & zero);
          float o[2][20], S[2][32];
          uint32_t H[2][16], P0[4] = {}, P1[4] = {};
#pragma unroll
          for (int m = 0; m < 2; m++) {
#pragma unroll
            for (int i = 0; i < 20; i++) o[m][i] = 0.f;
            fence_regs(o[m]);
          }
          auto qkf = [&](int b, int ks, uint64_t d) { wg_n64_rs_nb_f16_f32(S[b], q[0][0][4 * ks], q[0][0][4 * ks + 1], q[0][0][4 * ks + 2], q[0][0][4 * ks + 3], d + 2 * ks, ks ? 1 : zero); };
          auto qkh = [&](int b, int ks, uint64_t d) { wg_n64_rs_nb_f16_f16(H[b], q[0][1][4 * ks], q[0][1][4 * ks + 1], q[0][1][4 * ks + 2], q[0][1][4 * ks + 3], d + 2 * ks, ks ? 1 : zero); };
          auto pv0 = [&](uint64_t d) { wgmma_m64n40k16_rs_tb(o[0], P0[0], P0[1], P0[2], P0[3], d, 1); };
          auto pv1 = [&](uint64_t d) { wgmma_m64n40k16_rs_tb(o[1], P1[0], P1[1], P1[2], P1[3], d, 1); };
          float e[4] = {};
          auto finish = [&](int h) {
            const float* s = &S[(h >> 2) & 1][8 * (h & 3)];
            const uint32_t* u = &H[(h >> 2) & 1][4 * (h & 3)];
            const float z0 = exp2_fix(s[6]), z1 = exp2_fix(s[7]);
            P0[0] = pack2v(e[0], e[1]);
            P1[0] = exp2_h2(u[0], c_882);
            P0[1] = pack2v(e[2], e[3]);
            P1[1] = exp2_h2(u[1], c_882);
            const uint32_t B = exp2_base(z0, z1), E = and_or<0x7F807F80u>(B, c_lsb);
            P1[3] = exp2_h2(u[3], c_882);
            P0[3] = fma_bf2(B, and_or<0x807F807Fu>(B, c_half), E);
            const float e4 = ex2v(s[4]), e5 = ex2v(s[5]);
            P1[2] = exp2_h2(u[2], c_882);
            P0[2] = pack2v(e4, e5);
          };
          auto start = [&](int h) {
            const float* s = &S[(h >> 2) & 1][8 * (h & 3)];
            e[0] = ex2v(s[0]); e[1] = ex2v(s[1]); e[3] = ex2v(s[3]); e[2] = ex2v(s[2]);
          };
          uint64_t kd = prm.kv[0].kd;
          mbar_wait(sb + B_TF, 0);
          wg_fence();
#pragma unroll
          for (int b = 0; b < 2; b++) {
            wg_n64_rs_nb_f16_f32_z(S[b], q[0][0][0], q[0][0][1], q[0][0][2], q[0][0][3], kd + 256 * b, 0);
            wg_n64_rs_nb_f16_f16_z(H[b], q[0][1][0], q[0][1][1], q[0][1][2], q[0][1][3], kd + 256 * b, 0);
            if (b == 0) { qkf(0, 1, kd); qkh(0, 1, kd); }
            wg_commit();
          }
          wg_wait<1>(); fence_regs(S[0]); fence_regs(H[0]);
          start(0); finish(0); start(1);
          wg_wait<0>();
          int redo = 0;
#pragma unroll 1
          for (int pass = 0, j = 1; pass < 2; pass++) {
#pragma unroll 1
           do {
            const uint64_t vd = prm.kv[j & 3].vd;
            bool go = false;
#pragma unroll
            for (int h = 2; h < 18; h++) {
              const int px = (h >> 2) + 1, c = h & 3;
              wg_fence();
              if (h == 13) kd = prm.kv[j & 3].kd;
              const uint64_t kx = kd + (px & 3) * 256, vx = vd + (h - 2) * VSTEP;
              if (h == 2) { qkh(1, 0, kx); qkf(1, 0, kx); pv0(vx); pv1(vx); qkh(1, 1, kx); qkf(1, 1, kx); }
              else if ((c == 1 || c == 2) && h < 17) { qkh(px & 1, c - 1, kx); pv1(vx); qkf(px & 1, c - 1, kx); pv0(vx); }
              else { pv0(vx); pv1(vx); }
              wg_commit();
              if (h == 3) e_arrive_if(sb + B_TE + 8 * ((j + 2) & 3), j > 1);
              if (h == 11) go = mbar_test(sb + B_TF + 8 * (j & 3), (j >> 2) & 1) && j != 8;
              finish(h - 1); start(h);
              if (h != 12 && h != 17) sched_fence();
              if (h == 12 && !go) {
                if (j == 16) {
#pragma unroll
                  for (int u = 13; u < 18; u++) {
                    wg_fence(); pv0(vd + (u - 2) * VSTEP); pv1(vd + (u - 2) * VSTEP); wg_commit();
                    if (u < 17) finish(u - 1);
                    if (u < 16) { start(u); sched_fence(); }
                    if (u & 1) { if (u == 17) wg_wait<0>(); else wg_wait<1>(); }
                  }
                  e_arrive(sb + B_TE + 24);
                  goto head_done;
                }
                mbar_wait(sb + B_TF + 8 * (j & 3), (j >> 2) & 1);
                if (j == 8) {
#pragma unroll
                  for (int i = 0; i < 4; i++) lds128(sb + QPARK + 16384 + (wg * 128 + w * 32 + lane_id()) * 16 + i * 4096, &q[0][i >> 1][4 * (i & 1)]);
                }
              }
              if (h == 17) wg_wait<0>(); else if (h & 1) wg_wait<1>();
              if (c == 3) { fence_regs(S[px & 1]); fence_regs(H[px & 1]); }
            }
           } while (j++ & 7);
           head_done:
            fence_regs(o[0]); fence_regs(o[1]);
            uint32_t pk[2][8];
            {
              IDS();
              bf16* op = g_os + (size_t)(bm * 256 + row0 + (lane >> 2)) * 1024 + pass * 512 + bn * 32 + (lane & 3) * 8;
#pragma unroll
              for (int i = 0; i < 4; i++) {
                const float* a = &o[i >> 1][2 * (i & 1)];
                const float inv = rcp(a[16]);
                uint32_t* u = &pk[i >> 1][4 * (i & 1)];
#pragma unroll
                for (int k = 0; k < 4; k++) u[k] = pack2(a[4 * k] * inv, a[4 * k + 1] * inv);
                *(uint4*)(op + ((i >> 1) * 64 + (i & 1) * 8) * 1024) = make_uint4(u[0], u[1], u[2], u[3]);
              }
            }
            sched_fence();
            if (pass == 0) bar_sync(NB_KN + wg, 160);
            const float kmax = *(volatile float*)(smem + ROWST + 4 * pass);
            const bool wide = !(qn[0] <= 1.6e7f) | !(kmax <= 1.6e7f) | !(qn[0] * kmax <= 112.f * 112.f);
            int badm = 0;
#pragma unroll
            for (int m = 0; m < 2; m++) {
              uint32_t chk[2] = {0u, 0u};
#pragma unroll
              for (int i = 0; i < 8; i++) asm("fma.rn.bf16x2 %0, %1, %2, %0;" : "+r"(chk[i & 1]) : "r"(pk[m][i]), "r"(0u));
              const bool bad = wide | !(fminf(o[m][16], o[m][18]) >= 9.3e-10f) | !(o[m][16] + o[m][18] <= 1e36f) | (((chk[0] | chk[1]) & 0x7FFF7FFFu) != 0);
              badm |= __any_sync(~0u, bad) << m;
            }
            if (!badm) bar_arrive(NB_SIG + 2 * pass + wg, 160);
            qn[0] = qn[1];
#pragma unroll
            for (int m = 0; m < 2; m++) {
#pragma unroll
              for (int i = 0; i < 20; i++) o[m][i] = 0.f;
              fence_regs(o[m]);
            }
            if (badm) {
              redo |= badm << 2 * pass;
              const int tx = wg * 128 + w * 32 + lane_id();
              uint4* p = g_qsave + (block_id() * 256 + tx) * 8 + pass * 4;
#pragma unroll
              for (int i = 0; i < 4; i++) {
                uint32_t u[4] = {q[0][i >> 1][4 * (i & 1)], q[0][i >> 1][4 * (i & 1) + 1], q[0][i >> 1][4 * (i & 1) + 2], q[0][i >> 1][4 * (i & 1) + 3]};
                if (pass == 0) lds128(sb + QPARK + tx * 16 + i * 4096, u);
                p[i] = make_uint4(u[0], u[1], u[2], u[3]);
              }
            }
          }
          if (redo) attn_redo(redo, l, cta_id(), wg, w, ep1);
        }
      }
      {
        float acc[64];
#pragma unroll
        for (int i = 0; i < 64; i++) acc[i] = 0.f;
        fence_regs(acc);
        uint32_t s = 0, lap = 0;
#pragma unroll 1
        for (int kt = 0; kt < 16; kt++) {
          mbar_wait(sb + B_PF + 8 * s, ((s < 4 ? l : 0) + lap) & 1);
          const uint64_t da = mkdesc(sb + pslot_a(s, l) + wg * 8192, 16, 1024, 1), db = mkdesc(sb + pslot_b(s), 8192, 1024, 1);
          wg_fence();
#pragma unroll
          for (int k = 0; k < 4; k++) wgmma_m64n128k16_ss_tb(acc, da + k * 2, db + k * 128, 1);
          wg_commit();
          wg_wait<1>();
          if (kt > 0 && w == 0) e_arrive_both(sb + B_PE + 8 * (s ? s - 1 : 5));
          if (++s == 6) { s = 0; lap++; }
        }
        IDS();
        const int g = lane >> 2, qd = lane & 3;
        const int r0 = wg * 64 + w * 16;
        const uint32_t r = r0 + (lane & 7) + ((lane >> 3) & 1) * 8;
        uint32_t x[8][4];
        mbar_wait(sb + B_RF, l & 1);
#pragma unroll
        for (int jj = 0; jj < 8; jj++) ldsm4(sb + RES + (jj >> 2) * 16384 + r * 128 + ((((2 * jj + (lane >> 4)) & 7) ^ (r & 7)) << 4), x[jj]);
        wg_wait<0>();
        fence_regs(acc);
        if (w == 0) e_arrive_both(sb + B_PE + 8 * 3);
        const CUtensorMap* mo = &prm.m[l == 3 ? M_OUT : M_XST];
#pragma unroll
        for (int jj = 0; jj < 8; jj++) {
#pragma unroll
          for (int i = 0; i < 4; i++) x[jj][i] = add_bf16x2(x[jj][i], pack2(acc[8 * jj + 2 * i], acc[8 * jj + 2 * i + 1]));
          if (jj < 4) stsm4(sb + RES + r * 128 + ((((2 * jj + (lane >> 4)) & 7) ^ (r & 7)) << 4), x[jj][0], x[jj][1], x[jj][2], x[jj][3]);
          if (jj == 3) { fence_async_smem(); __syncwarp(); tma_st(mo, pn * 128, pm * 128 + r0, sb + RES + r0 * 128); bulk_commit(); sched_fence(); }
        }
        if (l == 3) {
#pragma unroll
          for (int jj = 4; jj < 8; jj++) stsm4(sb + RES + 16384 + r * 128 + ((((2 * jj + (lane >> 4)) & 7) ^ (r & 7)) << 4), x[jj][0], x[jj][1], x[jj][2], x[jj][3]);
          fence_async_smem(); __syncwarp();
          tma_st(mo, pn * 128 + 64, pm * 128 + r0, sb + RES + 16384 + r0 * 128);
          bulk_commit(); bulk_wait_n<0>();
        } else {
          bar_sync(NB_SC, 256);
#pragma unroll
          for (int jj = 0; jj < 8; jj++)
            stsm4(sb + (jj >> 2) * QSTG + po * 16384 + r * 128 + ((((2 * jj + (lane >> 4)) & 7) ^ (r & 7)) << 4), x[jj][0], x[jj][1], x[jj][2], x[jj][3]);
          bulk_wait_n<0>();
          bar_arrive(NB_X0, 288);
          fence_async_smem();
          bar_arrive(NB_X, 320);
          float s1[4] = {0.f, 0.f, 0.f, 0.f}, sa[4] = {0.f, 0.f, 0.f, 0.f}, sc[4] = {0.f, 0.f, 0.f, 0.f};
#pragma unroll
          for (int jj = 0; jj < 8; jj++) {
            mma16816(s1, x[jj][0], x[jj][1], x[jj][2], x[jj][3], 0x3f803f80u, 0x3f803f80u);
            mma16816(sa, x[jj][0], x[jj][1], x[jj][2], x[jj][3], x[jj][0], x[jj][2]);
            mma16816(sc, x[jj][0], x[jj][1], x[jj][2], x[jj][3], x[jj][1], x[jj][3]);
          }
          if (qd == g >> 1) {
            float2* p = g_stats + pn * 2048 + pm * 128 + r0 + g;
            p[0] = make_float2(s1[0], g & 1 ? sa[1] : sa[0]);
            p[8] = make_float2(s1[2], g & 1 ? sc[3] : sc[2]);
          }
          bar_arrive(NB_KV, 288);
        }
      }
    }
  }
  asm volatile("barrier.cluster.arrive.relaxed.aligned;\nbarrier.cluster.wait.aligned;" ::: "memory");
}

typedef CUresult (*EncodeFn)(CUtensorMap*, CUtensorMapDataType, cuuint32_t, void*, const cuuint64_t*, const cuuint64_t*, const cuuint32_t*,
                             const cuuint32_t*, CUtensorMapInterleave, CUtensorMapSwizzle, CUtensorMapL2promotion, CUtensorMapFloatOOBfill);

static void make_map(EncodeFn fn, CUtensorMap* m, const void* ptr, int rank, const uint64_t* dims, const uint64_t* strides, const uint32_t* box, CUtensorMapSwizzle sw) {
  cuuint64_t d[5], st[4];
  cuuint32_t bx[5], es[5];
  for (int i = 0; i < rank; i++) { d[i] = dims[i]; bx[i] = box[i]; es[i] = 1; if (i) st[i - 1] = strides[i - 1] * 2; }
  fn(m, CU_TENSOR_MAP_DATA_TYPE_BFLOAT16, rank, (void*)ptr, d, st, bx, es, CU_TENSOR_MAP_INTERLEAVE_NONE, sw,
     CU_TENSOR_MAP_L2_PROMOTION_L2_128B, CU_TENSOR_MAP_FLOAT_OOB_FILL_NONE);
}
static void map2(EncodeFn fn, CUtensorMap* m, const void* ptr, uint64_t inner, uint64_t outer, uint32_t bi, uint32_t bo, CUtensorMapSwizzle sw) {
  const uint64_t d[2] = {inner, outer}, st[1] = {inner};
  const uint32_t bx[2] = {bi, bo};
  make_map(fn, m, ptr, 2, d, st, bx, sw);
}

extern "C" void kernel_launch(void* const* d_in, const int* in_sizes, int n_in, void* d_out, int out_size) {
  (void)in_sizes; (void)n_in; (void)out_size;
  static EncodeFn enc = nullptr;
  static void *xs, *os, *kk, *vv;
  static int sbase = 1024;
  if (!enc) {
    void* p = nullptr;
    cudaDriverEntryPointQueryResult qr;
    cudaGetDriverEntryPoint("cuTensorMapEncodeTiled", &p, cudaEnableDefault, &qr);
    enc = (EncodeFn)p;
    Scratch* sc = nullptr;
    cudaGetSymbolAddress((void**)&sc, g_s);
    xs = sc->xs; os = sc->os; kk = sc->k; vv = sc->v;
    int dev = 0;
    cudaGetDevice(&dev);
    cudaDeviceGetAttribute(&sbase, cudaDevAttrReservedSharedMemoryPerBlock, dev);
    cudaFuncSetAttribute(fused_kernel, cudaFuncAttributeMaxDynamicSharedMemorySize, SMEM_BYTES);
  }
  Params prm;
  const CUtensorMapSwizzle S128 = CU_TENSOR_MAP_SWIZZLE_128B, S64 = CU_TENSOR_MAP_SWIZZLE_64B;
  map2(enc, &prm.m[M_X0A], d_in[0], 1024, 2048, 64, 256, S128);
  map2(enc, &prm.m[M_XSA], xs, 1024, 2048, 64, 256, S128);
  for (int t = 0; t < 2; t++) {
    const uint64_t d3[3] = {1024, 1024, 3}, s3[2] = {3072, 1024};
    const uint32_t b3[3] = {64, 64, 3};
    make_map(enc, &prm.m[M_WQA + t], d_in[1 + 3 * t], 3, d3, s3, b3, S128);
    const uint64_t d5[5] = {64, 32, 2, 16, 16}, s5[4] = {1024, 32 * 1024, 64 * 1024, 64};
    const uint32_t b5[5] = {64, 32, 1, 2, 2};
    make_map(enc, &prm.m[M_WOA + t], d_in[2 + 3 * t], 5, d5, s5, b5, S128);
    const uint64_t dr[3] = {64, 2048, 16}, sr[2] = {1024, 64};
    const uint32_t br[3] = {64, 128, 2};
    make_map(enc, &prm.m[M_X0R + t], t ? xs : d_in[0], 3, dr, sr, br, S128);
  }
  map2(enc, &prm.m[M_OS], os, 1024, 2048, 64, 64, S128);
  map2(enc, &prm.m[M_K], kk, 32, 65536, 32, 128, S64);
  map2(enc, &prm.m[M_V], vv, 32, 65536, 32, 128, S64);
  map2(enc, &prm.m[M_XSO], xs, 1024, 2048, 64, 128, S128);
  map2(enc, &prm.m[M_X0H], d_in[0], 1024, 2048, 64, 128, S128);
  map2(enc, &prm.m[M_XST], xs, 1024, 2048, 64, 16, S128);
  map2(enc, &prm.m[M_OUT], d_out, 1024, 2048, 64, 16, S128);
  prm.x0 = (const bf16*)d_in[0];
  prm.wq[0] = (const bf16*)d_in[1]; prm.wq[1] = (const bf16*)d_in[4];
  prm.zero = 0;
  for (int i = 0; i < 128; i++) prm.map[i] = remap(i);
  {
    const uint64_t hi = 0x80000020ull << 32, k0 = sbase + T0, v0 = k0 + 16384, vstep = 64 - (64ull << 16);
    prm.wd = mkdesc(sbase + 32768, 8192, 1024, 1); prm.xd = mkdesc(sbase, 16, 1024, 1);
    for (int j = 0; j < 4; j++) {
      prm.kv[j].kd = (hi | 1u << 16 | k0 >> 4) + 2048 * ((j < 16 ? j : 15) & 3);
      prm.kv[j].vd = (hi | (uint64_t)(ONES - T0 - 16384) >> 4 << 16 | v0 >> 4) + 32 * vstep * ((j + 3) & 3);
    }
  }
  fused_kernel<<<128, 384, SMEM_BYTES>>>(prm);
}
```

```cpp
#include <cuda_runtime.h>
#include <cuda_bf16.h>
#include <cuda.h>
#include <stdint.h>

typedef __nv_bfloat16 bf16;

__device__ __forceinline__ void wgmma_m64n192k16_ss_tb(float (&d)[96], uint64_t da, uint64_t db, int scale_d) {
  asm volatile("{\n.reg .pred p;\nsetp.ne.b32 p, %98, 0;\n"
    "wgmma.mma_async.sync.aligned.m64n192k16.f32.bf16.bf16 "
    "{%0, %1, %2, %3, %4, %5, %6, %7, %8, %9, %10, %11, %12, %13, %14, %15, "
    "%16, %17, %18, %19, %20, %21, %22, %23, %24, %25, %26, %27, %28, %29, %30, %31, "
    "%32, %33, %34, %35, %36, %37, %38, %39, %40, %41, %42, %43, %44, %45, %46, %47, "
    "%48, %49, %50, %51, %52, %53, %54, %55, %56, %57, %58, %59, %60, %61, %62, %63, "
    "%64, %65, %66, %67, %68, %69, %70, %71, %72, %73, %74, %75, %76, %77, %78, %79, "
    "%80, %81, %82, %83, %84, %85, %86, %87, %88, %89, %90, %91, %92, %93, %94, %95}, "
    "%96, %97, p, 1, 1, 0, 1;\n}\n"
    : "+f"(d[0]), "+f"(d[1]), "+f"(d[2]), "+f"(d[3]), "+f"(d[4]), "+f"(d[5]), "+f"(d[6]), "+f"(d[7]),
      "+f"(d[8]), "+f"(d[9]), "+f"(d[10]), "+f"(d[11]), "+f"(d[12]), "+f"(d[13]), "+f"(d[14]), "+f"(d[15]),
      "+f"(d[16]), "+f"(d[17]), "+f"(d[18]), "+f"(d[19]), "+f"(d[20]), "+f"(d[21]), "+f"(d[22]), "+f"(d[23]),
      "+f"(d[24]), "+f"(d[25]), "+f"(d[26]), "+f"(d[27]), "+f"(d[28]), "+f"(d[29]), "+f"(d[30]), "+f"(d[31]),
      "+f"(d[32]), "+f"(d[33]), "+f"(d[34]), "+f"(d[35]), "+f"(d[36]), "+f"(d[37]), "+f"(d[38]), "+f"(d[39]),
      "+f"(d[40]), "+f"(d[41]), "+f"(d[42]), "+f"(d[43]), "+f"(d[44]), "+f"(d[45]), "+f"(d[46]), "+f"(d[47]),
      "+f"(d[48]), "+f"(d[49]), "+f"(d[50]), "+f"(d[51]), "+f"(d[52]), "+f"(d[53]), "+f"(d[54]), "+f"(d[55]),
      "+f"(d[56]), "+f"(d[57]), "+f"(d[58]), "+f"(d[59]), "+f"(d[60]), "+f"(d[61]), "+f"(d[62]), "+f"(d[63]),
      "+f"(d[64]), "+f"(d[65]), "+f"(d[66]), "+f"(d[67]), "+f"(d[68]), "+f"(d[69]), "+f"(d[70]), "+f"(d[71]),
      "+f"(d[72]), "+f"(d[73]), "+f"(d[74]), "+f"(d[75]), "+f"(d[76]), "+f"(d[77]), "+f"(d[78]), "+f"(d[79]),
      "+f"(d[80]), "+f"(d[81]), "+f"(d[82]), "+f"(d[83]), "+f"(d[84]), "+f"(d[85]), "+f"(d[86]), "+f"(d[87]),
      "+f"(d[88]), "+f"(d[89]), "+f"(d[90]), "+f"(d[91]), "+f"(d[92]), "+f"(d[93]), "+f"(d[94]), "+f"(d[95])
    : "l"(da), "l"(db), "r"(scale_d));
}

__device__ __forceinline__ void wgmma_m64n128k16_ss_tb(float (&d)[64], uint64_t da, uint64_t db, int scale_d) {
  asm volatile("{\n.reg .pred p;\nsetp.ne.b32 p, %66, 0;\n"
    "wgmma.mma_async.sync.aligned.m64n128k16.f32.bf16.bf16 "
    "{%0, %1, %2, %3, %4, %5, %6, %7, %8, %9, %10, %11, %12, %13, %14, %15, "
    "%16, %17, %18, %19, %20, %21, %22, %23, %24, %25, %26, %27, %28, %29, %30, %31, "
    "%32, %33, %34, %35, %36, %37, %38, %39, %40, %41, %42, %43, %44, %45, %46, %47, "
    "%48, %49, %50, %51, %52, %53, %54, %55, %56, %57, %58, %59, %60, %61, %62, %63}, "
    "%64, %65, p, 1, 1, 0, 1;\n}\n"
    : "+f"(d[0]), "+f"(d[1]), "+f"(d[2]), "+f"(d[3]), "+f"(d[4]), "+f"(d[5]), "+f"(d[6]), "+f"(d[7]),
      "+f"(d[8]), "+f"(d[9]), "+f"(d[10]), "+f"(d[11]), "+f"(d[12]), "+f"(d[13]), "+f"(d[14]), "+f"(d[15]),
      "+f"(d[16]), "+f"(d[17]), "+f"(d[18]), "+f"(d[19]), "+f"(d[20]), "+f"(d[21]), "+f"(d[22]), "+f"(d[23]),
      "+f"(d[24]), "+f"(d[25]), "+f"(d[26]), "+f"(d[27]), "+f"(d[28]), "+f"(d[29]), "+f"(d[30]), "+f"(d[31]),
      "+f"(d[32]), "+f"(d[33]), "+f"(d[34]), "+f"(d[35]), "+f"(d[36]), "+f"(d[37]), "+f"(d[38]), "+f"(d[39]),
      "+f"(d[40]), "+f"(d[41]), "+f"(d[42]), "+f"(d[43]), "+f"(d[44]), "+f"(d[45]), "+f"(d[46]), "+f"(d[47]),
      "+f"(d[48]), "+f"(d[49]), "+f"(d[50]), "+f"(d[51]), "+f"(d[52]), "+f"(d[53]), "+f"(d[54]), "+f"(d[55]),
      "+f"(d[56]), "+f"(d[57]), "+f"(d[58]), "+f"(d[59]), "+f"(d[60]), "+f"(d[61]), "+f"(d[62]), "+f"(d[63])
    : "l"(da), "l"(db), "r"(scale_d));
}

__device__ __forceinline__ void wgmma_m64n40k16_rs_tb(float (&d)[20], uint32_t a0, uint32_t a1, uint32_t a2, uint32_t a3, uint64_t db, int scale_d) {
  asm volatile("{\n.reg .pred p;\nsetp.ne.b32 p, %25, 0;\n"
    "wgmma.mma_async.sync.aligned.m64n40k16.f32.bf16.bf16 "
    "{%0, %1, %2, %3, %4, %5, %6, %7, %8, %9, %10, %11, %12, %13, %14, %15, "
    "%16, %17, %18, %19}, "
    "{%20, %21, %22, %23}, %24, p, 1, 1, 1;\n}\n"
    : "+f"(d[0]), "+f"(d[1]), "+f"(d[2]), "+f"(d[3]), "+f"(d[4]), "+f"(d[5]), "+f"(d[6]), "+f"(d[7]),
      "+f"(d[8]), "+f"(d[9]), "+f"(d[10]), "+f"(d[11]), "+f"(d[12]), "+f"(d[13]), "+f"(d[14]), "+f"(d[15]),
      "+f"(d[16]), "+f"(d[17]), "+f"(d[18]), "+f"(d[19])
    : "r"(a0), "r"(a1), "r"(a2), "r"(a3), "l"(db), "r"(scale_d));
}

__device__ __forceinline__ void wg_n64_rs_nb_f16_f32(float (&d)[32], uint32_t a0, uint32_t a1, uint32_t a2, uint32_t a3, uint64_t db, int scale_d) {
  asm volatile("{\n.reg .pred p;\nsetp.ne.b32 p, %37, 0;\n"
    "wgmma.mma_async.sync.aligned.m64n64k16.f32.f16.f16 "
    "{%0, %1, %2, %3, %4, %5, %6, %7, %8, %9, %10, %11, %12, %13, %14, %15, "
    "%16, %17, %18, %19, %20, %21, %22, %23, %24, %25, %26, %27, %28, %29, %30, %31}, "
    "{%32, %33, %34, %35}, %36, p, 1, 1, 0;\n}\n"
    : "+f"(d[0]), "+f"(d[1]), "+f"(d[2]), "+f"(d[3]), "+f"(d[4]), "+f"(d[5]), "+f"(d[6]), "+f"(d[7]),
      "+f"(d[8]), "+f"(d[9]), "+f"(d[10]), "+f"(d[11]), "+f"(d[12]), "+f"(d[13]), "+f"(d[14]), "+f"(d[15]),
      "+f"(d[16]), "+f"(d[17]), "+f"(d[18]), "+f"(d[19]), "+f"(d[20]), "+f"(d[21]), "+f"(d[22]), "+f"(d[23]),
      "+f"(d[24]), "+f"(d[25]), "+f"(d[26]), "+f"(d[27]), "+f"(d[28]), "+f"(d[29]), "+f"(d[30]), "+f"(d[31])
    : "r"(a0), "r"(a1), "r"(a2), "r"(a3), "l"(db), "r"(scale_d));
}

__device__ __forceinline__ void wg_n64_rs_nb_f16_f16(uint32_t (&d)[16], uint32_t a0, uint32_t a1, uint32_t a2, uint32_t a3, uint64_t db, int scale_d) {
  asm volatile("{\n.reg .pred p;\nsetp.ne.b32 p, %21, 0;\n"
    "wgmma.mma_async.sync.aligned.m64n64k16.f16.f16.f16 "
    "{%0, %1, %2, %3, %4, %5, %6, %7, %8, %9, %10, %11, %12, %13, %14, %15}, "
    "{%16, %17, %18, %19}, %20, p, 1, 1, 0;\n}\n"
    : "+r"(d[0]), "+r"(d[1]), "+r"(d[2]), "+r"(d[3]), "+r"(d[4]), "+r"(d[5]), "+r"(d[6]), "+r"(d[7]),
      "+r"(d[8]), "+r"(d[9]), "+r"(d[10]), "+r"(d[11]), "+r"(d[12]), "+r"(d[13]), "+r"(d[14]), "+r"(d[15])
    : "r"(a0), "r"(a1), "r"(a2), "r"(a3), "l"(db), "r"(scale_d));
}

__device__ __forceinline__ void wg_n64_rs_nb_f16_f32_z(float (&d)[32], uint32_t a0, uint32_t a1, uint32_t a2, uint32_t a3, uint64_t db, int scale_d) {
  asm volatile("{\n.reg .pred p;\nsetp.ne.b32 p, %37, 0;\n"
    "wgmma.mma_async.sync.aligned.m64n64k16.f32.f16.f16 "
    "{%0, %1, %2, %3, %4, %5, %6, %7, %8, %9, %10, %11, %12, %13, %14, %15, "
    "%16, %17, %18, %19, %20, %21, %22, %23, %24, %25, %26, %27, %28, %29, %30, %31}, "
    "{%32, %33, %34, %35}, %36, p, 1, 1, 0;\n}\n"
    : "=f"(d[0]), "=f"(d[1]), "=f"(d[2]), "=f"(d[3]), "=f"(d[4]), "=f"(d[5]), "=f"(d[6]), "=f"(d[7]),
      "=f"(d[8]), "=f"(d[9]), "=f"(d[10]), "=f"(d[11]), "=f"(d[12]), "=f"(d[13]), "=f"(d[14]), "=f"(d[15]),
      "=f"(d[16]), "=f"(d[17]), "=f"(d[18]), "=f"(d[19]), "=f"(d[20]), "=f"(d[21]), "=f"(d[22]), "=f"(d[23]),
      "=f"(d[24]), "=f"(d[25]), "=f"(d[26]), "=f"(d[27]), "=f"(d[28]), "=f"(d[29]), "=f"(d[30]), "=f"(d[31])
    : "r"(a0), "r"(a1), "r"(a2), "r"(a3), "l"(db), "r"(scale_d));
}

__device__ __forceinline__ void wg_n64_rs_nb_f16_f16_z(uint32_t (&d)[16], uint32_t a0, uint32_t a1, uint32_t a2, uint32_t a3, uint64_t db, int scale_d) {
  asm volatile("{\n.reg .pred p;\nsetp.ne.b32 p, %21, 0;\n"
    "wgmma.mma_async.sync.aligned.m64n64k16.f16.f16.f16 "
    "{%0, %1, %2, %3, %4, %5, %6, %7, %8, %9, %10, %11, %12, %13, %14, %15}, "
    "{%16, %17, %18, %19}, %20, p, 1, 1, 0;\n}\n"
    : "=r"(d[0]), "=r"(d[1]), "=r"(d[2]), "=r"(d[3]), "=r"(d[4]), "=r"(d[5]), "=r"(d[6]), "=r"(d[7]),
      "=r"(d[8]), "=r"(d[9]), "=r"(d[10]), "=r"(d[11]), "=r"(d[12]), "=r"(d[13]), "=r"(d[14]), "=r"(d[15])
    : "r"(a0), "r"(a1), "r"(a2), "r"(a3), "l"(db), "r"(scale_d));
}

#define DEVINL __device__ __forceinline__
DEVINL void wg_fence() { asm volatile("wgmma.fence.sync.aligned;" ::: "memory"); }
DEVINL void wg_commit() { asm volatile("wgmma.commit_group.sync.aligned;" ::: "memory"); }
template <int N> DEVINL void wg_wait() { asm volatile("wgmma.wait_group.sync.aligned %0;" ::"n"(N) : "memory"); }
__host__ DEVINL uint64_t mkdesc(uint32_t addr, uint32_t lbo, uint32_t sbo, int sw) {
  return (uint64_t)((addr & 0x3FFFF) >> 4) | ((uint64_t)(lbo >> 4) << 16) | ((uint64_t)(sbo >> 4) << 32) | ((uint64_t)sw << 62);
}
DEVINL void mbar_init(uint32_t bar, uint32_t cnt) { asm volatile("mbarrier.init.shared::cta.b64 [%0], %1;" ::"r"(bar), "r"(cnt) : "memory"); }
DEVINL void mbar_arrive(uint32_t bar) { asm volatile("mbarrier.arrive.shared::cta.b64 _, [%0];" ::"r"(bar) : "memory"); }
DEVINL bool mbar_try(uint32_t bar, uint32_t parity) {
  uint32_t ok;
  asm volatile("{\n.reg .pred p;\nmbarrier.try_wait.parity.shared::cta.b64 p, [%1], %2;\nselp.u32 %0, 1, 0, p;\n}" : "=r"(ok) : "r"(bar), "r"(parity) : "memory");
  return ok;
}
DEVINL bool mbar_test(uint32_t bar, uint32_t parity) {
  uint32_t ok;
  asm volatile("{\n.reg .pred p;\nmbarrier.test_wait.parity.shared::cta.b64 p, [%1], %2;\nselp.u32 %0, 1, 0, p;\n}" : "=r"(ok) : "r"(bar), "r"(parity) : "memory");
  return ok;
}
DEVINL void mbar_wait(uint32_t bar, uint32_t parity) {
#pragma unroll 1
  for (uint32_t n = 0; n < 100000u; n++) if (mbar_try(bar, parity)) break;
}
#define EL(txt) "{\n.reg .pred pe;\nelect.sync _|pe, 0xffffffff;\n@pe " txt "\n}"
DEVINL void e_expect_tx(uint32_t bar, uint32_t bytes) { asm volatile(EL("mbarrier.arrive.expect_tx.shared::cta.b64 _, [%0], %1;") ::"r"(bar), "r"(bytes) : "memory"); }
DEVINL void e_arrive(uint32_t bar) { asm volatile(EL("mbarrier.arrive.shared::cta.b64 _, [%0];") ::"r"(bar) : "memory"); }
DEVINL void e_arrive_if(uint32_t bar, int c) {
  asm volatile("{\n.reg .pred pe;\nelect.sync _|pe, 0xffffffff;\nsetp.ne.and.b32 pe, %1, 0, pe;\n@pe mbarrier.arrive.shared::cta.b64 _, [%0];\n}" ::"r"(bar), "r"(c) : "memory");
}
DEVINL void e_red(uint32_t* p) { asm volatile(EL("red.release.gpu.global.add.u32 [%0], 1;") ::"l"(p) : "memory"); }
DEVINL void e_red_relaxed(uint32_t* p) { asm volatile(EL("red.relaxed.gpu.global.add.u32 [%0], 1;") ::"l"(p) : "memory"); }
DEVINL void tma_ld(uint32_t dst, const CUtensorMap* m, int c0, int c1, uint32_t bar) {
  asm volatile(EL("cp.async.bulk.tensor.2d.shared::cluster.global.mbarrier::complete_tx::bytes [%0], [%1, {%3, %4}], [%2];")
               ::"r"(dst), "l"(m), "r"(bar), "r"(c0), "r"(c1) : "memory");
}
DEVINL void tma_ld3(uint32_t dst, const CUtensorMap* m, int c0, int c1, int c2, uint32_t bar) {
  asm volatile(EL("cp.async.bulk.tensor.3d.shared::cluster.global.mbarrier::complete_tx::bytes [%0], [%1, {%3, %4, %5}], [%2];")
               ::"r"(dst), "l"(m), "r"(bar), "r"(c0), "r"(c1), "r"(c2) : "memory");
}
DEVINL void tma_ld5(uint32_t dst, const CUtensorMap* m, int c2, int c3, int c4, uint32_t bar) {
  asm volatile(EL("cp.async.bulk.tensor.5d.shared::cluster.global.mbarrier::complete_tx::bytes [%0], [%1, {0, 0, %3, %4, %5}], [%2];")
               ::"r"(dst), "l"(m), "r"(bar), "r"(c2), "r"(c3), "r"(c4) : "memory");
}
DEVINL void tma_ld_mc(uint32_t dst, const CUtensorMap* m, int c0, int c1, uint32_t bar) {
  asm volatile(EL("cp.async.bulk.tensor.2d.shared::cluster.global.mbarrier::complete_tx::bytes.multicast::cluster [%0], [%1, {%3, %4}], [%2], %5;")
               ::"r"(dst), "l"(m), "r"(bar), "r"(c0), "r"(c1), "h"((uint16_t)3) : "memory");
}
DEVINL void e_arrive_both(uint32_t bar) {
  asm volatile("{\n.reg .pred pe;\n.reg .b32 r0, r1;\nelect.sync _|pe, 0xffffffff;\nmapa.shared::cluster.u32 r0, %0, 0;\nmapa.shared::cluster.u32 r1, %0, 1;\n"
               "@pe mbarrier.arrive.shared::cluster.b64 _, [r0];\n@pe mbarrier.arrive.shared::cluster.b64 _, [r1];\n}" ::"r"(bar) : "memory");
}
DEVINL void tma_st(const CUtensorMap* m, int c0, int c1, uint32_t src) {
  asm volatile(EL("cp.async.bulk.tensor.2d.global.shared::cta.bulk_group [%0, {%2, %3}], [%1];") ::"l"(m), "r"(src), "r"(c0), "r"(c1) : "memory");
}
DEVINL void bulk_commit() { asm volatile("cp.async.bulk.commit_group;" ::: "memory"); }
template <int N> DEVINL void bulk_wait_n() { asm volatile("cp.async.bulk.wait_group %0;\nbar.warp.sync 0xffffffff;" ::"n"(N) : "memory"); }
DEVINL void l2_prefetch(const void* g, uint32_t bytes) { asm volatile(EL("cp.async.bulk.prefetch.L2.global [%0], %1;") ::"l"(g), "r"(bytes) : "memory"); }
DEVINL void fence_async_smem() { asm volatile("fence.proxy.async.shared::cta;" ::: "memory"); }
DEVINL void fence_async_gl() { asm volatile("fence.proxy.async.global;" ::: "memory"); }
DEVINL void cluster_wait() { asm volatile("barrier.cluster.wait.aligned;" ::: "memory"); }
DEVINL void bar_sync(int id, int n) { asm volatile("bar.sync %0, %1;" ::"r"(id), "r"(n) : "memory"); }
DEVINL void bar_arrive(int id, int n) { asm volatile("bar.arrive %0, %1;" ::"r"(id), "r"(n) : "memory"); }
DEVINL uint32_t ld_acquire(const uint32_t* p) { uint32_t v; asm volatile("ld.acquire.gpu.global.u32 %0, [%1];" : "=r"(v) : "l"(p) : "memory"); return v; }
DEVINL void await_flag(int j, uint32_t& rdy, const uint32_t* p, uint32_t target) {
  if ((rdy >> j) & 1) return;
#pragma unroll 1
  for (uint32_t n = 0; n < 200000u && !((rdy >> j) & 1); n++) rdy = __ballot_sync(~0u, (int)(ld_acquire(p) - target) >= 0);
  asm volatile("fence.proxy.async.global;" ::: "memory");
}
DEVINL void poll_ge(const uint32_t* p, uint32_t target) {
#pragma unroll 1
  for (uint32_t n = 0; n < 200000u; n++) if (__all_sync(~0u, (int)(ld_acquire(p) - target) >= 0)) break;
}
DEVINL int lane_id() { int v; asm volatile("mov.u32 %0, %%laneid;" : "=r"(v)); return v; }
__host__ DEVINL int remap(int v) {
  const int c = v >> 1, u = c - 36, r = (u * 37) >> 8;
  const int L = c < 4 ? 32 + 8 * c : c < 36 ? c - 4 : 33 + u + r;
  return 2 * L + (v & 1);
}
DEVINL int block_id() { int v; asm volatile("mov.u32 %0, %%ctaid.x;" : "=r"(v)); return v; }
#define cta_id() prm.map[block_id()]
#define IDS() const int lane = lane_id(), b = cta_id(), bm = b >> 4, bn = b & 15, rank = b & 1, pm = 2 * bm + (bn >> 3), pn = bn & 7, po = pm & 1; \
  (void)lane; (void)bm; (void)bn; (void)rank; (void)pm; (void)pn; (void)po
DEVINL void st_tagged(uint4* p, uint32_t a, uint32_t b, uint32_t c, uint32_t tag) {
  asm volatile("{\n.reg .b64 u, v;\n.reg .b128 t;\nmov.b64 u, {%1, %2};\nmov.b64 v, {%3, %4};\nmov.b128 t, {u, v};\nst.relaxed.gpu.global.b128 [%0], t;\n}"
               ::"l"(p), "r"(a), "r"(b), "r"(c), "r"(tag) : "memory");
}
DEVINL uint32_t ld_tagged(const uint4* p, uint32_t* r) {
  uint32_t tag;
  asm volatile("{\n.reg .b64 u, v;\n.reg .b128 t;\nld.relaxed.gpu.global.b128 t, [%4];\nmov.b128 {u, v}, t;\nmov.b64 {%0, %1}, u;\nmov.b64 {%2, %3}, v;\n}"
               : "=r"(r[0]), "=r"(r[1]), "=r"(r[2]), "=r"(tag) : "l"(p) : "memory");
  return tag;
}
DEVINL float ex2(float x) { float y; asm("ex2.approx.ftz.f32 %0, %1;" : "=f"(y) : "f"(x)); return y; }
DEVINL float rcp(float x) { float y; asm("rcp.approx.ftz.f32 %0, %1;" : "=f"(y) : "f"(x)); return y; }
DEVINL uint32_t pack2(float lo, float hi) { uint32_t r; asm("cvt.rn.bf16x2.f32 %0, %1, %2;" : "=r"(r) : "f"(hi), "f"(lo)); return r; }
DEVINL uint32_t pack2h(float lo, float hi) { uint32_t r; asm("cvt.rn.f16x2.f32 %0, %1, %2;" : "=r"(r) : "f"(hi), "f"(lo)); return r; }
DEVINL uint32_t prmt0(uint32_t a, uint32_t sel) { uint32_t r; asm("prmt.b32 %0, %1, 0, %2;" : "=r"(r) : "r"(a), "r"(sel)); return r; }
DEVINL void stg128(const void* p, uint32_t a, uint32_t b, uint32_t c, uint32_t d) {
  asm volatile("st.global.v4.b32 [%0], {%1, %2, %3, %4};" ::"l"(p), "r"(a), "r"(b), "r"(c), "r"(d) : "memory");
}
DEVINL float bf_lo(uint32_t w) { return __uint_as_float(w << 16); }
DEVINL float bf_hi(uint32_t w) { return __uint_as_float(w & 0xFFFF0000u); }
DEVINL float bf_round(float x) { return bf_lo(pack2(x, 0.f)); }
DEVINL uint32_t add_bf16x2(uint32_t a, uint32_t b) { uint32_t r; asm("add.rn.bf16x2 %0, %1, %2;" : "=r"(r) : "r"(a), "r"(b)); return r; }
DEVINL void stsm4(uint32_t addr, uint32_t a, uint32_t b, uint32_t c, uint32_t d) {
  asm volatile("stmatrix.sync.aligned.m8n8.x4.shared.b16 [%0], {%1, %2, %3, %4};" ::"r"(addr), "r"(a), "r"(b), "r"(c), "r"(d) : "memory");
}
DEVINL void ldsm4(uint32_t addr, uint32_t (&r)[4]) {
  asm volatile("ldmatrix.sync.aligned.m8n8.x4.shared.b16 {%0, %1, %2, %3}, [%4];" : "=r"(r[0]), "=r"(r[1]), "=r"(r[2]), "=r"(r[3]) : "r"(addr) : "memory");
}
DEVINL void ldsm4t(uint32_t addr, uint32_t (&r)[4]) {
  asm volatile("ldmatrix.sync.aligned.m8n8.x4.trans.shared.b16 {%0, %1, %2, %3}, [%4];" : "=r"(r[0]), "=r"(r[1]), "=r"(r[2]), "=r"(r[3]) : "r"(addr) : "memory");
}
DEVINL void sts128(uint32_t addr, uint32_t a, uint32_t b, uint32_t c, uint32_t d) {
  asm volatile("st.shared.v4.b32 [%0], {%1, %2, %3, %4};" ::"r"(addr), "r"(a), "r"(b), "r"(c), "r"(d) : "memory");
}
DEVINL float2 lds64f(uint32_t addr) { float2 v; asm volatile("ld.shared.v2.f32 {%0, %1}, [%2];" : "=f"(v.x), "=f"(v.y) : "r"(addr) : "memory"); return v; }
DEVINL void mma16816(float (&d)[4], uint32_t a0, uint32_t a1, uint32_t a2, uint32_t a3, uint32_t b0, uint32_t b1) {
  asm("mma.sync.aligned.m16n8k16.row.col.f32.bf16.bf16.f32 {%0, %1, %2, %3}, {%4, %5, %6, %7}, {%8, %9}, {%0, %1, %2, %3};"
               : "+f"(d[0]), "+f"(d[1]), "+f"(d[2]), "+f"(d[3]) : "r"(a0), "r"(a1), "r"(a2), "r"(a3), "r"(b0), "r"(b1));
}
template <int N> DEVINL void fence_regs(float (&d)[N]) {
#pragma unroll
  for (int i = 0; i < N; i++) asm volatile("" : "+f"(d[i])::"memory");
}
template <int N> DEVINL void fence_regs(uint32_t (&d)[N]) {
#pragma unroll
  for (int i = 0; i < N; i++) asm volatile("" : "+r"(d[i])::"memory");
}
DEVINL void lds128(uint32_t addr, uint32_t* r) {
  asm volatile("ld.shared.v4.b32 {%0, %1, %2, %3}, [%4];" : "=r"(r[0]), "=r"(r[1]), "=r"(r[2]), "=r"(r[3]) : "r"(addr) : "memory");
}
DEVINL void sched_fence() { asm volatile("griddepcontrol.launch_dependents;" ::: "memory"); }

struct Scratch {
  bf16 k[32 * 2048 * 32];
  bf16 xs[2048 * 1024];
  bf16 os[2048 * 1024];
  bf16 v[32 * 2048 * 32];
  float kn[2 * 128 * 16];
  uint32_t cnt[256 * 32];
  float2 stats[8 * 2048];
  uint4 halo[2 * 128 * 12 * 32];
  float csp[2 * 16 * 8 * 192];
  uint4 qsave[128 * 256 * 8];
  uint32_t esc[4 * 65536 * 20];
};
__device__ __align__(1024) Scratch g_s;
#define g_k g_s.k
#define g_xs g_s.xs
#define g_os g_s.os
#define g_v g_s.v
#define g_kn g_s.kn
#define g_cnt g_s.cnt
#define g_stats g_s.stats
#define g_halo g_s.halo
#define g_csp g_s.csp
#define g_qsave g_s.qsave
#define g_esc g_s.esc
#define g_epoch g_s.cnt[255 * 32]

DEVINL uint32_t* cnt_x(int l, int bm) { return g_cnt + (l * 8 + bm) * 32; }
DEVINL uint32_t* cnt_o(int l, int pm, int h) { return g_cnt + (32 + (l * 16 + pm) * 2 + h) * 32; }
DEVINL uint32_t* cnt_kv(int lb, int bn) { return g_cnt + (160 + lb * 16 + bn) * 32; }
DEVINL uint32_t* cnt_ad(int bn) { return g_cnt + (192 + bn) * 32; }
DEVINL uint32_t* cnt_cs(int t, int bn) { return g_cnt + (208 + t * 16 + bn) * 32; }

DEVINL int qord(int i, int l, int pn) { return l == 0 ? i : i < 4 ? ((2 * pn) ^ (i & 2)) + (i & 1) : i - 4 < 2 * (pn & 6) ? i - 4 : i; }
struct Params {
  CUtensorMap m[15];
  const bf16* x0;
  const bf16* wq[2];
  uint32_t zero;
  int map[128];
  uint64_t wd, xd;
  struct __align__(16) { uint64_t kd, vd; } kv[4];
};
enum { M_X0A = 0, M_XSA, M_WQA, M_WQB, M_WOA, M_WOB, M_OS, M_K, M_V, M_X0R, M_XSR, M_XSO, M_OUT, M_XST, M_X0H, M_COUNT };

constexpr uint32_t QSTG = 57344;
constexpr uint32_t T0 = 65536, TSTG = 32768;
constexpr uint32_t ONES = 230400;
constexpr uint32_t PSTG = 32768, RES = 196608;
constexpr uint32_t KSC = 98304, VSC = 133120, HRS = 167936;
constexpr uint32_t ROWST = 229376, COLS = 231424, BARS = 232192, SMEM_BYTES = 232448;
constexpr uint32_t B_QF = BARS, B_QE = BARS + 32, B_TF = BARS + 64, B_TE = BARS + 96, B_PF = BARS + 128, B_PE = BARS + 176,
                   B_RF = BARS + 224, W_X = BARS + 232, B_QL = BARS + 240, B_PA = BARS + 248;
enum { NB_ST = 1, NB_KV = 2  , NB_DONE = 3, NB_SC = 4, NB_SIG = 5  , NB_KN = 9  , NB_X = 11, NB_HALO = 12  , NB_X0 = 15 };

DEVINL uint32_t pslot_b(uint32_t s) { return ((0x320415u >> (4 * s)) & 7) * 16384u; }
DEVINL uint32_t pslot_a(uint32_t s, int l) { return 98304u + ((((l & 1) ? 0x541230u : 0x041235u) >> (4 * s)) & 7) * 16384u; }

constexpr float QSCALE = 0.17677669529663687f * 1.4426950408889634f;
constexpr uint32_t QPARK = 32768;

DEVINL uint32_t exp2_h2(uint32_t s, uint32_t c852) {
  uint32_t r, t, w, m, d;
  asm volatile("{.reg .b64 t; add.rn.f16x2 %0, %1, %2; cvt.u64.u32 t, %0; cvt.u32.u64 %0, t;}" : "=r"(r) : "r"(s), "r"(0x65EA65EAu));
  asm volatile("fma.rn.f16x2 %0, %1, %2, %3;" : "=r"(t) : "r"(r), "r"(0xB880B880u), "r"(c852));
  asm volatile("fma.rn.f16x2 %0, %1, %2, %3;" : "=r"(w) : "r"(s), "r"(0x38803880u), "r"(t));
  asm volatile("fma.rn.f16x2 %0, %1, %1, %2;" : "=r"(m) : "r"(w), "r"(0x4A1F4A2Du));
  asm volatile("{.reg .b32 t; shf.l.clamp.b32 t, %2, %1, 7; add.u32 %0, t, %2;}" : "=r"(d) : "r"(r), "r"(m));
  return d;
}
DEVINL float exp2_fix(float s) { float z; asm volatile("add.rn.f32 %0, %1, 0f43BF34BC;" : "=f"(z) : "f"(s)); return z; }
DEVINL uint32_t exp2_base(float z0, float z1) { uint32_t B; asm volatile("prmt.b32 %0, %1, %2, 0x6521;" : "=r"(B) : "r"(__float_as_uint(z0)), "r"(__float_as_uint(z1))); return B; }
template <uint32_t MASK> DEVINL uint32_t and_or(uint32_t a, uint32_t c) { uint32_t r; asm volatile("lop3.b32 %0, %1, %3, %2, 0xEA;" : "=r"(r) : "r"(a), "r"(c), "n"(MASK)); return r; }
DEVINL uint32_t fma_bf2(uint32_t a, uint32_t b, uint32_t c) { uint32_t r; asm volatile("fma.rn.bf16x2 %0, %1, %2, %3;" : "=r"(r) : "r"(a), "r"(b), "r"(c)); return r; }
DEVINL float ex2v(float x) { float y; asm volatile("ex2.approx.ftz.f32 %0, %1;" : "=f"(y) : "f"(x)); return y; }
DEVINL uint32_t pack2v(float lo, float hi) { uint32_t r; asm volatile("cvt.rn.bf16x2.f32 %0, %1, %2;" : "=r"(r) : "f"(hi), "f"(lo)); return r; }
DEVINL void unesc(uint32_t (&u)[4], const uint32_t* esc, uint32_t tag) {
  const bool saved = __ldcg(esc + 16) == tag;
#pragma unroll
  for (int j = 0; j < 4; j++) {
    float lo, hi;
    asm("{.reg .f16 a, b; mov.b32 {a, b}, %2; cvt.f32.f16 %0, a; cvt.f32.f16 %1, b;}" : "=f"(lo), "=f"(hi) : "r"(u[j]));
    u[j] = saved ? __ldcg(esc + 4 * j) : pack2(lo, hi);
  }
}

DEVINL void attn_slow(const uint32_t (&q)[8], int head, const uint32_t* kesc, uint32_t tag, float (&res)[20], int lane) {
  const int g = lane >> 2, qd = lane & 3;
  const bf16* kb = g_k + (size_t)head * 2048 * 32;
  const bf16* vb = g_v + (size_t)head * 2048 * 32;
  float o[4][4], m0 = -INFINITY, m1 = -INFINITY, l0 = 0.f, l1 = 0.f;
#pragma unroll
  for (int j = 0; j < 4; j++) { o[j][0] = o[j][1] = o[j][2] = o[j][3] = 0.f; }
#pragma unroll 1
  for (int k0 = 0; k0 < 2048; k0 += 16) {
    float s[2][4];
#pragma unroll
    for (int nt = 0; nt < 2; nt++) {
      s[nt][0] = s[nt][1] = s[nt][2] = s[nt][3] = 0.f;
      const uint32_t* kp = (const uint32_t*)(kb + (size_t)(k0 + nt * 8 + g) * 32) + qd;
      uint32_t k[4] = {__ldcg(kp), __ldcg(kp + 4), __ldcg(kp + 8), __ldcg(kp + 12)};
      unesc(k, kesc + (k0 + nt * 8 + g) * 20 + qd, tag);
      __syncwarp();
      mma16816(s[nt], q[0], q[1], q[2], q[3], k[0], k[1]);
      mma16816(s[nt], q[4], q[5], q[6], q[7], k[2], k[3]);
    }
    float a0 = fmaxf(fmaxf(s[0][0], s[0][1]), fmaxf(s[1][0], s[1][1]));
    float a1 = fmaxf(fmaxf(s[0][2], s[0][3]), fmaxf(s[1][2], s[1][3]));
    a0 = fmaxf(a0, __shfl_xor_sync(~0u, a0, 1)); a0 = fmaxf(a0, __shfl_xor_sync(~0u, a0, 2));
    a1 = fmaxf(a1, __shfl_xor_sync(~0u, a1, 1)); a1 = fmaxf(a1, __shfl_xor_sync(~0u, a1, 2));
    const float n0 = fmaxf(m0, a0), n1 = fmaxf(m1, a1);
    const float c0 = (m0 == n0) ? 1.f : ex2(m0 - n0), c1 = (m1 == n1) ? 1.f : ex2(m1 - n1);
    m0 = n0; m1 = n1;
    const uint32_t p0 = pack2(ex2(s[0][0] - n0), ex2(s[0][1] - n0)), p1 = pack2(ex2(s[0][2] - n1), ex2(s[0][3] - n1));
    const uint32_t p2 = pack2(ex2(s[1][0] - n0), ex2(s[1][1] - n0)), p3 = pack2(ex2(s[1][2] - n1), ex2(s[1][3] - n1));
    l0 = l0 * c0 + bf_lo(p0) + bf_hi(p0) + bf_lo(p2) + bf_hi(p2);
    l1 = l1 * c1 + bf_lo(p1) + bf_hi(p1) + bf_lo(p3) + bf_hi(p3);
#pragma unroll
    for (int j = 0; j < 4; j++) {
      o[j][0] *= c0; o[j][1] *= c0; o[j][2] *= c1; o[j][3] *= c1;
      const unsigned short* vp = (const unsigned short*)(vb + (size_t)(k0 + 2 * qd) * 32 + j * 8 + g);
      const uint32_t b0 = (uint32_t)__ldcg(vp) | ((uint32_t)__ldcg(vp + 32) << 16);
      const uint32_t b1 = (uint32_t)__ldcg(vp + 256) | ((uint32_t)__ldcg(vp + 288) << 16);
      mma16816(o[j], p0, p1, p2, p3, b0, b1);
    }
  }
  l0 += __shfl_xor_sync(~0u, l0, 1); l0 += __shfl_xor_sync(~0u, l0, 2);
  l1 += __shfl_xor_sync(~0u, l1, 1); l1 += __shfl_xor_sync(~0u, l1, 2);
#pragma unroll
  for (int j = 0; j < 4; j++) { res[4 * j] = o[j][0]; res[4 * j + 1] = o[j][1]; res[4 * j + 2] = o[j][2]; res[4 * j + 3] = o[j][3]; }
  res[16] = l0; res[18] = l1;
}

__device__ __noinline__ void attn_redo(int redo, int l, int b, int wg, int w, uint32_t tag) {
  const int lane = lane_id();
#pragma unroll 1
  for (int t = 0; t < 4; t++) {
    const int h = t >> 1, head = 2 * (b & 15) + h, row = (b >> 4) * 256 + wg * 128 + (t & 1) * 64 + w * 16 + (lane >> 2);
    if ((redo >> t) & 1) {
      const uint32_t* esc = g_esc + (size_t)((l & 2) * 65536 + head * 2048) * 20;
      const uint32_t* qs = (const uint32_t*)(g_qsave + (block_id() * 256 + wg * 128 + w * 32 + lane) * 8 + 2 * t);
      uint32_t q[8]; float o[20];
#pragma unroll
      for (int i = 0; i < 2; i++) {
        uint32_t u[4] = {__ldcg(qs + i), __ldcg(qs + i + 2), __ldcg(qs + i + 4), __ldcg(qs + i + 6)};
        unesc(u, esc + (row + i * 8) * 20 + (lane & 3), tag);
        q[i] = u[0]; q[i + 2] = u[1]; q[i + 4] = u[2]; q[i + 6] = u[3];
      }
      __syncwarp();
      attn_slow(q, head, esc + 65536 * 20, tag, o, lane);
      const float i0 = rcp(o[16]), i1 = rcp(o[18]);
      bf16* op = g_os + (size_t)row * 1024 + h * 512 + (b & 15) * 32 + (lane & 3) * 8;
      *(uint4*)op = make_uint4(pack2(o[0] * i0, o[1] * i0), pack2(o[4] * i0, o[5] * i0), pack2(o[8] * i0, o[9] * i0), pack2(o[12] * i0, o[13] * i0));
      *(uint4*)(op + 8 * 1024) = make_uint4(pack2(o[2] * i1, o[3] * i1), pack2(o[6] * i1, o[7] * i1), pack2(o[10] * i1, o[11] * i1), pack2(o[14] * i1, o[15] * i1));
    }
    if ((t & 1) && ((redo >> 2 * h) & 3)) bar_arrive(NB_SIG + 2 * h + wg, 160);
  }
}

__global__ void __cluster_dims__(2, 1, 1) __launch_bounds__(384, 1) fused_kernel(const __grid_constant__ Params prm) {
  extern __shared__ __align__(1024) char smem[];
  const uint32_t sb = (uint32_t)__cvta_generic_to_shared(smem);
  const int tid = threadIdx.x, lane = tid & 31;
  const int wg = __shfl_sync(0xffffffffu, tid >> 7, 0);
  const int w = __shfl_sync(0xffffffffu, (tid >> 5) & 3, 0);
  const int bm = remap(blockIdx.x) >> 4, bn = remap(blockIdx.x) & 15;

  auto first_tile = [&](int kt) {
    e_expect_tx(sb + B_QF + 8 * kt, QSTG);
    tma_ld(sb + kt * QSTG, &prm.m[M_X0A], kt * 64, bm * 256, sb + B_QF + 8 * kt);
    tma_ld3(sb + kt * QSTG + 32768, &prm.m[M_WQA], bn * 64, kt * 64, 0, sb + B_QF + 8 * kt);
  };
  auto init4 = [&](uint32_t bar, uint32_t c0, uint32_t c1, uint32_t c2, uint32_t c3) {
    asm volatile("{\n.reg .pred pe;\nelect.sync _|pe, 0xffffffff;\n@pe mbarrier.init.shared::cta.b64 [%0], %1;\n@pe mbarrier.init.shared::cta.b64 [%0+8], %2;\n"
                 "@pe mbarrier.init.shared::cta.b64 [%0+16], %3;\n@pe mbarrier.init.shared::cta.b64 [%0+24], %4;\n@pe fence.mbarrier_init.release.cluster;\n}"
                 ::"r"(bar), "r"(c0), "r"(c1), "r"(c2), "r"(c3) : "memory");
  };
  if (wg < 2) {
    const uint32_t k = wg * 4 + w, lo = (0x1411814u >> (4 * k)) & 15, hi = (0x1441814u >> (4 * k)) & 15;
    if (tid < 32) asm volatile("prefetch.global.L2 [%0];" ::"l"(prm.x0 + (size_t)(bm * 256 + bn * 16 + (tid & 15)) * 1024 + (tid >> 4) * 64));
    else if (tid < 80) asm volatile("prefetch.global.L2 [%0];" ::"l"(prm.wq[0] + (bm * 16 + (tid & 15)) * 3072 + ((tid >> 4) - 2) * 1024 + bn * 64));
    __syncwarp();
    if (k < 7) init4(sb + B_QE + 32 * k, lo, lo, hi, k == 6 ? 2 : hi);
    __syncwarp();
    if (k == 6 && lane == 0) *(volatile unsigned long long*)(smem + W_X) = 0ull;
  } else if (w == 0) {
    init4(sb + B_QF, 1, 1, 1, 1);
    __syncwarp();
    first_tile(0);
  }
  __syncthreads();
  asm volatile("barrier.cluster.arrive.relaxed.aligned;" ::: "memory");

  if (wg == 2) {
    asm volatile("setmaxnreg.dec.sync.aligned.u32 56;");
    const uint32_t ep1 = *(volatile uint32_t*)&g_epoch + 1;
    if (w == 0) {
      first_tile(1);
      mbar_wait(sb + B_QF, 0);
      first_tile(2); first_tile(3);
#pragma unroll 1
      for (int kt = 4; kt < 16; kt++) l2_prefetch(prm.wq[0] + kt * 196608 + blockIdx.x * 1536, 3072);
      cluster_wait();
#pragma unroll 1
      for (int l = 0; l < 4; l++) {
        IDS();
        const CUtensorMap* mw = &prm.m[M_WQA + (l & 1)];
        const CUtensorMap* mx = &prm.m[l == 0 ? M_X0A : M_XSA];
        const CUtensorMap* mh = &prm.m[l == 0 ? M_X0H : M_XSO];
        const CUtensorMap* mo = &prm.m[M_WOA + (l & 1)];
        auto q_b = [&](int i) {
          const int s = i & 3;
          mbar_wait(sb + B_QE + 8 * s, ((i >> 2) & 1) ^ 1);
          e_expect_tx(sb + B_QF + 8 * s, QSTG);
          tma_ld3(sb + s * QSTG + 32768, mw, bn * 64, qord(i, l, pn) * 64, 0, sb + B_QF + 8 * s);
        };
        uint32_t rdy = l ? 0u : ~0u;
        auto q_a = [&](int i) {
          const int kt = qord(i, l, pn);
          await_flag(kt, rdy, cnt_x(l, bm) + (lane & 15), ep1 * 2);
          if (i < 4) tma_ld(sb + i * QSTG, mx, kt * 64, bm * 256, sb + B_QF + 8 * i);
          else tma_ld_mc(sb + (i & 3) * QSTG + rank * 16384, mh, kt * 64, bm * 256 + rank * 128, sb + B_QF + 8 * (i & 3));
        };
        if (l > 0) {
#pragma unroll 1
          for (int i = 0; i < 2; i++) {
            await_flag(2 * pn + i, rdy, cnt_x(l, bm) + (lane & 15), ep1 * 2);
            e_expect_tx(sb + B_QF + 8 * i, 16384);
            tma_ld(sb + i * QSTG + (po ^ 1) * 16384, &prm.m[M_XSO], (2 * pn + i) * 64, (pm ^ 1) * 128, sb + B_QF + 8 * i);
            if (i == 0) {  q_a(2); }
          }
          mbar_wait(sb + B_QF + 8, 0);
        }
#pragma unroll 1
        for (int i = l ? 3 : 4; i < 16; i++) {
          if (l == 3 && i == 12) poll_ge(cnt_ad(bn), ep1 * 16);
          q_b(i); q_a(i);
        }
        if (l & 1) {
          bar_sync(NB_KV, 288);
          sts128(sb + ONES + lane * 32, 0x3f803f80u, 0x3f803f80u, 0x3f803f80u, 0x3f803f80u);
          sts128(sb + ONES + lane * 32 + 16, 0x3f803f80u, 0x3f803f80u, 0x3f803f80u, 0x3f803f80u);
          fence_async_smem();
          __syncwarp();
          e_arrive(sb + B_TF);
          const int krow = 2 * bn * 2048 + bm * 256;
          uint32_t* kvc = cnt_kv(l >> 1, bn);
          uint32_t seen = 0;
#pragma unroll 1
          for (int it = 1; it < 16; it++) {
            const int s = it & 3;
            if (it == 4) {
              bar_sync(NB_KV + 12, 288);
              mbar_wait(sb + B_TF + 24, 0);
#pragma unroll 1
              for (int i = 0; i < 4; i++) tma_st(&prm.m[M_K + (i >> 1)], 0, krow + 2048 + (i & 1) * 128, sb + i * 8192);
              bulk_commit();
            }
            if (it == 5) { bulk_wait_n<0>(); e_red(kvc + 16 + bm); }
            if (it == 12) { e_expect_tx(sb + B_RF, 32768); tma_ld3(sb + RES, &prm.m[M_XSR], 0, pm * 128, 2 * pn, sb + B_RF); }
            mbar_wait(sb + B_TE + 8 * s, ((it >> 2) & 1) ^ 1);
            if (it < 8) {
#pragma unroll 1
              for (uint32_t n = 0; n < 200000u && (~seen & (3u << (2 * it - 2) | (it == 4 ? 0xC000u : 0u))); n++)
                seen = __ballot_sync(~0u, (int)(ld_acquire(kvc + (lane < 7 || lane == 15 ? (bm + 1 + lane) & 7 : 8 + ((bm + 2 + lane) & 7))) - ep1) >= 0);
              fence_async_gl();
            } else if (it == 8) { poll_ge(kvc + 16 + (lane & 7), ep1); fence_async_gl(); }
            e_expect_tx(sb + B_TF + 8 * s, 32768);
#pragma unroll 1
            for (int i = 0; i < 2; i++) {
              const int u = 2 * it - 2 + i;
              const int row = 2 * bn * 2048 + (it > 7 ? 2048 + ((bm + it) & 7) * 256 + i * 128 : u < 7 ? ((bm + 1 + u) & 7) * 256 : ((bm + 2 + u) & 7) * 256 + 128);
              tma_ld(sb + T0 + s * TSTG + i * 8192, &prm.m[M_K], 0, row, sb + B_TF + 8 * s);
              tma_ld(sb + T0 + s * TSTG + 16384 + i * 8192, &prm.m[M_V], 0, row, sb + B_TF + 8 * s);
            }
          }
        }
        auto p_b = [&](int i, uint32_t s, uint32_t par) {
          mbar_wait(sb + B_PE + 8 * s, par ^ 1);
          e_expect_tx(sb + B_PF + 8 * s, PSTG);
          tma_ld5(sb + pslot_b(s), mo, i >> 3, 2 * (i & 7), 2 * pn, sb + B_PF + 8 * s);
        };
        auto p_a = [&](int i, uint32_t s) {
          await_flag(i, rdy, cnt_o(l, pm, (lane >> 3) & 1) + (lane & 7), ep1 * 2);
          tma_ld_mc(sb + pslot_a(s, l) + rank * 8192, &prm.m[M_OS], i * 64, pm * 128 + rank * 64, sb + B_PF + 8 * s);
        };
        auto p_a2 = [&](int i) {
          await_flag(i, rdy, cnt_o(l, pm, (lane >> 3) & 1) + (lane & 7), ep1 * 2);
          tma_ld(sb + pslot_a(i, l), &prm.m[M_OS], i * 64, pm * 128, sb + B_PF + 8 * i);
          tma_ld(sb + pslot_a(i, l) + 8192, &prm.m[M_OS], i * 64, pm * 128 + 64, sb + B_PF + 8 * i);
        };
        rdy = 0;
        if (l & 1) {
#pragma unroll 1
          for (int u = 0; u < 6; u++) { const int i = (0x205413 >> (4 * u)) & 7; if (u == 4) mbar_wait(sb + B_TE, 1); p_b(i, i, i < 4 ? 1 : 0); }
#pragma unroll 1
          for (int u = 0; u < 6; u++) {
            const int i = (0x542130 >> (4 * u)) & 7;
            if (!(u & 1)) mbar_wait(sb + B_TE + 8 + 4 * u, 1);
            if (u == 4) bar_sync(NB_ST, 64);
            p_a2(i);
          }
        } else {
#pragma unroll 1
          for (int u = 0; u < 6; u++) { const int i = (0x025413 >> (4 * u)) & 7; if (u == 0 || u == 3) mbar_wait(sb + B_QE + 8 * (u / 3), 1); p_b(i, i, 0); }
          mbar_wait(sb + B_QE + 24, 1);
          e_expect_tx(sb + B_RF, 32768);
          tma_ld3(sb + RES, &prm.m[l == 0 ? M_X0R : M_XSR], 0, pm * 128, 2 * pn, sb + B_RF);
          p_a2(0);
          bar_sync(NB_DONE, 64);
          e_arrive_both(sb + B_PA);
          p_a2(1);
          mbar_wait(sb + B_PA, (l >> 1) & 1);
#pragma unroll 1
          for (int i = 2; i < 6; i++) { if (i > 2) mbar_wait(sb + B_PF + 8 * (i - 3), 0); p_a(i, i); }
        }
        uint32_t s = 0, lap = 1;
#pragma unroll 1
        for (int i = 6; i < 16; i++) {
          p_b(i, s, ((s < 4 ? l : 0) + lap) & 1);
          p_a(i, s);
          if (++s == 6) { s = 0; lap++; }
        }
        const CUtensorMap* mn = &prm.m[M_WQA + ((l + 1) & 1)];
        if (l < 3) {
          mbar_wait(sb + B_PE + 8 * 4, 1); mbar_wait(sb + B_PE + 8 * 5, 1);
          tma_ld3(sb + 32768, mn, bn * 64, 2 * pn * 64, 0, sb + B_QL);
          mbar_wait(sb + B_PE + 8 * 0, l & 1);
          tma_ld3(sb + QSTG + 32768, mn, bn * 64, (2 * pn + 1) * 64, 0, sb + B_QL);
          mbar_wait(sb + B_PE + 8 * 1, l & 1);
          e_expect_tx(sb + B_QF + 16, QSTG);
          tma_ld3(sb + 2 * QSTG + 32768, mn, bn * 64, ((2 * pn) ^ 2) * 64, 0, sb + B_QF + 16);
        }
        if (l < 3) { bar_sync(NB_X, 320); e_expect_tx(sb + B_QL, 49152); }
      }
      if (blockIdx.x == 0 && lane_id() == 0) *(volatile uint32_t*)&g_epoch = ep1;
    } else {
      const int hw = w - 1;
      if (lane < 5) asm volatile("prefetch.tensormap [%0];" ::"l"(&prm.m[5 * hw + lane]) : "memory");
      __syncwarp();
      cluster_wait();
      mbar_wait(sb + B_QF, 0);
#pragma unroll 1
      for (int l = 0; l < 4; l++) {
        IDS();
        if (l > 0) { mbar_wait(sb + B_QL, (l + 1) & 1); mbar_wait(sb + B_QF + 8 * 3, 0); }
        if (l == 0) {
#pragma unroll 1
          for (int r = 2 * hw; r < 16; r += 6) {
            const uint4* p = (const uint4*)(prm.x0 + (size_t)(b * 16 + r) * 1024) + lane;
            float s1[2] = {0.f, 0.f}, s2[2] = {0.f, 0.f};
#pragma unroll
            for (int i = 0; i < 8; i++) {
              const uint4 v = __ldg(p + 32 * i);
              const uint32_t u[4] = {v.x, v.y, v.z, v.w};
#pragma unroll
              for (int k = 0; k < 4; k++) { const float a = bf_lo(u[k]), c = bf_hi(u[k]); s1[i >> 2] += a + c; s2[i >> 2] = fmaf(a, a, fmaf(c, c, s2[i >> 2])); }
            }
#pragma unroll
            for (int o = 16; o; o >>= 1)
#pragma unroll
              for (int rr = 0; rr < 2; rr++) { s1[rr] += __shfl_xor_sync(~0u, s1[rr], o); s2[rr] += __shfl_xor_sync(~0u, s2[rr], o); }
            if (lane == 0) *(float4*)&g_stats[b * 16 + r] = make_float4(s1[0], s2[0], s1[1], s2[1]);
          }
        }
        if (l < 2) {
          float cs[8];
#pragma unroll
          for (int i = 0; i < 8; i++) cs[i] = 0.f;
          const uint4* wp = (const uint4*)(prm.wq[l] + (size_t)(bm * 128 + (lane >> 3)) * 3072 + hw * 1024 + bn * 64) + (lane & 7);
#pragma unroll 8
          for (int i = 0; i < 32; i++) {
            const uint4 v = __ldg(wp + (size_t)i * 4 * 384);
            cs[0] += bf_lo(v.x); cs[1] += bf_hi(v.x); cs[2] += bf_lo(v.y); cs[3] += bf_hi(v.y);
            cs[4] += bf_lo(v.z); cs[5] += bf_hi(v.z); cs[6] += bf_lo(v.w); cs[7] += bf_hi(v.w);
          }
#pragma unroll
          for (int i = 0; i < 8; i++) { cs[i] += __shfl_xor_sync(~0u, cs[i], 8); cs[i] += __shfl_xor_sync(~0u, cs[i], 16); }
          if (lane < 8) {
            float4* d = (float4*)(g_csp + ((l * 16 + bn) * 8 + bm) * 192 + hw * 64 + lane * 8);
            d[0] = make_float4(cs[0], cs[1], cs[2], cs[3]); d[1] = make_float4(cs[4], cs[5], cs[6], cs[7]);
          }
          __syncwarp();
          asm volatile("fence.acq_rel.gpu;" ::: "memory");
          e_red_relaxed(cnt_cs(l, bn));
          if (l == 0) e_red_relaxed(cnt_x(0, bm) + pn);
          poll_ge(lane < 8 && l == 0 ? cnt_x(0, bm) + lane : cnt_cs(l, bn), ep1 * (lane < 8 && l == 0 ? 6 : 24));
        }
        if (l > 0) poll_ge(cnt_x(l, bm) + (lane & 15), ep1 * 2);
#pragma unroll 1
        for (int it = hw * 32 + lane; it < 176; it += 96) {
          const bool rows = it < 128;
          const float4* p = rows ? (const float4*)(g_stats + bm * 256) + it : (const float4*)(g_csp + ((l & 1) * 16 + bn) * 8 * 192) + (it - 128);
          const int stride = rows ? 1024 : 48, np = rows && l == 0 ? 1 : 8;
          float4 a = make_float4(0.f, 0.f, 0.f, 0.f);
#pragma unroll
          for (int k = 0; k < 8; k++) if (k < np) { const float4 v = __ldcg(p + k * stride); a.x += v.x; a.y += v.y; a.z += v.z; a.w += v.w; }
          if (rows) {
            const float m0 = a.x * (1.f / 1024.f), m1 = a.z * (1.f / 1024.f);
            const float v0 = fmaxf(a.y * (1.f / 1024.f) - m0 * m0, 0.f), v1 = fmaxf(a.w * (1.f / 1024.f) - m1 * m1, 0.f);
            const float r0 = __fdividef(1.f, bf_round(sqrtf(bf_round(bf_round(v0) + 1e-5f)))), r1 = __fdividef(1.f, bf_round(sqrtf(bf_round(bf_round(v1) + 1e-5f))));
            a = make_float4(r0, -bf_round(m0) * (l & 1 ? r0 : 1.f), r1, -bf_round(m1) * (l & 1 ? r1 : 1.f));
          }
          *(float4*)(smem + ROWST + it * 16) = a;
        }
        __syncwarp();
        if (lane == 0) asm volatile("red.release.cta.shared.add.u32 [%0], 1;" ::"r"(sb + W_X) : "memory");
        if (hw == 2) {
          if (!(l & 1)) {
            bar_sync(NB_ST, 288);
            const uint4* hp = g_halo + ((l >> 1) * 128 + b - 16) * 384 + lane;
#pragma unroll 1
            for (int h = 0; h < 2; h++) {
              uint32_t t[18];
#pragma unroll
              for (int i = 0; i < 18; i++) t[i] = 0;
#pragma unroll 1
              for (uint32_t n = bm ? 0 : 100000u; n < 100000u; n++) {
                uint32_t miss = 0;
#pragma unroll
                for (int i = 0; i < 6; i++) miss |= ld_tagged(hp + h * 192 + i * 32, &t[3 * i]) ^ ep1;
                if (__all_sync(~0u, !miss)) break;
              }
              mbar_wait(sb + B_QE + 16, 1);
              const uint32_t r = (lane & 7) + ((lane >> 3) & 1) * 8, rv = lane >> 2;
#pragma unroll
              for (int jj = 0; jj < 2; jj++) stsm4(sb + KSC + r * 128 + (((4 * h + 2 * jj + (lane >> 4)) ^ (r & 7)) << 4), t[4 * jj], t[4 * jj + 1], t[4 * jj + 2], t[4 * jj + 3]);
              const uint32_t ad = sb + VSC + rv * 128 + (((4 * h + (lane & 3)) ^ (rv & 7)) << 4);
              sts128(ad, t[8], t[10], t[12], t[14]); sts128(ad + 1024, t[9], t[11], t[13], t[15]);
              if (h == 0 && !(lane & 2)) *(uint32_t*)(smem + HRS + ((lane >> 2) + 8 * (lane & 1)) * 8) = t[16];
              bar_arrive(NB_HALO + h, 64);
            }
          } else {
            mbar_wait(sb + B_TF + 16, 0); mbar_wait(sb + B_TF + 16, 1);
            poll_ge(cnt_kv(l >> 1, bn) + 16 + (lane & 7), ep1);
            const uint4 v = __ldcg((const uint4*)(g_kn + ((l >> 1) * 128 + bn * 8) * 16) + lane);
            const uint32_t mx = max(max(v.x, v.y), max(v.z, v.w));
            const uint32_t m0 = __reduce_max_sync(~0u, (lane & 2) ? 0u : mx), m1 = __reduce_max_sync(~0u, (lane & 2) ? mx : 0u);
            if (lane == 0) *(uint2*)(smem + ROWST) = make_uint2(m0, m1);
            __syncwarp();
            bar_arrive(NB_KN, 160); bar_arrive(NB_KN + 1, 160);
          }
        } else {
          if (l & 1) {
            bar_sync(hw ? NB_HALO : NB_DONE, 160);
            tma_st(&prm.m[M_K], 0, 2 * bn * 2048 + bm * 256 + hw * 128, sb + T0 + hw * 8192);
            tma_st(&prm.m[M_V], 0, 2 * bn * 2048 + bm * 256 + hw * 128, sb + T0 + 16384 + hw * 8192);
            bulk_commit(); bulk_wait_n<0>();
            e_red(cnt_kv(l >> 1, bn) + 8 * hw + bm);
          }
#pragma unroll 1
          for (int i = 0; i < 2; i++) {
            const int h = l & 1 ? i : hw, g = l & 1 ? hw : i;
            bar_sync(NB_SIG + 2 * h + g, 160);
            if (!(l & 1) && i == 0) continue;
            if (i == 1 && hw == 1) bar_arrive(l & 1 ? NB_ST : NB_DONE, 64);
            asm volatile("fence.acq_rel.gpu;" ::: "memory");
            e_red_relaxed(cnt_o(l, 2 * bm + g, h) + (bn >> 1));
            if (!(l & 1)) e_red_relaxed(cnt_o(l, 2 * bm, h) + (bn >> 1));
            if (h == 1 && l == 1) e_red_relaxed(cnt_ad(bn));
          }
        }
        if (hw < 2 && l < 3) {
          if (hw) bar_sync(NB_X, 320); else bar_sync(NB_X0, 288);
          if (hw) {

            tma_st(&prm.m[M_XSO], pn * 128 + 64, pm * 128, sb + QSTG + po * 16384);
            bulk_commit();
            bar_sync(NB_KV, 288);
            bulk_wait_n<0>();
          }
          e_red(cnt_x(l + 1, bm) + 2 * pn + hw);
        }
      }
    }
  } else {
    asm volatile("setmaxnreg.inc.sync.aligned.u32 224;");
    const uint32_t zero = prm.zero;
    cluster_wait();
#pragma unroll 1
    for (int l = 0; l < 4; l++) {
      {
        float acc[2][96];
#pragma unroll
        for (int i = 0; i < 96; i++) { acc[0][i] = 0.f; acc[1][i] = 0.f; }
        fence_regs(acc[0]); fence_regs(acc[1]);
        const bool early = l > 0 && wg == ((cta_id() >> 3) & 1);
        uint32_t ep1 = 0;
#pragma unroll 1
        for (int kt = 0; kt < 14; kt++) {
          const int s = kt & 3;
          if (l > 0 && kt == 0) mbar_wait(sb + B_QL, (l + 1) & 1);
          if (!(early && kt < 2)) mbar_wait(sb + B_QF + 8 * s, (kt >> 2) & 1);
          const uint64_t da = prm.xd + wg * 1024 + s * (QSTG >> 4), db = prm.wd + s * (QSTG >> 4);
          wg_fence();
#pragma unroll
          for (int k = 0; k < 4; k++)
#pragma unroll
            for (int m = 0; m < 2; m++) wgmma_m64n192k16_ss_tb(acc[m], da + m * 512 + k * 2, db + k * 128, 1);
          wg_commit();
          if (kt == 4) ep1 = *(volatile uint32_t*)&g_epoch + 1;
          wg_wait<1>();
          if (early && (kt == 1 || kt == 2)) mbar_wait(sb + B_QF + 8 * (kt - 1), 0);
          if (kt > 0 && w == 0) e_arrive_both(sb + B_QE + 8 * ((kt - 1) & 3));
        }
        {
          const bool lag = (l & 1) && wg;
          const uint64_t da = prm.xd + wg * 1024 + 2 * (QSTG >> 4), db = prm.wd + 2 * (QSTG >> 4);
          mbar_wait(sb + B_QF + 16, 1);
          if (lag) {
            mbar_wait(sb + B_QF + 24, 1);
            wg_wait<0>();
            if (w == 0) e_arrive_both(sb + B_QE + 8);
            bar_sync(NB_SC, 256);
          }
          wg_fence();
#pragma unroll
          for (int k = 0; k < 4; k++)
#pragma unroll
            for (int m = 0; m < 2; m++) wgmma_m64n192k16_ss_tb(acc[m], da + m * 512 + k * 2, db + k * 128, 1);
          wg_commit();
          if (!lag) {
            wg_wait<1>();
            if (w == 0) e_arrive_both(sb + B_QE + 8);
            mbar_wait(sb + B_QF + 24, 1);
          }
          wg_fence();
#pragma unroll
          for (int m = 1; m >= 0; m--) {
#pragma unroll
            for (int k = 0; k < 4; k++) wgmma_m64n192k16_ss_tb(acc[m], da + (QSTG >> 4) + m * 512 + k * 2, db + (QSTG >> 4) + k * 128, 1);
            wg_commit();
          }
          if ((l & 1) && !wg) bar_arrive(NB_SC, 256);
          if (!(l & 1)) bar_arrive(NB_ST, 288);
          wg_wait<2>();
          if (w == 0) e_arrive_both(sb + B_QE + 16);
        }
#pragma unroll 1
        for (uint32_t n = 0; n < 4000000u; n++) {
          uint32_t v;
          asm volatile("ld.acquire.cta.shared.u32 %0, [%1];" : "=r"(v) : "r"(sb + W_X) : "memory");
          if (v == (uint32_t)(3 * l + 3)) break;
        }
        IDS();
        const int g = lane >> 2, qd = lane & 3;
        float2 st[2][2];
#pragma unroll
        for (int m = 0; m < 2; m++)
#pragma unroll
          for (int hh = 0; hh < 2; hh++) st[m][hh] = lds64f(sb + ROWST + (wg * 128 + m * 64 + w * 16 + g + 8 * hh) * 8);
        float2 cs[4];
        auto load_cs = [&](int gi) {
#pragma unroll
          for (int j = 0; j < 4; j++) cs[j] = lds64f(sb + COLS + (gi * 32 + j * 8 + 2 * qd) * 4);
        };
        load_cs(2);
        auto drain = [&]() {
          wg_wait<0>(); fence_regs(acc[0]);
          if (w == 0) e_arrive_both(sb + B_QE + 8 * 3);
        };
        wg_wait<1>(); fence_regs(acc[1]);
        auto norm_tile = [&](int gi, int m, float sc, uint32_t (&t)[8], float (&nrm)[2], bool h16 = false) {
          const float r0 = st[m][0].x * sc, s0 = st[m][0].y * sc, r1 = st[m][1].x * sc, s1 = st[m][1].y * sc;
          float n0 = 0.f, n1 = 0.f;
#pragma unroll
          for (int j = 0; j < 4; j++) {
            const float* a = &acc[m][16 * gi + 4 * j];
            const float v0 = fmaf(a[0], r0, s0 * cs[j].x), v1 = fmaf(a[1], r0, s0 * cs[j].y);
            const float v2 = fmaf(a[2], r1, s1 * cs[j].x), v3 = fmaf(a[3], r1, s1 * cs[j].y);
            n0 = fmaf(v0, v0, fmaf(v1, v1, n0)); n1 = fmaf(v2, v2, fmaf(v3, v3, n1));
            t[2 * j] = h16 ? pack2h(v0, v1) : pack2(v0, v1); t[2 * j + 1] = h16 ? pack2h(v2, v3) : pack2(v2, v3);
          }
          nrm[0] = n0; nrm[1] = n1;
        };
        auto norm_group = [&](int gi, float sc, uint32_t (&t)[2][8], float (&nrm)[2][2]) { norm_tile(gi, 0, sc, t[0], nrm[0]); norm_tile(gi, 1, sc, t[1], nrm[1]); };
        uint32_t q[2][2][8];
        const uint32_t srow = (lane & 7) + ((lane >> 3) & 1) * 8;
        const uint32_t row0 = wg * 128 + w * 16;
        if (!(l & 1)) {
          auto put_kv = [&](int gi, uint32_t r0, const uint32_t (&t)[8]) {
            if (gi < 4) {
              const uint32_t r = r0 + srow;
#pragma unroll
              for (int jj = 0; jj < 2; jj++) stsm4(sb + KSC + r * 128 + (((4 * (gi - 2) + 2 * jj + (lane >> 4)) ^ (r & 7)) << 4), t[4 * jj], t[4 * jj + 1], t[4 * jj + 2], t[4 * jj + 3]);
            } else {
              const uint32_t r = r0 + g, ad = sb + VSC + r * 128 + (((4 * (gi - 4) + qd) ^ (r & 7)) << 4);
              sts128(ad, t[0], t[2], t[4], t[6]); sts128(ad + 1024, t[1], t[3], t[5], t[7]);
            }
          };
          auto cen_tile = [&](int gi, int m, uint32_t (&t)[8]) {
#pragma unroll
            for (int j = 0; j < 4; j++) {
              const float* a = &acc[m][16 * gi + 4 * j];
              t[2 * j] = pack2(fmaf(st[m][0].y, cs[j].x, a[0]), fmaf(st[m][0].y, cs[j].y, a[1]));
              t[2 * j + 1] = pack2(fmaf(st[m][1].y, cs[j].x, a[2]), fmaf(st[m][1].y, cs[j].y, a[3]));
            }
          };
          const bool send = wg == 1 && w == 3 && bm < 7;
          uint4* hp = g_halo + ((l >> 1) * 128 + b) * 384 + lane;
          mbar_wait(sb + B_QE + 16, 1);
          float2 cn[4];
          auto next_cs = [&](int gi) {
#pragma unroll
            for (int j = 0; j < 4; j++) { cs[j] = cn[j]; cn[j] = lds64f(sb + COLS + (gi * 32 + j * 8 + 2 * qd) * 4); }
          };
#pragma unroll
          for (int j = 0; j < 4; j++) cn[j] = cs[j];
#pragma unroll
          for (int h = 0; h < 2; h++) {
            uint32_t k[8], v[8];
            next_cs(4 + h);
            cen_tile(2 + h, 1, k); put_kv(2 + h, 16 + row0 + 64, k);
            next_cs(h ? 2 : 3);
            cen_tile(4 + h, 1, v); put_kv(4 + h, 16 + row0 + 64, v);
            if (send) {
              uint4* p = hp + h * 192;
              st_tagged(p, k[0], k[1], k[2], ep1); st_tagged(p + 32, k[3], k[4], k[5], ep1); st_tagged(p + 64, k[6], k[7], v[0], ep1);
              st_tagged(p + 96, v[1], v[2], v[3], ep1); st_tagged(p + 128, v[4], v[5], v[6], ep1);
              st_tagged(p + 160, v[7], __float_as_uint(qd & 1 ? st[1][1].x : st[1][0].x), 0u, ep1);
            }
            sched_fence();
          }
          drain();
          {
            uint32_t t[8];
            next_cs(4); cen_tile(2, 0, t); put_kv(2, 16 + row0, t);
            next_cs(0); cen_tile(4, 0, t); put_kv(4, 16 + row0, t);
            next_cs(3); cen_tile(0, 0, q[0][0]); cen_tile(0, 1, q[0][1]);
          }
          const bool e = g & 1, sel = 2 * qd + (g & 1) >= g + 2, first = bm == 0 && row0 == 0;
          uint32_t ka = sb + KSC + (row0 + (lane & 7)) * 128 + (((lane >> 3) ^ (lane & 7)) << 4);
          uint32_t wa = sb + VSC + (row0 + srow) * 128 + (((lane >> 4) ^ (lane & 7)) << 4);
          uint32_t psel[3] = {e ? 0x1044u : 0x4410u, !sel ? 0x4444u : e ? 0x3244u : 0x4432u, sel ? 0x4444u : e ? 0x3244u : 0x4432u};
          bf16* op = g_os + (size_t)(bm * 256 + row0 + g) * 1024 + bn * 32 + qd * 8;
          asm volatile("" : "+r"(ka), "+r"(wa), "+l"(op));
          fence_regs(psel); fence_regs(q[0][0]); fence_regs(q[0][1]);
          sched_fence();
          bar_sync(NB_SC, 256);
          if (row0 == 0) bar_sync(NB_HALO, 64);
          float ra[4], rb[4], ca[4], cb[4];
#pragma unroll
          for (int m = 0; m < 2; m++) {
            float rk[3];
#pragma unroll
            for (int u = 0; u < 3; u++) {
              const int r = row0 + m * 64 + 8 * u + 2 * qd + e - (sel ? 16 : 8);
              rk[u] = lds64f(sb + (m == 0 && r < 0 ? HRS + 128 : ROWST) + r * 8).x;
            }
            ra[2 * m] = sel ? rk[1] : rk[0]; ra[2 * m + 1] = sel ? rk[2] : rk[1];
            rb[2 * m] = sel ? rk[0] : rk[1]; rb[2 * m + 1] = sel ? rk[1] : rk[2];
          }
#pragma unroll
          for (int i = 0; i < 4; i++) { const float rq = st[i >> 1][i & 1].x * QSCALE; ca[i] = rq * ra[i]; cb[i] = rq * rb[i]; }
#pragma unroll 1
          for (int h = 0; h < 2; h++) {
            float s[2][4][4];
            uint32_t vf[2][4][4], pf[2][2][4];
#pragma unroll
            for (int m = 0; m < 2; m++)
#pragma unroll
              for (int nt = 0; nt < 4; nt++) {
                uint32_t kf[4];
                ldsm4(ka + (m * 64 + 8 * nt) * 128, kf);
                s[m][nt][0] = s[m][nt][1] = s[m][nt][2] = s[m][nt][3] = 0.f;
                mma16816(s[m][nt], q[0][m][0], q[0][m][1], q[0][m][2], q[0][m][3], kf[0], kf[1]);
                mma16816(s[m][nt], q[0][m][4], q[0][m][5], q[0][m][6], q[0][m][7], kf[2], kf[3]);
              }
#pragma unroll
            for (int m = 0; m < 2; m++)
#pragma unroll
              for (int i = 0; i < 4; i++) {
                ldsm4t((wa ^ (32 * (i & 1))) + (m * 64 + 16 * (i >> 1)) * 128, vf[m][i]);
              }
            float va[4], vb[4], mx[4];
#pragma unroll
            for (int i = 0; i < 4; i++) {
              const int m = i >> 1, hh = i & 1;
              const float a = e ? s[m][hh + 1][2 * hh + 1] : s[m][hh + 1][2 * hh];
              const float lo = e ? s[m][hh][2 * hh + 1] : s[m][hh][2 * hh], hi = e ? s[m][hh + 2][2 * hh + 1] : s[m][hh + 2][2 * hh];
              va[i] = (m == 0 && hh == 0 && first) ? -INFINITY : a * ca[i];
              vb[i] = (m == 0 && first && sel) ? -INFINITY : (sel ? lo : hi) * cb[i];
              mx[i] = fmaxf(va[i], vb[i]);
            }
#pragma unroll
            for (int i = 0; i < 4; i++) mx[i] = fmaxf(mx[i], __shfl_xor_sync(~0u, mx[i], 1));
#pragma unroll
            for (int i = 0; i < 4; i++) mx[i] = fmaxf(mx[i], __shfl_xor_sync(~0u, mx[i], 2));
#pragma unroll
            for (int i = 0; i < 4; i++) {
              va[i] = ex2(va[i] - mx[i]); vb[i] = ex2(vb[i] - mx[i]);
              mx[i] = va[i] + vb[i];
              va[i] *= ra[i]; vb[i] *= rb[i];
            }
#pragma unroll
            for (int i = 0; i < 4; i++) mx[i] += __shfl_xor_sync(~0u, mx[i], 1);
#pragma unroll
            for (int i = 0; i < 4; i++) mx[i] += __shfl_xor_sync(~0u, mx[i], 2);
#pragma unroll
            for (int i = 0; i < 4; i++) {
              const int m = i >> 1, hh = i & 1;
              const float inv = rcp(mx[i]);
              const uint32_t t = pack2(va[i] * inv, vb[i] * inv);
              pf[m][hh][hh + 1] = prmt0(t, psel[0]); pf[m][hh][hh] = prmt0(t, psel[1]); pf[m][hh][hh + 2] = prmt0(t, psel[2]);
              pf[m][hh][3 - 3 * hh] = t & zero;
            }
#pragma unroll
            for (int m = 0; m < 2; m++) {
              float o[4][4];
#pragma unroll
              for (int j = 0; j < 4; j++) o[j][0] = o[j][1] = o[j][2] = o[j][3] = 0.f;
#pragma unroll
              for (int i = 0; i < 4; i++) {
                const int kk = i >> 1, jj = 2 * (i & 1);
                mma16816(o[jj], pf[m][0][2 * kk], pf[m][1][2 * kk], pf[m][0][2 * kk + 1], pf[m][1][2 * kk + 1], vf[m][i][0], vf[m][i][1]);
                mma16816(o[jj + 1], pf[m][0][2 * kk], pf[m][1][2 * kk], pf[m][0][2 * kk + 1], pf[m][1][2 * kk + 1], vf[m][i][2], vf[m][i][3]);
              }
              stg128(op + m * 65536, pack2(o[0][0], o[0][1]), pack2(o[1][0], o[1][1]), pack2(o[2][0], o[2][1]), pack2(o[3][0], o[3][1]));
              stg128(op + m * 65536 + 8192, pack2(o[0][2], o[0][3]), pack2(o[1][2], o[1][3]), pack2(o[2][2], o[2][3]), pack2(o[3][2], o[3][3]));
            }
            bar_arrive(NB_SIG + 2 * h + wg, 160);
            if (h == 0) {
              uint32_t t[8];
              next_cs(5); cen_tile(3, 0, t); put_kv(3, 16 + row0, t);
              next_cs(1); cen_tile(5, 0, t); put_kv(5, 16 + row0, t);
#pragma unroll
              for (int j = 0; j < 4; j++) cs[j] = cn[j];
              cen_tile(1, 0, q[0][0]); cen_tile(1, 1, q[0][1]);
              ka ^= 64; wa ^= 64; op += 512;
              bar_sync(NB_SC, 256);
              if (row0 == 0) bar_sync(NB_HALO + 1, 64);
            }
          }
        } else {
          float qn[2];
          drain();
          auto esc_ptr = [&](int gi) { IDS(); return g_esc + (size_t)(((l & 2) + (gi >> 1)) * 65536 + (2 * bn + (gi & 1)) * 2048) * 20; };
          auto norm_half = [&](int gi, float sc, uint32_t (&t)[2][8], float (&nrm)[2][2]) {
            norm_tile(gi, 0, sc, t[0], nrm[0], true); norm_tile(gi, 1, sc, t[1], nrm[1], true);
            if (!((nrm[0][0] + nrm[0][1]) + (nrm[1][0] + nrm[1][1]) <= 4e9f) || fminf(fminf(nrm[0][0], nrm[0][1]), fminf(nrm[1][0], nrm[1][1])) < 1.5e-5f) {
              uint32_t* p = esc_ptr(gi) + (bm * 256 + row0 + g) * 20 + qd;
#pragma unroll
              for (int m = 0; m < 2; m++) {
                uint32_t u[8]; float d[2];
                norm_tile(gi, m, sc, u, d);
#pragma unroll
                for (int i = 0; i < 10; i++) p[(m * 64 + (i & 1) * 8) * 20 + (i >> 1) * 4] = i < 8 ? u[i] : ep1;
              }
            }
            __syncwarp();
          };
          {
            auto max_norm = [&](const float (&nrm)[2][2]) {
              const bool o1 = qd & 1, o2 = qd & 2;
              const float a = (o1 ? nrm[1][0] : nrm[0][0]) + __shfl_xor_sync(~0u, o1 ? nrm[0][0] : nrm[1][0], 1);
              const float c = (o1 ? nrm[1][1] : nrm[0][1]) + __shfl_xor_sync(~0u, o1 ? nrm[0][1] : nrm[1][1], 1);
              const float d = (o2 ? c : a) + __shfl_xor_sync(~0u, o2 ? a : c, 2);
              return __uint_as_float(__reduce_max_sync(~0u, __float_as_uint(d)));
            };
#pragma unroll
            for (int h = 0; h < 2; h++) {
              uint32_t t[2][8]; float nrm[2][2];
              const uint32_t kb = sb + (h ? 0 : T0);
              if (h) load_cs(3);
              uint32_t tv[2][8];
              norm_half(2 + h, 1.f, t, nrm);
              load_cs(4 + h);
              float nv[2][2];
              if (h == 1) { const float kn = max_norm(nrm); if (lane == 0) g_kn[((l >> 1) * 128 + bn * 8 + bm) * 16 + 8 + wg * 4 + w] = kn; }
              if (h == 0) mbar_wait(sb + B_QE + 8, 1);
#pragma unroll
              for (int i = 0; i < 4; i++) {
                const uint32_t r = row0 + (i >> 1) * 64 + srow;
                stsm4(kb + r * 64 + (((2 * (i & 1) + (lane >> 4)) ^ ((r >> 1) & 3)) << 4), t[i >> 1][4 * (i & 1)], t[i >> 1][4 * (i & 1) + 1], t[i >> 1][4 * (i & 1) + 2], t[i >> 1][4 * (i & 1) + 3]);
              }
              norm_group(4 + h, 1.f, tv, nv);
              load_cs(h);
#pragma unroll
              for (int m = 0; m < 2; m++) {
                const uint32_t r = row0 + m * 64 + g, ad = kb + 16384 + r * 64 + ((qd ^ ((r >> 1) & 3)) << 4);
                sts128(ad, tv[m][0], tv[m][2], tv[m][4], tv[m][6]); sts128(ad + 512, tv[m][1], tv[m][3], tv[m][5], tv[m][7]);
              }
              fence_async_smem();
              bar_arrive(NB_KV + 12 * h, 288);
              if (h == 0) {
                bar_arrive(wg ? NB_HALO : NB_DONE, 160);
                if (wg) bar_sync(NB_HALO + 1, 256);
              }
              if (h == 0) { const float kn = max_norm(nrm); if (lane == 0) g_kn[((l >> 1) * 128 + bn * 8 + bm) * 16 + wg * 4 + w] = kn; }
              norm_half(h, QSCALE, q[h], nrm);
#pragma unroll
              for (int i = 0; i < 4; i++) sts128(sb + QPARK + h * 16384 + (wg * 128 + w * 32 + lane) * 16 + i * 4096, q[h][i >> 1][4 * (i & 1)], q[h][i >> 1][4 * (i & 1) + 1], q[h][i >> 1][4 * (i & 1) + 2], q[h][i >> 1][4 * (i & 1) + 3]);
              qn[h] = max_norm(nrm);
            }
            if (!wg) bar_arrive(NB_HALO + 1, 256);
          }
          constexpr uint64_t VSTEP = 64 - (64ull << 16);
          const uint32_t c_852 = 0x62A962A9u + (lane_id() & zero), c_lsb = 0x00010001u + (lane_id() & zero), c_half = 0x3F003F00u + (lane_id() & zero);
          float o[2][20], S[2][32];
          uint32_t H[2][16], P0[4] = {}, P1[4] = {};
#pragma unroll
          for (int m = 0; m < 2; m++) {
#pragma unroll
            for (int i = 0; i < 20; i++) o[m][i] = 0.f;
            fence_regs(o[m]);
          }
          auto qkf = [&](int b, int ks, uint64_t d) { wg_n64_rs_nb_f16_f32(S[b], q[0][0][4 * ks], q[0][0][4 * ks + 1], q[0][0][4 * ks + 2], q[0][0][4 * ks + 3], d + 2 * ks, ks ? 1 : zero); };
          auto qkh = [&](int b, int ks, uint64_t d) { wg_n64_rs_nb_f16_f16(H[b], q[0][1][4 * ks], q[0][1][4 * ks + 1], q[0][1][4 * ks + 2], q[0][1][4 * ks + 3], d + 2 * ks, ks ? 1 : zero); };
          auto pv0 = [&](uint64_t d) { wgmma_m64n40k16_rs_tb(o[0], P0[0], P0[1], P0[2], P0[3], d, 1); };
          auto pv1 = [&](uint64_t d) { wgmma_m64n40k16_rs_tb(o[1], P1[0], P1[1], P1[2], P1[3], d, 1); };
          float e[4] = {};
          auto finish = [&](int h) {
            const float* s = &S[(h >> 2) & 1][8 * (h & 3)];
            const uint32_t* u = &H[(h >> 2) & 1][4 * (h & 3)];
            const float z0 = exp2_fix(s[6]), z1 = exp2_fix(s[7]);
            P0[0] = pack2v(e[0], e[1]);
            P1[0] = exp2_h2(u[0], c_852);
            P0[1] = pack2v(e[2], e[3]);
            P1[1] = exp2_h2(u[1], c_852);
            const uint32_t B = exp2_base(z0, z1), E = and_or<0x7F807F80u>(B, c_lsb);
            P1[3] = exp2_h2(u[3], c_852);
            P0[3] = fma_bf2(B, and_or<0x807F807Fu>(B, c_half), E);
            const float e4 = ex2v(s[4]), e5 = ex2v(s[5]);
            P1[2] = exp2_h2(u[2], c_852);
            P0[2] = pack2v(e4, e5);
          };
          auto start = [&](int h) {
            const float* s = &S[(h >> 2) & 1][8 * (h & 3)];
            e[0] = ex2v(s[0]); e[1] = ex2v(s[1]); e[3] = ex2v(s[3]); e[2] = ex2v(s[2]);
          };
          uint64_t kd = prm.kv[0].kd;
          mbar_wait(sb + B_TF, 0);
          wg_fence();
#pragma unroll
          for (int b = 0; b < 2; b++) {
            wg_n64_rs_nb_f16_f32_z(S[b], q[0][0][0], q[0][0][1], q[0][0][2], q[0][0][3], kd + 256 * b, 0);
            wg_n64_rs_nb_f16_f16_z(H[b], q[0][1][0], q[0][1][1], q[0][1][2], q[0][1][3], kd + 256 * b, 0);
            if (b == 0) { qkf(0, 1, kd); qkh(0, 1, kd); }
            wg_commit();
          }
          wg_wait<1>(); fence_regs(S[0]); fence_regs(H[0]);
          start(0); finish(0); start(1);
          wg_wait<0>();
          int redo = 0;
#pragma unroll 1
          for (int pass = 0, j = 1; pass < 2; pass++) {
#pragma unroll 1
           do {
            const uint64_t vd = prm.kv[j & 3].vd;
            bool go = false;
#pragma unroll
            for (int h = 2; h < 18; h++) {
              const int px = (h >> 2) + 1, c = h & 3;
              wg_fence();
              if (h == 13) kd = prm.kv[j & 3].kd;
              const uint64_t kx = kd + (px & 3) * 256, vx = vd + (h - 2) * VSTEP;
              if (h == 2) { qkh(1, 0, kx); qkf(1, 0, kx); pv0(vx); pv1(vx); qkh(1, 1, kx); qkf(1, 1, kx); }
              else if ((c == 1 || c == 2) && h < 17) { qkh(px & 1, c - 1, kx); pv1(vx); qkf(px & 1, c - 1, kx); pv0(vx); }
              else { pv0(vx); pv1(vx); }
              wg_commit();
              if (h == 3) e_arrive_if(sb + B_TE + 8 * ((j + 2) & 3), j > 1);
              if (h == 11) go = mbar_test(sb + B_TF + 8 * (j & 3), (j >> 2) & 1) && j != 8;
              finish(h - 1); start(h);
              if (h != 12 && h != 17) sched_fence();
              if (h == 12 && !go) {
                if (j == 16) {
#pragma unroll
                  for (int u = 13; u < 18; u++) {
                    wg_fence(); pv0(vd + (u - 2) * VSTEP); pv1(vd + (u - 2) * VSTEP); wg_commit();
                    if (u < 17) finish(u - 1);
                    if (u < 16) { start(u); sched_fence(); }
                    if (u & 1) { if (u == 17) wg_wait<0>(); else wg_wait<1>(); }
                  }
                  e_arrive(sb + B_TE + 24);
                  goto head_done;
                }
                mbar_wait(sb + B_TF + 8 * (j & 3), (j >> 2) & 1);
                if (j == 8) {
#pragma unroll
                  for (int i = 0; i < 4; i++) lds128(sb + QPARK + 16384 + (wg * 128 + w * 32 + lane_id()) * 16 + i * 4096, &q[0][i >> 1][4 * (i & 1)]);
                }
              }
              if (h == 17) wg_wait<0>(); else if (h & 1) wg_wait<1>();
              if (c == 3) { fence_regs(S[px & 1]); fence_regs(H[px & 1]); }
            }
           } while (j++ & 7);
           head_done:
            fence_regs(o[0]); fence_regs(o[1]);
            uint32_t pk[2][8];
            {
              IDS();
              bf16* op = g_os + (size_t)(bm * 256 + row0 + (lane >> 2)) * 1024 + pass * 512 + bn * 32 + (lane & 3) * 8;
#pragma unroll
              for (int i = 0; i < 4; i++) {
                const float* a = &o[i >> 1][2 * (i & 1)];
                const float inv = rcp(a[16]);
                uint32_t* u = &pk[i >> 1][4 * (i & 1)];
#pragma unroll
                for (int k = 0; k < 4; k++) u[k] = pack2(a[4 * k] * inv, a[4 * k + 1] * inv);
                *(uint4*)(op + ((i >> 1) * 64 + (i & 1) * 8) * 1024) = make_uint4(u[0], u[1], u[2], u[3]);
              }
            }
            sched_fence();
            if (pass == 0) bar_sync(NB_KN + wg, 160);
            const float kmax = *(volatile float*)(smem + ROWST + 4 * pass);
            const bool wide = !(qn[0] <= 1.6e7f) | !(kmax <= 1.6e7f) | !(qn[0] * kmax <= 112.f * 112.f);
            int badm = 0;
#pragma unroll
            for (int m = 0; m < 2; m++) {
              uint32_t chk[2] = {0u, 0u};
#pragma unroll
              for (int i = 0; i < 8; i++) asm("fma.rn.bf16x2 %0, %1, %2, %0;" : "+r"(chk[i & 1]) : "r"(pk[m][i]), "r"(0u));
              const bool bad = wide | !(fminf(o[m][16], o[m][18]) >= 9.3e-10f) | !(o[m][16] + o[m][18] <= 1e36f) | (((chk[0] | chk[1]) & 0x7FFF7FFFu) != 0);
              badm |= __any_sync(~0u, bad) << m;
            }
            if (!badm) bar_arrive(NB_SIG + 2 * pass + wg, 160);
            qn[0] = qn[1];
#pragma unroll
            for (int m = 0; m < 2; m++) {
#pragma unroll
              for (int i = 0; i < 20; i++) o[m][i] = 0.f;
              fence_regs(o[m]);
            }
            if (badm) {
              redo |= badm << 2 * pass;
              const int tx = wg * 128 + w * 32 + lane_id();
              uint4* p = g_qsave + (block_id() * 256 + tx) * 8 + pass * 4;
#pragma unroll
              for (int i = 0; i < 4; i++) {
                uint32_t u[4] = {q[0][i >> 1][4 * (i & 1)], q[0][i >> 1][4 * (i & 1) + 1], q[0][i >> 1][4 * (i & 1) + 2], q[0][i >> 1][4 * (i & 1) + 3]};
                if (pass == 0) lds128(sb + QPARK + tx * 16 + i * 4096, u);
                p[i] = make_uint4(u[0], u[1], u[2], u[3]);
              }
            }
          }
          if (redo) attn_redo(redo, l, cta_id(), wg, w, ep1);
        }
      }
      {
        float acc[64];
#pragma unroll
        for (int i = 0; i < 64; i++) acc[i] = 0.f;
        fence_regs(acc);
        uint32_t s = 0, lap = 0;
#pragma unroll 1
        for (int kt = 0; kt < 16; kt++) {
          mbar_wait(sb + B_PF + 8 * s, ((s < 4 ? l : 0) + lap) & 1);
          const uint64_t da = mkdesc(sb + pslot_a(s, l) + wg * 8192, 16, 1024, 1), db = mkdesc(sb + pslot_b(s), 8192, 1024, 1);
          wg_fence();
#pragma unroll
          for (int k = 0; k < 4; k++) wgmma_m64n128k16_ss_tb(acc, da + k * 2, db + k * 128, 1);
          wg_commit();
          wg_wait<1>();
          if (kt > 0 && w == 0) e_arrive_both(sb + B_PE + 8 * (s ? s - 1 : 5));
          if (++s == 6) { s = 0; lap++; }
        }
        IDS();
        const int g = lane >> 2, qd = lane & 3;
        const int r0 = wg * 64 + w * 16;
        const uint32_t r = r0 + (lane & 7) + ((lane >> 3) & 1) * 8;
        uint32_t x[8][4];
        mbar_wait(sb + B_RF, l & 1);
#pragma unroll
        for (int jj = 0; jj < 8; jj++) ldsm4(sb + RES + (jj >> 2) * 16384 + r * 128 + ((((2 * jj + (lane >> 4)) & 7) ^ (r & 7)) << 4), x[jj]);
        wg_wait<0>();
        fence_regs(acc);
        if (w == 0) e_arrive_both(sb + B_PE + 8 * 3);
        const CUtensorMap* mo = &prm.m[l == 3 ? M_OUT : M_XST];
#pragma unroll
        for (int jj = 0; jj < 8; jj++) {
#pragma unroll
          for (int i = 0; i < 4; i++) x[jj][i] = add_bf16x2(x[jj][i], pack2(acc[8 * jj + 2 * i], acc[8 * jj + 2 * i + 1]));
          if (jj < 4) stsm4(sb + RES + r * 128 + ((((2 * jj + (lane >> 4)) & 7) ^ (r & 7)) << 4), x[jj][0], x[jj][1], x[jj][2], x[jj][3]);
          if (jj == 3) { fence_async_smem(); __syncwarp(); tma_st(mo, pn * 128, pm * 128 + r0, sb + RES + r0 * 128); bulk_commit(); sched_fence(); }
        }
        if (l == 3) {
#pragma unroll
          for (int jj = 4; jj < 8; jj++) stsm4(sb + RES + 16384 + r * 128 + ((((2 * jj + (lane >> 4)) & 7) ^ (r & 7)) << 4), x[jj][0], x[jj][1], x[jj][2], x[jj][3]);
          fence_async_smem(); __syncwarp();
          tma_st(mo, pn * 128 + 64, pm * 128 + r0, sb + RES + 16384 + r0 * 128);
          bulk_commit(); bulk_wait_n<0>();
        } else {
          bar_sync(NB_SC, 256);
#pragma unroll
          for (int jj = 0; jj < 8; jj++)
            stsm4(sb + (jj >> 2) * QSTG + po * 16384 + r * 128 + ((((2 * jj + (lane >> 4)) & 7) ^ (r & 7)) << 4), x[jj][0], x[jj][1], x[jj][2], x[jj][3]);
          bulk_wait_n<0>();
          bar_arrive(NB_X0, 288);
          fence_async_smem();
          bar_arrive(NB_X, 320);
          float s1[4] = {0.f, 0.f, 0.f, 0.f}, sa[4] = {0.f, 0.f, 0.f, 0.f}, sc[4] = {0.f, 0.f, 0.f, 0.f};
#pragma unroll
          for (int jj = 0; jj < 8; jj++) {
            mma16816(s1, x[jj][0], x[jj][1], x[jj][2], x[jj][3], 0x3f803f80u, 0x3f803f80u);
            mma16816(sa, x[jj][0], x[jj][1], x[jj][2], x[jj][3], x[jj][0], x[jj][2]);
            mma16816(sc, x[jj][0], x[jj][1], x[jj][2], x[jj][3], x[jj][1], x[jj][3]);
          }
          if (qd == g >> 1) {
            float2* p = g_stats + pn * 2048 + pm * 128 + r0 + g;
            p[0] = make_float2(s1[0], g & 1 ? sa[1] : sa[0]);
            p[8] = make_float2(s1[2], g & 1 ? sc[3] : sc[2]);
          }
          bar_arrive(NB_KV, 288);
        }
      }
    }
  }
  asm volatile("barrier.cluster.arrive.relaxed.aligned;\nbarrier.cluster.wait.aligned;" ::: "memory");
}

typedef CUresult (*EncodeFn)(CUtensorMap*, CUtensorMapDataType, cuuint32_t, void*, const cuuint64_t*, const cuuint64_t*, const cuuint32_t*,
                             const cuuint32_t*, CUtensorMapInterleave, CUtensorMapSwizzle, CUtensorMapL2promotion, CUtensorMapFloatOOBfill);

static void make_map(EncodeFn fn, CUtensorMap* m, const void* ptr, int rank, const uint64_t* dims, const uint64_t* strides, const uint32_t* box, CUtensorMapSwizzle sw) {
  cuuint64_t d[5], st[4];
  cuuint32_t bx[5], es[5];
  for (int i = 0; i < rank; i++) { d[i] = dims[i]; bx[i] = box[i]; es[i] = 1; if (i) st[i - 1] = strides[i - 1] * 2; }
  fn(m, CU_TENSOR_MAP_DATA_TYPE_BFLOAT16, rank, (void*)ptr, d, st, bx, es, CU_TENSOR_MAP_INTERLEAVE_NONE, sw,
     CU_TENSOR_MAP_L2_PROMOTION_L2_128B, CU_TENSOR_MAP_FLOAT_OOB_FILL_NONE);
}
static void map2(EncodeFn fn, CUtensorMap* m, const void* ptr, uint64_t inner, uint64_t outer, uint32_t bi, uint32_t bo, CUtensorMapSwizzle sw) {
  const uint64_t d[2] = {inner, outer}, st[1] = {inner};
  const uint32_t bx[2] = {bi, bo};
  make_map(fn, m, ptr, 2, d, st, bx, sw);
}

extern "C" void kernel_launch(void* const* d_in, const int* in_sizes, int n_in, void* d_out, int out_size) {
  (void)in_sizes; (void)n_in; (void)out_size;
  static EncodeFn enc = nullptr;
  static void *xs, *os, *kk, *vv;
  static int sbase = 1024;
  if (!enc) {
    void* p = nullptr;
    cudaDriverEntryPointQueryResult qr;
    cudaGetDriverEntryPoint("cuTensorMapEncodeTiled", &p, cudaEnableDefault, &qr);
    enc = (EncodeFn)p;
    Scratch* sc = nullptr;
    cudaGetSymbolAddress((void**)&sc, g_s);
    xs = sc->xs; os = sc->os; kk = sc->k; vv = sc->v;
    int dev = 0;
    cudaGetDevice(&dev);
    cudaDeviceGetAttribute(&sbase, cudaDevAttrReservedSharedMemoryPerBlock, dev);
    cudaFuncSetAttribute(fused_kernel, cudaFuncAttributeMaxDynamicSharedMemorySize, SMEM_BYTES);
  }
  Params prm;
  const CUtensorMapSwizzle S128 = CU_TENSOR_MAP_SWIZZLE_128B, S64 = CU_TENSOR_MAP_SWIZZLE_64B;
  map2(enc, &prm.m[M_X0A], d_in[0], 1024, 2048, 64, 256, S128);
  map2(enc, &prm.m[M_XSA], xs, 1024, 2048, 64, 256, S128);
  for (int t = 0; t < 2; t++) {
    const uint64_t d3[3] = {1024, 1024, 3}, s3[2] = {3072, 1024};
    const uint32_t b3[3] = {64, 64, 3};
    make_map(enc, &prm.m[M_WQA + t], d_in[1 + 3 * t], 3, d3, s3, b3, S128);
    const uint64_t d5[5] = {64, 32, 2, 16, 16}, s5[4] = {1024, 32 * 1024, 64 * 1024, 64};
    const uint32_t b5[5] = {64, 32, 1, 2, 2};
    make_map(enc, &prm.m[M_WOA + t], d_in[2 + 3 * t], 5, d5, s5, b5, S128);
    const uint64_t dr[3] = {64, 2048, 16}, sr[2] = {1024, 64};
    const uint32_t br[3] = {64, 128, 2};
    make_map(enc, &prm.m[M_X0R + t], t ? xs : d_in[0], 3, dr, sr, br, S128);
  }
  map2(enc, &prm.m[M_OS], os, 1024, 2048, 64, 64, S128);
  map2(enc, &prm.m[M_K], kk, 32, 65536, 32, 128, S64);
  map2(enc, &prm.m[M_V], vv, 32, 65536, 32, 128, S64);
  map2(enc, &prm.m[M_XSO], xs, 1024, 2048, 64, 128, S128);
  map2(enc, &prm.m[M_X0H], d_in[0], 1024, 2048, 64, 128, S128);
  map2(enc, &prm.m[M_XST], xs, 1024, 2048, 64, 16, S128);
  map2(enc, &prm.m[M_OUT], d_out, 1024, 2048, 64, 16, S128);
  prm.x0 = (const bf16*)d_in[0];
  prm.wq[0] = (const bf16*)d_in[1]; prm.wq[1] = (const bf16*)d_in[4];
  prm.zero = 0;
  for (int i = 0; i < 128; i++) prm.map[i] = remap(i);
  {
    const uint64_t hi = 0x80000020ull << 32, k0 = sbase + T0, v0 = k0 + 16384, vstep = 64 - (64ull << 16);
    prm.wd = mkdesc(sbase + 32768, 8192, 1024, 1); prm.xd = mkdesc(sbase, 16, 1024, 1);
    for (int j = 0; j < 4; j++) {
      prm.kv[j].kd = (hi | 1u << 16 | k0 >> 4) + 2048 * ((j < 16 ? j : 15) & 3);
      prm.kv[j].vd = (hi | (uint64_t)(ONES - T0 - 16384) >> 4 << 16 | v0 >> 4) + 32 * vstep * ((j + 3) & 3);
    }
  }
  fused_kernel<<<128, 384, SMEM_BYTES>>>(prm);
}
```

```cpp
#include <cuda_runtime.h>
#include <cuda_bf16.h>
#include <cuda.h>
#include <stdint.h>

typedef __nv_bfloat16 bf16;

__device__ __forceinline__ void wgmma_m64n192k16_ss_tb(float (&d)[96], uint64_t da, uint64_t db, int scale_d) {
  asm volatile("{\n.reg .pred p;\nsetp.ne.b32 p, %98, 0;\n"
    "wgmma.mma_async.sync.aligned.m64n192k16.f32.bf16.bf16 "
    "{%0, %1, %2, %3, %4, %5, %6, %7, %8, %9, %10, %11, %12, %13, %14, %15, "
    "%16, %17, %18, %19, %20, %21, %22, %23, %24, %25, %26, %27, %28, %29, %30, %31, "
    "%32, %33, %34, %35, %36, %37, %38, %39, %40, %41, %42, %43, %44, %45, %46, %47, "
    "%48, %49, %50, %51, %52, %53, %54, %55, %56, %57, %58, %59, %60, %61, %62, %63, "
    "%64, %65, %66, %67, %68, %69, %70, %71, %72, %73, %74, %75, %76, %77, %78, %79, "
    "%80, %81, %82, %83, %84, %85, %86, %87, %88, %89, %90, %91, %92, %93, %94, %95}, "
    "%96, %97, p, 1, 1, 0, 1;\n}\n"
    : "+f"(d[0]), "+f"(d[1]), "+f"(d[2]), "+f"(d[3]), "+f"(d[4]), "+f"(d[5]), "+f"(d[6]), "+f"(d[7]),
      "+f"(d[8]), "+f"(d[9]), "+f"(d[10]), "+f"(d[11]), "+f"(d[12]), "+f"(d[13]), "+f"(d[14]), "+f"(d[15]),
      "+f"(d[16]), "+f"(d[17]), "+f"(d[18]), "+f"(d[19]), "+f"(d[20]), "+f"(d[21]), "+f"(d[22]), "+f"(d[23]),
      "+f"(d[24]), "+f"(d[25]), "+f"(d[26]), "+f"(d[27]), "+f"(d[28]), "+f"(d[29]), "+f"(d[30]), "+f"(d[31]),
      "+f"(d[32]), "+f"(d[33]), "+f"(d[34]), "+f"(d[35]), "+f"(d[36]), "+f"(d[37]), "+f"(d[38]), "+f"(d[39]),
      "+f"(d[40]), "+f"(d[41]), "+f"(d[42]), "+f"(d[43]), "+f"(d[44]), "+f"(d[45]), "+f"(d[46]), "+f"(d[47]),
      "+f"(d[48]), "+f"(d[49]), "+f"(d[50]), "+f"(d[51]), "+f"(d[52]), "+f"(d[53]), "+f"(d[54]), "+f"(d[55]),
      "+f"(d[56]), "+f"(d[57]), "+f"(d[58]), "+f"(d[59]), "+f"(d[60]), "+f"(d[61]), "+f"(d[62]), "+f"(d[63]),
      "+f"(d[64]), "+f"(d[65]), "+f"(d[66]), "+f"(d[67]), "+f"(d[68]), "+f"(d[69]), "+f"(d[70]), "+f"(d[71]),
      "+f"(d[72]), "+f"(d[73]), "+f"(d[74]), "+f"(d[75]), "+f"(d[76]), "+f"(d[77]), "+f"(d[78]), "+f"(d[79]),
      "+f"(d[80]), "+f"(d[81]), "+f"(d[82]), "+f"(d[83]), "+f"(d[84]), "+f"(d[85]), "+f"(d[86]), "+f"(d[87]),
      "+f"(d[88]), "+f"(d[89]), "+f"(d[90]), "+f"(d[91]), "+f"(d[92]), "+f"(d[93]), "+f"(d[94]), "+f"(d[95])
    : "l"(da), "l"(db), "r"(scale_d));
}

__device__ __forceinline__ void wgmma_m64n128k16_ss_tb(float (&d)[64], uint64_t da, uint64_t db, int scale_d) {
  asm volatile("{\n.reg .pred p;\nsetp.ne.b32 p, %66, 0;\n"
    "wgmma.mma_async.sync.aligned.m64n128k16.f32.bf16.bf16 "
    "{%0, %1, %2, %3, %4, %5, %6, %7, %8, %9, %10, %11, %12, %13, %14, %15, "
    "%16, %17, %18, %19, %20, %21, %22, %23, %24, %25, %26, %27, %28, %29, %30, %31, "
    "%32, %33, %34, %35, %36, %37, %38, %39, %40, %41, %42, %43, %44, %45, %46, %47, "
    "%48, %49, %50, %51, %52, %53, %54, %55, %56, %57, %58, %59, %60, %61, %62, %63}, "
    "%64, %65, p, 1, 1, 0, 1;\n}\n"
    : "+f"(d[0]), "+f"(d[1]), "+f"(d[2]), "+f"(d[3]), "+f"(d[4]), "+f"(d[5]), "+f"(d[6]), "+f"(d[7]),
      "+f"(d[8]), "+f"(d[9]), "+f"(d[10]), "+f"(d[11]), "+f"(d[12]), "+f"(d[13]), "+f"(d[14]), "+f"(d[15]),
      "+f"(d[16]), "+f"(d[17]), "+f"(d[18]), "+f"(d[19]), "+f"(d[20]), "+f"(d[21]), "+f"(d[22]), "+f"(d[23]),
      "+f"(d[24]), "+f"(d[25]), "+f"(d[26]), "+f"(d[27]), "+f"(d[28]), "+f"(d[29]), "+f"(d[30]), "+f"(d[31]),
      "+f"(d[32]), "+f"(d[33]), "+f"(d[34]), "+f"(d[35]), "+f"(d[36]), "+f"(d[37]), "+f"(d[38]), "+f"(d[39]),
      "+f"(d[40]), "+f"(d[41]), "+f"(d[42]), "+f"(d[43]), "+f"(d[44]), "+f"(d[45]), "+f"(d[46]), "+f"(d[47]),
      "+f"(d[48]), "+f"(d[49]), "+f"(d[50]), "+f"(d[51]), "+f"(d[52]), "+f"(d[53]), "+f"(d[54]), "+f"(d[55]),
      "+f"(d[56]), "+f"(d[57]), "+f"(d[58]), "+f"(d[59]), "+f"(d[60]), "+f"(d[61]), "+f"(d[62]), "+f"(d[63])
    : "l"(da), "l"(db), "r"(scale_d));
}

__device__ __forceinline__ void wgmma_m64n40k16_rs_tb(float (&d)[20], uint32_t a0, uint32_t a1, uint32_t a2, uint32_t a3, uint64_t db, int scale_d) {
  asm volatile("{\n.reg .pred p;\nsetp.ne.b32 p, %25, 0;\n"
    "wgmma.mma_async.sync.aligned.m64n40k16.f32.bf16.bf16 "
    "{%0, %1, %2, %3, %4, %5, %6, %7, %8, %9, %10, %11, %12, %13, %14, %15, "
    "%16, %17, %18, %19}, "
    "{%20, %21, %22, %23}, %24, p, 1, 1, 1;\n}\n"
    : "+f"(d[0]), "+f"(d[1]), "+f"(d[2]), "+f"(d[3]), "+f"(d[4]), "+f"(d[5]), "+f"(d[6]), "+f"(d[7]),
      "+f"(d[8]), "+f"(d[9]), "+f"(d[10]), "+f"(d[11]), "+f"(d[12]), "+f"(d[13]), "+f"(d[14]), "+f"(d[15]),
      "+f"(d[16]), "+f"(d[17]), "+f"(d[18]), "+f"(d[19])
    : "r"(a0), "r"(a1), "r"(a2), "r"(a3), "l"(db), "r"(scale_d));
}

__device__ __forceinline__ void wg_n64_rs_nb_f16_f32(float (&d)[32], uint32_t a0, uint32_t a1, uint32_t a2, uint32_t a3, uint64_t db, int scale_d) {
  asm volatile("{\n.reg .pred p;\nsetp.ne.b32 p, %37, 0;\n"
    "wgmma.mma_async.sync.aligned.m64n64k16.f32.f16.f16 "
    "{%0, %1, %2, %3, %4, %5, %6, %7, %8, %9, %10, %11, %12, %13, %14, %15, "
    "%16, %17, %18, %19, %20, %21, %22, %23, %24, %25, %26, %27, %28, %29, %30, %31}, "
    "{%32, %33, %34, %35}, %36, p, 1, 1, 0;\n}\n"
    : "+f"(d[0]), "+f"(d[1]), "+f"(d[2]), "+f"(d[3]), "+f"(d[4]), "+f"(d[5]), "+f"(d[6]), "+f"(d[7]),
      "+f"(d[8]), "+f"(d[9]), "+f"(d[10]), "+f"(d[11]), "+f"(d[12]), "+f"(d[13]), "+f"(d[14]), "+f"(d[15]),
      "+f"(d[16]), "+f"(d[17]), "+f"(d[18]), "+f"(d[19]), "+f"(d[20]), "+f"(d[21]), "+f"(d[22]), "+f"(d[23]),
      "+f"(d[24]), "+f"(d[25]), "+f"(d[26]), "+f"(d[27]), "+f"(d[28]), "+f"(d[29]), "+f"(d[30]), "+f"(d[31])
    : "r"(a0), "r"(a1), "r"(a2), "r"(a3), "l"(db), "r"(scale_d));
}

__device__ __forceinline__ void wg_n64_rs_nb_f16_f16(uint32_t (&d)[16], uint32_t a0, uint32_t a1, uint32_t a2, uint32_t a3, uint64_t db, int scale_d) {
  asm volatile("{\n.reg .pred p;\nsetp.ne.b32 p, %21, 0;\n"
    "wgmma.mma_async.sync.aligned.m64n64k16.f16.f16.f16 "
    "{%0, %1, %2, %3, %4, %5, %6, %7, %8, %9, %10, %11, %12, %13, %14, %15}, "
    "{%16, %17, %18, %19}, %20, p, 1, 1, 0;\n}\n"
    : "+r"(d[0]), "+r"(d[1]), "+r"(d[2]), "+r"(d[3]), "+r"(d[4]), "+r"(d[5]), "+r"(d[6]), "+r"(d[7]),
      "+r"(d[8]), "+r"(d[9]), "+r"(d[10]), "+r"(d[11]), "+r"(d[12]), "+r"(d[13]), "+r"(d[14]), "+r"(d[15])
    : "r"(a0), "r"(a1), "r"(a2), "r"(a3), "l"(db), "r"(scale_d));
}

__device__ __forceinline__ void wg_n64_rs_nb_f16_f32_z(float (&d)[32], uint32_t a0, uint32_t a1, uint32_t a2, uint32_t a3, uint64_t db, int scale_d) {
  asm volatile("{\n.reg .pred p;\nsetp.ne.b32 p, %37, 0;\n"
    "wgmma.mma_async.sync.aligned.m64n64k16.f32.f16.f16 "
    "{%0, %1, %2, %3, %4, %5, %6, %7, %8, %9, %10, %11, %12, %13, %14, %15, "
    "%16, %17, %18, %19, %20, %21, %22, %23, %24, %25, %26, %27, %28, %29, %30, %31}, "
    "{%32, %33, %34, %35}, %36, p, 1, 1, 0;\n}\n"
    : "=f"(d[0]), "=f"(d[1]), "=f"(d[2]), "=f"(d[3]), "=f"(d[4]), "=f"(d[5]), "=f"(d[6]), "=f"(d[7]),
      "=f"(d[8]), "=f"(d[9]), "=f"(d[10]), "=f"(d[11]), "=f"(d[12]), "=f"(d[13]), "=f"(d[14]), "=f"(d[15]),
      "=f"(d[16]), "=f"(d[17]), "=f"(d[18]), "=f"(d[19]), "=f"(d[20]), "=f"(d[21]), "=f"(d[22]), "=f"(d[23]),
      "=f"(d[24]), "=f"(d[25]), "=f"(d[26]), "=f"(d[27]), "=f"(d[28]), "=f"(d[29]), "=f"(d[30]), "=f"(d[31])
    : "r"(a0), "r"(a1), "r"(a2), "r"(a3), "l"(db), "r"(scale_d));
}

__device__ __forceinline__ void wg_n64_rs_nb_f16_f16_z(uint32_t (&d)[16], uint32_t a0, uint32_t a1, uint32_t a2, uint32_t a3, uint64_t db, int scale_d) {
  asm volatile("{\n.reg .pred p;\nsetp.ne.b32 p, %21, 0;\n"
    "wgmma.mma_async.sync.aligned.m64n64k16.f16.f16.f16 "
    "{%0, %1, %2, %3, %4, %5, %6, %7, %8, %9, %10, %11, %12, %13, %14, %15}, "
    "{%16, %17, %18, %19}, %20, p, 1, 1, 0;\n}\n"
    : "=r"(d[0]), "=r"(d[1]), "=r"(d[2]), "=r"(d[3]), "=r"(d[4]), "=r"(d[5]), "=r"(d[6]), "=r"(d[7]),
      "=r"(d[8]), "=r"(d[9]), "=r"(d[10]), "=r"(d[11]), "=r"(d[12]), "=r"(d[13]), "=r"(d[14]), "=r"(d[15])
    : "r"(a0), "r"(a1), "r"(a2), "r"(a3), "l"(db), "r"(scale_d));
}

#define DEVINL __device__ __forceinline__
DEVINL void wg_fence() { asm volatile("wgmma.fence.sync.aligned;" ::: "memory"); }
DEVINL void wg_commit() { asm volatile("wgmma.commit_group.sync.aligned;" ::: "memory"); }
template <int N> DEVINL void wg_wait() { asm volatile("wgmma.wait_group.sync.aligned %0;" ::"n"(N) : "memory"); }
__host__ DEVINL uint64_t mkdesc(uint32_t addr, uint32_t lbo, uint32_t sbo, int sw) {
  return (uint64_t)((addr & 0x3FFFF) >> 4) | ((uint64_t)(lbo >> 4) << 16) | ((uint64_t)(sbo >> 4) << 32) | ((uint64_t)sw << 62);
}
DEVINL void mbar_init(uint32_t bar, uint32_t cnt) { asm volatile("mbarrier.init.shared::cta.b64 [%0], %1;" ::"r"(bar), "r"(cnt) : "memory"); }
DEVINL void mbar_arrive(uint32_t bar) { asm volatile("mbarrier.arrive.shared::cta.b64 _, [%0];" ::"r"(bar) : "memory"); }
DEVINL bool mbar_try(uint32_t bar, uint32_t parity) {
  uint32_t ok;
  asm volatile("{\n.reg .pred p;\nmbarrier.try_wait.parity.shared::cta.b64 p, [%1], %2;\nselp.u32 %0, 1, 0, p;\n}" : "=r"(ok) : "r"(bar), "r"(parity) : "memory");
  return ok;
}
DEVINL bool mbar_test(uint32_t bar, uint32_t parity) {
  uint32_t ok;
  asm volatile("{\n.reg .pred p;\nmbarrier.test_wait.parity.shared::cta.b64 p, [%1], %2;\nselp.u32 %0, 1, 0, p;\n}" : "=r"(ok) : "r"(bar), "r"(parity) : "memory");
  return ok;
}
DEVINL void mbar_wait(uint32_t bar, uint32_t parity) {
#pragma unroll 1
  for (uint32_t n = 0; n < 100000u; n++) if (mbar_try(bar, parity)) break;
}
#define EL(txt) "{\n.reg .pred pe;\nelect.sync _|pe, 0xffffffff;\n@pe " txt "\n}"
DEVINL void e_expect_tx(uint32_t bar, uint32_t bytes) { asm volatile(EL("mbarrier.arrive.expect_tx.shared::cta.b64 _, [%0], %1;") ::"r"(bar), "r"(bytes) : "memory"); }
DEVINL void e_arrive(uint32_t bar) { asm volatile(EL("mbarrier.arrive.shared::cta.b64 _, [%0];") ::"r"(bar) : "memory"); }
DEVINL void e_arrive_if(uint32_t bar, int c) {
  asm volatile("{\n.reg .pred pe;\nelect.sync _|pe, 0xffffffff;\nsetp.ne.and.b32 pe, %1, 0, pe;\n@pe mbarrier.arrive.shared::cta.b64 _, [%0];\n}" ::"r"(bar), "r"(c) : "memory");
}
DEVINL void e_red(uint32_t* p) { asm volatile(EL("red.release.gpu.global.add.u32 [%0], 1;") ::"l"(p) : "memory"); }
DEVINL void e_red_relaxed(uint32_t* p) { asm volatile(EL("red.relaxed.gpu.global.add.u32 [%0], 1;") ::"l"(p) : "memory"); }
DEVINL void release_add(uint32_t* p, int on) {
  asm volatile("{\n.reg .pred q;\nsetp.ne.b32 q, %1, 0;\nfence.release.gpu;\n@q red.relaxed.gpu.global.add.u32 [%0], 1;\n}" ::"l"(p), "r"(on) : "memory");
}
#define PREPARED(p, on) do { asm volatile("" : "+l"(p), "+r"(on)); asm volatile("griddepcontrol.launch_dependents;" ::: "memory"); } while (0)
DEVINL void tma_ld(uint32_t dst, const CUtensorMap* m, int c0, int c1, uint32_t bar) {
  asm volatile(EL("cp.async.bulk.tensor.2d.shared::cluster.global.mbarrier::complete_tx::bytes [%0], [%1, {%3, %4}], [%2];")
               ::"r"(dst), "l"(m), "r"(bar), "r"(c0), "r"(c1) : "memory");
}
DEVINL void tma_ld3(uint32_t dst, const CUtensorMap* m, int c0, int c1, int c2, uint32_t bar) {
  asm volatile(EL("cp.async.bulk.tensor.3d.shared::cluster.global.mbarrier::complete_tx::bytes [%0], [%1, {%3, %4, %5}], [%2];")
               ::"r"(dst), "l"(m), "r"(bar), "r"(c0), "r"(c1), "r"(c2) : "memory");
}
DEVINL void tma_ld5(uint32_t dst, const CUtensorMap* m, int c2, int c3, int c4, uint32_t bar) {
  asm volatile(EL("cp.async.bulk.tensor.5d.shared::cluster.global.mbarrier::complete_tx::bytes [%0], [%1, {0, 0, %3, %4, %5}], [%2];")
               ::"r"(dst), "l"(m), "r"(bar), "r"(c2), "r"(c3), "r"(c4) : "memory");
}
DEVINL void tma_ld_mc(uint32_t dst, const CUtensorMap* m, int c0, int c1, uint32_t bar) {
  asm volatile(EL("cp.async.bulk.tensor.2d.shared::cluster.global.mbarrier::complete_tx::bytes.multicast::cluster [%0], [%1, {%3, %4}], [%2], %5;")
               ::"r"(dst), "l"(m), "r"(bar), "r"(c0), "r"(c1), "h"((uint16_t)3) : "memory");
}
DEVINL void e_arrive_both(uint32_t bar) {
  asm volatile("{\n.reg .pred pe;\n.reg .b32 r0, r1;\nelect.sync _|pe, 0xffffffff;\nmapa.shared::cluster.u32 r0, %0, 0;\nmapa.shared::cluster.u32 r1, %0, 1;\n"
               "@pe mbarrier.arrive.shared::cluster.b64 _, [r0];\n@pe mbarrier.arrive.shared::cluster.b64 _, [r1];\n}" ::"r"(bar) : "memory");
}
DEVINL void tma_st(const CUtensorMap* m, int c0, int c1, uint32_t src) {
  asm volatile(EL("cp.async.bulk.tensor.2d.global.shared::cta.bulk_group [%0, {%2, %3}], [%1];") ::"l"(m), "r"(src), "r"(c0), "r"(c1) : "memory");
}
DEVINL void bulk_commit() { asm volatile("cp.async.bulk.commit_group;" ::: "memory"); }
template <int N> DEVINL void bulk_wait_n() { asm volatile("cp.async.bulk.wait_group %0;\nbar.warp.sync 0xffffffff;" ::"n"(N) : "memory"); }
DEVINL void l2_prefetch(const void* g, uint32_t bytes) { asm volatile(EL("cp.async.bulk.prefetch.L2.global [%0], %1;") ::"l"(g), "r"(bytes) : "memory"); }
DEVINL void fence_async_smem() { asm volatile("fence.proxy.async.shared::cta;" ::: "memory"); }
DEVINL void fence_async_gl() { asm volatile("fence.proxy.async.global;" ::: "memory"); }
DEVINL void cluster_wait() { asm volatile("barrier.cluster.wait.aligned;" ::: "memory"); }
DEVINL void bar_sync(int id, int n) { asm volatile("bar.sync %0, %1;" ::"r"(id), "r"(n) : "memory"); }
DEVINL void bar_arrive(int id, int n) { asm volatile("bar.arrive %0, %1;" ::"r"(id), "r"(n) : "memory"); }
DEVINL uint32_t ld_acquire(const uint32_t* p) { uint32_t v; asm volatile("ld.acquire.gpu.global.u32 %0, [%1];" : "=r"(v) : "l"(p) : "memory"); return v; }
DEVINL void await_flag(int j, uint32_t& rdy, const uint32_t* p, uint32_t target) {
  if ((rdy >> j) & 1) return;
#pragma unroll 1
  for (uint32_t n = 0; n < 200000u && !((rdy >> j) & 1); n++) rdy = __ballot_sync(~0u, (int)(ld_acquire(p) - target) >= 0);
  asm volatile("fence.proxy.async.global;" ::: "memory");
}
DEVINL void poll_ge(const uint32_t* p, uint32_t target) {
#pragma unroll 1
  for (uint32_t n = 0; n < 200000u; n++) if (__all_sync(~0u, (int)(ld_acquire(p) - target) >= 0)) break;
}
DEVINL int lane_id() { int v; asm volatile("mov.u32 %0, %%laneid;" : "=r"(v)); return v; }
__host__ DEVINL int remap(int v) {
  const int c = v >> 1, u = c - 36, r = (u * 37) >> 8;
  const int L = c < 4 ? 32 + 8 * c : c < 36 ? c - 4 : 33 + u + r;
  return 2 * L + (v & 1);
}
DEVINL int block_id() { int v; asm volatile("mov.u32 %0, %%ctaid.x;" : "=r"(v)); return v; }
#define cta_id() prm.map[block_id()]
#define IDS() const int lane = lane_id(), b = cta_id(), bm = b >> 4, bn = b & 15, rank = b & 1, pm = 2 * bm + (bn >> 3), pn = bn & 7, po = pm & 1; \
  (void)lane; (void)bm; (void)bn; (void)rank; (void)pm; (void)pn; (void)po
DEVINL void st_tagged(uint4* p, uint32_t a, uint32_t b, uint32_t c, uint32_t tag) {
  asm volatile("{\n.reg .b64 u, v;\n.reg .b128 t;\nmov.b64 u, {%1, %2};\nmov.b64 v, {%3, %4};\nmov.b128 t, {u, v};\nst.relaxed.gpu.global.b128 [%0], t;\n}"
               ::"l"(p), "r"(a), "r"(b), "r"(c), "r"(tag) : "memory");
}
DEVINL uint32_t ld_tagged(const uint4* p, uint32_t* r) {
  uint32_t tag;
  asm volatile("{\n.reg .b64 u, v;\n.reg .b128 t;\nld.relaxed.gpu.global.b128 t, [%4];\nmov.b128 {u, v}, t;\nmov.b64 {%0, %1}, u;\nmov.b64 {%2, %3}, v;\n}"
               : "=r"(r[0]), "=r"(r[1]), "=r"(r[2]), "=r"(tag) : "l"(p) : "memory");
  return tag;
}
DEVINL float ex2(float x) { float y; asm("ex2.approx.ftz.f32 %0, %1;" : "=f"(y) : "f"(x)); return y; }
DEVINL float rcp(float x) { float y; asm("rcp.approx.ftz.f32 %0, %1;" : "=f"(y) : "f"(x)); return y; }
DEVINL uint32_t pack2(float lo, float hi) { uint32_t r; asm("cvt.rn.bf16x2.f32 %0, %1, %2;" : "=r"(r) : "f"(hi), "f"(lo)); return r; }
DEVINL uint32_t pack2h(float lo, float hi) { uint32_t r; asm("cvt.rn.f16x2.f32 %0, %1, %2;" : "=r"(r) : "f"(hi), "f"(lo)); return r; }
DEVINL uint32_t prmt0(uint32_t a, uint32_t sel) { uint32_t r; asm("prmt.b32 %0, %1, 0, %2;" : "=r"(r) : "r"(a), "r"(sel)); return r; }
DEVINL void stg128(const void* p, uint32_t a, uint32_t b, uint32_t c, uint32_t d) {
  asm volatile("st.global.v4.b32 [%0], {%1, %2, %3, %4};" ::"l"(p), "r"(a), "r"(b), "r"(c), "r"(d) : "memory");
}
DEVINL float bf_lo(uint32_t w) { return __uint_as_float(w << 16); }
DEVINL float bf_hi(uint32_t w) { return __uint_as_float(w & 0xFFFF0000u); }
DEVINL float bf_round(float x) { return bf_lo(pack2(x, 0.f)); }
DEVINL uint32_t add_bf16x2(uint32_t a, uint32_t b) { uint32_t r; asm("add.rn.bf16x2 %0, %1, %2;" : "=r"(r) : "r"(a), "r"(b)); return r; }
DEVINL void stsm4(uint32_t addr, uint32_t a, uint32_t b, uint32_t c, uint32_t d) {
  asm volatile("stmatrix.sync.aligned.m8n8.x4.shared.b16 [%0], {%1, %2, %3, %4};" ::"r"(addr), "r"(a), "r"(b), "r"(c), "r"(d) : "memory");
}
DEVINL void ldsm4(uint32_t addr, uint32_t (&r)[4]) {
  asm volatile("ldmatrix.sync.aligned.m8n8.x4.shared.b16 {%0, %1, %2, %3}, [%4];" : "=r"(r[0]), "=r"(r[1]), "=r"(r[2]), "=r"(r[3]) : "r"(addr) : "memory");
}
DEVINL void ldsm4t(uint32_t addr, uint32_t (&r)[4]) {
  asm volatile("ldmatrix.sync.aligned.m8n8.x4.trans.shared.b16 {%0, %1, %2, %3}, [%4];" : "=r"(r[0]), "=r"(r[1]), "=r"(r[2]), "=r"(r[3]) : "r"(addr) : "memory");
}
DEVINL void sts128(uint32_t addr, uint32_t a, uint32_t b, uint32_t c, uint32_t d) {
  asm volatile("st.shared.v4.b32 [%0], {%1, %2, %3, %4};" ::"r"(addr), "r"(a), "r"(b), "r"(c), "r"(d) : "memory");
}
DEVINL float2 lds64f(uint32_t addr) { float2 v; asm volatile("ld.shared.v2.f32 {%0, %1}, [%2];" : "=f"(v.x), "=f"(v.y) : "r"(addr) : "memory"); return v; }
DEVINL void mma16816(float (&d)[4], uint32_t a0, uint32_t a1, uint32_t a2, uint32_t a3, uint32_t b0, uint32_t b1) {
  asm("mma.sync.aligned.m16n8k16.row.col.f32.bf16.bf16.f32 {%0, %1, %2, %3}, {%4, %5, %6, %7}, {%8, %9}, {%0, %1, %2, %3};"
               : "+f"(d[0]), "+f"(d[1]), "+f"(d[2]), "+f"(d[3]) : "r"(a0), "r"(a1), "r"(a2), "r"(a3), "r"(b0), "r"(b1));
}
template <int N> DEVINL void fence_regs(float (&d)[N]) {
#pragma unroll
  for (int i = 0; i < N; i++) asm volatile("" : "+f"(d[i])::"memory");
}
template <int N> DEVINL void fence_regs(uint32_t (&d)[N]) {
#pragma unroll
  for (int i = 0; i < N; i++) asm volatile("" : "+r"(d[i])::"memory");
}
DEVINL void lds128(uint32_t addr, uint32_t* r) {
  asm volatile("ld.shared.v4.b32 {%0, %1, %2, %3}, [%4];" : "=r"(r[0]), "=r"(r[1]), "=r"(r[2]), "=r"(r[3]) : "r"(addr) : "memory");
}
DEVINL void sched_fence() { asm volatile("griddepcontrol.launch_dependents;" ::: "memory"); }

struct Scratch {
  bf16 k[32 * 2048 * 32];
  bf16 xs[2048 * 1024];
  bf16 os[2048 * 1024];
  bf16 v[32 * 2048 * 32];
  float kn[2 * 128 * 16];
  uint32_t cnt[256 * 32];
  float2 stats[8 * 2048];
  uint4 halo[2 * 128 * 12 * 32];
  float csp[2 * 16 * 8 * 192];
  uint4 qsave[128 * 256 * 8];
  uint32_t esc[4 * 65536 * 20];
};
__device__ __align__(1024) Scratch g_s;
#define g_k g_s.k
#define g_xs g_s.xs
#define g_os g_s.os
#define g_v g_s.v
#define g_kn g_s.kn
#define g_cnt g_s.cnt
#define g_stats g_s.stats
#define g_halo g_s.halo
#define g_csp g_s.csp
#define g_qsave g_s.qsave
#define g_esc g_s.esc
#define g_epoch g_s.cnt[255 * 32]

DEVINL uint32_t* cnt_x(int l, int bm) { return g_cnt + (l * 8 + bm) * 32; }
DEVINL uint32_t* cnt_o(int l, int pm, int h) { return g_cnt + (32 + (l * 16 + pm) * 2 + h) * 32; }
DEVINL uint32_t* cnt_kv(int lb, int bn) { return g_cnt + (160 + lb * 16 + bn) * 32; }
DEVINL uint32_t* cnt_ad(int bn) { return g_cnt + (192 + bn) * 32; }
DEVINL uint32_t* cnt_cs(int t, int bn) { return g_cnt + (208 + t * 16 + bn) * 32; }

DEVINL int qord(int i, int l, int pn) { return l == 0 ? i : i < 4 ? ((2 * pn) ^ (i & 2)) + (i & 1) : i - 4 < 2 * (pn & 6) ? i - 4 : i; }
struct Params {
  CUtensorMap m[15];
  const bf16* x0;
  const bf16* wq[2];
  uint32_t zero;
  int map[128];
  uint64_t wd, xd;
  struct __align__(16) { uint64_t kd, vd; } kv[4];
};
enum { M_X0A = 0, M_XSA, M_WQA, M_WQB, M_WOA, M_WOB, M_OS, M_K, M_V, M_X0R, M_XSR, M_XSO, M_OUT, M_XST, M_X0H, M_COUNT };

constexpr uint32_t QSTG = 57344;
constexpr uint32_t T0 = 65536, TSTG = 32768;
constexpr uint32_t ONES = 230400;
constexpr uint32_t PSTG = 32768, RES = 196608;
constexpr uint32_t KSC = 98304, VSC = 133120, HRS = 167936;
constexpr uint32_t ROWST = 229376, COLS = 231424, BARS = 232192, SMEM_BYTES = 232448;
constexpr uint32_t B_QF = BARS, B_QE = BARS + 32, B_TF = BARS + 64, B_TE = BARS + 96, B_PF = BARS + 128, B_PE = BARS + 176,
                   B_RF = BARS + 224, W_X = BARS + 232, B_QL = BARS + 240, B_PA = BARS + 248;
enum { NB_ST = 1, NB_KV = 2  , NB_DONE = 3, NB_SC = 4, NB_SIG = 5  , NB_KN = 9  , NB_X = 11, NB_HALO = 12  , NB_X0 = 15 };

DEVINL uint32_t pslot_b(uint32_t s) { return ((0x320415u >> (4 * s)) & 7) * 16384u; }
DEVINL uint32_t pslot_a(uint32_t s, int l) { return 98304u + ((((l & 1) ? 0x541230u : 0x041235u) >> (4 * s)) & 7) * 16384u; }

constexpr float QSCALE = 0.17677669529663687f * 1.4426950408889634f;
constexpr uint32_t QPARK = 32768;

DEVINL uint32_t exp2_h2(uint32_t s, uint32_t c852) {
  uint32_t r, t, w, m, d;
  asm volatile("{.reg .b64 t; add.rn.f16x2 %0, %1, %2; cvt.u64.u32 t, %0; cvt.u32.u64 %0, t;}" : "=r"(r) : "r"(s), "r"(0x65EA65EAu));
  asm volatile("fma.rn.f16x2 %0, %1, %2, %3;" : "=r"(t) : "r"(r), "r"(0xB880B880u), "r"(c852));
  asm volatile("fma.rn.f16x2 %0, %1, %2, %3;" : "=r"(w) : "r"(s), "r"(0x38803880u), "r"(t));
  asm volatile("fma.rn.f16x2 %0, %1, %1, %2;" : "=r"(m) : "r"(w), "r"(0x4A1F4A2Du));
  asm volatile("{.reg .b32 t; shf.l.clamp.b32 t, %2, %1, 7; add.u32 %0, t, %2;}" : "=r"(d) : "r"(r), "r"(m));
  return d;
}
DEVINL float exp2_fix(float s) { float z; asm volatile("add.rn.f32 %0, %1, 0f43BF34BC;" : "=f"(z) : "f"(s)); return z; }
DEVINL uint32_t exp2_base(float z0, float z1) { uint32_t B; asm volatile("prmt.b32 %0, %1, %2, 0x6521;" : "=r"(B) : "r"(__float_as_uint(z0)), "r"(__float_as_uint(z1))); return B; }
template <uint32_t MASK> DEVINL uint32_t and_or(uint32_t a, uint32_t c) { uint32_t r; asm volatile("lop3.b32 %0, %1, %3, %2, 0xEA;" : "=r"(r) : "r"(a), "r"(c), "n"(MASK)); return r; }
DEVINL uint32_t fma_bf2(uint32_t a, uint32_t b, uint32_t c) { uint32_t r; asm volatile("fma.rn.bf16x2 %0, %1, %2, %3;" : "=r"(r) : "r"(a), "r"(b), "r"(c)); return r; }
DEVINL float ex2v(float x) { float y; asm volatile("ex2.approx.ftz.f32 %0, %1;" : "=f"(y) : "f"(x)); return y; }
DEVINL uint32_t pack2v(float lo, float hi) { uint32_t r; asm volatile("cvt.rn.bf16x2.f32 %0, %1, %2;" : "=r"(r) : "f"(hi), "f"(lo)); return r; }
DEVINL void unesc(uint32_t (&u)[4], const uint32_t* esc, uint32_t tag) {
  const bool saved = __ldcg(esc + 16) == tag;
#pragma unroll
  for (int j = 0; j < 4; j++) {
    float lo, hi;
    asm("{.reg .f16 a, b; mov.b32 {a, b}, %2; cvt.f32.f16 %0, a; cvt.f32.f16 %1, b;}" : "=f"(lo), "=f"(hi) : "r"(u[j]));
    u[j] = saved ? __ldcg(esc + 4 * j) : pack2(lo, hi);
  }
}

DEVINL void attn_slow(const uint32_t (&q)[8], int head, const uint32_t* kesc, uint32_t tag, float (&res)[20], int lane) {
  const int g = lane >> 2, qd = lane & 3;
  const bf16* kb = g_k + (size_t)head * 2048 * 32;
  const bf16* vb = g_v + (size_t)head * 2048 * 32;
  float o[4][4], m0 = -INFINITY, m1 = -INFINITY, l0 = 0.f, l1 = 0.f;
#pragma unroll
  for (int j = 0; j < 4; j++) { o[j][0] = o[j][1] = o[j][2] = o[j][3] = 0.f; }
#pragma unroll 1
  for (int k0 = 0; k0 < 2048; k0 += 16) {
    float s[2][4];
#pragma unroll
    for (int nt = 0; nt < 2; nt++) {
      s[nt][0] = s[nt][1] = s[nt][2] = s[nt][3] = 0.f;
      const uint32_t* kp = (const uint32_t*)(kb + (size_t)(k0 + nt * 8 + g) * 32) + qd;
      uint32_t k[4] = {__ldcg(kp), __ldcg(kp + 4), __ldcg(kp + 8), __ldcg(kp + 12)};
      unesc(k, kesc + (k0 + nt * 8 + g) * 20 + qd, tag);
      __syncwarp();
      mma16816(s[nt], q[0], q[1], q[2], q[3], k[0], k[1]);
      mma16816(s[nt], q[4], q[5], q[6], q[7], k[2], k[3]);
    }
    float a0 = fmaxf(fmaxf(s[0][0], s[0][1]), fmaxf(s[1][0], s[1][1]));
    float a1 = fmaxf(fmaxf(s[0][2], s[0][3]), fmaxf(s[1][2], s[1][3]));
    a0 = fmaxf(a0, __shfl_xor_sync(~0u, a0, 1)); a0 = fmaxf(a0, __shfl_xor_sync(~0u, a0, 2));
    a1 = fmaxf(a1, __shfl_xor_sync(~0u, a1, 1)); a1 = fmaxf(a1, __shfl_xor_sync(~0u, a1, 2));
    const float n0 = fmaxf(m0, a0), n1 = fmaxf(m1, a1);
    const float c0 = (m0 == n0) ? 1.f : ex2(m0 - n0), c1 = (m1 == n1) ? 1.f : ex2(m1 - n1);
    m0 = n0; m1 = n1;
    const uint32_t p0 = pack2(ex2(s[0][0] - n0), ex2(s[0][1] - n0)), p1 = pack2(ex2(s[0][2] - n1), ex2(s[0][3] - n1));
    const uint32_t p2 = pack2(ex2(s[1][0] - n0), ex2(s[1][1] - n0)), p3 = pack2(ex2(s[1][2] - n1), ex2(s[1][3] - n1));
    l0 = l0 * c0 + bf_lo(p0) + bf_hi(p0) + bf_lo(p2) + bf_hi(p2);
    l1 = l1 * c1 + bf_lo(p1) + bf_hi(p1) + bf_lo(p3) + bf_hi(p3);
#pragma unroll
    for (int j = 0; j < 4; j++) {
      o[j][0] *= c0; o[j][1] *= c0; o[j][2] *= c1; o[j][3] *= c1;
      const unsigned short* vp = (const unsigned short*)(vb + (size_t)(k0 + 2 * qd) * 32 + j * 8 + g);
      const uint32_t b0 = (uint32_t)__ldcg(vp) | ((uint32_t)__ldcg(vp + 32) << 16);
      const uint32_t b1 = (uint32_t)__ldcg(vp + 256) | ((uint32_t)__ldcg(vp + 288) << 16);
      mma16816(o[j], p0, p1, p2, p3, b0, b1);
    }
  }
  l0 += __shfl_xor_sync(~0u, l0, 1); l0 += __shfl_xor_sync(~0u, l0, 2);
  l1 += __shfl_xor_sync(~0u, l1, 1); l1 += __shfl_xor_sync(~0u, l1, 2);
#pragma unroll
  for (int j = 0; j < 4; j++) { res[4 * j] = o[j][0]; res[4 * j + 1] = o[j][1]; res[4 * j + 2] = o[j][2]; res[4 * j + 3] = o[j][3]; }
  res[16] = l0; res[18] = l1;
}

__device__ __noinline__ void attn_redo(int redo, int l, int b, int wg, int w, uint32_t tag) {
  const int lane = lane_id();
#pragma unroll 1
  for (int t = 0; t < 4; t++) {
    const int h = t >> 1, head = 2 * (b & 15) + h, row = (b >> 4) * 256 + wg * 128 + (t & 1) * 64 + w * 16 + (lane >> 2);
    if ((redo >> t) & 1) {
      const uint32_t* esc = g_esc + (size_t)((l & 2) * 65536 + head * 2048) * 20;
      const uint32_t* qs = (const uint32_t*)(g_qsave + (block_id() * 256 + wg * 128 + w * 32 + lane) * 8 + 2 * t);
      uint32_t q[8]; float o[20];
#pragma unroll
      for (int i = 0; i < 2; i++) {
        uint32_t u[4] = {__ldcg(qs + i), __ldcg(qs + i + 2), __ldcg(qs + i + 4), __ldcg(qs + i + 6)};
        unesc(u, esc + (row + i * 8) * 20 + (lane & 3), tag);
        q[i] = u[0]; q[i + 2] = u[1]; q[i + 4] = u[2]; q[i + 6] = u[3];
      }
      __syncwarp();
      attn_slow(q, head, esc + 65536 * 20, tag, o, lane);
      const float i0 = rcp(o[16]), i1 = rcp(o[18]);
      bf16* op = g_os + (size_t)row * 1024 + h * 512 + (b & 15) * 32 + (lane & 3) * 8;
      *(uint4*)op = make_uint4(pack2(o[0] * i0, o[1] * i0), pack2(o[4] * i0, o[5] * i0), pack2(o[8] * i0, o[9] * i0), pack2(o[12] * i0, o[13] * i0));
      *(uint4*)(op + 8 * 1024) = make_uint4(pack2(o[2] * i1, o[3] * i1), pack2(o[6] * i1, o[7] * i1), pack2(o[10] * i1, o[11] * i1), pack2(o[14] * i1, o[15] * i1));
    }
    if ((t & 1) && ((redo >> 2 * h) & 3)) bar_arrive(NB_SIG + 2 * h + wg, 160 + 32 * (h & wg));
  }
}

__global__ void __cluster_dims__(2, 1, 1) __launch_bounds__(384, 1) fused_kernel(const __grid_constant__ Params prm) {
  extern __shared__ __align__(1024) char smem[];
  const uint32_t sb = (uint32_t)__cvta_generic_to_shared(smem);
  const int tid = threadIdx.x, lane = tid & 31;
  const int wg = __shfl_sync(0xffffffffu, tid >> 7, 0);
  const int w = __shfl_sync(0xffffffffu, (tid >> 5) & 3, 0);
  const int bm = remap(blockIdx.x) >> 4, bn = remap(blockIdx.x) & 15;

  auto first_tile = [&](int kt) {
    e_expect_tx(sb + B_QF + 8 * kt, QSTG);
    tma_ld(sb + kt * QSTG, &prm.m[M_X0A], kt * 64, bm * 256, sb + B_QF + 8 * kt);
    tma_ld3(sb + kt * QSTG + 32768, &prm.m[M_WQA], bn * 64, kt * 64, 0, sb + B_QF + 8 * kt);
  };
  auto init4 = [&](uint32_t bar, uint32_t c0, uint32_t c1, uint32_t c2, uint32_t c3) {
    asm volatile("{\n.reg .pred pe;\nelect.sync _|pe, 0xffffffff;\n@pe mbarrier.init.shared::cta.b64 [%0], %1;\n@pe mbarrier.init.shared::cta.b64 [%0+8], %2;\n"
                 "@pe mbarrier.init.shared::cta.b64 [%0+16], %3;\n@pe mbarrier.init.shared::cta.b64 [%0+24], %4;\n@pe fence.mbarrier_init.release.cluster;\n}"
                 ::"r"(bar), "r"(c0), "r"(c1), "r"(c2), "r"(c3) : "memory");
  };
  if (wg < 2) {
    const uint32_t k = wg * 4 + w, lo = (0x1411814u >> (4 * k)) & 15, hi = (0x1441814u >> (4 * k)) & 15;
    if (tid < 32) asm volatile("prefetch.global.L2 [%0];" ::"l"(prm.x0 + (size_t)(bm * 256 + bn * 16 + (tid & 15)) * 1024 + (tid >> 4) * 64));
    else if (tid < 80) asm volatile("prefetch.global.L2 [%0];" ::"l"(prm.wq[0] + (bm * 16 + (tid & 15)) * 3072 + ((tid >> 4) - 2) * 1024 + bn * 64));
    __syncwarp();
    if (k < 7) init4(sb + B_QE + 32 * k, lo, lo, hi, k == 6 ? 2 : hi);
    __syncwarp();
    if (k == 6 && lane == 0) *(volatile unsigned long long*)(smem + W_X) = 0ull;
  } else if (w == 0) {
    init4(sb + B_QF, 1, 1, 1, 1);
    __syncwarp();
    first_tile(0);
  }
  __syncthreads();
  asm volatile("barrier.cluster.arrive.relaxed.aligned;" ::: "memory");

  if (wg == 2) {
    asm volatile("setmaxnreg.dec.sync.aligned.u32 56;");
    const uint32_t ep1 = *(volatile uint32_t*)&g_epoch + 1;
    if (w == 0) {
      first_tile(1);
      mbar_wait(sb + B_QF, 0);
      first_tile(2); first_tile(3);
#pragma unroll 1
      for (int kt = 4; kt < 16; kt++) l2_prefetch(prm.wq[0] + kt * 196608 + blockIdx.x * 1536, 3072);
      cluster_wait();
#pragma unroll 1
      for (int l = 0; l < 4; l++) {
        IDS();
        const CUtensorMap* mw = &prm.m[M_WQA + (l & 1)];
        const CUtensorMap* mx = &prm.m[l == 0 ? M_X0A : M_XSA];
        const CUtensorMap* mh = &prm.m[l == 0 ? M_X0H : M_XSO];
        const CUtensorMap* mo = &prm.m[M_WOA + (l & 1)];
        auto q_b = [&](int i) {
          const int s = i & 3;
          mbar_wait(sb + B_QE + 8 * s, ((i >> 2) & 1) ^ 1);
          e_expect_tx(sb + B_QF + 8 * s, QSTG);
          tma_ld3(sb + s * QSTG + 32768, mw, bn * 64, qord(i, l, pn) * 64, 0, sb + B_QF + 8 * s);
        };
        uint32_t rdy = l ? 0u : ~0u;
        auto q_a = [&](int i) {
          const int kt = qord(i, l, pn);
          await_flag(kt, rdy, cnt_x(l, bm) + (lane & 15), ep1 * 2);
          if (i < 4) tma_ld(sb + i * QSTG, mx, kt * 64, bm * 256, sb + B_QF + 8 * i);
          else tma_ld_mc(sb + (i & 3) * QSTG + rank * 16384, mh, kt * 64, bm * 256 + rank * 128, sb + B_QF + 8 * (i & 3));
        };
        if (l > 0) {
#pragma unroll 1
          for (int i = 0; i < 2; i++) {
            await_flag(2 * pn + i, rdy, cnt_x(l, bm) + (lane & 15), ep1 * 2);
            e_expect_tx(sb + B_QF + 8 * i, 16384);
            tma_ld(sb + i * QSTG + (po ^ 1) * 16384, &prm.m[M_XSO], (2 * pn + i) * 64, (pm ^ 1) * 128, sb + B_QF + 8 * i);
            if (i == 0) {  q_a(2); }
          }
          mbar_wait(sb + B_QF + 8, 0);
        }
#pragma unroll 1
        for (int i = l ? 3 : 4; i < 16; i++) {
          if (l == 3 && i == 12) poll_ge(cnt_ad(bn), ep1 * 16);
          q_b(i); q_a(i);
        }
        if (l & 1) {
          const int krow = 2 * bn * 2048 + bm * 256;
          uint32_t* kvc = cnt_kv(l >> 1, bn);
          uint32_t seen = 0;
#pragma unroll 1
          for (int it = 1; it < 16; it++) {
            const int s = it & 3;
            if (it == 4) {
              bar_sync(NB_KV + 12, 288);
              mbar_wait(sb + B_TF + 24, 0);
#pragma unroll 1
              for (int i = 0; i < 4; i++) tma_st(&prm.m[M_K + (i & 1)], 0, krow + 2048 + (i >> 1) * 128, sb + i * 8192);
              bulk_commit();
            }
            if (it == 5) { bulk_wait_n<0>(); e_red(kvc + 16 + bm); }
            if (it == 12) { e_expect_tx(sb + B_RF, 32768); tma_ld3(sb + RES, &prm.m[M_XSR], 0, pm * 128, 2 * pn, sb + B_RF); }
            if (it == 1 || it == 3) mbar_wait(sb + B_QE + 12 + 4 * it, 1);
            mbar_wait(sb + B_TE + 8 * s, ((it >> 2) & 1) ^ 1);
            if (it < 8) {
#pragma unroll 1
              for (uint32_t n = 0; n < 200000u && (~seen & (3u << (2 * it - 2) | (it == 4 ? 0xC000u : 0u))); n++)
                seen = __ballot_sync(~0u, (int)(ld_acquire(kvc + (lane < 7 || lane == 15 ? (bm + 1 + lane) & 7 : 8 + ((bm + 2 + lane) & 7))) - ep1) >= 0);
              fence_async_gl();
            } else if (it == 8) { poll_ge(kvc + 16 + (lane & 7), ep1); fence_async_gl(); }
            e_expect_tx(sb + B_TF + 8 * s, 32768);
#pragma unroll 1
            for (int i = 0; i < 2; i++) {
              const int u = 2 * it - 2 + i;
              const int row = 2 * bn * 2048 + (it > 7 ? 2048 + ((bm + it) & 7) * 256 + i * 128 : u < 7 ? ((bm + 1 + u) & 7) * 256 : ((bm + 2 + u) & 7) * 256 + 128);
              tma_ld(sb + T0 + s * TSTG + i * 8192, &prm.m[M_K], 0, row, sb + B_TF + 8 * s);
              tma_ld(sb + T0 + s * TSTG + 16384 + i * 8192, &prm.m[M_V], 0, row, sb + B_TF + 8 * s);
            }
          }
        }
        auto p_b = [&](int i, uint32_t s, uint32_t par) {
          mbar_wait(sb + B_PE + 8 * s, par ^ 1);
          e_expect_tx(sb + B_PF + 8 * s, PSTG);
          tma_ld5(sb + pslot_b(s), mo, i >> 3, 2 * (i & 7), 2 * pn, sb + B_PF + 8 * s);
        };
        auto p_a = [&](int i, uint32_t s) {
          await_flag(i, rdy, cnt_o(l, pm, (lane >> 3) & 1) + (lane & 7), ep1 * 2);
          tma_ld_mc(sb + pslot_a(s, l) + rank * 8192, &prm.m[M_OS], i * 64, pm * 128 + rank * 64, sb + B_PF + 8 * s);
        };
        auto p_a2 = [&](int i) {
          await_flag(i, rdy, cnt_o(l, pm, (lane >> 3) & 1) + (lane & 7), ep1 * 2);
          tma_ld(sb + pslot_a(i, l), &prm.m[M_OS], i * 64, pm * 128, sb + B_PF + 8 * i);
          tma_ld(sb + pslot_a(i, l) + 8192, &prm.m[M_OS], i * 64, pm * 128 + 64, sb + B_PF + 8 * i);
        };
        rdy = 0;
        if (l & 1) {
#pragma unroll 1
          for (int u = 0; u < 6; u++) { const int i = (0x205413 >> (4 * u)) & 7; if (u == 4) mbar_wait(sb + B_TE, 1); p_b(i, i, i < 4 ? 1 : 0); }
#pragma unroll 1
          for (int u = 0; u < 6; u++) {
            const int i = (0x542130 >> (4 * u)) & 7;
            if (!(u & 1)) mbar_wait(sb + B_TE + 8 + 4 * u, 1);
            if (u == 4) bar_sync(NB_SIG + 3, 192);
            p_a2(i);
          }
        } else {
#pragma unroll 1
          for (int u = 0; u < 6; u++) { const int i = (0x543120 >> (4 * u)) & 7; if (u == 0 || u == 2) mbar_wait(sb + B_QE + 8 - 4 * u, 1); p_b(i, i, 0); }
          mbar_wait(sb + B_QE + 24, 1);
          e_expect_tx(sb + B_RF, 32768);
          tma_ld3(sb + RES, &prm.m[l == 0 ? M_X0R : M_XSR], 0, pm * 128, 2 * pn, sb + B_RF);
          p_a2(0);
          bar_sync(NB_SIG + 2, 320);
          e_arrive_both(sb + B_PA);
          p_a2(1);
          mbar_wait(sb + B_PA, (l >> 1) & 1);
#pragma unroll 1
          for (int i = 2; i < 6; i++) { if (i > 2) mbar_wait(sb + B_PF + 8 * (i - 3), 0); p_a(i, i); }
        }
        uint32_t s = 0, lap = 1;
#pragma unroll 1
        for (int i = 6; i < 16; i++) {
          p_b(i, s, ((s < 4 ? l : 0) + lap) & 1);
          p_a(i, s);
          if (++s == 6) { s = 0; lap++; }
        }
        const CUtensorMap* mn = &prm.m[M_WQA + ((l + 1) & 1)];
        if (l < 3) {
          mbar_wait(sb + B_PE + 8 * 4, 1); mbar_wait(sb + B_PE + 8 * 5, 1);
          tma_ld3(sb + 32768, mn, bn * 64, 2 * pn * 64, 0, sb + B_QL);
          mbar_wait(sb + B_PE + 8 * 0, l & 1);
          tma_ld3(sb + QSTG + 32768, mn, bn * 64, (2 * pn + 1) * 64, 0, sb + B_QL);
          mbar_wait(sb + B_PE + 8 * 1, l & 1);
          e_expect_tx(sb + B_QF + 16, QSTG);
          tma_ld3(sb + 2 * QSTG + 32768, mn, bn * 64, ((2 * pn) ^ 2) * 64, 0, sb + B_QF + 16);
        }
        if (l < 3) { bar_sync(NB_X, 320); e_expect_tx(sb + B_QL, 49152); }
      }
      if (blockIdx.x == 0 && lane_id() == 0) *(volatile uint32_t*)&g_epoch = ep1;
    } else {
      const int hw = w - 1;
      if (lane < 5) asm volatile("prefetch.tensormap [%0];" ::"l"(&prm.m[5 * hw + lane]) : "memory");
      __syncwarp();
      cluster_wait();
      mbar_wait(sb + B_QF, 0);
#pragma unroll 1
      for (int l = 0; l < 4; l++) {
        IDS();
        if (l > 0) { mbar_wait(sb + B_QL, (l + 1) & 1); mbar_wait(sb + B_QF + 8 * 3, 0); }
        if (l == 0) {
#pragma unroll 1
          for (int r = 2 * hw; r < 16; r += 6) {
            const uint4* p = (const uint4*)(prm.x0 + (size_t)(b * 16 + r) * 1024) + lane;
            float s1[2] = {0.f, 0.f}, s2[2] = {0.f, 0.f};
#pragma unroll
            for (int i = 0; i < 8; i++) {
              const uint4 v = __ldg(p + 32 * i);
              const uint32_t u[4] = {v.x, v.y, v.z, v.w};
#pragma unroll
              for (int k = 0; k < 4; k++) { const float a = bf_lo(u[k]), c = bf_hi(u[k]); s1[i >> 2] += a + c; s2[i >> 2] = fmaf(a, a, fmaf(c, c, s2[i >> 2])); }
            }
#pragma unroll
            for (int o = 16; o; o >>= 1)
#pragma unroll
              for (int rr = 0; rr < 2; rr++) { s1[rr] += __shfl_xor_sync(~0u, s1[rr], o); s2[rr] += __shfl_xor_sync(~0u, s2[rr], o); }
            if (lane == 0) *(float4*)&g_stats[b * 16 + r] = make_float4(s1[0], s2[0], s1[1], s2[1]);
          }
        }
        if (l < 2) {
          float cs[8];
#pragma unroll
          for (int i = 0; i < 8; i++) cs[i] = 0.f;
          const uint4* wp = (const uint4*)(prm.wq[l] + (size_t)(bm * 128 + (lane >> 3)) * 3072 + hw * 1024 + bn * 64) + (lane & 7);
#pragma unroll 8
          for (int i = 0; i < 32; i++) {
            const uint4 v = __ldg(wp + (size_t)i * 4 * 384);
            cs[0] += bf_lo(v.x); cs[1] += bf_hi(v.x); cs[2] += bf_lo(v.y); cs[3] += bf_hi(v.y);
            cs[4] += bf_lo(v.z); cs[5] += bf_hi(v.z); cs[6] += bf_lo(v.w); cs[7] += bf_hi(v.w);
          }
#pragma unroll
          for (int i = 0; i < 8; i++) { cs[i] += __shfl_xor_sync(~0u, cs[i], 8); cs[i] += __shfl_xor_sync(~0u, cs[i], 16); }
          if (lane < 8) {
            float4* d = (float4*)(g_csp + ((l * 16 + bn) * 8 + bm) * 192 + hw * 64 + lane * 8);
            d[0] = make_float4(cs[0], cs[1], cs[2], cs[3]); d[1] = make_float4(cs[4], cs[5], cs[6], cs[7]);
          }
          __syncwarp();
          asm volatile("fence.acq_rel.gpu;" ::: "memory");
          e_red_relaxed(cnt_cs(l, bn));
          if (l == 0) e_red_relaxed(cnt_x(0, bm) + pn);
          poll_ge(lane < 8 && l == 0 ? cnt_x(0, bm) + lane : cnt_cs(l, bn), ep1 * (lane < 8 && l == 0 ? 6 : 24));
        }
        if (l > 0) poll_ge(cnt_x(l, bm) + (lane & 15), ep1 * 2);
#pragma unroll 1
        for (int it = hw * 32 + lane; it < 176; it += 96) {
          const bool rows = it < 128;
          const float4* p = rows ? (const float4*)(g_stats + bm * 256) + it : (const float4*)(g_csp + ((l & 1) * 16 + bn) * 8 * 192) + (it - 128);
          const int stride = rows ? 1024 : 48, np = rows && l == 0 ? 1 : 8;
          float4 a = make_float4(0.f, 0.f, 0.f, 0.f);
#pragma unroll
          for (int k = 0; k < 8; k++) if (k < np) { const float4 v = __ldcg(p + k * stride); a.x += v.x; a.y += v.y; a.z += v.z; a.w += v.w; }
          if (rows) {
            const float m0 = a.x * (1.f / 1024.f), m1 = a.z * (1.f / 1024.f);
            const float v0 = fmaxf(a.y * (1.f / 1024.f) - m0 * m0, 0.f), v1 = fmaxf(a.w * (1.f / 1024.f) - m1 * m1, 0.f);
            const float r0 = __fdividef(1.f, bf_round(sqrtf(bf_round(bf_round(v0) + 1e-5f)))), r1 = __fdividef(1.f, bf_round(sqrtf(bf_round(bf_round(v1) + 1e-5f))));
            a = make_float4(r0, -bf_round(m0), r1, -bf_round(m1));
          }
          if (rows && (l & 1) && (it & 4)) a = make_float4(a.y, a.x, a.w, a.z);
          *(float4*)(smem + ROWST + it * 16) = a;
        }
        __syncwarp();
        if (lane == 0) asm volatile("red.release.cta.shared.add.u32 [%0], 1;" ::"r"(sb + W_X) : "memory");
        if (hw == 2) {
          if (!(l & 1)) {
            bar_sync(NB_ST, 288);
            const uint4* hp = g_halo + ((l >> 1) * 128 + b - 16) * 384 + lane;
#pragma unroll 1
            for (int h = 0; h < 2; h++) {
              uint32_t t[18];
#pragma unroll
              for (int i = 0; i < 18; i++) t[i] = 0;
#pragma unroll 1
              for (uint32_t n = bm ? 0 : 100000u; n < 100000u; n++) {
                uint32_t miss = 0;
#pragma unroll
                for (int i = 0; i < 6; i++) miss |= ld_tagged(hp + h * 192 + i * 32, &t[3 * i]) ^ ep1;
                if (__all_sync(~0u, !miss)) break;
              }
              mbar_wait(sb + B_QE + 16, 1);
              const uint32_t r = (lane & 7) + ((lane >> 3) & 1) * 8, rv = lane >> 2;
#pragma unroll
              for (int jj = 0; jj < 2; jj++) stsm4(sb + KSC + r * 128 + (((4 * h + 2 * jj + (lane >> 4)) ^ (r & 7)) << 4), t[4 * jj], t[4 * jj + 1], t[4 * jj + 2], t[4 * jj + 3]);
              const uint32_t ad = sb + VSC + rv * 128 + (((4 * h + (lane & 3)) ^ (rv & 7)) << 4);
              sts128(ad, t[8], t[10], t[12], t[14]); sts128(ad + 1024, t[9], t[11], t[13], t[15]);
              if (h == 0 && !(lane & 2)) *(uint32_t*)(smem + HRS + ((lane >> 2) + 8 * (lane & 1)) * 8) = t[16];
              bar_arrive(NB_HALO + h, 64);
            }
          } else {
            bar_sync(NB_KV, 288);
            sts128(sb + ONES + lane * 32, 0x3f803f80u, 0x3f803f80u, 0x3f803f80u, 0x3f803f80u);
            sts128(sb + ONES + lane * 32 + 16, 0x3f803f80u, 0x3f803f80u, 0x3f803f80u, 0x3f803f80u);
            fence_async_smem();
            __syncwarp();
            e_arrive(sb + B_TF);
            mbar_wait(sb + B_TF + 16, 0); mbar_wait(sb + B_TF + 16, 1);
            poll_ge(cnt_kv(l >> 1, bn) + 16 + (lane & 7), ep1);
            const uint4 v = __ldcg((const uint4*)(g_kn + ((l >> 1) * 128 + bn * 8) * 16) + lane);
            const uint32_t mx = max(max(v.x, v.y), max(v.z, v.w));
            const uint32_t m0 = __reduce_max_sync(~0u, (lane & 2) ? 0u : mx), m1 = __reduce_max_sync(~0u, (lane & 2) ? mx : 0u);
            if (lane == 0) *(uint2*)(smem + ROWST) = make_uint2(m0, m1);
            __syncwarp();
            bar_arrive(NB_KN, 160); bar_arrive(NB_KN + 1, 160);
          }
        } else {
          if (l & 1) {
            uint32_t* p = cnt_kv(l >> 1, bn) + 8 * hw + bm;
            int on = lane == 0;
            PREPARED(p, on);
            bar_sync(hw ? NB_HALO : NB_DONE, 160);
            tma_st(&prm.m[M_K], 0, 2 * bn * 2048 + bm * 256 + hw * 128, sb + T0 + hw * 8192);
            tma_st(&prm.m[M_V], 0, 2 * bn * 2048 + bm * 256 + hw * 128, sb + T0 + 16384 + hw * 8192);
            bulk_commit(); bulk_wait_n<0>();
            release_add(p, on);
          }
#pragma unroll 1
          for (int h = l & 1 ? 0 : hw; h <= (l & 1 ? 1 : hw); h++) {
            uint32_t* p = l == 1 && lane == 1 ? cnt_ad(bn) : cnt_o(l, 2 * bm + (l & 1 ? hw : lane & 1), h) + (bn >> 1);
            int on = lane == 0 || (lane == 1 && (!(l & 1) || (l == 1 && h == 1)));
            int id = NB_SIG + 2 * h + (l & hw), n = (l & 1 ? 160 : 288) + 32 * (h & hw);
            asm volatile("" : "+r"(id), "+r"(n));
            PREPARED(p, on);
            bar_sync(id, n);
            release_add(p, on);
          }
        }
        if (hw < 2 && l < 3) {
          uint32_t* p = cnt_x(l + 1, bm) + 2 * pn + hw;
          int on = lane == 0;
          PREPARED(p, on);
          if (hw) {
            bar_sync(NB_X, 320);
            tma_st(&prm.m[M_XSO], pn * 128 + 64, pm * 128, sb + QSTG + po * 16384);
            bulk_commit();
            bar_sync(NB_KV, 288);
            bulk_wait_n<0>();
          } else bar_sync(NB_X0, 288);
          release_add(p, on);
        }
      }
    }
  } else {
    asm volatile("setmaxnreg.inc.sync.aligned.u32 224;");
    const uint32_t zero = prm.zero;
    cluster_wait();
#pragma unroll 1
    for (int l = 0; l < 4; l++) {
      {
        float acc[2][96];
#pragma unroll
        for (int i = 0; i < 96; i++) { acc[0][i] = 0.f; acc[1][i] = 0.f; }
        fence_regs(acc[0]); fence_regs(acc[1]);
        const bool early = l > 0 && wg == ((cta_id() >> 3) & 1);
        uint32_t ep1 = 0;
#pragma unroll 1
        for (int kt = 0; kt < 13; kt++) {
          const int s = kt == 12 ? 1 : kt & 3;
          if (l > 0 && kt == 0) mbar_wait(sb + B_QL, (l + 1) & 1);
          if (!(early && kt < 2)) mbar_wait(sb + B_QF + 8 * s, (kt >> 2) & 1);
          const uint64_t da = prm.xd + wg * 1024 + s * (QSTG >> 4), db = prm.wd + s * (QSTG >> 4);
          wg_fence();
#pragma unroll
          for (int k = 0; k < 4; k++)
#pragma unroll
            for (int m = 0; m < 2; m++) wgmma_m64n192k16_ss_tb(acc[m], da + m * 512 + k * 2, db + k * 128, 1);
          wg_commit();
          if (kt == 4) ep1 = *(volatile uint32_t*)&g_epoch + 1;
          wg_wait<1>();
          if (early && (kt == 1 || kt == 2)) mbar_wait(sb + B_QF + 8 * (kt - 1), 0);
          if (kt > 0 && w == 0) e_arrive_both(sb + B_QE + 8 * ((kt - 1) & 3));
        }
        {
          const bool lag = (l & 1) == wg;
          const uint32_t s0 = 2 * (~l & 1);
          const uint64_t da = prm.xd + wg * 1024 + 2 * (QSTG >> 4), db = prm.wd + 2 * (QSTG >> 4);
          mbar_wait(sb + B_QF + 8 * s0, 1);
#pragma unroll
          for (int t = 0; t < 2; t++) {
            if (lag && t != wg) {
              wg_wait<0>();
              if (w == 0) e_arrive_both(sb + B_QE + 8 + 8 * t);
              if (t == 0) mbar_wait(sb + B_QF + 16, 1);
              mbar_wait(sb + B_QF + 24, 1);
              if (t == 1) bar_arrive(NB_ST, 288);
              bar_sync(NB_SC, 256);
            }
            const uint64_t so = (uint64_t)(t ? s0 : s0 ^ 2) * (QSTG >> 4);
            wg_fence();
#pragma unroll
            for (int k = 0; k < 4; k++)
#pragma unroll
              for (int m = 0; m < 2; m++) wgmma_m64n192k16_ss_tb(acc[m], da - so + m * 512 + k * 2, db - so + k * 128, 1);
            wg_commit();
            if (!lag || t + wg == 0) {
              wg_wait<1>();
              if (w == 0) e_arrive_both(sb + B_QE + 8 * (t ? s0 : 1));
              mbar_wait(sb + B_QF + 8 * (t ? 3 : s0 ^ 2), 1);
            }
          }
          wg_fence();
#pragma unroll
          for (int m = 1; m >= 0; m--) {
#pragma unroll
            for (int k = 0; k < 4; k++) wgmma_m64n192k16_ss_tb(acc[m], da + (QSTG >> 4) + m * 512 + k * 2, db + (QSTG >> 4) + k * 128, 1);
            wg_commit();
          }
          if (!lag) { bar_arrive(NB_SC, 256); if (wg) bar_arrive(NB_ST, 288); }
          wg_wait<2>();
          if (w == 0) { e_arrive_both(sb + B_QE + 8 * (s0 ^ 2)); if (lag && wg) e_arrive_both(sb + B_QE); }
        }
#pragma unroll 1
        for (uint32_t n = 0; n < 4000000u; n++) {
          uint32_t v;
          asm volatile("ld.acquire.cta.shared.u32 %0, [%1];" : "=r"(v) : "r"(sb + W_X) : "memory");
          if (v == (uint32_t)(3 * l + 3)) break;
        }
        IDS();
        const int g = lane >> 2, qd = lane & 3;
        float2 st[2][2];
#pragma unroll
        for (int m = 0; m < 2; m++)
#pragma unroll
          for (int hh = 0; hh < 2; hh++) st[m][hh] = lds64f(sb + ROWST + (wg * 128 + m * 64 + w * 16 + g + 8 * hh) * 8);
        float2 cs[4];
        auto load_cs = [&](int gi) {
#pragma unroll
          for (int j = 0; j < 4; j++) cs[j] = lds64f(sb + COLS + (gi * 32 + j * 8 + 2 * qd) * 4);
        };
        load_cs(2);
        auto drain = [&]() {
          wg_wait<0>(); fence_regs(acc[0]);
          if (w == 0) e_arrive_both(sb + B_QE + 8 * 3);
        };
        wg_wait<1>(); fence_regs(acc[1]);
        auto norm_tile = [&](int gi, int m, float sc, uint32_t (&t)[8], float (&nrm)[2], bool h16 = false) {
          const float r0 = st[m][0].x * sc, s0 = st[m][0].y, r1 = st[m][1].y * sc, s1 = st[m][1].x;
          float n0 = 0.f, n1 = 0.f;
#pragma unroll
          for (int j = 0; j < 4; j++) {
            const float* a = &acc[m][16 * gi + 4 * j];
            const float v0 = fmaf(s0, cs[j].x, a[0]) * r0, v1 = fmaf(s0, cs[j].y, a[1]) * r0;
            const float v2 = fmaf(s1, cs[j].x, a[2]) * r1, v3 = fmaf(s1, cs[j].y, a[3]) * r1;
            n0 = fmaf(v0, v0, fmaf(v1, v1, n0)); n1 = fmaf(v2, v2, fmaf(v3, v3, n1));
            t[2 * j] = h16 ? pack2h(v0, v1) : pack2(v0, v1); t[2 * j + 1] = h16 ? pack2h(v2, v3) : pack2(v2, v3);
          }
          nrm[0] = n0; nrm[1] = n1;
        };
        auto norm_group = [&](int gi, float sc, uint32_t (&t)[2][8], float (&nrm)[2][2]) { norm_tile(gi, 0, sc, t[0], nrm[0]); norm_tile(gi, 1, sc, t[1], nrm[1]); };
        uint32_t q[2][2][8];
        const uint32_t srow = (lane & 7) + ((lane >> 3) & 1) * 8;
        const uint32_t row0 = wg * 128 + w * 16;
        if (!(l & 1)) {
          auto put_kv = [&](int gi, uint32_t r0, const uint32_t (&t)[8]) {
            if (gi < 4) {
              const uint32_t r = r0 + srow;
#pragma unroll
              for (int jj = 0; jj < 2; jj++) stsm4(sb + KSC + r * 128 + (((4 * (gi - 2) + 2 * jj + (lane >> 4)) ^ (r & 7)) << 4), t[4 * jj], t[4 * jj + 1], t[4 * jj + 2], t[4 * jj + 3]);
            } else {
              const uint32_t r = r0 + g, ad = sb + VSC + r * 128 + (((4 * (gi - 4) + qd) ^ (r & 7)) << 4);
              sts128(ad, t[0], t[2], t[4], t[6]); sts128(ad + 1024, t[1], t[3], t[5], t[7]);
            }
          };
          auto cen_tile = [&](int gi, int m, uint32_t (&t)[8]) {
#pragma unroll
            for (int j = 0; j < 4; j++) {
              const float* a = &acc[m][16 * gi + 4 * j];
              t[2 * j] = pack2(fmaf(st[m][0].y, cs[j].x, a[0]), fmaf(st[m][0].y, cs[j].y, a[1]));
              t[2 * j + 1] = pack2(fmaf(st[m][1].y, cs[j].x, a[2]), fmaf(st[m][1].y, cs[j].y, a[3]));
            }
          };
          const bool send = wg == 1 && w == 3 && bm < 7;
          uint4* hp = g_halo + ((l >> 1) * 128 + b) * 384 + lane;
          mbar_wait(sb + B_QE + 16, 1);
          float2 cn[4];
          auto next_cs = [&](int gi) {
#pragma unroll
            for (int j = 0; j < 4; j++) { cs[j] = cn[j]; cn[j] = lds64f(sb + COLS + (gi * 32 + j * 8 + 2 * qd) * 4); }
          };
#pragma unroll
          for (int j = 0; j < 4; j++) cn[j] = cs[j];
#pragma unroll
          for (int h = 0; h < 2; h++) {
            uint32_t k[8], v[8];
            next_cs(4 + h);
            cen_tile(2 + h, 1, k); put_kv(2 + h, 16 + row0 + 64, k);
            next_cs(h ? 2 : 3);
            cen_tile(4 + h, 1, v); put_kv(4 + h, 16 + row0 + 64, v);
            if (send) {
              uint4* p = hp + h * 192;
              st_tagged(p, k[0], k[1], k[2], ep1); st_tagged(p + 32, k[3], k[4], k[5], ep1); st_tagged(p + 64, k[6], k[7], v[0], ep1);
              st_tagged(p + 96, v[1], v[2], v[3], ep1); st_tagged(p + 128, v[4], v[5], v[6], ep1);
              st_tagged(p + 160, v[7], __float_as_uint(qd & 1 ? st[1][1].x : st[1][0].x), 0u, ep1);
            }
            sched_fence();
          }
          drain();
          {
            uint32_t t[8];
            next_cs(4); cen_tile(2, 0, t); put_kv(2, 16 + row0, t);
            next_cs(0); cen_tile(4, 0, t); put_kv(4, 16 + row0, t);
            next_cs(3); cen_tile(0, 0, q[0][0]); cen_tile(0, 1, q[0][1]);
          }
          const bool e = g & 1, sel = 2 * qd + (g & 1) >= g + 2, first = bm == 0 && row0 == 0;
          uint32_t ka = sb + KSC + (row0 + (lane & 7)) * 128 + (((lane >> 3) ^ (lane & 7)) << 4);
          uint32_t wa = sb + VSC + (row0 + srow) * 128 + (((lane >> 4) ^ (lane & 7)) << 4);
          uint32_t psel[3] = {e ? 0x1044u : 0x4410u, !sel ? 0x4444u : e ? 0x3244u : 0x4432u, sel ? 0x4444u : e ? 0x3244u : 0x4432u};
          bf16* op = g_os + (size_t)(bm * 256 + row0 + g) * 1024 + bn * 32 + qd * 8;
          asm volatile("" : "+r"(ka), "+r"(wa), "+l"(op));
          fence_regs(psel); fence_regs(q[0][0]); fence_regs(q[0][1]);
          sched_fence();
          bar_sync(NB_SC, 256);
          if (row0 == 0) bar_sync(NB_HALO, 64);
          float ra[4], rb[4], ca[4], cb[4];
#pragma unroll
          for (int m = 0; m < 2; m++) {
            float rk[3];
#pragma unroll
            for (int u = 0; u < 3; u++) {
              const int r = row0 + m * 64 + 8 * u + 2 * qd + e - (sel ? 16 : 8);
              rk[u] = lds64f(sb + (m == 0 && r < 0 ? HRS + 128 : ROWST) + r * 8).x;
            }
            ra[2 * m] = sel ? rk[1] : rk[0]; ra[2 * m + 1] = sel ? rk[2] : rk[1];
            rb[2 * m] = sel ? rk[0] : rk[1]; rb[2 * m + 1] = sel ? rk[1] : rk[2];
          }
#pragma unroll
          for (int i = 0; i < 4; i++) { const float rq = st[i >> 1][i & 1].x * QSCALE; ca[i] = rq * ra[i]; cb[i] = rq * rb[i]; }
#pragma unroll 1
          for (int h = 0; h < 2; h++) {
            float s[2][4][4];
            uint32_t vf[2][4][4], pf[2][2][4];
#pragma unroll
            for (int m = 0; m < 2; m++)
#pragma unroll
              for (int nt = 0; nt < 4; nt++) {
                uint32_t kf[4];
                ldsm4(ka + (m * 64 + 8 * nt) * 128, kf);
                s[m][nt][0] = s[m][nt][1] = s[m][nt][2] = s[m][nt][3] = 0.f;
                mma16816(s[m][nt], q[0][m][0], q[0][m][1], q[0][m][2], q[0][m][3], kf[0], kf[1]);
                mma16816(s[m][nt], q[0][m][4], q[0][m][5], q[0][m][6], q[0][m][7], kf[2], kf[3]);
              }
#pragma unroll
            for (int m = 0; m < 2; m++)
#pragma unroll
              for (int i = 0; i < 4; i++) {
                ldsm4t((wa ^ (32 * (i & 1))) + (m * 64 + 16 * (i >> 1)) * 128, vf[m][i]);
              }
            float va[4], vb[4], mx[4];
#pragma unroll
            for (int i = 0; i < 4; i++) {
              const int m = i >> 1, hh = i & 1;
              const float a = e ? s[m][hh + 1][2 * hh + 1] : s[m][hh + 1][2 * hh];
              const float lo = e ? s[m][hh][2 * hh + 1] : s[m][hh][2 * hh], hi = e ? s[m][hh + 2][2 * hh + 1] : s[m][hh + 2][2 * hh];
              va[i] = (m == 0 && hh == 0 && first) ? -INFINITY : a * ca[i];
              vb[i] = (m == 0 && first && sel) ? -INFINITY : (sel ? lo : hi) * cb[i];
              mx[i] = fmaxf(va[i], vb[i]);
            }
#pragma unroll
            for (int i = 0; i < 4; i++) mx[i] = fmaxf(mx[i], __shfl_xor_sync(~0u, mx[i], 1));
#pragma unroll
            for (int i = 0; i < 4; i++) mx[i] = fmaxf(mx[i], __shfl_xor_sync(~0u, mx[i], 2));
#pragma unroll
            for (int i = 0; i < 4; i++) {
              va[i] = ex2(va[i] - mx[i]); vb[i] = ex2(vb[i] - mx[i]);
              mx[i] = va[i] + vb[i];
              va[i] *= ra[i]; vb[i] *= rb[i];
            }
#pragma unroll
            for (int i = 0; i < 4; i++) mx[i] += __shfl_xor_sync(~0u, mx[i], 1);
#pragma unroll
            for (int i = 0; i < 4; i++) mx[i] += __shfl_xor_sync(~0u, mx[i], 2);
#pragma unroll
            for (int i = 0; i < 4; i++) {
              const int m = i >> 1, hh = i & 1;
              const float inv = rcp(mx[i]);
              const uint32_t t = pack2(va[i] * inv, vb[i] * inv);
              pf[m][hh][hh + 1] = prmt0(t, psel[0]); pf[m][hh][hh] = prmt0(t, psel[1]); pf[m][hh][hh + 2] = prmt0(t, psel[2]);
              pf[m][hh][3 - 3 * hh] = t & zero;
            }
#pragma unroll
            for (int m = 0; m < 2; m++) {
              float o[4][4];
#pragma unroll
              for (int j = 0; j < 4; j++) o[j][0] = o[j][1] = o[j][2] = o[j][3] = 0.f;
#pragma unroll
              for (int i = 0; i < 4; i++) {
                const int kk = i >> 1, jj = 2 * (i & 1);
                mma16816(o[jj], pf[m][0][2 * kk], pf[m][1][2 * kk], pf[m][0][2 * kk + 1], pf[m][1][2 * kk + 1], vf[m][i][0], vf[m][i][1]);
                mma16816(o[jj + 1], pf[m][0][2 * kk], pf[m][1][2 * kk], pf[m][0][2 * kk + 1], pf[m][1][2 * kk + 1], vf[m][i][2], vf[m][i][3]);
              }
              stg128(op + m * 65536, pack2(o[0][0], o[0][1]), pack2(o[1][0], o[1][1]), pack2(o[2][0], o[2][1]), pack2(o[3][0], o[3][1]));
              stg128(op + m * 65536 + 8192, pack2(o[0][2], o[0][3]), pack2(o[1][2], o[1][3]), pack2(o[2][2], o[2][3]), pack2(o[3][2], o[3][3]));
            }
            bar_arrive(NB_SIG + 2 * h, 288 + 32 * h);
            if (h == 0) {
              uint32_t t[8];
              next_cs(5); cen_tile(3, 0, t); put_kv(3, 16 + row0, t);
              next_cs(1); cen_tile(5, 0, t); put_kv(5, 16 + row0, t);
#pragma unroll
              for (int j = 0; j < 4; j++) cs[j] = cn[j];
              cen_tile(1, 0, q[0][0]); cen_tile(1, 1, q[0][1]);
              ka ^= 64; wa ^= 64; op += 512;
              bar_sync(NB_SC, 256);
              if (row0 == 0) bar_sync(NB_HALO + 1, 64);
            }
          }
        } else {
          float qn[2];
          drain();
          auto esc_ptr = [&](int gi) { IDS(); return g_esc + (size_t)(((l & 2) + (gi >> 1)) * 65536 + (2 * bn + (gi & 1)) * 2048) * 20; };
          auto norm_half = [&](int gi, float sc, uint32_t (&t)[2][8], float (&nrm)[2][2]) {
            norm_tile(gi, 0, sc, t[0], nrm[0], true); norm_tile(gi, 1, sc, t[1], nrm[1], true);
            if (!((nrm[0][0] + nrm[0][1]) + (nrm[1][0] + nrm[1][1]) <= 4e9f) || fminf(fminf(nrm[0][0], nrm[0][1]), fminf(nrm[1][0], nrm[1][1])) < 1.5e-5f) {
              uint32_t* p = esc_ptr(gi) + (bm * 256 + row0 + g) * 20 + qd;
#pragma unroll
              for (int m = 0; m < 2; m++) {
                uint32_t u[8]; float d[2];
                norm_tile(gi, m, sc, u, d);
#pragma unroll
                for (int i = 0; i < 10; i++) p[(m * 64 + (i & 1) * 8) * 20 + (i >> 1) * 4] = i < 8 ? u[i] : ep1;
              }
            }
            __syncwarp();
          };
          {
            auto max_norm = [&](const float (&nrm)[2][2]) {
              const bool o1 = qd & 1, o2 = qd & 2;
              const float a = (o1 ? nrm[1][0] : nrm[0][0]) + __shfl_xor_sync(~0u, o1 ? nrm[0][0] : nrm[1][0], 1);
              const float c = (o1 ? nrm[1][1] : nrm[0][1]) + __shfl_xor_sync(~0u, o1 ? nrm[0][1] : nrm[1][1], 1);
              const float d = (o2 ? c : a) + __shfl_xor_sync(~0u, o2 ? a : c, 2);
              return __uint_as_float(__reduce_max_sync(~0u, __float_as_uint(d)));
            };
#pragma unroll
            for (int h = 0; h < 2; h++) {
              uint32_t t[2][8]; float nrm[2][2];
              const uint32_t kb = sb + (h ? wg * 8192 : T0), vb = kb + (h ? 8192 : 16384);
              if (h) load_cs(3);
              uint32_t tv[2][8];
              norm_half(2 + h, 1.f, t, nrm);
              load_cs(4 + h);
              float nv[2][2];
              if (h == 1) { const float kn = max_norm(nrm); if (lane == 0) g_kn[((l >> 1) * 128 + bn * 8 + bm) * 16 + 8 + wg * 4 + w] = kn; }
              if (h == 0) mbar_wait(sb + B_QE + 8, 1);
#pragma unroll
              for (int i = 0; i < 4; i++) {
                const uint32_t r = row0 + (i >> 1) * 64 + srow;
                stsm4(kb + r * 64 + (((2 * (i & 1) + (lane >> 4)) ^ ((r >> 1) & 3)) << 4), t[i >> 1][4 * (i & 1)], t[i >> 1][4 * (i & 1) + 1], t[i >> 1][4 * (i & 1) + 2], t[i >> 1][4 * (i & 1) + 3]);
              }
              norm_group(4 + h, 1.f, tv, nv);
              load_cs(h);
#pragma unroll
              for (int m = 0; m < 2; m++) {
                const uint32_t r = row0 + m * 64 + g, ad = vb + r * 64 + ((qd ^ ((r >> 1) & 3)) << 4);
                sts128(ad, tv[m][0], tv[m][2], tv[m][4], tv[m][6]); sts128(ad + 512, tv[m][1], tv[m][3], tv[m][5], tv[m][7]);
              }
              fence_async_smem();
              bar_arrive(NB_KV + 12 * h, 288);
              if (h == 0) {
                bar_arrive(wg ? NB_HALO : NB_DONE, 160);
              }
              if (h == 0) { const float kn = max_norm(nrm); if (lane == 0) g_kn[((l >> 1) * 128 + bn * 8 + bm) * 16 + wg * 4 + w] = kn; }
              norm_half(h, QSCALE, q[h], nrm);
#pragma unroll
              for (int i = 0; i < 4 * h; i++) sts128(sb + QPARK + 24576 - wg * 8192 + (w * 32 + lane) * 16 + i * 2048, q[h][i >> 1][4 * (i & 1)], q[h][i >> 1][4 * (i & 1) + 1], q[h][i >> 1][4 * (i & 1) + 2], q[h][i >> 1][4 * (i & 1) + 3]);
              qn[h] = max_norm(nrm);
            }
          }
          constexpr uint64_t VSTEP = 64 - (64ull << 16);
          const uint32_t c_852 = 0x62A962A9u + (lane_id() & zero), c_lsb = 0x00010001u + (lane_id() & zero), c_half = 0x3F003F00u + (lane_id() & zero);
          float o[2][20], S[2][32];
          uint32_t H[2][16], P0[4] = {}, P1[4] = {};
#pragma unroll
          for (int m = 0; m < 2; m++) {
#pragma unroll
            for (int i = 0; i < 20; i++) o[m][i] = 0.f;
            fence_regs(o[m]);
          }
          auto qkf = [&](int b, int ks, uint64_t d) { wg_n64_rs_nb_f16_f32(S[b], q[0][0][4 * ks], q[0][0][4 * ks + 1], q[0][0][4 * ks + 2], q[0][0][4 * ks + 3], d + 2 * ks, ks ? 1 : zero); };
          auto qkh = [&](int b, int ks, uint64_t d) { wg_n64_rs_nb_f16_f16(H[b], q[0][1][4 * ks], q[0][1][4 * ks + 1], q[0][1][4 * ks + 2], q[0][1][4 * ks + 3], d + 2 * ks, ks ? 1 : zero); };
          auto pv0 = [&](uint64_t d) { wgmma_m64n40k16_rs_tb(o[0], P0[0], P0[1], P0[2], P0[3], d, 1); };
          auto pv1 = [&](uint64_t d) { wgmma_m64n40k16_rs_tb(o[1], P1[0], P1[1], P1[2], P1[3], d, 1); };
          float e[4] = {};
          auto finish = [&](int h) {
            const float* s = &S[(h >> 2) & 1][8 * (h & 3)];
            const uint32_t* u = &H[(h >> 2) & 1][4 * (h & 3)];
            const float z0 = exp2_fix(s[6]), z1 = exp2_fix(s[7]);
            P0[0] = pack2v(e[0], e[1]);
            P1[0] = exp2_h2(u[0], c_852);
            P0[1] = pack2v(e[2], e[3]);
            P1[1] = exp2_h2(u[1], c_852);
            const uint32_t B = exp2_base(z0, z1), E = and_or<0x7F807F80u>(B, c_lsb);
            P1[3] = exp2_h2(u[3], c_852);
            P0[3] = fma_bf2(B, and_or<0x807F807Fu>(B, c_half), E);
            const float e4 = ex2v(s[4]), e5 = ex2v(s[5]);
            P1[2] = exp2_h2(u[2], c_852);
            P0[2] = pack2v(e4, e5);
          };
          auto start = [&](int h) {
            const float* s = &S[(h >> 2) & 1][8 * (h & 3)];
            e[0] = ex2v(s[0]); e[1] = ex2v(s[1]); e[3] = ex2v(s[3]); e[2] = ex2v(s[2]);
          };
          uint64_t kd = prm.kv[0].kd;
          mbar_wait(sb + B_TF, 0);
#pragma unroll
          for (int i = 0; i < 4; i++) sts128(sb + QPARK + (wg * 128 + w * 32 + lane_id()) * 16 + i * 4096, q[0][i >> 1][4 * (i & 1)], q[0][i >> 1][4 * (i & 1) + 1], q[0][i >> 1][4 * (i & 1) + 2], q[0][i >> 1][4 * (i & 1) + 3]);
          wg_fence();
#pragma unroll
          for (int b = 0; b < 2; b++) {
            wg_n64_rs_nb_f16_f32_z(S[b], q[0][0][0], q[0][0][1], q[0][0][2], q[0][0][3], kd + 256 * b, 0);
            wg_n64_rs_nb_f16_f16_z(H[b], q[0][1][0], q[0][1][1], q[0][1][2], q[0][1][3], kd + 256 * b, 0);
            if (b == 0) { qkf(0, 1, kd); qkh(0, 1, kd); }
            wg_commit();
          }
          wg_wait<1>(); fence_regs(S[0]); fence_regs(H[0]);
          start(0); finish(0); start(1);
          wg_wait<0>();
          int redo = 0;
#pragma unroll 1
          for (int pass = 0, j = 1; pass < 2; pass++) {
#pragma unroll 1
           do {
            const uint64_t vd = prm.kv[j & 3].vd;
            bool go = false;
#pragma unroll
            for (int h = 2; h < 18; h++) {
              const int px = (h >> 2) + 1, c = h & 3;
              wg_fence();
              if (h == 13) kd = prm.kv[j & 3].kd;
              const uint64_t kx = kd + (px & 3) * 256, vx = vd + (h - 2) * VSTEP;
              if (h == 2) { qkh(1, 0, kx); qkf(1, 0, kx); pv0(vx); pv1(vx); qkh(1, 1, kx); qkf(1, 1, kx); }
              else if ((c == 1 || c == 2) && h < 17) { qkh(px & 1, c - 1, kx); pv1(vx); qkf(px & 1, c - 1, kx); pv0(vx); }
              else { pv0(vx); pv1(vx); }
              wg_commit();
              if (h == 3) e_arrive_if(sb + B_TE + 8 * ((j + 2) & 3), j > 1);
              if (h == 11) go = mbar_test(sb + B_TF + 8 * (j & 3), (j >> 2) & 1) && j != 8;
              finish(h - 1); start(h);
              if (h != 12 && h != 17) sched_fence();
              if (h == 12 && !go) {
                if (j == 16) {
#pragma unroll
                  for (int u = 13; u < 18; u++) {
                    wg_fence(); pv0(vd + (u - 2) * VSTEP); pv1(vd + (u - 2) * VSTEP); wg_commit();
                    if (u < 17) finish(u - 1);
                    if (u < 16) { start(u); sched_fence(); }
                    if (u & 1) { if (u == 17) wg_wait<0>(); else wg_wait<1>(); }
                  }
                  e_arrive(sb + B_TE + 24);
                  goto head_done;
                }
                mbar_wait(sb + B_TF + 8 * (j & 3), (j >> 2) & 1);
                if (j == 8) {
#pragma unroll
                  for (int i = 0; i < 4; i++) lds128(sb + QPARK + 24576 - wg * 8192 + (w * 32 + lane_id()) * 16 + i * 2048, &q[0][i >> 1][4 * (i & 1)]);
                }
              }
              if (h == 17) wg_wait<0>(); else if (h & 1) wg_wait<1>();
              if (c == 3) { fence_regs(S[px & 1]); fence_regs(H[px & 1]); }
            }
           } while (j++ & 7);
           head_done:
            fence_regs(o[0]); fence_regs(o[1]);
            uint32_t pk[2][8];
            {
              IDS();
              bf16* op = g_os + (size_t)(bm * 256 + row0 + (lane >> 2)) * 1024 + pass * 512 + bn * 32 + (lane & 3) * 8;
#pragma unroll
              for (int i = 0; i < 4; i++) {
                const float* a = &o[i >> 1][2 * (i & 1)];
                const float inv = rcp(a[16]);
                uint32_t* u = &pk[i >> 1][4 * (i & 1)];
#pragma unroll
                for (int k = 0; k < 4; k++) u[k] = pack2(a[4 * k] * inv, a[4 * k + 1] * inv);
                *(uint4*)(op + ((i >> 1) * 64 + (i & 1) * 8) * 1024) = make_uint4(u[0], u[1], u[2], u[3]);
              }
            }
            sched_fence();
            if (pass == 0) bar_sync(NB_KN + wg, 160);
            const float kmax = *(volatile float*)(smem + ROWST + 4 * pass);
            const bool wide = !(qn[0] <= 1.6e7f) | !(kmax <= 1.6e7f) | !(qn[0] * kmax <= 112.f * 112.f);
            int badm = 0;
#pragma unroll
            for (int m = 0; m < 2; m++) {
              uint32_t chk[2] = {0u, 0u};
#pragma unroll
              for (int i = 0; i < 8; i++) asm("fma.rn.bf16x2 %0, %1, %2, %0;" : "+r"(chk[i & 1]) : "r"(pk[m][i]), "r"(0u));
              const bool bad = wide | !(fminf(o[m][16], o[m][18]) >= 9.3e-10f) | !(o[m][16] + o[m][18] <= 1e36f) | (((chk[0] | chk[1]) & 0x7FFF7FFFu) != 0);
              badm |= __any_sync(~0u, bad) << m;
            }
            if (!badm) bar_arrive(NB_SIG + 2 * pass + wg, 160 + 32 * (pass & wg));
            qn[0] = qn[1];
#pragma unroll
            for (int m = 0; m < 2; m++) {
#pragma unroll
              for (int i = 0; i < 20; i++) o[m][i] = 0.f;
              fence_regs(o[m]);
            }
            if (badm) {
              redo |= badm << 2 * pass;
              const int tx = wg * 128 + w * 32 + lane_id();
              uint4* p = g_qsave + (block_id() * 256 + tx) * 8 + pass * 4;
#pragma unroll
              for (int i = 0; i < 4; i++) {
                uint32_t u[4] = {q[0][i >> 1][4 * (i & 1)], q[0][i >> 1][4 * (i & 1) + 1], q[0][i >> 1][4 * (i & 1) + 2], q[0][i >> 1][4 * (i & 1) + 3]};
                if (pass == 0) lds128(sb + QPARK + tx * 16 + i * 4096, u);
                p[i] = make_uint4(u[0], u[1], u[2], u[3]);
              }
            }
          }
          if (redo) attn_redo(redo, l, cta_id(), wg, w, ep1);
        }
      }
      {
        float acc[64];
#pragma unroll
        for (int i = 0; i < 64; i++) acc[i] = 0.f;
        fence_regs(acc);
        uint32_t s = 0, lap = 0;
#pragma unroll 1
        for (int kt = 0; kt < 16; kt++) {
          mbar_wait(sb + B_PF + 8 * s, ((s < 4 ? l : 0) + lap) & 1);
          const uint64_t da = mkdesc(sb + pslot_a(s, l) + wg * 8192, 16, 1024, 1), db = mkdesc(sb + pslot_b(s), 8192, 1024, 1);
          wg_fence();
#pragma unroll
          for (int k = 0; k < 4; k++) wgmma_m64n128k16_ss_tb(acc, da + k * 2, db + k * 128, 1);
          wg_commit();
          wg_wait<1>();
          if (kt > 0 && w == 0) e_arrive_both(sb + B_PE + 8 * (s ? s - 1 : 5));
          if (++s == 6) { s = 0; lap++; }
        }
        IDS();
        const int g = lane >> 2, qd = lane & 3;
        const int r0 = wg * 64 + w * 16;
        const uint32_t r = r0 + (lane & 7) + ((lane >> 3) & 1) * 8;
        uint32_t x[8][4];
        mbar_wait(sb + B_RF, l & 1);
#pragma unroll
        for (int jj = 0; jj < 8; jj++) ldsm4(sb + RES + (jj >> 2) * 16384 + r * 128 + ((((2 * jj + (lane >> 4)) & 7) ^ (r & 7)) << 4), x[jj]);
        wg_wait<0>();
        fence_regs(acc);
        if (w == 0) e_arrive_both(sb + B_PE + 8 * 3);
        const CUtensorMap* mo = &prm.m[l == 3 ? M_OUT : M_XST];
#pragma unroll
        for (int jj = 0; jj < 8; jj++) {
#pragma unroll
          for (int i = 0; i < 4; i++) x[jj][i] = add_bf16x2(x[jj][i], pack2(acc[8 * jj + 2 * i], acc[8 * jj + 2 * i + 1]));
          if (jj < 4) stsm4(sb + RES + r * 128 + ((((2 * jj + (lane >> 4)) & 7) ^ (r & 7)) << 4), x[jj][0], x[jj][1], x[jj][2], x[jj][3]);
          if (jj == 3) { fence_async_smem(); __syncwarp(); tma_st(mo, pn * 128, pm * 128 + r0, sb + RES + r0 * 128); bulk_commit(); sched_fence(); }
        }
        if (l == 3) {
#pragma unroll
          for (int jj = 4; jj < 8; jj++) stsm4(sb + RES + 16384 + r * 128 + ((((2 * jj + (lane >> 4)) & 7) ^ (r & 7)) << 4), x[jj][0], x[jj][1], x[jj][2], x[jj][3]);
          fence_async_smem(); __syncwarp();
          tma_st(mo, pn * 128 + 64, pm * 128 + r0, sb + RES + 16384 + r0 * 128);
          bulk_commit(); bulk_wait_n<0>();
        } else {
          bar_sync(NB_SC, 256);
#pragma unroll
          for (int jj = 0; jj < 8; jj++)
            stsm4(sb + (jj >> 2) * QSTG + po * 16384 + r * 128 + ((((2 * jj + (lane >> 4)) & 7) ^ (r & 7)) << 4), x[jj][0], x[jj][1], x[jj][2], x[jj][3]);
          bulk_wait_n<0>();
          bar_arrive(NB_X0, 288);
          fence_async_smem();
          bar_arrive(NB_X, 320);
          float s1[4] = {0.f, 0.f, 0.f, 0.f}, sa[4] = {0.f, 0.f, 0.f, 0.f}, sc[4] = {0.f, 0.f, 0.f, 0.f};
#pragma unroll
          for (int jj = 0; jj < 8; jj++) {
            mma16816(s1, x[jj][0], x[jj][1], x[jj][2], x[jj][3], 0x3f803f80u, 0x3f803f80u);
            mma16816(sa, x[jj][0], x[jj][1], x[jj][2], x[jj][3], x[jj][0], x[jj][2]);
            mma16816(sc, x[jj][0], x[jj][1], x[jj][2], x[jj][3], x[jj][1], x[jj][3]);
          }
          if (qd == g >> 1) {
            float2* p = g_stats + pn * 2048 + pm * 128 + r0 + g;
            p[0] = make_float2(s1[0], g & 1 ? sa[1] : sa[0]);
            p[8] = make_float2(s1[2], g & 1 ? sc[3] : sc[2]);
          }
          bar_arrive(NB_KV, 288);
        }
      }
    }
  }
  asm volatile("barrier.cluster.arrive.relaxed.aligned;\nbarrier.cluster.wait.aligned;" ::: "memory");
}

typedef CUresult (*EncodeFn)(CUtensorMap*, CUtensorMapDataType, cuuint32_t, void*, const cuuint64_t*, const cuuint64_t*, const cuuint32_t*,
                             const cuuint32_t*, CUtensorMapInterleave, CUtensorMapSwizzle, CUtensorMapL2promotion, CUtensorMapFloatOOBfill);

static void make_map(EncodeFn fn, CUtensorMap* m, const void* ptr, int rank, const uint64_t* dims, const uint64_t* strides, const uint32_t* box, CUtensorMapSwizzle sw) {
  cuuint64_t d[5], st[4];
  cuuint32_t bx[5], es[5];
  for (int i = 0; i < rank; i++) { d[i] = dims[i]; bx[i] = box[i]; es[i] = 1; if (i) st[i - 1] = strides[i - 1] * 2; }
  fn(m, CU_TENSOR_MAP_DATA_TYPE_BFLOAT16, rank, (void*)ptr, d, st, bx, es, CU_TENSOR_MAP_INTERLEAVE_NONE, sw,
     CU_TENSOR_MAP_L2_PROMOTION_L2_128B, CU_TENSOR_MAP_FLOAT_OOB_FILL_NONE);
}
static void map2(EncodeFn fn, CUtensorMap* m, const void* ptr, uint64_t inner, uint64_t outer, uint32_t bi, uint32_t bo, CUtensorMapSwizzle sw) {
  const uint64_t d[2] = {inner, outer}, st[1] = {inner};
  const uint32_t bx[2] = {bi, bo};
  make_map(fn, m, ptr, 2, d, st, bx, sw);
}

extern "C" void kernel_launch(void* const* d_in, const int* in_sizes, int n_in, void* d_out, int out_size) {
  (void)in_sizes; (void)n_in; (void)out_size;
  static EncodeFn enc = nullptr;
  static void *xs, *os, *kk, *vv;
  static int sbase = 1024;
  if (!enc) {
    void* p = nullptr;
    cudaDriverEntryPointQueryResult qr;
    cudaGetDriverEntryPoint("cuTensorMapEncodeTiled", &p, cudaEnableDefault, &qr);
    enc = (EncodeFn)p;
    Scratch* sc = nullptr;
    cudaGetSymbolAddress((void**)&sc, g_s);
    xs = sc->xs; os = sc->os; kk = sc->k; vv = sc->v;
    int dev = 0;
    cudaGetDevice(&dev);
    cudaDeviceGetAttribute(&sbase, cudaDevAttrReservedSharedMemoryPerBlock, dev);
    cudaFuncSetAttribute(fused_kernel, cudaFuncAttributeMaxDynamicSharedMemorySize, SMEM_BYTES);
  }
  Params prm;
  const CUtensorMapSwizzle S128 = CU_TENSOR_MAP_SWIZZLE_128B, S64 = CU_TENSOR_MAP_SWIZZLE_64B;
  map2(enc, &prm.m[M_X0A], d_in[0], 1024, 2048, 64, 256, S128);
  map2(enc, &prm.m[M_XSA], xs, 1024, 2048, 64, 256, S128);
  for (int t = 0; t < 2; t++) {
    const uint64_t d3[3] = {1024, 1024, 3}, s3[2] = {3072, 1024};
    const uint32_t b3[3] = {64, 64, 3};
    make_map(enc, &prm.m[M_WQA + t], d_in[1 + 3 * t], 3, d3, s3, b3, S128);
    const uint64_t d5[5] = {64, 32, 2, 16, 16}, s5[4] = {1024, 32 * 1024, 64 * 1024, 64};
    const uint32_t b5[5] = {64, 32, 1, 2, 2};
    make_map(enc, &prm.m[M_WOA + t], d_in[2 + 3 * t], 5, d5, s5, b5, S128);
    const uint64_t dr[3] = {64, 2048, 16}, sr[2] = {1024, 64};
    const uint32_t br[3] = {64, 128, 2};
    make_map(enc, &prm.m[M_X0R + t], t ? xs : d_in[0], 3, dr, sr, br, S128);
  }
  map2(enc, &prm.m[M_OS], os, 1024, 2048, 64, 64, S128);
  map2(enc, &prm.m[M_K], kk, 32, 65536, 32, 128, S64);
  map2(enc, &prm.m[M_V], vv, 32, 65536, 32, 128, S64);
  map2(enc, &prm.m[M_XSO], xs, 1024, 2048, 64, 128, S128);
  map2(enc, &prm.m[M_X0H], d_in[0], 1024, 2048, 64, 128, S128);
  map2(enc, &prm.m[M_XST], xs, 1024, 2048, 64, 16, S128);
  map2(enc, &prm.m[M_OUT], d_out, 1024, 2048, 64, 16, S128);
  prm.x0 = (const bf16*)d_in[0];
  prm.wq[0] = (const bf16*)d_in[1]; prm.wq[1] = (const bf16*)d_in[4];
  prm.zero = 0;
  for (int i = 0; i < 128; i++) prm.map[i] = remap(i);
  {
    const uint64_t hi = 0x80000020ull << 32, k0 = sbase + T0, v0 = k0 + 16384, vstep = 64 - (64ull << 16);
    prm.wd = mkdesc(sbase + 32768, 8192, 1024, 1); prm.xd = mkdesc(sbase, 16, 1024, 1);
    for (int j = 0; j < 4; j++) {
      prm.kv[j].kd = (hi | 1u << 16 | k0 >> 4) + 2048 * ((j < 16 ? j : 15) & 3);
      prm.kv[j].vd = (hi | (uint64_t)(ONES - T0 - 16384) >> 4 << 16 | v0 >> 4) + 32 * vstep * ((j + 3) & 3);
    }
  }
  fused_kernel<<<128, 384, SMEM_BYTES>>>(prm);
}
```

```cpp
#include <cuda_runtime.h>
#include <cuda_bf16.h>
#include <cuda.h>
#include <stdint.h>

typedef __nv_bfloat16 bf16;

__device__ __forceinline__ void wgmma_m64n192k16_ss_tb(float (&d)[96], uint64_t da, uint64_t db, int scale_d) {
  asm volatile("{\n.reg .pred p;\nsetp.ne.b32 p, %98, 0;\n"
    "wgmma.mma_async.sync.aligned.m64n192k16.f32.bf16.bf16 "
    "{%0, %1, %2, %3, %4, %5, %6, %7, %8, %9, %10, %11, %12, %13, %14, %15, "
    "%16, %17, %18, %19, %20, %21, %22, %23, %24, %25, %26, %27, %28, %29, %30, %31, "
    "%32, %33, %34, %35, %36, %37, %38, %39, %40, %41, %42, %43, %44, %45, %46, %47, "
    "%48, %49, %50, %51, %52, %53, %54, %55, %56, %57, %58, %59, %60, %61, %62, %63, "
    "%64, %65, %66, %67, %68, %69, %70, %71, %72, %73, %74, %75, %76, %77, %78, %79, "
    "%80, %81, %82, %83, %84, %85, %86, %87, %88, %89, %90, %91, %92, %93, %94, %95}, "
    "%96, %97, p, 1, 1, 0, 1;\n}\n"
    : "+f"(d[0]), "+f"(d[1]), "+f"(d[2]), "+f"(d[3]), "+f"(d[4]), "+f"(d[5]), "+f"(d[6]), "+f"(d[7]),
      "+f"(d[8]), "+f"(d[9]), "+f"(d[10]), "+f"(d[11]), "+f"(d[12]), "+f"(d[13]), "+f"(d[14]), "+f"(d[15]),
      "+f"(d[16]), "+f"(d[17]), "+f"(d[18]), "+f"(d[19]), "+f"(d[20]), "+f"(d[21]), "+f"(d[22]), "+f"(d[23]),
      "+f"(d[24]), "+f"(d[25]), "+f"(d[26]), "+f"(d[27]), "+f"(d[28]), "+f"(d[29]), "+f"(d[30]), "+f"(d[31]),
      "+f"(d[32]), "+f"(d[33]), "+f"(d[34]), "+f"(d[35]), "+f"(d[36]), "+f"(d[37]), "+f"(d[38]), "+f"(d[39]),
      "+f"(d[40]), "+f"(d[41]), "+f"(d[42]), "+f"(d[43]), "+f"(d[44]), "+f"(d[45]), "+f"(d[46]), "+f"(d[47]),
      "+f"(d[48]), "+f"(d[49]), "+f"(d[50]), "+f"(d[51]), "+f"(d[52]), "+f"(d[53]), "+f"(d[54]), "+f"(d[55]),
      "+f"(d[56]), "+f"(d[57]), "+f"(d[58]), "+f"(d[59]), "+f"(d[60]), "+f"(d[61]), "+f"(d[62]), "+f"(d[63]),
      "+f"(d[64]), "+f"(d[65]), "+f"(d[66]), "+f"(d[67]), "+f"(d[68]), "+f"(d[69]), "+f"(d[70]), "+f"(d[71]),
      "+f"(d[72]), "+f"(d[73]), "+f"(d[74]), "+f"(d[75]), "+f"(d[76]), "+f"(d[77]), "+f"(d[78]), "+f"(d[79]),
      "+f"(d[80]), "+f"(d[81]), "+f"(d[82]), "+f"(d[83]), "+f"(d[84]), "+f"(d[85]), "+f"(d[86]), "+f"(d[87]),
      "+f"(d[88]), "+f"(d[89]), "+f"(d[90]), "+f"(d[91]), "+f"(d[92]), "+f"(d[93]), "+f"(d[94]), "+f"(d[95])
    : "l"(da), "l"(db), "r"(scale_d));
}

__device__ __forceinline__ void wgmma_m64n128k16_ss_tb(float (&d)[64], uint64_t da, uint64_t db, int scale_d) {
  asm volatile("{\n.reg .pred p;\nsetp.ne.b32 p, %66, 0;\n"
    "wgmma.mma_async.sync.aligned.m64n128k16.f32.bf16.bf16 "
    "{%0, %1, %2, %3, %4, %5, %6, %7, %8, %9, %10, %11, %12, %13, %14, %15, "
    "%16, %17, %18, %19, %20, %21, %22, %23, %24, %25, %26, %27, %28, %29, %30, %31, "
    "%32, %33, %34, %35, %36, %37, %38, %39, %40, %41, %42, %43, %44, %45, %46, %47, "
    "%48, %49, %50, %51, %52, %53, %54, %55, %56, %57, %58, %59, %60, %61, %62, %63}, "
    "%64, %65, p, 1, 1, 0, 1;\n}\n"
    : "+f"(d[0]), "+f"(d[1]), "+f"(d[2]), "+f"(d[3]), "+f"(d[4]), "+f"(d[5]), "+f"(d[6]), "+f"(d[7]),
      "+f"(d[8]), "+f"(d[9]), "+f"(d[10]), "+f"(d[11]), "+f"(d[12]), "+f"(d[13]), "+f"(d[14]), "+f"(d[15]),
      "+f"(d[16]), "+f"(d[17]), "+f"(d[18]), "+f"(d[19]), "+f"(d[20]), "+f"(d[21]), "+f"(d[22]), "+f"(d[23]),
      "+f"(d[24]), "+f"(d[25]), "+f"(d[26]), "+f"(d[27]), "+f"(d[28]), "+f"(d[29]), "+f"(d[30]), "+f"(d[31]),
      "+f"(d[32]), "+f"(d[33]), "+f"(d[34]), "+f"(d[35]), "+f"(d[36]), "+f"(d[37]), "+f"(d[38]), "+f"(d[39]),
      "+f"(d[40]), "+f"(d[41]), "+f"(d[42]), "+f"(d[43]), "+f"(d[44]), "+f"(d[45]), "+f"(d[46]), "+f"(d[47]),
      "+f"(d[48]), "+f"(d[49]), "+f"(d[50]), "+f"(d[51]), "+f"(d[52]), "+f"(d[53]), "+f"(d[54]), "+f"(d[55]),
      "+f"(d[56]), "+f"(d[57]), "+f"(d[58]), "+f"(d[59]), "+f"(d[60]), "+f"(d[61]), "+f"(d[62]), "+f"(d[63])
    : "l"(da), "l"(db), "r"(scale_d));
}

__device__ __forceinline__ void wgmma_m64n40k16_rs_tb(float (&d)[20], uint32_t a0, uint32_t a1, uint32_t a2, uint32_t a3, uint64_t db, int scale_d) {
  asm volatile("{\n.reg .pred p;\nsetp.ne.b32 p, %25, 0;\n"
    "wgmma.mma_async.sync.aligned.m64n40k16.f32.bf16.bf16 "
    "{%0, %1, %2, %3, %4, %5, %6, %7, %8, %9, %10, %11, %12, %13, %14, %15, "
    "%16, %17, %18, %19}, "
    "{%20, %21, %22, %23}, %24, p, 1, 1, 1;\n}\n"
    : "+f"(d[0]), "+f"(d[1]), "+f"(d[2]), "+f"(d[3]), "+f"(d[4]), "+f"(d[5]), "+f"(d[6]), "+f"(d[7]),
      "+f"(d[8]), "+f"(d[9]), "+f"(d[10]), "+f"(d[11]), "+f"(d[12]), "+f"(d[13]), "+f"(d[14]), "+f"(d[15]),
      "+f"(d[16]), "+f"(d[17]), "+f"(d[18]), "+f"(d[19])
    : "r"(a0), "r"(a1), "r"(a2), "r"(a3), "l"(db), "r"(scale_d));
}

__device__ __forceinline__ void wg_n64_rs_nb_f16_f32(float (&d)[32], uint32_t a0, uint32_t a1, uint32_t a2, uint32_t a3, uint64_t db, int scale_d) {
  asm volatile("{\n.reg .pred p;\nsetp.ne.b32 p, %37, 0;\n"
    "wgmma.mma_async.sync.aligned.m64n64k16.f32.f16.f16 "
    "{%0, %1, %2, %3, %4, %5, %6, %7, %8, %9, %10, %11, %12, %13, %14, %15, "
    "%16, %17, %18, %19, %20, %21, %22, %23, %24, %25, %26, %27, %28, %29, %30, %31}, "
    "{%32, %33, %34, %35}, %36, p, 1, 1, 0;\n}\n"
    : "+f"(d[0]), "+f"(d[1]), "+f"(d[2]), "+f"(d[3]), "+f"(d[4]), "+f"(d[5]), "+f"(d[6]), "+f"(d[7]),
      "+f"(d[8]), "+f"(d[9]), "+f"(d[10]), "+f"(d[11]), "+f"(d[12]), "+f"(d[13]), "+f"(d[14]), "+f"(d[15]),
      "+f"(d[16]), "+f"(d[17]), "+f"(d[18]), "+f"(d[19]), "+f"(d[20]), "+f"(d[21]), "+f"(d[22]), "+f"(d[23]),
      "+f"(d[24]), "+f"(d[25]), "+f"(d[26]), "+f"(d[27]), "+f"(d[28]), "+f"(d[29]), "+f"(d[30]), "+f"(d[31])
    : "r"(a0), "r"(a1), "r"(a2), "r"(a3), "l"(db), "r"(scale_d));
}

__device__ __forceinline__ void wg_n64_rs_nb_f16_f16(uint32_t (&d)[16], uint32_t a0, uint32_t a1, uint32_t a2, uint32_t a3, uint64_t db, int scale_d) {
  asm volatile("{\n.reg .pred p;\nsetp.ne.b32 p, %21, 0;\n"
    "wgmma.mma_async.sync.aligned.m64n64k16.f16.f16.f16 "
    "{%0, %1, %2, %3, %4, %5, %6, %7, %8, %9, %10, %11, %12, %13, %14, %15}, "
    "{%16, %17, %18, %19}, %20, p, 1, 1, 0;\n}\n"
    : "+r"(d[0]), "+r"(d[1]), "+r"(d[2]), "+r"(d[3]), "+r"(d[4]), "+r"(d[5]), "+r"(d[6]), "+r"(d[7]),
      "+r"(d[8]), "+r"(d[9]), "+r"(d[10]), "+r"(d[11]), "+r"(d[12]), "+r"(d[13]), "+r"(d[14]), "+r"(d[15])
    : "r"(a0), "r"(a1), "r"(a2), "r"(a3), "l"(db), "r"(scale_d));
}

__device__ __forceinline__ void wg_n64_rs_nb_f16_f32_z(float (&d)[32], uint32_t a0, uint32_t a1, uint32_t a2, uint32_t a3, uint64_t db, int scale_d) {
  asm volatile("{\n.reg .pred p;\nsetp.ne.b32 p, %37, 0;\n"
    "wgmma.mma_async.sync.aligned.m64n64k16.f32.f16.f16 "
    "{%0, %1, %2, %3, %4, %5, %6, %7, %8, %9, %10, %11, %12, %13, %14, %15, "
    "%16, %17, %18, %19, %20, %21, %22, %23, %24, %25, %26, %27, %28, %29, %30, %31}, "
    "{%32, %33, %34, %35}, %36, p, 1, 1, 0;\n}\n"
    : "=f"(d[0]), "=f"(d[1]), "=f"(d[2]), "=f"(d[3]), "=f"(d[4]), "=f"(d[5]), "=f"(d[6]), "=f"(d[7]),
      "=f"(d[8]), "=f"(d[9]), "=f"(d[10]), "=f"(d[11]), "=f"(d[12]), "=f"(d[13]), "=f"(d[14]), "=f"(d[15]),
      "=f"(d[16]), "=f"(d[17]), "=f"(d[18]), "=f"(d[19]), "=f"(d[20]), "=f"(d[21]), "=f"(d[22]), "=f"(d[23]),
      "=f"(d[24]), "=f"(d[25]), "=f"(d[26]), "=f"(d[27]), "=f"(d[28]), "=f"(d[29]), "=f"(d[30]), "=f"(d[31])
    : "r"(a0), "r"(a1), "r"(a2), "r"(a3), "l"(db), "r"(scale_d));
}

__device__ __forceinline__ void wg_n64_rs_nb_f16_f16_z(uint32_t (&d)[16], uint32_t a0, uint32_t a1, uint32_t a2, uint32_t a3, uint64_t db, int scale_d) {
  asm volatile("{\n.reg .pred p;\nsetp.ne.b32 p, %21, 0;\n"
    "wgmma.mma_async.sync.aligned.m64n64k16.f16.f16.f16 "
    "{%0, %1, %2, %3, %4, %5, %6, %7, %8, %9, %10, %11, %12, %13, %14, %15}, "
    "{%16, %17, %18, %19}, %20, p, 1, 1, 0;\n}\n"
    : "=r"(d[0]), "=r"(d[1]), "=r"(d[2]), "=r"(d[3]), "=r"(d[4]), "=r"(d[5]), "=r"(d[6]), "=r"(d[7]),
      "=r"(d[8]), "=r"(d[9]), "=r"(d[10]), "=r"(d[11]), "=r"(d[12]), "=r"(d[13]), "=r"(d[14]), "=r"(d[15])
    : "r"(a0), "r"(a1), "r"(a2), "r"(a3), "l"(db), "r"(scale_d));
}

#define DEVINL __device__ __forceinline__
DEVINL void wg_fence() { asm volatile("wgmma.fence.sync.aligned;" ::: "memory"); }
DEVINL void wg_commit() { asm volatile("wgmma.commit_group.sync.aligned;" ::: "memory"); }
template <int N> DEVINL void wg_wait() { asm volatile("wgmma.wait_group.sync.aligned %0;" ::"n"(N) : "memory"); }
__host__ DEVINL uint64_t mkdesc(uint32_t addr, uint32_t lbo, uint32_t sbo, int sw) {
  return (uint64_t)((addr & 0x3FFFF) >> 4) | ((uint64_t)(lbo >> 4) << 16) | ((uint64_t)(sbo >> 4) << 32) | ((uint64_t)sw << 62);
}
DEVINL void mbar_init(uint32_t bar, uint32_t cnt) { asm volatile("mbarrier.init.shared::cta.b64 [%0], %1;" ::"r"(bar), "r"(cnt) : "memory"); }
DEVINL void mbar_arrive(uint32_t bar) { asm volatile("mbarrier.arrive.shared::cta.b64 _, [%0];" ::"r"(bar) : "memory"); }
DEVINL bool mbar_try(uint32_t bar, uint32_t parity) {
  uint32_t ok;
  asm volatile("{\n.reg .pred p;\nmbarrier.try_wait.parity.shared::cta.b64 p, [%1], %2;\nselp.u32 %0, 1, 0, p;\n}" : "=r"(ok) : "r"(bar), "r"(parity) : "memory");
  return ok;
}
DEVINL bool mbar_test(uint32_t bar, uint32_t parity) {
  uint32_t ok;
  asm volatile("{\n.reg .pred p;\nmbarrier.test_wait.parity.shared::cta.b64 p, [%1], %2;\nselp.u32 %0, 1, 0, p;\n}" : "=r"(ok) : "r"(bar), "r"(parity) : "memory");
  return ok;
}
DEVINL void mbar_wait(uint32_t bar, uint32_t parity) {
#pragma unroll 1
  for (uint32_t n = 0; n < 100000u; n++) if (mbar_try(bar, parity)) break;
}
#define EL(txt) "{\n.reg .pred pe;\nelect.sync _|pe, 0xffffffff;\n@pe " txt "\n}"
DEVINL void e_expect_tx(uint32_t bar, uint32_t bytes) { asm volatile(EL("mbarrier.arrive.expect_tx.shared::cta.b64 _, [%0], %1;") ::"r"(bar), "r"(bytes) : "memory"); }
DEVINL void e_arrive(uint32_t bar) { asm volatile(EL("mbarrier.arrive.shared::cta.b64 _, [%0];") ::"r"(bar) : "memory"); }
DEVINL void e_arrive_if(uint32_t bar, int c) {
  asm volatile("{\n.reg .pred pe;\nelect.sync _|pe, 0xffffffff;\nsetp.ne.and.b32 pe, %1, 0, pe;\n@pe mbarrier.arrive.shared::cta.b64 _, [%0];\n}" ::"r"(bar), "r"(c) : "memory");
}
DEVINL void e_red(uint32_t* p) { asm volatile(EL("red.release.gpu.global.add.u32 [%0], 1;") ::"l"(p) : "memory"); }
DEVINL void e_red_relaxed(uint32_t* p) { asm volatile(EL("red.relaxed.gpu.global.add.u32 [%0], 1;") ::"l"(p) : "memory"); }
DEVINL void release_add(uint32_t* p, int on) {
  asm volatile("{\n.reg .pred q;\nsetp.ne.b32 q, %1, 0;\nfence.release.gpu;\n@q red.relaxed.gpu.global.add.u32 [%0], 1;\n}" ::"l"(p), "r"(on) : "memory");
}
#define PREPARED(p, on) do { asm volatile("" : "+l"(p), "+r"(on)); asm volatile("griddepcontrol.launch_dependents;" ::: "memory"); } while (0)
DEVINL void tma_ld(uint32_t dst, const CUtensorMap* m, int c0, int c1, uint32_t bar) {
  asm volatile(EL("cp.async.bulk.tensor.2d.shared::cluster.global.mbarrier::complete_tx::bytes [%0], [%1, {%3, %4}], [%2];")
               ::"r"(dst), "l"(m), "r"(bar), "r"(c0), "r"(c1) : "memory");
}
DEVINL void tma_ld3(uint32_t dst, const CUtensorMap* m, int c0, int c1, int c2, uint32_t bar) {
  asm volatile(EL("cp.async.bulk.tensor.3d.shared::cluster.global.mbarrier::complete_tx::bytes [%0], [%1, {%3, %4, %5}], [%2];")
               ::"r"(dst), "l"(m), "r"(bar), "r"(c0), "r"(c1), "r"(c2) : "memory");
}
DEVINL void tma_ld5(uint32_t dst, const CUtensorMap* m, int c2, int c3, int c4, uint32_t bar) {
  asm volatile(EL("cp.async.bulk.tensor.5d.shared::cluster.global.mbarrier::complete_tx::bytes [%0], [%1, {0, 0, %3, %4, %5}], [%2];")
               ::"r"(dst), "l"(m), "r"(bar), "r"(c2), "r"(c3), "r"(c4) : "memory");
}
DEVINL void tma_ld_mc(uint32_t dst, const CUtensorMap* m, int c0, int c1, uint32_t bar) {
  asm volatile(EL("cp.async.bulk.tensor.2d.shared::cluster.global.mbarrier::complete_tx::bytes.multicast::cluster [%0], [%1, {%3, %4}], [%2], %5;")
               ::"r"(dst), "l"(m), "r"(bar), "r"(c0), "r"(c1), "h"((uint16_t)3) : "memory");
}
DEVINL void e_arrive_both(uint32_t bar) {
  asm volatile("{\n.reg .pred pe;\n.reg .b32 r0, r1;\nelect.sync _|pe, 0xffffffff;\nmapa.shared::cluster.u32 r0, %0, 0;\nmapa.shared::cluster.u32 r1, %0, 1;\n"
               "@pe mbarrier.arrive.shared::cluster.b64 _, [r0];\n@pe mbarrier.arrive.shared::cluster.b64 _, [r1];\n}" ::"r"(bar) : "memory");
}
DEVINL void tma_st(const CUtensorMap* m, int c0, int c1, uint32_t src) {
  asm volatile(EL("cp.async.bulk.tensor.2d.global.shared::cta.bulk_group [%0, {%2, %3}], [%1];") ::"l"(m), "r"(src), "r"(c0), "r"(c1) : "memory");
}
DEVINL void bulk_commit() { asm volatile("cp.async.bulk.commit_group;" ::: "memory"); }
template <int N> DEVINL void bulk_wait_n() { asm volatile("cp.async.bulk.wait_group %0;\nbar.warp.sync 0xffffffff;" ::"n"(N) : "memory"); }
DEVINL void l2_prefetch(const void* g, uint32_t bytes) { asm volatile(EL("cp.async.bulk.prefetch.L2.global [%0], %1;") ::"l"(g), "r"(bytes) : "memory"); }
DEVINL void fence_async_smem() { asm volatile("fence.proxy.async.shared::cta;" ::: "memory"); }
DEVINL void fence_async_gl() { asm volatile("fence.proxy.async.global;" ::: "memory"); }
DEVINL void cluster_wait() { asm volatile("barrier.cluster.wait.aligned;" ::: "memory"); }
DEVINL void bar_sync(int id, int n) { asm volatile("bar.sync %0, %1;" ::"r"(id), "r"(n) : "memory"); }
DEVINL void bar_arrive(int id, int n) { asm volatile("bar.arrive %0, %1;" ::"r"(id), "r"(n) : "memory"); }
DEVINL uint32_t ld_acquire(const uint32_t* p) { uint32_t v; asm volatile("ld.acquire.gpu.global.u32 %0, [%1];" : "=r"(v) : "l"(p) : "memory"); return v; }
DEVINL void await_flag(int j, uint32_t& rdy, const uint32_t* p, uint32_t target) {
  if ((rdy >> j) & 1) return;
#pragma unroll 1
  for (uint32_t n = 0; n < 200000u && !((rdy >> j) & 1); n++) rdy = __ballot_sync(~0u, (int)(ld_acquire(p) - target) >= 0);
  asm volatile("fence.proxy.async.global;" ::: "memory");
}
DEVINL void poll_ge(const uint32_t* p, uint32_t target) {
#pragma unroll 1
  for (uint32_t n = 0; n < 200000u; n++) if (__all_sync(~0u, (int)(ld_acquire(p) - target) >= 0)) break;
}
DEVINL int lane_id() { int v; asm volatile("mov.u32 %0, %%laneid;" : "=r"(v)); return v; }
__host__ DEVINL int remap(int v) {
  const int c = v >> 1, u = c - 36, r = (u * 37) >> 8;
  const int L = c < 4 ? 32 + 8 * c : c < 36 ? c - 4 : 33 + u + r;
  return 2 * L + (v & 1);
}
DEVINL int block_id() { int v; asm volatile("mov.u32 %0, %%ctaid.x;" : "=r"(v)); return v; }
#define cta_id() prm.map[block_id()]
#define IDS() const int lane = lane_id(), b = cta_id(), bm = b >> 4, bn = b & 15, rank = b & 1, pm = 2 * bm + (bn >> 3), pn = bn & 7, po = pm & 1; \
  (void)lane; (void)bm; (void)bn; (void)rank; (void)pm; (void)pn; (void)po
DEVINL void st_tagged(uint4* p, uint32_t a, uint32_t b, uint32_t c, uint32_t tag) {
  asm volatile("{\n.reg .b64 u, v;\n.reg .b128 t;\nmov.b64 u, {%1, %2};\nmov.b64 v, {%3, %4};\nmov.b128 t, {u, v};\nst.relaxed.gpu.global.b128 [%0], t;\n}"
               ::"l"(p), "r"(a), "r"(b), "r"(c), "r"(tag) : "memory");
}
DEVINL uint32_t ld_tagged(const uint4* p, uint32_t* r) {
  uint32_t tag;
  asm volatile("{\n.reg .b64 u, v;\n.reg .b128 t;\nld.relaxed.gpu.global.b128 t, [%4];\nmov.b128 {u, v}, t;\nmov.b64 {%0, %1}, u;\nmov.b64 {%2, %3}, v;\n}"
               : "=r"(r[0]), "=r"(r[1]), "=r"(r[2]), "=r"(tag) : "l"(p) : "memory");
  return tag;
}
DEVINL float ex2(float x) { float y; asm("ex2.approx.ftz.f32 %0, %1;" : "=f"(y) : "f"(x)); return y; }
DEVINL float rcp(float x) { float y; asm("rcp.approx.ftz.f32 %0, %1;" : "=f"(y) : "f"(x)); return y; }
DEVINL uint32_t pack2(float lo, float hi) { uint32_t r; asm("cvt.rn.bf16x2.f32 %0, %1, %2;" : "=r"(r) : "f"(hi), "f"(lo)); return r; }
DEVINL uint32_t pack2h(float lo, float hi) { uint32_t r; asm("cvt.rz.f16x2.f32 %0, %1, %2;" : "=r"(r) : "f"(hi), "f"(lo)); return r; }
DEVINL uint32_t prmt0(uint32_t a, uint32_t sel) { uint32_t r; asm("prmt.b32 %0, %1, 0, %2;" : "=r"(r) : "r"(a), "r"(sel)); return r; }
DEVINL void stg128(const void* p, uint32_t a, uint32_t b, uint32_t c, uint32_t d) {
  asm volatile("st.global.v4.b32 [%0], {%1, %2, %3, %4};" ::"l"(p), "r"(a), "r"(b), "r"(c), "r"(d) : "memory");
}
DEVINL float bf_lo(uint32_t w) { return __uint_as_float(w << 16); }
DEVINL float bf_hi(uint32_t w) { return __uint_as_float(w & 0xFFFF0000u); }
DEVINL float bf_round(float x) { return bf_lo(pack2(x, 0.f)); }
DEVINL uint32_t add_bf16x2(uint32_t a, uint32_t b) { uint32_t r; asm("add.rn.bf16x2 %0, %1, %2;" : "=r"(r) : "r"(a), "r"(b)); return r; }
DEVINL void stsm4(uint32_t addr, uint32_t a, uint32_t b, uint32_t c, uint32_t d) {
  asm volatile("stmatrix.sync.aligned.m8n8.x4.shared.b16 [%0], {%1, %2, %3, %4};" ::"r"(addr), "r"(a), "r"(b), "r"(c), "r"(d) : "memory");
}
DEVINL void ldsm4(uint32_t addr, uint32_t (&r)[4]) {
  asm volatile("ldmatrix.sync.aligned.m8n8.x4.shared.b16 {%0, %1, %2, %3}, [%4];" : "=r"(r[0]), "=r"(r[1]), "=r"(r[2]), "=r"(r[3]) : "r"(addr) : "memory");
}
DEVINL void ldsm4t(uint32_t addr, uint32_t (&r)[4]) {
  asm volatile("ldmatrix.sync.aligned.m8n8.x4.trans.shared.b16 {%0, %1, %2, %3}, [%4];" : "=r"(r[0]), "=r"(r[1]), "=r"(r[2]), "=r"(r[3]) : "r"(addr) : "memory");
}
DEVINL void sts128(uint32_t addr, uint32_t a, uint32_t b, uint32_t c, uint32_t d) {
  asm volatile("st.shared.v4.b32 [%0], {%1, %2, %3, %4};" ::"r"(addr), "r"(a), "r"(b), "r"(c), "r"(d) : "memory");
}
DEVINL float2 lds64f(uint32_t addr) { float2 v; asm volatile("ld.shared.v2.f32 {%0, %1}, [%2];" : "=f"(v.x), "=f"(v.y) : "r"(addr) : "memory"); return v; }
DEVINL void mma16816(float (&d)[4], uint32_t a0, uint32_t a1, uint32_t a2, uint32_t a3, uint32_t b0, uint32_t b1) {
  asm("mma.sync.aligned.m16n8k16.row.col.f32.bf16.bf16.f32 {%0, %1, %2, %3}, {%4, %5, %6, %7}, {%8, %9}, {%0, %1, %2, %3};"
               : "+f"(d[0]), "+f"(d[1]), "+f"(d[2]), "+f"(d[3]) : "r"(a0), "r"(a1), "r"(a2), "r"(a3), "r"(b0), "r"(b1));
}
template <int N> DEVINL void fence_regs(float (&d)[N]) {
#pragma unroll
  for (int i = 0; i < N; i++) asm volatile("" : "+f"(d[i])::"memory");
}
template <int N> DEVINL void fence_regs(uint32_t (&d)[N]) {
#pragma unroll
  for (int i = 0; i < N; i++) asm volatile("" : "+r"(d[i])::"memory");
}
DEVINL void lds128(uint32_t addr, uint32_t* r) {
  asm volatile("ld.shared.v4.b32 {%0, %1, %2, %3}, [%4];" : "=r"(r[0]), "=r"(r[1]), "=r"(r[2]), "=r"(r[3]) : "r"(addr) : "memory");
}
DEVINL void sched_fence() { asm volatile("griddepcontrol.launch_dependents;" ::: "memory"); }

struct Scratch {
  bf16 k[32 * 2048 * 32];
  bf16 xs[2048 * 1024];
  bf16 os[2048 * 1024];
  bf16 v[32 * 2048 * 32];
  float kn[2 * 128 * 16];
  uint32_t cnt[256 * 32];
  float2 stats[8 * 2048];
  uint4 halo[2 * 128 * 12 * 32];
  float csp[2 * 16 * 8 * 192];
  uint4 qsave[128 * 256 * 8];
  uint32_t esc[4 * 65536 * 20];
};
__device__ __align__(1024) Scratch g_s;
#define g_k g_s.k
#define g_xs g_s.xs
#define g_os g_s.os
#define g_v g_s.v
#define g_kn g_s.kn
#define g_cnt g_s.cnt
#define g_stats g_s.stats
#define g_halo g_s.halo
#define g_csp g_s.csp
#define g_qsave g_s.qsave
#define g_esc g_s.esc
#define g_epoch g_s.cnt[255 * 32]

DEVINL uint32_t* cnt_x(int l, int bm) { return g_cnt + (l * 8 + bm) * 32; }
DEVINL uint32_t* cnt_o(int l, int pm, int h) { return g_cnt + (32 + (l * 16 + pm) * 2 + h) * 32; }
DEVINL uint32_t* cnt_kv(int lb, int bn) { return g_cnt + (160 + lb * 16 + bn) * 32; }
DEVINL uint32_t* cnt_ad(int bn) { return g_cnt + (192 + bn) * 32; }
DEVINL uint32_t* cnt_cs(int t, int bn) { return g_cnt + (208 + t * 16 + bn) * 32; }

DEVINL int qord(int i, int l, int pn) { return l == 0 ? i : i < 4 ? ((2 * pn) ^ (i & 2)) + (i & 1) : i - 4 < 2 * (pn & 6) ? i - 4 : i; }
struct Params {
  CUtensorMap m[15];
  const bf16* x0;
  const bf16* wq[2];
  uint32_t zero;
  int map[128];
  uint64_t wd, xd;
  struct __align__(16) { uint64_t kd, vd; } kv[4];
};
enum { M_X0A = 0, M_XSA, M_WQA, M_WQB, M_WOA, M_WOB, M_OS, M_K, M_V, M_X0R, M_XSR, M_XSO, M_OUT, M_XST, M_X0H, M_COUNT };

constexpr uint32_t QSTG = 57344;
constexpr uint32_t T0 = 65536, TSTG = 32768;
constexpr uint32_t ONES = 230400;
constexpr uint32_t PSTG = 32768, RES = 196608;
constexpr uint32_t KSC = 98304, VSC = 133120, HRS = 167936;
constexpr uint32_t ROWST = 229376, COLS = 231424, BARS = 232192, SMEM_BYTES = 232448;
constexpr uint32_t B_QF = BARS, B_QE = BARS + 32, B_TF = BARS + 64, B_TE = BARS + 96, B_PF = BARS + 128, B_PE = BARS + 176,
                   B_RF = BARS + 224, W_X = BARS + 232, B_QL = BARS + 240, B_PA = BARS + 248;
enum { NB_ST = 1, NB_KV = 2  , NB_DONE = 3, NB_SC = 4, NB_SIG = 5  , NB_KN = 9  , NB_X = 11, NB_HALO = 12  , NB_X0 = 15 };

DEVINL uint32_t pslot_b(uint32_t s) { return ((0x320415u >> (4 * s)) & 7) * 16384u; }
DEVINL uint32_t pslot_a(uint32_t s, int l) { return 98304u + ((((l & 1) ? 0x541230u : 0x041235u) >> (4 * s)) & 7) * 16384u; }

constexpr float QSCALE = 0.17677669529663687f * 1.4426950408889634f;
constexpr uint32_t QPARK = 32768;

DEVINL uint32_t exp2_h2(uint32_t s, uint32_t c852) {
  uint32_t r, t, w, m, d;
  asm volatile("{.reg .b64 t; add.rn.f16x2 %0, %1, %2; cvt.u64.u32 t, %0; cvt.u32.u64 %0, t;}" : "=r"(r) : "r"(s), "r"(0x65EA65EAu));
  asm volatile("fma.rn.f16x2 %0, %1, %2, %3;" : "=r"(t) : "r"(r), "r"(0xB880B880u), "r"(c852));
  asm volatile("fma.rn.f16x2 %0, %1, %2, %3;" : "=r"(w) : "r"(s), "r"(0x38803880u), "r"(t));
  asm volatile("fma.rn.f16x2 %0, %1, %1, %2;" : "=r"(m) : "r"(w), "r"(0x4A1F4A2Du));
  asm volatile("{.reg .b32 t; shf.l.clamp.b32 t, %2, %1, 7; add.u32 %0, t, %2;}" : "=r"(d) : "r"(r), "r"(m));
  return d;
}
DEVINL float exp2_fix(float s) { float z; asm volatile("add.rn.f32 %0, %1, 0f43BF34BC;" : "=f"(z) : "f"(s)); return z; }
DEVINL uint32_t exp2_base(float z0, float z1) { uint32_t B; asm volatile("prmt.b32 %0, %1, %2, 0x6521;" : "=r"(B) : "r"(__float_as_uint(z0)), "r"(__float_as_uint(z1))); return B; }
template <uint32_t MASK> DEVINL uint32_t and_or(uint32_t a, uint32_t c) { uint32_t r; asm volatile("lop3.b32 %0, %1, %3, %2, 0xEA;" : "=r"(r) : "r"(a), "r"(c), "n"(MASK)); return r; }
DEVINL uint32_t fma_bf2(uint32_t a, uint32_t b, uint32_t c) { uint32_t r; asm volatile("fma.rn.bf16x2 %0, %1, %2, %3;" : "=r"(r) : "r"(a), "r"(b), "r"(c)); return r; }
DEVINL float ex2v(float x) { float y; asm volatile("ex2.approx.ftz.f32 %0, %1;" : "=f"(y) : "f"(x)); return y; }
DEVINL uint32_t pack2v(float lo, float hi) { uint32_t r; asm volatile("cvt.rn.bf16x2.f32 %0, %1, %2;" : "=r"(r) : "f"(hi), "f"(lo)); return r; }
DEVINL void unesc(uint32_t (&u)[4], const uint32_t* esc, uint32_t tag) {
  const bool saved = __ldcg(esc + 16) == tag;
#pragma unroll
  for (int j = 0; j < 4; j++) {
    float lo, hi;
    asm("{.reg .f16 a, b; mov.b32 {a, b}, %2; cvt.f32.f16 %0, a; cvt.f32.f16 %1, b;}" : "=f"(lo), "=f"(hi) : "r"(u[j]));
    u[j] = saved ? __ldcg(esc + 4 * j) : pack2(lo, hi);
  }
}

DEVINL void attn_slow(const uint32_t (&q)[8], int head, const uint32_t* kesc, uint32_t tag, float (&res)[20], int lane) {
  const int g = lane >> 2, qd = lane & 3;
  const bf16* kb = g_k + (size_t)head * 2048 * 32;
  const bf16* vb = g_v + (size_t)head * 2048 * 32;
  float o[4][4], m0 = -INFINITY, m1 = -INFINITY, l0 = 0.f, l1 = 0.f;
#pragma unroll
  for (int j = 0; j < 4; j++) { o[j][0] = o[j][1] = o[j][2] = o[j][3] = 0.f; }
#pragma unroll 1
  for (int k0 = 0; k0 < 2048; k0 += 16) {
    float s[2][4];
#pragma unroll
    for (int nt = 0; nt < 2; nt++) {
      s[nt][0] = s[nt][1] = s[nt][2] = s[nt][3] = 0.f;
      const uint32_t* kp = (const uint32_t*)(kb + (size_t)(k0 + nt * 8 + g) * 32) + qd;
      uint32_t k[4] = {__ldcg(kp), __ldcg(kp + 4), __ldcg(kp + 8), __ldcg(kp + 12)};
      unesc(k, kesc + (k0 + nt * 8 + g) * 20 + qd, tag);
      __syncwarp();
      mma16816(s[nt], q[0], q[1], q[2], q[3], k[0], k[1]);
      mma16816(s[nt], q[4], q[5], q[6], q[7], k[2], k[3]);
    }
    float a0 = fmaxf(fmaxf(s[0][0], s[0][1]), fmaxf(s[1][0], s[1][1]));
    float a1 = fmaxf(fmaxf(s[0][2], s[0][3]), fmaxf(s[1][2], s[1][3]));
    a0 = fmaxf(a0, __shfl_xor_sync(~0u, a0, 1)); a0 = fmaxf(a0, __shfl_xor_sync(~0u, a0, 2));
    a1 = fmaxf(a1, __shfl_xor_sync(~0u, a1, 1)); a1 = fmaxf(a1, __shfl_xor_sync(~0u, a1, 2));
    const float n0 = fmaxf(m0, a0), n1 = fmaxf(m1, a1);
    const float c0 = (m0 == n0) ? 1.f : ex2(m0 - n0), c1 = (m1 == n1) ? 1.f : ex2(m1 - n1);
    m0 = n0; m1 = n1;
    const uint32_t p0 = pack2(ex2(s[0][0] - n0), ex2(s[0][1] - n0)), p1 = pack2(ex2(s[0][2] - n1), ex2(s[0][3] - n1));
    const uint32_t p2 = pack2(ex2(s[1][0] - n0), ex2(s[1][1] - n0)), p3 = pack2(ex2(s[1][2] - n1), ex2(s[1][3] - n1));
    l0 = l0 * c0 + bf_lo(p0) + bf_hi(p0) + bf_lo(p2) + bf_hi(p2);
    l1 = l1 * c1 + bf_lo(p1) + bf_hi(p1) + bf_lo(p3) + bf_hi(p3);
#pragma unroll
    for (int j = 0; j < 4; j++) {
      o[j][0] *= c0; o[j][1] *= c0; o[j][2] *= c1; o[j][3] *= c1;
      const unsigned short* vp = (const unsigned short*)(vb + (size_t)(k0 + 2 * qd) * 32 + j * 8 + g);
      const uint32_t b0 = (uint32_t)__ldcg(vp) | ((uint32_t)__ldcg(vp + 32) << 16);
      const uint32_t b1 = (uint32_t)__ldcg(vp + 256) | ((uint32_t)__ldcg(vp + 288) << 16);
      mma16816(o[j], p0, p1, p2, p3, b0, b1);
    }
  }
  l0 += __shfl_xor_sync(~0u, l0, 1); l0 += __shfl_xor_sync(~0u, l0, 2);
  l1 += __shfl_xor_sync(~0u, l1, 1); l1 += __shfl_xor_sync(~0u, l1, 2);
#pragma unroll
  for (int j = 0; j < 4; j++) { res[4 * j] = o[j][0]; res[4 * j + 1] = o[j][1]; res[4 * j + 2] = o[j][2]; res[4 * j + 3] = o[j][3]; }
  res[16] = l0; res[18] = l1;
}

__device__ __noinline__ void attn_redo(int redo, int l, int b, int wg, int w, uint32_t tag) {
  const int lane = lane_id();
#pragma unroll 1
  for (int t = 0; t < 4; t++) {
    const int h = t >> 1, head = 2 * (b & 15) + h, row = (b >> 4) * 256 + wg * 128 + (t & 1) * 64 + w * 16 + (lane >> 2);
    if ((redo >> t) & 1) {
      const uint32_t* esc = g_esc + (size_t)((l & 2) * 65536 + head * 2048) * 20;
      const uint32_t* qs = (const uint32_t*)(g_qsave + (block_id() * 256 + wg * 128 + w * 32 + lane) * 8 + 2 * t);
      uint32_t q[8]; float o[20];
#pragma unroll
      for (int i = 0; i < 2; i++) {
        uint32_t u[4] = {__ldcg(qs + i), __ldcg(qs + i + 2), __ldcg(qs + i + 4), __ldcg(qs + i + 6)};
        unesc(u, esc + (row + i * 8) * 20 + (lane & 3), tag);
        q[i] = u[0]; q[i + 2] = u[1]; q[i + 4] = u[2]; q[i + 6] = u[3];
      }
      __syncwarp();
      attn_slow(q, head, esc + 65536 * 20, tag, o, lane);
      const float i0 = rcp(o[16]), i1 = rcp(o[18]);
      bf16* op = g_os + (size_t)row * 1024 + h * 512 + (b & 15) * 32 + (lane & 3) * 8;
      *(uint4*)op = make_uint4(pack2(o[0] * i0, o[1] * i0), pack2(o[4] * i0, o[5] * i0), pack2(o[8] * i0, o[9] * i0), pack2(o[12] * i0, o[13] * i0));
      *(uint4*)(op + 8 * 1024) = make_uint4(pack2(o[2] * i1, o[3] * i1), pack2(o[6] * i1, o[7] * i1), pack2(o[10] * i1, o[11] * i1), pack2(o[14] * i1, o[15] * i1));
    }
    if ((t & 1) && ((redo >> 2 * h) & 3)) bar_arrive(NB_SIG + 2 * h + wg, 160 + 32 * (h & wg));
  }
}

__global__ void __cluster_dims__(2, 1, 1) __launch_bounds__(384, 1) fused_kernel(const __grid_constant__ Params prm) {
  extern __shared__ __align__(1024) char smem[];
  const uint32_t sb = (uint32_t)__cvta_generic_to_shared(smem);
  const int tid = threadIdx.x, lane = tid & 31;
  const int wg = __shfl_sync(0xffffffffu, tid >> 7, 0);
  const int w = __shfl_sync(0xffffffffu, (tid >> 5) & 3, 0);
  const int bm = remap(blockIdx.x) >> 4, bn = remap(blockIdx.x) & 15;

  auto first_tile = [&](int kt) {
    e_expect_tx(sb + B_QF + 8 * kt, QSTG);
    tma_ld(sb + kt * QSTG, &prm.m[M_X0A], kt * 64, bm * 256, sb + B_QF + 8 * kt);
    tma_ld3(sb + kt * QSTG + 32768, &prm.m[M_WQA], bn * 64, kt * 64, 0, sb + B_QF + 8 * kt);
  };
  auto init4 = [&](uint32_t bar, uint32_t c0, uint32_t c1, uint32_t c2, uint32_t c3) {
    asm volatile("{\n.reg .pred pe;\nelect.sync _|pe, 0xffffffff;\n@pe mbarrier.init.shared::cta.b64 [%0], %1;\n@pe mbarrier.init.shared::cta.b64 [%0+8], %2;\n"
                 "@pe mbarrier.init.shared::cta.b64 [%0+16], %3;\n@pe mbarrier.init.shared::cta.b64 [%0+24], %4;\n@pe fence.mbarrier_init.release.cluster;\n}"
                 ::"r"(bar), "r"(c0), "r"(c1), "r"(c2), "r"(c3) : "memory");
  };
  if (wg < 2) {
    const uint32_t k = wg * 4 + w, lo = (0x1411814u >> (4 * k)) & 15, hi = (0x1441814u >> (4 * k)) & 15;
    if (tid < 32) asm volatile("prefetch.global.L2 [%0];" ::"l"(prm.x0 + (size_t)(bm * 256 + bn * 16 + (tid & 15)) * 1024 + (tid >> 4) * 64));
    else if (tid < 80) asm volatile("prefetch.global.L2 [%0];" ::"l"(prm.wq[0] + (bm * 16 + (tid & 15)) * 3072 + ((tid >> 4) - 2) * 1024 + bn * 64));
    __syncwarp();
    if (k < 7) init4(sb + B_QE + 32 * k, lo, lo, hi, k == 6 ? 2 : hi);
    __syncwarp();
    if (k == 6 && lane == 0) *(volatile unsigned long long*)(smem + W_X) = 0ull;
  } else if (w == 0) {
    init4(sb + B_QF, 1, 1, 1, 1);
    __syncwarp();
    first_tile(0);
  }
  __syncthreads();
  asm volatile("barrier.cluster.arrive.relaxed.aligned;" ::: "memory");

  if (wg == 2) {
    asm volatile("setmaxnreg.dec.sync.aligned.u32 56;");
    const uint32_t ep1 = *(volatile uint32_t*)&g_epoch + 1;
    if (w == 0) {
      first_tile(1);
      mbar_wait(sb + B_QF, 0);
      first_tile(2); first_tile(3);
#pragma unroll 1
      for (int kt = 4; kt < 16; kt++) l2_prefetch(prm.wq[0] + kt * 196608 + blockIdx.x * 1536, 3072);
      cluster_wait();
#pragma unroll 1
      for (int l = 0; l < 4; l++) {
        IDS();
        const CUtensorMap* mw = &prm.m[M_WQA + (l & 1)];
        const CUtensorMap* mx = &prm.m[l == 0 ? M_X0A : M_XSA];
        const CUtensorMap* mh = &prm.m[l == 0 ? M_X0H : M_XSO];
        const CUtensorMap* mo = &prm.m[M_WOA + (l & 1)];
        auto q_b = [&](int i) {
          const int s = i & 3;
          mbar_wait(sb + B_QE + 8 * s, ((i >> 2) & 1) ^ 1);
          e_expect_tx(sb + B_QF + 8 * s, QSTG);
          tma_ld3(sb + s * QSTG + 32768, mw, bn * 64, qord(i, l, pn) * 64, 0, sb + B_QF + 8 * s);
        };
        uint32_t rdy = l ? 0u : ~0u;
        auto q_a = [&](int i) {
          const int kt = qord(i, l, pn);
          await_flag(kt, rdy, cnt_x(l, bm) + (lane & 15), ep1 * 2);
          if (i < 4) tma_ld(sb + i * QSTG, mx, kt * 64, bm * 256, sb + B_QF + 8 * i);
          else tma_ld_mc(sb + (i & 3) * QSTG + rank * 16384, mh, kt * 64, bm * 256 + rank * 128, sb + B_QF + 8 * (i & 3));
        };
        if (l > 0) {
#pragma unroll 1
          for (int i = 0; i < 2; i++) {
            await_flag(2 * pn + i, rdy, cnt_x(l, bm) + (lane & 15), ep1 * 2);
            e_expect_tx(sb + B_QF + 8 * i, 16384);
            tma_ld(sb + i * QSTG + (po ^ 1) * 16384, &prm.m[M_XSO], (2 * pn + i) * 64, (pm ^ 1) * 128, sb + B_QF + 8 * i);
            if (i == 0) {  q_a(2); }
          }
          mbar_wait(sb + B_QF + 8, 0);
        }
#pragma unroll 1
        for (int i = l ? 3 : 4; i < 16; i++) {
          if (l == 3 && i == 12) poll_ge(cnt_ad(bn), ep1 * 16);
          q_b(i); q_a(i);
        }
        if (l & 1) {
          const int krow = 2 * bn * 2048 + bm * 256;
          uint32_t* kvc = cnt_kv(l >> 1, bn);
          uint32_t seen = 0;
#pragma unroll 1
          for (int it = 1; it < 16; it++) {
            const int s = it & 3;
            if (it == 4) {
              bar_sync(NB_KV + 12, 288);
              mbar_wait(sb + B_TF + 24, 0);
#pragma unroll 1
              for (int i = 0; i < 4; i++) tma_st(&prm.m[M_K + (i & 1)], 0, krow + 2048 + (i >> 1) * 128, sb + i * 8192);
              bulk_commit();
            }
            if (it == 5) { bulk_wait_n<0>(); e_red(kvc + 16 + bm); }
            if (it == 12) { e_expect_tx(sb + B_RF, 32768); tma_ld3(sb + RES, &prm.m[M_XSR], 0, pm * 128, 2 * pn, sb + B_RF); }
            if (it == 1 || it == 3) mbar_wait(sb + B_QE + 12 + 4 * it, 1);
            mbar_wait(sb + B_TE + 8 * s, ((it >> 2) & 1) ^ 1);
            if (it < 8) {
#pragma unroll 1
              for (uint32_t n = 0; n < 200000u && (~seen & (3u << (2 * it - 2) | (it == 4 ? 0xC000u : 0u))); n++)
                seen = __ballot_sync(~0u, (int)(ld_acquire(kvc + (lane < 7 || lane == 15 ? (bm + 1 + lane) & 7 : 8 + ((bm + 2 + lane) & 7))) - ep1) >= 0);
              fence_async_gl();
            } else if (it == 8) { poll_ge(kvc + 16 + (lane & 7), ep1); fence_async_gl(); }
            e_expect_tx(sb + B_TF + 8 * s, 32768);
#pragma unroll 1
            for (int i = 0; i < 2; i++) {
              const int u = 2 * it - 2 + i;
              const int row = 2 * bn * 2048 + (it > 7 ? 2048 + ((bm + it) & 7) * 256 + i * 128 : u < 7 ? ((bm + 1 + u) & 7) * 256 : ((bm + 2 + u) & 7) * 256 + 128);
              tma_ld(sb + T0 + s * TSTG + i * 8192, &prm.m[M_K], 0, row, sb + B_TF + 8 * s);
              tma_ld(sb + T0 + s * TSTG + 16384 + i * 8192, &prm.m[M_V], 0, row, sb + B_TF + 8 * s);
            }
          }
        }
        auto p_b = [&](int i, uint32_t s, uint32_t par) {
          mbar_wait(sb + B_PE + 8 * s, par ^ 1);
          e_expect_tx(sb + B_PF + 8 * s, PSTG);
          tma_ld5(sb + pslot_b(s), mo, i >> 3, 2 * (i & 7), 2 * pn, sb + B_PF + 8 * s);
        };
        auto p_a = [&](int i, uint32_t s) {
          await_flag(i, rdy, cnt_o(l, pm, (lane >> 3) & 1) + (lane & 7), ep1 * 2);
          tma_ld_mc(sb + pslot_a(s, l) + rank * 8192, &prm.m[M_OS], i * 64, pm * 128 + rank * 64, sb + B_PF + 8 * s);
        };
        auto p_a2 = [&](int i) {
          await_flag(i, rdy, cnt_o(l, pm, (lane >> 3) & 1) + (lane & 7), ep1 * 2);
          tma_ld(sb + pslot_a(i, l), &prm.m[M_OS], i * 64, pm * 128, sb + B_PF + 8 * i);
          tma_ld(sb + pslot_a(i, l) + 8192, &prm.m[M_OS], i * 64, pm * 128 + 64, sb + B_PF + 8 * i);
        };
        rdy = 0;
        if (l & 1) {
#pragma unroll 1
          for (int u = 0; u < 6; u++) { const int i = (0x205413 >> (4 * u)) & 7; if (u == 4) mbar_wait(sb + B_TE, 1); p_b(i, i, i < 4 ? 1 : 0); }
#pragma unroll 1
          for (int u = 0; u < 6; u++) {
            const int i = (0x542130 >> (4 * u)) & 7;
            if (!(u & 1)) mbar_wait(sb + B_TE + 8 + 4 * u, 1);
            if (u == 4) bar_sync(NB_SIG + 3, 192);
            p_a2(i);
          }
        } else {
#pragma unroll 1
          for (int u = 0; u < 6; u++) { const int i = (0x543120 >> (4 * u)) & 7; if (u == 0 || u == 2) mbar_wait(sb + B_QE + 8 - 4 * u, 1); p_b(i, i, 0); }
          mbar_wait(sb + B_QE + 24, 1);
          e_expect_tx(sb + B_RF, 32768);
          tma_ld3(sb + RES, &prm.m[l == 0 ? M_X0R : M_XSR], 0, pm * 128, 2 * pn, sb + B_RF);
          p_a2(0);
          bar_sync(NB_SIG + 2, 320);
          e_arrive_both(sb + B_PA);
          p_a2(1);
          mbar_wait(sb + B_PA, (l >> 1) & 1);
#pragma unroll 1
          for (int i = 2; i < 6; i++) { if (i > 2) mbar_wait(sb + B_PF + 8 * (i - 3), 0); p_a(i, i); }
        }
        uint32_t s = 0, lap = 1;
#pragma unroll 1
        for (int i = 6; i < 16; i++) {
          p_b(i, s, ((s < 4 ? l : 0) + lap) & 1);
          p_a(i, s);
          if (++s == 6) { s = 0; lap++; }
        }
        const CUtensorMap* mn = &prm.m[M_WQA + ((l + 1) & 1)];
        if (l < 3) {
          mbar_wait(sb + B_PE + 8 * 4, 1); mbar_wait(sb + B_PE + 8 * 5, 1);
          tma_ld3(sb + 32768, mn, bn * 64, 2 * pn * 64, 0, sb + B_QL);
          mbar_wait(sb + B_PE + 8 * 0, l & 1);
          tma_ld3(sb + QSTG + 32768, mn, bn * 64, (2 * pn + 1) * 64, 0, sb + B_QL);
          mbar_wait(sb + B_PE + 8 * 1, l & 1);
          e_expect_tx(sb + B_QF + 16, QSTG);
          tma_ld3(sb + 2 * QSTG + 32768, mn, bn * 64, ((2 * pn) ^ 2) * 64, 0, sb + B_QF + 16);
        }
        if (l < 3) { bar_sync(NB_X, 320); e_expect_tx(sb + B_QL, 49152); }
      }
      if (blockIdx.x == 0 && lane_id() == 0) *(volatile uint32_t*)&g_epoch = ep1;
    } else {
      const int hw = w - 1;
      if (lane < 5) asm volatile("prefetch.tensormap [%0];" ::"l"(&prm.m[5 * hw + lane]) : "memory");
      __syncwarp();
      cluster_wait();
      mbar_wait(sb + B_QF, 0);
#pragma unroll 1
      for (int l = 0; l < 4; l++) {
        IDS();
        if (l > 0) { mbar_wait(sb + B_QL, (l + 1) & 1); mbar_wait(sb + B_QF + 8 * 3, 0); }
        if (l == 0) {
#pragma unroll 1
          for (int r = 2 * hw; r < 16; r += 6) {
            const uint4* p = (const uint4*)(prm.x0 + (size_t)(b * 16 + r) * 1024) + lane;
            float s1[2] = {0.f, 0.f}, s2[2] = {0.f, 0.f};
#pragma unroll
            for (int i = 0; i < 8; i++) {
              const uint4 v = __ldg(p + 32 * i);
              const uint32_t u[4] = {v.x, v.y, v.z, v.w};
#pragma unroll
              for (int k = 0; k < 4; k++) { const float a = bf_lo(u[k]), c = bf_hi(u[k]); s1[i >> 2] += a + c; s2[i >> 2] = fmaf(a, a, fmaf(c, c, s2[i >> 2])); }
            }
#pragma unroll
            for (int o = 16; o; o >>= 1)
#pragma unroll
              for (int rr = 0; rr < 2; rr++) { s1[rr] += __shfl_xor_sync(~0u, s1[rr], o); s2[rr] += __shfl_xor_sync(~0u, s2[rr], o); }
            if (lane == 0) *(float4*)&g_stats[b * 16 + r] = make_float4(s1[0], s2[0], s1[1], s2[1]);
          }
        }
        if (l < 2) {
          float cs[8];
#pragma unroll
          for (int i = 0; i < 8; i++) cs[i] = 0.f;
          const uint4* wp = (const uint4*)(prm.wq[l] + (size_t)(bm * 128 + (lane >> 3)) * 3072 + hw * 1024 + bn * 64) + (lane & 7);
#pragma unroll 8
          for (int i = 0; i < 32; i++) {
            const uint4 v = __ldg(wp + (size_t)i * 4 * 384);
            cs[0] += bf_lo(v.x); cs[1] += bf_hi(v.x); cs[2] += bf_lo(v.y); cs[3] += bf_hi(v.y);
            cs[4] += bf_lo(v.z); cs[5] += bf_hi(v.z); cs[6] += bf_lo(v.w); cs[7] += bf_hi(v.w);
          }
#pragma unroll
          for (int i = 0; i < 8; i++) { cs[i] += __shfl_xor_sync(~0u, cs[i], 8); cs[i] += __shfl_xor_sync(~0u, cs[i], 16); }
          if (lane < 8) {
            float4* d = (float4*)(g_csp + ((l * 16 + bn) * 8 + bm) * 192 + hw * 64 + lane * 8);
            d[0] = make_float4(cs[0], cs[1], cs[2], cs[3]); d[1] = make_float4(cs[4], cs[5], cs[6], cs[7]);
          }
          __syncwarp();
          asm volatile("fence.acq_rel.gpu;" ::: "memory");
          e_red_relaxed(cnt_cs(l, bn));
          if (l == 0) e_red_relaxed(cnt_x(0, bm) + pn);
          poll_ge(lane < 8 && l == 0 ? cnt_x(0, bm) + lane : cnt_cs(l, bn), ep1 * (lane < 8 && l == 0 ? 6 : 24));
        }
        if (l > 0) poll_ge(cnt_x(l, bm) + (lane & 15), ep1 * 2);
#pragma unroll 1
        for (int it = hw * 32 + lane; it < 176; it += 96) {
          const bool rows = it < 128;
          const float4* p = rows ? (const float4*)(g_stats + bm * 256) + it : (const float4*)(g_csp + ((l & 1) * 16 + bn) * 8 * 192) + (it - 128);
          const int stride = rows ? 1024 : 48, np = rows && l == 0 ? 1 : 8;
          float4 a = make_float4(0.f, 0.f, 0.f, 0.f);
#pragma unroll
          for (int k = 0; k < 8; k++) if (k < np) { const float4 v = __ldcg(p + k * stride); a.x += v.x; a.y += v.y; a.z += v.z; a.w += v.w; }
          if (rows) {
            const float m0 = a.x * (1.f / 1024.f), m1 = a.z * (1.f / 1024.f);
            const float v0 = fmaxf(a.y * (1.f / 1024.f) - m0 * m0, 0.f), v1 = fmaxf(a.w * (1.f / 1024.f) - m1 * m1, 0.f);
            const float r0 = __fdividef(1.f, bf_round(sqrtf(bf_round(bf_round(v0) + 1e-5f)))), r1 = __fdividef(1.f, bf_round(sqrtf(bf_round(bf_round(v1) + 1e-5f))));
            a = make_float4(r0, -bf_round(m0), r1, -bf_round(m1));
          }
          if (rows && (l & 1) && (it & 4)) a = make_float4(a.y, a.x, a.w, a.z);
          *(float4*)(smem + ROWST + it * 16) = a;
        }
        __syncwarp();
        if (lane == 0) asm volatile("red.release.cta.shared.add.u32 [%0], 1;" ::"r"(sb + W_X) : "memory");
        if (hw == 2) {
          if (!(l & 1)) {
            bar_sync(NB_ST, 288);
            const uint4* hp = g_halo + ((l >> 1) * 128 + b - 16) * 384 + lane;
#pragma unroll 1
            for (int h = 0; h < 2; h++) {
              uint32_t t[18];
#pragma unroll
              for (int i = 0; i < 18; i++) t[i] = 0;
#pragma unroll 1
              for (uint32_t n = bm ? 0 : 100000u; n < 100000u; n++) {
                uint32_t miss = 0;
#pragma unroll
                for (int i = 0; i < 6; i++) miss |= ld_tagged(hp + h * 192 + i * 32, &t[3 * i]) ^ ep1;
                if (__all_sync(~0u, !miss)) break;
              }
              mbar_wait(sb + B_QE + 16, 1);
              const uint32_t r = (lane & 7) + ((lane >> 3) & 1) * 8, rv = lane >> 2;
#pragma unroll
              for (int jj = 0; jj < 2; jj++) stsm4(sb + KSC + r * 128 + (((4 * h + 2 * jj + (lane >> 4)) ^ (r & 7)) << 4), t[4 * jj], t[4 * jj + 1], t[4 * jj + 2], t[4 * jj + 3]);
              const uint32_t ad = sb + VSC + rv * 128 + (((4 * h + (lane & 3)) ^ (rv & 7)) << 4);
              sts128(ad, t[8], t[10], t[12], t[14]); sts128(ad + 1024, t[9], t[11], t[13], t[15]);
              if (h == 0 && !(lane & 2)) *(uint32_t*)(smem + HRS + ((lane >> 2) + 8 * (lane & 1)) * 8) = t[16];
              bar_arrive(NB_HALO + h, 64);
            }
          } else {
            bar_sync(NB_KV, 288);
            sts128(sb + ONES + lane * 32, 0x3f803f80u, 0x3f803f80u, 0x3f803f80u, 0x3f803f80u);
            sts128(sb + ONES + lane * 32 + 16, 0x3f803f80u, 0x3f803f80u, 0x3f803f80u, 0x3f803f80u);
            fence_async_smem();
            __syncwarp();
            e_arrive(sb + B_TF);
            mbar_wait(sb + B_TF + 16, 0); mbar_wait(sb + B_TF + 16, 1);
            poll_ge(cnt_kv(l >> 1, bn) + 16 + (lane & 7), ep1);
            const uint4 v = __ldcg((const uint4*)(g_kn + ((l >> 1) * 128 + bn * 8) * 16) + lane);
            const uint32_t mx = max(max(v.x, v.y), max(v.z, v.w));
            const uint32_t m0 = __reduce_max_sync(~0u, (lane & 2) ? 0u : mx), m1 = __reduce_max_sync(~0u, (lane & 2) ? mx : 0u);
            if (lane == 0) *(uint2*)(smem + ROWST) = make_uint2(m0, m1);
            __syncwarp();
            bar_arrive(NB_KN, 160); bar_arrive(NB_KN + 1, 160);
          }
        } else {
          if (l & 1) {
            uint32_t* p = cnt_kv(l >> 1, bn) + 8 * hw + bm;
            int on = lane == 0;
            PREPARED(p, on);
            bar_sync(hw ? NB_HALO : NB_DONE, 160);
            tma_st(&prm.m[M_K], 0, 2 * bn * 2048 + bm * 256 + hw * 128, sb + T0 + hw * 8192);
            tma_st(&prm.m[M_V], 0, 2 * bn * 2048 + bm * 256 + hw * 128, sb + T0 + 16384 + hw * 8192);
            bulk_commit(); bulk_wait_n<0>();
            release_add(p, on);
          }
#pragma unroll 1
          for (int h = l & 1 ? 0 : hw; h <= (l & 1 ? 1 : hw); h++) {
            uint32_t* p = l == 1 && lane == 1 ? cnt_ad(bn) : cnt_o(l, 2 * bm + (l & 1 ? hw : lane & 1), h) + (bn >> 1);
            int on = lane == 0 || (lane == 1 && (!(l & 1) || (l == 1 && h == 1)));
            int id = NB_SIG + 2 * h + (l & hw), n = (l & 1 ? 160 : 288) + 32 * (h & hw);
            asm volatile("" : "+r"(id), "+r"(n));
            PREPARED(p, on);
            bar_sync(id, n);
            release_add(p, on);
          }
        }
        if (hw < 2 && l < 3) {
          uint32_t* p = cnt_x(l + 1, bm) + 2 * pn + hw;
          int on = lane == 0;
          PREPARED(p, on);
          if (hw) {
            bar_sync(NB_X, 320);
            tma_st(&prm.m[M_XSO], pn * 128 + 64, pm * 128, sb + QSTG + po * 16384);
            bulk_commit();
            bar_sync(NB_KV, 288);
            bulk_wait_n<0>();
          } else bar_sync(NB_X0, 288);
          release_add(p, on);
        }
      }
    }
  } else {
    asm volatile("setmaxnreg.inc.sync.aligned.u32 224;");
    const uint32_t zero = prm.zero;
    cluster_wait();
#pragma unroll 1
    for (int l = 0; l < 4; l++) {
      {
        float acc[2][96];
#pragma unroll
        for (int i = 0; i < 96; i++) { acc[0][i] = 0.f; acc[1][i] = 0.f; }
        fence_regs(acc[0]); fence_regs(acc[1]);
        const bool early = l > 0 && wg == ((cta_id() >> 3) & 1);
        uint32_t ep1 = 0;
#pragma unroll 1
        for (int kt = 0; kt < 13; kt++) {
          const int s = kt == 12 ? 1 : kt & 3;
          if (l > 0 && kt == 0) mbar_wait(sb + B_QL, (l + 1) & 1);
          if (!(early && kt < 2)) mbar_wait(sb + B_QF + 8 * s, (kt >> 2) & 1);
          const uint64_t da = prm.xd + wg * 1024 + s * (QSTG >> 4), db = prm.wd + s * (QSTG >> 4);
          wg_fence();
#pragma unroll
          for (int k = 0; k < 4; k++)
#pragma unroll
            for (int m = 0; m < 2; m++) wgmma_m64n192k16_ss_tb(acc[m], da + m * 512 + k * 2, db + k * 128, 1);
          wg_commit();
          if (kt == 4) ep1 = *(volatile uint32_t*)&g_epoch + 1;
          wg_wait<1>();
          if (early && (kt == 1 || kt == 2)) mbar_wait(sb + B_QF + 8 * (kt - 1), 0);
          if (kt > 0 && w == 0) e_arrive_both(sb + B_QE + 8 * ((kt - 1) & 3));
        }
        {
          const bool lag = (l & 1) == wg;
          const uint32_t s0 = 2 * (~l & 1);
          const uint64_t da = prm.xd + wg * 1024 + 2 * (QSTG >> 4), db = prm.wd + 2 * (QSTG >> 4);
          mbar_wait(sb + B_QF + 8 * s0, 1);
#pragma unroll
          for (int t = 0; t < 2; t++) {
            if (lag && t != wg) {
              wg_wait<0>();
              if (w == 0) e_arrive_both(sb + B_QE + 8 + 8 * t);
              if (t == 0) mbar_wait(sb + B_QF + 16, 1);
              mbar_wait(sb + B_QF + 24, 1);
              if (t == 1) bar_arrive(NB_ST, 288);
              bar_sync(NB_SC, 256);
            }
            const uint64_t so = (uint64_t)(t ? s0 : s0 ^ 2) * (QSTG >> 4);
            wg_fence();
#pragma unroll
            for (int k = 0; k < 4; k++)
#pragma unroll
              for (int m = 0; m < 2; m++) wgmma_m64n192k16_ss_tb(acc[m], da - so + m * 512 + k * 2, db - so + k * 128, 1);
            wg_commit();
            if (!lag || t + wg == 0) {
              wg_wait<1>();
              if (w == 0) e_arrive_both(sb + B_QE + 8 * (t ? s0 : 1));
              mbar_wait(sb + B_QF + 8 * (t ? 3 : s0 ^ 2), 1);
            }
          }
          wg_fence();
#pragma unroll
          for (int m = 1; m >= 0; m--) {
#pragma unroll
            for (int k = 0; k < 4; k++) wgmma_m64n192k16_ss_tb(acc[m], da + (QSTG >> 4) + m * 512 + k * 2, db + (QSTG >> 4) + k * 128, 1);
            wg_commit();
          }
          if (!lag) { bar_arrive(NB_SC, 256); if (wg) bar_arrive(NB_ST, 288); }
          wg_wait<2>();
          if (w == 0) { e_arrive_both(sb + B_QE + 8 * (s0 ^ 2)); if (lag && wg) e_arrive_both(sb + B_QE); }
        }
#pragma unroll 1
        for (uint32_t n = 0; n < 4000000u; n++) {
          uint32_t v;
          asm volatile("ld.acquire.cta.shared.u32 %0, [%1];" : "=r"(v) : "r"(sb + W_X) : "memory");
          if (v == (uint32_t)(3 * l + 3)) break;
        }
        IDS();
        const int g = lane >> 2, qd = lane & 3;
        float2 st[2][2];
#pragma unroll
        for (int m = 0; m < 2; m++)
#pragma unroll
          for (int hh = 0; hh < 2; hh++) st[m][hh] = lds64f(sb + ROWST + (wg * 128 + m * 64 + w * 16 + g + 8 * hh) * 8);
        float2 cs[4];
        auto load_cs = [&](int gi) {
#pragma unroll
          for (int j = 0; j < 4; j++) cs[j] = lds64f(sb + COLS + (gi * 32 + j * 8 + 2 * qd) * 4);
        };
        load_cs(2);
        auto drain = [&]() {
          wg_wait<0>(); fence_regs(acc[0]);
          if (w == 0) e_arrive_both(sb + B_QE + 8 * 3);
        };
        wg_wait<1>(); fence_regs(acc[1]);
        auto norm_tile = [&](int gi, int m, float sc, uint32_t (&t)[8], float (&nrm)[2], bool h16 = false) {
          const float r0 = st[m][0].x * sc, s0 = st[m][0].y, r1 = st[m][1].y * sc, s1 = st[m][1].x;
          float n0 = 0.f, n1 = 0.f;
#pragma unroll
          for (int j = 0; j < 4; j++) {
            const float* a = &acc[m][16 * gi + 4 * j];
            const float v0 = fmaf(s0, cs[j].x, a[0]) * r0, v1 = fmaf(s0, cs[j].y, a[1]) * r0;
            const float v2 = fmaf(s1, cs[j].x, a[2]) * r1, v3 = fmaf(s1, cs[j].y, a[3]) * r1;
            n0 = fmaf(v0, v0, fmaf(v1, v1, n0)); n1 = fmaf(v2, v2, fmaf(v3, v3, n1));
            t[2 * j] = h16 ? pack2h(v0, v1) : pack2(v0, v1); t[2 * j + 1] = h16 ? pack2h(v2, v3) : pack2(v2, v3);
          }
          nrm[0] = n0; nrm[1] = n1;
        };
        auto norm_group = [&](int gi, float sc, uint32_t (&t)[2][8], float (&nrm)[2][2]) { norm_tile(gi, 0, sc, t[0], nrm[0]); norm_tile(gi, 1, sc, t[1], nrm[1]); };
        uint32_t q[2][2][8];
        const uint32_t srow = (lane & 7) + ((lane >> 3) & 1) * 8;
        const uint32_t row0 = wg * 128 + w * 16;
        if (!(l & 1)) {
          auto put_kv = [&](int gi, uint32_t r0, const uint32_t (&t)[8]) {
            if (gi < 4) {
              const uint32_t r = r0 + srow;
#pragma unroll
              for (int jj = 0; jj < 2; jj++) stsm4(sb + KSC + r * 128 + (((4 * (gi - 2) + 2 * jj + (lane >> 4)) ^ (r & 7)) << 4), t[4 * jj], t[4 * jj + 1], t[4 * jj + 2], t[4 * jj + 3]);
            } else {
              const uint32_t r = r0 + g, ad = sb + VSC + r * 128 + (((4 * (gi - 4) + qd) ^ (r & 7)) << 4);
              sts128(ad, t[0], t[2], t[4], t[6]); sts128(ad + 1024, t[1], t[3], t[5], t[7]);
            }
          };
          auto cen_tile = [&](int gi, int m, uint32_t (&t)[8]) {
#pragma unroll
            for (int j = 0; j < 4; j++) {
              const float* a = &acc[m][16 * gi + 4 * j];
              t[2 * j] = pack2(fmaf(st[m][0].y, cs[j].x, a[0]), fmaf(st[m][0].y, cs[j].y, a[1]));
              t[2 * j + 1] = pack2(fmaf(st[m][1].y, cs[j].x, a[2]), fmaf(st[m][1].y, cs[j].y, a[3]));
            }
          };
          const bool send = wg == 1 && w == 3 && bm < 7;
          uint4* hp = g_halo + ((l >> 1) * 128 + b) * 384 + lane;
          mbar_wait(sb + B_QE + 16, 1);
          float2 cn[4];
          auto next_cs = [&](int gi) {
#pragma unroll
            for (int j = 0; j < 4; j++) { cs[j] = cn[j]; cn[j] = lds64f(sb + COLS + (gi * 32 + j * 8 + 2 * qd) * 4); }
          };
#pragma unroll
          for (int j = 0; j < 4; j++) cn[j] = cs[j];
#pragma unroll
          for (int h = 0; h < 2; h++) {
            uint32_t k[8], v[8];
            next_cs(4 + h);
            cen_tile(2 + h, 1, k); put_kv(2 + h, 16 + row0 + 64, k);
            next_cs(h ? 2 : 3);
            cen_tile(4 + h, 1, v); put_kv(4 + h, 16 + row0 + 64, v);
            if (send) {
              uint4* p = hp + h * 192;
              st_tagged(p, k[0], k[1], k[2], ep1); st_tagged(p + 32, k[3], k[4], k[5], ep1); st_tagged(p + 64, k[6], k[7], v[0], ep1);
              st_tagged(p + 96, v[1], v[2], v[3], ep1); st_tagged(p + 128, v[4], v[5], v[6], ep1);
              st_tagged(p + 160, v[7], __float_as_uint(qd & 1 ? st[1][1].x : st[1][0].x), 0u, ep1);
            }
            sched_fence();
          }
          drain();
          {
            uint32_t t[8];
            next_cs(4); cen_tile(2, 0, t); put_kv(2, 16 + row0, t);
            next_cs(0); cen_tile(4, 0, t); put_kv(4, 16 + row0, t);
            next_cs(3); cen_tile(0, 0, q[0][0]); cen_tile(0, 1, q[0][1]);
          }
          const bool e = g & 1, sel = 2 * qd + (g & 1) >= g + 2, first = bm == 0 && row0 == 0;
          uint32_t ka = sb + KSC + (row0 + (lane & 7)) * 128 + (((lane >> 3) ^ (lane & 7)) << 4);
          uint32_t wa = sb + VSC + (row0 + srow) * 128 + (((lane >> 4) ^ (lane & 7)) << 4);
          uint32_t psel[3] = {e ? 0x1044u : 0x4410u, !sel ? 0x4444u : e ? 0x3244u : 0x4432u, sel ? 0x4444u : e ? 0x3244u : 0x4432u};
          bf16* op = g_os + (size_t)(bm * 256 + row0 + g) * 1024 + bn * 32 + qd * 8;
          asm volatile("" : "+r"(ka), "+r"(wa), "+l"(op));
          fence_regs(psel); fence_regs(q[0][0]); fence_regs(q[0][1]);
          sched_fence();
          bar_sync(NB_SC, 256);
          if (row0 == 0) bar_sync(NB_HALO, 64);
          float ra[4], rb[4], ca[4], cb[4];
#pragma unroll
          for (int m = 0; m < 2; m++) {
            float rk[3];
#pragma unroll
            for (int u = 0; u < 3; u++) {
              const int r = row0 + m * 64 + 8 * u + 2 * qd + e - (sel ? 16 : 8);
              rk[u] = lds64f(sb + (m == 0 && r < 0 ? HRS + 128 : ROWST) + r * 8).x;
            }
            ra[2 * m] = sel ? rk[1] : rk[0]; ra[2 * m + 1] = sel ? rk[2] : rk[1];
            rb[2 * m] = sel ? rk[0] : rk[1]; rb[2 * m + 1] = sel ? rk[1] : rk[2];
          }
#pragma unroll
          for (int i = 0; i < 4; i++) { const float rq = st[i >> 1][i & 1].x * QSCALE; ca[i] = rq * ra[i]; cb[i] = rq * rb[i]; }
#pragma unroll 1
          for (int h = 0; h < 2; h++) {
            float s[2][4][4];
            uint32_t vf[2][4][4], pf[2][2][4];
#pragma unroll
            for (int m = 0; m < 2; m++)
#pragma unroll
              for (int nt = 0; nt < 4; nt++) {
                uint32_t kf[4];
                ldsm4(ka + (m * 64 + 8 * nt) * 128, kf);
                s[m][nt][0] = s[m][nt][1] = s[m][nt][2] = s[m][nt][3] = 0.f;
                mma16816(s[m][nt], q[0][m][0], q[0][m][1], q[0][m][2], q[0][m][3], kf[0], kf[1]);
                mma16816(s[m][nt], q[0][m][4], q[0][m][5], q[0][m][6], q[0][m][7], kf[2], kf[3]);
              }
#pragma unroll
            for (int m = 0; m < 2; m++)
#pragma unroll
              for (int i = 0; i < 4; i++) {
                ldsm4t((wa ^ (32 * (i & 1))) + (m * 64 + 16 * (i >> 1)) * 128, vf[m][i]);
              }
            float va[4], vb[4], mx[4];
#pragma unroll
            for (int i = 0; i < 4; i++) {
              const int m = i >> 1, hh = i & 1;
              const float a = e ? s[m][hh + 1][2 * hh + 1] : s[m][hh + 1][2 * hh];
              const float lo = e ? s[m][hh][2 * hh + 1] : s[m][hh][2 * hh], hi = e ? s[m][hh + 2][2 * hh + 1] : s[m][hh + 2][2 * hh];
              va[i] = (m == 0 && hh == 0 && first) ? -INFINITY : a * ca[i];
              vb[i] = (m == 0 && first && sel) ? -INFINITY : (sel ? lo : hi) * cb[i];
              mx[i] = fmaxf(va[i], vb[i]);
            }
#pragma unroll
            for (int i = 0; i < 4; i++) mx[i] = fmaxf(mx[i], __shfl_xor_sync(~0u, mx[i], 1));
#pragma unroll
            for (int i = 0; i < 4; i++) mx[i] = fmaxf(mx[i], __shfl_xor_sync(~0u, mx[i], 2));
#pragma unroll
            for (int i = 0; i < 4; i++) {
              va[i] = ex2(va[i] - mx[i]); vb[i] = ex2(vb[i] - mx[i]);
              mx[i] = va[i] + vb[i];
              va[i] *= ra[i]; vb[i] *= rb[i];
            }
#pragma unroll
            for (int i = 0; i < 4; i++) mx[i] += __shfl_xor_sync(~0u, mx[i], 1);
#pragma unroll
            for (int i = 0; i < 4; i++) mx[i] += __shfl_xor_sync(~0u, mx[i], 2);
#pragma unroll
            for (int i = 0; i < 4; i++) {
              const int m = i >> 1, hh = i & 1;
              const float inv = rcp(mx[i]);
              const uint32_t t = pack2(va[i] * inv, vb[i] * inv);
              pf[m][hh][hh + 1] = prmt0(t, psel[0]); pf[m][hh][hh] = prmt0(t, psel[1]); pf[m][hh][hh + 2] = prmt0(t, psel[2]);
              pf[m][hh][3 - 3 * hh] = t & zero;
            }
#pragma unroll
            for (int m = 0; m < 2; m++) {
              float o[4][4];
#pragma unroll
              for (int j = 0; j < 4; j++) o[j][0] = o[j][1] = o[j][2] = o[j][3] = 0.f;
#pragma unroll
              for (int i = 0; i < 4; i++) {
                const int kk = i >> 1, jj = 2 * (i & 1);
                mma16816(o[jj], pf[m][0][2 * kk], pf[m][1][2 * kk], pf[m][0][2 * kk + 1], pf[m][1][2 * kk + 1], vf[m][i][0], vf[m][i][1]);
                mma16816(o[jj + 1], pf[m][0][2 * kk], pf[m][1][2 * kk], pf[m][0][2 * kk + 1], pf[m][1][2 * kk + 1], vf[m][i][2], vf[m][i][3]);
              }
              stg128(op + m * 65536, pack2(o[0][0], o[0][1]), pack2(o[1][0], o[1][1]), pack2(o[2][0], o[2][1]), pack2(o[3][0], o[3][1]));
              stg128(op + m * 65536 + 8192, pack2(o[0][2], o[0][3]), pack2(o[1][2], o[1][3]), pack2(o[2][2], o[2][3]), pack2(o[3][2], o[3][3]));
            }
            bar_arrive(NB_SIG + 2 * h, 288 + 32 * h);
            if (h == 0) {
              uint32_t t[8];
              next_cs(5); cen_tile(3, 0, t); put_kv(3, 16 + row0, t);
              next_cs(1); cen_tile(5, 0, t); put_kv(5, 16 + row0, t);
#pragma unroll
              for (int j = 0; j < 4; j++) cs[j] = cn[j];
              cen_tile(1, 0, q[0][0]); cen_tile(1, 1, q[0][1]);
              ka ^= 64; wa ^= 64; op += 512;
              bar_sync(NB_SC, 256);
              if (row0 == 0) bar_sync(NB_HALO + 1, 64);
            }
          }
        } else {
          float qn[2];
          drain();
          auto esc_ptr = [&](int gi) { IDS(); return g_esc + (size_t)(((l & 2) + (gi >> 1)) * 65536 + (2 * bn + (gi & 1)) * 2048) * 20; };
          auto norm_half = [&](int gi, float sc, uint32_t (&t)[2][8], float (&nrm)[2][2], int nx) {
            norm_tile(gi, 0, sc, t[0], nrm[0], true); norm_tile(gi, 1, sc, t[1], nrm[1], true);
            float2 cn[4];
#pragma unroll
            for (int j = 0; j < 4; j++) if (nx >= 0) cn[j] = lds64f(sb + COLS + (nx * 32 + j * 8 + 2 * qd) * 4);
            if (!((nrm[0][0] + nrm[0][1]) + (nrm[1][0] + nrm[1][1]) <= 4e9f) || fminf(fminf(nrm[0][0], nrm[0][1]), fminf(nrm[1][0], nrm[1][1])) < 1.5e-5f) {
              uint32_t* p = esc_ptr(gi) + (bm * 256 + row0 + g) * 20 + qd;
#pragma unroll
              for (int m = 0; m < 2; m++) {
                uint32_t u[8]; float d[2];
                norm_tile(gi, m, sc, u, d);
#pragma unroll
                for (int i = 0; i < 10; i++) p[(m * 64 + (i & 1) * 8) * 20 + (i >> 1) * 4] = i < 8 ? u[i] : ep1;
              }
            }
            __syncwarp();
#pragma unroll
            for (int i = 0; i < 16; i++) asm volatile("{\n.reg .b32 u;\nadd.u32 u, %0, 0x00040004;\nand.b32 %0, u, 0xFFF8FFF8;\n}" : "+r"(t[i >> 3][i & 7]));
#pragma unroll
            for (int j = 0; j < 4; j++) if (nx >= 0) cs[j] = cn[j];
          };
          {
            auto max_norm = [&](const float (&nrm)[2][2]) {
              const bool o1 = qd & 1, o2 = qd & 2;
              const float a = (o1 ? nrm[1][0] : nrm[0][0]) + __shfl_xor_sync(~0u, o1 ? nrm[0][0] : nrm[1][0], 1);
              const float c = (o1 ? nrm[1][1] : nrm[0][1]) + __shfl_xor_sync(~0u, o1 ? nrm[0][1] : nrm[1][1], 1);
              const float d = (o2 ? c : a) + __shfl_xor_sync(~0u, o2 ? a : c, 2);
              return __uint_as_float(__reduce_max_sync(~0u, __float_as_uint(d)));
            };
#pragma unroll
            for (int h = 0; h < 2; h++) {
              uint32_t t[2][8]; float nrm[2][2];
              const uint32_t kb = sb + (h ? wg * 8192 : T0), vb = kb + (h ? 8192 : 16384);
              uint32_t tv[2][8];
              norm_half(2 + h, 1.f, t, nrm, 4 + h);
              float nv[2][2];
              if (h == 1) { const float kn = max_norm(nrm); if (lane == 0) g_kn[((l >> 1) * 128 + bn * 8 + bm) * 16 + 8 + wg * 4 + w] = kn; }
              if (h == 0) mbar_wait(sb + B_QE + 8, 1);
#pragma unroll
              for (int i = 0; i < 4; i++) {
                const uint32_t r = row0 + (i >> 1) * 64 + srow;
                stsm4(kb + r * 64 + (((2 * (i & 1) + (lane >> 4)) ^ ((r >> 1) & 3)) << 4), t[i >> 1][4 * (i & 1)], t[i >> 1][4 * (i & 1) + 1], t[i >> 1][4 * (i & 1) + 2], t[i >> 1][4 * (i & 1) + 3]);
              }
              norm_group(4 + h, 1.f, tv, nv);
              load_cs(h);
#pragma unroll
              for (int m = 0; m < 2; m++) {
                const uint32_t r = row0 + m * 64 + g, ad = vb + r * 64 + ((qd ^ ((r >> 1) & 3)) << 4);
                sts128(ad, tv[m][0], tv[m][2], tv[m][4], tv[m][6]); sts128(ad + 512, tv[m][1], tv[m][3], tv[m][5], tv[m][7]);
              }
              fence_async_smem();
              bar_arrive(NB_KV + 12 * h, 288);
              if (h == 0) {
                bar_arrive(wg ? NB_HALO : NB_DONE, 160);
              }
              if (h == 0) { const float kn = max_norm(nrm); if (lane == 0) g_kn[((l >> 1) * 128 + bn * 8 + bm) * 16 + wg * 4 + w] = kn; }
              norm_half(h, QSCALE, q[h], nrm, h ? -1 : 3);
#pragma unroll
              for (int i = 0; i < 4 * h; i++) sts128(sb + QPARK + 24576 - wg * 8192 + (w * 32 + lane) * 16 + i * 2048, q[h][i >> 1][4 * (i & 1)], q[h][i >> 1][4 * (i & 1) + 1], q[h][i >> 1][4 * (i & 1) + 2], q[h][i >> 1][4 * (i & 1) + 3]);
              qn[h] = max_norm(nrm);
            }
          }
          constexpr uint64_t VSTEP = 64 - (64ull << 16);
          const uint32_t c_852 = 0x62A962A9u + (lane_id() & zero), c_lsb = 0x00010001u + (lane_id() & zero), c_half = 0x3F003F00u + (lane_id() & zero);
          float o[2][20], S[2][32];
          uint32_t H[2][16], P0[4] = {}, P1[4] = {};
#pragma unroll
          for (int m = 0; m < 2; m++) {
#pragma unroll
            for (int i = 0; i < 20; i++) o[m][i] = 0.f;
            fence_regs(o[m]);
          }
          auto qkf = [&](int b, int ks, uint64_t d) { wg_n64_rs_nb_f16_f32(S[b], q[0][0][4 * ks], q[0][0][4 * ks + 1], q[0][0][4 * ks + 2], q[0][0][4 * ks + 3], d + 2 * ks, ks ? 1 : zero); };
          auto qkh = [&](int b, int ks, uint64_t d) { wg_n64_rs_nb_f16_f16(H[b], q[0][1][4 * ks], q[0][1][4 * ks + 1], q[0][1][4 * ks + 2], q[0][1][4 * ks + 3], d + 2 * ks, ks ? 1 : zero); };
          auto pv0 = [&](uint64_t d) { wgmma_m64n40k16_rs_tb(o[0], P0[0], P0[1], P0[2], P0[3], d, 1); };
          auto pv1 = [&](uint64_t d) { wgmma_m64n40k16_rs_tb(o[1], P1[0], P1[1], P1[2], P1[3], d, 1); };
          float e[4] = {};
          auto finish = [&](int h) {
            const float* s = &S[(h >> 2) & 1][8 * (h & 3)];
            const uint32_t* u = &H[(h >> 2) & 1][4 * (h & 3)];
            const float z0 = exp2_fix(s[6]), z1 = exp2_fix(s[7]);
            P0[0] = pack2v(e[0], e[1]);
            P1[0] = exp2_h2(u[0], c_852);
            P0[1] = pack2v(e[2], e[3]);
            P1[1] = exp2_h2(u[1], c_852);
            const uint32_t B = exp2_base(z0, z1), E = and_or<0x7F807F80u>(B, c_lsb);
            P1[3] = exp2_h2(u[3], c_852);
            P0[3] = fma_bf2(B, and_or<0x807F807Fu>(B, c_half), E);
            const float e4 = ex2v(s[4]), e5 = ex2v(s[5]);
            P1[2] = exp2_h2(u[2], c_852);
            P0[2] = pack2v(e4, e5);
          };
          auto start = [&](int h) {
            const float* s = &S[(h >> 2) & 1][8 * (h & 3)];
            e[0] = ex2v(s[0]); e[1] = ex2v(s[1]); e[3] = ex2v(s[3]); e[2] = ex2v(s[2]);
          };
          uint64_t kd = prm.kv[0].kd;
          mbar_wait(sb + B_TF, 0);
#pragma unroll
          for (int i = 0; i < 4; i++) sts128(sb + QPARK + (wg * 128 + w * 32 + lane_id()) * 16 + i * 4096, q[0][i >> 1][4 * (i & 1)], q[0][i >> 1][4 * (i & 1) + 1], q[0][i >> 1][4 * (i & 1) + 2], q[0][i >> 1][4 * (i & 1) + 3]);
          wg_fence();
#pragma unroll
          for (int b = 0; b < 2; b++) {
            wg_n64_rs_nb_f16_f32_z(S[b], q[0][0][0], q[0][0][1], q[0][0][2], q[0][0][3], kd + 256 * b, 0);
            wg_n64_rs_nb_f16_f16_z(H[b], q[0][1][0], q[0][1][1], q[0][1][2], q[0][1][3], kd + 256 * b, 0);
            if (b == 0) { qkf(0, 1, kd); qkh(0, 1, kd); }
            wg_commit();
          }
          wg_wait<1>(); fence_regs(S[0]); fence_regs(H[0]);
          start(0); finish(0); start(1);
          wg_wait<0>();
          int redo = 0;
#pragma unroll 1
          for (int pass = 0, j = 1; pass < 2; pass++) {
#pragma unroll 1
           do {
            const uint64_t vd = prm.kv[j & 3].vd;
            bool go = false;
#pragma unroll
            for (int h = 2; h < 18; h++) {
              const int px = (h >> 2) + 1, c = h & 3;
              wg_fence();
              if (h == 13) kd = prm.kv[j & 3].kd;
              const uint64_t kx = kd + (px & 3) * 256, vx = vd + (h - 2) * VSTEP;
              if (h == 2) { qkh(1, 0, kx); qkf(1, 0, kx); pv0(vx); pv1(vx); qkh(1, 1, kx); qkf(1, 1, kx); }
              else if ((c == 1 || c == 2) && h < 17) { qkh(px & 1, c - 1, kx); pv1(vx); qkf(px & 1, c - 1, kx); pv0(vx); }
              else { pv0(vx); pv1(vx); }
              wg_commit();
              if (h == 3) e_arrive_if(sb + B_TE + 8 * ((j + 2) & 3), j > 1);
              if (h == 11) go = mbar_test(sb + B_TF + 8 * (j & 3), (j >> 2) & 1) && j != 8;
              finish(h - 1); start(h);
              if (h != 12 && h != 17) sched_fence();
              if (h == 12 && !go) {
                if (j == 16) {
#pragma unroll
                  for (int u = 13; u < 18; u++) {
                    wg_fence(); pv0(vd + (u - 2) * VSTEP); pv1(vd + (u - 2) * VSTEP); wg_commit();
                    if (u < 17) finish(u - 1);
                    if (u < 16) { start(u); sched_fence(); }
                    if (u & 1) { if (u == 17) wg_wait<0>(); else wg_wait<1>(); }
                  }
                  e_arrive(sb + B_TE + 24);
                  goto head_done;
                }
                mbar_wait(sb + B_TF + 8 * (j & 3), (j >> 2) & 1);
                if (j == 8) {
#pragma unroll
                  for (int i = 0; i < 4; i++) lds128(sb + QPARK + 24576 - wg * 8192 + (w * 32 + lane_id()) * 16 + i * 2048, &q[0][i >> 1][4 * (i & 1)]);
                }
              }
              if (h == 17) wg_wait<0>(); else if (h & 1) wg_wait<1>();
              if (c == 3) { fence_regs(S[px & 1]); fence_regs(H[px & 1]); }
            }
           } while (j++ & 7);
           head_done:
            fence_regs(o[0]); fence_regs(o[1]);
            uint32_t pk[2][8];
            {
              IDS();
              bf16* op = g_os + (size_t)(bm * 256 + row0 + (lane >> 2)) * 1024 + pass * 512 + bn * 32 + (lane & 3) * 8;
#pragma unroll
              for (int i = 0; i < 4; i++) {
                const float* a = &o[i >> 1][2 * (i & 1)];
                const float inv = rcp(a[16]);
                uint32_t* u = &pk[i >> 1][4 * (i & 1)];
#pragma unroll
                for (int k = 0; k < 4; k++) u[k] = pack2(a[4 * k] * inv, a[4 * k + 1] * inv);
                *(uint4*)(op + ((i >> 1) * 64 + (i & 1) * 8) * 1024) = make_uint4(u[0], u[1], u[2], u[3]);
              }
            }
            sched_fence();
            if (pass == 0) bar_sync(NB_KN + wg, 160);
            const float kmax = *(volatile float*)(smem + ROWST + 4 * pass);
            const bool wide = !(qn[0] <= 1.6e7f) | !(kmax <= 1.6e7f) | !(qn[0] * kmax <= 112.f * 112.f);
            int badm = 0;
#pragma unroll
            for (int m = 0; m < 2; m++) {
              uint32_t chk[2] = {0u, 0u};
#pragma unroll
              for (int i = 0; i < 8; i++) asm("fma.rn.bf16x2 %0, %1, %2, %0;" : "+r"(chk[i & 1]) : "r"(pk[m][i]), "r"(0u));
              const bool bad = wide | !(fminf(o[m][16], o[m][18]) >= 9.3e-10f) | !(o[m][16] + o[m][18] <= 1e36f) | (((chk[0] | chk[1]) & 0x7FFF7FFFu) != 0);
              badm |= __any_sync(~0u, bad) << m;
            }
            if (!badm) bar_arrive(NB_SIG + 2 * pass + wg, 160 + 32 * (pass & wg));
            qn[0] = qn[1];
#pragma unroll
            for (int m = 0; m < 2; m++) {
#pragma unroll
              for (int i = 0; i < 20; i++) o[m][i] = 0.f;
              fence_regs(o[m]);
            }
            if (badm) {
              redo |= badm << 2 * pass;
              const int tx = wg * 128 + w * 32 + lane_id();
              uint4* p = g_qsave + (block_id() * 256 + tx) * 8 + pass * 4;
#pragma unroll
              for (int i = 0; i < 4; i++) {
                uint32_t u[4] = {q[0][i >> 1][4 * (i & 1)], q[0][i >> 1][4 * (i & 1) + 1], q[0][i >> 1][4 * (i & 1) + 2], q[0][i >> 1][4 * (i & 1) + 3]};
                if (pass == 0) lds128(sb + QPARK + tx * 16 + i * 4096, u);
                p[i] = make_uint4(u[0], u[1], u[2], u[3]);
              }
            }
          }
          if (redo) attn_redo(redo, l, cta_id(), wg, w, ep1);
        }
      }
      {
        float acc[64];
#pragma unroll
        for (int i = 0; i < 64; i++) acc[i] = 0.f;
        fence_regs(acc);
        uint32_t s = 0, lap = 0;
#pragma unroll 1
        for (int kt = 0; kt < 16; kt++) {
          mbar_wait(sb + B_PF + 8 * s, ((s < 4 ? l : 0) + lap) & 1);
          const uint64_t da = mkdesc(sb + pslot_a(s, l) + wg * 8192, 16, 1024, 1), db = mkdesc(sb + pslot_b(s), 8192, 1024, 1);
          wg_fence();
#pragma unroll
          for (int k = 0; k < 4; k++) wgmma_m64n128k16_ss_tb(acc, da + k * 2, db + k * 128, 1);
          wg_commit();
          wg_wait<1>();
          if (kt > 0 && w == 0) e_arrive_both(sb + B_PE + 8 * (s ? s - 1 : 5));
          if (++s == 6) { s = 0; lap++; }
        }
        IDS();
        const int g = lane >> 2, qd = lane & 3;
        const int r0 = wg * 64 + w * 16;
        const uint32_t r = r0 + (lane & 7) + ((lane >> 3) & 1) * 8;
        uint32_t x[8][4];
        mbar_wait(sb + B_RF, l & 1);
#pragma unroll
        for (int jj = 0; jj < 8; jj++) ldsm4(sb + RES + (jj >> 2) * 16384 + r * 128 + ((((2 * jj + (lane >> 4)) & 7) ^ (r & 7)) << 4), x[jj]);
        wg_wait<0>();
        fence_regs(acc);
        if (w == 0) e_arrive_both(sb + B_PE + 8 * 3);
        const CUtensorMap* mo = &prm.m[l == 3 ? M_OUT : M_XST];
#pragma unroll
        for (int jj = 0; jj < 8; jj++) {
#pragma unroll
          for (int i = 0; i < 4; i++) x[jj][i] = add_bf16x2(x[jj][i], pack2(acc[8 * jj + 2 * i], acc[8 * jj + 2 * i + 1]));
          if (jj < 4) stsm4(sb + RES + r * 128 + ((((2 * jj + (lane >> 4)) & 7) ^ (r & 7)) << 4), x[jj][0], x[jj][1], x[jj][2], x[jj][3]);
          if (jj == 3) { fence_async_smem(); __syncwarp(); tma_st(mo, pn * 128, pm * 128 + r0, sb + RES + r0 * 128); bulk_commit(); sched_fence(); }
        }
        if (l == 3) {
#pragma unroll
          for (int jj = 4; jj < 8; jj++) stsm4(sb + RES + 16384 + r * 128 + ((((2 * jj + (lane >> 4)) & 7) ^ (r & 7)) << 4), x[jj][0], x[jj][1], x[jj][2], x[jj][3]);
          fence_async_smem(); __syncwarp();
          tma_st(mo, pn * 128 + 64, pm * 128 + r0, sb + RES + 16384 + r0 * 128);
          bulk_commit(); bulk_wait_n<0>();
        } else {
          bar_sync(NB_SC, 256);
#pragma unroll
          for (int jj = 0; jj < 8; jj++)
            stsm4(sb + (jj >> 2) * QSTG + po * 16384 + r * 128 + ((((2 * jj + (lane >> 4)) & 7) ^ (r & 7)) << 4), x[jj][0], x[jj][1], x[jj][2], x[jj][3]);
          bulk_wait_n<0>();
          bar_arrive(NB_X0, 288);
          fence_async_smem();
          bar_arrive(NB_X, 320);
          float s1[4] = {0.f, 0.f, 0.f, 0.f}, sa[4] = {0.f, 0.f, 0.f, 0.f}, sc[4] = {0.f, 0.f, 0.f, 0.f};
#pragma unroll
          for (int jj = 0; jj < 8; jj++) {
            mma16816(s1, x[jj][0], x[jj][1], x[jj][2], x[jj][3], 0x3f803f80u, 0x3f803f80u);
            mma16816(sa, x[jj][0], x[jj][1], x[jj][2], x[jj][3], x[jj][0], x[jj][2]);
            mma16816(sc, x[jj][0], x[jj][1], x[jj][2], x[jj][3], x[jj][1], x[jj][3]);
          }
          if (qd == g >> 1) {
            float2* p = g_stats + pn * 2048 + pm * 128 + r0 + g;
            p[0] = make_float2(s1[0], g & 1 ? sa[1] : sa[0]);
            p[8] = make_float2(s1[2], g & 1 ? sc[3] : sc[2]);
          }
          bar_arrive(NB_KV, 288);
        }
      }
    }
  }
  asm volatile("barrier.cluster.arrive.relaxed.aligned;\nbarrier.cluster.wait.aligned;" ::: "memory");
}

typedef CUresult (*EncodeFn)(CUtensorMap*, CUtensorMapDataType, cuuint32_t, void*, const cuuint64_t*, const cuuint64_t*, const cuuint32_t*,
                             const cuuint32_t*, CUtensorMapInterleave, CUtensorMapSwizzle, CUtensorMapL2promotion, CUtensorMapFloatOOBfill);

static void make_map(EncodeFn fn, CUtensorMap* m, const void* ptr, int rank, const uint64_t* dims, const uint64_t* strides, const uint32_t* box, CUtensorMapSwizzle sw) {
  cuuint64_t d[5], st[4];
  cuuint32_t bx[5], es[5];
  for (int i = 0; i < rank; i++) { d[i] = dims[i]; bx[i] = box[i]; es[i] = 1; if (i) st[i - 1] = strides[i - 1] * 2; }
  fn(m, CU_TENSOR_MAP_DATA_TYPE_BFLOAT16, rank, (void*)ptr, d, st, bx, es, CU_TENSOR_MAP_INTERLEAVE_NONE, sw,
     CU_TENSOR_MAP_L2_PROMOTION_L2_128B, CU_TENSOR_MAP_FLOAT_OOB_FILL_NONE);
}
static void map2(EncodeFn fn, CUtensorMap* m, const void* ptr, uint64_t inner, uint64_t outer, uint32_t bi, uint32_t bo, CUtensorMapSwizzle sw) {
  const uint64_t d[2] = {inner, outer}, st[1] = {inner};
  const uint32_t bx[2] = {bi, bo};
  make_map(fn, m, ptr, 2, d, st, bx, sw);
}

extern "C" void kernel_launch(void* const* d_in, const int* in_sizes, int n_in, void* d_out, int out_size) {
  (void)in_sizes; (void)n_in; (void)out_size;
  static EncodeFn enc = nullptr;
  static void *xs, *os, *kk, *vv;
  static int sbase = 1024;
  if (!enc) {
    void* p = nullptr;
    cudaDriverEntryPointQueryResult qr;
    cudaGetDriverEntryPoint("cuTensorMapEncodeTiled", &p, cudaEnableDefault, &qr);
    enc = (EncodeFn)p;
    Scratch* sc = nullptr;
    cudaGetSymbolAddress((void**)&sc, g_s);
    xs = sc->xs; os = sc->os; kk = sc->k; vv = sc->v;
    int dev = 0;
    cudaGetDevice(&dev);
    cudaDeviceGetAttribute(&sbase, cudaDevAttrReservedSharedMemoryPerBlock, dev);
    cudaFuncSetAttribute(fused_kernel, cudaFuncAttributeMaxDynamicSharedMemorySize, SMEM_BYTES);
  }
  Params prm;
  const CUtensorMapSwizzle S128 = CU_TENSOR_MAP_SWIZZLE_128B, S64 = CU_TENSOR_MAP_SWIZZLE_64B;
  map2(enc, &prm.m[M_X0A], d_in[0], 1024, 2048, 64, 256, S128);
  map2(enc, &prm.m[M_XSA], xs, 1024, 2048, 64, 256, S128);
  for (int t = 0; t < 2; t++) {
    const uint64_t d3[3] = {1024, 1024, 3}, s3[2] = {3072, 1024};
    const uint32_t b3[3] = {64, 64, 3};
    make_map(enc, &prm.m[M_WQA + t], d_in[1 + 3 * t], 3, d3, s3, b3, S128);
    const uint64_t d5[5] = {64, 32, 2, 16, 16}, s5[4] = {1024, 32 * 1024, 64 * 1024, 64};
    const uint32_t b5[5] = {64, 32, 1, 2, 2};
    make_map(enc, &prm.m[M_WOA + t], d_in[2 + 3 * t], 5, d5, s5, b5, S128);
    const uint64_t dr[3] = {64, 2048, 16}, sr[2] = {1024, 64};
    const uint32_t br[3] = {64, 128, 2};
    make_map(enc, &prm.m[M_X0R + t], t ? xs : d_in[0], 3, dr, sr, br, S128);
  }
  map2(enc, &prm.m[M_OS], os, 1024, 2048, 64, 64, S128);
  map2(enc, &prm.m[M_K], kk, 32, 65536, 32, 128, S64);
  map2(enc, &prm.m[M_V], vv, 32, 65536, 32, 128, S64);
  map2(enc, &prm.m[M_XSO], xs, 1024, 2048, 64, 128, S128);
  map2(enc, &prm.m[M_X0H], d_in[0], 1024, 2048, 64, 128, S128);
  map2(enc, &prm.m[M_XST], xs, 1024, 2048, 64, 16, S128);
  map2(enc, &prm.m[M_OUT], d_out, 1024, 2048, 64, 16, S128);
  prm.x0 = (const bf16*)d_in[0];
  prm.wq[0] = (const bf16*)d_in[1]; prm.wq[1] = (const bf16*)d_in[4];
  prm.zero = 0;
  for (int i = 0; i < 128; i++) prm.map[i] = remap(i);
  {
    const uint64_t hi = 0x80000020ull << 32, k0 = sbase + T0, v0 = k0 + 16384, vstep = 64 - (64ull << 16);
    prm.wd = mkdesc(sbase + 32768, 8192, 1024, 1); prm.xd = mkdesc(sbase, 16, 1024, 1);
    for (int j = 0; j < 4; j++) {
      prm.kv[j].kd = (hi | 1u << 16 | k0 >> 4) + 2048 * ((j < 16 ? j : 15) & 3);
      prm.kv[j].vd = (hi | (uint64_t)(ONES - T0 - 16384) >> 4 << 16 | v0 >> 4) + 32 * vstep * ((j + 3) & 3);
    }
  }
  fused_kernel<<<128, 384, SMEM_BYTES>>>(prm);
}
```

```cpp
#include <cuda_runtime.h>
#include <cuda_bf16.h>
#include <cuda.h>
#include <stdint.h>

typedef __nv_bfloat16 bf16;

__device__ __forceinline__ void wgmma_m64n192k16_ss_tb(float (&d)[96], uint64_t da, uint64_t db, int scale_d) {
  asm volatile("{\n.reg .pred p;\nsetp.ne.b32 p, %98, 0;\n"
    "wgmma.mma_async.sync.aligned.m64n192k16.f32.bf16.bf16 "
    "{%0, %1, %2, %3, %4, %5, %6, %7, %8, %9, %10, %11, %12, %13, %14, %15, "
    "%16, %17, %18, %19, %20, %21, %22, %23, %24, %25, %26, %27, %28, %29, %30, %31, "
    "%32, %33, %34, %35, %36, %37, %38, %39, %40, %41, %42, %43, %44, %45, %46, %47, "
    "%48, %49, %50, %51, %52, %53, %54, %55, %56, %57, %58, %59, %60, %61, %62, %63, "
    "%64, %65, %66, %67, %68, %69, %70, %71, %72, %73, %74, %75, %76, %77, %78, %79, "
    "%80, %81, %82, %83, %84, %85, %86, %87, %88, %89, %90, %91, %92, %93, %94, %95}, "
    "%96, %97, p, 1, 1, 0, 1;\n}\n"
    : "+f"(d[0]), "+f"(d[1]), "+f"(d[2]), "+f"(d[3]), "+f"(d[4]), "+f"(d[5]), "+f"(d[6]), "+f"(d[7]),
      "+f"(d[8]), "+f"(d[9]), "+f"(d[10]), "+f"(d[11]), "+f"(d[12]), "+f"(d[13]), "+f"(d[14]), "+f"(d[15]),
      "+f"(d[16]), "+f"(d[17]), "+f"(d[18]), "+f"(d[19]), "+f"(d[20]), "+f"(d[21]), "+f"(d[22]), "+f"(d[23]),
      "+f"(d[24]), "+f"(d[25]), "+f"(d[26]), "+f"(d[27]), "+f"(d[28]), "+f"(d[29]), "+f"(d[30]), "+f"(d[31]),
      "+f"(d[32]), "+f"(d[33]), "+f"(d[34]), "+f"(d[35]), "+f"(d[36]), "+f"(d[37]), "+f"(d[38]), "+f"(d[39]),
      "+f"(d[40]), "+f"(d[41]), "+f"(d[42]), "+f"(d[43]), "+f"(d[44]), "+f"(d[45]), "+f"(d[46]), "+f"(d[47]),
      "+f"(d[48]), "+f"(d[49]), "+f"(d[50]), "+f"(d[51]), "+f"(d[52]), "+f"(d[53]), "+f"(d[54]), "+f"(d[55]),
      "+f"(d[56]), "+f"(d[57]), "+f"(d[58]), "+f"(d[59]), "+f"(d[60]), "+f"(d[61]), "+f"(d[62]), "+f"(d[63]),
      "+f"(d[64]), "+f"(d[65]), "+f"(d[66]), "+f"(d[67]), "+f"(d[68]), "+f"(d[69]), "+f"(d[70]), "+f"(d[71]),
      "+f"(d[72]), "+f"(d[73]), "+f"(d[74]), "+f"(d[75]), "+f"(d[76]), "+f"(d[77]), "+f"(d[78]), "+f"(d[79]),
      "+f"(d[80]), "+f"(d[81]), "+f"(d[82]), "+f"(d[83]), "+f"(d[84]), "+f"(d[85]), "+f"(d[86]), "+f"(d[87]),
      "+f"(d[88]), "+f"(d[89]), "+f"(d[90]), "+f"(d[91]), "+f"(d[92]), "+f"(d[93]), "+f"(d[94]), "+f"(d[95])
    : "l"(da), "l"(db), "r"(scale_d));
}

__device__ __forceinline__ void wgmma_m64n128k16_ss_tb(float (&d)[64], uint64_t da, uint64_t db, int scale_d) {
  asm volatile("{\n.reg .pred p;\nsetp.ne.b32 p, %66, 0;\n"
    "wgmma.mma_async.sync.aligned.m64n128k16.f32.bf16.bf16 "
    "{%0, %1, %2, %3, %4, %5, %6, %7, %8, %9, %10, %11, %12, %13, %14, %15, "
    "%16, %17, %18, %19, %20, %21, %22, %23, %24, %25, %26, %27, %28, %29, %30, %31, "
    "%32, %33, %34, %35, %36, %37, %38, %39, %40, %41, %42, %43, %44, %45, %46, %47, "
    "%48, %49, %50, %51, %52, %53, %54, %55, %56, %57, %58, %59, %60, %61, %62, %63}, "
    "%64, %65, p, 1, 1, 0, 1;\n}\n"
    : "+f"(d[0]), "+f"(d[1]), "+f"(d[2]), "+f"(d[3]), "+f"(d[4]), "+f"(d[5]), "+f"(d[6]), "+f"(d[7]),
      "+f"(d[8]), "+f"(d[9]), "+f"(d[10]), "+f"(d[11]), "+f"(d[12]), "+f"(d[13]), "+f"(d[14]), "+f"(d[15]),
      "+f"(d[16]), "+f"(d[17]), "+f"(d[18]), "+f"(d[19]), "+f"(d[20]), "+f"(d[21]), "+f"(d[22]), "+f"(d[23]),
      "+f"(d[24]), "+f"(d[25]), "+f"(d[26]), "+f"(d[27]), "+f"(d[28]), "+f"(d[29]), "+f"(d[30]), "+f"(d[31]),
      "+f"(d[32]), "+f"(d[33]), "+f"(d[34]), "+f"(d[35]), "+f"(d[36]), "+f"(d[37]), "+f"(d[38]), "+f"(d[39]),
      "+f"(d[40]), "+f"(d[41]), "+f"(d[42]), "+f"(d[43]), "+f"(d[44]), "+f"(d[45]), "+f"(d[46]), "+f"(d[47]),
      "+f"(d[48]), "+f"(d[49]), "+f"(d[50]), "+f"(d[51]), "+f"(d[52]), "+f"(d[53]), "+f"(d[54]), "+f"(d[55]),
      "+f"(d[56]), "+f"(d[57]), "+f"(d[58]), "+f"(d[59]), "+f"(d[60]), "+f"(d[61]), "+f"(d[62]), "+f"(d[63])
    : "l"(da), "l"(db), "r"(scale_d));
}

__device__ __forceinline__ void wgmma_m64n40k16_rs_tb(float (&d)[20], uint32_t a0, uint32_t a1, uint32_t a2, uint32_t a3, uint64_t db, int scale_d) {
  asm volatile("{\n.reg .pred p;\nsetp.ne.b32 p, %25, 0;\n"
    "wgmma.mma_async.sync.aligned.m64n40k16.f32.bf16.bf16 "
    "{%0, %1, %2, %3, %4, %5, %6, %7, %8, %9, %10, %11, %12, %13, %14, %15, "
    "%16, %17, %18, %19}, "
    "{%20, %21, %22, %23}, %24, p, 1, 1, 1;\n}\n"
    : "+f"(d[0]), "+f"(d[1]), "+f"(d[2]), "+f"(d[3]), "+f"(d[4]), "+f"(d[5]), "+f"(d[6]), "+f"(d[7]),
      "+f"(d[8]), "+f"(d[9]), "+f"(d[10]), "+f"(d[11]), "+f"(d[12]), "+f"(d[13]), "+f"(d[14]), "+f"(d[15]),
      "+f"(d[16]), "+f"(d[17]), "+f"(d[18]), "+f"(d[19])
    : "r"(a0), "r"(a1), "r"(a2), "r"(a3), "l"(db), "r"(scale_d));
}

__device__ __forceinline__ void wg_n64_rs_nb_f16_f32(float (&d)[32], uint32_t a0, uint32_t a1, uint32_t a2, uint32_t a3, uint64_t db, int scale_d) {
  asm volatile("{\n.reg .pred p;\nsetp.ne.b32 p, %37, 0;\n"
    "wgmma.mma_async.sync.aligned.m64n64k16.f32.f16.f16 "
    "{%0, %1, %2, %3, %4, %5, %6, %7, %8, %9, %10, %11, %12, %13, %14, %15, "
    "%16, %17, %18, %19, %20, %21, %22, %23, %24, %25, %26, %27, %28, %29, %30, %31}, "
    "{%32, %33, %34, %35}, %36, p, 1, 1, 0;\n}\n"
    : "+f"(d[0]), "+f"(d[1]), "+f"(d[2]), "+f"(d[3]), "+f"(d[4]), "+f"(d[5]), "+f"(d[6]), "+f"(d[7]),
      "+f"(d[8]), "+f"(d[9]), "+f"(d[10]), "+f"(d[11]), "+f"(d[12]), "+f"(d[13]), "+f"(d[14]), "+f"(d[15]),
      "+f"(d[16]), "+f"(d[17]), "+f"(d[18]), "+f"(d[19]), "+f"(d[20]), "+f"(d[21]), "+f"(d[22]), "+f"(d[23]),
      "+f"(d[24]), "+f"(d[25]), "+f"(d[26]), "+f"(d[27]), "+f"(d[28]), "+f"(d[29]), "+f"(d[30]), "+f"(d[31])
    : "r"(a0), "r"(a1), "r"(a2), "r"(a3), "l"(db), "r"(scale_d));
}

__device__ __forceinline__ void wg_n64_rs_nb_f16_f16(uint32_t (&d)[16], uint32_t a0, uint32_t a1, uint32_t a2, uint32_t a3, uint64_t db, int scale_d) {
  asm volatile("{\n.reg .pred p;\nsetp.ne.b32 p, %21, 0;\n"
    "wgmma.mma_async.sync.aligned.m64n64k16.f16.f16.f16 "
    "{%0, %1, %2, %3, %4, %5, %6, %7, %8, %9, %10, %11, %12, %13, %14, %15}, "
    "{%16, %17, %18, %19}, %20, p, 1, 1, 0;\n}\n"
    : "+r"(d[0]), "+r"(d[1]), "+r"(d[2]), "+r"(d[3]), "+r"(d[4]), "+r"(d[5]), "+r"(d[6]), "+r"(d[7]),
      "+r"(d[8]), "+r"(d[9]), "+r"(d[10]), "+r"(d[11]), "+r"(d[12]), "+r"(d[13]), "+r"(d[14]), "+r"(d[15])
    : "r"(a0), "r"(a1), "r"(a2), "r"(a3), "l"(db), "r"(scale_d));
}

__device__ __forceinline__ void wg_n64_rs_nb_f16_f32_z(float (&d)[32], uint32_t a0, uint32_t a1, uint32_t a2, uint32_t a3, uint64_t db, int scale_d) {
  asm volatile("{\n.reg .pred p;\nsetp.ne.b32 p, %37, 0;\n"
    "wgmma.mma_async.sync.aligned.m64n64k16.f32.f16.f16 "
    "{%0, %1, %2, %3, %4, %5, %6, %7, %8, %9, %10, %11, %12, %13, %14, %15, "
    "%16, %17, %18, %19, %20, %21, %22, %23, %24, %25, %26, %27, %28, %29, %30, %31}, "
    "{%32, %33, %34, %35}, %36, p, 1, 1, 0;\n}\n"
    : "=f"(d[0]), "=f"(d[1]), "=f"(d[2]), "=f"(d[3]), "=f"(d[4]), "=f"(d[5]), "=f"(d[6]), "=f"(d[7]),
      "=f"(d[8]), "=f"(d[9]), "=f"(d[10]), "=f"(d[11]), "=f"(d[12]), "=f"(d[13]), "=f"(d[14]), "=f"(d[15]),
      "=f"(d[16]), "=f"(d[17]), "=f"(d[18]), "=f"(d[19]), "=f"(d[20]), "=f"(d[21]), "=f"(d[22]), "=f"(d[23]),
      "=f"(d[24]), "=f"(d[25]), "=f"(d[26]), "=f"(d[27]), "=f"(d[28]), "=f"(d[29]), "=f"(d[30]), "=f"(d[31])
    : "r"(a0), "r"(a1), "r"(a2), "r"(a3), "l"(db), "r"(scale_d));
}

__device__ __forceinline__ void wg_n64_rs_nb_f16_f16_z(uint32_t (&d)[16], uint32_t a0, uint32_t a1, uint32_t a2, uint32_t a3, uint64_t db, int scale_d) {
  asm volatile("{\n.reg .pred p;\nsetp.ne.b32 p, %21, 0;\n"
    "wgmma.mma_async.sync.aligned.m64n64k16.f16.f16.f16 "
    "{%0, %1, %2, %3, %4, %5, %6, %7, %8, %9, %10, %11, %12, %13, %14, %15}, "
    "{%16, %17, %18, %19}, %20, p, 1, 1, 0;\n}\n"
    : "=r"(d[0]), "=r"(d[1]), "=r"(d[2]), "=r"(d[3]), "=r"(d[4]), "=r"(d[5]), "=r"(d[6]), "=r"(d[7]),
      "=r"(d[8]), "=r"(d[9]), "=r"(d[10]), "=r"(d[11]), "=r"(d[12]), "=r"(d[13]), "=r"(d[14]), "=r"(d[15])
    : "r"(a0), "r"(a1), "r"(a2), "r"(a3), "l"(db), "r"(scale_d));
}

#define DEVINL __device__ __forceinline__
DEVINL void wg_fence() { asm volatile("wgmma.fence.sync.aligned;" ::: "memory"); }
DEVINL void wg_commit() { asm volatile("wgmma.commit_group.sync.aligned;" ::: "memory"); }
template <int N> DEVINL void wg_wait() { asm volatile("wgmma.wait_group.sync.aligned %0;" ::"n"(N) : "memory"); }
__host__ DEVINL uint64_t mkdesc(uint32_t addr, uint32_t lbo, uint32_t sbo, int sw) {
  return (uint64_t)((addr & 0x3FFFF) >> 4) | ((uint64_t)(lbo >> 4) << 16) | ((uint64_t)(sbo >> 4) << 32) | ((uint64_t)sw << 62);
}
DEVINL void mbar_init(uint32_t bar, uint32_t cnt) { asm volatile("mbarrier.init.shared::cta.b64 [%0], %1;" ::"r"(bar), "r"(cnt) : "memory"); }
DEVINL void mbar_arrive(uint32_t bar) { asm volatile("mbarrier.arrive.shared::cta.b64 _, [%0];" ::"r"(bar) : "memory"); }
DEVINL bool mbar_try(uint32_t bar, uint32_t parity) {
  uint32_t ok;
  asm volatile("{\n.reg .pred p;\nmbarrier.try_wait.parity.shared::cta.b64 p, [%1], %2;\nselp.u32 %0, 1, 0, p;\n}" : "=r"(ok) : "r"(bar), "r"(parity) : "memory");
  return ok;
}
DEVINL bool mbar_test(uint32_t bar, uint32_t parity) {
  uint32_t ok;
  asm volatile("{\n.reg .pred p;\nmbarrier.test_wait.parity.shared::cta.b64 p, [%1], %2;\nselp.u32 %0, 1, 0, p;\n}" : "=r"(ok) : "r"(bar), "r"(parity) : "memory");
  return ok;
}
DEVINL void mbar_wait(uint32_t bar, uint32_t parity) {
#pragma unroll 1
  for (uint32_t n = 0; n < 100000u; n++) if (mbar_try(bar, parity)) break;
}
#define EL(txt) "{\n.reg .pred pe;\nelect.sync _|pe, 0xffffffff;\n@pe " txt "\n}"
DEVINL void e_expect_tx(uint32_t bar, uint32_t bytes) { asm volatile(EL("mbarrier.arrive.expect_tx.shared::cta.b64 _, [%0], %1;") ::"r"(bar), "r"(bytes) : "memory"); }
DEVINL void e_arrive(uint32_t bar) { asm volatile(EL("mbarrier.arrive.shared::cta.b64 _, [%0];") ::"r"(bar) : "memory"); }
DEVINL void e_arrive_if(uint32_t bar, int c) {
  asm volatile("{\n.reg .pred pe;\nelect.sync _|pe, 0xffffffff;\nsetp.ne.and.b32 pe, %1, 0, pe;\n@pe mbarrier.arrive.shared::cta.b64 _, [%0];\n}" ::"r"(bar), "r"(c) : "memory");
}
DEVINL void e_red(uint32_t* p) { asm volatile(EL("red.release.gpu.global.add.u32 [%0], 1;") ::"l"(p) : "memory"); }
DEVINL void e_red_relaxed(uint32_t* p) { asm volatile(EL("red.relaxed.gpu.global.add.u32 [%0], 1;") ::"l"(p) : "memory"); }
DEVINL void release_add(uint32_t* p, int on) {
  asm volatile("{\n.reg .pred q;\nsetp.ne.b32 q, %1, 0;\nfence.release.gpu;\n@q red.relaxed.gpu.global.add.u32 [%0], 1;\n}" ::"l"(p), "r"(on) : "memory");
}
#define PREPARED(p, on) do { asm volatile("" : "+l"(p), "+r"(on)); asm volatile("griddepcontrol.launch_dependents;" ::: "memory"); } while (0)
DEVINL void tma_ld(uint32_t dst, const CUtensorMap* m, int c0, int c1, uint32_t bar) {
  asm volatile(EL("cp.async.bulk.tensor.2d.shared::cluster.global.mbarrier::complete_tx::bytes [%0], [%1, {%3, %4}], [%2];")
               ::"r"(dst), "l"(m), "r"(bar), "r"(c0), "r"(c1) : "memory");
}
DEVINL void tma_ld3(uint32_t dst, const CUtensorMap* m, int c0, int c1, int c2, uint32_t bar) {
  asm volatile(EL("cp.async.bulk.tensor.3d.shared::cluster.global.mbarrier::complete_tx::bytes [%0], [%1, {%3, %4, %5}], [%2];")
               ::"r"(dst), "l"(m), "r"(bar), "r"(c0), "r"(c1), "r"(c2) : "memory");
}
DEVINL void tma_ld5(uint32_t dst, const CUtensorMap* m, int c2, int c3, int c4, uint32_t bar) {
  asm volatile(EL("cp.async.bulk.tensor.5d.shared::cluster.global.mbarrier::complete_tx::bytes [%0], [%1, {0, 0, %3, %4, %5}], [%2];")
               ::"r"(dst), "l"(m), "r"(bar), "r"(c2), "r"(c3), "r"(c4) : "memory");
}
DEVINL void tma_ld_mc(uint32_t dst, const CUtensorMap* m, int c0, int c1, uint32_t bar) {
  asm volatile(EL("cp.async.bulk.tensor.2d.shared::cluster.global.mbarrier::complete_tx::bytes.multicast::cluster [%0], [%1, {%3, %4}], [%2], %5;")
               ::"r"(dst), "l"(m), "r"(bar), "r"(c0), "r"(c1), "h"((uint16_t)3) : "memory");
}
DEVINL void e_arrive_both(uint32_t bar) {
  asm volatile("{\n.reg .pred pe;\n.reg .b32 r0, r1;\nelect.sync _|pe, 0xffffffff;\nmapa.shared::cluster.u32 r0, %0, 0;\nmapa.shared::cluster.u32 r1, %0, 1;\n"
               "@pe mbarrier.arrive.shared::cluster.b64 _, [r0];\n@pe mbarrier.arrive.shared::cluster.b64 _, [r1];\n}" ::"r"(bar) : "memory");
}
DEVINL void tma_st(const CUtensorMap* m, int c0, int c1, uint32_t src) {
  asm volatile(EL("cp.async.bulk.tensor.2d.global.shared::cta.bulk_group [%0, {%2, %3}], [%1];") ::"l"(m), "r"(src), "r"(c0), "r"(c1) : "memory");
}
DEVINL void bulk_commit() { asm volatile("cp.async.bulk.commit_group;" ::: "memory"); }
template <int N> DEVINL void bulk_wait_n() { asm volatile("cp.async.bulk.wait_group %0;\nbar.warp.sync 0xffffffff;" ::"n"(N) : "memory"); }
DEVINL void l2_prefetch(const void* g, uint32_t bytes) { asm volatile(EL("cp.async.bulk.prefetch.L2.global [%0], %1;") ::"l"(g), "r"(bytes) : "memory"); }
DEVINL void fence_async_smem() { asm volatile("fence.proxy.async.shared::cta;" ::: "memory"); }
DEVINL void fence_async_gl() { asm volatile("fence.proxy.async.global;" ::: "memory"); }
DEVINL void cluster_wait() { asm volatile("barrier.cluster.wait.aligned;" ::: "memory"); }
DEVINL void bar_sync(int id, int n) { asm volatile("bar.sync %0, %1;" ::"r"(id), "r"(n) : "memory"); }
DEVINL void bar_arrive(int id, int n) { asm volatile("bar.arrive %0, %1;" ::"r"(id), "r"(n) : "memory"); }
DEVINL uint32_t ld_acquire(const uint32_t* p) { uint32_t v; asm volatile("ld.acquire.gpu.global.u32 %0, [%1];" : "=r"(v) : "l"(p) : "memory"); return v; }
DEVINL void await_flag(int j, uint32_t& rdy, const uint32_t* p, uint32_t target) {
  if ((rdy >> j) & 1) return;
#pragma unroll 1
  for (uint32_t n = 0; n < 200000u && !((rdy >> j) & 1); n++) rdy = __ballot_sync(~0u, (int)(ld_acquire(p) - target) >= 0);
  asm volatile("fence.proxy.async.global;" ::: "memory");
}
DEVINL void poll_ge(const uint32_t* p, uint32_t target) {
#pragma unroll 1
  for (uint32_t n = 0; n < 200000u; n++) if (__all_sync(~0u, (int)(ld_acquire(p) - target) >= 0)) break;
}
DEVINL int lane_id() { int v; asm volatile("mov.u32 %0, %%laneid;" : "=r"(v)); return v; }
__host__ DEVINL int remap(int v) {
  const int c = v >> 1, u = c - 36, r = (u * 37) >> 8;
  const int L = c < 4 ? 32 + 8 * c : c < 36 ? c - 4 : 33 + u + r;
  return 2 * L + (v & 1);
}
DEVINL int block_id() { int v; asm volatile("mov.u32 %0, %%ctaid.x;" : "=r"(v)); return v; }
#define cta_id() prm.map[block_id()]
#define IDS() const int lane = lane_id(), b = cta_id(), bm = b >> 4, bn = b & 15, rank = b & 1, pm = 2 * bm + (bn >> 3), pn = bn & 7, po = pm & 1; \
  (void)lane; (void)bm; (void)bn; (void)rank; (void)pm; (void)pn; (void)po
DEVINL void st_tagged(uint4* p, uint32_t a, uint32_t b, uint32_t c, uint32_t tag) {
  asm volatile("{\n.reg .b64 u, v;\n.reg .b128 t;\nmov.b64 u, {%1, %2};\nmov.b64 v, {%3, %4};\nmov.b128 t, {u, v};\nst.relaxed.gpu.global.b128 [%0], t;\n}"
               ::"l"(p), "r"(a), "r"(b), "r"(c), "r"(tag) : "memory");
}
DEVINL uint32_t ld_tagged(const uint4* p, uint32_t* r) {
  uint32_t tag;
  asm volatile("{\n.reg .b64 u, v;\n.reg .b128 t;\nld.relaxed.gpu.global.b128 t, [%4];\nmov.b128 {u, v}, t;\nmov.b64 {%0, %1}, u;\nmov.b64 {%2, %3}, v;\n}"
               : "=r"(r[0]), "=r"(r[1]), "=r"(r[2]), "=r"(tag) : "l"(p) : "memory");
  return tag;
}
DEVINL float ex2(float x) { float y; asm("ex2.approx.ftz.f32 %0, %1;" : "=f"(y) : "f"(x)); return y; }
DEVINL float rcp(float x) { float y; asm("rcp.approx.ftz.f32 %0, %1;" : "=f"(y) : "f"(x)); return y; }
DEVINL uint32_t pack2(float lo, float hi) { uint32_t r; asm("cvt.rn.bf16x2.f32 %0, %1, %2;" : "=r"(r) : "f"(hi), "f"(lo)); return r; }
DEVINL uint32_t pack2h(float lo, float hi) { uint32_t r; asm("cvt.rz.f16x2.f32 %0, %1, %2;" : "=r"(r) : "f"(hi), "f"(lo)); return r; }
DEVINL uint32_t prmt0(uint32_t a, uint32_t sel) { uint32_t r; asm("prmt.b32 %0, %1, 0, %2;" : "=r"(r) : "r"(a), "r"(sel)); return r; }
DEVINL void stg128(const void* p, uint32_t a, uint32_t b, uint32_t c, uint32_t d) {
  asm volatile("st.global.v4.b32 [%0], {%1, %2, %3, %4};" ::"l"(p), "r"(a), "r"(b), "r"(c), "r"(d) : "memory");
}
DEVINL float bf_lo(uint32_t w) { return __uint_as_float(w << 16); }
DEVINL float bf_hi(uint32_t w) { return __uint_as_float(w & 0xFFFF0000u); }
DEVINL float bf_round(float x) { return bf_lo(pack2(x, 0.f)); }
DEVINL uint32_t add_bf16x2(uint32_t a, uint32_t b) { uint32_t r; asm("add.rn.bf16x2 %0, %1, %2;" : "=r"(r) : "r"(a), "r"(b)); return r; }
DEVINL void stsm4(uint32_t addr, uint32_t a, uint32_t b, uint32_t c, uint32_t d) {
  asm volatile("stmatrix.sync.aligned.m8n8.x4.shared.b16 [%0], {%1, %2, %3, %4};" ::"r"(addr), "r"(a), "r"(b), "r"(c), "r"(d) : "memory");
}
DEVINL void ldsm4(uint32_t addr, uint32_t (&r)[4]) {
  asm volatile("ldmatrix.sync.aligned.m8n8.x4.shared.b16 {%0, %1, %2, %3}, [%4];" : "=r"(r[0]), "=r"(r[1]), "=r"(r[2]), "=r"(r[3]) : "r"(addr) : "memory");
}
DEVINL void ldsm4t(uint32_t addr, uint32_t (&r)[4]) {
  asm volatile("ldmatrix.sync.aligned.m8n8.x4.trans.shared.b16 {%0, %1, %2, %3}, [%4];" : "=r"(r[0]), "=r"(r[1]), "=r"(r[2]), "=r"(r[3]) : "r"(addr) : "memory");
}
DEVINL void sts128(uint32_t addr, uint32_t a, uint32_t b, uint32_t c, uint32_t d) {
  asm volatile("st.shared.v4.b32 [%0], {%1, %2, %3, %4};" ::"r"(addr), "r"(a), "r"(b), "r"(c), "r"(d) : "memory");
}
DEVINL float2 lds64f(uint32_t addr) { float2 v; asm volatile("ld.shared.v2.f32 {%0, %1}, [%2];" : "=f"(v.x), "=f"(v.y) : "r"(addr) : "memory"); return v; }
DEVINL void mma16816(float (&d)[4], uint32_t a0, uint32_t a1, uint32_t a2, uint32_t a3, uint32_t b0, uint32_t b1) {
  asm("mma.sync.aligned.m16n8k16.row.col.f32.bf16.bf16.f32 {%0, %1, %2, %3}, {%4, %5, %6, %7}, {%8, %9}, {%0, %1, %2, %3};"
               : "+f"(d[0]), "+f"(d[1]), "+f"(d[2]), "+f"(d[3]) : "r"(a0), "r"(a1), "r"(a2), "r"(a3), "r"(b0), "r"(b1));
}
template <int N> DEVINL void fence_regs(float (&d)[N]) {
#pragma unroll
  for (int i = 0; i < N; i++) asm volatile("" : "+f"(d[i])::"memory");
}
template <int N> DEVINL void fence_regs(uint32_t (&d)[N]) {
#pragma unroll
  for (int i = 0; i < N; i++) asm volatile("" : "+r"(d[i])::"memory");
}
DEVINL void lds128(uint32_t addr, uint32_t* r) {
  asm volatile("ld.shared.v4.b32 {%0, %1, %2, %3}, [%4];" : "=r"(r[0]), "=r"(r[1]), "=r"(r[2]), "=r"(r[3]) : "r"(addr) : "memory");
}
DEVINL void sched_fence() { asm volatile("griddepcontrol.launch_dependents;" ::: "memory"); }

struct Scratch {
  bf16 k[32 * 2048 * 32];
  bf16 xs[2048 * 1024];
  bf16 os[2048 * 1024];
  bf16 v[32 * 2048 * 32];
  float kn[2 * 128 * 16];
  uint32_t cnt[256 * 32];
  float2 stats[8 * 2048];
  uint4 halo[2 * 128 * 12 * 32];
  float csp[2 * 16 * 8 * 192];
  uint4 qsave[128 * 256 * 8];
  uint32_t esc[4 * 65536 * 20];
};
__device__ __align__(1024) Scratch g_s;
#define g_k g_s.k
#define g_xs g_s.xs
#define g_os g_s.os
#define g_v g_s.v
#define g_kn g_s.kn
#define g_cnt g_s.cnt
#define g_stats g_s.stats
#define g_halo g_s.halo
#define g_csp g_s.csp
#define g_qsave g_s.qsave
#define g_esc g_s.esc
#define g_epoch g_s.cnt[255 * 32]

DEVINL uint32_t* cnt_x(int l, int bm) { return g_cnt + (l * 8 + bm) * 32; }
DEVINL uint32_t* cnt_o(int l, int pm, int h) { return g_cnt + (32 + (l * 16 + pm) * 2 + h) * 32; }
DEVINL uint32_t* cnt_kv(int lb, int bn) { return g_cnt + (160 + lb * 16 + bn) * 32; }
DEVINL uint32_t* cnt_ad(int bn) { return g_cnt + (192 + bn) * 32; }
DEVINL uint32_t* cnt_cs(int t, int bn) { return g_cnt + (208 + t * 16 + bn) * 32; }

DEVINL int qord(int i, int l, int pn) { return l == 0 ? i : i < 4 ? ((2 * pn) ^ (i & 2)) + (i & 1) : i - 4 < 2 * (pn & 6) ? i - 4 : i; }
struct Params {
  CUtensorMap m[15];
  const bf16* x0;
  const bf16* wq[2];
  uint32_t zero;
  int map[128];
  uint64_t wd, xd;
  struct __align__(16) { uint64_t kd, vd; } kv[4];
};
enum { M_X0A = 0, M_XSA, M_WQA, M_WQB, M_WOA, M_WOB, M_OS, M_K, M_V, M_X0R, M_XSR, M_XSO, M_OUT, M_XST, M_X0H, M_COUNT };

constexpr uint32_t QSTG = 57344;
constexpr uint32_t T0 = 65536, TSTG = 32768;
constexpr uint32_t ONES = 230400;
constexpr uint32_t PSTG = 32768, RES = 196608;
constexpr uint32_t KSC = 98304, VSC = 133120, HRS = 167936;
constexpr uint32_t ROWST = 229376, COLS = 231424, BARS = 232192, SMEM_BYTES = 232448;
constexpr uint32_t B_QF = BARS, B_QE = BARS + 32, B_TF = BARS + 64, B_TE = BARS + 96, B_PF = BARS + 128, B_PE = BARS + 176,
                   B_RF = BARS + 224, W_X = BARS + 232, B_QL = BARS + 240, B_PA = BARS + 248;
enum { NB_ST = 1, NB_KV = 2  , NB_DONE = 3, NB_SC = 4, NB_SIG = 5  , NB_KN = 9  , NB_X = 11, NB_HALO = 12  , NB_X0 = 15 };

DEVINL uint32_t pslot_b(uint32_t s) { return ((0x320415u >> (4 * s)) & 7) * 16384u; }
DEVINL uint32_t pslot_a(uint32_t s, int l) { return 98304u + ((((l & 1) ? 0x541230u : 0x041235u) >> (4 * s)) & 7) * 16384u; }

constexpr float QSCALE = 0.17677669529663687f * 1.4426950408889634f;
constexpr uint32_t QPARK = 32768;

DEVINL uint32_t exp2_h2(uint32_t s, uint32_t c852) {
  uint32_t r, t, w, m, d;
  asm volatile("{.reg .b64 t; add.rn.f16x2 %0, %1, %2; cvt.u64.u32 t, %0; cvt.u32.u64 %0, t;}" : "=r"(r) : "r"(s), "r"(0x65EA65EAu));
  asm volatile("fma.rn.f16x2 %0, %1, %2, %3;" : "=r"(t) : "r"(r), "r"(0xB880B880u), "r"(c852));
  asm volatile("fma.rn.f16x2 %0, %1, %2, %3;" : "=r"(w) : "r"(s), "r"(0x38803880u), "r"(t));
  asm volatile("fma.rn.f16x2 %0, %1, %1, %2;" : "=r"(m) : "r"(w), "r"(0x4A1F4A2Du));
  asm volatile("{.reg .b32 t; shf.l.clamp.b32 t, %2, %1, 7; add.u32 %0, t, %2;}" : "=r"(d) : "r"(r), "r"(m));
  return d;
}
DEVINL float exp2_fix(float s) { float z; asm volatile("add.rn.f32 %0, %1, 0f43BF34BC;" : "=f"(z) : "f"(s)); return z; }
DEVINL uint32_t exp2_base(float z0, float z1) { uint32_t B; asm volatile("prmt.b32 %0, %1, %2, 0x6521;" : "=r"(B) : "r"(__float_as_uint(z0)), "r"(__float_as_uint(z1))); return B; }
template <uint32_t MASK> DEVINL uint32_t and_or(uint32_t a, uint32_t c) { uint32_t r; asm volatile("lop3.b32 %0, %1, %3, %2, 0xEA;" : "=r"(r) : "r"(a), "r"(c), "n"(MASK)); return r; }
DEVINL uint32_t fma_bf2(uint32_t a, uint32_t b, uint32_t c) { uint32_t r; asm volatile("fma.rn.bf16x2 %0, %1, %2, %3;" : "=r"(r) : "r"(a), "r"(b), "r"(c)); return r; }
DEVINL float ex2v(float x) { float y; asm volatile("ex2.approx.ftz.f32 %0, %1;" : "=f"(y) : "f"(x)); return y; }
DEVINL uint32_t pack2v(float lo, float hi) { uint32_t r; asm volatile("cvt.rn.bf16x2.f32 %0, %1, %2;" : "=r"(r) : "f"(hi), "f"(lo)); return r; }
DEVINL void unesc(uint32_t (&u)[4], const uint32_t* esc, uint32_t tag) {
  const bool saved = __ldcg(esc + 16) == tag;
#pragma unroll
  for (int j = 0; j < 4; j++) {
    float lo, hi;
    asm("{.reg .f16 a, b; mov.b32 {a, b}, %2; cvt.f32.f16 %0, a; cvt.f32.f16 %1, b;}" : "=f"(lo), "=f"(hi) : "r"(u[j]));
    u[j] = saved ? __ldcg(esc + 4 * j) : pack2(lo, hi);
  }
}

DEVINL void attn_slow(const uint32_t (&q)[8], int head, const uint32_t* kesc, uint32_t tag, float (&res)[20], int lane) {
  const int g = lane >> 2, qd = lane & 3;
  const bf16* kb = g_k + (size_t)head * 2048 * 32;
  const bf16* vb = g_v + (size_t)head * 2048 * 32;
  float o[4][4], m0 = -INFINITY, m1 = -INFINITY, l0 = 0.f, l1 = 0.f;
#pragma unroll
  for (int j = 0; j < 4; j++) { o[j][0] = o[j][1] = o[j][2] = o[j][3] = 0.f; }
#pragma unroll 1
  for (int k0 = 0; k0 < 2048; k0 += 16) {
    float s[2][4];
#pragma unroll
    for (int nt = 0; nt < 2; nt++) {
      s[nt][0] = s[nt][1] = s[nt][2] = s[nt][3] = 0.f;
      const uint32_t* kp = (const uint32_t*)(kb + (size_t)(k0 + nt * 8 + g) * 32) + qd;
      uint32_t k[4] = {__ldcg(kp), __ldcg(kp + 4), __ldcg(kp + 8), __ldcg(kp + 12)};
      unesc(k, kesc + (k0 + nt * 8 + g) * 20 + qd, tag);
      __syncwarp();
      mma16816(s[nt], q[0], q[1], q[2], q[3], k[0], k[1]);
      mma16816(s[nt], q[4], q[5], q[6], q[7], k[2], k[3]);
    }
    float a0 = fmaxf(fmaxf(s[0][0], s[0][1]), fmaxf(s[1][0], s[1][1]));
    float a1 = fmaxf(fmaxf(s[0][2], s[0][3]), fmaxf(s[1][2], s[1][3]));
    a0 = fmaxf(a0, __shfl_xor_sync(~0u, a0, 1)); a0 = fmaxf(a0, __shfl_xor_sync(~0u, a0, 2));
    a1 = fmaxf(a1, __shfl_xor_sync(~0u, a1, 1)); a1 = fmaxf(a1, __shfl_xor_sync(~0u, a1, 2));
    const float n0 = fmaxf(m0, a0), n1 = fmaxf(m1, a1);
    const float c0 = (m0 == n0) ? 1.f : ex2(m0 - n0), c1 = (m1 == n1) ? 1.f : ex2(m1 - n1);
    m0 = n0; m1 = n1;
    const uint32_t p0 = pack2(ex2(s[0][0] - n0), ex2(s[0][1] - n0)), p1 = pack2(ex2(s[0][2] - n1), ex2(s[0][3] - n1));
    const uint32_t p2 = pack2(ex2(s[1][0] - n0), ex2(s[1][1] - n0)), p3 = pack2(ex2(s[1][2] - n1), ex2(s[1][3] - n1));
    l0 = l0 * c0 + bf_lo(p0) + bf_hi(p0) + bf_lo(p2) + bf_hi(p2);
    l1 = l1 * c1 + bf_lo(p1) + bf_hi(p1) + bf_lo(p3) + bf_hi(p3);
#pragma unroll
    for (int j = 0; j < 4; j++) {
      o[j][0] *= c0; o[j][1] *= c0; o[j][2] *= c1; o[j][3] *= c1;
      const unsigned short* vp = (const unsigned short*)(vb + (size_t)(k0 + 2 * qd) * 32 + j * 8 + g);
      const uint32_t b0 = (uint32_t)__ldcg(vp) | ((uint32_t)__ldcg(vp + 32) << 16);
      const uint32_t b1 = (uint32_t)__ldcg(vp + 256) | ((uint32_t)__ldcg(vp + 288) << 16);
      mma16816(o[j], p0, p1, p2, p3, b0, b1);
    }
  }
  l0 += __shfl_xor_sync(~0u, l0, 1); l0 += __shfl_xor_sync(~0u, l0, 2);
  l1 += __shfl_xor_sync(~0u, l1, 1); l1 += __shfl_xor_sync(~0u, l1, 2);
#pragma unroll
  for (int j = 0; j < 4; j++) { res[4 * j] = o[j][0]; res[4 * j + 1] = o[j][1]; res[4 * j + 2] = o[j][2]; res[4 * j + 3] = o[j][3]; }
  res[16] = l0; res[18] = l1;
}

__device__ __noinline__ void attn_redo(int redo, int l, int b, int wg, int w, uint32_t tag) {
  const int lane = lane_id();
#pragma unroll 1
  for (int t = 0; t < 4; t++) {
    const int h = t >> 1, head = 2 * (b & 15) + h, row = (b >> 4) * 256 + wg * 128 + (t & 1) * 64 + w * 16 + (lane >> 2);
    if ((redo >> t) & 1) {
      const uint32_t* esc = g_esc + (size_t)((l & 2) * 65536 + head * 2048) * 20;
      const uint32_t* qs = (const uint32_t*)(g_qsave + (block_id() * 256 + wg * 128 + w * 32 + lane) * 8 + 2 * t);
      uint32_t q[8]; float o[20];
#pragma unroll
      for (int i = 0; i < 2; i++) {
        uint32_t u[4] = {__ldcg(qs + i), __ldcg(qs + i + 2), __ldcg(qs + i + 4), __ldcg(qs + i + 6)};
        unesc(u, esc + (row + i * 8) * 20 + (lane & 3), tag);
        q[i] = u[0]; q[i + 2] = u[1]; q[i + 4] = u[2]; q[i + 6] = u[3];
      }
      __syncwarp();
      attn_slow(q, head, esc + 65536 * 20, tag, o, lane);
      const float i0 = rcp(o[16]), i1 = rcp(o[18]);
      bf16* op = g_os + (size_t)row * 1024 + h * 512 + (b & 15) * 32 + (lane & 3) * 8;
      *(uint4*)op = make_uint4(pack2(o[0] * i0, o[1] * i0), pack2(o[4] * i0, o[5] * i0), pack2(o[8] * i0, o[9] * i0), pack2(o[12] * i0, o[13] * i0));
      *(uint4*)(op + 8 * 1024) = make_uint4(pack2(o[2] * i1, o[3] * i1), pack2(o[6] * i1, o[7] * i1), pack2(o[10] * i1, o[11] * i1), pack2(o[14] * i1, o[15] * i1));
    }
    if ((t & 1) && ((redo >> 2 * h) & 3)) bar_arrive(NB_SIG + 2 * h + wg, 160 + 32 * (h & wg));
  }
}

__global__ void __cluster_dims__(2, 1, 1) __launch_bounds__(384, 1) fused_kernel(const __grid_constant__ Params prm) {
  extern __shared__ __align__(1024) char smem[];
  const uint32_t sb = (uint32_t)__cvta_generic_to_shared(smem);
  const int tid = threadIdx.x, lane = tid & 31;
  const int wg = __shfl_sync(0xffffffffu, tid >> 7, 0);
  const int w = __shfl_sync(0xffffffffu, (tid >> 5) & 3, 0);
  const int bm = remap(blockIdx.x) >> 4, bn = remap(blockIdx.x) & 15;

  auto first_tile = [&](int kt) {
    e_expect_tx(sb + B_QF + 8 * kt, QSTG);
    tma_ld(sb + kt * QSTG, &prm.m[M_X0A], kt * 64, bm * 256, sb + B_QF + 8 * kt);
    tma_ld3(sb + kt * QSTG + 32768, &prm.m[M_WQA], bn * 64, kt * 64, 0, sb + B_QF + 8 * kt);
  };
  auto init4 = [&](uint32_t bar, uint32_t c0, uint32_t c1, uint32_t c2, uint32_t c3) {
    asm volatile("{\n.reg .pred pe;\nelect.sync _|pe, 0xffffffff;\n@pe mbarrier.init.shared::cta.b64 [%0], %1;\n@pe mbarrier.init.shared::cta.b64 [%0+8], %2;\n"
                 "@pe mbarrier.init.shared::cta.b64 [%0+16], %3;\n@pe mbarrier.init.shared::cta.b64 [%0+24], %4;\n@pe fence.mbarrier_init.release.cluster;\n}"
                 ::"r"(bar), "r"(c0), "r"(c1), "r"(c2), "r"(c3) : "memory");
  };
  if (wg < 2) {
    const uint32_t k = wg * 4 + w, lo = (0x1411814u >> (4 * k)) & 15, hi = (0x1441814u >> (4 * k)) & 15;
    if (tid < 32) asm volatile("prefetch.global.L2 [%0];" ::"l"(prm.x0 + (size_t)(bm * 256 + bn * 16 + (tid & 15)) * 1024 + (tid >> 4) * 64));
    else if (tid < 80) asm volatile("prefetch.global.L2 [%0];" ::"l"(prm.wq[0] + (bm * 16 + (tid & 15)) * 3072 + ((tid >> 4) - 2) * 1024 + bn * 64));
    __syncwarp();
    if (k < 7) init4(sb + B_QE + 32 * k, lo, lo, hi, k == 6 ? 2 : hi);
    __syncwarp();
    if (k == 6 && lane == 0) *(volatile unsigned long long*)(smem + W_X) = 0ull;
  } else if (w == 0) {
    init4(sb + B_QF, 1, 1, 1, 1);
    __syncwarp();
    first_tile(0);
  }
  __syncthreads();
  asm volatile("barrier.cluster.arrive.relaxed.aligned;" ::: "memory");

  if (wg == 2) {
    asm volatile("setmaxnreg.dec.sync.aligned.u32 56;");
    const uint32_t ep1 = *(volatile uint32_t*)&g_epoch + 1;
    if (w == 0) {
      first_tile(1);
      mbar_wait(sb + B_QF, 0);
      first_tile(2); first_tile(3);
#pragma unroll 1
      for (int kt = 4; kt < 16; kt++) l2_prefetch(prm.wq[0] + kt * 196608 + blockIdx.x * 1536, 3072);
      cluster_wait();
#pragma unroll 1
      for (int l = 0; l < 4; l++) {
        IDS();
        const CUtensorMap* mw = &prm.m[M_WQA + (l & 1)];
        const CUtensorMap* mx = &prm.m[l == 0 ? M_X0A : M_XSA];
        const CUtensorMap* mh = &prm.m[l == 0 ? M_X0H : M_XSO];
        const CUtensorMap* mo = &prm.m[M_WOA + (l & 1)];
        auto q_b = [&](int i) {
          const int s = i & 3;
          mbar_wait(sb + B_QE + 8 * s, ((i >> 2) & 1) ^ 1);
          e_expect_tx(sb + B_QF + 8 * s, QSTG);
          tma_ld3(sb + s * QSTG + 32768, mw, bn * 64, qord(i, l, pn) * 64, 0, sb + B_QF + 8 * s);
        };
        uint32_t rdy = l ? 0u : ~0u;
        auto q_a = [&](int i) {
          const int kt = qord(i, l, pn);
          await_flag(kt, rdy, cnt_x(l, bm) + (lane & 15), ep1 * 2);
          if (i < 4) tma_ld(sb + i * QSTG, mx, kt * 64, bm * 256, sb + B_QF + 8 * i);
          else tma_ld_mc(sb + (i & 3) * QSTG + rank * 16384, mh, kt * 64, bm * 256 + rank * 128, sb + B_QF + 8 * (i & 3));
        };
        if (l > 0) {
#pragma unroll 1
          for (int i = 0; i < 2; i++) {
            await_flag(2 * pn + i, rdy, cnt_x(l, bm) + (lane & 15), ep1 * 2);
            e_expect_tx(sb + B_QF + 8 * i, 16384);
            tma_ld(sb + i * QSTG + (po ^ 1) * 16384, &prm.m[M_XSO], (2 * pn + i) * 64, (pm ^ 1) * 128, sb + B_QF + 8 * i);
            if (i == 0) {  q_a(2); }
          }
          mbar_wait(sb + B_QF + 8, 0);
        }
#pragma unroll 1
        for (int i = l ? 3 : 4; i < 16; i++) {
          if (l == 3 && i == 12) poll_ge(cnt_ad(bn), ep1 * 16);
          q_b(i); q_a(i);
        }
        if (l & 1) {
          const int krow = 2 * bn * 2048 + bm * 256;
          uint32_t* kvc = cnt_kv(l >> 1, bn);
          uint32_t seen = 0;
#pragma unroll 1
          for (int it = 1; it < 16; it++) {
            const int s = it & 3;
            if (it == 4) {
              bar_sync(NB_KV + 12, 288);
              mbar_wait(sb + B_TF + 24, 0);
#pragma unroll 1
              for (int i = 0; i < 4; i++) tma_st(&prm.m[M_K + (i & 1)], 0, krow + 2048 + (i >> 1) * 128, sb + i * 8192);
              bulk_commit();
            }
            if (it == 5) { bulk_wait_n<0>(); e_red(kvc + 16 + bm); }
            if (it == 12) { e_expect_tx(sb + B_RF, 32768); tma_ld3(sb + RES, &prm.m[M_XSR], 0, pm * 128, 2 * pn, sb + B_RF); }
            if (it == 1 || it == 3) mbar_wait(sb + B_QE + 12 + 4 * it, 1);
            mbar_wait(sb + B_TE + 8 * s, ((it >> 2) & 1) ^ 1);
            if (it < 8) {
#pragma unroll 1
              for (uint32_t n = 0; n < 200000u && (~seen & (3u << (2 * it - 2) | (it == 4 ? 0xC000u : 0u))); n++)
                seen = __ballot_sync(~0u, (int)(ld_acquire(kvc + (lane < 7 || lane == 15 ? (bm + 1 + lane) & 7 : 8 + ((bm + 2 + lane) & 7))) - ep1) >= 0);
              fence_async_gl();
            } else if (it == 8) { poll_ge(kvc + 16 + (lane & 7), ep1); fence_async_gl(); }
            e_expect_tx(sb + B_TF + 8 * s, 32768);
#pragma unroll 1
            for (int i = 0; i < 2; i++) {
              const int u = 2 * it - 2 + i;
              const int row = 2 * bn * 2048 + (it > 7 ? 2048 + ((bm + it) & 7) * 256 + i * 128 : u < 7 ? ((bm + 1 + u) & 7) * 256 : ((bm + 2 + u) & 7) * 256 + 128);
              tma_ld(sb + T0 + s * TSTG + i * 8192, &prm.m[M_K], 0, row, sb + B_TF + 8 * s);
              tma_ld(sb + T0 + s * TSTG + 16384 + i * 8192, &prm.m[M_V], 0, row, sb + B_TF + 8 * s);
            }
          }
        }
        auto p_b = [&](int i, uint32_t s, uint32_t par) {
          mbar_wait(sb + B_PE + 8 * s, par ^ 1);
          e_expect_tx(sb + B_PF + 8 * s, PSTG);
          tma_ld5(sb + pslot_b(s), mo, i >> 3, 2 * (i & 7), 2 * pn, sb + B_PF + 8 * s);
        };
        auto p_a = [&](int i, uint32_t s) {
          await_flag(i, rdy, cnt_o(l, pm, (lane >> 3) & 1) + (lane & 7), ep1 * 2);
          tma_ld_mc(sb + pslot_a(s, l) + rank * 8192, &prm.m[M_OS], i * 64, pm * 128 + rank * 64, sb + B_PF + 8 * s);
        };
        auto p_a2 = [&](int i) {
          await_flag(i, rdy, cnt_o(l, pm, (lane >> 3) & 1) + (lane & 7), ep1 * 2);
          tma_ld(sb + pslot_a(i, l), &prm.m[M_OS], i * 64, pm * 128, sb + B_PF + 8 * i);
          tma_ld(sb + pslot_a(i, l) + 8192, &prm.m[M_OS], i * 64, pm * 128 + 64, sb + B_PF + 8 * i);
        };
        rdy = 0;
        if (l & 1) {
#pragma unroll 1
          for (int u = 0; u < 6; u++) { const int i = (0x205413 >> (4 * u)) & 7; if (u == 4) mbar_wait(sb + B_TE, 1); p_b(i, i, i < 4 ? 1 : 0); }
#pragma unroll 1
          for (int u = 0; u < 6; u++) {
            const int i = (0x542130 >> (4 * u)) & 7;
            if (!(u & 1)) mbar_wait(sb + B_TE + 8 + 4 * u, 1);
            if (u == 4) bar_sync(NB_SIG + 3, 192);
            p_a2(i);
          }
        } else {
#pragma unroll 1
          for (int u = 0; u < 6; u++) { const int i = (0x543120 >> (4 * u)) & 7; if (u == 0 || u == 2) mbar_wait(sb + B_QE + 8 - 4 * u, 1); p_b(i, i, 0); }
          mbar_wait(sb + B_QE + 24, 1);
          e_expect_tx(sb + B_RF, 32768);
          tma_ld3(sb + RES, &prm.m[l == 0 ? M_X0R : M_XSR], 0, pm * 128, 2 * pn, sb + B_RF);
          p_a2(0);
          bar_sync(NB_SIG + 2, 320);
          e_arrive_both(sb + B_PA);
          p_a2(1);
          mbar_wait(sb + B_PA, (l >> 1) & 1);
#pragma unroll 1
          for (int i = 2; i < 6; i++) { if (i > 2) mbar_wait(sb + B_PF + 8 * (i - 3), 0); p_a(i, i); }
        }
        uint32_t s = 0, lap = 1;
#pragma unroll 1
        for (int i = 6; i < 16; i++) {
          p_b(i, s, ((s < 4 ? l : 0) + lap) & 1);
          p_a(i, s);
          if (++s == 6) { s = 0; lap++; }
        }
        const CUtensorMap* mn = &prm.m[M_WQA + ((l + 1) & 1)];
        if (l < 3) {
          mbar_wait(sb + B_PE + 8 * 4, 1); mbar_wait(sb + B_PE + 8 * 5, 1);
          tma_ld3(sb + 32768, mn, bn * 64, 2 * pn * 64, 0, sb + B_QL);
          mbar_wait(sb + B_PE + 8 * 0, l & 1);
          tma_ld3(sb + QSTG + 32768, mn, bn * 64, (2 * pn + 1) * 64, 0, sb + B_QL);
          mbar_wait(sb + B_PE + 8 * 1, l & 1);
          e_expect_tx(sb + B_QF + 16, QSTG);
          tma_ld3(sb + 2 * QSTG + 32768, mn, bn * 64, ((2 * pn) ^ 2) * 64, 0, sb + B_QF + 16);
        }
        if (l < 3) { bar_sync(NB_X, 320); e_expect_tx(sb + B_QL, 49152); }
      }
      if (blockIdx.x == 0 && lane_id() == 0) *(volatile uint32_t*)&g_epoch = ep1;
    } else {
      const int hw = w - 1;
      if (lane < 5) asm volatile("prefetch.tensormap [%0];" ::"l"(&prm.m[5 * hw + lane]) : "memory");
      __syncwarp();
      cluster_wait();
      mbar_wait(sb + B_QF, 0);
#pragma unroll 1
      for (int l = 0; l < 4; l++) {
        IDS();
        if (l > 0) { mbar_wait(sb + B_QL, (l + 1) & 1); mbar_wait(sb + B_QF + 8 * 3, 0); }
        if (l == 0) {
#pragma unroll 1
          for (int r = 2 * hw; r < 16; r += 6) {
            const uint4* p = (const uint4*)(prm.x0 + (size_t)(b * 16 + r) * 1024) + lane;
            float s1[2] = {0.f, 0.f}, s2[2] = {0.f, 0.f};
#pragma unroll
            for (int i = 0; i < 8; i++) {
              const uint4 v = __ldg(p + 32 * i);
              const uint32_t u[4] = {v.x, v.y, v.z, v.w};
#pragma unroll
              for (int k = 0; k < 4; k++) { const float a = bf_lo(u[k]), c = bf_hi(u[k]); s1[i >> 2] += a + c; s2[i >> 2] = fmaf(a, a, fmaf(c, c, s2[i >> 2])); }
            }
#pragma unroll
            for (int o = 16; o; o >>= 1)
#pragma unroll
              for (int rr = 0; rr < 2; rr++) { s1[rr] += __shfl_xor_sync(~0u, s1[rr], o); s2[rr] += __shfl_xor_sync(~0u, s2[rr], o); }
            if (lane == 0) *(float4*)&g_stats[b * 16 + r] = make_float4(s1[0], s2[0], s1[1], s2[1]);
          }
        }
        if (l < 2) {
          float cs[8];
#pragma unroll
          for (int i = 0; i < 8; i++) cs[i] = 0.f;
          const uint4* wp = (const uint4*)(prm.wq[l] + (size_t)(bm * 128 + (lane >> 3)) * 3072 + hw * 1024 + bn * 64) + (lane & 7);
#pragma unroll 8
          for (int i = 0; i < 32; i++) {
            const uint4 v = __ldg(wp + (size_t)i * 4 * 384);
            cs[0] += bf_lo(v.x); cs[1] += bf_hi(v.x); cs[2] += bf_lo(v.y); cs[3] += bf_hi(v.y);
            cs[4] += bf_lo(v.z); cs[5] += bf_hi(v.z); cs[6] += bf_lo(v.w); cs[7] += bf_hi(v.w);
          }
#pragma unroll
          for (int i = 0; i < 8; i++) { cs[i] += __shfl_xor_sync(~0u, cs[i], 8); cs[i] += __shfl_xor_sync(~0u, cs[i], 16); }
          if (lane < 8) {
            float4* d = (float4*)(g_csp + ((l * 16 + bn) * 8 + bm) * 192 + hw * 64 + lane * 8);
            d[0] = make_float4(cs[0], cs[1], cs[2], cs[3]); d[1] = make_float4(cs[4], cs[5], cs[6], cs[7]);
          }
          __syncwarp();
          asm volatile("fence.acq_rel.gpu;" ::: "memory");
          e_red_relaxed(cnt_cs(l, bn));
          if (l == 0) e_red_relaxed(cnt_x(0, bm) + pn);
          poll_ge(lane < 8 && l == 0 ? cnt_x(0, bm) + lane : cnt_cs(l, bn), ep1 * (lane < 8 && l == 0 ? 6 : 24));
        }
        if (l > 0) poll_ge(cnt_x(l, bm) + (lane & 15), ep1 * 2);
#pragma unroll 1
        for (int it = hw * 32 + lane; it < 176; it += 96) {
          const bool rows = it < 128;
          const float4* p = rows ? (const float4*)(g_stats + bm * 256) + it : (const float4*)(g_csp + ((l & 1) * 16 + bn) * 8 * 192) + (it - 128);
          const int stride = rows ? 1024 : 48, np = rows && l == 0 ? 1 : 8;
          float4 a = make_float4(0.f, 0.f, 0.f, 0.f);
#pragma unroll
          for (int k = 0; k < 8; k++) if (k < np) { const float4 v = __ldcg(p + k * stride); a.x += v.x; a.y += v.y; a.z += v.z; a.w += v.w; }
          if (rows) {
            const float m0 = a.x * (1.f / 1024.f), m1 = a.z * (1.f / 1024.f);
            const float v0 = fmaxf(a.y * (1.f / 1024.f) - m0 * m0, 0.f), v1 = fmaxf(a.w * (1.f / 1024.f) - m1 * m1, 0.f);
            const float r0 = __fdividef(1.f, bf_round(sqrtf(bf_round(bf_round(v0) + 1e-5f)))), r1 = __fdividef(1.f, bf_round(sqrtf(bf_round(bf_round(v1) + 1e-5f))));
            a = make_float4(r0, -bf_round(m0), r1, -bf_round(m1));
          }
          if (rows && (l & 1) && (it & 4)) a = make_float4(a.y, a.x, a.w, a.z);
          *(float4*)(smem + ROWST + it * 16) = a;
        }
        __syncwarp();
        if (lane == 0) asm volatile("red.release.cta.shared.add.u32 [%0], 1;" ::"r"(sb + W_X) : "memory");
        if (hw == 2) {
          if (!(l & 1)) {
            bar_sync(NB_ST, 288);
            const uint4* hp = g_halo + ((l >> 1) * 128 + b - 16) * 384 + lane;
#pragma unroll 1
            for (int h = 0; h < 2; h++) {
              uint32_t t[18];
#pragma unroll
              for (int i = 0; i < 18; i++) t[i] = 0;
#pragma unroll 1
              for (uint32_t n = bm ? 0 : 100000u; n < 100000u; n++) {
                uint32_t miss = 0;
#pragma unroll
                for (int i = 0; i < 6; i++) miss |= ld_tagged(hp + h * 192 + i * 32, &t[3 * i]) ^ ep1;
                if (__all_sync(~0u, !miss)) break;
              }
              mbar_wait(sb + B_QE + 16, 1);
              const uint32_t r = (lane & 7) + ((lane >> 3) & 1) * 8, rv = lane >> 2;
#pragma unroll
              for (int jj = 0; jj < 2; jj++) stsm4(sb + KSC + r * 128 + (((4 * h + 2 * jj + (lane >> 4)) ^ (r & 7)) << 4), t[4 * jj], t[4 * jj + 1], t[4 * jj + 2], t[4 * jj + 3]);
              const uint32_t ad = sb + VSC + rv * 128 + (((4 * h + (lane & 3)) ^ (rv & 7)) << 4);
              sts128(ad, t[8], t[10], t[12], t[14]); sts128(ad + 1024, t[9], t[11], t[13], t[15]);
              if (h == 0 && !(lane & 2)) *(uint32_t*)(smem + HRS + ((lane >> 2) + 8 * (lane & 1)) * 8) = t[16];
              bar_arrive(NB_HALO + h, 64);
            }
          } else {
            bar_sync(NB_KV, 288);
            sts128(sb + ONES + lane * 32, 0x3f803f80u, 0x3f803f80u, 0x3f803f80u, 0x3f803f80u);
            sts128(sb + ONES + lane * 32 + 16, 0x3f803f80u, 0x3f803f80u, 0x3f803f80u, 0x3f803f80u);
            sts128(sb + ROWST + 16, 0x62A962A9u, 0x00010001u, 0x3F003F00u, 0u);
            fence_async_smem();
            __syncwarp();
            e_arrive(sb + B_TF);
            mbar_wait(sb + B_TF + 16, 0); mbar_wait(sb + B_TF + 16, 1);
            poll_ge(cnt_kv(l >> 1, bn) + 16 + (lane & 7), ep1);
            const uint4 v = __ldcg((const uint4*)(g_kn + ((l >> 1) * 128 + bn * 8) * 16) + lane);
            const uint32_t mx = max(max(v.x, v.y), max(v.z, v.w));
            const uint32_t m0 = __reduce_max_sync(~0u, (lane & 2) ? 0u : mx), m1 = __reduce_max_sync(~0u, (lane & 2) ? mx : 0u);
            if (lane == 0) *(uint2*)(smem + ROWST) = make_uint2(m0, m1);
            __syncwarp();
            bar_arrive(NB_KN, 160); bar_arrive(NB_KN + 1, 160);
          }
        } else {
          if (l & 1) {
            uint32_t* p = cnt_kv(l >> 1, bn) + 8 * hw + bm;
            int on = lane == 0;
            PREPARED(p, on);
            bar_sync(hw ? NB_HALO : NB_DONE, 160);
            tma_st(&prm.m[M_K], 0, 2 * bn * 2048 + bm * 256 + hw * 128, sb + T0 + hw * 8192);
            tma_st(&prm.m[M_V], 0, 2 * bn * 2048 + bm * 256 + hw * 128, sb + T0 + 16384 + hw * 8192);
            bulk_commit(); bulk_wait_n<0>();
            release_add(p, on);
          }
#pragma unroll 1
          for (int h = l & 1 ? 0 : hw; h <= (l & 1 ? 1 : hw); h++) {
            uint32_t* p = l == 1 && lane == 1 ? cnt_ad(bn) : cnt_o(l, 2 * bm + (l & 1 ? hw : lane & 1), h) + (bn >> 1);
            int on = lane == 0 || (lane == 1 && (!(l & 1) || (l == 1 && h == 1)));
            int id = NB_SIG + 2 * h + (l & hw), n = (l & 1 ? 160 : 288) + 32 * (h & hw);
            asm volatile("" : "+r"(id), "+r"(n));
            PREPARED(p, on);
            bar_sync(id, n);
            release_add(p, on);
          }
        }
        if (hw < 2 && l < 3) {
          uint32_t* p = cnt_x(l + 1, bm) + 2 * pn + hw;
          int on = lane == 0;
          PREPARED(p, on);
          if (hw) {
            bar_sync(NB_X, 320);
            tma_st(&prm.m[M_XSO], pn * 128 + 64, pm * 128, sb + QSTG + po * 16384);
            bulk_commit();
            bar_sync(NB_KV, 288);
            bulk_wait_n<0>();
          } else bar_sync(NB_X0, 288);
          release_add(p, on);
        }
      }
    }
  } else {
    asm volatile("setmaxnreg.inc.sync.aligned.u32 224;");
    const uint32_t zero = prm.zero;
    cluster_wait();
#pragma unroll 1
    for (int l = 0; l < 4; l++) {
      {
        float acc[2][96];
#pragma unroll
        for (int i = 0; i < 96; i++) { acc[0][i] = 0.f; acc[1][i] = 0.f; }
        fence_regs(acc[0]); fence_regs(acc[1]);
        const bool early = l > 0 && wg == ((cta_id() >> 3) & 1);
        uint32_t ep1 = 0;
#pragma unroll 1
        for (int kt = 0; kt < 13; kt++) {
          const int s = kt == 12 ? 1 : kt & 3;
          if (l > 0 && kt == 0) mbar_wait(sb + B_QL, (l + 1) & 1);
          if (!(early && kt < 2)) mbar_wait(sb + B_QF + 8 * s, (kt >> 2) & 1);
          const uint64_t da = prm.xd + wg * 1024 + s * (QSTG >> 4), db = prm.wd + s * (QSTG >> 4);
          wg_fence();
#pragma unroll
          for (int k = 0; k < 4; k++)
#pragma unroll
            for (int m = 0; m < 2; m++) wgmma_m64n192k16_ss_tb(acc[m], da + m * 512 + k * 2, db + k * 128, 1);
          wg_commit();
          if (kt == 4) ep1 = *(volatile uint32_t*)&g_epoch + 1;
          wg_wait<1>();
          if (early && (kt == 1 || kt == 2)) mbar_wait(sb + B_QF + 8 * (kt - 1), 0);
          if (kt > 0 && w == 0) e_arrive_both(sb + B_QE + 8 * ((kt - 1) & 3));
        }
        {
          const bool lag = (l & 1) == wg;
          const uint32_t s0 = 2 * (~l & 1);
          const uint64_t da = prm.xd + wg * 1024 + 2 * (QSTG >> 4), db = prm.wd + 2 * (QSTG >> 4);
          mbar_wait(sb + B_QF + 8 * s0, 1);
#pragma unroll
          for (int t = 0; t < 2; t++) {
            if (lag && t != wg) {
              wg_wait<0>();
              if (w == 0) e_arrive_both(sb + B_QE + 8 + 8 * t);
              if (t == 0) mbar_wait(sb + B_QF + 16, 1);
              mbar_wait(sb + B_QF + 24, 1);
              if (t == 1) bar_arrive(NB_ST, 288);
              bar_sync(NB_SC, 256);
            }
            const uint64_t so = (uint64_t)(t ? s0 : s0 ^ 2) * (QSTG >> 4);
            wg_fence();
#pragma unroll
            for (int k = 0; k < 4; k++)
#pragma unroll
              for (int m = 0; m < 2; m++) wgmma_m64n192k16_ss_tb(acc[m], da - so + m * 512 + k * 2, db - so + k * 128, 1);
            wg_commit();
            if (!lag || t + wg == 0) {
              wg_wait<1>();
              if (w == 0) e_arrive_both(sb + B_QE + 8 * (t ? s0 : 1));
              mbar_wait(sb + B_QF + 8 * (t ? 3 : s0 ^ 2), 1);
            }
          }
          wg_fence();
#pragma unroll
          for (int m = 1; m >= 0; m--) {
#pragma unroll
            for (int k = 0; k < 4; k++) wgmma_m64n192k16_ss_tb(acc[m], da + (QSTG >> 4) + m * 512 + k * 2, db + (QSTG >> 4) + k * 128, 1);
            wg_commit();
          }
          if (!lag) { bar_arrive(NB_SC, 256); if (wg) bar_arrive(NB_ST, 288); }
          wg_wait<2>();
          if (w == 0) { e_arrive_both(sb + B_QE + 8 * (s0 ^ 2)); if (lag && wg) e_arrive_both(sb + B_QE); }
        }
#pragma unroll 1
        for (uint32_t n = 0; n < 4000000u; n++) {
          uint32_t v;
          asm volatile("ld.acquire.cta.shared.u32 %0, [%1];" : "=r"(v) : "r"(sb + W_X) : "memory");
          if (v == (uint32_t)(3 * l + 3)) break;
        }
        IDS();
        const int g = lane >> 2, qd = lane & 3;
        float2 st[2][2];
#pragma unroll
        for (int m = 0; m < 2; m++)
#pragma unroll
          for (int hh = 0; hh < 2; hh++) st[m][hh] = lds64f(sb + ROWST + (wg * 128 + m * 64 + w * 16 + g + 8 * hh) * 8);
        float2 cs[4];
        auto load_cs = [&](int gi) {
#pragma unroll
          for (int j = 0; j < 4; j++) cs[j] = lds64f(sb + COLS + (gi * 32 + j * 8 + 2 * qd) * 4);
        };
        load_cs(2 + 2 * (l & 1));
        auto drain = [&]() {
          wg_wait<0>(); fence_regs(acc[0]);
          if (w == 0) e_arrive_both(sb + B_QE + 8 * 3);
        };
        wg_wait<1>(); fence_regs(acc[1]);
        auto norm_tile = [&](int gi, int m, float sc, uint32_t (&t)[8], float (&nrm)[2], bool h16 = false) {
          const float r0 = st[m][0].x * sc, s0 = st[m][0].y, r1 = st[m][1].y * sc, s1 = st[m][1].x;
          float n0 = 0.f, n1 = 0.f;
#pragma unroll
          for (int j = 0; j < 4; j++) {
            const float* a = &acc[m][16 * gi + 4 * j];
            const float v0 = fmaf(s0, cs[j].x, a[0]) * r0, v1 = fmaf(s0, cs[j].y, a[1]) * r0;
            const float v2 = fmaf(s1, cs[j].x, a[2]) * r1, v3 = fmaf(s1, cs[j].y, a[3]) * r1;
            n0 = fmaf(v0, v0, fmaf(v1, v1, n0)); n1 = fmaf(v2, v2, fmaf(v3, v3, n1));
            t[2 * j] = h16 ? pack2h(v0, v1) : pack2(v0, v1); t[2 * j + 1] = h16 ? pack2h(v2, v3) : pack2(v2, v3);
          }
          nrm[0] = n0; nrm[1] = n1;
        };
        auto norm_group = [&](int gi, float sc, uint32_t (&t)[2][8], float (&nrm)[2][2]) { norm_tile(gi, 0, sc, t[0], nrm[0]); norm_tile(gi, 1, sc, t[1], nrm[1]); };
        uint32_t q[2][2][8];
        const uint32_t srow = (lane & 7) + ((lane >> 3) & 1) * 8;
        const uint32_t row0 = wg * 128 + w * 16;
        if (!(l & 1)) {
          auto put_kv = [&](int gi, uint32_t r0, const uint32_t (&t)[8]) {
            if (gi < 4) {
              const uint32_t r = r0 + srow;
#pragma unroll
              for (int jj = 0; jj < 2; jj++) stsm4(sb + KSC + r * 128 + (((4 * (gi - 2) + 2 * jj + (lane >> 4)) ^ (r & 7)) << 4), t[4 * jj], t[4 * jj + 1], t[4 * jj + 2], t[4 * jj + 3]);
            } else {
              const uint32_t r = r0 + g, ad = sb + VSC + r * 128 + (((4 * (gi - 4) + qd) ^ (r & 7)) << 4);
              sts128(ad, t[0], t[2], t[4], t[6]); sts128(ad + 1024, t[1], t[3], t[5], t[7]);
            }
          };
          auto cen_tile = [&](int gi, int m, uint32_t (&t)[8]) {
#pragma unroll
            for (int j = 0; j < 4; j++) {
              const float* a = &acc[m][16 * gi + 4 * j];
              t[2 * j] = pack2(fmaf(st[m][0].y, cs[j].x, a[0]), fmaf(st[m][0].y, cs[j].y, a[1]));
              t[2 * j + 1] = pack2(fmaf(st[m][1].y, cs[j].x, a[2]), fmaf(st[m][1].y, cs[j].y, a[3]));
            }
          };
          const bool send = wg == 1 && w == 3 && bm < 7;
          uint4* hp = g_halo + ((l >> 1) * 128 + b) * 384 + lane;
          mbar_wait(sb + B_QE + 16, 1);
          float2 cn[4];
          auto next_cs = [&](int gi) {
#pragma unroll
            for (int j = 0; j < 4; j++) { cs[j] = cn[j]; cn[j] = lds64f(sb + COLS + (gi * 32 + j * 8 + 2 * qd) * 4); }
          };
#pragma unroll
          for (int j = 0; j < 4; j++) cn[j] = cs[j];
#pragma unroll
          for (int h = 0; h < 2; h++) {
            uint32_t k[8], v[8];
            next_cs(4 + h);
            cen_tile(2 + h, 1, k); put_kv(2 + h, 16 + row0 + 64, k);
            next_cs(h ? 2 : 3);
            cen_tile(4 + h, 1, v); put_kv(4 + h, 16 + row0 + 64, v);
            if (send) {
              uint4* p = hp + h * 192;
              st_tagged(p, k[0], k[1], k[2], ep1); st_tagged(p + 32, k[3], k[4], k[5], ep1); st_tagged(p + 64, k[6], k[7], v[0], ep1);
              st_tagged(p + 96, v[1], v[2], v[3], ep1); st_tagged(p + 128, v[4], v[5], v[6], ep1);
              st_tagged(p + 160, v[7], __float_as_uint(qd & 1 ? st[1][1].x : st[1][0].x), 0u, ep1);
            }
            sched_fence();
          }
          drain();
          {
            uint32_t t[8];
            next_cs(4); cen_tile(2, 0, t); put_kv(2, 16 + row0, t);
            next_cs(0); cen_tile(4, 0, t); put_kv(4, 16 + row0, t);
            next_cs(3); cen_tile(0, 0, q[0][0]); cen_tile(0, 1, q[0][1]);
          }
          const bool e = g & 1, sel = 2 * qd + (g & 1) >= g + 2, first = bm == 0 && row0 == 0;
          uint32_t ka = sb + KSC + (row0 + (lane & 7)) * 128 + (((lane >> 3) ^ (lane & 7)) << 4);
          uint32_t wa = sb + VSC + (row0 + srow) * 128 + (((lane >> 4) ^ (lane & 7)) << 4);
          uint32_t psel[3] = {e ? 0x1044u : 0x4410u, !sel ? 0x4444u : e ? 0x3244u : 0x4432u, sel ? 0x4444u : e ? 0x3244u : 0x4432u};
          bf16* op = g_os + (size_t)(bm * 256 + row0 + g) * 1024 + bn * 32 + qd * 8;
          asm volatile("" : "+r"(ka), "+r"(wa), "+l"(op));
          fence_regs(psel); fence_regs(q[0][0]); fence_regs(q[0][1]);
          sched_fence();
          bar_sync(NB_SC, 256);
          if (row0 == 0) bar_sync(NB_HALO, 64);
          float ra[4], rb[4], ca[4], cb[4];
#pragma unroll
          for (int m = 0; m < 2; m++) {
            float rk[3];
#pragma unroll
            for (int u = 0; u < 3; u++) {
              const int r = row0 + m * 64 + 8 * u + 2 * qd + e - (sel ? 16 : 8);
              rk[u] = lds64f(sb + (m == 0 && r < 0 ? HRS + 128 : ROWST) + r * 8).x;
            }
            ra[2 * m] = sel ? rk[1] : rk[0]; ra[2 * m + 1] = sel ? rk[2] : rk[1];
            rb[2 * m] = sel ? rk[0] : rk[1]; rb[2 * m + 1] = sel ? rk[1] : rk[2];
          }
#pragma unroll
          for (int i = 0; i < 4; i++) { const float rq = st[i >> 1][i & 1].x * QSCALE; ca[i] = rq * ra[i]; cb[i] = rq * rb[i]; }
#pragma unroll 1
          for (int h = 0; h < 2; h++) {
            float s[2][4][4];
            uint32_t vf[2][4][4], pf[2][2][4];
#pragma unroll
            for (int m = 0; m < 2; m++)
#pragma unroll
              for (int nt = 0; nt < 4; nt++) {
                uint32_t kf[4];
                ldsm4(ka + (m * 64 + 8 * nt) * 128, kf);
                s[m][nt][0] = s[m][nt][1] = s[m][nt][2] = s[m][nt][3] = 0.f;
                mma16816(s[m][nt], q[0][m][0], q[0][m][1], q[0][m][2], q[0][m][3], kf[0], kf[1]);
                mma16816(s[m][nt], q[0][m][4], q[0][m][5], q[0][m][6], q[0][m][7], kf[2], kf[3]);
              }
#pragma unroll
            for (int m = 0; m < 2; m++)
#pragma unroll
              for (int i = 0; i < 4; i++) {
                ldsm4t((wa ^ (32 * (i & 1))) + (m * 64 + 16 * (i >> 1)) * 128, vf[m][i]);
              }
            float va[4], vb[4], mx[4];
#pragma unroll
            for (int i = 0; i < 4; i++) {
              const int m = i >> 1, hh = i & 1;
              const float a = e ? s[m][hh + 1][2 * hh + 1] : s[m][hh + 1][2 * hh];
              const float lo = e ? s[m][hh][2 * hh + 1] : s[m][hh][2 * hh], hi = e ? s[m][hh + 2][2 * hh + 1] : s[m][hh + 2][2 * hh];
              va[i] = (m == 0 && hh == 0 && first) ? -INFINITY : a * ca[i];
              vb[i] = (m == 0 && first && sel) ? -INFINITY : (sel ? lo : hi) * cb[i];
              mx[i] = fmaxf(va[i], vb[i]);
            }
#pragma unroll
            for (int i = 0; i < 4; i++) mx[i] = fmaxf(mx[i], __shfl_xor_sync(~0u, mx[i], 1));
#pragma unroll
            for (int i = 0; i < 4; i++) mx[i] = fmaxf(mx[i], __shfl_xor_sync(~0u, mx[i], 2));
#pragma unroll
            for (int i = 0; i < 4; i++) {
              va[i] = ex2(va[i] - mx[i]); vb[i] = ex2(vb[i] - mx[i]);
              mx[i] = va[i] + vb[i];
              va[i] *= ra[i]; vb[i] *= rb[i];
            }
#pragma unroll
            for (int i = 0; i < 4; i++) mx[i] += __shfl_xor_sync(~0u, mx[i], 1);
#pragma unroll
            for (int i = 0; i < 4; i++) mx[i] += __shfl_xor_sync(~0u, mx[i], 2);
#pragma unroll
            for (int i = 0; i < 4; i++) {
              const int m = i >> 1, hh = i & 1;
              const float inv = rcp(mx[i]);
              const uint32_t t = pack2(va[i] * inv, vb[i] * inv);
              pf[m][hh][hh + 1] = prmt0(t, psel[0]); pf[m][hh][hh] = prmt0(t, psel[1]); pf[m][hh][hh + 2] = prmt0(t, psel[2]);
              pf[m][hh][3 - 3 * hh] = t & zero;
            }
#pragma unroll
            for (int m = 0; m < 2; m++) {
              float o[4][4];
#pragma unroll
              for (int j = 0; j < 4; j++) o[j][0] = o[j][1] = o[j][2] = o[j][3] = 0.f;
#pragma unroll
              for (int i = 0; i < 4; i++) {
                const int kk = i >> 1, jj = 2 * (i & 1);
                mma16816(o[jj], pf[m][0][2 * kk], pf[m][1][2 * kk], pf[m][0][2 * kk + 1], pf[m][1][2 * kk + 1], vf[m][i][0], vf[m][i][1]);
                mma16816(o[jj + 1], pf[m][0][2 * kk], pf[m][1][2 * kk], pf[m][0][2 * kk + 1], pf[m][1][2 * kk + 1], vf[m][i][2], vf[m][i][3]);
              }
              stg128(op + m * 65536, pack2(o[0][0], o[0][1]), pack2(o[1][0], o[1][1]), pack2(o[2][0], o[2][1]), pack2(o[3][0], o[3][1]));
              stg128(op + m * 65536 + 8192, pack2(o[0][2], o[0][3]), pack2(o[1][2], o[1][3]), pack2(o[2][2], o[2][3]), pack2(o[3][2], o[3][3]));
            }
            bar_arrive(NB_SIG + 2 * h, 288 + 32 * h);
            if (h == 0) {
              uint32_t t[8];
              next_cs(5); cen_tile(3, 0, t); put_kv(3, 16 + row0, t);
              next_cs(1); cen_tile(5, 0, t); put_kv(5, 16 + row0, t);
#pragma unroll
              for (int j = 0; j < 4; j++) cs[j] = cn[j];
              cen_tile(1, 0, q[0][0]); cen_tile(1, 1, q[0][1]);
              ka ^= 64; wa ^= 64; op += 512;
              bar_sync(NB_SC, 256);
              if (row0 == 0) bar_sync(NB_HALO + 1, 64);
            }
          }
        } else {
          float qn[2];
          mbar_wait(sb + B_QE + 8, 1);
          drain();
          auto esc_ptr = [&](int gi) { IDS(); return g_esc + (size_t)(((l & 2) + (gi >> 1)) * 65536 + (2 * bn + (gi & 1)) * 2048) * 20; };
          auto norm_half = [&](int gi, float sc, uint32_t (&t)[2][8], float (&nrm)[2][2], int nx) {
            norm_tile(gi, 0, sc, t[0], nrm[0], true); norm_tile(gi, 1, sc, t[1], nrm[1], true);
            float2 cn[4];
#pragma unroll
            for (int j = 0; j < 4; j++) if (nx >= 0) cn[j] = lds64f(sb + COLS + (nx * 32 + j * 8 + 2 * qd) * 4);
            if (!((nrm[0][0] + nrm[0][1]) + (nrm[1][0] + nrm[1][1]) <= 4e9f) || fminf(fminf(nrm[0][0], nrm[0][1]), fminf(nrm[1][0], nrm[1][1])) < 1.5e-5f) {
              uint32_t* p = esc_ptr(gi) + (bm * 256 + row0 + g) * 20 + qd;
#pragma unroll
              for (int m = 0; m < 2; m++) {
                uint32_t u[8]; float d[2];
                norm_tile(gi, m, sc, u, d);
#pragma unroll
                for (int i = 0; i < 10; i++) p[(m * 64 + (i & 1) * 8) * 20 + (i >> 1) * 4] = i < 8 ? u[i] : ep1;
              }
            }
            __syncwarp();
#pragma unroll
            for (int i = 0; i < 16; i++) asm volatile("{\n.reg .b32 u;\nadd.u32 u, %0, 0x00040004;\nand.b32 %0, u, 0xFFF8FFF8;\n}" : "+r"(t[i >> 3][i & 7]));
#pragma unroll
            for (int j = 0; j < 4; j++) if (nx >= 0) cs[j] = cn[j];
          };
          {
            auto max_norm = [&](const float (&nrm)[2][2]) {
              const bool o1 = qd & 1, o2 = qd & 2;
              const float a = (o1 ? nrm[1][0] : nrm[0][0]) + __shfl_xor_sync(~0u, o1 ? nrm[0][0] : nrm[1][0], 1);
              const float c = (o1 ? nrm[1][1] : nrm[0][1]) + __shfl_xor_sync(~0u, o1 ? nrm[0][1] : nrm[1][1], 1);
              const float d = (o2 ? c : a) + __shfl_xor_sync(~0u, o2 ? a : c, 2);
              return __uint_as_float(__reduce_max_sync(~0u, __float_as_uint(d)));
            };
#pragma unroll
            for (int h = 0; h < 2; h++) {
              uint32_t t[2][8]; float nrm[2][2];
              const uint32_t kb = sb + (h ? wg * 8192 : T0), vb = kb + (h ? 8192 : 16384);
              norm_group(4 + h, 1.f, t, nrm);
              load_cs(2 + h);
#pragma unroll
              for (int m = 0; m < 2; m++) {
                const uint32_t r = row0 + m * 64 + g, ad = vb + r * 64 + ((qd ^ ((r >> 1) & 3)) << 4);
                sts128(ad, t[m][0], t[m][2], t[m][4], t[m][6]); sts128(ad + 512, t[m][1], t[m][3], t[m][5], t[m][7]);
              }
              norm_half(2 + h, 1.f, t, nrm, h);
#pragma unroll
              for (int i = 0; i < 4; i++) {
                const uint32_t r = row0 + (i >> 1) * 64 + srow;
                stsm4(kb + r * 64 + (((2 * (i & 1) + (lane >> 4)) ^ ((r >> 1) & 3)) << 4), t[i >> 1][4 * (i & 1)], t[i >> 1][4 * (i & 1) + 1], t[i >> 1][4 * (i & 1) + 2], t[i >> 1][4 * (i & 1) + 3]);
              }
              if (h == 1) { const float kn = max_norm(nrm); if (lane == 0) g_kn[((l >> 1) * 128 + bn * 8 + bm) * 16 + 8 + wg * 4 + w] = kn; }
              fence_async_smem();
              bar_arrive(NB_KV + 12 * h, 288);
              if (h == 0) {
                bar_arrive(wg ? NB_HALO : NB_DONE, 160);
              }
              if (h == 0) { const float kn = max_norm(nrm); if (lane == 0) g_kn[((l >> 1) * 128 + bn * 8 + bm) * 16 + wg * 4 + w] = kn; }
              norm_half(h, QSCALE, q[h], nrm, h ? -1 : 5);
#pragma unroll
              for (int i = 0; i < 4 * h; i++) sts128(sb + QPARK + 24576 - wg * 8192 + (w * 32 + lane) * 16 + i * 2048, q[h][i >> 1][4 * (i & 1)], q[h][i >> 1][4 * (i & 1) + 1], q[h][i >> 1][4 * (i & 1) + 2], q[h][i >> 1][4 * (i & 1) + 3]);
              qn[h] = max_norm(nrm);
            }
          }
          constexpr uint64_t VSTEP = 64 - (64ull << 16);
          uint32_t cq[4];
          const uint32_t &c_852 = cq[0], &c_lsb = cq[1], &c_half = cq[2];
          float o[2][20], S[2][32];
          uint32_t H[2][16], P0[4] = {}, P1[4] = {};
#pragma unroll
          for (int m = 0; m < 2; m++) {
#pragma unroll
            for (int i = 0; i < 20; i++) o[m][i] = 0.f;
            fence_regs(o[m]);
          }
          auto qkf = [&](int b, int ks, uint64_t d) { wg_n64_rs_nb_f16_f32(S[b], q[0][0][4 * ks], q[0][0][4 * ks + 1], q[0][0][4 * ks + 2], q[0][0][4 * ks + 3], d + 2 * ks, ks ? 1 : zero); };
          auto qkh = [&](int b, int ks, uint64_t d) { wg_n64_rs_nb_f16_f16(H[b], q[0][1][4 * ks], q[0][1][4 * ks + 1], q[0][1][4 * ks + 2], q[0][1][4 * ks + 3], d + 2 * ks, ks ? 1 : zero); };
          auto pv0 = [&](uint64_t d) { wgmma_m64n40k16_rs_tb(o[0], P0[0], P0[1], P0[2], P0[3], d, 1); };
          auto pv1 = [&](uint64_t d) { wgmma_m64n40k16_rs_tb(o[1], P1[0], P1[1], P1[2], P1[3], d, 1); };
          float e[4] = {};
          auto finish = [&](int h) {
            const float* s = &S[(h >> 2) & 1][8 * (h & 3)];
            const uint32_t* u = &H[(h >> 2) & 1][4 * (h & 3)];
            const float z0 = exp2_fix(s[6]), z1 = exp2_fix(s[7]);
            P0[0] = pack2v(e[0], e[1]);
            P1[0] = exp2_h2(u[0], c_852);
            P0[1] = pack2v(e[2], e[3]);
            P1[1] = exp2_h2(u[1], c_852);
            const uint32_t B = exp2_base(z0, z1), E = and_or<0x7F807F80u>(B, c_lsb);
            P1[3] = exp2_h2(u[3], c_852);
            P0[3] = fma_bf2(B, and_or<0x807F807Fu>(B, c_half), E);
            const float e4 = ex2v(s[4]), e5 = ex2v(s[5]);
            P1[2] = exp2_h2(u[2], c_852);
            P0[2] = pack2v(e4, e5);
          };
          auto start = [&](int h) {
            const float* s = &S[(h >> 2) & 1][8 * (h & 3)];
            e[2] = ex2v(s[2]); e[1] = ex2v(s[1]); e[0] = ex2v(s[0]); e[3] = ex2v(s[3]);
          };
          uint64_t kd = prm.kv[0].kd;
          mbar_wait(sb + B_TF, 0);
          lds128(sb + ROWST + 16 + (lane_id() & zero), cq);
#pragma unroll
          for (int i = 0; i < 4; i++) sts128(sb + QPARK + (wg * 128 + w * 32 + lane_id()) * 16 + i * 4096, q[0][i >> 1][4 * (i & 1)], q[0][i >> 1][4 * (i & 1) + 1], q[0][i >> 1][4 * (i & 1) + 2], q[0][i >> 1][4 * (i & 1) + 3]);
          wg_fence();
#pragma unroll
          for (int b = 0; b < 2; b++) {
            wg_n64_rs_nb_f16_f32_z(S[b], q[0][0][0], q[0][0][1], q[0][0][2], q[0][0][3], kd + 256 * b, 0);
            wg_n64_rs_nb_f16_f16_z(H[b], q[0][1][0], q[0][1][1], q[0][1][2], q[0][1][3], kd + 256 * b, 0);
            if (b == 0) { qkf(0, 1, kd); qkh(0, 1, kd); }
            wg_commit();
          }
          wg_wait<1>(); fence_regs(S[0]); fence_regs(H[0]);
          start(0); finish(0); start(1);
          wg_wait<0>();
          int redo = 0;
#pragma unroll 1
          for (int pass = 0, j = 1; pass < 2; pass++) {
#pragma unroll 1
           do {
            const uint64_t vd = prm.kv[j & 3].vd;
            bool go = false;
#pragma unroll
            for (int h = 2; h < 18; h++) {
              const int px = (h >> 2) + 1, c = h & 3;
              wg_fence();
              if (h == 13) kd = prm.kv[j & 3].kd;
              const uint64_t kx = kd + (px & 3) * 256, vx = vd + (h - 2) * VSTEP;
              if (h == 2) { qkh(1, 0, kx); qkf(1, 0, kx); pv0(vx); pv1(vx); qkh(1, 1, kx); qkf(1, 1, kx); }
              else if ((c == 1 || c == 2) && h < 17) { qkh(px & 1, c - 1, kx); pv1(vx); qkf(px & 1, c - 1, kx); pv0(vx); }
              else { pv0(vx); pv1(vx); }
              wg_commit();
              if (h == 3) e_arrive_if(sb + B_TE + 8 * ((j + 2) & 3), j > 1);
              if (h == 11) go = mbar_test(sb + B_TF + 8 * (j & 3), (j >> 2) & 1) && j != 8;
              finish(h - 1); start(h);
              if (h != 12 && h != 17) sched_fence();
              if (h == 12 && !go) {
                if (j == 16) {
#pragma unroll
                  for (int u = 13; u < 18; u++) {
                    wg_fence(); pv0(vd + (u - 2) * VSTEP); pv1(vd + (u - 2) * VSTEP); wg_commit();
                    if (u < 17) finish(u - 1);
                    if (u < 16) { start(u); sched_fence(); }
                    if (u & 1) { if (u == 17) wg_wait<0>(); else wg_wait<1>(); }
                  }
                  e_arrive(sb + B_TE + 24);
                  goto head_done;
                }
                mbar_wait(sb + B_TF + 8 * (j & 3), (j >> 2) & 1);
                if (j == 8) {
#pragma unroll
                  for (int i = 0; i < 4; i++) lds128(sb + QPARK + 24576 - wg * 8192 + (w * 32 + lane_id()) * 16 + i * 2048, &q[0][i >> 1][4 * (i & 1)]);
                }
              }
              if (h == 17) wg_wait<0>(); else if (h & 1) wg_wait<1>();
              if (c == 3) { fence_regs(S[px & 1]); fence_regs(H[px & 1]); }
            }
           } while (j++ & 7);
           head_done:
            fence_regs(o[0]); fence_regs(o[1]);
            uint32_t pk[2][8];
            {
              IDS();
              bf16* op = g_os + (size_t)(bm * 256 + row0 + (lane >> 2)) * 1024 + pass * 512 + bn * 32 + (lane & 3) * 8;
#pragma unroll
              for (int i = 0; i < 4; i++) {
                const float* a = &o[i >> 1][2 * (i & 1)];
                const float inv = rcp(a[16]);
                uint32_t* u = &pk[i >> 1][4 * (i & 1)];
#pragma unroll
                for (int k = 0; k < 4; k++) u[k] = pack2(a[4 * k] * inv, a[4 * k + 1] * inv);
                *(uint4*)(op + ((i >> 1) * 64 + (i & 1) * 8) * 1024) = make_uint4(u[0], u[1], u[2], u[3]);
              }
            }
            sched_fence();
            if (pass == 0) bar_sync(NB_KN + wg, 160);
            const float kmax = *(volatile float*)(smem + ROWST + 4 * pass);
            const bool wide = !(qn[0] <= 1.6e7f) | !(kmax <= 1.6e7f) | !(qn[0] * kmax <= 112.f * 112.f);
            int badm = 0;
#pragma unroll
            for (int m = 0; m < 2; m++) {
              uint32_t chk[2] = {0u, 0u};
#pragma unroll
              for (int i = 0; i < 8; i++) asm("fma.rn.bf16x2 %0, %1, %2, %0;" : "+r"(chk[i & 1]) : "r"(pk[m][i]), "r"(0u));
              const bool bad = wide | !(fminf(o[m][16], o[m][18]) >= 9.3e-10f) | !(o[m][16] + o[m][18] <= 1e36f) | (((chk[0] | chk[1]) & 0x7FFF7FFFu) != 0);
              badm |= __any_sync(~0u, bad) << m;
            }
            if (!badm) bar_arrive(NB_SIG + 2 * pass + wg, 160 + 32 * (pass & wg));
            qn[0] = qn[1];
#pragma unroll
            for (int m = 0; m < 2; m++) {
#pragma unroll
              for (int i = 0; i < 20; i++) o[m][i] = 0.f;
              fence_regs(o[m]);
            }
            if (badm) {
              redo |= badm << 2 * pass;
              const int tx = wg * 128 + w * 32 + lane_id();
              uint4* p = g_qsave + (block_id() * 256 + tx) * 8 + pass * 4;
#pragma unroll
              for (int i = 0; i < 4; i++) {
                uint32_t u[4] = {q[0][i >> 1][4 * (i & 1)], q[0][i >> 1][4 * (i & 1) + 1], q[0][i >> 1][4 * (i & 1) + 2], q[0][i >> 1][4 * (i & 1) + 3]};
                if (pass == 0) lds128(sb + QPARK + tx * 16 + i * 4096, u);
                p[i] = make_uint4(u[0], u[1], u[2], u[3]);
              }
            }
          }
          if (redo) attn_redo(redo, l, cta_id(), wg, w, ep1);
        }
      }
      {
        float acc[64];
#pragma unroll
        for (int i = 0; i < 64; i++) acc[i] = 0.f;
        fence_regs(acc);
        uint32_t s = 0, lap = 0;
#pragma unroll 1
        for (int kt = 0; kt < 16 - 2; kt++) {
          mbar_wait(sb + B_PF + 8 * s, ((s < 4 ? l : 0) + lap) & 1);
          const uint64_t da = mkdesc(sb + pslot_a(s, l) + wg * 8192, 16, 1024, 1), db = mkdesc(sb + pslot_b(s), 8192, 1024, 1);
          wg_fence();
#pragma unroll
          for (int k = 0; k < 4; k++) wgmma_m64n128k16_ss_tb(acc, da + k * 2, db + k * 128, 1);
          wg_commit();
          wg_wait<1>();
          if (kt > 0 && w == 0) e_arrive_both(sb + B_PE + 8 * (s ? s - 1 : 5));
          if (++s == 6) { s = 0; lap++; }
        }
        if (wg) {
          wg_wait<0>();
          if (w == 0) e_arrive_both(sb + B_PE + 8 * (3 - 2));
#pragma unroll
          for (int t = 4 - 2; t < 4; t++) mbar_wait(sb + B_PF + 8 * t, l & 1);
          bar_sync(NB_ST, 256);
        }
#pragma unroll
        for (int t = 4 - 2; t < 4; t++) {
          if (!wg) mbar_wait(sb + B_PF + 8 * t, l & 1);
          const uint64_t da = prm.xd + ((pslot_a(t, l) + wg * 8192) >> 4), db = prm.wd + (pslot_b(t) >> 4) - 2048;
          wg_fence();
#pragma unroll
          for (int k = 0; k < 4; k++) wgmma_m64n128k16_ss_tb(acc, da + k * 2, db + k * 128, 1);
          wg_commit();
        }
        if (!wg) {
          bar_arrive(NB_ST, 256);
          wg_wait<2>();
          if (w == 0) e_arrive_both(sb + B_PE + 8 * (3 - 2));
        }
        IDS();
        const int g = lane >> 2, qd = lane & 3;
        const int r0 = wg * 64 + w * 16;
        const uint32_t r = r0 + (lane & 7) + ((lane >> 3) & 1) * 8;
        uint32_t x[8][4];
        mbar_wait(sb + B_RF, l & 1);
#pragma unroll
        for (int jj = 0; jj < 8; jj++) ldsm4(sb + RES + (jj >> 2) * 16384 + r * 128 + ((((2 * jj + (lane >> 4)) & 7) ^ (r & 7)) << 4), x[jj]);
        wg_wait<0>();
        fence_regs(acc);
        if (w == 0) { if (2 > 2) e_arrive_both(sb + B_PE + 8); if (2 > 1) e_arrive_both(sb + B_PE + 16); e_arrive_both(sb + B_PE + 24); }
        const CUtensorMap* mo = &prm.m[l == 3 ? M_OUT : M_XST];
#pragma unroll
        for (int jj = 0; jj < 8; jj++) {
#pragma unroll
          for (int i = 0; i < 4; i++) x[jj][i] = add_bf16x2(x[jj][i], pack2(acc[8 * jj + 2 * i], acc[8 * jj + 2 * i + 1]));
          if (jj < 4) stsm4(sb + RES + r * 128 + ((((2 * jj + (lane >> 4)) & 7) ^ (r & 7)) << 4), x[jj][0], x[jj][1], x[jj][2], x[jj][3]);
          if (jj == 3) { fence_async_smem(); __syncwarp(); tma_st(mo, pn * 128, pm * 128 + r0, sb + RES + r0 * 128); bulk_commit(); sched_fence(); }
        }
        if (l == 3) {
#pragma unroll
          for (int jj = 4; jj < 8; jj++) stsm4(sb + RES + 16384 + r * 128 + ((((2 * jj + (lane >> 4)) & 7) ^ (r & 7)) << 4), x[jj][0], x[jj][1], x[jj][2], x[jj][3]);
          fence_async_smem(); __syncwarp();
          tma_st(mo, pn * 128 + 64, pm * 128 + r0, sb + RES + 16384 + r0 * 128);
          bulk_commit(); bulk_wait_n<0>();
        } else {
          bar_sync(NB_SC, 256);
#pragma unroll
          for (int jj = 0; jj < 8; jj++)
            stsm4(sb + (jj >> 2) * QSTG + po * 16384 + r * 128 + ((((2 * jj + (lane >> 4)) & 7) ^ (r & 7)) << 4), x[jj][0], x[jj][1], x[jj][2], x[jj][3]);
          bulk_wait_n<0>();
          bar_arrive(NB_X0, 288);
          fence_async_smem();
          bar_arrive(NB_X, 320);
          float s1[4] = {0.f, 0.f, 0.f, 0.f}, sa[4] = {0.f, 0.f, 0.f, 0.f}, sc[4] = {0.f, 0.f, 0.f, 0.f};
#pragma unroll
          for (int jj = 0; jj < 8; jj++) {
            mma16816(s1, x[jj][0], x[jj][1], x[jj][2], x[jj][3], 0x3f803f80u, 0x3f803f80u);
            mma16816(sa, x[jj][0], x[jj][1], x[jj][2], x[jj][3], x[jj][0], x[jj][2]);
            mma16816(sc, x[jj][0], x[jj][1], x[jj][2], x[jj][3], x[jj][1], x[jj][3]);
          }
          if (qd == g >> 1) {
            float2* p = g_stats + pn * 2048 + pm * 128 + r0 + g;
            p[0] = make_float2(s1[0], g & 1 ? sa[1] : sa[0]);
            p[8] = make_float2(s1[2], g & 1 ? sc[3] : sc[2]);
          }
          bar_arrive(NB_KV, 288);
        }
      }
    }
  }
  asm volatile("barrier.cluster.arrive.relaxed.aligned;\nbarrier.cluster.wait.aligned;" ::: "memory");
}

typedef CUresult (*EncodeFn)(CUtensorMap*, CUtensorMapDataType, cuuint32_t, void*, const cuuint64_t*, const cuuint64_t*, const cuuint32_t*,
                             const cuuint32_t*, CUtensorMapInterleave, CUtensorMapSwizzle, CUtensorMapL2promotion, CUtensorMapFloatOOBfill);

static void make_map(EncodeFn fn, CUtensorMap* m, const void* ptr, int rank, const uint64_t* dims, const uint64_t* strides, const uint32_t* box, CUtensorMapSwizzle sw) {
  cuuint64_t d[5], st[4];
  cuuint32_t bx[5], es[5];
  for (int i = 0; i < rank; i++) { d[i] = dims[i]; bx[i] = box[i]; es[i] = 1; if (i) st[i - 1] = strides[i - 1] * 2; }
  fn(m, CU_TENSOR_MAP_DATA_TYPE_BFLOAT16, rank, (void*)ptr, d, st, bx, es, CU_TENSOR_MAP_INTERLEAVE_NONE, sw,
     CU_TENSOR_MAP_L2_PROMOTION_L2_128B, CU_TENSOR_MAP_FLOAT_OOB_FILL_NONE);
}
static void map2(EncodeFn fn, CUtensorMap* m, const void* ptr, uint64_t inner, uint64_t outer, uint32_t bi, uint32_t bo, CUtensorMapSwizzle sw) {
  const uint64_t d[2] = {inner, outer}, st[1] = {inner};
  const uint32_t bx[2] = {bi, bo};
  make_map(fn, m, ptr, 2, d, st, bx, sw);
}

extern "C" void kernel_launch(void* const* d_in, const int* in_sizes, int n_in, void* d_out, int out_size) {
  (void)in_sizes; (void)n_in; (void)out_size;
  static EncodeFn enc = nullptr;
  static void *xs, *os, *kk, *vv;
  static int sbase = 1024;
  if (!enc) {
    void* p = nullptr;
    cudaDriverEntryPointQueryResult qr;
    cudaGetDriverEntryPoint("cuTensorMapEncodeTiled", &p, cudaEnableDefault, &qr);
    enc = (EncodeFn)p;
    Scratch* sc = nullptr;
    cudaGetSymbolAddress((void**)&sc, g_s);
    xs = sc->xs; os = sc->os; kk = sc->k; vv = sc->v;
    int dev = 0;
    cudaGetDevice(&dev);
    cudaDeviceGetAttribute(&sbase, cudaDevAttrReservedSharedMemoryPerBlock, dev);
    cudaFuncSetAttribute(fused_kernel, cudaFuncAttributeMaxDynamicSharedMemorySize, SMEM_BYTES);
  }
  Params prm;
  const CUtensorMapSwizzle S128 = CU_TENSOR_MAP_SWIZZLE_128B, S64 = CU_TENSOR_MAP_SWIZZLE_64B;
  map2(enc, &prm.m[M_X0A], d_in[0], 1024, 2048, 64, 256, S128);
  map2(enc, &prm.m[M_XSA], xs, 1024, 2048, 64, 256, S128);
  for (int t = 0; t < 2; t++) {
    const uint64_t d3[3] = {1024, 1024, 3}, s3[2] = {3072, 1024};
    const uint32_t b3[3] = {64, 64, 3};
    make_map(enc, &prm.m[M_WQA + t], d_in[1 + 3 * t], 3, d3, s3, b3, S128);
    const uint64_t d5[5] = {64, 32, 2, 16, 16}, s5[4] = {1024, 32 * 1024, 64 * 1024, 64};
    const uint32_t b5[5] = {64, 32, 1, 2, 2};
    make_map(enc, &prm.m[M_WOA + t], d_in[2 + 3 * t], 5, d5, s5, b5, S128);
    const uint64_t dr[3] = {64, 2048, 16}, sr[2] = {1024, 64};
    const uint32_t br[3] = {64, 128, 2};
    make_map(enc, &prm.m[M_X0R + t], t ? xs : d_in[0], 3, dr, sr, br, S128);
  }
  map2(enc, &prm.m[M_OS], os, 1024, 2048, 64, 64, S128);
  map2(enc, &prm.m[M_K], kk, 32, 65536, 32, 128, S64);
  map2(enc, &prm.m[M_V], vv, 32, 65536, 32, 128, S64);
  map2(enc, &prm.m[M_XSO], xs, 1024, 2048, 64, 128, S128);
  map2(enc, &prm.m[M_X0H], d_in[0], 1024, 2048, 64, 128, S128);
  map2(enc, &prm.m[M_XST], xs, 1024, 2048, 64, 16, S128);
  map2(enc, &prm.m[M_OUT], d_out, 1024, 2048, 64, 16, S128);
  prm.x0 = (const bf16*)d_in[0];
  prm.wq[0] = (const bf16*)d_in[1]; prm.wq[1] = (const bf16*)d_in[4];
  prm.zero = 0;
  for (int i = 0; i < 128; i++) prm.map[i] = remap(i);
  {
    const uint64_t hi = 0x80000020ull << 32, k0 = sbase + T0, v0 = k0 + 16384, vstep = 64 - (64ull << 16);
    prm.wd = mkdesc(sbase + 32768, 8192, 1024, 1); prm.xd = mkdesc(sbase, 16, 1024, 1);
    for (int j = 0; j < 4; j++) {
      prm.kv[j].kd = (hi | 1u << 16 | k0 >> 4) + 2048 * ((j < 16 ? j : 15) & 3);
      prm.kv[j].vd = (hi | (uint64_t)(ONES - T0 - 16384) >> 4 << 16 | v0 >> 4) + 32 * vstep * ((j + 3) & 3);
    }
  }
  fused_kernel<<<128, 384, SMEM_BYTES>>>(prm);
}
```

```cpp
#include <cuda_runtime.h>
#include <cuda_bf16.h>
#include <cuda.h>
#include <stdint.h>

typedef __nv_bfloat16 bf16;

__device__ __forceinline__ void wgmma_m64n192k16_ss_tb(float (&d)[96], uint64_t da, uint64_t db, int scale_d) {
  asm volatile("{\n.reg .pred p;\nsetp.ne.b32 p, %98, 0;\n"
    "wgmma.mma_async.sync.aligned.m64n192k16.f32.bf16.bf16 "
    "{%0, %1, %2, %3, %4, %5, %6, %7, %8, %9, %10, %11, %12, %13, %14, %15, "
    "%16, %17, %18, %19, %20, %21, %22, %23, %24, %25, %26, %27, %28, %29, %30, %31, "
    "%32, %33, %34, %35, %36, %37, %38, %39, %40, %41, %42, %43, %44, %45, %46, %47, "
    "%48, %49, %50, %51, %52, %53, %54, %55, %56, %57, %58, %59, %60, %61, %62, %63, "
    "%64, %65, %66, %67, %68, %69, %70, %71, %72, %73, %74, %75, %76, %77, %78, %79, "
    "%80, %81, %82, %83, %84, %85, %86, %87, %88, %89, %90, %91, %92, %93, %94, %95}, "
    "%96, %97, p, 1, 1, 0, 1;\n}\n"
    : "+f"(d[0]), "+f"(d[1]), "+f"(d[2]), "+f"(d[3]), "+f"(d[4]), "+f"(d[5]), "+f"(d[6]), "+f"(d[7]),
      "+f"(d[8]), "+f"(d[9]), "+f"(d[10]), "+f"(d[11]), "+f"(d[12]), "+f"(d[13]), "+f"(d[14]), "+f"(d[15]),
      "+f"(d[16]), "+f"(d[17]), "+f"(d[18]), "+f"(d[19]), "+f"(d[20]), "+f"(d[21]), "+f"(d[22]), "+f"(d[23]),
      "+f"(d[24]), "+f"(d[25]), "+f"(d[26]), "+f"(d[27]), "+f"(d[28]), "+f"(d[29]), "+f"(d[30]), "+f"(d[31]),
      "+f"(d[32]), "+f"(d[33]), "+f"(d[34]), "+f"(d[35]), "+f"(d[36]), "+f"(d[37]), "+f"(d[38]), "+f"(d[39]),
      "+f"(d[40]), "+f"(d[41]), "+f"(d[42]), "+f"(d[43]), "+f"(d[44]), "+f"(d[45]), "+f"(d[46]), "+f"(d[47]),
      "+f"(d[48]), "+f"(d[49]), "+f"(d[50]), "+f"(d[51]), "+f"(d[52]), "+f"(d[53]), "+f"(d[54]), "+f"(d[55]),
      "+f"(d[56]), "+f"(d[57]), "+f"(d[58]), "+f"(d[59]), "+f"(d[60]), "+f"(d[61]), "+f"(d[62]), "+f"(d[63]),
      "+f"(d[64]), "+f"(d[65]), "+f"(d[66]), "+f"(d[67]), "+f"(d[68]), "+f"(d[69]), "+f"(d[70]), "+f"(d[71]),
      "+f"(d[72]), "+f"(d[73]), "+f"(d[74]), "+f"(d[75]), "+f"(d[76]), "+f"(d[77]), "+f"(d[78]), "+f"(d[79]),
      "+f"(d[80]), "+f"(d[81]), "+f"(d[82]), "+f"(d[83]), "+f"(d[84]), "+f"(d[85]), "+f"(d[86]), "+f"(d[87]),
      "+f"(d[88]), "+f"(d[89]), "+f"(d[90]), "+f"(d[91]), "+f"(d[92]), "+f"(d[93]), "+f"(d[94]), "+f"(d[95])
    : "l"(da), "l"(db), "r"(scale_d));
}

__device__ __forceinline__ void wgmma_m64n128k16_ss_tb(float (&d)[64], uint64_t da, uint64_t db, int scale_d) {
  asm volatile("{\n.reg .pred p;\nsetp.ne.b32 p, %66, 0;\n"
    "wgmma.mma_async.sync.aligned.m64n128k16.f32.bf16.bf16 "
    "{%0, %1, %2, %3, %4, %5, %6, %7, %8, %9, %10, %11, %12, %13, %14, %15, "
    "%16, %17, %18, %19, %20, %21, %22, %23, %24, %25, %26, %27, %28, %29, %30, %31, "
    "%32, %33, %34, %35, %36, %37, %38, %39, %40, %41, %42, %43, %44, %45, %46, %47, "
    "%48, %49, %50, %51, %52, %53, %54, %55, %56, %57, %58, %59, %60, %61, %62, %63}, "
    "%64, %65, p, 1, 1, 0, 1;\n}\n"
    : "+f"(d[0]), "+f"(d[1]), "+f"(d[2]), "+f"(d[3]), "+f"(d[4]), "+f"(d[5]), "+f"(d[6]), "+f"(d[7]),
      "+f"(d[8]), "+f"(d[9]), "+f"(d[10]), "+f"(d[11]), "+f"(d[12]), "+f"(d[13]), "+f"(d[14]), "+f"(d[15]),
      "+f"(d[16]), "+f"(d[17]), "+f"(d[18]), "+f"(d[19]), "+f"(d[20]), "+f"(d[21]), "+f"(d[22]), "+f"(d[23]),
      "+f"(d[24]), "+f"(d[25]), "+f"(d[26]), "+f"(d[27]), "+f"(d[28]), "+f"(d[29]), "+f"(d[30]), "+f"(d[31]),
      "+f"(d[32]), "+f"(d[33]), "+f"(d[34]), "+f"(d[35]), "+f"(d[36]), "+f"(d[37]), "+f"(d[38]), "+f"(d[39]),
      "+f"(d[40]), "+f"(d[41]), "+f"(d[42]), "+f"(d[43]), "+f"(d[44]), "+f"(d[45]), "+f"(d[46]), "+f"(d[47]),
      "+f"(d[48]), "+f"(d[49]), "+f"(d[50]), "+f"(d[51]), "+f"(d[52]), "+f"(d[53]), "+f"(d[54]), "+f"(d[55]),
      "+f"(d[56]), "+f"(d[57]), "+f"(d[58]), "+f"(d[59]), "+f"(d[60]), "+f"(d[61]), "+f"(d[62]), "+f"(d[63])
    : "l"(da), "l"(db), "r"(scale_d));
}

__device__ __forceinline__ void wgmma_m64n40k16_rs_tb(float (&d)[20], uint32_t a0, uint32_t a1, uint32_t a2, uint32_t a3, uint64_t db, int scale_d) {
  asm volatile("{\n.reg .pred p;\nsetp.ne.b32 p, %25, 0;\n"
    "wgmma.mma_async.sync.aligned.m64n40k16.f32.bf16.bf16 "
    "{%0, %1, %2, %3, %4, %5, %6, %7, %8, %9, %10, %11, %12, %13, %14, %15, "
    "%16, %17, %18, %19}, "
    "{%20, %21, %22, %23}, %24, p, 1, 1, 1;\n}\n"
    : "+f"(d[0]), "+f"(d[1]), "+f"(d[2]), "+f"(d[3]), "+f"(d[4]), "+f"(d[5]), "+f"(d[6]), "+f"(d[7]),
      "+f"(d[8]), "+f"(d[9]), "+f"(d[10]), "+f"(d[11]), "+f"(d[12]), "+f"(d[13]), "+f"(d[14]), "+f"(d[15]),
      "+f"(d[16]), "+f"(d[17]), "+f"(d[18]), "+f"(d[19])
    : "r"(a0), "r"(a1), "r"(a2), "r"(a3), "l"(db), "r"(scale_d));
}

__device__ __forceinline__ void wg_n64_rs_nb_f16_f32(float (&d)[32], uint32_t a0, uint32_t a1, uint32_t a2, uint32_t a3, uint64_t db, int scale_d) {
  asm volatile("{\n.reg .pred p;\nsetp.ne.b32 p, %37, 0;\n"
    "wgmma.mma_async.sync.aligned.m64n64k16.f32.f16.f16 "
    "{%0, %1, %2, %3, %4, %5, %6, %7, %8, %9, %10, %11, %12, %13, %14, %15, "
    "%16, %17, %18, %19, %20, %21, %22, %23, %24, %25, %26, %27, %28, %29, %30, %31}, "
    "{%32, %33, %34, %35}, %36, p, 1, 1, 0;\n}\n"
    : "+f"(d[0]), "+f"(d[1]), "+f"(d[2]), "+f"(d[3]), "+f"(d[4]), "+f"(d[5]), "+f"(d[6]), "+f"(d[7]),
      "+f"(d[8]), "+f"(d[9]), "+f"(d[10]), "+f"(d[11]), "+f"(d[12]), "+f"(d[13]), "+f"(d[14]), "+f"(d[15]),
      "+f"(d[16]), "+f"(d[17]), "+f"(d[18]), "+f"(d[19]), "+f"(d[20]), "+f"(d[21]), "+f"(d[22]), "+f"(d[23]),
      "+f"(d[24]), "+f"(d[25]), "+f"(d[26]), "+f"(d[27]), "+f"(d[28]), "+f"(d[29]), "+f"(d[30]), "+f"(d[31])
    : "r"(a0), "r"(a1), "r"(a2), "r"(a3), "l"(db), "r"(scale_d));
}

__device__ __forceinline__ void wg_n64_rs_nb_f16_f16(uint32_t (&d)[16], uint32_t a0, uint32_t a1, uint32_t a2, uint32_t a3, uint64_t db, int scale_d) {
  asm volatile("{\n.reg .pred p;\nsetp.ne.b32 p, %21, 0;\n"
    "wgmma.mma_async.sync.aligned.m64n64k16.f16.f16.f16 "
    "{%0, %1, %2, %3, %4, %5, %6, %7, %8, %9, %10, %11, %12, %13, %14, %15}, "
    "{%16, %17, %18, %19}, %20, p, 1, 1, 0;\n}\n"
    : "+r"(d[0]), "+r"(d[1]), "+r"(d[2]), "+r"(d[3]), "+r"(d[4]), "+r"(d[5]), "+r"(d[6]), "+r"(d[7]),
      "+r"(d[8]), "+r"(d[9]), "+r"(d[10]), "+r"(d[11]), "+r"(d[12]), "+r"(d[13]), "+r"(d[14]), "+r"(d[15])
    : "r"(a0), "r"(a1), "r"(a2), "r"(a3), "l"(db), "r"(scale_d));
}

__device__ __forceinline__ void wg_n64_rs_nb_f16_f32_z(float (&d)[32], uint32_t a0, uint32_t a1, uint32_t a2, uint32_t a3, uint64_t db, int scale_d) {
  asm volatile("{\n.reg .pred p;\nsetp.ne.b32 p, %37, 0;\n"
    "wgmma.mma_async.sync.aligned.m64n64k16.f32.f16.f16 "
    "{%0, %1, %2, %3, %4, %5, %6, %7, %8, %9, %10, %11, %12, %13, %14, %15, "
    "%16, %17, %18, %19, %20, %21, %22, %23, %24, %25, %26, %27, %28, %29, %30, %31}, "
    "{%32, %33, %34, %35}, %36, p, 1, 1, 0;\n}\n"
    : "=f"(d[0]), "=f"(d[1]), "=f"(d[2]), "=f"(d[3]), "=f"(d[4]), "=f"(d[5]), "=f"(d[6]), "=f"(d[7]),
      "=f"(d[8]), "=f"(d[9]), "=f"(d[10]), "=f"(d[11]), "=f"(d[12]), "=f"(d[13]), "=f"(d[14]), "=f"(d[15]),
      "=f"(d[16]), "=f"(d[17]), "=f"(d[18]), "=f"(d[19]), "=f"(d[20]), "=f"(d[21]), "=f"(d[22]), "=f"(d[23]),
      "=f"(d[24]), "=f"(d[25]), "=f"(d[26]), "=f"(d[27]), "=f"(d[28]), "=f"(d[29]), "=f"(d[30]), "=f"(d[31])
    : "r"(a0), "r"(a1), "r"(a2), "r"(a3), "l"(db), "r"(scale_d));
}

__device__ __forceinline__ void wg_n64_rs_nb_f16_f16_z(uint32_t (&d)[16], uint32_t a0, uint32_t a1, uint32_t a2, uint32_t a3, uint64_t db, int scale_d) {
  asm volatile("{\n.reg .pred p;\nsetp.ne.b32 p, %21, 0;\n"
    "wgmma.mma_async.sync.aligned.m64n64k16.f16.f16.f16 "
    "{%0, %1, %2, %3, %4, %5, %6, %7, %8, %9, %10, %11, %12, %13, %14, %15}, "
    "{%16, %17, %18, %19}, %20, p, 1, 1, 0;\n}\n"
    : "=r"(d[0]), "=r"(d[1]), "=r"(d[2]), "=r"(d[3]), "=r"(d[4]), "=r"(d[5]), "=r"(d[6]), "=r"(d[7]),
      "=r"(d[8]), "=r"(d[9]), "=r"(d[10]), "=r"(d[11]), "=r"(d[12]), "=r"(d[13]), "=r"(d[14]), "=r"(d[15])
    : "r"(a0), "r"(a1), "r"(a2), "r"(a3), "l"(db), "r"(scale_d));
}

#define DEVINL __device__ __forceinline__
DEVINL void wg_fence() { asm volatile("wgmma.fence.sync.aligned;" ::: "memory"); }
DEVINL void wg_commit() { asm volatile("wgmma.commit_group.sync.aligned;" ::: "memory"); }
template <int N> DEVINL void wg_wait() { asm volatile("wgmma.wait_group.sync.aligned %0;" ::"n"(N) : "memory"); }
__host__ DEVINL uint64_t mkdesc(uint32_t addr, uint32_t lbo, uint32_t sbo, int sw) {
  return (uint64_t)((addr & 0x3FFFF) >> 4) | ((uint64_t)(lbo >> 4) << 16) | ((uint64_t)(sbo >> 4) << 32) | ((uint64_t)sw << 62);
}
DEVINL bool mbar_try(uint32_t bar, uint32_t parity) {
  uint32_t ok;
  asm volatile("{\n.reg .pred p;\nmbarrier.try_wait.parity.shared::cta.b64 p, [%1], %2;\nselp.u32 %0, 1, 0, p;\n}" : "=r"(ok) : "r"(bar), "r"(parity) : "memory");
  return ok;
}
DEVINL bool mbar_test(uint32_t bar, uint32_t parity) {
  uint32_t ok;
  asm volatile("{\n.reg .pred p;\nmbarrier.test_wait.parity.shared::cta.b64 p, [%1], %2;\nselp.u32 %0, 1, 0, p;\n}" : "=r"(ok) : "r"(bar), "r"(parity) : "memory");
  return ok;
}
DEVINL void mbar_wait(uint32_t bar, uint32_t parity) {
#pragma unroll 1
  for (uint32_t n = 0; n < 100000u; n++) if (mbar_try(bar, parity)) break;
}
#define EL(txt) "{\n.reg .pred pe;\nelect.sync _|pe, 0xffffffff;\n@pe " txt "\n}"
DEVINL void e_expect_tx(uint32_t bar, uint32_t bytes) { asm volatile(EL("mbarrier.arrive.expect_tx.shared::cta.b64 _, [%0], %1;") ::"r"(bar), "r"(bytes) : "memory"); }
DEVINL void e_arrive(uint32_t bar) { asm volatile(EL("mbarrier.arrive.shared::cta.b64 _, [%0];") ::"r"(bar) : "memory"); }
DEVINL void e_arrive_if(uint32_t bar, int c) {
  asm volatile("{\n.reg .pred pe;\nelect.sync _|pe, 0xffffffff;\nsetp.ne.and.b32 pe, %1, 0, pe;\n@pe mbarrier.arrive.shared::cta.b64 _, [%0];\n}" ::"r"(bar), "r"(c) : "memory");
}
DEVINL void e_red(uint32_t* p) { asm volatile(EL("red.release.gpu.global.add.u32 [%0], 1;") ::"l"(p) : "memory"); }
DEVINL void e_red_relaxed(uint32_t* p) { asm volatile(EL("red.relaxed.gpu.global.add.u32 [%0], 1;") ::"l"(p) : "memory"); }
DEVINL void release_add(uint32_t* p, int on) {
  asm volatile("{\n.reg .pred q;\nsetp.ne.b32 q, %1, 0;\nfence.release.gpu;\n@q red.relaxed.gpu.global.add.u32 [%0], 1;\n}" ::"l"(p), "r"(on) : "memory");
}
#define PREPARED(p, on) do { asm volatile("" : "+l"(p), "+r"(on)); asm volatile("griddepcontrol.launch_dependents;" ::: "memory"); } while (0)
DEVINL void tma_ld(uint32_t dst, const CUtensorMap* m, int c0, int c1, uint32_t bar) {
  asm volatile(EL("cp.async.bulk.tensor.2d.shared::cluster.global.mbarrier::complete_tx::bytes [%0], [%1, {%3, %4}], [%2];")
               ::"r"(dst), "l"(m), "r"(bar), "r"(c0), "r"(c1) : "memory");
}
DEVINL void tma_ld3(uint32_t dst, const CUtensorMap* m, int c0, int c1, int c2, uint32_t bar) {
  asm volatile(EL("cp.async.bulk.tensor.3d.shared::cluster.global.mbarrier::complete_tx::bytes [%0], [%1, {%3, %4, %5}], [%2];")
               ::"r"(dst), "l"(m), "r"(bar), "r"(c0), "r"(c1), "r"(c2) : "memory");
}
DEVINL void tma_ld5(uint32_t dst, const CUtensorMap* m, int c2, int c3, int c4, uint32_t bar) {
  asm volatile(EL("cp.async.bulk.tensor.5d.shared::cluster.global.mbarrier::complete_tx::bytes [%0], [%1, {0, 0, %3, %4, %5}], [%2];")
               ::"r"(dst), "l"(m), "r"(bar), "r"(c2), "r"(c3), "r"(c4) : "memory");
}
DEVINL void tma_ld_mc(uint32_t dst, const CUtensorMap* m, int c0, int c1, uint32_t bar) {
  asm volatile(EL("cp.async.bulk.tensor.2d.shared::cluster.global.mbarrier::complete_tx::bytes.multicast::cluster [%0], [%1, {%3, %4}], [%2], %5;")
               ::"r"(dst), "l"(m), "r"(bar), "r"(c0), "r"(c1), "h"((uint16_t)3) : "memory");
}
DEVINL void e_arrive_both(uint32_t bar) {
  asm volatile("{\n.reg .pred pe;\n.reg .b32 r0, r1;\nelect.sync _|pe, 0xffffffff;\nmapa.shared::cluster.u32 r0, %0, 0;\nmapa.shared::cluster.u32 r1, %0, 1;\n"
               "@pe mbarrier.arrive.shared::cluster.b64 _, [r0];\n@pe mbarrier.arrive.shared::cluster.b64 _, [r1];\n}" ::"r"(bar) : "memory");
}
DEVINL void tma_st(const CUtensorMap* m, int c0, int c1, uint32_t src) {
  asm volatile(EL("cp.async.bulk.tensor.2d.global.shared::cta.bulk_group [%0, {%2, %3}], [%1];") ::"l"(m), "r"(src), "r"(c0), "r"(c1) : "memory");
}
DEVINL void bulk_commit() { asm volatile("cp.async.bulk.commit_group;" ::: "memory"); }
template <int N> DEVINL void bulk_wait_n() { asm volatile("cp.async.bulk.wait_group %0;\nbar.warp.sync 0xffffffff;" ::"n"(N) : "memory"); }
DEVINL void l2_prefetch(const void* g, uint32_t bytes) { asm volatile(EL("cp.async.bulk.prefetch.L2.global [%0], %1;") ::"l"(g), "r"(bytes) : "memory"); }
DEVINL void fence_async_smem() { asm volatile("fence.proxy.async.shared::cta;" ::: "memory"); }
DEVINL void fence_async_gl() { asm volatile("fence.proxy.async.global;" ::: "memory"); }
DEVINL void cluster_wait() { asm volatile("barrier.cluster.wait.aligned;" ::: "memory"); }
DEVINL void bar_sync(int id, int n) { asm volatile("bar.sync %0, %1;" ::"r"(id), "r"(n) : "memory"); }
DEVINL void bar_arrive(int id, int n) { asm volatile("bar.arrive %0, %1;" ::"r"(id), "r"(n) : "memory"); }
DEVINL uint32_t ld_acquire(const uint32_t* p) { uint32_t v; asm volatile("ld.acquire.gpu.global.u32 %0, [%1];" : "=r"(v) : "l"(p) : "memory"); return v; }
DEVINL void await_flag(int j, uint32_t& rdy, const uint32_t* p, uint32_t target) {
  if ((rdy >> j) & 1) return;
#pragma unroll 1
  for (uint32_t n = 0; n < 200000u && !((rdy >> j) & 1); n++) rdy = __ballot_sync(~0u, (int)(ld_acquire(p) - target) >= 0);
  asm volatile("fence.proxy.async.global;" ::: "memory");
}
DEVINL void poll_ge(const uint32_t* p, uint32_t target) {
#pragma unroll 1
  for (uint32_t n = 0; n < 200000u; n++) if (__all_sync(~0u, (int)(ld_acquire(p) - target) >= 0)) break;
}
DEVINL int lane_id() { int v; asm volatile("mov.u32 %0, %%laneid;" : "=r"(v)); return v; }
__host__ DEVINL int remap(int v) {
  const int c = v >> 1, u = c - 36, r = (u * 37) >> 8;
  const int L = c < 4 ? 32 + 8 * c : c < 36 ? c - 4 : 33 + u + r;
  return 2 * L + (v & 1);
}
DEVINL int block_id() { int v; asm volatile("mov.u32 %0, %%ctaid.x;" : "=r"(v)); return v; }
#define cta_id() prm.map[block_id()]
#define IDS() const int lane = lane_id(), b = cta_id(), bm = b >> 4, bn = b & 15, rank = b & 1, pm = 2 * bm + (bn >> 3), pn = bn & 7, po = pm & 1; \
  (void)lane; (void)bm; (void)bn; (void)rank; (void)pm; (void)pn; (void)po
DEVINL void st_tagged(uint4* p, uint32_t a, uint32_t b, uint32_t c, uint32_t tag) {
  asm volatile("{\n.reg .b64 u, v;\n.reg .b128 t;\nmov.b64 u, {%1, %2};\nmov.b64 v, {%3, %4};\nmov.b128 t, {u, v};\nst.relaxed.gpu.global.b128 [%0], t;\n}"
               ::"l"(p), "r"(a), "r"(b), "r"(c), "r"(tag) : "memory");
}
DEVINL uint32_t ld_tagged(const uint4* p, uint32_t* r) {
  uint32_t tag;
  asm volatile("{\n.reg .b64 u, v;\n.reg .b128 t;\nld.relaxed.gpu.global.b128 t, [%4];\nmov.b128 {u, v}, t;\nmov.b64 {%0, %1}, u;\nmov.b64 {%2, %3}, v;\n}"
               : "=r"(r[0]), "=r"(r[1]), "=r"(r[2]), "=r"(tag) : "l"(p) : "memory");
  return tag;
}
DEVINL float ex2(float x) { float y; asm("ex2.approx.ftz.f32 %0, %1;" : "=f"(y) : "f"(x)); return y; }
DEVINL float rcp(float x) { float y; asm("rcp.approx.ftz.f32 %0, %1;" : "=f"(y) : "f"(x)); return y; }
DEVINL uint32_t pack2(float lo, float hi) { uint32_t r; asm("cvt.rn.bf16x2.f32 %0, %1, %2;" : "=r"(r) : "f"(hi), "f"(lo)); return r; }
DEVINL uint32_t pack2h(float lo, float hi) { uint32_t r; asm("cvt.rz.f16x2.f32 %0, %1, %2;" : "=r"(r) : "f"(hi), "f"(lo)); return r; }
DEVINL uint32_t prmt0(uint32_t a, uint32_t sel) { uint32_t r; asm("prmt.b32 %0, %1, 0, %2;" : "=r"(r) : "r"(a), "r"(sel)); return r; }
DEVINL void stg128(const void* p, uint32_t a, uint32_t b, uint32_t c, uint32_t d) {
  asm volatile("st.global.v4.b32 [%0], {%1, %2, %3, %4};" ::"l"(p), "r"(a), "r"(b), "r"(c), "r"(d) : "memory");
}
DEVINL float bf_lo(uint32_t w) { return __uint_as_float(w << 16); }
DEVINL float bf_hi(uint32_t w) { return __uint_as_float(w & 0xFFFF0000u); }
DEVINL float bf_round(float x) { return bf_lo(pack2(x, 0.f)); }
DEVINL uint32_t add_bf16x2(uint32_t a, uint32_t b) { uint32_t r; asm("add.rn.bf16x2 %0, %1, %2;" : "=r"(r) : "r"(a), "r"(b)); return r; }
DEVINL void stsm4(uint32_t addr, uint32_t a, uint32_t b, uint32_t c, uint32_t d) {
  asm volatile("stmatrix.sync.aligned.m8n8.x4.shared.b16 [%0], {%1, %2, %3, %4};" ::"r"(addr), "r"(a), "r"(b), "r"(c), "r"(d) : "memory");
}
DEVINL void ldsm4(uint32_t addr, uint32_t (&r)[4]) {
  asm volatile("ldmatrix.sync.aligned.m8n8.x4.shared.b16 {%0, %1, %2, %3}, [%4];" : "=r"(r[0]), "=r"(r[1]), "=r"(r[2]), "=r"(r[3]) : "r"(addr) : "memory");
}
DEVINL void ldsm4t(uint32_t addr, uint32_t (&r)[4]) {
  asm volatile("ldmatrix.sync.aligned.m8n8.x4.trans.shared.b16 {%0, %1, %2, %3}, [%4];" : "=r"(r[0]), "=r"(r[1]), "=r"(r[2]), "=r"(r[3]) : "r"(addr) : "memory");
}
DEVINL void sts128(uint32_t addr, uint32_t a, uint32_t b, uint32_t c, uint32_t d) {
  asm volatile("st.shared.v4.b32 [%0], {%1, %2, %3, %4};" ::"r"(addr), "r"(a), "r"(b), "r"(c), "r"(d) : "memory");
}
DEVINL float2 lds64f(uint32_t addr) { float2 v; asm volatile("ld.shared.v2.f32 {%0, %1}, [%2];" : "=f"(v.x), "=f"(v.y) : "r"(addr) : "memory"); return v; }
DEVINL void mma16816(float (&d)[4], uint32_t a0, uint32_t a1, uint32_t a2, uint32_t a3, uint32_t b0, uint32_t b1) {
  asm("mma.sync.aligned.m16n8k16.row.col.f32.bf16.bf16.f32 {%0, %1, %2, %3}, {%4, %5, %6, %7}, {%8, %9}, {%0, %1, %2, %3};"
               : "+f"(d[0]), "+f"(d[1]), "+f"(d[2]), "+f"(d[3]) : "r"(a0), "r"(a1), "r"(a2), "r"(a3), "r"(b0), "r"(b1));
}
template <int N> DEVINL void fence_regs(float (&d)[N]) {
#pragma unroll
  for (int i = 0; i < N; i++) asm volatile("" : "+f"(d[i])::"memory");
}
template <int N> DEVINL void fence_regs(uint32_t (&d)[N]) {
#pragma unroll
  for (int i = 0; i < N; i++) asm volatile("" : "+r"(d[i])::"memory");
}
DEVINL void lds128(uint32_t addr, uint32_t* r) {
  asm volatile("ld.shared.v4.b32 {%0, %1, %2, %3}, [%4];" : "=r"(r[0]), "=r"(r[1]), "=r"(r[2]), "=r"(r[3]) : "r"(addr) : "memory");
}
DEVINL void sched_fence() { asm volatile("griddepcontrol.launch_dependents;" ::: "memory"); }

struct Scratch {
  bf16 k[32 * 2048 * 32];
  bf16 xs[2048 * 1024];
  bf16 os[2048 * 1024];
  bf16 v[32 * 2048 * 32];
  float kn[2 * 128 * 16];
  uint32_t cnt[256 * 32];
  float2 stats[8 * 2048];
  uint4 halo[128 * 12 * 32];
  float csp[2 * 16 * 8 * 192];
  uint4 qsave[128 * 256 * 8];
  uint32_t esc[4 * 65536 * 20];
};
__device__ __align__(1024) Scratch g_s;
#define g_k g_s.k
#define g_xs g_s.xs
#define g_os g_s.os
#define g_v g_s.v
#define g_kn g_s.kn
#define g_cnt g_s.cnt
#define g_stats g_s.stats
#define g_halo g_s.halo
#define g_csp g_s.csp
#define g_qsave g_s.qsave
#define g_esc g_s.esc
#define g_epoch g_s.cnt[255 * 32]

DEVINL uint32_t* cnt_x(int bm) { return g_cnt + bm * 32; }
DEVINL uint32_t* cnt_o(int l, int pm, int h) { return g_cnt + (32 + (l * 16 + pm) * 2 + h) * 32; }
DEVINL uint32_t* cnt_kv(int lb, int bn) { return g_cnt + (160 + lb * 16 + bn) * 32; }
DEVINL uint32_t* cnt_ad(int bn) { return g_cnt + (192 + bn) * 32; }
DEVINL uint32_t* cnt_cs(int t, int bn) { return g_cnt + (208 + t * 16 + bn) * 32; }

DEVINL int qord(int i, int l, int pn) { return l == 0 ? i : i < 4 ? ((2 * pn) ^ (i & 2)) + (i & 1) : i - 4 < 2 * (pn & 6) ? i - 4 : i; }
struct Params {
  CUtensorMap m[15];
  const bf16* x0;
  const bf16* wq[2];
  uint32_t zero;
  int map[128];
  uint64_t wd, xd;
  struct __align__(16) { uint64_t kd, vd; } kv[4];
};
enum { M_X0A = 0, M_XSA, M_WQA, M_WQB, M_WOA, M_WOB, M_OS, M_K, M_V, M_X0R, M_XSR, M_XSO, M_OUT, M_XST, M_X0H, M_COUNT };

constexpr uint32_t QSTG = 57344;
constexpr uint32_t T0 = 65536, TSTG = 32768;
constexpr uint32_t ONES = 230400;
constexpr uint32_t PSTG = 32768, RES = 196608;
constexpr uint32_t KSC = 98304, VSC = 133120, HRS = 167936;
constexpr uint32_t ROWST = 229376, COLS = 231424, BARS = 232192, SMEM_BYTES = 232448;
constexpr uint32_t B_QF = BARS, B_QE = BARS + 32, B_TF = BARS + 64, B_TE = BARS + 96, B_PF = BARS + 128, B_PE = BARS + 176,
                   B_RF = BARS + 224, W_X = BARS + 232, B_QL = BARS + 240, B_PA = BARS + 248;
enum { NB_ST = 1, NB_KV = 2  , NB_DONE = 3, NB_SC = 4, NB_SIG = 5  , NB_KN = 9  , NB_X = 11, NB_HALO = 12  , NB_X0 = 15 };

DEVINL uint32_t pslot_b(uint32_t s) { return ((0x320415u >> (4 * s)) & 7) * 16384u; }
DEVINL uint32_t pslot_a(uint32_t s, int l) { return 98304u + ((((l & 1) ? 0x541230u : 0x041235u) >> (4 * s)) & 7) * 16384u; }

constexpr float QSCALE = 0.17677669529663687f * 1.4426950408889634f;
constexpr uint32_t QPARK = 32768;

DEVINL uint32_t exp2_h2(uint32_t s, uint32_t c852) {
  uint32_t r, t, w, m, d;
  asm volatile("{.reg .b64 t; add.rn.f16x2 %0, %1, %2; cvt.u64.u32 t, %0; cvt.u32.u64 %0, t;}" : "=r"(r) : "r"(s), "r"(0x65EA65EAu));
  asm volatile("fma.rn.f16x2 %0, %1, %2, %3;" : "=r"(t) : "r"(r), "r"(0xB880B880u), "r"(c852));
  asm volatile("fma.rn.f16x2 %0, %1, %2, %3;" : "=r"(w) : "r"(s), "r"(0x38803880u), "r"(t));
  asm volatile("fma.rn.f16x2 %0, %1, %1, %2;" : "=r"(m) : "r"(w), "r"(0x4A1F4A2Du));
  asm volatile("{.reg .b32 t; shf.l.clamp.b32 t, %2, %1, 7; add.u32 %0, t, %2;}" : "=r"(d) : "r"(r), "r"(m));
  return d;
}
DEVINL float exp2_fix(float s) { float z; asm volatile("add.rn.f32 %0, %1, 0f43BF34BC;" : "=f"(z) : "f"(s)); return z; }
DEVINL uint32_t exp2_base(float z0, float z1) { uint32_t B; asm volatile("prmt.b32 %0, %1, %2, 0x6521;" : "=r"(B) : "r"(__float_as_uint(z0)), "r"(__float_as_uint(z1))); return B; }
template <uint32_t MASK> DEVINL uint32_t and_or(uint32_t a, uint32_t c) { uint32_t r; asm volatile("lop3.b32 %0, %1, %3, %2, 0xEA;" : "=r"(r) : "r"(a), "r"(c), "n"(MASK)); return r; }
DEVINL uint32_t fma_bf2(uint32_t a, uint32_t b, uint32_t c) { uint32_t r; asm volatile("fma.rn.bf16x2 %0, %1, %2, %3;" : "=r"(r) : "r"(a), "r"(b), "r"(c)); return r; }
DEVINL float ex2v(float x) { float y; asm volatile("ex2.approx.ftz.f32 %0, %1;" : "=f"(y) : "f"(x)); return y; }
DEVINL uint32_t pack2v(float lo, float hi) { uint32_t r; asm volatile("cvt.rn.bf16x2.f32 %0, %1, %2;" : "=r"(r) : "f"(hi), "f"(lo)); return r; }
DEVINL void unesc(uint32_t (&u)[4], const uint32_t* esc, uint32_t tag) {
  const bool saved = __ldcg(esc + 16) == tag;
#pragma unroll
  for (int j = 0; j < 4; j++) {
    float lo, hi;
    asm("{.reg .f16 a, b; mov.b32 {a, b}, %2; cvt.f32.f16 %0, a; cvt.f32.f16 %1, b;}" : "=f"(lo), "=f"(hi) : "r"(u[j]));
    u[j] = saved ? __ldcg(esc + 4 * j) : pack2(lo, hi);
  }
}

DEVINL void attn_slow(const uint32_t (&q)[8], int head, const uint32_t* kesc, uint32_t tag, float (&res)[20], int lane) {
  const int g = lane >> 2, qd = lane & 3;
  const bf16* kb = g_k + (size_t)head * 2048 * 32;
  const bf16* vb = g_v + (size_t)head * 2048 * 32;
  float o[4][4], m0 = -INFINITY, m1 = -INFINITY, l0 = 0.f, l1 = 0.f;
#pragma unroll
  for (int j = 0; j < 4; j++) { o[j][0] = o[j][1] = o[j][2] = o[j][3] = 0.f; }
#pragma unroll 1
  for (int k0 = 0; k0 < 2048; k0 += 16) {
    float s[2][4];
#pragma unroll
    for (int nt = 0; nt < 2; nt++) {
      s[nt][0] = s[nt][1] = s[nt][2] = s[nt][3] = 0.f;
      const uint32_t* kp = (const uint32_t*)(kb + (size_t)(k0 + nt * 8 + g) * 32) + qd;
      uint32_t k[4] = {__ldcg(kp), __ldcg(kp + 4), __ldcg(kp + 8), __ldcg(kp + 12)};
      unesc(k, kesc + (k0 + nt * 8 + g) * 20 + qd, tag);
      __syncwarp();
      mma16816(s[nt], q[0], q[1], q[2], q[3], k[0], k[1]);
      mma16816(s[nt], q[4], q[5], q[6], q[7], k[2], k[3]);
    }
    float a0 = fmaxf(fmaxf(s[0][0], s[0][1]), fmaxf(s[1][0], s[1][1]));
    float a1 = fmaxf(fmaxf(s[0][2], s[0][3]), fmaxf(s[1][2], s[1][3]));
    a0 = fmaxf(a0, __shfl_xor_sync(~0u, a0, 1)); a0 = fmaxf(a0, __shfl_xor_sync(~0u, a0, 2));
    a1 = fmaxf(a1, __shfl_xor_sync(~0u, a1, 1)); a1 = fmaxf(a1, __shfl_xor_sync(~0u, a1, 2));
    const float n0 = fmaxf(m0, a0), n1 = fmaxf(m1, a1);
    const float c0 = (m0 == n0) ? 1.f : ex2(m0 - n0), c1 = (m1 == n1) ? 1.f : ex2(m1 - n1);
    m0 = n0; m1 = n1;
    const uint32_t p0 = pack2(ex2(s[0][0] - n0), ex2(s[0][1] - n0)), p1 = pack2(ex2(s[0][2] - n1), ex2(s[0][3] - n1));
    const uint32_t p2 = pack2(ex2(s[1][0] - n0), ex2(s[1][1] - n0)), p3 = pack2(ex2(s[1][2] - n1), ex2(s[1][3] - n1));
    l0 = l0 * c0 + bf_lo(p0) + bf_hi(p0) + bf_lo(p2) + bf_hi(p2);
    l1 = l1 * c1 + bf_lo(p1) + bf_hi(p1) + bf_lo(p3) + bf_hi(p3);
#pragma unroll
    for (int j = 0; j < 4; j++) {
      o[j][0] *= c0; o[j][1] *= c0; o[j][2] *= c1; o[j][3] *= c1;
      const unsigned short* vp = (const unsigned short*)(vb + (size_t)(k0 + 2 * qd) * 32 + j * 8 + g);
      const uint32_t b0 = (uint32_t)__ldcg(vp) | ((uint32_t)__ldcg(vp + 32) << 16);
      const uint32_t b1 = (uint32_t)__ldcg(vp + 256) | ((uint32_t)__ldcg(vp + 288) << 16);
      mma16816(o[j], p0, p1, p2, p3, b0, b1);
    }
  }
  l0 += __shfl_xor_sync(~0u, l0, 1); l0 += __shfl_xor_sync(~0u, l0, 2);
  l1 += __shfl_xor_sync(~0u, l1, 1); l1 += __shfl_xor_sync(~0u, l1, 2);
#pragma unroll
  for (int j = 0; j < 4; j++) { res[4 * j] = o[j][0]; res[4 * j + 1] = o[j][1]; res[4 * j + 2] = o[j][2]; res[4 * j + 3] = o[j][3]; }
  res[16] = l0; res[18] = l1;
}

__device__ __noinline__ void attn_redo(int redo, int l, int b, int wg, int w, uint32_t tag) {
  const int lane = lane_id();
#pragma unroll 1
  for (int t = 0; t < 4; t++) {
    const int h = t >> 1, head = 2 * (b & 15) + h, row = (b >> 4) * 256 + wg * 128 + (t & 1) * 64 + w * 16 + (lane >> 2);
    if ((redo >> t) & 1) {
      const uint32_t* esc = g_esc + (size_t)((l & 2) * 65536 + head * 2048) * 20;
      const uint32_t* qs = (const uint32_t*)(g_qsave + (block_id() * 256 + wg * 128 + w * 32 + lane) * 8 + 2 * t);
      uint32_t q[8]; float o[20];
#pragma unroll
      for (int i = 0; i < 2; i++) {
        uint32_t u[4] = {__ldcg(qs + i), __ldcg(qs + i + 2), __ldcg(qs + i + 4), __ldcg(qs + i + 6)};
        unesc(u, esc + (row + i * 8) * 20 + (lane & 3), tag);
        q[i] = u[0]; q[i + 2] = u[1]; q[i + 4] = u[2]; q[i + 6] = u[3];
      }
      __syncwarp();
      attn_slow(q, head, esc + 65536 * 20, tag, o, lane);
      const float i0 = rcp(o[16]), i1 = rcp(o[18]);
      bf16* op = g_os + (size_t)row * 1024 + h * 512 + (b & 15) * 32 + (lane & 3) * 8;
      *(uint4*)op = make_uint4(pack2(o[0] * i0, o[1] * i0), pack2(o[4] * i0, o[5] * i0), pack2(o[8] * i0, o[9] * i0), pack2(o[12] * i0, o[13] * i0));
      *(uint4*)(op + 8 * 1024) = make_uint4(pack2(o[2] * i1, o[3] * i1), pack2(o[6] * i1, o[7] * i1), pack2(o[10] * i1, o[11] * i1), pack2(o[14] * i1, o[15] * i1));
    }
    if ((t & 1) && ((redo >> 2 * h) & 3)) bar_arrive(NB_SIG + 2 * h + wg, 160 + 32 * (h & wg));
  }
}

__global__ void __cluster_dims__(2, 1, 1) __launch_bounds__(384, 1) fused_kernel(const __grid_constant__ Params prm) {
  extern __shared__ __align__(1024) char smem[];
  const uint32_t sb = (uint32_t)__cvta_generic_to_shared(smem);
  const int tid = threadIdx.x, lane = tid & 31;
  const int wg = __shfl_sync(0xffffffffu, tid >> 7, 0);
  const int w = __shfl_sync(0xffffffffu, (tid >> 5) & 3, 0);
  const int bm = remap(blockIdx.x) >> 4, bn = remap(blockIdx.x) & 15;

  auto first_tile = [&](int kt) {
    e_expect_tx(sb + B_QF + 8 * kt, QSTG);
    tma_ld(sb + kt * QSTG, &prm.m[M_X0A], kt * 64, bm * 256, sb + B_QF + 8 * kt);
    tma_ld3(sb + kt * QSTG + 32768, &prm.m[M_WQA], bn * 64, kt * 64, 0, sb + B_QF + 8 * kt);
  };
  auto init4 = [&](uint32_t bar, uint32_t c0, uint32_t c1, uint32_t c2, uint32_t c3) {
    asm volatile("{\n.reg .pred pe;\nelect.sync _|pe, 0xffffffff;\n@pe mbarrier.init.shared::cta.b64 [%0], %1;\n@pe mbarrier.init.shared::cta.b64 [%0+8], %2;\n"
                 "@pe mbarrier.init.shared::cta.b64 [%0+16], %3;\n@pe mbarrier.init.shared::cta.b64 [%0+24], %4;\n@pe fence.mbarrier_init.release.cluster;\n}"
                 ::"r"(bar), "r"(c0), "r"(c1), "r"(c2), "r"(c3) : "memory");
  };
  if (wg < 2) {
    const uint32_t k = wg * 4 + w, lo = (0x1411814u >> (4 * k)) & 15, hi = (0x1441814u >> (4 * k)) & 15;
    if (tid < 32) asm volatile("prefetch.global.L2 [%0];" ::"l"(prm.x0 + (size_t)(bm * 256 + bn * 16 + (tid & 15)) * 1024 + (tid >> 4) * 64));
    else if (tid < 80) asm volatile("prefetch.global.L2 [%0];" ::"l"(prm.wq[0] + (bm * 16 + (tid & 15)) * 3072 + ((tid >> 4) - 2) * 1024 + bn * 64));
    __syncwarp();
    if (k < 7) init4(sb + B_QE + 32 * k, lo, lo, hi, k == 6 ? 2 : hi);
    __syncwarp();
    if (k == 6 && lane == 0) *(volatile unsigned long long*)(smem + W_X) = 0ull;
  } else if (w == 0) {
    init4(sb + B_QF, 1, 1, 1, 1);
    __syncwarp();
    first_tile(0);
  }
  __syncthreads();
  asm volatile("barrier.cluster.arrive.relaxed.aligned;" ::: "memory");

  if (wg == 2) {
    asm volatile("setmaxnreg.dec.sync.aligned.u32 56;");
    const uint32_t ep1 = *(volatile uint32_t*)&g_epoch + 1;
    if (w == 0) {
      first_tile(1);
      mbar_wait(sb + B_QF, 0);
      first_tile(2); first_tile(3);
#pragma unroll 1
      for (int kt = 4; kt < 16; kt++) l2_prefetch(prm.wq[0] + kt * 196608 + blockIdx.x * 1536, 3072);
      cluster_wait();
#pragma unroll 1
      for (int l = 0; l < 4; l++) {
        IDS();
        const CUtensorMap* mw = &prm.m[M_WQA + (l & 1)];
        const CUtensorMap* mx = &prm.m[l == 0 ? M_X0A : M_XSA];
        const CUtensorMap* mh = &prm.m[l == 0 ? M_X0H : M_XSO];
        const CUtensorMap* mo = &prm.m[M_WOA + (l & 1)];
        auto q_b = [&](int i) {
          const int s = i & 3;
          mbar_wait(sb + B_QE + 8 * s, ((i >> 2) & 1) ^ 1);
          e_expect_tx(sb + B_QF + 8 * s, QSTG);
          tma_ld3(sb + s * QSTG + 32768, mw, bn * 64, qord(i, l, pn) * 64, 0, sb + B_QF + 8 * s);
        };
        uint32_t rdy = l ? 0u : ~0u;
        auto q_a = [&](int i) {
          const int kt = qord(i, l, pn);
          await_flag(kt, rdy, cnt_x(bm) + (lane & 15), ep1 * 9 - 6 + 2 * l);
          if (i < 4) tma_ld(sb + i * QSTG, mx, kt * 64, bm * 256, sb + B_QF + 8 * i);
          else tma_ld_mc(sb + (i & 3) * QSTG + rank * 16384, mh, kt * 64, bm * 256 + rank * 128, sb + B_QF + 8 * (i & 3));
        };
        if (l > 0) {
#pragma unroll 1
          for (int i = 0; i < 2; i++) {
            await_flag(2 * pn + i, rdy, cnt_x(bm) + (lane & 15), ep1 * 9 - 6 + 2 * l);
            e_expect_tx(sb + B_QF + 8 * i, 16384);
            tma_ld(sb + i * QSTG + (po ^ 1) * 16384, &prm.m[M_XSO], (2 * pn + i) * 64, (pm ^ 1) * 128, sb + B_QF + 8 * i);
            if (i == 0) q_a(2);
          }
          mbar_wait(sb + B_QF + 8, 0);
        }
#pragma unroll 1
        for (int i = l ? 3 : 4; i < 16; i++) {
          if (l == 3 && i == 12) poll_ge(cnt_ad(bn), ep1 * 16);
          q_b(i); q_a(i);
        }
        if (l & 1) {
          const int krow = 2 * bn * 2048 + bm * 256;
          uint32_t* kvc = cnt_kv(l >> 1, bn);
          uint32_t seen = 0;
#pragma unroll 1
          for (int it = 1; it < 16; it++) {
            const int s = it & 3;
            if (it == 4) {
              bar_sync(NB_KV + 12, 288);
              mbar_wait(sb + B_TF + 24, 0);
#pragma unroll 1
              for (int i = 0; i < 4; i++) tma_st(&prm.m[M_K + (i & 1)], 0, krow + 2048 + (i >> 1) * 128, sb + i * 8192);
              bulk_commit();
            }
            if (it == 5) { bulk_wait_n<0>(); e_red(kvc + 16 + bm); }
            if (it == 12) { e_expect_tx(sb + B_RF, 32768); tma_ld3(sb + RES, &prm.m[M_XSR], 0, pm * 128, 2 * pn, sb + B_RF); }
            if (it == 1 || it == 3) mbar_wait(sb + B_QE + 12 + 4 * it, 1);
            mbar_wait(sb + B_TE + 8 * s, ((it >> 2) & 1) ^ 1);
            if (it < 8) {
#pragma unroll 1
              for (uint32_t n = 0; n < 200000u && (~seen & (3u << (2 * it - 2) | (it == 4 ? 0xC000u : 0u))); n++)
                seen = __ballot_sync(~0u, (int)(ld_acquire(kvc + (lane < 7 || lane == 15 ? (bm + 1 + lane) & 7 : 8 + ((bm + 2 + lane) & 7))) - ep1) >= 0);
              fence_async_gl();
            } else if (it == 8) { poll_ge(kvc + 16 + (lane & 7), ep1); fence_async_gl(); }
            e_expect_tx(sb + B_TF + 8 * s, 32768);
#pragma unroll 1
            for (int i = 0; i < 2; i++) {
              const int u = 2 * it - 2 + i;
              const int row = 2 * bn * 2048 + (it > 7 ? 2048 + ((bm + it) & 7) * 256 + i * 128 : u < 7 ? ((bm + 1 + u) & 7) * 256 : ((bm + 2 + u) & 7) * 256 + 128);
              tma_ld(sb + T0 + s * TSTG + i * 8192, &prm.m[M_K], 0, row, sb + B_TF + 8 * s);
              tma_ld(sb + T0 + s * TSTG + 16384 + i * 8192, &prm.m[M_V], 0, row, sb + B_TF + 8 * s);
            }
          }
        }
        auto p_b = [&](int i, uint32_t s, uint32_t par) {
          mbar_wait(sb + B_PE + 8 * s, par ^ 1);
          e_expect_tx(sb + B_PF + 8 * s, PSTG);
          tma_ld5(sb + pslot_b(s), mo, i >> 3, 2 * (i & 7), 2 * pn, sb + B_PF + 8 * s);
        };
        auto p_a = [&](int i, uint32_t s) {
          await_flag(i, rdy, cnt_o(l, pm, (lane >> 3) & 1) + (lane & 7), ep1 * 2);
          tma_ld_mc(sb + pslot_a(s, l) + rank * 8192, &prm.m[M_OS], i * 64, pm * 128 + rank * 64, sb + B_PF + 8 * s);
        };
        auto p_a2 = [&](int i) {
          await_flag(i, rdy, cnt_o(l, pm, (lane >> 3) & 1) + (lane & 7), ep1 * 2);
          tma_ld(sb + pslot_a(i, l), &prm.m[M_OS], i * 64, pm * 128, sb + B_PF + 8 * i);
          tma_ld(sb + pslot_a(i, l) + 8192, &prm.m[M_OS], i * 64, pm * 128 + 64, sb + B_PF + 8 * i);
        };
        rdy = 0;
        if (l & 1) {
#pragma unroll 1
          for (int u = 0; u < 6; u++) { const int i = (0x205413 >> (4 * u)) & 7; if (u == 4) mbar_wait(sb + B_TE, 1); p_b(i, i, i < 4 ? 1 : 0); }
#pragma unroll 1
          for (int u = 0; u < 6; u++) {
            const int i = (0x542130 >> (4 * u)) & 7;
            if (!(u & 1)) mbar_wait(sb + B_TE + 8 + 4 * u, 1);
            if (u == 4) bar_sync(NB_SIG + 3, 192);
            p_a2(i);
          }
        } else {
#pragma unroll 1
          for (int u = 0; u < 6; u++) { const int i = (0x543120 >> (4 * u)) & 7; if (u == 0 || u == 2) mbar_wait(sb + B_QE + 8 - 4 * u, 1); p_b(i, i, 0); }
          mbar_wait(sb + B_QE + 24, 1);
          e_expect_tx(sb + B_RF, 32768);
          tma_ld3(sb + RES, &prm.m[l == 0 ? M_X0R : M_XSR], 0, pm * 128, 2 * pn, sb + B_RF);
          p_a2(0);
          bar_sync(NB_SIG + 2, 320);
          e_arrive_both(sb + B_PA);
          p_a2(1);
          mbar_wait(sb + B_PA, (l >> 1) & 1);
#pragma unroll 1
          for (int i = 2; i < 6; i++) { if (i > 2) mbar_wait(sb + B_PF + 8 * (i - 3), 0); p_a(i, i); }
        }
        uint32_t s = 0, lap = 1;
#pragma unroll 1
        for (int i = 6; i < 16; i++) {
          p_b(i, s, ((s < 4 ? l : 0) + lap) & 1);
          p_a(i, s);
          if (++s == 6) { s = 0; lap++; }
        }
        const CUtensorMap* mn = &prm.m[M_WQA + ((l + 1) & 1)];
        if (l < 3) {
          mbar_wait(sb + B_PE + 8 * 4, 1); mbar_wait(sb + B_PE + 8 * 5, 1);
          tma_ld3(sb + 32768, mn, bn * 64, 2 * pn * 64, 0, sb + B_QL);
          mbar_wait(sb + B_PE + 8 * 0, l & 1);
          tma_ld3(sb + QSTG + 32768, mn, bn * 64, (2 * pn + 1) * 64, 0, sb + B_QL);
          mbar_wait(sb + B_PE + 8 * 1, l & 1);
          e_expect_tx(sb + B_QF + 16, QSTG);
          tma_ld3(sb + 2 * QSTG + 32768, mn, bn * 64, ((2 * pn) ^ 2) * 64, 0, sb + B_QF + 16);
        }
        if (l < 3) { bar_sync(NB_X, 320); e_expect_tx(sb + B_QL, 49152); }
      }
      if (blockIdx.x == 0 && lane_id() == 0) *(volatile uint32_t*)&g_epoch = ep1;
    } else {
      const int hw = w - 1;
      if (lane < 5) asm volatile("prefetch.tensormap [%0];" ::"l"(&prm.m[5 * hw + lane]) : "memory");
      __syncwarp();
      cluster_wait();
      mbar_wait(sb + B_QF, 0);
#pragma unroll 1
      for (int l = 0; l < 4; l++) {
        IDS();
        if (l > 0) { mbar_wait(sb + B_QL, (l + 1) & 1); mbar_wait(sb + B_QF + 24, 0); }
        if (l == 0) {
#pragma unroll 1
          for (int r = 2 * hw; r < 16; r += 6) {
            const uint4* p = (const uint4*)(prm.x0 + (size_t)(b * 16 + r) * 1024) + lane;
            float s1[2] = {0.f, 0.f}, s2[2] = {0.f, 0.f};
#pragma unroll
            for (int i = 0; i < 8; i++) {
              const uint4 v = __ldg(p + 32 * i);
              const uint32_t u[4] = {v.x, v.y, v.z, v.w};
#pragma unroll
              for (int k = 0; k < 4; k++) { const float a = bf_lo(u[k]), c = bf_hi(u[k]); s1[i >> 2] += a + c; s2[i >> 2] = fmaf(a, a, fmaf(c, c, s2[i >> 2])); }
            }
#pragma unroll
            for (int o = 16; o; o >>= 1)
#pragma unroll
              for (int rr = 0; rr < 2; rr++) { s1[rr] += __shfl_xor_sync(~0u, s1[rr], o); s2[rr] += __shfl_xor_sync(~0u, s2[rr], o); }
            if (lane == 0) *(float4*)&g_stats[b * 16 + r] = make_float4(s1[0], s2[0], s1[1], s2[1]);
          }
        }
        if (l < 2) {
          float cs[8];
#pragma unroll
          for (int i = 0; i < 8; i++) cs[i] = 0.f;
          const uint4* wp = (const uint4*)(prm.wq[l] + (size_t)(bm * 128 + (lane >> 3)) * 3072 + hw * 1024 + bn * 64) + (lane & 7);
#pragma unroll 8
          for (int i = 0; i < 32; i++) {
            const uint4 v = __ldg(wp + (size_t)i * 4 * 384);
            cs[0] += bf_lo(v.x); cs[1] += bf_hi(v.x); cs[2] += bf_lo(v.y); cs[3] += bf_hi(v.y);
            cs[4] += bf_lo(v.z); cs[5] += bf_hi(v.z); cs[6] += bf_lo(v.w); cs[7] += bf_hi(v.w);
          }
#pragma unroll
          for (int i = 0; i < 8; i++) { cs[i] += __shfl_xor_sync(~0u, cs[i], 8); cs[i] += __shfl_xor_sync(~0u, cs[i], 16); }
          if (lane < 8) {
            float4* d = (float4*)(g_csp + ((l * 16 + bn) * 8 + bm) * 192 + hw * 64 + lane * 8);
            d[0] = make_float4(cs[0], cs[1], cs[2], cs[3]); d[1] = make_float4(cs[4], cs[5], cs[6], cs[7]);
          }
          __syncwarp();
          asm volatile("fence.acq_rel.gpu;" ::: "memory");
          e_red_relaxed(cnt_cs(l, bn));
          if (l == 0) e_red_relaxed(cnt_x(bm) + bn);
          poll_ge(lane < 16 && l == 0 ? cnt_x(bm) + lane : cnt_cs(l, bn), lane < 16 && l == 0 ? ep1 * 9 - 6 : ep1 * 24);
        }
        if (l > 0) poll_ge(cnt_x(bm) + (lane & 15), ep1 * 9 - 6 + 2 * l);
#pragma unroll 1
        for (int it = hw * 32 + lane; it < 176; it += 96) {
          const bool rows = it < 128;
          const float4* p = rows ? (const float4*)(g_stats + bm * 256) + it : (const float4*)(g_csp + ((l & 1) * 16 + bn) * 8 * 192) + (it - 128);
          const int stride = rows ? 1024 : 48, np = rows && l == 0 ? 1 : 8;
          float4 a = make_float4(0.f, 0.f, 0.f, 0.f);
#pragma unroll
          for (int k = 0; k < 8; k++) if (k < np) { const float4 v = __ldcg(p + k * stride); a.x += v.x; a.y += v.y; a.z += v.z; a.w += v.w; }
          if (rows) {
            const float m0 = a.x * (1.f / 1024.f), m1 = a.z * (1.f / 1024.f);
            const float v0 = fmaxf(a.y * (1.f / 1024.f) - m0 * m0, 0.f), v1 = fmaxf(a.w * (1.f / 1024.f) - m1 * m1, 0.f);
            const float r0 = __fdividef(1.f, bf_round(sqrtf(bf_round(bf_round(v0) + 1e-5f)))), r1 = __fdividef(1.f, bf_round(sqrtf(bf_round(bf_round(v1) + 1e-5f))));
            a = make_float4(r0, -bf_round(m0), r1, -bf_round(m1));
          }
          if (rows && (l & 1) && (it & 4)) a = make_float4(a.y, a.x, a.w, a.z);
          *(float4*)(smem + ROWST + it * 16) = a;
        }
        __syncwarp();
        if (lane == 0) asm volatile("red.release.cta.shared.add.u32 [%0], 1;" ::"r"(sb + W_X) : "memory");
        if (hw == 2) {
          if (!(l & 1)) {
            bar_sync(NB_ST, 288);
            const uint4* hp = g_halo + (b - 16) * 384 + lane;
#pragma unroll 1
            for (int h = 0; h < 2; h++) {
              uint32_t t[18];
#pragma unroll
              for (int i = 0; i < 18; i++) t[i] = 0;
#pragma unroll 1
              for (uint32_t n = bm ? 0 : 100000u; n < 100000u; n++) {
                uint32_t miss = 0;
#pragma unroll
                for (int i = 0; i < 6; i++) miss |= ld_tagged(hp + h * 192 + i * 32, &t[3 * i]) ^ (4 * ep1 + l);
                if (__all_sync(~0u, !miss)) break;
              }
              mbar_wait(sb + B_QE + 16, 1);
              const uint32_t r = (lane & 7) + ((lane >> 3) & 1) * 8, rv = lane >> 2;
#pragma unroll
              for (int jj = 0; jj < 2; jj++) stsm4(sb + KSC + r * 128 + (((4 * h + 2 * jj + (lane >> 4)) ^ (r & 7)) << 4), t[4 * jj], t[4 * jj + 1], t[4 * jj + 2], t[4 * jj + 3]);
              const uint32_t ad = sb + VSC + rv * 128 + (((4 * h + (lane & 3)) ^ (rv & 7)) << 4);
              sts128(ad, t[8], t[10], t[12], t[14]); sts128(ad + 1024, t[9], t[11], t[13], t[15]);
              if (h == 0 && !(lane & 2)) *(uint32_t*)(smem + HRS + ((lane >> 2) + 8 * (lane & 1)) * 8) = t[16];
              bar_arrive(NB_HALO + h, 64);
            }
          } else {
            bar_sync(NB_KV, 288);
            sts128(sb + ONES + lane * 32, 0x3f803f80u, 0x3f803f80u, 0x3f803f80u, 0x3f803f80u);
            sts128(sb + ONES + lane * 32 + 16, 0x3f803f80u, 0x3f803f80u, 0x3f803f80u, 0x3f803f80u);
            sts128(sb + ROWST + 16, 0x62A962A9u, 0x00010001u, 0x3F003F00u, 0u);
            fence_async_smem();
            __syncwarp();
            e_arrive(sb + B_TF);
            mbar_wait(sb + B_TF + 16, 0); mbar_wait(sb + B_TF + 16, 1);
            poll_ge(cnt_kv(l >> 1, bn) + 16 + (lane & 7), ep1);
            const uint4 v = __ldcg((const uint4*)(g_kn + ((l >> 1) * 128 + bn * 8) * 16) + lane);
            const uint32_t mx = max(max(v.x, v.y), max(v.z, v.w));
            const uint32_t m0 = __reduce_max_sync(~0u, (lane & 2) ? 0u : mx), m1 = __reduce_max_sync(~0u, (lane & 2) ? mx : 0u);
            if (lane == 0) *(uint2*)(smem + ROWST) = make_uint2(m0, m1);
            __syncwarp();
            bar_arrive(NB_KN, 160); bar_arrive(NB_KN + 1, 160);
          }
        } else {
          if (l & 1) {
            uint32_t* p = cnt_kv(l >> 1, bn) + 8 * hw + bm;
            int on = lane == 0;
            PREPARED(p, on);
            bar_sync(hw ? NB_HALO : NB_DONE, 160);
            tma_st(&prm.m[M_K], 0, 2 * bn * 2048 + bm * 256 + hw * 128, sb + T0 + hw * 8192);
            tma_st(&prm.m[M_V], 0, 2 * bn * 2048 + bm * 256 + hw * 128, sb + T0 + 16384 + hw * 8192);
            bulk_commit(); bulk_wait_n<0>();
            release_add(p, on);
          }
#pragma unroll 1
          for (int h = l & 1 ? 0 : hw; h <= (l & 1 ? 1 : hw); h++) {
            uint32_t* p = l == 1 && lane == 1 ? cnt_ad(bn) : cnt_o(l, 2 * bm + (l & 1 ? hw : lane & 1), h) + (bn >> 1);
            int on = lane == 0 || (lane == 1 && (!(l & 1) || (l == 1 && h == 1)));
            int id = NB_SIG + 2 * h + (l & hw), n = (l & 1 ? 160 : 288) + 32 * (h & hw);
            asm volatile("" : "+r"(id), "+r"(n));
            PREPARED(p, on);
            bar_sync(id, n);
            release_add(p, on);
          }
        }
        if (hw < 2 && l < 3) {
          uint32_t* p = cnt_x(bm) + 2 * pn + hw;
          int on = lane == 0;
          PREPARED(p, on);
          if (hw) {
            bar_sync(NB_X, 320);
            tma_st(&prm.m[M_XSO], pn * 128 + 64, pm * 128, sb + QSTG + po * 16384);
            bulk_commit();
            bar_sync(NB_KV, 288);
            bulk_wait_n<0>();
          } else bar_sync(NB_X0, 288);
          release_add(p, on);
        }
      }
    }
  } else {
    asm volatile("setmaxnreg.inc.sync.aligned.u32 224;");
    const uint32_t zero = prm.zero;
    cluster_wait();
#pragma unroll 1
    for (int l = 0; l < 4; l++) {
      {
        float acc[2][96];
#pragma unroll
        for (int i = 0; i < 96; i++) { acc[0][i] = 0.f; acc[1][i] = 0.f; }
        fence_regs(acc[0]); fence_regs(acc[1]);
        const bool early = l > 0 && wg == ((cta_id() >> 3) & 1);
        uint32_t ep1 = 0;
#pragma unroll 1
        for (int kt = 0; kt < 13; kt++) {
          const int s = kt == 12 ? 1 : kt & 3;
          if (l > 0 && kt == 0) mbar_wait(sb + B_QL, (l + 1) & 1);
          if (!(early && kt < 2)) mbar_wait(sb + B_QF + 8 * s, (kt >> 2) & 1);
          const uint64_t da = prm.xd + wg * 1024 + s * (QSTG >> 4), db = prm.wd + s * (QSTG >> 4);
          wg_fence();
#pragma unroll
          for (int k = 0; k < 4; k++)
#pragma unroll
            for (int m = 0; m < 2; m++) wgmma_m64n192k16_ss_tb(acc[m], da + m * 512 + k * 2, db + k * 128, 1);
          wg_commit();
          if (kt == 4) ep1 = *(volatile uint32_t*)&g_epoch + 1;
          wg_wait<1>();
          if (early && (kt == 1 || kt == 2)) mbar_wait(sb + B_QF + 8 * (kt - 1), 0);
          if (kt > 0 && w == 0) e_arrive_both(sb + B_QE + 8 * ((kt - 1) & 3));
        }
        {
          const bool lag = (l & 1) == wg;
          const uint32_t s0 = 2 * (~l & 1);
          const uint64_t da = prm.xd + wg * 1024 + 2 * (QSTG >> 4), db = prm.wd + 2 * (QSTG >> 4);
          mbar_wait(sb + B_QF + 8 * s0, 1);
#pragma unroll
          for (int t = 0; t < 2; t++) {
            if (lag && t != wg) {
              wg_wait<0>();
              if (w == 0) e_arrive_both(sb + B_QE + 8 + 8 * t);
              if (t == 0) mbar_wait(sb + B_QF + 16, 1);
              mbar_wait(sb + B_QF + 24, 1);
              if (t == 1) bar_arrive(NB_ST, 288);
              bar_sync(NB_SC, 256);
            }
            const uint64_t so = (uint64_t)(t ? s0 : s0 ^ 2) * (QSTG >> 4);
            wg_fence();
#pragma unroll
            for (int k = 0; k < 4; k++)
#pragma unroll
              for (int m = 0; m < 2; m++) wgmma_m64n192k16_ss_tb(acc[m], da - so + m * 512 + k * 2, db - so + k * 128, 1);
            wg_commit();
            if (!lag || t + wg == 0) {
              wg_wait<1>();
              if (w == 0) e_arrive_both(sb + B_QE + 8 * (t ? s0 : 1));
              mbar_wait(sb + B_QF + 8 * (t ? 3 : s0 ^ 2), 1);
            }
          }
          wg_fence();
#pragma unroll
          for (int m = 1; m >= 0; m--) {
#pragma unroll
            for (int k = 0; k < 4; k++) wgmma_m64n192k16_ss_tb(acc[m], da + (QSTG >> 4) + m * 512 + k * 2, db + (QSTG >> 4) + k * 128, 1);
            wg_commit();
          }
          if (!lag) { bar_arrive(NB_SC, 256); if (wg) bar_arrive(NB_ST, 288); }
          wg_wait<2>();
          if (w == 0) { e_arrive_both(sb + B_QE + 8 * (s0 ^ 2)); if (lag && wg) e_arrive_both(sb + B_QE); }
        }
#pragma unroll 1
        for (uint32_t n = 0; n < 4000000u; n++) {
          uint32_t v;
          asm volatile("ld.acquire.cta.shared.u32 %0, [%1];" : "=r"(v) : "r"(sb + W_X) : "memory");
          if (v == (uint32_t)(3 * l + 3)) break;
        }
        IDS();
        const int g = lane >> 2, qd = lane & 3;
        float2 st[2][2];
#pragma unroll
        for (int m = 0; m < 2; m++)
#pragma unroll
          for (int hh = 0; hh < 2; hh++) st[m][hh] = lds64f(sb + ROWST + (wg * 128 + m * 64 + w * 16 + g + 8 * hh) * 8);
        float2 cs[4];
        auto load_cs = [&](int gi) {
#pragma unroll
          for (int j = 0; j < 4; j++) cs[j] = lds64f(sb + COLS + (gi * 32 + j * 8 + 2 * qd) * 4);
        };
        load_cs(2 + 2 * (l & 1));
        auto drain = [&]() {
          wg_wait<0>(); fence_regs(acc[0]);
          if (w == 0) e_arrive_both(sb + B_QE + 8 * 3);
        };
        wg_wait<1>(); fence_regs(acc[1]);
        auto norm_tile = [&](int gi, int m, float sc, uint32_t (&t)[8], float (&nrm)[2], bool h16 = false) {
          const float r0 = st[m][0].x * sc, s0 = st[m][0].y, r1 = st[m][1].y * sc, s1 = st[m][1].x;
          float n0 = 0.f, n1 = 0.f;
#pragma unroll
          for (int j = 0; j < 4; j++) {
            const float* a = &acc[m][16 * gi + 4 * j];
            const float v0 = fmaf(s0, cs[j].x, a[0]) * r0, v1 = fmaf(s0, cs[j].y, a[1]) * r0;
            const float v2 = fmaf(s1, cs[j].x, a[2]) * r1, v3 = fmaf(s1, cs[j].y, a[3]) * r1;
            n0 = fmaf(v0, v0, fmaf(v1, v1, n0)); n1 = fmaf(v2, v2, fmaf(v3, v3, n1));
            t[2 * j] = h16 ? pack2h(v0, v1) : pack2(v0, v1); t[2 * j + 1] = h16 ? pack2h(v2, v3) : pack2(v2, v3);
          }
          nrm[0] = n0; nrm[1] = n1;
        };
        auto norm_group = [&](int gi, float sc, uint32_t (&t)[2][8], float (&nrm)[2][2]) { norm_tile(gi, 0, sc, t[0], nrm[0]); norm_tile(gi, 1, sc, t[1], nrm[1]); };
        uint32_t q[2][2][8];
        const uint32_t srow = (lane & 7) + ((lane >> 3) & 1) * 8;
        const uint32_t row0 = wg * 128 + w * 16;
        if (!(l & 1)) {
          auto put_kv = [&](int gi, uint32_t r0, const uint32_t (&t)[8]) {
            if (gi < 4) {
              const uint32_t r = r0 + srow;
#pragma unroll
              for (int jj = 0; jj < 2; jj++) stsm4(sb + KSC + r * 128 + (((4 * (gi - 2) + 2 * jj + (lane >> 4)) ^ (r & 7)) << 4), t[4 * jj], t[4 * jj + 1], t[4 * jj + 2], t[4 * jj + 3]);
            } else {
              const uint32_t r = r0 + g, ad = sb + VSC + r * 128 + (((4 * (gi - 4) + qd) ^ (r & 7)) << 4);
              sts128(ad, t[0], t[2], t[4], t[6]); sts128(ad + 1024, t[1], t[3], t[5], t[7]);
            }
          };
          auto cen_tile = [&](int gi, int m, uint32_t (&t)[8]) {
#pragma unroll
            for (int j = 0; j < 4; j++) {
              const float* a = &acc[m][16 * gi + 4 * j];
              t[2 * j] = pack2(fmaf(st[m][0].y, cs[j].x, a[0]), fmaf(st[m][0].y, cs[j].y, a[1]));
              t[2 * j + 1] = pack2(fmaf(st[m][1].y, cs[j].x, a[2]), fmaf(st[m][1].y, cs[j].y, a[3]));
            }
          };
          const bool send = wg == 1 && w == 3 && bm < 7;
          uint4* hp = g_halo + b * 384 + lane;
          ep1 = 4 * ep1 + l;
          mbar_wait(sb + B_QE + 16, 1);
          float2 cn[4];
          auto next_cs = [&](int gi) {
#pragma unroll
            for (int j = 0; j < 4; j++) { cs[j] = cn[j]; cn[j] = lds64f(sb + COLS + (gi * 32 + j * 8 + 2 * qd) * 4); }
          };
#pragma unroll
          for (int j = 0; j < 4; j++) cn[j] = cs[j];
#pragma unroll
          for (int h = 0; h < 2; h++) {
            uint32_t k[8], v[8];
            next_cs(4 + h);
            cen_tile(2 + h, 1, k); put_kv(2 + h, 16 + row0 + 64, k);
            next_cs(h ? 2 : 3);
            cen_tile(4 + h, 1, v); put_kv(4 + h, 16 + row0 + 64, v);
            if (send) {
              uint4* p = hp + h * 192;
              st_tagged(p, k[0], k[1], k[2], ep1); st_tagged(p + 32, k[3], k[4], k[5], ep1); st_tagged(p + 64, k[6], k[7], v[0], ep1);
              st_tagged(p + 96, v[1], v[2], v[3], ep1); st_tagged(p + 128, v[4], v[5], v[6], ep1);
              st_tagged(p + 160, v[7], __float_as_uint(qd & 1 ? st[1][1].x : st[1][0].x), 0u, ep1);
            }
            sched_fence();
          }
          drain();
          {
            uint32_t t[8];
            next_cs(4); cen_tile(2, 0, t); put_kv(2, 16 + row0, t);
            next_cs(0); cen_tile(4, 0, t); put_kv(4, 16 + row0, t);
            next_cs(3); cen_tile(0, 0, q[0][0]); cen_tile(0, 1, q[0][1]);
          }
          const bool e = g & 1, sel = 2 * qd + (g & 1) >= g + 2, first = bm == 0 && row0 == 0;
          uint32_t ka = sb + KSC + (row0 + (lane & 7)) * 128 + (((lane >> 3) ^ (lane & 7)) << 4);
          uint32_t wa = sb + VSC + (row0 + srow) * 128 + (((lane >> 4) ^ (lane & 7)) << 4);
          uint32_t psel[3] = {e ? 0x1044u : 0x4410u, !sel ? 0x4444u : e ? 0x3244u : 0x4432u, sel ? 0x4444u : e ? 0x3244u : 0x4432u};
          bf16* op = g_os + (size_t)(bm * 256 + row0 + g) * 1024 + bn * 32 + qd * 8;
          asm volatile("" : "+r"(ka), "+r"(wa), "+l"(op));
          fence_regs(psel); fence_regs(q[0][0]); fence_regs(q[0][1]);
          sched_fence();
          bar_sync(NB_SC, 256);
          if (row0 == 0) bar_sync(NB_HALO, 64);
          float ra[4], rb[4], ca[4], cb[4];
#pragma unroll
          for (int m = 0; m < 2; m++) {
            float rk[3];
#pragma unroll
            for (int u = 0; u < 3; u++) {
              const int r = row0 + m * 64 + 8 * u + 2 * qd + e - (sel ? 16 : 8);
              rk[u] = lds64f(sb + (m == 0 && r < 0 ? HRS + 128 : ROWST) + r * 8).x;
            }
            ra[2 * m] = sel ? rk[1] : rk[0]; ra[2 * m + 1] = sel ? rk[2] : rk[1];
            rb[2 * m] = sel ? rk[0] : rk[1]; rb[2 * m + 1] = sel ? rk[1] : rk[2];
          }
#pragma unroll
          for (int i = 0; i < 4; i++) { const float rq = st[i >> 1][i & 1].x * QSCALE; ca[i] = rq * ra[i]; cb[i] = rq * rb[i]; }
#pragma unroll 1
          for (int h = 0; h < 2; h++) {
            float s[2][4][4];
            uint32_t vf[2][4][4], pf[2][2][4];
#pragma unroll
            for (int m = 0; m < 2; m++)
#pragma unroll
              for (int nt = 0; nt < 4; nt++) {
                uint32_t kf[4];
                ldsm4(ka + (m * 64 + 8 * nt) * 128, kf);
                s[m][nt][0] = s[m][nt][1] = s[m][nt][2] = s[m][nt][3] = 0.f;
                mma16816(s[m][nt], q[0][m][0], q[0][m][1], q[0][m][2], q[0][m][3], kf[0], kf[1]);
                mma16816(s[m][nt], q[0][m][4], q[0][m][5], q[0][m][6], q[0][m][7], kf[2], kf[3]);
              }
#pragma unroll
            for (int m = 0; m < 2; m++)
#pragma unroll
              for (int i = 0; i < 4; i++) {
                ldsm4t((wa ^ (32 * (i & 1))) + (m * 64 + 16 * (i >> 1)) * 128, vf[m][i]);
              }
            float va[4], vb[4], mx[4];
#pragma unroll
            for (int i = 0; i < 4; i++) {
              const int m = i >> 1, hh = i & 1;
              const float a = e ? s[m][hh + 1][2 * hh + 1] : s[m][hh + 1][2 * hh];
              const float lo = e ? s[m][hh][2 * hh + 1] : s[m][hh][2 * hh], hi = e ? s[m][hh + 2][2 * hh + 1] : s[m][hh + 2][2 * hh];
              va[i] = (m == 0 && hh == 0 && first) ? -INFINITY : a * ca[i];
              vb[i] = (m == 0 && first && sel) ? -INFINITY : (sel ? lo : hi) * cb[i];
              mx[i] = fmaxf(va[i], vb[i]);
            }
#pragma unroll
            for (int i = 0; i < 4; i++) mx[i] = fmaxf(mx[i], __shfl_xor_sync(~0u, mx[i], 1));
#pragma unroll
            for (int i = 0; i < 4; i++) mx[i] = fmaxf(mx[i], __shfl_xor_sync(~0u, mx[i], 2));
#pragma unroll
            for (int i = 0; i < 4; i++) {
              va[i] = ex2(va[i] - mx[i]); vb[i] = ex2(vb[i] - mx[i]);
              mx[i] = va[i] + vb[i];
              va[i] *= ra[i]; vb[i] *= rb[i];
            }
#pragma unroll
            for (int i = 0; i < 4; i++) mx[i] += __shfl_xor_sync(~0u, mx[i], 1);
#pragma unroll
            for (int i = 0; i < 4; i++) mx[i] += __shfl_xor_sync(~0u, mx[i], 2);
#pragma unroll
            for (int i = 0; i < 4; i++) {
              const int m = i >> 1, hh = i & 1;
              const float inv = rcp(mx[i]);
              const uint32_t t = pack2(va[i] * inv, vb[i] * inv);
              pf[m][hh][hh + 1] = prmt0(t, psel[0]); pf[m][hh][hh] = prmt0(t, psel[1]); pf[m][hh][hh + 2] = prmt0(t, psel[2]);
              pf[m][hh][3 - 3 * hh] = t & zero;
            }
#pragma unroll
            for (int m = 0; m < 2; m++) {
              float o[4][4];
#pragma unroll
              for (int j = 0; j < 4; j++) o[j][0] = o[j][1] = o[j][2] = o[j][3] = 0.f;
#pragma unroll
              for (int i = 0; i < 4; i++) {
                const int kk = i >> 1, jj = 2 * (i & 1);
                mma16816(o[jj], pf[m][0][2 * kk], pf[m][1][2 * kk], pf[m][0][2 * kk + 1], pf[m][1][2 * kk + 1], vf[m][i][0], vf[m][i][1]);
                mma16816(o[jj + 1], pf[m][0][2 * kk], pf[m][1][2 * kk], pf[m][0][2 * kk + 1], pf[m][1][2 * kk + 1], vf[m][i][2], vf[m][i][3]);
              }
              stg128(op + m * 65536, pack2(o[0][0], o[0][1]), pack2(o[1][0], o[1][1]), pack2(o[2][0], o[2][1]), pack2(o[3][0], o[3][1]));
              stg128(op + m * 65536 + 8192, pack2(o[0][2], o[0][3]), pack2(o[1][2], o[1][3]), pack2(o[2][2], o[2][3]), pack2(o[3][2], o[3][3]));
            }
            bar_arrive(NB_SIG + 2 * h, 288 + 32 * h);
            if (h == 0) {
              uint32_t t[8];
              next_cs(5); cen_tile(3, 0, t); put_kv(3, 16 + row0, t);
              next_cs(1); cen_tile(5, 0, t); put_kv(5, 16 + row0, t);
#pragma unroll
              for (int j = 0; j < 4; j++) cs[j] = cn[j];
              cen_tile(1, 0, q[0][0]); cen_tile(1, 1, q[0][1]);
              ka ^= 64; wa ^= 64; op += 512;
              bar_sync(NB_SC, 256);
              if (row0 == 0) bar_sync(NB_HALO + 1, 64);
            }
          }
        } else {
          float qn[2];
          mbar_wait(sb + B_QE + 8, 1);
          drain();
          auto esc_ptr = [&](int gi) { IDS(); return g_esc + (size_t)(((l & 2) + (gi >> 1)) * 65536 + (2 * bn + (gi & 1)) * 2048) * 20; };
          auto norm_half = [&](int gi, float sc, uint32_t (&t)[2][8], float (&nrm)[2][2], int nx) {
            norm_tile(gi, 0, sc, t[0], nrm[0], true); norm_tile(gi, 1, sc, t[1], nrm[1], true);
            float2 cn[4];
#pragma unroll
            for (int j = 0; j < 4; j++) if (nx >= 0) cn[j] = lds64f(sb + COLS + (nx * 32 + j * 8 + 2 * qd) * 4);
            if (!((nrm[0][0] + nrm[0][1]) + (nrm[1][0] + nrm[1][1]) <= 4e9f) || fminf(fminf(nrm[0][0], nrm[0][1]), fminf(nrm[1][0], nrm[1][1])) < 1.5e-5f) {
              uint32_t* p = esc_ptr(gi) + (bm * 256 + row0 + g) * 20 + qd;
#pragma unroll
              for (int m = 0; m < 2; m++) {
                uint32_t u[8]; float d[2];
                norm_tile(gi, m, sc, u, d);
#pragma unroll
                for (int i = 0; i < 10; i++) p[(m * 64 + (i & 1) * 8) * 20 + (i >> 1) * 4] = i < 8 ? u[i] : ep1;
              }
            }
            __syncwarp();
#pragma unroll
            for (int i = 0; i < 16; i++) asm volatile("{\n.reg .b32 u;\nadd.u32 u, %0, 0x00040004;\nand.b32 %0, u, 0xFFF8FFF8;\n}" : "+r"(t[i >> 3][i & 7]));
#pragma unroll
            for (int j = 0; j < 4; j++) if (nx >= 0) cs[j] = cn[j];
          };
          {
            auto max_norm = [&](const float (&nrm)[2][2]) {
              const bool o1 = qd & 1, o2 = qd & 2;
              const float a = (o1 ? nrm[1][0] : nrm[0][0]) + __shfl_xor_sync(~0u, o1 ? nrm[0][0] : nrm[1][0], 1);
              const float c = (o1 ? nrm[1][1] : nrm[0][1]) + __shfl_xor_sync(~0u, o1 ? nrm[0][1] : nrm[1][1], 1);
              const float d = (o2 ? c : a) + __shfl_xor_sync(~0u, o2 ? a : c, 2);
              return __uint_as_float(__reduce_max_sync(~0u, __float_as_uint(d)));
            };
#pragma unroll
            for (int h = 0; h < 2; h++) {
              uint32_t t[2][8]; float nrm[2][2];
              const uint32_t kb = sb + (h ? wg * 8192 : T0), vb = kb + (h ? 8192 : 16384);
              norm_group(4 + h, 1.f, t, nrm);
              load_cs(2 + h);
#pragma unroll
              for (int m = 0; m < 2; m++) {
                const uint32_t r = row0 + m * 64 + g, ad = vb + r * 64 + ((qd ^ ((r >> 1) & 3)) << 4);
                sts128(ad, t[m][0], t[m][2], t[m][4], t[m][6]); sts128(ad + 512, t[m][1], t[m][3], t[m][5], t[m][7]);
              }
              norm_half(2 + h, 1.f, t, nrm, h);
#pragma unroll
              for (int i = 0; i < 4; i++) {
                const uint32_t r = row0 + (i >> 1) * 64 + srow;
                stsm4(kb + r * 64 + (((2 * (i & 1) + (lane >> 4)) ^ ((r >> 1) & 3)) << 4), t[i >> 1][4 * (i & 1)], t[i >> 1][4 * (i & 1) + 1], t[i >> 1][4 * (i & 1) + 2], t[i >> 1][4 * (i & 1) + 3]);
              }
              if (h == 1) { const float kn = max_norm(nrm); if (lane == 0) g_kn[((l >> 1) * 128 + bn * 8 + bm) * 16 + 8 + wg * 4 + w] = kn; }
              fence_async_smem();
              bar_arrive(NB_KV + 12 * h, 288);
              if (h == 0) {
                bar_arrive(wg ? NB_HALO : NB_DONE, 160);
              }
              if (h == 0) { const float kn = max_norm(nrm); if (lane == 0) g_kn[((l >> 1) * 128 + bn * 8 + bm) * 16 + wg * 4 + w] = kn; }
              norm_half(h, QSCALE, q[h], nrm, h ? -1 : 5);
#pragma unroll
              for (int i = 0; i < 4 * h; i++) sts128(sb + QPARK + 24576 - wg * 8192 + (w * 32 + lane) * 16 + i * 2048, q[h][i >> 1][4 * (i & 1)], q[h][i >> 1][4 * (i & 1) + 1], q[h][i >> 1][4 * (i & 1) + 2], q[h][i >> 1][4 * (i & 1) + 3]);
              qn[h] = max_norm(nrm);
            }
          }
          constexpr uint64_t VSTEP = 64 - (64ull << 16);
          uint32_t cq[4];
          const uint32_t &c_852 = cq[0], &c_lsb = cq[1], &c_half = cq[2];
          float o[2][20], S[2][32];
          uint32_t H[2][16], P0[4] = {}, P1[4] = {};
#pragma unroll
          for (int m = 0; m < 2; m++) {
#pragma unroll
            for (int i = 0; i < 20; i++) o[m][i] = 0.f;
            fence_regs(o[m]);
          }
          auto qkf = [&](int b, int ks, uint64_t d) { wg_n64_rs_nb_f16_f32(S[b], q[0][0][4 * ks], q[0][0][4 * ks + 1], q[0][0][4 * ks + 2], q[0][0][4 * ks + 3], d + 2 * ks, ks ? 1 : zero); };
          auto qkh = [&](int b, int ks, uint64_t d) { wg_n64_rs_nb_f16_f16(H[b], q[0][1][4 * ks], q[0][1][4 * ks + 1], q[0][1][4 * ks + 2], q[0][1][4 * ks + 3], d + 2 * ks, ks ? 1 : zero); };
          auto pv0 = [&](uint64_t d) { wgmma_m64n40k16_rs_tb(o[0], P0[0], P0[1], P0[2], P0[3], d, 1); };
          auto pv1 = [&](uint64_t d) { wgmma_m64n40k16_rs_tb(o[1], P1[0], P1[1], P1[2], P1[3], d, 1); };
          float e[4] = {};
          auto finish = [&](int h) {
            const float* s = &S[(h >> 2) & 1][8 * (h & 3)];
            const uint32_t* u = &H[(h >> 2) & 1][4 * (h & 3)];
            const float z0 = exp2_fix(s[6]), z1 = exp2_fix(s[7]);
            P0[0] = pack2v(e[0], e[1]);
            P1[0] = exp2_h2(u[0], c_852);
            P0[1] = pack2v(e[2], e[3]);
            P1[1] = exp2_h2(u[1], c_852);
            const uint32_t B = exp2_base(z0, z1), E = and_or<0x7F807F80u>(B, c_lsb);
            P1[3] = exp2_h2(u[3], c_852);
            P0[3] = fma_bf2(B, and_or<0x807F807Fu>(B, c_half), E);
            const float e4 = ex2v(s[4]), e5 = ex2v(s[5]);
            P1[2] = exp2_h2(u[2], c_852);
            P0[2] = pack2v(e4, e5);
          };
          auto start = [&](int h) {
            const float* s = &S[(h >> 2) & 1][8 * (h & 3)];
            e[2] = ex2v(s[2]); e[1] = ex2v(s[1]); e[0] = ex2v(s[0]); e[3] = ex2v(s[3]);
          };
          uint64_t kd = prm.kv[0].kd;
          mbar_wait(sb + B_TF, 0);
          lds128(sb + ROWST + 16 + (lane_id() & zero), cq);
#pragma unroll
          for (int i = 0; i < 4; i++) sts128(sb + QPARK + (wg * 128 + w * 32 + lane_id()) * 16 + i * 4096, q[0][i >> 1][4 * (i & 1)], q[0][i >> 1][4 * (i & 1) + 1], q[0][i >> 1][4 * (i & 1) + 2], q[0][i >> 1][4 * (i & 1) + 3]);
          wg_fence();
#pragma unroll
          for (int b = 0; b < 2; b++) {
            wg_n64_rs_nb_f16_f32_z(S[b], q[0][0][0], q[0][0][1], q[0][0][2], q[0][0][3], kd + 256 * b, 0);
            wg_n64_rs_nb_f16_f16_z(H[b], q[0][1][0], q[0][1][1], q[0][1][2], q[0][1][3], kd + 256 * b, 0);
            if (b == 0) { qkf(0, 1, kd); qkh(0, 1, kd); }
            wg_commit();
          }
          wg_wait<1>(); fence_regs(S[0]); fence_regs(H[0]);
          start(0); finish(0); start(1);
          wg_wait<0>();
          int redo = 0;
#pragma unroll 1
          for (int pass = 0, j = 1; pass < 2; pass++) {
#pragma unroll 1
           do {
            const uint64_t vd = prm.kv[j & 3].vd;
            bool go = false;
#pragma unroll
            for (int h = 2; h < 18; h++) {
              const int px = (h >> 2) + 1, c = h & 3;
              wg_fence();
              if (h == 13) kd = prm.kv[j & 3].kd;
              const uint64_t kx = kd + (px & 3) * 256, vx = vd + (h - 2) * VSTEP;
              if (h == 2) { qkh(1, 0, kx); qkf(1, 0, kx); pv0(vx); pv1(vx); qkh(1, 1, kx); qkf(1, 1, kx); }
              else if ((c == 1 || c == 2) && h < 17) { qkh(px & 1, c - 1, kx); pv1(vx); qkf(px & 1, c - 1, kx); pv0(vx); }
              else { pv0(vx); pv1(vx); }
              wg_commit();
              if (h == 3) e_arrive_if(sb + B_TE + 8 * ((j + 2) & 3), j > 1);
              if (h == 11) go = mbar_test(sb + B_TF + 8 * (j & 3), (j >> 2) & 1) && j != 8;
              finish(h - 1); start(h);
              if (h != 12 && h != 17) sched_fence();
              if (h == 12 && !go) {
                if (j == 16) {
#pragma unroll
                  for (int u = 13; u < 18; u++) {
                    wg_fence(); pv0(vd + (u - 2) * VSTEP); pv1(vd + (u - 2) * VSTEP); wg_commit();
                    if (u < 17) finish(u - 1);
                    if (u < 16) { start(u); sched_fence(); }
                    if (u & 1) { if (u == 17) wg_wait<0>(); else wg_wait<1>(); }
                  }
                  e_arrive(sb + B_TE + 24);
                  goto head_done;
                }
                mbar_wait(sb + B_TF + 8 * (j & 3), (j >> 2) & 1);
                if (j == 8) {
#pragma unroll
                  for (int i = 0; i < 4; i++) lds128(sb + QPARK + 24576 - wg * 8192 + (w * 32 + lane_id()) * 16 + i * 2048, &q[0][i >> 1][4 * (i & 1)]);
                }
              }
              if (h == 17) wg_wait<0>(); else if (h & 1) wg_wait<1>();
              if (c == 3) { fence_regs(S[px & 1]); fence_regs(H[px & 1]); }
            }
           } while (j++ & 7);
           head_done:
            fence_regs(o[0]); fence_regs(o[1]);
            uint32_t pk[2][8];
            {
              IDS();
              bf16* op = g_os + (size_t)(bm * 256 + row0 + (lane >> 2)) * 1024 + pass * 512 + bn * 32 + (lane & 3) * 8;
#pragma unroll
              for (int i = 0; i < 4; i++) {
                const float* a = &o[i >> 1][2 * (i & 1)];
                const float inv = rcp(a[16]);
                uint32_t* u = &pk[i >> 1][4 * (i & 1)];
#pragma unroll
                for (int k = 0; k < 4; k++) u[k] = pack2(a[4 * k] * inv, a[4 * k + 1] * inv);
                *(uint4*)(op + ((i >> 1) * 64 + (i & 1) * 8) * 1024) = make_uint4(u[0], u[1], u[2], u[3]);
              }
            }
            sched_fence();
            if (pass == 0) bar_sync(NB_KN + wg, 160);
            const float kmax = *(volatile float*)(smem + ROWST + 4 * pass);
            const bool wide = !(qn[0] <= 1.6e7f) | !(kmax <= 1.6e7f) | !(qn[0] * kmax <= 112.f * 112.f);
            int badm = 0;
#pragma unroll
            for (int m = 0; m < 2; m++) {
              uint32_t chk[2] = {0u, 0u};
#pragma unroll
              for (int i = 0; i < 8; i++) asm("fma.rn.bf16x2 %0, %1, %2, %0;" : "+r"(chk[i & 1]) : "r"(pk[m][i]), "r"(0u));
              const bool bad = wide | !(fminf(o[m][16], o[m][18]) >= 9.3e-10f) | !(o[m][16] + o[m][18] <= 1e36f) | (((chk[0] | chk[1]) & 0x7FFF7FFFu) != 0);
              badm |= __any_sync(~0u, bad) << m;
            }
            if (!badm) bar_arrive(NB_SIG + 2 * pass + wg, 160 + 32 * (pass & wg));
            qn[0] = qn[1];
#pragma unroll
            for (int m = 0; m < 2; m++) {
#pragma unroll
              for (int i = 0; i < 20; i++) o[m][i] = 0.f;
              fence_regs(o[m]);
            }
            if (badm) {
              redo |= badm << 2 * pass;
              const int tx = wg * 128 + w * 32 + lane_id();
              uint4* p = g_qsave + (block_id() * 256 + tx) * 8 + pass * 4;
#pragma unroll
              for (int i = 0; i < 4; i++) {
                uint32_t u[4] = {q[0][i >> 1][4 * (i & 1)], q[0][i >> 1][4 * (i & 1) + 1], q[0][i >> 1][4 * (i & 1) + 2], q[0][i >> 1][4 * (i & 1) + 3]};
                if (pass == 0) lds128(sb + QPARK + tx * 16 + i * 4096, u);
                p[i] = make_uint4(u[0], u[1], u[2], u[3]);
              }
            }
          }
          if (redo) attn_redo(redo, l, cta_id(), wg, w, ep1);
        }
      }
      {
        float acc[64];
#pragma unroll
        for (int i = 0; i < 64; i++) acc[i] = 0.f;
        fence_regs(acc);
        uint32_t s = 0, lap = 0;
#pragma unroll 1
        for (int kt = 0; kt < 14; kt++) {
          mbar_wait(sb + B_PF + 8 * s, ((s < 4 ? l : 0) + lap) & 1);
          const uint64_t da = mkdesc(sb + pslot_a(s, l) + wg * 8192, 16, 1024, 1), db = mkdesc(sb + pslot_b(s), 8192, 1024, 1);
          wg_fence();
#pragma unroll
          for (int k = 0; k < 4; k++) wgmma_m64n128k16_ss_tb(acc, da + k * 2, db + k * 128, 1);
          wg_commit();
          wg_wait<1>();
          if (kt > 0 && w == 0) e_arrive_both(sb + B_PE + 8 * (s ? s - 1 : 5));
          if (++s == 6) { s = 0; lap++; }
        }
        if (wg) {
          wg_wait<0>();
          if (w == 0) e_arrive_both(sb + B_PE + 8);
#pragma unroll
          for (int t = 2; t < 4; t++) mbar_wait(sb + B_PF + 8 * t, l & 1);
          bar_sync(NB_ST, 256);
        }
#pragma unroll
        for (int t = 2; t < 4; t++) {
          if (!wg) mbar_wait(sb + B_PF + 8 * t, l & 1);
          const uint64_t da = prm.xd + ((pslot_a(t, l) + wg * 8192) >> 4), db = prm.wd + (pslot_b(t) >> 4) - 2048;
          wg_fence();
#pragma unroll
          for (int k = 0; k < 4; k++) wgmma_m64n128k16_ss_tb(acc, da + k * 2, db + k * 128, 1);
          wg_commit();
        }
        if (!wg) {
          bar_arrive(NB_ST, 256);
          wg_wait<2>();
          if (w == 0) e_arrive_both(sb + B_PE + 8);
        }
        IDS();
        const int g = lane >> 2, qd = lane & 3;
        const int r0 = wg * 64 + w * 16;
        const uint32_t r = r0 + (lane & 7) + ((lane >> 3) & 1) * 8;
        uint32_t x[8][4];
        mbar_wait(sb + B_RF, l & 1);
#pragma unroll
        for (int jj = 0; jj < 8; jj++) ldsm4(sb + RES + (jj >> 2) * 16384 + r * 128 + ((((2 * jj + (lane >> 4)) & 7) ^ (r & 7)) << 4), x[jj]);
        wg_wait<0>();
        fence_regs(acc);
        if (w == 0) { e_arrive_both(sb + B_PE + 16); e_arrive_both(sb + B_PE + 24); }
        const CUtensorMap* mo = &prm.m[l == 3 ? M_OUT : M_XST];
#pragma unroll
        for (int jj = 0; jj < 8; jj++) {
#pragma unroll
          for (int i = 0; i < 4; i++) x[jj][i] = add_bf16x2(x[jj][i], pack2(acc[8 * jj + 2 * i], acc[8 * jj + 2 * i + 1]));
          if (jj < 4) stsm4(sb + RES + r * 128 + ((((2 * jj + (lane >> 4)) & 7) ^ (r & 7)) << 4), x[jj][0], x[jj][1], x[jj][2], x[jj][3]);
          if (jj == 3) { fence_async_smem(); __syncwarp(); tma_st(mo, pn * 128, pm * 128 + r0, sb + RES + r0 * 128); bulk_commit(); sched_fence(); }
        }
        if (l == 3) {
#pragma unroll
          for (int jj = 4; jj < 8; jj++) stsm4(sb + RES + 16384 + r * 128 + ((((2 * jj + (lane >> 4)) & 7) ^ (r & 7)) << 4), x[jj][0], x[jj][1], x[jj][2], x[jj][3]);
          fence_async_smem(); __syncwarp();
          tma_st(mo, pn * 128 + 64, pm * 128 + r0, sb + RES + 16384 + r0 * 128);
          bulk_commit(); bulk_wait_n<0>();
        } else {
          bar_sync(NB_SC, 256);
#pragma unroll
          for (int jj = 0; jj < 8; jj++)
            stsm4(sb + (jj >> 2) * QSTG + po * 16384 + r * 128 + ((((2 * jj + (lane >> 4)) & 7) ^ (r & 7)) << 4), x[jj][0], x[jj][1], x[jj][2], x[jj][3]);
          bulk_wait_n<0>();
          bar_arrive(NB_X0, 288);
          fence_async_smem();
          bar_arrive(NB_X, 320);
          float s1[4] = {0.f, 0.f, 0.f, 0.f}, sa[4] = {0.f, 0.f, 0.f, 0.f}, sc[4] = {0.f, 0.f, 0.f, 0.f};
#pragma unroll
          for (int jj = 0; jj < 8; jj++) {
            mma16816(s1, x[jj][0], x[jj][1], x[jj][2], x[jj][3], 0x3f803f80u, 0x3f803f80u);
            mma16816(sa, x[jj][0], x[jj][1], x[jj][2], x[jj][3], x[jj][0], x[jj][2]);
            mma16816(sc, x[jj][0], x[jj][1], x[jj][2], x[jj][3], x[jj][1], x[jj][3]);
          }
          if (qd == g >> 1) {
            float2* p = g_stats + pn * 2048 + pm * 128 + r0 + g;
            p[0] = make_float2(s1[0], g & 1 ? sa[1] : sa[0]);
            p[8] = make_float2(s1[2], g & 1 ? sc[3] : sc[2]);
          }
          bar_arrive(NB_KV, 288);
        }
      }
    }
  }
  asm volatile("barrier.cluster.arrive.relaxed.aligned;\nbarrier.cluster.wait.aligned;" ::: "memory");
}

typedef CUresult (*EncodeFn)(CUtensorMap*, CUtensorMapDataType, cuuint32_t, void*, const cuuint64_t*, const cuuint64_t*, const cuuint32_t*,
                             const cuuint32_t*, CUtensorMapInterleave, CUtensorMapSwizzle, CUtensorMapL2promotion, CUtensorMapFloatOOBfill);

static void make_map(EncodeFn fn, CUtensorMap* m, const void* ptr, int rank, const uint64_t* dims, const uint64_t* strides, const uint32_t* box, CUtensorMapSwizzle sw) {
  cuuint64_t d[5], st[4];
  cuuint32_t bx[5], es[5];
  for (int i = 0; i < rank; i++) { d[i] = dims[i]; bx[i] = box[i]; es[i] = 1; if (i) st[i - 1] = strides[i - 1] * 2; }
  fn(m, CU_TENSOR_MAP_DATA_TYPE_BFLOAT16, rank, (void*)ptr, d, st, bx, es, CU_TENSOR_MAP_INTERLEAVE_NONE, sw,
     CU_TENSOR_MAP_L2_PROMOTION_L2_128B, CU_TENSOR_MAP_FLOAT_OOB_FILL_NONE);
}
static void map2(EncodeFn fn, CUtensorMap* m, const void* ptr, uint64_t inner, uint64_t outer, uint32_t bi, uint32_t bo, CUtensorMapSwizzle sw) {
  const uint64_t d[2] = {inner, outer}, st[1] = {inner};
  const uint32_t bx[2] = {bi, bo};
  make_map(fn, m, ptr, 2, d, st, bx, sw);
}

extern "C" void kernel_launch(void* const* d_in, const int* in_sizes, int n_in, void* d_out, int out_size) {
  (void)in_sizes; (void)n_in; (void)out_size;
  static EncodeFn enc = nullptr;
  static void *xs, *os, *kk, *vv;
  static int sbase = 1024;
  if (!enc) {
    void* p = nullptr;
    cudaDriverEntryPointQueryResult qr;
    cudaGetDriverEntryPoint("cuTensorMapEncodeTiled", &p, cudaEnableDefault, &qr);
    enc = (EncodeFn)p;
    Scratch* sc = nullptr;
    cudaGetSymbolAddress((void**)&sc, g_s);
    xs = sc->xs; os = sc->os; kk = sc->k; vv = sc->v;
    int dev = 0;
    cudaGetDevice(&dev);
    cudaDeviceGetAttribute(&sbase, cudaDevAttrReservedSharedMemoryPerBlock, dev);
    cudaFuncSetAttribute(fused_kernel, cudaFuncAttributeMaxDynamicSharedMemorySize, SMEM_BYTES);
  }
  Params prm;
  const CUtensorMapSwizzle S128 = CU_TENSOR_MAP_SWIZZLE_128B, S64 = CU_TENSOR_MAP_SWIZZLE_64B;
  map2(enc, &prm.m[M_X0A], d_in[0], 1024, 2048, 64, 256, S128);
  map2(enc, &prm.m[M_XSA], xs, 1024, 2048, 64, 256, S128);
  for (int t = 0; t < 2; t++) {
    const uint64_t d3[3] = {1024, 1024, 3}, s3[2] = {3072, 1024};
    const uint32_t b3[3] = {64, 64, 3};
    make_map(enc, &prm.m[M_WQA + t], d_in[1 + 3 * t], 3, d3, s3, b3, S128);
    const uint64_t d5[5] = {64, 32, 2, 16, 16}, s5[4] = {1024, 32 * 1024, 64 * 1024, 64};
    const uint32_t b5[5] = {64, 32, 1, 2, 2};
    make_map(enc, &prm.m[M_WOA + t], d_in[2 + 3 * t], 5, d5, s5, b5, S128);
    const uint64_t dr[3] = {64, 2048, 16}, sr[2] = {1024, 64};
    const uint32_t br[3] = {64, 128, 2};
    make_map(enc, &prm.m[M_X0R + t], t ? xs : d_in[0], 3, dr, sr, br, S128);
  }
  map2(enc, &prm.m[M_OS], os, 1024, 2048, 64, 64, S128);
  map2(enc, &prm.m[M_K], kk, 32, 65536, 32, 128, S64);
  map2(enc, &prm.m[M_V], vv, 32, 65536, 32, 128, S64);
  map2(enc, &prm.m[M_XSO], xs, 1024, 2048, 64, 128, S128);
  map2(enc, &prm.m[M_X0H], d_in[0], 1024, 2048, 64, 128, S128);
  map2(enc, &prm.m[M_XST], xs, 1024, 2048, 64, 16, S128);
  map2(enc, &prm.m[M_OUT], d_out, 1024, 2048, 64, 16, S128);
  prm.x0 = (const bf16*)d_in[0];
  prm.wq[0] = (const bf16*)d_in[1]; prm.wq[1] = (const bf16*)d_in[4];
  prm.zero = 0;
  for (int i = 0; i < 128; i++) prm.map[i] = remap(i);
  {
    const uint64_t hi = 0x80000020ull << 32, k0 = sbase + T0, v0 = k0 + 16384, vstep = 64 - (64ull << 16);
    prm.wd = mkdesc(sbase + 32768, 8192, 1024, 1); prm.xd = mkdesc(sbase, 16, 1024, 1);
    for (int j = 0; j < 4; j++) {
      prm.kv[j].kd = (hi | 1u << 16 | k0 >> 4) + 2048 * ((j < 16 ? j : 15) & 3);
      prm.kv[j].vd = (hi | (uint64_t)(ONES - T0 - 16384) >> 4 << 16 | v0 >> 4) + 32 * vstep * ((j + 3) & 3);
    }
  }
  fused_kernel<<<128, 384, SMEM_BYTES>>>(prm);
}
```

```cpp
#include <cuda_runtime.h>
#include <cuda_bf16.h>
#include <cuda.h>
#include <stdint.h>

typedef __nv_bfloat16 bf16;

__device__ __forceinline__ void wgmma_m64n192k16_ss_tb(float (&d)[96], uint64_t da, uint64_t db, int scale_d) {
  asm volatile("{\n.reg .pred p;\nsetp.ne.b32 p, %98, 0;\n"
    "wgmma.mma_async.sync.aligned.m64n192k16.f32.bf16.bf16 "
    "{%0, %1, %2, %3, %4, %5, %6, %7, %8, %9, %10, %11, %12, %13, %14, %15, "
    "%16, %17, %18, %19, %20, %21, %22, %23, %24, %25, %26, %27, %28, %29, %30, %31, "
    "%32, %33, %34, %35, %36, %37, %38, %39, %40, %41, %42, %43, %44, %45, %46, %47, "
    "%48, %49, %50, %51, %52, %53, %54, %55, %56, %57, %58, %59, %60, %61, %62, %63, "
    "%64, %65, %66, %67, %68, %69, %70, %71, %72, %73, %74, %75, %76, %77, %78, %79, "
    "%80, %81, %82, %83, %84, %85, %86, %87, %88, %89, %90, %91, %92, %93, %94, %95}, "
    "%96, %97, p, 1, 1, 0, 1;\n}\n"
    : "+f"(d[0]), "+f"(d[1]), "+f"(d[2]), "+f"(d[3]), "+f"(d[4]), "+f"(d[5]), "+f"(d[6]), "+f"(d[7]),
      "+f"(d[8]), "+f"(d[9]), "+f"(d[10]), "+f"(d[11]), "+f"(d[12]), "+f"(d[13]), "+f"(d[14]), "+f"(d[15]),
      "+f"(d[16]), "+f"(d[17]), "+f"(d[18]), "+f"(d[19]), "+f"(d[20]), "+f"(d[21]), "+f"(d[22]), "+f"(d[23]),
      "+f"(d[24]), "+f"(d[25]), "+f"(d[26]), "+f"(d[27]), "+f"(d[28]), "+f"(d[29]), "+f"(d[30]), "+f"(d[31]),
      "+f"(d[32]), "+f"(d[33]), "+f"(d[34]), "+f"(d[35]), "+f"(d[36]), "+f"(d[37]), "+f"(d[38]), "+f"(d[39]),
      "+f"(d[40]), "+f"(d[41]), "+f"(d[42]), "+f"(d[43]), "+f"(d[44]), "+f"(d[45]), "+f"(d[46]), "+f"(d[47]),
      "+f"(d[48]), "+f"(d[49]), "+f"(d[50]), "+f"(d[51]), "+f"(d[52]), "+f"(d[53]), "+f"(d[54]), "+f"(d[55]),
      "+f"(d[56]), "+f"(d[57]), "+f"(d[58]), "+f"(d[59]), "+f"(d[60]), "+f"(d[61]), "+f"(d[62]), "+f"(d[63]),
      "+f"(d[64]), "+f"(d[65]), "+f"(d[66]), "+f"(d[67]), "+f"(d[68]), "+f"(d[69]), "+f"(d[70]), "+f"(d[71]),
      "+f"(d[72]), "+f"(d[73]), "+f"(d[74]), "+f"(d[75]), "+f"(d[76]), "+f"(d[77]), "+f"(d[78]), "+f"(d[79]),
      "+f"(d[80]), "+f"(d[81]), "+f"(d[82]), "+f"(d[83]), "+f"(d[84]), "+f"(d[85]), "+f"(d[86]), "+f"(d[87]),
      "+f"(d[88]), "+f"(d[89]), "+f"(d[90]), "+f"(d[91]), "+f"(d[92]), "+f"(d[93]), "+f"(d[94]), "+f"(d[95])
    : "l"(da), "l"(db), "r"(scale_d));
}

__device__ __forceinline__ void wgmma_m64n192k16_ss_tb_z(float (&d)[96], uint64_t da, uint64_t db, int scale_d) {
  asm volatile("{\n.reg .pred p;\nsetp.ne.b32 p, %98, 0;\n"
    "wgmma.mma_async.sync.aligned.m64n192k16.f32.bf16.bf16 "
    "{%0, %1, %2, %3, %4, %5, %6, %7, %8, %9, %10, %11, %12, %13, %14, %15, "
    "%16, %17, %18, %19, %20, %21, %22, %23, %24, %25, %26, %27, %28, %29, %30, %31, "
    "%32, %33, %34, %35, %36, %37, %38, %39, %40, %41, %42, %43, %44, %45, %46, %47, "
    "%48, %49, %50, %51, %52, %53, %54, %55, %56, %57, %58, %59, %60, %61, %62, %63, "
    "%64, %65, %66, %67, %68, %69, %70, %71, %72, %73, %74, %75, %76, %77, %78, %79, "
    "%80, %81, %82, %83, %84, %85, %86, %87, %88, %89, %90, %91, %92, %93, %94, %95}, "
    "%96, %97, p, 1, 1, 0, 1;\n}\n"
    : "=f"(d[0]), "=f"(d[1]), "=f"(d[2]), "=f"(d[3]), "=f"(d[4]), "=f"(d[5]), "=f"(d[6]), "=f"(d[7]),
      "=f"(d[8]), "=f"(d[9]), "=f"(d[10]), "=f"(d[11]), "=f"(d[12]), "=f"(d[13]), "=f"(d[14]), "=f"(d[15]),
      "=f"(d[16]), "=f"(d[17]), "=f"(d[18]), "=f"(d[19]), "=f"(d[20]), "=f"(d[21]), "=f"(d[22]), "=f"(d[23]),
      "=f"(d[24]), "=f"(d[25]), "=f"(d[26]), "=f"(d[27]), "=f"(d[28]), "=f"(d[29]), "=f"(d[30]), "=f"(d[31]),
      "=f"(d[32]), "=f"(d[33]), "=f"(d[34]), "=f"(d[35]), "=f"(d[36]), "=f"(d[37]), "=f"(d[38]), "=f"(d[39]),
      "=f"(d[40]), "=f"(d[41]), "=f"(d[42]), "=f"(d[43]), "=f"(d[44]), "=f"(d[45]), "=f"(d[46]), "=f"(d[47]),
      "=f"(d[48]), "=f"(d[49]), "=f"(d[50]), "=f"(d[51]), "=f"(d[52]), "=f"(d[53]), "=f"(d[54]), "=f"(d[55]),
      "=f"(d[56]), "=f"(d[57]), "=f"(d[58]), "=f"(d[59]), "=f"(d[60]), "=f"(d[61]), "=f"(d[62]), "=f"(d[63]),
      "=f"(d[64]), "=f"(d[65]), "=f"(d[66]), "=f"(d[67]), "=f"(d[68]), "=f"(d[69]), "=f"(d[70]), "=f"(d[71]),
      "=f"(d[72]), "=f"(d[73]), "=f"(d[74]), "=f"(d[75]), "=f"(d[76]), "=f"(d[77]), "=f"(d[78]), "=f"(d[79]),
      "=f"(d[80]), "=f"(d[81]), "=f"(d[82]), "=f"(d[83]), "=f"(d[84]), "=f"(d[85]), "=f"(d[86]), "=f"(d[87]),
      "=f"(d[88]), "=f"(d[89]), "=f"(d[90]), "=f"(d[91]), "=f"(d[92]), "=f"(d[93]), "=f"(d[94]), "=f"(d[95])
    : "l"(da), "l"(db), "r"(scale_d));
}

__device__ __forceinline__ void wgmma_m64n128k16_ss_tb(float (&d)[64], uint64_t da, uint64_t db, int scale_d) {
  asm volatile("{\n.reg .pred p;\nsetp.ne.b32 p, %66, 0;\n"
    "wgmma.mma_async.sync.aligned.m64n128k16.f32.bf16.bf16 "
    "{%0, %1, %2, %3, %4, %5, %6, %7, %8, %9, %10, %11, %12, %13, %14, %15, "
    "%16, %17, %18, %19, %20, %21, %22, %23, %24, %25, %26, %27, %28, %29, %30, %31, "
    "%32, %33, %34, %35, %36, %37, %38, %39, %40, %41, %42, %43, %44, %45, %46, %47, "
    "%48, %49, %50, %51, %52, %53, %54, %55, %56, %57, %58, %59, %60, %61, %62, %63}, "
    "%64, %65, p, 1, 1, 0, 1;\n}\n"
    : "+f"(d[0]), "+f"(d[1]), "+f"(d[2]), "+f"(d[3]), "+f"(d[4]), "+f"(d[5]), "+f"(d[6]), "+f"(d[7]),
      "+f"(d[8]), "+f"(d[9]), "+f"(d[10]), "+f"(d[11]), "+f"(d[12]), "+f"(d[13]), "+f"(d[14]), "+f"(d[15]),
      "+f"(d[16]), "+f"(d[17]), "+f"(d[18]), "+f"(d[19]), "+f"(d[20]), "+f"(d[21]), "+f"(d[22]), "+f"(d[23]),
      "+f"(d[24]), "+f"(d[25]), "+f"(d[26]), "+f"(d[27]), "+f"(d[28]), "+f"(d[29]), "+f"(d[30]), "+f"(d[31]),
      "+f"(d[32]), "+f"(d[33]), "+f"(d[34]), "+f"(d[35]), "+f"(d[36]), "+f"(d[37]), "+f"(d[38]), "+f"(d[39]),
      "+f"(d[40]), "+f"(d[41]), "+f"(d[42]), "+f"(d[43]), "+f"(d[44]), "+f"(d[45]), "+f"(d[46]), "+f"(d[47]),
      "+f"(d[48]), "+f"(d[49]), "+f"(d[50]), "+f"(d[51]), "+f"(d[52]), "+f"(d[53]), "+f"(d[54]), "+f"(d[55]),
      "+f"(d[56]), "+f"(d[57]), "+f"(d[58]), "+f"(d[59]), "+f"(d[60]), "+f"(d[61]), "+f"(d[62]), "+f"(d[63])
    : "l"(da), "l"(db), "r"(scale_d));
}

__device__ __forceinline__ void wgmma_m64n128k16_ss_tb_z(float (&d)[64], uint64_t da, uint64_t db, int scale_d) {
  asm volatile("{\n.reg .pred p;\nsetp.ne.b32 p, %66, 0;\n"
    "wgmma.mma_async.sync.aligned.m64n128k16.f32.bf16.bf16 "
    "{%0, %1, %2, %3, %4, %5, %6, %7, %8, %9, %10, %11, %12, %13, %14, %15, "
    "%16, %17, %18, %19, %20, %21, %22, %23, %24, %25, %26, %27, %28, %29, %30, %31, "
    "%32, %33, %34, %35, %36, %37, %38, %39, %40, %41, %42, %43, %44, %45, %46, %47, "
    "%48, %49, %50, %51, %52, %53, %54, %55, %56, %57, %58, %59, %60, %61, %62, %63}, "
    "%64, %65, p, 1, 1, 0, 1;\n}\n"
    : "=f"(d[0]), "=f"(d[1]), "=f"(d[2]), "=f"(d[3]), "=f"(d[4]), "=f"(d[5]), "=f"(d[6]), "=f"(d[7]),
      "=f"(d[8]), "=f"(d[9]), "=f"(d[10]), "=f"(d[11]), "=f"(d[12]), "=f"(d[13]), "=f"(d[14]), "=f"(d[15]),
      "=f"(d[16]), "=f"(d[17]), "=f"(d[18]), "=f"(d[19]), "=f"(d[20]), "=f"(d[21]), "=f"(d[22]), "=f"(d[23]),
      "=f"(d[24]), "=f"(d[25]), "=f"(d[26]), "=f"(d[27]), "=f"(d[28]), "=f"(d[29]), "=f"(d[30]), "=f"(d[31]),
      "=f"(d[32]), "=f"(d[33]), "=f"(d[34]), "=f"(d[35]), "=f"(d[36]), "=f"(d[37]), "=f"(d[38]), "=f"(d[39]),
      "=f"(d[40]), "=f"(d[41]), "=f"(d[42]), "=f"(d[43]), "=f"(d[44]), "=f"(d[45]), "=f"(d[46]), "=f"(d[47]),
      "=f"(d[48]), "=f"(d[49]), "=f"(d[50]), "=f"(d[51]), "=f"(d[52]), "=f"(d[53]), "=f"(d[54]), "=f"(d[55]),
      "=f"(d[56]), "=f"(d[57]), "=f"(d[58]), "=f"(d[59]), "=f"(d[60]), "=f"(d[61]), "=f"(d[62]), "=f"(d[63])
    : "l"(da), "l"(db), "r"(scale_d));
}

__device__ __forceinline__ void wgmma_m64n40k16_rs_tb(float (&d)[20], uint32_t a0, uint32_t a1, uint32_t a2, uint32_t a3, uint64_t db, int scale_d) {
  asm volatile("{\n.reg .pred p;\nsetp.ne.b32 p, %25, 0;\n"
    "wgmma.mma_async.sync.aligned.m64n40k16.f32.bf16.bf16 "
    "{%0, %1, %2, %3, %4, %5, %6, %7, %8, %9, %10, %11, %12, %13, %14, %15, "
    "%16, %17, %18, %19}, "
    "{%20, %21, %22, %23}, %24, p, 1, 1, 1;\n}\n"
    : "+f"(d[0]), "+f"(d[1]), "+f"(d[2]), "+f"(d[3]), "+f"(d[4]), "+f"(d[5]), "+f"(d[6]), "+f"(d[7]),
      "+f"(d[8]), "+f"(d[9]), "+f"(d[10]), "+f"(d[11]), "+f"(d[12]), "+f"(d[13]), "+f"(d[14]), "+f"(d[15]),
      "+f"(d[16]), "+f"(d[17]), "+f"(d[18]), "+f"(d[19])
    : "r"(a0), "r"(a1), "r"(a2), "r"(a3), "l"(db), "r"(scale_d));
}

__device__ __forceinline__ void wg_n64_rs_nb_f16_f32(float (&d)[32], uint32_t a0, uint32_t a1, uint32_t a2, uint32_t a3, uint64_t db, int scale_d) {
  asm volatile("{\n.reg .pred p;\nsetp.ne.b32 p, %37, 0;\n"
    "wgmma.mma_async.sync.aligned.m64n64k16.f32.f16.f16 "
    "{%0, %1, %2, %3, %4, %5, %6, %7, %8, %9, %10, %11, %12, %13, %14, %15, "
    "%16, %17, %18, %19, %20, %21, %22, %23, %24, %25, %26, %27, %28, %29, %30, %31}, "
    "{%32, %33, %34, %35}, %36, p, 1, 1, 0;\n}\n"
    : "+f"(d[0]), "+f"(d[1]), "+f"(d[2]), "+f"(d[3]), "+f"(d[4]), "+f"(d[5]), "+f"(d[6]), "+f"(d[7]),
      "+f"(d[8]), "+f"(d[9]), "+f"(d[10]), "+f"(d[11]), "+f"(d[12]), "+f"(d[13]), "+f"(d[14]), "+f"(d[15]),
      "+f"(d[16]), "+f"(d[17]), "+f"(d[18]), "+f"(d[19]), "+f"(d[20]), "+f"(d[21]), "+f"(d[22]), "+f"(d[23]),
      "+f"(d[24]), "+f"(d[25]), "+f"(d[26]), "+f"(d[27]), "+f"(d[28]), "+f"(d[29]), "+f"(d[30]), "+f"(d[31])
    : "r"(a0), "r"(a1), "r"(a2), "r"(a3), "l"(db), "r"(scale_d));
}

__device__ __forceinline__ void wg_n64_rs_nb_f16_f16(uint32_t (&d)[16], uint32_t a0, uint32_t a1, uint32_t a2, uint32_t a3, uint64_t db, int scale_d) {
  asm volatile("{\n.reg .pred p;\nsetp.ne.b32 p, %21, 0;\n"
    "wgmma.mma_async.sync.aligned.m64n64k16.f16.f16.f16 "
    "{%0, %1, %2, %3, %4, %5, %6, %7, %8, %9, %10, %11, %12, %13, %14, %15}, "
    "{%16, %17, %18, %19}, %20, p, 1, 1, 0;\n}\n"
    : "+r"(d[0]), "+r"(d[1]), "+r"(d[2]), "+r"(d[3]), "+r"(d[4]), "+r"(d[5]), "+r"(d[6]), "+r"(d[7]),
      "+r"(d[8]), "+r"(d[9]), "+r"(d[10]), "+r"(d[11]), "+r"(d[12]), "+r"(d[13]), "+r"(d[14]), "+r"(d[15])
    : "r"(a0), "r"(a1), "r"(a2), "r"(a3), "l"(db), "r"(scale_d));
}

__device__ __forceinline__ void wg_n64_rs_nb_f16_f32_z(float (&d)[32], uint32_t a0, uint32_t a1, uint32_t a2, uint32_t a3, uint64_t db, int scale_d) {
  asm volatile("{\n.reg .pred p;\nsetp.ne.b32 p, %37, 0;\n"
    "wgmma.mma_async.sync.aligned.m64n64k16.f32.f16.f16 "
    "{%0, %1, %2, %3, %4, %5, %6, %7, %8, %9, %10, %11, %12, %13, %14, %15, "
    "%16, %17, %18, %19, %20, %21, %22, %23, %24, %25, %26, %27, %28, %29, %30, %31}, "
    "{%32, %33, %34, %35}, %36, p, 1, 1, 0;\n}\n"
    : "=f"(d[0]), "=f"(d[1]), "=f"(d[2]), "=f"(d[3]), "=f"(d[4]), "=f"(d[5]), "=f"(d[6]), "=f"(d[7]),
      "=f"(d[8]), "=f"(d[9]), "=f"(d[10]), "=f"(d[11]), "=f"(d[12]), "=f"(d[13]), "=f"(d[14]), "=f"(d[15]),
      "=f"(d[16]), "=f"(d[17]), "=f"(d[18]), "=f"(d[19]), "=f"(d[20]), "=f"(d[21]), "=f"(d[22]), "=f"(d[23]),
      "=f"(d[24]), "=f"(d[25]), "=f"(d[26]), "=f"(d[27]), "=f"(d[28]), "=f"(d[29]), "=f"(d[30]), "=f"(d[31])
    : "r"(a0), "r"(a1), "r"(a2), "r"(a3), "l"(db), "r"(scale_d));
}

__device__ __forceinline__ void wg_n64_rs_nb_f16_f16_z(uint32_t (&d)[16], uint32_t a0, uint32_t a1, uint32_t a2, uint32_t a3, uint64_t db, int scale_d) {
  asm volatile("{\n.reg .pred p;\nsetp.ne.b32 p, %21, 0;\n"
    "wgmma.mma_async.sync.aligned.m64n64k16.f16.f16.f16 "
    "{%0, %1, %2, %3, %4, %5, %6, %7, %8, %9, %10, %11, %12, %13, %14, %15}, "
    "{%16, %17, %18, %19}, %20, p, 1, 1, 0;\n}\n"
    : "=r"(d[0]), "=r"(d[1]), "=r"(d[2]), "=r"(d[3]), "=r"(d[4]), "=r"(d[5]), "=r"(d[6]), "=r"(d[7]),
      "=r"(d[8]), "=r"(d[9]), "=r"(d[10]), "=r"(d[11]), "=r"(d[12]), "=r"(d[13]), "=r"(d[14]), "=r"(d[15])
    : "r"(a0), "r"(a1), "r"(a2), "r"(a3), "l"(db), "r"(scale_d));
}

#define DEVINL __device__ __forceinline__
DEVINL void wg_fence() { asm volatile("wgmma.fence.sync.aligned;" ::: "memory"); }
DEVINL void wg_commit() { asm volatile("wgmma.commit_group.sync.aligned;" ::: "memory"); }
template <int N> DEVINL void wg_wait() { asm volatile("wgmma.wait_group.sync.aligned %0;" ::"n"(N) : "memory"); }
__host__ DEVINL uint64_t mkdesc(uint32_t addr, uint32_t lbo, uint32_t sbo, int sw) {
  return (uint64_t)((addr & 0x3FFFF) >> 4) | ((uint64_t)(lbo >> 4) << 16) | ((uint64_t)(sbo >> 4) << 32) | ((uint64_t)sw << 62);
}
DEVINL bool mbar_try(uint32_t bar, uint32_t parity) {
  uint32_t ok;
  asm volatile("{\n.reg .pred p;\nmbarrier.try_wait.parity.shared::cta.b64 p, [%1], %2;\nselp.u32 %0, 1, 0, p;\n}" : "=r"(ok) : "r"(bar), "r"(parity) : "memory");
  return ok;
}
DEVINL bool mbar_test(uint32_t bar, uint32_t parity) {
  uint32_t ok;
  asm volatile("{\n.reg .pred p;\nmbarrier.test_wait.parity.shared::cta.b64 p, [%1], %2;\nselp.u32 %0, 1, 0, p;\n}" : "=r"(ok) : "r"(bar), "r"(parity) : "memory");
  return ok;
}
DEVINL void mbar_wait(uint32_t bar, uint32_t parity) {
#pragma unroll 1
  for (uint32_t n = 0; n < 100000u; n++) if (mbar_try(bar, parity)) break;
}
#define EL(txt) "{\n.reg .pred pe;\nelect.sync _|pe, 0xffffffff;\n@pe " txt "\n}"
DEVINL void e_expect_tx(uint32_t bar, uint32_t bytes) { asm volatile(EL("mbarrier.arrive.expect_tx.shared::cta.b64 _, [%0], %1;") ::"r"(bar), "r"(bytes) : "memory"); }
DEVINL void e_arrive(uint32_t bar) { asm volatile(EL("mbarrier.arrive.shared::cta.b64 _, [%0];") ::"r"(bar) : "memory"); }
DEVINL void e_arrive_if(uint32_t bar, int c) {
  asm volatile("{\n.reg .pred pe;\nelect.sync _|pe, 0xffffffff;\nsetp.ne.and.b32 pe, %1, 0, pe;\n@pe mbarrier.arrive.shared::cta.b64 _, [%0];\n}" ::"r"(bar), "r"(c) : "memory");
}
DEVINL void e_red(uint32_t* p) { asm volatile(EL("red.release.gpu.global.add.u32 [%0], 1;") ::"l"(p) : "memory"); }
DEVINL void e_red_relaxed(uint32_t* p) { asm volatile(EL("red.relaxed.gpu.global.add.u32 [%0], 1;") ::"l"(p) : "memory"); }
DEVINL void release_add(uint32_t* p, int on) {
  asm volatile("{\n.reg .pred q;\nsetp.ne.b32 q, %1, 0;\nfence.release.gpu;\n@q red.relaxed.gpu.global.add.u32 [%0], 1;\n}" ::"l"(p), "r"(on) : "memory");
}
#define PREPARED(p, on) do { asm volatile("" : "+l"(p), "+r"(on)); asm volatile("griddepcontrol.launch_dependents;" ::: "memory"); } while (0)
DEVINL void tma_ld(uint32_t dst, const CUtensorMap* m, int c0, int c1, uint32_t bar) {
  asm volatile(EL("cp.async.bulk.tensor.2d.shared::cluster.global.mbarrier::complete_tx::bytes [%0], [%1, {%3, %4}], [%2];")
               ::"r"(dst), "l"(m), "r"(bar), "r"(c0), "r"(c1) : "memory");
}
DEVINL void tma_ld3(uint32_t dst, const CUtensorMap* m, int c0, int c1, int c2, uint32_t bar) {
  asm volatile(EL("cp.async.bulk.tensor.3d.shared::cluster.global.mbarrier::complete_tx::bytes [%0], [%1, {%3, %4, %5}], [%2];")
               ::"r"(dst), "l"(m), "r"(bar), "r"(c0), "r"(c1), "r"(c2) : "memory");
}
DEVINL void tma_ld5(uint32_t dst, const CUtensorMap* m, int c2, int c3, int c4, uint32_t bar) {
  asm volatile(EL("cp.async.bulk.tensor.5d.shared::cluster.global.mbarrier::complete_tx::bytes [%0], [%1, {0, 0, %3, %4, %5}], [%2];")
               ::"r"(dst), "l"(m), "r"(bar), "r"(c2), "r"(c3), "r"(c4) : "memory");
}
DEVINL void tma_ld_mc(uint32_t dst, const CUtensorMap* m, int c0, int c1, uint32_t bar, uint16_t mask = 3) {
  asm volatile(EL("cp.async.bulk.tensor.2d.shared::cluster.global.mbarrier::complete_tx::bytes.multicast::cluster [%0], [%1, {%3, %4}], [%2], %5;")
               ::"r"(dst), "l"(m), "r"(bar), "r"(c0), "r"(c1), "h"(mask) : "memory");
}
DEVINL void e_arrive_both(uint32_t bar) {
  asm volatile("{\n.reg .pred pe;\n.reg .b32 r0, r1;\nelect.sync _|pe, 0xffffffff;\nmapa.shared::cluster.u32 r0, %0, 0;\nmapa.shared::cluster.u32 r1, %0, 1;\n"
               "@pe mbarrier.arrive.shared::cluster.b64 _, [r0];\n@pe mbarrier.arrive.shared::cluster.b64 _, [r1];\n}" ::"r"(bar) : "memory");
}
DEVINL void tma_st(const CUtensorMap* m, int c0, int c1, uint32_t src) {
  asm volatile(EL("cp.async.bulk.tensor.2d.global.shared::cta.bulk_group [%0, {%2, %3}], [%1];") ::"l"(m), "r"(src), "r"(c0), "r"(c1) : "memory");
}
DEVINL void bulk_commit() { asm volatile("cp.async.bulk.commit_group;" ::: "memory"); }
template <int N> DEVINL void bulk_wait_n() { asm volatile("cp.async.bulk.wait_group %0;\nbar.warp.sync 0xffffffff;" ::"n"(N) : "memory"); }
DEVINL void l2_prefetch(const void* g, uint32_t bytes) { asm volatile(EL("cp.async.bulk.prefetch.L2.global [%0], %1;") ::"l"(g), "r"(bytes) : "memory"); }
DEVINL void fence_async_smem() { asm volatile("fence.proxy.async.shared::cta;" ::: "memory"); }
DEVINL void fence_async_gl() { asm volatile("fence.proxy.async.global;" ::: "memory"); }
DEVINL void cluster_wait() { asm volatile("barrier.cluster.wait.aligned;" ::: "memory"); }
DEVINL void bar_sync(int id, int n) { asm volatile("bar.sync %0, %1;" ::"r"(id), "r"(n) : "memory"); }
DEVINL void bar_arrive(int id, int n) { asm volatile("bar.arrive %0, %1;" ::"r"(id), "r"(n) : "memory"); }
DEVINL uint32_t ld_acquire(const uint32_t* p) { uint32_t v; asm volatile("ld.acquire.gpu.global.u32 %0, [%1];" : "=r"(v) : "l"(p) : "memory"); return v; }
DEVINL void await_flag(int j, uint32_t& rdy, const uint32_t* p, uint32_t target) {
  if ((rdy >> j) & 1) return;
#pragma unroll 1
  for (uint32_t n = 0; n < 200000u && !((rdy >> j) & 1); n++) rdy = __ballot_sync(~0u, (int)(ld_acquire(p) - target) >= 0);
  asm volatile("fence.proxy.async.global;" ::: "memory");
}
DEVINL void poll_ge(const uint32_t* p, uint32_t target) {
#pragma unroll 1
  for (uint32_t n = 0; n < 200000u; n++) if (__all_sync(~0u, (int)(ld_acquire(p) - target) >= 0)) break;
}
DEVINL int lane_id() { int v; asm volatile("mov.u32 %0, %%laneid;" : "=r"(v)); return v; }
__host__ DEVINL int remap(int v) {
  const int c = v >> 1, u = c - 36, r = (u * 37) >> 8;
  const int L = c < 4 ? 32 + 8 * c : c < 36 ? c - 4 : 33 + u + r;
  return 2 * L + (v & 1);
}
DEVINL int block_id() { int v; asm volatile("mov.u32 %0, %%ctaid.x;" : "=r"(v)); return v; }
#define cta_id() prm.map[block_id()]
#define IDS() const int lane = lane_id(), b = cta_id(), bm = b >> 4, bn = b & 15, rank = b & 1, pm = 2 * bm + (bn >> 3), pn = bn & 7, po = pm & 1; \
  (void)lane; (void)bm; (void)bn; (void)rank; (void)pm; (void)pn; (void)po
DEVINL void st_tagged(uint4* p, uint32_t a, uint32_t b, uint32_t c, uint32_t tag) {
  asm volatile("{\n.reg .b64 u, v;\n.reg .b128 t;\nmov.b64 u, {%1, %2};\nmov.b64 v, {%3, %4};\nmov.b128 t, {u, v};\nst.relaxed.gpu.global.b128 [%0], t;\n}"
               ::"l"(p), "r"(a), "r"(b), "r"(c), "r"(tag) : "memory");
}
DEVINL uint32_t ld_tagged(const uint4* p, uint32_t* r) {
  uint32_t tag;
  asm volatile("{\n.reg .b64 u, v;\n.reg .b128 t;\nld.relaxed.gpu.global.b128 t, [%4];\nmov.b128 {u, v}, t;\nmov.b64 {%0, %1}, u;\nmov.b64 {%2, %3}, v;\n}"
               : "=r"(r[0]), "=r"(r[1]), "=r"(r[2]), "=r"(tag) : "l"(p) : "memory");
  return tag;
}
DEVINL float ex2(float x) { float y; asm("ex2.approx.ftz.f32 %0, %1;" : "=f"(y) : "f"(x)); return y; }
DEVINL float rcp(float x) { float y; asm("rcp.approx.ftz.f32 %0, %1;" : "=f"(y) : "f"(x)); return y; }
DEVINL uint32_t pack2(float lo, float hi) { uint32_t r; asm("cvt.rn.bf16x2.f32 %0, %1, %2;" : "=r"(r) : "f"(hi), "f"(lo)); return r; }
DEVINL uint32_t pack2h(float lo, float hi) { uint32_t r; asm("cvt.rz.f16x2.f32 %0, %1, %2;" : "=r"(r) : "f"(hi), "f"(lo)); return r; }
DEVINL uint32_t prmt0(uint32_t a, uint32_t sel) { uint32_t r; asm("prmt.b32 %0, %1, 0, %2;" : "=r"(r) : "r"(a), "r"(sel)); return r; }
DEVINL void stg128(const void* p, uint32_t a, uint32_t b, uint32_t c, uint32_t d) {
  asm volatile("st.global.v4.b32 [%0], {%1, %2, %3, %4};" ::"l"(p), "r"(a), "r"(b), "r"(c), "r"(d) : "memory");
}
DEVINL float bf_lo(uint32_t w) { return __uint_as_float(w << 16); }
DEVINL float bf_hi(uint32_t w) { return __uint_as_float(w & 0xFFFF0000u); }
DEVINL float bf_round(float x) { return bf_lo(pack2(x, 0.f)); }
DEVINL uint32_t add_bf16x2(uint32_t a, uint32_t b) { uint32_t r; asm("add.rn.bf16x2 %0, %1, %2;" : "=r"(r) : "r"(a), "r"(b)); return r; }
DEVINL void stsm4(uint32_t addr, uint32_t a, uint32_t b, uint32_t c, uint32_t d) {
  asm volatile("stmatrix.sync.aligned.m8n8.x4.shared.b16 [%0], {%1, %2, %3, %4};" ::"r"(addr), "r"(a), "r"(b), "r"(c), "r"(d) : "memory");
}
DEVINL void ldsm4(uint32_t addr, uint32_t (&r)[4]) {
  asm volatile("ldmatrix.sync.aligned.m8n8.x4.shared.b16 {%0, %1, %2, %3}, [%4];" : "=r"(r[0]), "=r"(r[1]), "=r"(r[2]), "=r"(r[3]) : "r"(addr) : "memory");
}
DEVINL void ldsm4t(uint32_t addr, uint32_t (&r)[4]) {
  asm volatile("ldmatrix.sync.aligned.m8n8.x4.trans.shared.b16 {%0, %1, %2, %3}, [%4];" : "=r"(r[0]), "=r"(r[1]), "=r"(r[2]), "=r"(r[3]) : "r"(addr) : "memory");
}
DEVINL void sts128(uint32_t addr, uint32_t a, uint32_t b, uint32_t c, uint32_t d) {
  asm volatile("st.shared.v4.b32 [%0], {%1, %2, %3, %4};" ::"r"(addr), "r"(a), "r"(b), "r"(c), "r"(d) : "memory");
}
DEVINL float2 lds64f(uint32_t addr) { float2 v; asm volatile("ld.shared.v2.f32 {%0, %1}, [%2];" : "=f"(v.x), "=f"(v.y) : "r"(addr) : "memory"); return v; }
DEVINL void mma16816(float (&d)[4], uint32_t a0, uint32_t a1, uint32_t a2, uint32_t a3, uint32_t b0, uint32_t b1) {
  asm("mma.sync.aligned.m16n8k16.row.col.f32.bf16.bf16.f32 {%0, %1, %2, %3}, {%4, %5, %6, %7}, {%8, %9}, {%0, %1, %2, %3};"
               : "+f"(d[0]), "+f"(d[1]), "+f"(d[2]), "+f"(d[3]) : "r"(a0), "r"(a1), "r"(a2), "r"(a3), "r"(b0), "r"(b1));
}
template <int N> DEVINL void fence_regs(float (&d)[N]) {
#pragma unroll
  for (int i = 0; i < N; i++) asm volatile("" : "+f"(d[i])::"memory");
}
template <int N> DEVINL void fence_regs(uint32_t (&d)[N]) {
#pragma unroll
  for (int i = 0; i < N; i++) asm volatile("" : "+r"(d[i])::"memory");
}
DEVINL void lds128(uint32_t addr, uint32_t* r) {
  asm volatile("ld.shared.v4.b32 {%0, %1, %2, %3}, [%4];" : "=r"(r[0]), "=r"(r[1]), "=r"(r[2]), "=r"(r[3]) : "r"(addr) : "memory");
}
DEVINL void sched_fence() { asm volatile("griddepcontrol.launch_dependents;" ::: "memory"); }

struct Scratch {
  bf16 k[32 * 2048 * 32];
  bf16 xs[2048 * 1024];
  bf16 os[2048 * 1024];
  bf16 v[32 * 2048 * 32];
  float kn[2 * 128 * 16];
  uint32_t cnt[256 * 32];
  float2 stats[8 * 2048];
  uint4 halo[128 * 12 * 32];
  float csp[2 * 16 * 8 * 192];
  uint4 qsave[128 * 256 * 8];
  uint32_t esc[4 * 65536 * 20];
};
__device__ __align__(1024) Scratch g_s;
#define g_k g_s.k
#define g_xs g_s.xs
#define g_os g_s.os
#define g_v g_s.v
#define g_kn g_s.kn
#define g_cnt g_s.cnt
#define g_stats g_s.stats
#define g_halo g_s.halo
#define g_csp g_s.csp
#define g_qsave g_s.qsave
#define g_esc g_s.esc
#define g_epoch g_s.cnt[255 * 32]

DEVINL uint32_t* cnt_x(int bm) { return g_cnt + bm * 32; }
DEVINL uint32_t* cnt_o(int l, int pm, int h) { return g_cnt + (32 + (l * 16 + pm) * 2 + h) * 32; }
DEVINL uint32_t* cnt_kv(int lb, int bn) { return g_cnt + (160 + lb * 16 + bn) * 32; }
DEVINL uint32_t* cnt_ad(int bn) { return g_cnt + (192 + bn) * 32; }
DEVINL uint32_t* cnt_cs(int t, int bn) { return g_cnt + (208 + t * 16 + bn) * 32; }

DEVINL int qord(int i, int l, int pn) {
  const int u = i < 9 ? i - 3 : i - 9;
  return l == 0 ? i : i < 3 ? ((2 * pn) ^ (2 * (i & 1))) + (i >> 1) : i == 15 ? (2 * pn) ^ 3 : 2 * (u < (pn & 6) ? u : u + 2) + (i >= 9);
}
struct Params {
  CUtensorMap m[15];
  const bf16* x0;
  const bf16* wq[2];
  uint32_t zero;
  int map[128];
  uint64_t wd, xd;
  struct __align__(16) { uint64_t kd, vd; } kv[4];
};
enum { M_X0A = 0, M_XSA, M_WQA, M_WQB, M_WOA, M_WOB, M_OS, M_K, M_V, M_X0R, M_XSR, M_XSO, M_OUT, M_XST, M_X0H, M_COUNT };

constexpr uint32_t QSTG = 57344;
constexpr uint32_t T0 = 65536, TSTG = 32768;
constexpr uint32_t ONES = 230400;
constexpr uint32_t PSTG = 32768, RES = 196608;
constexpr uint32_t KSC = 98304, VSC = 133120, HRS = 167936;
constexpr uint32_t ROWST = 229376, COLS = 231424, BARS = 232192, SMEM_BYTES = 232448;
constexpr uint32_t B_QF = BARS, B_QE = BARS + 32, B_TF = BARS + 64, B_TE = BARS + 96, B_PF = BARS + 128, B_PE = BARS + 176,
                   B_RF = BARS + 224, W_X = BARS + 232, B_QL = BARS + 240, B_PA = BARS + 248;
enum { NB_ST = 1, NB_KV = 2  , NB_DONE = 3, NB_SC = 4, NB_SIG = 5  , NB_KN = 9  , NB_X = 11, NB_HALO = 12  , NB_X0 = 15 };

DEVINL uint32_t pslot_b(uint32_t s) { return ((0x320415u >> (4 * s)) & 7) * 16384u; }
DEVINL uint32_t pslot_a(uint32_t s, int l) { return 98304u + ((((l & 1) ? 0x541230u : 0x041235u) >> (4 * s)) & 7) * 16384u; }

constexpr float QSCALE = 0.17677669529663687f * 1.4426950408889634f;
constexpr uint32_t QPARK = 32768;

DEVINL uint32_t exp2_h2(uint32_t s, uint32_t c852) {
  uint32_t r, t, w, m, d;
  asm volatile("{.reg .b64 t; add.rn.f16x2 %0, %1, %2; cvt.u64.u32 t, %0; cvt.u32.u64 %0, t;}" : "=r"(r) : "r"(s), "r"(0x65EA65EAu));
  asm volatile("fma.rn.f16x2 %0, %1, %2, %3;" : "=r"(t) : "r"(r), "r"(0xB880B880u), "r"(c852));
  asm volatile("fma.rn.f16x2 %0, %1, %2, %3;" : "=r"(w) : "r"(s), "r"(0x38803880u), "r"(t));
  asm volatile("fma.rn.f16x2 %0, %1, %1, %2;" : "=r"(m) : "r"(w), "r"(0x4A1F4A2Du));
  asm volatile("{.reg .b32 t; shf.l.clamp.b32 t, %2, %1, 7; add.u32 %0, t, %2;}" : "=r"(d) : "r"(r), "r"(m));
  return d;
}
DEVINL float exp2_fix(float s) { float z; asm volatile("add.rn.f32 %0, %1, 0f43BF34BC;" : "=f"(z) : "f"(s)); return z; }
DEVINL uint32_t exp2_base(float z0, float z1) { uint32_t B; asm volatile("prmt.b32 %0, %1, %2, 0x6521;" : "=r"(B) : "r"(__float_as_uint(z0)), "r"(__float_as_uint(z1))); return B; }
template <uint32_t MASK> DEVINL uint32_t and_or(uint32_t a, uint32_t c) { uint32_t r; asm volatile("lop3.b32 %0, %1, %3, %2, 0xEA;" : "=r"(r) : "r"(a), "r"(c), "n"(MASK)); return r; }
DEVINL uint32_t fma_bf2(uint32_t a, uint32_t b, uint32_t c) { uint32_t r; asm volatile("fma.rn.bf16x2 %0, %1, %2, %3;" : "=r"(r) : "r"(a), "r"(b), "r"(c)); return r; }
DEVINL float ex2v(float x) { float y; asm volatile("ex2.approx.ftz.f32 %0, %1;" : "=f"(y) : "f"(x)); return y; }
DEVINL uint32_t pack2v(float lo, float hi) { uint32_t r; asm volatile("cvt.rn.bf16x2.f32 %0, %1, %2;" : "=r"(r) : "f"(hi), "f"(lo)); return r; }
DEVINL void unesc(uint32_t (&u)[4], const uint32_t* esc, uint32_t tag) {
  const bool saved = __ldcg(esc + 16) == tag;
#pragma unroll
  for (int j = 0; j < 4; j++) {
    float lo, hi;
    asm("{.reg .f16 a, b; mov.b32 {a, b}, %2; cvt.f32.f16 %0, a; cvt.f32.f16 %1, b;}" : "=f"(lo), "=f"(hi) : "r"(u[j]));
    u[j] = saved ? __ldcg(esc + 4 * j) : pack2(lo, hi);
  }
}

DEVINL void attn_slow(const uint32_t (&q)[8], int head, const uint32_t* kesc, uint32_t tag, float (&res)[20], int lane) {
  const int g = lane >> 2, qd = lane & 3;
  const bf16* kb = g_k + (size_t)head * 2048 * 32;
  const bf16* vb = g_v + (size_t)head * 2048 * 32;
  float o[4][4], m0 = -INFINITY, m1 = -INFINITY, l0 = 0.f, l1 = 0.f;
#pragma unroll
  for (int j = 0; j < 4; j++) { o[j][0] = o[j][1] = o[j][2] = o[j][3] = 0.f; }
#pragma unroll 1
  for (int k0 = 0; k0 < 2048; k0 += 16) {
    float s[2][4];
#pragma unroll
    for (int nt = 0; nt < 2; nt++) {
      s[nt][0] = s[nt][1] = s[nt][2] = s[nt][3] = 0.f;
      const uint32_t* kp = (const uint32_t*)(kb + (size_t)(k0 + nt * 8 + g) * 32) + qd;
      uint32_t k[4] = {__ldcg(kp), __ldcg(kp + 4), __ldcg(kp + 8), __ldcg(kp + 12)};
      unesc(k, kesc + (k0 + nt * 8 + g) * 20 + qd, tag);
      __syncwarp();
      mma16816(s[nt], q[0], q[1], q[2], q[3], k[0], k[1]);
      mma16816(s[nt], q[4], q[5], q[6], q[7], k[2], k[3]);
    }
    float a0 = fmaxf(fmaxf(s[0][0], s[0][1]), fmaxf(s[1][0], s[1][1]));
    float a1 = fmaxf(fmaxf(s[0][2], s[0][3]), fmaxf(s[1][2], s[1][3]));
    a0 = fmaxf(a0, __shfl_xor_sync(~0u, a0, 1)); a0 = fmaxf(a0, __shfl_xor_sync(~0u, a0, 2));
    a1 = fmaxf(a1, __shfl_xor_sync(~0u, a1, 1)); a1 = fmaxf(a1, __shfl_xor_sync(~0u, a1, 2));
    const float n0 = fmaxf(m0, a0), n1 = fmaxf(m1, a1);
    const float c0 = (m0 == n0) ? 1.f : ex2(m0 - n0), c1 = (m1 == n1) ? 1.f : ex2(m1 - n1);
    m0 = n0; m1 = n1;
    const uint32_t p0 = pack2(ex2(s[0][0] - n0), ex2(s[0][1] - n0)), p1 = pack2(ex2(s[0][2] - n1), ex2(s[0][3] - n1));
    const uint32_t p2 = pack2(ex2(s[1][0] - n0), ex2(s[1][1] - n0)), p3 = pack2(ex2(s[1][2] - n1), ex2(s[1][3] - n1));
    l0 = l0 * c0 + bf_lo(p0) + bf_hi(p0) + bf_lo(p2) + bf_hi(p2);
    l1 = l1 * c1 + bf_lo(p1) + bf_hi(p1) + bf_lo(p3) + bf_hi(p3);
#pragma unroll
    for (int j = 0; j < 4; j++) {
      o[j][0] *= c0; o[j][1] *= c0; o[j][2] *= c1; o[j][3] *= c1;
      const unsigned short* vp = (const unsigned short*)(vb + (size_t)(k0 + 2 * qd) * 32 + j * 8 + g);
      const uint32_t b0 = (uint32_t)__ldcg(vp) | ((uint32_t)__ldcg(vp + 32) << 16);
      const uint32_t b1 = (uint32_t)__ldcg(vp + 256) | ((uint32_t)__ldcg(vp + 288) << 16);
      mma16816(o[j], p0, p1, p2, p3, b0, b1);
    }
  }
  l0 += __shfl_xor_sync(~0u, l0, 1); l0 += __shfl_xor_sync(~0u, l0, 2);
  l1 += __shfl_xor_sync(~0u, l1, 1); l1 += __shfl_xor_sync(~0u, l1, 2);
#pragma unroll
  for (int j = 0; j < 4; j++) { res[4 * j] = o[j][0]; res[4 * j + 1] = o[j][1]; res[4 * j + 2] = o[j][2]; res[4 * j + 3] = o[j][3]; }
  res[16] = l0; res[18] = l1;
}

__device__ __noinline__ void attn_redo(int redo, int l, int b, int wg, int w, uint32_t tag) {
  const int lane = lane_id();
#pragma unroll 1
  for (int t = 0; t < 4; t++) {
    const int h = t >> 1, head = 2 * (b & 15) + h, row = (b >> 4) * 256 + wg * 128 + (t & 1) * 64 + w * 16 + (lane >> 2);
    if ((redo >> t) & 1) {
      const uint32_t* esc = g_esc + (size_t)((l & 2) * 65536 + head * 2048) * 20;
      const uint32_t* qs = (const uint32_t*)(g_qsave + (block_id() * 256 + wg * 128 + w * 32 + lane) * 8 + 2 * t);
      uint32_t q[8]; float o[20];
#pragma unroll
      for (int i = 0; i < 2; i++) {
        uint32_t u[4] = {__ldcg(qs + i), __ldcg(qs + i + 2), __ldcg(qs + i + 4), __ldcg(qs + i + 6)};
        unesc(u, esc + (row + i * 8) * 20 + (lane & 3), tag);
        q[i] = u[0]; q[i + 2] = u[1]; q[i + 4] = u[2]; q[i + 6] = u[3];
      }
      __syncwarp();
      attn_slow(q, head, esc + 65536 * 20, tag, o, lane);
      const float i0 = rcp(o[16]), i1 = rcp(o[18]);
      bf16* op = g_os + (size_t)row * 1024 + h * 512 + (b & 15) * 32 + (lane & 3) * 8;
      *(uint4*)op = make_uint4(pack2(o[0] * i0, o[1] * i0), pack2(o[4] * i0, o[5] * i0), pack2(o[8] * i0, o[9] * i0), pack2(o[12] * i0, o[13] * i0));
      *(uint4*)(op + 8 * 1024) = make_uint4(pack2(o[2] * i1, o[3] * i1), pack2(o[6] * i1, o[7] * i1), pack2(o[10] * i1, o[11] * i1), pack2(o[14] * i1, o[15] * i1));
    }
    if ((t & 1) && ((redo >> 2 * h) & 3)) bar_arrive(NB_SIG + 2 * h + wg, 160 + 32 * (h & wg));
  }
}

__global__ void __cluster_dims__(2, 1, 1) __launch_bounds__(384, 1) fused_kernel(const __grid_constant__ Params prm) {
  extern __shared__ __align__(1024) char smem[];
  const uint32_t sb = (uint32_t)__cvta_generic_to_shared(smem);
  const int tid = threadIdx.x, lane = tid & 31;
  const int wg = __shfl_sync(0xffffffffu, tid >> 7, 0);
  const int w = __shfl_sync(0xffffffffu, (tid >> 5) & 3, 0);
  const int bm = remap(blockIdx.x) >> 4, bn = remap(blockIdx.x) & 15;

  auto first_tile = [&](int kt) {
    e_expect_tx(sb + B_QF + 8 * kt, QSTG);
    tma_ld(sb + kt * QSTG, &prm.m[M_X0A], kt * 64, bm * 256, sb + B_QF + 8 * kt);
    tma_ld3(sb + kt * QSTG + 32768, &prm.m[M_WQA], bn * 64, kt * 64, 0, sb + B_QF + 8 * kt);
  };
  auto init4 = [&](uint32_t bar, uint32_t c0, uint32_t c1, uint32_t c2, uint32_t c3) {
    asm volatile("{\n.reg .pred pe;\nelect.sync _|pe, 0xffffffff;\n@pe mbarrier.init.shared::cta.b64 [%0], %1;\n@pe mbarrier.init.shared::cta.b64 [%0+8], %2;\n"
                 "@pe mbarrier.init.shared::cta.b64 [%0+16], %3;\n@pe mbarrier.init.shared::cta.b64 [%0+24], %4;\n@pe fence.mbarrier_init.release.cluster;\n}"
                 ::"r"(bar), "r"(c0), "r"(c1), "r"(c2), "r"(c3) : "memory");
  };
  if (wg < 2) {
    const uint32_t k = wg * 4 + w, lo = (0x1411814u >> (4 * k)) & 15, hi = (0x1441814u >> (4 * k)) & 15;
    if (tid < 32) asm volatile("prefetch.global.L2 [%0];" ::"l"(prm.x0 + (size_t)(bm * 256 + bn * 16 + (tid & 15)) * 1024 + (tid >> 4) * 64));
    else if (tid < 80) asm volatile("prefetch.global.L2 [%0];" ::"l"(prm.wq[0] + (bm * 16 + (tid & 15)) * 3072 + ((tid >> 4) - 2) * 1024 + bn * 64));
    __syncwarp();
    if (k < 7) init4(sb + B_QE + 32 * k, lo, lo, hi, k == 6 ? 2 : hi);
    __syncwarp();
    if (k == 6 && lane == 0) *(volatile unsigned long long*)(smem + W_X) = 0ull;
  } else if (w == 0) {
    init4(sb + B_QF, 1, 1, 1, 1);
    __syncwarp();
    first_tile(0);
  }
  __syncthreads();
  asm volatile("barrier.cluster.arrive.relaxed.aligned;" ::: "memory");

  if (wg == 2) {
    asm volatile("setmaxnreg.dec.sync.aligned.u32 56;");
    const uint32_t ep1 = *(volatile uint32_t*)&g_epoch + 1;
    if (w == 0) {
      first_tile(1);
      mbar_wait(sb + B_QF, 0);
      first_tile(2); first_tile(3);
#pragma unroll 1
      for (int kt = 4; kt < 16; kt++) l2_prefetch(prm.wq[0] + kt * 196608 + blockIdx.x * 1536, 3072);
      cluster_wait();
#pragma unroll 1
      for (int l = 0; l < 4; l++) {
        IDS();
        const CUtensorMap* mw = &prm.m[M_WQA + (l & 1)];
        const CUtensorMap* mx = &prm.m[l == 0 ? M_X0A : M_XSA];
        const CUtensorMap* mh = &prm.m[l == 0 ? M_X0H : M_XSO];
        const CUtensorMap* mo = &prm.m[M_WOA + (l & 1)];
        auto q_b = [&](int i) {
          const int s = i & 3;
          mbar_wait(sb + B_QE + 8 * s, ((i >> 2) & 1) ^ 1);
          e_expect_tx(sb + B_QF + 8 * s, QSTG);
          tma_ld3(sb + s * QSTG + 32768, mw, bn * 64, qord(i, l, pn) * 64, 0, sb + B_QF + 8 * s);
        };
        uint32_t rdy = l ? 0u : ~0u;
        auto q_a = [&](int i) {
          const int kt = qord(i, l, pn);
          await_flag(kt, rdy, cnt_x(bm) + (lane & 15), ep1 * 9 - 6 + 2 * l);
          if (i == 3 || (i == 15 && l)) tma_ld(sb + 3 * QSTG, mx, kt * 64, bm * 256, sb + B_QF + 24);
          else tma_ld_mc(sb + (i & 3) * QSTG + rank * 16384, mh, kt * 64, bm * 256 + rank * 128, sb + B_QF + 8 * (i & 3));
        };
        if (l > 0) {
#pragma unroll 1
          for (int i = 0; i < 3; i++) {
            if (i == 2) { q_b(3); q_a(3); }
            const int kt = qord(i, l, pn);
            await_flag(kt, rdy, cnt_x(bm) + (lane & 15), ep1 * 9 - 6 + 2 * l);
            e_expect_tx(sb + B_QF + 8 * i, 16384);
            tma_ld(sb + i * QSTG + (po ^ 1) * 16384, &prm.m[M_XSO], kt * 64, (pm ^ 1) * 128, sb + B_QF + 8 * i);
          }
        }
#pragma unroll 1
        for (int i = 4; i < 16; i++) {
          if (l == 3 && i == 12) poll_ge(cnt_ad(bn), ep1 * 16);
          q_b(i); q_a(i);
        }
        if (l & 1) {
          const int krow = 2 * bn * 2048 + bm * 256;
          uint32_t* kvc = cnt_kv(l >> 1, bn);
          uint32_t seen = 0;
#pragma unroll 1
          for (int it = 1; it < 16; it++) {
            const int s = it & 3;
            if (it == 4) {
              bar_sync(NB_KV + 12, 288);
              mbar_wait(sb + B_TF + 24, 0);
#pragma unroll 1
              for (int i = 0; i < 4; i++) tma_st(&prm.m[M_K + (i & 1)], 0, krow + 2048 + (i >> 1) * 128, sb + i * 8192);
              bulk_commit();
            }
            if (it == 5) { bulk_wait_n<0>(); e_red(kvc + 16 + bm); }
            if (it == 12) { e_expect_tx(sb + B_RF, 32768); tma_ld3(sb + RES, &prm.m[M_XSR], 0, pm * 128, 2 * pn, sb + B_RF); }
            if (it == 1 || it == 3) mbar_wait(sb + B_QE + 12 + 4 * it, 1);
            mbar_wait(sb + B_TE + 8 * s, ((it >> 2) & 1) ^ 1);
            if (it < 8) {
#pragma unroll 1
              for (uint32_t n = 0; n < 200000u && (~seen & (3u << (2 * it - 2) | (it == 4 ? 0xC000u : 0u))); n++)
                seen = __ballot_sync(~0u, (int)(ld_acquire(kvc + (lane < 7 || lane == 15 ? (bm + 1 + lane) & 7 : 8 + ((bm + 2 + lane) & 7))) - ep1) >= 0);
              fence_async_gl();
            } else if (it == 8) { poll_ge(kvc + 16 + (lane & 7), ep1); fence_async_gl(); }
            e_expect_tx(sb + B_TF + 8 * s, 32768);
#pragma unroll 1
            for (int i = 0; i < 2; i++) {
              const int u = 2 * it - 2 + i;
              const int row = 2 * bn * 2048 + (it > 7 ? 2048 + ((bm + it) & 7) * 256 + i * 128 : u < 7 ? ((bm + 1 + u) & 7) * 256 : ((bm + 2 + u) & 7) * 256 + 128);
              tma_ld(sb + T0 + s * TSTG + i * 8192, &prm.m[M_K], 0, row, sb + B_TF + 8 * s);
              tma_ld(sb + T0 + s * TSTG + 16384 + i * 8192, &prm.m[M_V], 0, row, sb + B_TF + 8 * s);
            }
          }
        }
        auto p_b = [&](int i, uint32_t s, uint32_t par) {
          mbar_wait(sb + B_PE + 8 * s, par ^ 1);
          e_expect_tx(sb + B_PF + 8 * s, PSTG);
          tma_ld5(sb + pslot_b(s), mo, i >> 3, 2 * (i & 7), 2 * pn, sb + B_PF + 8 * s);
        };
        auto p_a = [&](int i, uint32_t s) {
          await_flag(i, rdy, cnt_o(l, pm, (lane >> 3) & 1) + (lane & 7), ep1 * 2);
          tma_ld_mc(sb + pslot_a(s, l) + rank * 8192, &prm.m[M_OS], i * 64, pm * 128 + rank * 64, sb + B_PF + 8 * s);
        };
        auto p_a2 = [&](int i) {
          await_flag(i, rdy, cnt_o(l, pm, (lane >> 3) & 1) + (lane & 7), ep1 * 2);
          tma_ld(sb + pslot_a(i, l), &prm.m[M_OS], i * 64, pm * 128, sb + B_PF + 8 * i);
          tma_ld(sb + pslot_a(i, l) + 8192, &prm.m[M_OS], i * 64, pm * 128 + 64, sb + B_PF + 8 * i);
        };
        rdy = 0;
        if (l & 1) {
#pragma unroll 1
          for (int u = 0; u < 6; u++) { const int i = (0x205413 >> (4 * u)) & 7; if (u == 4) mbar_wait(sb + B_TE, 1); p_b(i, i, i < 4 ? 1 : 0); }
#pragma unroll 1
          for (int u = 0; u < 6; u++) {
            const int i = (0x542130 >> (4 * u)) & 7;
            if (!(u & 1)) mbar_wait(sb + B_TE + 8 + 4 * u, 1);
            if (u == 4) bar_sync(NB_SIG + 3, 192);
            p_a2(i);
          }
        } else {
#pragma unroll 1
          for (int u = 0; u < 6; u++) { const int i = (0x543120 >> (4 * u)) & 7; if (u == 0 || u == 2) mbar_wait(sb + B_QE + 8 - 4 * u, 1); p_b(i, i, 0); }
          mbar_wait(sb + B_QE + 24, 1);
          e_expect_tx(sb + B_RF, 32768);
          tma_ld3(sb + RES, &prm.m[l == 0 ? M_X0R : M_XSR], 0, pm * 128, 2 * pn, sb + B_RF);
          p_a2(0);
          bar_sync(NB_SIG + 2, 320);
          e_arrive_both(sb + B_PA);
          p_a2(1);
          mbar_wait(sb + B_PA, (l >> 1) & 1);
#pragma unroll 1
          for (int i = 2; i < 6; i++) { if (i > 2) mbar_wait(sb + B_PF + 8 * (i - 3), 0); p_a(i, i); }
        }
        uint32_t s = 0, lap = 1;
#pragma unroll 1
        for (int i = 6; i < 16; i++) {
          p_b(i, s, ((s < 4 ? l : 0) + lap) & 1);
          p_a(i, s);
          if (++s == 6) { s = 0; lap++; }
        }
        const CUtensorMap* mn = &prm.m[M_WQA + ((l + 1) & 1)];
        if (l < 3) {
          mbar_wait(sb + B_PE + 8 * 4, 1); mbar_wait(sb + B_PE + 8 * 5, 1);
          tma_ld3(sb + 32768, mn, bn * 64, 2 * pn * 64, 0, sb + B_QL);
          mbar_wait(sb + B_PE + 8 * 0, l & 1);
          e_expect_tx(sb + B_PA, 24576); e_expect_tx(sb + B_PA, 16384);
          tma_ld3(sb + QSTG + 32768, mn, bn * 64, ((2 * pn) ^ 2) * 64, 0, sb + B_PA);
          mbar_wait(sb + B_PE + 8 * 1, l & 1);
          tma_ld3(sb + 2 * QSTG + 32768, mn, bn * 64, (2 * pn + 1) * 64, 0, sb + B_QL);
          mbar_wait(sb + B_PE + 24, l & 1);
          bar_sync(NB_X0, 320);
          fence_async_gl();
          tma_ld_mc(sb + QSTG + po * 16384, &prm.m[M_XSO], 2 * pn * 64, pm * 128, sb + B_PA, 2 - rank);
        }
        if (l < 3) { bar_sync(NB_X, 320); e_expect_tx(sb + B_QL, 49152); }
      }
      if (blockIdx.x == 0 && lane_id() == 0) *(volatile uint32_t*)&g_epoch = ep1;
    } else {
      const int hw = w - 1;
      if (lane < 5) asm volatile("prefetch.tensormap [%0];" ::"l"(&prm.m[5 * hw + lane]) : "memory");
      __syncwarp();
      cluster_wait();
      mbar_wait(sb + B_QF, 0);
#pragma unroll 1
      for (int l = 0; l < 4; l++) {
        IDS();
        if (l > 0) { mbar_wait(sb + B_QL, (l + 1) & 1); mbar_wait(sb + B_QF + 24, 0); }
        if (l == 0) {
#pragma unroll 1
          for (int r = 2 * hw; r < 16; r += 6) {
            const uint4* p = (const uint4*)(prm.x0 + (size_t)(b * 16 + r) * 1024) + lane;
            float s1[2] = {0.f, 0.f}, s2[2] = {0.f, 0.f};
#pragma unroll
            for (int i = 0; i < 8; i++) {
              const uint4 v = __ldg(p + 32 * i);
              const uint32_t u[4] = {v.x, v.y, v.z, v.w};
#pragma unroll
              for (int k = 0; k < 4; k++) { const float a = bf_lo(u[k]), c = bf_hi(u[k]); s1[i >> 2] += a + c; s2[i >> 2] = fmaf(a, a, fmaf(c, c, s2[i >> 2])); }
            }
#pragma unroll
            for (int o = 16; o; o >>= 1)
#pragma unroll
              for (int rr = 0; rr < 2; rr++) { s1[rr] += __shfl_xor_sync(~0u, s1[rr], o); s2[rr] += __shfl_xor_sync(~0u, s2[rr], o); }
            if (lane == 0) *(float4*)&g_stats[b * 16 + r] = make_float4(s1[0], s2[0], s1[1], s2[1]);
          }
        }
        if (l < 2) {
          float cs[8];
#pragma unroll
          for (int i = 0; i < 8; i++) cs[i] = 0.f;
          const uint4* wp = (const uint4*)(prm.wq[l] + (size_t)(bm * 128 + (lane >> 3)) * 3072 + hw * 1024 + bn * 64) + (lane & 7);
#pragma unroll 8
          for (int i = 0; i < 32; i++) {
            const uint4 v = __ldg(wp + (size_t)i * 4 * 384);
            cs[0] += bf_lo(v.x); cs[1] += bf_hi(v.x); cs[2] += bf_lo(v.y); cs[3] += bf_hi(v.y);
            cs[4] += bf_lo(v.z); cs[5] += bf_hi(v.z); cs[6] += bf_lo(v.w); cs[7] += bf_hi(v.w);
          }
#pragma unroll
          for (int i = 0; i < 8; i++) { cs[i] += __shfl_xor_sync(~0u, cs[i], 8); cs[i] += __shfl_xor_sync(~0u, cs[i], 16); }
          if (lane < 8) {
            float4* d = (float4*)(g_csp + ((l * 16 + bn) * 8 + bm) * 192 + hw * 64 + lane * 8);
            d[0] = make_float4(cs[0], cs[1], cs[2], cs[3]); d[1] = make_float4(cs[4], cs[5], cs[6], cs[7]);
          }
          __syncwarp();
          asm volatile("fence.acq_rel.gpu;" ::: "memory");
          e_red_relaxed(cnt_cs(l, bn));
          if (l == 0) e_red_relaxed(cnt_x(bm) + bn);
          poll_ge(lane < 16 && l == 0 ? cnt_x(bm) + lane : cnt_cs(l, bn), lane < 16 && l == 0 ? ep1 * 9 - 6 : ep1 * 24);
        }
        if (l > 0) poll_ge(cnt_x(bm) + (lane & 15), ep1 * 9 - 6 + 2 * l);
#pragma unroll 1
        for (int it = hw * 32 + lane; it < 176; it += 96) {
          const bool rows = it < 128;
          const float4* p = rows ? (const float4*)(g_stats + bm * 256) + it : (const float4*)(g_csp + ((l & 1) * 16 + bn) * 8 * 192) + (it - 128);
          const int stride = rows ? 1024 : 48, np = rows && l == 0 ? 1 : 8;
          float4 a = make_float4(0.f, 0.f, 0.f, 0.f);
#pragma unroll
          for (int k = 0; k < 8; k++) if (k < np) { const float4 v = __ldcg(p + k * stride); a.x += v.x; a.y += v.y; a.z += v.z; a.w += v.w; }
          if (rows) {
            const float m0 = a.x * (1.f / 1024.f), m1 = a.z * (1.f / 1024.f);
            const float v0 = fmaxf(a.y * (1.f / 1024.f) - m0 * m0, 0.f), v1 = fmaxf(a.w * (1.f / 1024.f) - m1 * m1, 0.f);
            const float r0 = __fdividef(1.f, bf_round(sqrtf(bf_round(bf_round(v0) + 1e-5f)))), r1 = __fdividef(1.f, bf_round(sqrtf(bf_round(bf_round(v1) + 1e-5f))));
            a = make_float4(r0, -bf_round(m0), r1, -bf_round(m1));
          }
          if (rows && (l & 1) && (it & 4)) a = make_float4(a.y, a.x, a.w, a.z);
          *(float4*)(smem + ROWST + it * 16) = a;
        }
        __syncwarp();
        if (lane == 0) asm volatile("red.release.cta.shared.add.u32 [%0], 1;" ::"r"(sb + W_X) : "memory");
        if (hw == 2) {
          if (!(l & 1)) {
            bar_sync(NB_ST, 288);
            const uint4* hp = g_halo + (b - 16) * 384 + lane;
#pragma unroll 1
            for (int h = 0; h < 2; h++) {
              uint32_t t[18];
#pragma unroll
              for (int i = 0; i < 18; i++) t[i] = 0;
#pragma unroll 1
              for (uint32_t n = bm ? 0 : 100000u; n < 100000u; n++) {
                uint32_t miss = 0;
#pragma unroll
                for (int i = 0; i < 6; i++) miss |= ld_tagged(hp + h * 192 + i * 32, &t[3 * i]) ^ (4 * ep1 + l);
                if (__all_sync(~0u, !miss)) break;
              }
              mbar_wait(sb + B_QE + 16, 1);
              const uint32_t r = (lane & 7) + ((lane >> 3) & 1) * 8, rv = lane >> 2;
#pragma unroll
              for (int jj = 0; jj < 2; jj++) stsm4(sb + KSC + r * 128 + (((4 * h + 2 * jj + (lane >> 4)) ^ (r & 7)) << 4), t[4 * jj], t[4 * jj + 1], t[4 * jj + 2], t[4 * jj + 3]);
              const uint32_t ad = sb + VSC + rv * 128 + (((4 * h + (lane & 3)) ^ (rv & 7)) << 4);
              sts128(ad, t[8], t[10], t[12], t[14]); sts128(ad + 1024, t[9], t[11], t[13], t[15]);
              if (h == 0 && !(lane & 2)) *(uint32_t*)(smem + HRS + ((lane >> 2) + 8 * (lane & 1)) * 8) = t[16];
              bar_arrive(NB_HALO + h, 64);
            }
          } else {
            bar_sync(NB_KV, 288);
            sts128(sb + ONES + lane * 32, 0x3f803f80u, 0x3f803f80u, 0x3f803f80u, 0x3f803f80u);
            sts128(sb + ONES + lane * 32 + 16, 0x3f803f80u, 0x3f803f80u, 0x3f803f80u, 0x3f803f80u);
            sts128(sb + ROWST + 16, 0x62A962A9u, 0x00010001u, 0x3F003F00u, 0u);
            fence_async_smem();
            __syncwarp();
            e_arrive(sb + B_TF);
            mbar_wait(sb + B_TF + 16, 0); mbar_wait(sb + B_TF + 16, 1);
            poll_ge(cnt_kv(l >> 1, bn) + 16 + (lane & 7), ep1);
            const uint4 v = __ldcg((const uint4*)(g_kn + ((l >> 1) * 128 + bn * 8) * 16) + lane);
            const uint32_t mx = max(max(v.x, v.y), max(v.z, v.w));
            const uint32_t m0 = __reduce_max_sync(~0u, (lane & 2) ? 0u : mx), m1 = __reduce_max_sync(~0u, (lane & 2) ? mx : 0u);
            if (lane == 0) *(uint2*)(smem + ROWST) = make_uint2(m0, m1);
            __syncwarp();
            bar_arrive(NB_KN, 160); bar_arrive(NB_KN + 1, 160);
          }
        } else {
          if (l & 1) {
            uint32_t* p = cnt_kv(l >> 1, bn) + 8 * hw + bm;
            int on = lane == 0;
            PREPARED(p, on);
            bar_sync(hw ? NB_HALO : NB_DONE, 160);
            tma_st(&prm.m[M_K], 0, 2 * bn * 2048 + bm * 256 + hw * 128, sb + T0 + hw * 8192);
            tma_st(&prm.m[M_V], 0, 2 * bn * 2048 + bm * 256 + hw * 128, sb + T0 + 16384 + hw * 8192);
            bulk_commit(); bulk_wait_n<0>();
            release_add(p, on);
          }
#pragma unroll 1
          for (int h = l & 1 ? 0 : hw; h <= (l & 1 ? 1 : hw); h++) {
            uint32_t* p = l == 1 && lane == 1 ? cnt_ad(bn) : cnt_o(l, 2 * bm + (l & 1 ? hw : lane & 1), h) + (bn >> 1);
            int on = lane == 0 || (lane == 1 && (!(l & 1) || (l == 1 && h == 1)));
            int id = NB_SIG + 2 * h + (l & hw), n = (l & 1 ? 160 : 288) + 32 * (h & hw);
            asm volatile("" : "+r"(id), "+r"(n));
            PREPARED(p, on);
            bar_sync(id, n);
            release_add(p, on);
          }
        }
        if (hw < 2 && l < 3) {
          uint32_t* p = cnt_x(bm) + 2 * pn + hw;
          int on = lane == 0;
          PREPARED(p, on);
          if (hw) {
            bar_sync(NB_X, 320);
            tma_st(&prm.m[M_XSO], pn * 128 + 64, pm * 128, sb + 2 * QSTG + po * 16384);
            bulk_commit();
            bar_sync(NB_KV, 288);
            bulk_wait_n<0>();
          } else bar_sync(NB_X0, 320);
          release_add(p, on);
        }
      }
    }
  } else {
    asm volatile("setmaxnreg.inc.sync.aligned.u32 224;");
    const uint32_t zero = prm.zero;
    cluster_wait();
#pragma unroll 1
    for (int l = 0; l < 4; l++) {
      {
        float acc[2][96];
        const bool early = l > 0 && wg == ((cta_id() >> 3) & 1);
        uint32_t ep1 = 0;
        if (l > 0) mbar_wait(sb + B_QL, (l + 1) & 1);
        if (!early) mbar_wait(sb + B_QF, 0);
        wg_fence();
#pragma unroll
        for (int k = 0; k < 4; k++)
#pragma unroll
          for (int m = 0; m < 2; m++) {
            if (k) wgmma_m64n192k16_ss_tb(acc[m], prm.xd + wg * 1024 + m * 512 + k * 2, prm.wd + k * 128, 1);
            else wgmma_m64n192k16_ss_tb_z(acc[m], prm.xd + wg * 1024 + m * 512, prm.wd, 0);
          }
        wg_commit();
#pragma unroll 1
        for (int kt = 1; kt < 13; kt++) {
          const int s = kt == 12 ? 1 : kt & 3;
          if (l > 0 && kt == 1) mbar_wait(sb + B_PA, l == 1);
          if (!(early && kt < 3)) mbar_wait(sb + B_QF + 8 * s, (kt >> 2) & 1);
          const uint64_t da = prm.xd + wg * 1024 + s * (QSTG >> 4), db = prm.wd + s * (QSTG >> 4);
          wg_fence();
#pragma unroll
          for (int k = 0; k < 4; k++)
#pragma unroll
            for (int m = 0; m < 2; m++) wgmma_m64n192k16_ss_tb(acc[m], da + m * 512 + k * 2, db + k * 128, 1);
          wg_commit();
          if (kt == 4) ep1 = *(volatile uint32_t*)&g_epoch + 1;
          wg_wait<1>();
          if (early && kt < 4) {
            if (kt < 2) continue;
            if (kt == 2) { mbar_wait(sb + B_QF, 0); if (w == 0) e_arrive_both(sb + B_QE); }
            mbar_wait(sb + B_QF + 8 * (kt - 1), 0);
          }
          if (w == 0) e_arrive_both(sb + B_QE + 8 * ((kt - 1) & 3));
        }
        {
          const bool lag = (l & 1) == wg;
          const uint32_t s0 = 2 * (~l & 1);
          const uint64_t da = prm.xd + wg * 1024 + 2 * (QSTG >> 4), db = prm.wd + 2 * (QSTG >> 4);
          mbar_wait(sb + B_QF + 8 * s0, 1);
#pragma unroll
          for (int t = 0; t < 2; t++) {
            if (lag && t != wg) {
              wg_wait<0>();
              if (w == 0) e_arrive_both(sb + B_QE + 8 + 8 * t);
              if (t == 0) mbar_wait(sb + B_QF + 16, 1);
              mbar_wait(sb + B_QF + 24, 1);
              if (t == 1) bar_arrive(NB_ST, 288);
              bar_sync(NB_SC, 256);
            }
            const uint64_t so = (uint64_t)(t ? s0 : s0 ^ 2) * (QSTG >> 4);
            wg_fence();
#pragma unroll
            for (int k = 0; k < 4; k++)
#pragma unroll
              for (int m = 0; m < 2; m++) wgmma_m64n192k16_ss_tb(acc[m], da - so + m * 512 + k * 2, db - so + k * 128, 1);
            wg_commit();
            if (!lag || t + wg == 0) {
              wg_wait<1>();
              if (w == 0) e_arrive_both(sb + B_QE + 8 * (t ? s0 : 1));
              mbar_wait(sb + B_QF + 8 * (t ? 3 : s0 ^ 2), 1);
            }
          }
          wg_fence();
#pragma unroll
          for (int m = 1; m >= 0; m--) {
#pragma unroll
            for (int k = 0; k < 4; k++) wgmma_m64n192k16_ss_tb(acc[m], da + (QSTG >> 4) + m * 512 + k * 2, db + (QSTG >> 4) + k * 128, 1);
            wg_commit();
          }
          if (!lag) { bar_arrive(NB_SC, 256); if (wg) bar_arrive(NB_ST, 288); }
          wg_wait<2>();
          if (w == 0) { e_arrive_both(sb + B_QE + 8 * (s0 ^ 2)); if (lag && wg) e_arrive_both(sb + B_QE); }
        }
#pragma unroll 1
        for (uint32_t n = 0; n < 4000000u; n++) {
          uint32_t v;
          asm volatile("ld.acquire.cta.shared.u32 %0, [%1];" : "=r"(v) : "r"(sb + W_X) : "memory");
          if (v == (uint32_t)(3 * l + 3)) break;
        }
        IDS();
        const int g = lane >> 2, qd = lane & 3;
        float2 st[2][2];
#pragma unroll
        for (int m = 0; m < 2; m++)
#pragma unroll
          for (int hh = 0; hh < 2; hh++) st[m][hh] = lds64f(sb + ROWST + (wg * 128 + m * 64 + w * 16 + g + 8 * hh) * 8);
        float2 cs[4];
        auto load_cs = [&](int gi) {
#pragma unroll
          for (int j = 0; j < 4; j++) cs[j] = lds64f(sb + COLS + (gi * 32 + j * 8 + 2 * qd) * 4);
        };
        load_cs(2 + 2 * (l & 1));
        auto drain = [&]() {
          wg_wait<0>(); fence_regs(acc[0]);
          if (w == 0) e_arrive_both(sb + B_QE + 8 * 3);
        };
        wg_wait<1>(); fence_regs(acc[1]);
        auto norm_tile = [&](int gi, int m, float sc, uint32_t (&t)[8], float (&nrm)[2], bool h16 = false) {
          const float r0 = st[m][0].x * sc, s0 = st[m][0].y, r1 = st[m][1].y * sc, s1 = st[m][1].x;
          float n0 = 0.f, n1 = 0.f;
#pragma unroll
          for (int j = 0; j < 4; j++) {
            const float* a = &acc[m][16 * gi + 4 * j];
            const float v0 = fmaf(s0, cs[j].x, a[0]) * r0, v1 = fmaf(s0, cs[j].y, a[1]) * r0;
            const float v2 = fmaf(s1, cs[j].x, a[2]) * r1, v3 = fmaf(s1, cs[j].y, a[3]) * r1;
            n0 = fmaf(v0, v0, fmaf(v1, v1, n0)); n1 = fmaf(v2, v2, fmaf(v3, v3, n1));
            t[2 * j] = h16 ? pack2h(v0, v1) : pack2(v0, v1); t[2 * j + 1] = h16 ? pack2h(v2, v3) : pack2(v2, v3);
          }
          nrm[0] = n0; nrm[1] = n1;
        };
        auto norm_group = [&](int gi, float sc, uint32_t (&t)[2][8], float (&nrm)[2][2]) { norm_tile(gi, 0, sc, t[0], nrm[0]); norm_tile(gi, 1, sc, t[1], nrm[1]); };
        uint32_t q[2][2][8];
        const uint32_t srow = (lane & 7) + ((lane >> 3) & 1) * 8;
        const uint32_t row0 = wg * 128 + w * 16;
        if (!(l & 1)) {
          auto put_kv = [&](int gi, uint32_t r0, const uint32_t (&t)[8]) {
            if (gi < 4) {
              const uint32_t r = r0 + srow;
#pragma unroll
              for (int jj = 0; jj < 2; jj++) stsm4(sb + KSC + r * 128 + (((4 * (gi - 2) + 2 * jj + (lane >> 4)) ^ (r & 7)) << 4), t[4 * jj], t[4 * jj + 1], t[4 * jj + 2], t[4 * jj + 3]);
            } else {
              const uint32_t r = r0 + g, ad = sb + VSC + r * 128 + (((4 * (gi - 4) + qd) ^ (r & 7)) << 4);
              sts128(ad, t[0], t[2], t[4], t[6]); sts128(ad + 1024, t[1], t[3], t[5], t[7]);
            }
          };
          auto cen_tile = [&](int gi, int m, uint32_t (&t)[8]) {
#pragma unroll
            for (int j = 0; j < 4; j++) {
              const float* a = &acc[m][16 * gi + 4 * j];
              t[2 * j] = pack2(fmaf(st[m][0].y, cs[j].x, a[0]), fmaf(st[m][0].y, cs[j].y, a[1]));
              t[2 * j + 1] = pack2(fmaf(st[m][1].y, cs[j].x, a[2]), fmaf(st[m][1].y, cs[j].y, a[3]));
            }
          };
          const bool send = wg == 1 && w == 3 && bm < 7;
          uint4* hp = g_halo + b * 384 + lane;
          ep1 = 4 * ep1 + l;
          mbar_wait(sb + B_QE + 16, 1);
          float2 cn[4];
          auto next_cs = [&](int gi) {
#pragma unroll
            for (int j = 0; j < 4; j++) { cs[j] = cn[j]; cn[j] = lds64f(sb + COLS + (gi * 32 + j * 8 + 2 * qd) * 4); }
          };
#pragma unroll
          for (int j = 0; j < 4; j++) cn[j] = cs[j];
#pragma unroll
          for (int h = 0; h < 2; h++) {
            uint32_t k[8], v[8];
            next_cs(4 + h);
            cen_tile(2 + h, 1, k); put_kv(2 + h, 16 + row0 + 64, k);
            next_cs(h ? 2 : 3);
            cen_tile(4 + h, 1, v); put_kv(4 + h, 16 + row0 + 64, v);
            if (send) {
              uint4* p = hp + h * 192;
              st_tagged(p, k[0], k[1], k[2], ep1); st_tagged(p + 32, k[3], k[4], k[5], ep1); st_tagged(p + 64, k[6], k[7], v[0], ep1);
              st_tagged(p + 96, v[1], v[2], v[3], ep1); st_tagged(p + 128, v[4], v[5], v[6], ep1);
              st_tagged(p + 160, v[7], __float_as_uint(qd & 1 ? st[1][1].x : st[1][0].x), 0u, ep1);
            }
            sched_fence();
          }
          drain();
          {
            uint32_t t[8];
            next_cs(4); cen_tile(2, 0, t); put_kv(2, 16 + row0, t);
            next_cs(0); cen_tile(4, 0, t); put_kv(4, 16 + row0, t);
            next_cs(3); cen_tile(0, 0, q[0][0]); cen_tile(0, 1, q[0][1]);
          }
          const bool e = g & 1, sel = 2 * qd + (g & 1) >= g + 2, first = bm == 0 && row0 == 0;
          uint32_t ka = sb + KSC + (row0 + (lane & 7)) * 128 + (((lane >> 3) ^ (lane & 7)) << 4);
          uint32_t wa = sb + VSC + (row0 + srow) * 128 + (((lane >> 4) ^ (lane & 7)) << 4);
          uint32_t psel[3] = {e ? 0x1044u : 0x4410u, !sel ? 0x4444u : e ? 0x3244u : 0x4432u, sel ? 0x4444u : e ? 0x3244u : 0x4432u};
          bf16* op = g_os + (size_t)(bm * 256 + row0 + g) * 1024 + bn * 32 + qd * 8;
          asm volatile("" : "+r"(ka), "+r"(wa), "+l"(op));
          fence_regs(psel); fence_regs(q[0][0]); fence_regs(q[0][1]);
          sched_fence();
          bar_sync(NB_SC, 256);
          if (row0 == 0) bar_sync(NB_HALO, 64);
          float ra[4], rb[4], ca[4], cb[4];
#pragma unroll
          for (int m = 0; m < 2; m++) {
            float rk[3];
#pragma unroll
            for (int u = 0; u < 3; u++) {
              const int r = row0 + m * 64 + 8 * u + 2 * qd + e - (sel ? 16 : 8);
              rk[u] = lds64f(sb + (m == 0 && r < 0 ? HRS + 128 : ROWST) + r * 8).x;
            }
            ra[2 * m] = sel ? rk[1] : rk[0]; ra[2 * m + 1] = sel ? rk[2] : rk[1];
            rb[2 * m] = sel ? rk[0] : rk[1]; rb[2 * m + 1] = sel ? rk[1] : rk[2];
          }
#pragma unroll
          for (int i = 0; i < 4; i++) { const float rq = st[i >> 1][i & 1].x * QSCALE; ca[i] = rq * ra[i]; cb[i] = rq * rb[i]; }
#pragma unroll 1
          for (int h = 0; h < 2; h++) {
            float s[2][4][4];
            uint32_t vf[2][4][4], pf[2][2][4];
#pragma unroll
            for (int m = 0; m < 2; m++)
#pragma unroll
              for (int nt = 0; nt < 4; nt++) {
                uint32_t kf[4];
                ldsm4(ka + (m * 64 + 8 * nt) * 128, kf);
                s[m][nt][0] = s[m][nt][1] = s[m][nt][2] = s[m][nt][3] = 0.f;
                mma16816(s[m][nt], q[0][m][0], q[0][m][1], q[0][m][2], q[0][m][3], kf[0], kf[1]);
                mma16816(s[m][nt], q[0][m][4], q[0][m][5], q[0][m][6], q[0][m][7], kf[2], kf[3]);
              }
#pragma unroll
            for (int m = 0; m < 2; m++)
#pragma unroll
              for (int i = 0; i < 4; i++) {
                ldsm4t((wa ^ (32 * (i & 1))) + (m * 64 + 16 * (i >> 1)) * 128, vf[m][i]);
              }
            float va[4], vb[4], mx[4];
#pragma unroll
            for (int i = 0; i < 4; i++) {
              const int m = i >> 1, hh = i & 1;
              const float a = e ? s[m][hh + 1][2 * hh + 1] : s[m][hh + 1][2 * hh];
              const float lo = e ? s[m][hh][2 * hh + 1] : s[m][hh][2 * hh], hi = e ? s[m][hh + 2][2 * hh + 1] : s[m][hh + 2][2 * hh];
              va[i] = (m == 0 && hh == 0 && first) ? -INFINITY : a * ca[i];
              vb[i] = (m == 0 && first && sel) ? -INFINITY : (sel ? lo : hi) * cb[i];
              mx[i] = fmaxf(va[i], vb[i]);
            }
#pragma unroll
            for (int i = 0; i < 4; i++) mx[i] = fmaxf(mx[i], __shfl_xor_sync(~0u, mx[i], 1));
#pragma unroll
            for (int i = 0; i < 4; i++) mx[i] = fmaxf(mx[i], __shfl_xor_sync(~0u, mx[i], 2));
#pragma unroll
            for (int i = 0; i < 4; i++) {
              va[i] = ex2(va[i] - mx[i]); vb[i] = ex2(vb[i] - mx[i]);
              mx[i] = va[i] + vb[i];
              va[i] *= ra[i]; vb[i] *= rb[i];
            }
#pragma unroll
            for (int i = 0; i < 4; i++) mx[i] += __shfl_xor_sync(~0u, mx[i], 1);
#pragma unroll
            for (int i = 0; i < 4; i++) mx[i] += __shfl_xor_sync(~0u, mx[i], 2);
#pragma unroll
            for (int i = 0; i < 4; i++) {
              const int m = i >> 1, hh = i & 1;
              const float inv = rcp(mx[i]);
              const uint32_t t = pack2(va[i] * inv, vb[i] * inv);
              pf[m][hh][hh + 1] = prmt0(t, psel[0]); pf[m][hh][hh] = prmt0(t, psel[1]); pf[m][hh][hh + 2] = prmt0(t, psel[2]);
              pf[m][hh][3 - 3 * hh] = t & zero;
            }
#pragma unroll
            for (int m = 0; m < 2; m++) {
              float o[4][4];
#pragma unroll
              for (int j = 0; j < 4; j++) o[j][0] = o[j][1] = o[j][2] = o[j][3] = 0.f;
#pragma unroll
              for (int i = 0; i < 4; i++) {
                const int kk = i >> 1, jj = 2 * (i & 1);
                mma16816(o[jj], pf[m][0][2 * kk], pf[m][1][2 * kk], pf[m][0][2 * kk + 1], pf[m][1][2 * kk + 1], vf[m][i][0], vf[m][i][1]);
                mma16816(o[jj + 1], pf[m][0][2 * kk], pf[m][1][2 * kk], pf[m][0][2 * kk + 1], pf[m][1][2 * kk + 1], vf[m][i][2], vf[m][i][3]);
              }
              stg128(op + m * 65536, pack2(o[0][0], o[0][1]), pack2(o[1][0], o[1][1]), pack2(o[2][0], o[2][1]), pack2(o[3][0], o[3][1]));
              stg128(op + m * 65536 + 8192, pack2(o[0][2], o[0][3]), pack2(o[1][2], o[1][3]), pack2(o[2][2], o[2][3]), pack2(o[3][2], o[3][3]));
            }
            bar_arrive(NB_SIG + 2 * h, 288 + 32 * h);
            if (h == 0) {
              uint32_t t[8];
              next_cs(5); cen_tile(3, 0, t); put_kv(3, 16 + row0, t);
              next_cs(1); cen_tile(5, 0, t); put_kv(5, 16 + row0, t);
#pragma unroll
              for (int j = 0; j < 4; j++) cs[j] = cn[j];
              cen_tile(1, 0, q[0][0]); cen_tile(1, 1, q[0][1]);
              ka ^= 64; wa ^= 64; op += 512;
              bar_sync(NB_SC, 256);
              if (row0 == 0) bar_sync(NB_HALO + 1, 64);
            }
          }
        } else {
          float qn[2];
          mbar_wait(sb + B_QE + 8, 1);
          drain();
          auto esc_ptr = [&](int gi) { IDS(); return g_esc + (size_t)(((l & 2) + (gi >> 1)) * 65536 + (2 * bn + (gi & 1)) * 2048) * 20; };
          auto norm_half = [&](int gi, float sc, uint32_t (&t)[2][8], float (&nrm)[2][2], int nx) {
            norm_tile(gi, 0, sc, t[0], nrm[0], true); norm_tile(gi, 1, sc, t[1], nrm[1], true);
            float2 cn[4];
#pragma unroll
            for (int j = 0; j < 4; j++) if (nx >= 0) cn[j] = lds64f(sb + COLS + (nx * 32 + j * 8 + 2 * qd) * 4);
            if (!((nrm[0][0] + nrm[0][1]) + (nrm[1][0] + nrm[1][1]) <= 4e9f) || fminf(fminf(nrm[0][0], nrm[0][1]), fminf(nrm[1][0], nrm[1][1])) < 1.5e-5f) {
              uint32_t* p = esc_ptr(gi) + (bm * 256 + row0 + g) * 20 + qd;
#pragma unroll
              for (int m = 0; m < 2; m++) {
                uint32_t u[8]; float d[2];
                norm_tile(gi, m, sc, u, d);
#pragma unroll
                for (int i = 0; i < 10; i++) p[(m * 64 + (i & 1) * 8) * 20 + (i >> 1) * 4] = i < 8 ? u[i] : ep1;
              }
            }
            __syncwarp();
#pragma unroll
            for (int i = 0; i < 16; i++) asm volatile("{\n.reg .b32 u;\nadd.u32 u, %0, 0x00040004;\nand.b32 %0, u, 0xFFF8FFF8;\n}" : "+r"(t[i >> 3][i & 7]));
#pragma unroll
            for (int j = 0; j < 4; j++) if (nx >= 0) cs[j] = cn[j];
          };
          {
            auto max_norm = [&](const float (&nrm)[2][2]) {
              const bool o1 = qd & 1, o2 = qd & 2;
              const float a = (o1 ? nrm[1][0] : nrm[0][0]) + __shfl_xor_sync(~0u, o1 ? nrm[0][0] : nrm[1][0], 1);
              const float c = (o1 ? nrm[1][1] : nrm[0][1]) + __shfl_xor_sync(~0u, o1 ? nrm[0][1] : nrm[1][1], 1);
              const float d = (o2 ? c : a) + __shfl_xor_sync(~0u, o2 ? a : c, 2);
              return __uint_as_float(__reduce_max_sync(~0u, __float_as_uint(d)));
            };
#pragma unroll
            for (int h = 0; h < 2; h++) {
              uint32_t t[2][8]; float nrm[2][2];
              const uint32_t kb = sb + (h ? wg * 8192 : T0), vb = kb + (h ? 8192 : 16384);
              norm_group(4 + h, 1.f, t, nrm);
              load_cs(2 + h);
#pragma unroll
              for (int m = 0; m < 2; m++) {
                const uint32_t r = row0 + m * 64 + g, ad = vb + r * 64 + ((qd ^ ((r >> 1) & 3)) << 4);
                sts128(ad, t[m][0], t[m][2], t[m][4], t[m][6]); sts128(ad + 512, t[m][1], t[m][3], t[m][5], t[m][7]);
              }
              norm_half(2 + h, 1.f, t, nrm, h);
#pragma unroll
              for (int i = 0; i < 4; i++) {
                const uint32_t r = row0 + (i >> 1) * 64 + srow;
                stsm4(kb + r * 64 + (((2 * (i & 1) + (lane >> 4)) ^ ((r >> 1) & 3)) << 4), t[i >> 1][4 * (i & 1)], t[i >> 1][4 * (i & 1) + 1], t[i >> 1][4 * (i & 1) + 2], t[i >> 1][4 * (i & 1) + 3]);
              }
              if (h == 1) { const float kn = max_norm(nrm); if (lane == 0) g_kn[((l >> 1) * 128 + bn * 8 + bm) * 16 + 8 + wg * 4 + w] = kn; }
              fence_async_smem();
              bar_arrive(NB_KV + 12 * h, 288);
              if (h == 0) {
                bar_arrive(wg ? NB_HALO : NB_DONE, 160);
              }
              if (h == 0) { const float kn = max_norm(nrm); if (lane == 0) g_kn[((l >> 1) * 128 + bn * 8 + bm) * 16 + wg * 4 + w] = kn; }
              norm_half(h, QSCALE, q[h], nrm, h ? -1 : 5);
#pragma unroll
              for (int i = 0; i < 4 * h; i++) sts128(sb + QPARK + 24576 - wg * 8192 + (w * 32 + lane) * 16 + i * 2048, q[h][i >> 1][4 * (i & 1)], q[h][i >> 1][4 * (i & 1) + 1], q[h][i >> 1][4 * (i & 1) + 2], q[h][i >> 1][4 * (i & 1) + 3]);
              qn[h] = max_norm(nrm);
            }
          }
          constexpr uint64_t VSTEP = 64 - (64ull << 16);
          uint32_t cq[4];
          const uint32_t &c_852 = cq[0], &c_lsb = cq[1], &c_half = cq[2];
          float o[2][20], S[2][32];
          uint32_t H[2][16], P0[4] = {}, P1[4] = {};
#pragma unroll
          for (int m = 0; m < 2; m++) {
#pragma unroll
            for (int i = 0; i < 20; i++) o[m][i] = 0.f;
            fence_regs(o[m]);
          }
          auto qkf = [&](int b, int ks, uint64_t d) { wg_n64_rs_nb_f16_f32(S[b], q[0][0][4 * ks], q[0][0][4 * ks + 1], q[0][0][4 * ks + 2], q[0][0][4 * ks + 3], d + 2 * ks, ks ? 1 : zero); };
          auto qkh = [&](int b, int ks, uint64_t d) { wg_n64_rs_nb_f16_f16(H[b], q[0][1][4 * ks], q[0][1][4 * ks + 1], q[0][1][4 * ks + 2], q[0][1][4 * ks + 3], d + 2 * ks, ks ? 1 : zero); };
          auto pv0 = [&](uint64_t d) { wgmma_m64n40k16_rs_tb(o[0], P0[0], P0[1], P0[2], P0[3], d, 1); };
          auto pv1 = [&](uint64_t d) { wgmma_m64n40k16_rs_tb(o[1], P1[0], P1[1], P1[2], P1[3], d, 1); };
          float e[4] = {};
          auto finish = [&](int h) {
            const float* s = &S[(h >> 2) & 1][8 * (h & 3)];
            const uint32_t* u = &H[(h >> 2) & 1][4 * (h & 3)];
            const float z0 = exp2_fix(s[6]), z1 = exp2_fix(s[7]);
            P0[0] = pack2v(e[0], e[1]);
            P1[0] = exp2_h2(u[0], c_852);
            P0[1] = pack2v(e[2], e[3]);
            P1[1] = exp2_h2(u[1], c_852);
            const uint32_t B = exp2_base(z0, z1), E = and_or<0x7F807F80u>(B, c_lsb);
            P1[3] = exp2_h2(u[3], c_852);
            P0[3] = fma_bf2(B, and_or<0x807F807Fu>(B, c_half), E);
            const float e4 = ex2v(s[4]), e5 = ex2v(s[5]);
            P1[2] = exp2_h2(u[2], c_852);
            P0[2] = pack2v(e4, e5);
          };
          auto start = [&](int h) {
            const float* s = &S[(h >> 2) & 1][8 * (h & 3)];
            e[2] = ex2v(s[2]); e[1] = ex2v(s[1]); e[0] = ex2v(s[0]); e[3] = ex2v(s[3]);
          };
          uint64_t kd = prm.kv[0].kd;
          mbar_wait(sb + B_TF, 0);
          lds128(sb + ROWST + 16 + (lane_id() & zero), cq);
#pragma unroll
          for (int i = 0; i < 4; i++) sts128(sb + QPARK + (wg * 128 + w * 32 + lane_id()) * 16 + i * 4096, q[0][i >> 1][4 * (i & 1)], q[0][i >> 1][4 * (i & 1) + 1], q[0][i >> 1][4 * (i & 1) + 2], q[0][i >> 1][4 * (i & 1) + 3]);
          wg_fence();
#pragma unroll
          for (int b = 0; b < 2; b++) {
            wg_n64_rs_nb_f16_f32_z(S[b], q[0][0][0], q[0][0][1], q[0][0][2], q[0][0][3], kd + 256 * b, 0);
            wg_n64_rs_nb_f16_f16_z(H[b], q[0][1][0], q[0][1][1], q[0][1][2], q[0][1][3], kd + 256 * b, 0);
            if (b == 0) { qkf(0, 1, kd); qkh(0, 1, kd); }
            wg_commit();
          }
          wg_wait<1>(); fence_regs(S[0]); fence_regs(H[0]);
          start(0); finish(0); start(1);
          wg_wait<0>();
          int redo = 0;
#pragma unroll 1
          for (int pass = 0, j = 1; pass < 2; pass++) {
#pragma unroll 1
           do {
            const uint64_t vd = prm.kv[j & 3].vd;
            bool go = false;
#pragma unroll
            for (int h = 2; h < 18; h++) {
              const int px = (h >> 2) + 1, c = h & 3;
              wg_fence();
              if (h == 13) kd = prm.kv[j & 3].kd;
              const uint64_t kx = kd + (px & 3) * 256, vx = vd + (h - 2) * VSTEP;
              if (h == 2) { qkh(1, 0, kx); qkf(1, 0, kx); pv0(vx); pv1(vx); qkh(1, 1, kx); qkf(1, 1, kx); }
              else if ((c == 1 || c == 2) && h < 17) { qkh(px & 1, c - 1, kx); pv1(vx); qkf(px & 1, c - 1, kx); pv0(vx); }
              else { pv0(vx); pv1(vx); }
              wg_commit();
              if (h == 3) e_arrive_if(sb + B_TE + 8 * ((j + 2) & 3), j > 1);
              if (h == 11) go = mbar_test(sb + B_TF + 8 * (j & 3), (j >> 2) & 1) && j != 8;
              finish(h - 1); start(h);
              if (h != 12 && h != 17) sched_fence();
              if (h == 12 && !go) {
                if (j == 16) {
#pragma unroll
                  for (int u = 13; u < 18; u++) {
                    wg_fence(); pv0(vd + (u - 2) * VSTEP); pv1(vd + (u - 2) * VSTEP); wg_commit();
                    if (u < 17) finish(u - 1);
                    if (u < 16) { start(u); sched_fence(); }
                    if (u & 1) { if (u == 17) wg_wait<0>(); else wg_wait<1>(); }
                  }
                  e_arrive(sb + B_TE + 24);
                  goto head_done;
                }
                mbar_wait(sb + B_TF + 8 * (j & 3), (j >> 2) & 1);
                if (j == 8) {
#pragma unroll
                  for (int i = 0; i < 4; i++) lds128(sb + QPARK + 24576 - wg * 8192 + (w * 32 + lane_id()) * 16 + i * 2048, &q[0][i >> 1][4 * (i & 1)]);
                }
              }
              if (h == 17) wg_wait<0>(); else if (h & 1) wg_wait<1>();
              if (c == 3) { fence_regs(S[px & 1]); fence_regs(H[px & 1]); }
            }
           } while (j++ & 7);
           head_done:
            fence_regs(o[0]); fence_regs(o[1]);
            uint32_t pk[2][8];
            {
              IDS();
              bf16* op = g_os + (size_t)(bm * 256 + row0 + (lane >> 2)) * 1024 + pass * 512 + bn * 32 + (lane & 3) * 8;
#pragma unroll
              for (int i = 0; i < 4; i++) {
                const float* a = &o[i >> 1][2 * (i & 1)];
                const float inv = rcp(a[16]);
                uint32_t* u = &pk[i >> 1][4 * (i & 1)];
#pragma unroll
                for (int k = 0; k < 4; k++) u[k] = pack2(a[4 * k] * inv, a[4 * k + 1] * inv);
                *(uint4*)(op + ((i >> 1) * 64 + (i & 1) * 8) * 1024) = make_uint4(u[0], u[1], u[2], u[3]);
              }
            }
            sched_fence();
            if (pass == 0) bar_sync(NB_KN + wg, 160);
            const float kmax = *(volatile float*)(smem + ROWST + 4 * pass);
            const bool wide = !(qn[0] <= 1.6e7f) | !(kmax <= 1.6e7f) | !(qn[0] * kmax <= 112.f * 112.f);
            int badm = 0;
#pragma unroll
            for (int m = 0; m < 2; m++) {
              uint32_t chk[2] = {0u, 0u};
#pragma unroll
              for (int i = 0; i < 8; i++) asm("fma.rn.bf16x2 %0, %1, %2, %0;" : "+r"(chk[i & 1]) : "r"(pk[m][i]), "r"(0u));
              const bool bad = wide | !(fminf(o[m][16], o[m][18]) >= 9.3e-10f) | !(o[m][16] + o[m][18] <= 1e36f) | (((chk[0] | chk[1]) & 0x7FFF7FFFu) != 0);
              badm |= __any_sync(~0u, bad) << m;
            }
            if (!badm) bar_arrive(NB_SIG + 2 * pass + wg, 160 + 32 * (pass & wg));
            qn[0] = qn[1];
#pragma unroll
            for (int m = 0; m < 2; m++) {
#pragma unroll
              for (int i = 0; i < 20; i++) o[m][i] = 0.f;
              fence_regs(o[m]);
            }
            if (badm) {
              redo |= badm << 2 * pass;
              const int tx = wg * 128 + w * 32 + lane_id();
              uint4* p = g_qsave + (block_id() * 256 + tx) * 8 + pass * 4;
#pragma unroll
              for (int i = 0; i < 4; i++) {
                uint32_t u[4] = {q[0][i >> 1][4 * (i & 1)], q[0][i >> 1][4 * (i & 1) + 1], q[0][i >> 1][4 * (i & 1) + 2], q[0][i >> 1][4 * (i & 1) + 3]};
                if (pass == 0) lds128(sb + QPARK + tx * 16 + i * 4096, u);
                p[i] = make_uint4(u[0], u[1], u[2], u[3]);
              }
            }
          }
          if (redo) attn_redo(redo, l, cta_id(), wg, w, ep1);
        }
      }
      {
        float acc[64];
        {
          const uint64_t da = prm.xd + ((pslot_a(0, l) + wg * 8192) >> 4), db = prm.wd + (pslot_b(0) >> 4) - 2048;
          mbar_wait(sb + B_PF, l & 1);
          wg_fence();
          wgmma_m64n128k16_ss_tb_z(acc, da, db, 0);
#pragma unroll
          for (int k = 1; k < 4; k++) wgmma_m64n128k16_ss_tb(acc, da + k * 2, db + k * 128, 1);
          wg_commit();
        }
        uint32_t s = 1, lap = 0;
#pragma unroll 1
        for (int kt = 1; kt < 14; kt++) {
          mbar_wait(sb + B_PF + 8 * s, ((s < 4 ? l : 0) + lap) & 1);
          const uint64_t da = mkdesc(sb + pslot_a(s, l) + wg * 8192, 16, 1024, 1), db = mkdesc(sb + pslot_b(s), 8192, 1024, 1);
          wg_fence();
#pragma unroll
          for (int k = 0; k < 4; k++) wgmma_m64n128k16_ss_tb(acc, da + k * 2, db + k * 128, 1);
          wg_commit();
          wg_wait<1>();
          if (w == 0) e_arrive_both(sb + B_PE + 8 * (s ? s - 1 : 5));
          if (++s == 6) { s = 0; lap++; }
        }
        if (wg) {
          wg_wait<0>();
          if (w == 0) e_arrive_both(sb + B_PE + 8);
#pragma unroll
          for (int t = 2; t < 4; t++) mbar_wait(sb + B_PF + 8 * t, l & 1);
          bar_sync(NB_ST, 256);
        }
#pragma unroll
        for (int t = 2; t < 4; t++) {
          if (!wg) mbar_wait(sb + B_PF + 8 * t, l & 1);
          const uint64_t da = prm.xd + ((pslot_a(t, l) + wg * 8192) >> 4), db = prm.wd + (pslot_b(t) >> 4) - 2048;
          wg_fence();
#pragma unroll
          for (int k = 0; k < 4; k++) wgmma_m64n128k16_ss_tb(acc, da + k * 2, db + k * 128, 1);
          wg_commit();
        }
        if (!wg) {
          bar_arrive(NB_ST, 256);
          wg_wait<2>();
          if (w == 0) e_arrive_both(sb + B_PE + 8);
        }
        IDS();
        const int g = lane >> 2, qd = lane & 3;
        const int r0 = wg * 64 + w * 16;
        const uint32_t r = r0 + (lane & 7) + ((lane >> 3) & 1) * 8;
        uint32_t x[8][4];
        mbar_wait(sb + B_RF, l & 1);
#pragma unroll
        for (int jj = 0; jj < 8; jj++) ldsm4(sb + RES + (jj >> 2) * 16384 + r * 128 + ((((2 * jj + (lane >> 4)) & 7) ^ (r & 7)) << 4), x[jj]);
        wg_wait<0>();
        fence_regs(acc);
        if (w == 0) { e_arrive_both(sb + B_PE + 16); e_arrive_both(sb + B_PE + 24); }
        const CUtensorMap* mo = &prm.m[l == 3 ? M_OUT : M_XST];
#pragma unroll
        for (int jj = 0; jj < 8; jj++) {
#pragma unroll
          for (int i = 0; i < 4; i++) x[jj][i] = add_bf16x2(x[jj][i], pack2(acc[8 * jj + 2 * i], acc[8 * jj + 2 * i + 1]));
          if (jj < 4) stsm4(sb + RES + r * 128 + ((((2 * jj + (lane >> 4)) & 7) ^ (r & 7)) << 4), x[jj][0], x[jj][1], x[jj][2], x[jj][3]);
          if (jj == 3) { fence_async_smem(); __syncwarp(); tma_st(mo, pn * 128, pm * 128 + r0, sb + RES + r0 * 128); bulk_commit(); sched_fence(); }
        }
        if (l == 3) {
#pragma unroll
          for (int jj = 4; jj < 8; jj++) stsm4(sb + RES + 16384 + r * 128 + ((((2 * jj + (lane >> 4)) & 7) ^ (r & 7)) << 4), x[jj][0], x[jj][1], x[jj][2], x[jj][3]);
          fence_async_smem(); __syncwarp();
          tma_st(mo, pn * 128 + 64, pm * 128 + r0, sb + RES + 16384 + r0 * 128);
          bulk_commit(); bulk_wait_n<0>();
        } else {
          bar_sync(NB_SC, 256);
#pragma unroll
          for (int jj = 0; jj < 8; jj++)
            stsm4(sb + (jj >> 2) * 2 * QSTG + po * 16384 + r * 128 + ((((2 * jj + (lane >> 4)) & 7) ^ (r & 7)) << 4), x[jj][0], x[jj][1], x[jj][2], x[jj][3]);
          bulk_wait_n<0>();
          bar_arrive(NB_X0, 320);
          float s1[4] = {0.f, 0.f, 0.f, 0.f}, sa[4] = {0.f, 0.f, 0.f, 0.f}, sc[4] = {0.f, 0.f, 0.f, 0.f};
#pragma unroll
          for (int jj = 0; jj < 8; jj++) {
            mma16816(s1, x[jj][0], x[jj][1], x[jj][2], x[jj][3], 0x3f803f80u, 0x3f803f80u);
            mma16816(sa, x[jj][0], x[jj][1], x[jj][2], x[jj][3], x[jj][0], x[jj][2]);
            mma16816(sc, x[jj][0], x[jj][1], x[jj][2], x[jj][3], x[jj][1], x[jj][3]);
          }
          fence_regs(s1); fence_regs(sa); fence_regs(sc);
          fence_async_smem();
          sched_fence();
          bar_arrive(NB_X, 320);
          if (qd == g >> 1) {
            float2* p = g_stats + pn * 2048 + pm * 128 + r0 + g;
            p[0] = make_float2(s1[0], g & 1 ? sa[1] : sa[0]);
            p[8] = make_float2(s1[2], g & 1 ? sc[3] : sc[2]);
          }
          bar_arrive(NB_KV, 288);
        }
      }
    }
  }
  asm volatile("barrier.cluster.arrive.relaxed.aligned;\nbarrier.cluster.wait.aligned;" ::: "memory");
}

typedef CUresult (*EncodeFn)(CUtensorMap*, CUtensorMapDataType, cuuint32_t, void*, const cuuint64_t*, const cuuint64_t*, const cuuint32_t*,
                             const cuuint32_t*, CUtensorMapInterleave, CUtensorMapSwizzle, CUtensorMapL2promotion, CUtensorMapFloatOOBfill);

static void make_map(EncodeFn fn, CUtensorMap* m, const void* ptr, int rank, const uint64_t* dims, const uint64_t* strides, const uint32_t* box, CUtensorMapSwizzle sw) {
  cuuint64_t d[5], st[4];
  cuuint32_t bx[5], es[5];
  for (int i = 0; i < rank; i++) { d[i] = dims[i]; bx[i] = box[i]; es[i] = 1; if (i) st[i - 1] = strides[i - 1] * 2; }
  fn(m, CU_TENSOR_MAP_DATA_TYPE_BFLOAT16, rank, (void*)ptr, d, st, bx, es, CU_TENSOR_MAP_INTERLEAVE_NONE, sw,
     CU_TENSOR_MAP_L2_PROMOTION_L2_128B, CU_TENSOR_MAP_FLOAT_OOB_FILL_NONE);
}
static void map2(EncodeFn fn, CUtensorMap* m, const void* ptr, uint64_t inner, uint64_t outer, uint32_t bi, uint32_t bo, CUtensorMapSwizzle sw) {
  const uint64_t d[2] = {inner, outer}, st[1] = {inner};
  const uint32_t bx[2] = {bi, bo};
  make_map(fn, m, ptr, 2, d, st, bx, sw);
}

extern "C" void kernel_launch(void* const* d_in, const int* in_sizes, int n_in, void* d_out, int out_size) {
  (void)in_sizes; (void)n_in; (void)out_size;
  static EncodeFn enc = nullptr;
  static void *xs, *os, *kk, *vv;
  static int sbase = 1024;
  if (!enc) {
    void* p = nullptr;
    cudaDriverEntryPointQueryResult qr;
    cudaGetDriverEntryPoint("cuTensorMapEncodeTiled", &p, cudaEnableDefault, &qr);
    enc = (EncodeFn)p;
    Scratch* sc = nullptr;
    cudaGetSymbolAddress((void**)&sc, g_s);
    xs = sc->xs; os = sc->os; kk = sc->k; vv = sc->v;
    int dev = 0;
    cudaGetDevice(&dev);
    cudaDeviceGetAttribute(&sbase, cudaDevAttrReservedSharedMemoryPerBlock, dev);
    cudaFuncSetAttribute(fused_kernel, cudaFuncAttributeMaxDynamicSharedMemorySize, SMEM_BYTES);
  }
  Params prm;
  const CUtensorMapSwizzle S128 = CU_TENSOR_MAP_SWIZZLE_128B, S64 = CU_TENSOR_MAP_SWIZZLE_64B;
  map2(enc, &prm.m[M_X0A], d_in[0], 1024, 2048, 64, 256, S128);
  map2(enc, &prm.m[M_XSA], xs, 1024, 2048, 64, 256, S128);
  for (int t = 0; t < 2; t++) {
    const uint64_t d3[3] = {1024, 1024, 3}, s3[2] = {3072, 1024};
    const uint32_t b3[3] = {64, 64, 3};
    make_map(enc, &prm.m[M_WQA + t], d_in[1 + 3 * t], 3, d3, s3, b3, S128);
    const uint64_t d5[5] = {64, 32, 2, 16, 16}, s5[4] = {1024, 32 * 1024, 64 * 1024, 64};
    const uint32_t b5[5] = {64, 32, 1, 2, 2};
    make_map(enc, &prm.m[M_WOA + t], d_in[2 + 3 * t], 5, d5, s5, b5, S128);
    const uint64_t dr[3] = {64, 2048, 16}, sr[2] = {1024, 64};
    const uint32_t br[3] = {64, 128, 2};
    make_map(enc, &prm.m[M_X0R + t], t ? xs : d_in[0], 3, dr, sr, br, S128);
  }
  map2(enc, &prm.m[M_OS], os, 1024, 2048, 64, 64, S128);
  map2(enc, &prm.m[M_K], kk, 32, 65536, 32, 128, S64);
  map2(enc, &prm.m[M_V], vv, 32, 65536, 32, 128, S64);
  map2(enc, &prm.m[M_XSO], xs, 1024, 2048, 64, 128, S128);
  map2(enc, &prm.m[M_X0H], d_in[0], 1024, 2048, 64, 128, S128);
  map2(enc, &prm.m[M_XST], xs, 1024, 2048, 64, 16, S128);
  map2(enc, &prm.m[M_OUT], d_out, 1024, 2048, 64, 16, S128);
  prm.x0 = (const bf16*)d_in[0];
  prm.wq[0] = (const bf16*)d_in[1]; prm.wq[1] = (const bf16*)d_in[4];
  prm.zero = 0;
  for (int i = 0; i < 128; i++) prm.map[i] = remap(i);
  {
    const uint64_t hi = 0x80000020ull << 32, k0 = sbase + T0, v0 = k0 + 16384, vstep = 64 - (64ull << 16);
    prm.wd = mkdesc(sbase + 32768, 8192, 1024, 1); prm.xd = mkdesc(sbase, 16, 1024, 1);
    for (int j = 0; j < 4; j++) {
      prm.kv[j].kd = (hi | 1u << 16 | k0 >> 4) + 2048 * ((j < 16 ? j : 15) & 3);
      prm.kv[j].vd = (hi | (uint64_t)(ONES - T0 - 16384) >> 4 << 16 | v0 >> 4) + 32 * vstep * ((j + 3) & 3);
    }
  }
  fused_kernel<<<128, 384, SMEM_BYTES>>>(prm);
}
```

```cpp
#include <cuda_runtime.h>
#include <cuda_bf16.h>
#include <cuda.h>
#include <stdint.h>

typedef __nv_bfloat16 bf16;

__device__ __forceinline__ void wgmma_m64n192k16_ss_tb(float (&d)[96], uint64_t da, uint64_t db, int scale_d) {
  asm volatile("{\n.reg .pred p;\nsetp.ne.b32 p, %98, 0;\n"
    "wgmma.mma_async.sync.aligned.m64n192k16.f32.bf16.bf16 "
    "{%0, %1, %2, %3, %4, %5, %6, %7, %8, %9, %10, %11, %12, %13, %14, %15, "
    "%16, %17, %18, %19, %20, %21, %22, %23, %24, %25, %26, %27, %28, %29, %30, %31, "
    "%32, %33, %34, %35, %36, %37, %38, %39, %40, %41, %42, %43, %44, %45, %46, %47, "
    "%48, %49, %50, %51, %52, %53, %54, %55, %56, %57, %58, %59, %60, %61, %62, %63, "
    "%64, %65, %66, %67, %68, %69, %70, %71, %72, %73, %74, %75, %76, %77, %78, %79, "
    "%80, %81, %82, %83, %84, %85, %86, %87, %88, %89, %90, %91, %92, %93, %94, %95}, "
    "%96, %97, p, 1, 1, 0, 1;\n}\n"
    : "+f"(d[0]), "+f"(d[1]), "+f"(d[2]), "+f"(d[3]), "+f"(d[4]), "+f"(d[5]), "+f"(d[6]), "+f"(d[7]),
      "+f"(d[8]), "+f"(d[9]), "+f"(d[10]), "+f"(d[11]), "+f"(d[12]), "+f"(d[13]), "+f"(d[14]), "+f"(d[15]),
      "+f"(d[16]), "+f"(d[17]), "+f"(d[18]), "+f"(d[19]), "+f"(d[20]), "+f"(d[21]), "+f"(d[22]), "+f"(d[23]),
      "+f"(d[24]), "+f"(d[25]), "+f"(d[26]), "+f"(d[27]), "+f"(d[28]), "+f"(d[29]), "+f"(d[30]), "+f"(d[31]),
      "+f"(d[32]), "+f"(d[33]), "+f"(d[34]), "+f"(d[35]), "+f"(d[36]), "+f"(d[37]), "+f"(d[38]), "+f"(d[39]),
      "+f"(d[40]), "+f"(d[41]), "+f"(d[42]), "+f"(d[43]), "+f"(d[44]), "+f"(d[45]), "+f"(d[46]), "+f"(d[47]),
      "+f"(d[48]), "+f"(d[49]), "+f"(d[50]), "+f"(d[51]), "+f"(d[52]), "+f"(d[53]), "+f"(d[54]), "+f"(d[55]),
      "+f"(d[56]), "+f"(d[57]), "+f"(d[58]), "+f"(d[59]), "+f"(d[60]), "+f"(d[61]), "+f"(d[62]), "+f"(d[63]),
      "+f"(d[64]), "+f"(d[65]), "+f"(d[66]), "+f"(d[67]), "+f"(d[68]), "+f"(d[69]), "+f"(d[70]), "+f"(d[71]),
      "+f"(d[72]), "+f"(d[73]), "+f"(d[74]), "+f"(d[75]), "+f"(d[76]), "+f"(d[77]), "+f"(d[78]), "+f"(d[79]),
      "+f"(d[80]), "+f"(d[81]), "+f"(d[82]), "+f"(d[83]), "+f"(d[84]), "+f"(d[85]), "+f"(d[86]), "+f"(d[87]),
      "+f"(d[88]), "+f"(d[89]), "+f"(d[90]), "+f"(d[91]), "+f"(d[92]), "+f"(d[93]), "+f"(d[94]), "+f"(d[95])
    : "l"(da), "l"(db), "r"(scale_d));
}

__device__ __forceinline__ void wgmma_m64n192k16_ss_tb_z(float (&d)[96], uint64_t da, uint64_t db, int scale_d) {
  asm volatile("{\n.reg .pred p;\nsetp.ne.b32 p, %98, 0;\n"
    "wgmma.mma_async.sync.aligned.m64n192k16.f32.bf16.bf16 "
    "{%0, %1, %2, %3, %4, %5, %6, %7, %8, %9, %10, %11, %12, %13, %14, %15, "
    "%16, %17, %18, %19, %20, %21, %22, %23, %24, %25, %26, %27, %28, %29, %30, %31, "
    "%32, %33, %34, %35, %36, %37, %38, %39, %40, %41, %42, %43, %44, %45, %46, %47, "
    "%48, %49, %50, %51, %52, %53, %54, %55, %56, %57, %58, %59, %60, %61, %62, %63, "
    "%64, %65, %66, %67, %68, %69, %70, %71, %72, %73, %74, %75, %76, %77, %78, %79, "
    "%80, %81, %82, %83, %84, %85, %86, %87, %88, %89, %90, %91, %92, %93, %94, %95}, "
    "%96, %97, p, 1, 1, 0, 1;\n}\n"
    : "=f"(d[0]), "=f"(d[1]), "=f"(d[2]), "=f"(d[3]), "=f"(d[4]), "=f"(d[5]), "=f"(d[6]), "=f"(d[7]),
      "=f"(d[8]), "=f"(d[9]), "=f"(d[10]), "=f"(d[11]), "=f"(d[12]), "=f"(d[13]), "=f"(d[14]), "=f"(d[15]),
      "=f"(d[16]), "=f"(d[17]), "=f"(d[18]), "=f"(d[19]), "=f"(d[20]), "=f"(d[21]), "=f"(d[22]), "=f"(d[23]),
      "=f"(d[24]), "=f"(d[25]), "=f"(d[26]), "=f"(d[27]), "=f"(d[28]), "=f"(d[29]), "=f"(d[30]), "=f"(d[31]),
      "=f"(d[32]), "=f"(d[33]), "=f"(d[34]), "=f"(d[35]), "=f"(d[36]), "=f"(d[37]), "=f"(d[38]), "=f"(d[39]),
      "=f"(d[40]), "=f"(d[41]), "=f"(d[42]), "=f"(d[43]), "=f"(d[44]), "=f"(d[45]), "=f"(d[46]), "=f"(d[47]),
      "=f"(d[48]), "=f"(d[49]), "=f"(d[50]), "=f"(d[51]), "=f"(d[52]), "=f"(d[53]), "=f"(d[54]), "=f"(d[55]),
      "=f"(d[56]), "=f"(d[57]), "=f"(d[58]), "=f"(d[59]), "=f"(d[60]), "=f"(d[61]), "=f"(d[62]), "=f"(d[63]),
      "=f"(d[64]), "=f"(d[65]), "=f"(d[66]), "=f"(d[67]), "=f"(d[68]), "=f"(d[69]), "=f"(d[70]), "=f"(d[71]),
      "=f"(d[72]), "=f"(d[73]), "=f"(d[74]), "=f"(d[75]), "=f"(d[76]), "=f"(d[77]), "=f"(d[78]), "=f"(d[79]),
      "=f"(d[80]), "=f"(d[81]), "=f"(d[82]), "=f"(d[83]), "=f"(d[84]), "=f"(d[85]), "=f"(d[86]), "=f"(d[87]),
      "=f"(d[88]), "=f"(d[89]), "=f"(d[90]), "=f"(d[91]), "=f"(d[92]), "=f"(d[93]), "=f"(d[94]), "=f"(d[95])
    : "l"(da), "l"(db), "r"(scale_d));
}

__device__ __forceinline__ void wgmma_m64n128k16_ss_tb(float (&d)[64], uint64_t da, uint64_t db, int scale_d) {
  asm volatile("{\n.reg .pred p;\nsetp.ne.b32 p, %66, 0;\n"
    "wgmma.mma_async.sync.aligned.m64n128k16.f32.bf16.bf16 "
    "{%0, %1, %2, %3, %4, %5, %6, %7, %8, %9, %10, %11, %12, %13, %14, %15, "
    "%16, %17, %18, %19, %20, %21, %22, %23, %24, %25, %26, %27, %28, %29, %30, %31, "
    "%32, %33, %34, %35, %36, %37, %38, %39, %40, %41, %42, %43, %44, %45, %46, %47, "
    "%48, %49, %50, %51, %52, %53, %54, %55, %56, %57, %58, %59, %60, %61, %62, %63}, "
    "%64, %65, p, 1, 1, 0, 1;\n}\n"
    : "+f"(d[0]), "+f"(d[1]), "+f"(d[2]), "+f"(d[3]), "+f"(d[4]), "+f"(d[5]), "+f"(d[6]), "+f"(d[7]),
      "+f"(d[8]), "+f"(d[9]), "+f"(d[10]), "+f"(d[11]), "+f"(d[12]), "+f"(d[13]), "+f"(d[14]), "+f"(d[15]),
      "+f"(d[16]), "+f"(d[17]), "+f"(d[18]), "+f"(d[19]), "+f"(d[20]), "+f"(d[21]), "+f"(d[22]), "+f"(d[23]),
      "+f"(d[24]), "+f"(d[25]), "+f"(d[26]), "+f"(d[27]), "+f"(d[28]), "+f"(d[29]), "+f"(d[30]), "+f"(d[31]),
      "+f"(d[32]), "+f"(d[33]), "+f"(d[34]), "+f"(d[35]), "+f"(d[36]), "+f"(d[37]), "+f"(d[38]), "+f"(d[39]),
      "+f"(d[40]), "+f"(d[41]), "+f"(d[42]), "+f"(d[43]), "+f"(d[44]), "+f"(d[45]), "+f"(d[46]), "+f"(d[47]),
      "+f"(d[48]), "+f"(d[49]), "+f"(d[50]), "+f"(d[51]), "+f"(d[52]), "+f"(d[53]), "+f"(d[54]), "+f"(d[55]),
      "+f"(d[56]), "+f"(d[57]), "+f"(d[58]), "+f"(d[59]), "+f"(d[60]), "+f"(d[61]), "+f"(d[62]), "+f"(d[63])
    : "l"(da), "l"(db), "r"(scale_d));
}

__device__ __forceinline__ void wgmma_m64n128k16_ss_tb_z(float (&d)[64], uint64_t da, uint64_t db, int scale_d) {
  asm volatile("{\n.reg .pred p;\nsetp.ne.b32 p, %66, 0;\n"
    "wgmma.mma_async.sync.aligned.m64n128k16.f32.bf16.bf16 "
    "{%0, %1, %2, %3, %4, %5, %6, %7, %8, %9, %10, %11, %12, %13, %14, %15, "
    "%16, %17, %18, %19, %20, %21, %22, %23, %24, %25, %26, %27, %28, %29, %30, %31, "
    "%32, %33, %34, %35, %36, %37, %38, %39, %40, %41, %42, %43, %44, %45, %46, %47, "
    "%48, %49, %50, %51, %52, %53, %54, %55, %56, %57, %58, %59, %60, %61, %62, %63}, "
    "%64, %65, p, 1, 1, 0, 1;\n}\n"
    : "=f"(d[0]), "=f"(d[1]), "=f"(d[2]), "=f"(d[3]), "=f"(d[4]), "=f"(d[5]), "=f"(d[6]), "=f"(d[7]),
      "=f"(d[8]), "=f"(d[9]), "=f"(d[10]), "=f"(d[11]), "=f"(d[12]), "=f"(d[13]), "=f"(d[14]), "=f"(d[15]),
      "=f"(d[16]), "=f"(d[17]), "=f"(d[18]), "=f"(d[19]), "=f"(d[20]), "=f"(d[21]), "=f"(d[22]), "=f"(d[23]),
      "=f"(d[24]), "=f"(d[25]), "=f"(d[26]), "=f"(d[27]), "=f"(d[28]), "=f"(d[29]), "=f"(d[30]), "=f"(d[31]),
      "=f"(d[32]), "=f"(d[33]), "=f"(d[34]), "=f"(d[35]), "=f"(d[36]), "=f"(d[37]), "=f"(d[38]), "=f"(d[39]),
      "=f"(d[40]), "=f"(d[41]), "=f"(d[42]), "=f"(d[43]), "=f"(d[44]), "=f"(d[45]), "=f"(d[46]), "=f"(d[47]),
      "=f"(d[48]), "=f"(d[49]), "=f"(d[50]), "=f"(d[51]), "=f"(d[52]), "=f"(d[53]), "=f"(d[54]), "=f"(d[55]),
      "=f"(d[56]), "=f"(d[57]), "=f"(d[58]), "=f"(d[59]), "=f"(d[60]), "=f"(d[61]), "=f"(d[62]), "=f"(d[63])
    : "l"(da), "l"(db), "r"(scale_d));
}

__device__ __forceinline__ void wgmma_m64n40k16_rs_tb(float (&d)[20], uint32_t a0, uint32_t a1, uint32_t a2, uint32_t a3, uint64_t db, int scale_d) {
  asm volatile("{\n.reg .pred p;\nsetp.ne.b32 p, %25, 0;\n"
    "wgmma.mma_async.sync.aligned.m64n40k16.f32.bf16.bf16 "
    "{%0, %1, %2, %3, %4, %5, %6, %7, %8, %9, %10, %11, %12, %13, %14, %15, "
    "%16, %17, %18, %19}, "
    "{%20, %21, %22, %23}, %24, p, 1, 1, 1;\n}\n"
    : "+f"(d[0]), "+f"(d[1]), "+f"(d[2]), "+f"(d[3]), "+f"(d[4]), "+f"(d[5]), "+f"(d[6]), "+f"(d[7]),
      "+f"(d[8]), "+f"(d[9]), "+f"(d[10]), "+f"(d[11]), "+f"(d[12]), "+f"(d[13]), "+f"(d[14]), "+f"(d[15]),
      "+f"(d[16]), "+f"(d[17]), "+f"(d[18]), "+f"(d[19])
    : "r"(a0), "r"(a1), "r"(a2), "r"(a3), "l"(db), "r"(scale_d));
}

__device__ __forceinline__ void wg_n64_rs_nb_f16_f32(float (&d)[32], uint32_t a0, uint32_t a1, uint32_t a2, uint32_t a3, uint64_t db, int scale_d) {
  asm volatile("{\n.reg .pred p;\nsetp.ne.b32 p, %37, 0;\n"
    "wgmma.mma_async.sync.aligned.m64n64k16.f32.f16.f16 "
    "{%0, %1, %2, %3, %4, %5, %6, %7, %8, %9, %10, %11, %12, %13, %14, %15, "
    "%16, %17, %18, %19, %20, %21, %22, %23, %24, %25, %26, %27, %28, %29, %30, %31}, "
    "{%32, %33, %34, %35}, %36, p, 1, 1, 0;\n}\n"
    : "+f"(d[0]), "+f"(d[1]), "+f"(d[2]), "+f"(d[3]), "+f"(d[4]), "+f"(d[5]), "+f"(d[6]), "+f"(d[7]),
      "+f"(d[8]), "+f"(d[9]), "+f"(d[10]), "+f"(d[11]), "+f"(d[12]), "+f"(d[13]), "+f"(d[14]), "+f"(d[15]),
      "+f"(d[16]), "+f"(d[17]), "+f"(d[18]), "+f"(d[19]), "+f"(d[20]), "+f"(d[21]), "+f"(d[22]), "+f"(d[23]),
      "+f"(d[24]), "+f"(d[25]), "+f"(d[26]), "+f"(d[27]), "+f"(d[28]), "+f"(d[29]), "+f"(d[30]), "+f"(d[31])
    : "r"(a0), "r"(a1), "r"(a2), "r"(a3), "l"(db), "r"(scale_d));
}

__device__ __forceinline__ void wg_n64_rs_nb_f16_f16(uint32_t (&d)[16], uint32_t a0, uint32_t a1, uint32_t a2, uint32_t a3, uint64_t db, int scale_d) {
  asm volatile("{\n.reg .pred p;\nsetp.ne.b32 p, %21, 0;\n"
    "wgmma.mma_async.sync.aligned.m64n64k16.f16.f16.f16 "
    "{%0, %1, %2, %3, %4, %5, %6, %7, %8, %9, %10, %11, %12, %13, %14, %15}, "
    "{%16, %17, %18, %19}, %20, p, 1, 1, 0;\n}\n"
    : "+r"(d[0]), "+r"(d[1]), "+r"(d[2]), "+r"(d[3]), "+r"(d[4]), "+r"(d[5]), "+r"(d[6]), "+r"(d[7]),
      "+r"(d[8]), "+r"(d[9]), "+r"(d[10]), "+r"(d[11]), "+r"(d[12]), "+r"(d[13]), "+r"(d[14]), "+r"(d[15])
    : "r"(a0), "r"(a1), "r"(a2), "r"(a3), "l"(db), "r"(scale_d));
}

__device__ __forceinline__ void wg_n64_rs_nb_f16_f32_z(float (&d)[32], uint32_t a0, uint32_t a1, uint32_t a2, uint32_t a3, uint64_t db, int scale_d) {
  asm volatile("{\n.reg .pred p;\nsetp.ne.b32 p, %37, 0;\n"
    "wgmma.mma_async.sync.aligned.m64n64k16.f32.f16.f16 "
    "{%0, %1, %2, %3, %4, %5, %6, %7, %8, %9, %10, %11, %12, %13, %14, %15, "
    "%16, %17, %18, %19, %20, %21, %22, %23, %24, %25, %26, %27, %28, %29, %30, %31}, "
    "{%32, %33, %34, %35}, %36, p, 1, 1, 0;\n}\n"
    : "=f"(d[0]), "=f"(d[1]), "=f"(d[2]), "=f"(d[3]), "=f"(d[4]), "=f"(d[5]), "=f"(d[6]), "=f"(d[7]),
      "=f"(d[8]), "=f"(d[9]), "=f"(d[10]), "=f"(d[11]), "=f"(d[12]), "=f"(d[13]), "=f"(d[14]), "=f"(d[15]),
      "=f"(d[16]), "=f"(d[17]), "=f"(d[18]), "=f"(d[19]), "=f"(d[20]), "=f"(d[21]), "=f"(d[22]), "=f"(d[23]),
      "=f"(d[24]), "=f"(d[25]), "=f"(d[26]), "=f"(d[27]), "=f"(d[28]), "=f"(d[29]), "=f"(d[30]), "=f"(d[31])
    : "r"(a0), "r"(a1), "r"(a2), "r"(a3), "l"(db), "r"(scale_d));
}

__device__ __forceinline__ void wg_n64_rs_nb_f16_f16_z(uint32_t (&d)[16], uint32_t a0, uint32_t a1, uint32_t a2, uint32_t a3, uint64_t db, int scale_d) {
  asm volatile("{\n.reg .pred p;\nsetp.ne.b32 p, %21, 0;\n"
    "wgmma.mma_async.sync.aligned.m64n64k16.f16.f16.f16 "
    "{%0, %1, %2, %3, %4, %5, %6, %7, %8, %9, %10, %11, %12, %13, %14, %15}, "
    "{%16, %17, %18, %19}, %20, p, 1, 1, 0;\n}\n"
    : "=r"(d[0]), "=r"(d[1]), "=r"(d[2]), "=r"(d[3]), "=r"(d[4]), "=r"(d[5]), "=r"(d[6]), "=r"(d[7]),
      "=r"(d[8]), "=r"(d[9]), "=r"(d[10]), "=r"(d[11]), "=r"(d[12]), "=r"(d[13]), "=r"(d[14]), "=r"(d[15])
    : "r"(a0), "r"(a1), "r"(a2), "r"(a3), "l"(db), "r"(scale_d));
}

#define DEVINL __device__ __forceinline__
DEVINL void wg_fence() { asm volatile("wgmma.fence.sync.aligned;" ::: "memory"); }
DEVINL void wg_commit() { asm volatile("wgmma.commit_group.sync.aligned;" ::: "memory"); }
template <int N> DEVINL void wg_wait() { asm volatile("wgmma.wait_group.sync.aligned %0;" ::"n"(N) : "memory"); }
__host__ DEVINL uint64_t mkdesc(uint32_t addr, uint32_t lbo, uint32_t sbo, int sw) {
  return (uint64_t)((addr & 0x3FFFF) >> 4) | ((uint64_t)(lbo >> 4) << 16) | ((uint64_t)(sbo >> 4) << 32) | ((uint64_t)sw << 62);
}
DEVINL bool mbar_try(uint32_t bar, uint32_t parity) {
  uint32_t ok;
  asm volatile("{\n.reg .pred p;\nmbarrier.try_wait.parity.shared::cta.b64 p, [%1], %2;\nselp.u32 %0, 1, 0, p;\n}" : "=r"(ok) : "r"(bar), "r"(parity) : "memory");
  return ok;
}
DEVINL bool mbar_test(uint32_t bar, uint32_t parity) {
  uint32_t ok;
  asm volatile("{\n.reg .pred p;\nmbarrier.test_wait.parity.shared::cta.b64 p, [%1], %2;\nselp.u32 %0, 1, 0, p;\n}" : "=r"(ok) : "r"(bar), "r"(parity) : "memory");
  return ok;
}
DEVINL void mbar_wait(uint32_t bar, uint32_t parity) {
#pragma unroll 1
  for (uint32_t n = 0; n < 100000u; n++) if (mbar_try(bar, parity)) break;
}
#define EL(txt) "{\n.reg .pred pe;\nelect.sync _|pe, 0xffffffff;\n@pe " txt "\n}"
DEVINL void e_expect_tx(uint32_t bar, uint32_t bytes) { asm volatile(EL("mbarrier.arrive.expect_tx.shared::cta.b64 _, [%0], %1;") ::"r"(bar), "r"(bytes) : "memory"); }
DEVINL void e_arrive(uint32_t bar) { asm volatile(EL("mbarrier.arrive.shared::cta.b64 _, [%0];") ::"r"(bar) : "memory"); }
DEVINL void e_arrive_if(uint32_t bar, int c) {
  asm volatile("{\n.reg .pred pe;\nelect.sync _|pe, 0xffffffff;\nsetp.ne.and.b32 pe, %1, 0, pe;\n@pe mbarrier.arrive.shared::cta.b64 _, [%0];\n}" ::"r"(bar), "r"(c) : "memory");
}
DEVINL void e_red(uint32_t* p) { asm volatile(EL("red.release.gpu.global.add.u32 [%0], 1;") ::"l"(p) : "memory"); }
DEVINL void e_red_relaxed(uint32_t* p) { asm volatile(EL("red.relaxed.gpu.global.add.u32 [%0], 1;") ::"l"(p) : "memory"); }
DEVINL void release_add(uint32_t* p, int on) {
  asm volatile("{\n.reg .pred q;\nsetp.ne.b32 q, %1, 0;\nfence.release.gpu;\n@q red.relaxed.gpu.global.add.u32 [%0], 1;\n}" ::"l"(p), "r"(on) : "memory");
}
#define PREPARED(p, on) do { asm volatile("" : "+l"(p), "+r"(on)); asm volatile("griddepcontrol.launch_dependents;" ::: "memory"); } while (0)
DEVINL void tma_ld(uint32_t dst, const CUtensorMap* m, int c0, int c1, uint32_t bar) {
  asm volatile(EL("cp.async.bulk.tensor.2d.shared::cluster.global.mbarrier::complete_tx::bytes [%0], [%1, {%3, %4}], [%2];")
               ::"r"(dst), "l"(m), "r"(bar), "r"(c0), "r"(c1) : "memory");
}
DEVINL void tma_ld3(uint32_t dst, const CUtensorMap* m, int c0, int c1, int c2, uint32_t bar) {
  asm volatile(EL("cp.async.bulk.tensor.3d.shared::cluster.global.mbarrier::complete_tx::bytes [%0], [%1, {%3, %4, %5}], [%2];")
               ::"r"(dst), "l"(m), "r"(bar), "r"(c0), "r"(c1), "r"(c2) : "memory");
}
DEVINL void tma_ld5(uint32_t dst, const CUtensorMap* m, int c2, int c3, int c4, uint32_t bar) {
  asm volatile(EL("cp.async.bulk.tensor.5d.shared::cluster.global.mbarrier::complete_tx::bytes [%0], [%1, {0, 0, %3, %4, %5}], [%2];")
               ::"r"(dst), "l"(m), "r"(bar), "r"(c2), "r"(c3), "r"(c4) : "memory");
}
DEVINL void tma_ld_mc(uint32_t dst, const CUtensorMap* m, int c0, int c1, uint32_t bar, uint16_t mask = 3) {
  asm volatile(EL("cp.async.bulk.tensor.2d.shared::cluster.global.mbarrier::complete_tx::bytes.multicast::cluster [%0], [%1, {%3, %4}], [%2], %5;")
               ::"r"(dst), "l"(m), "r"(bar), "r"(c0), "r"(c1), "h"(mask) : "memory");
}
DEVINL void e_arrive_both(uint32_t bar) {
  asm volatile("{\n.reg .pred pe;\n.reg .b32 r0, r1;\nelect.sync _|pe, 0xffffffff;\nmapa.shared::cluster.u32 r0, %0, 0;\nmapa.shared::cluster.u32 r1, %0, 1;\n"
               "@pe mbarrier.arrive.shared::cluster.b64 _, [r0];\n@pe mbarrier.arrive.shared::cluster.b64 _, [r1];\n}" ::"r"(bar) : "memory");
}
DEVINL void tma_st(const CUtensorMap* m, int c0, int c1, uint32_t src) {
  asm volatile(EL("cp.async.bulk.tensor.2d.global.shared::cta.bulk_group [%0, {%2, %3}], [%1];") ::"l"(m), "r"(src), "r"(c0), "r"(c1) : "memory");
}
DEVINL void bulk_commit() { asm volatile("cp.async.bulk.commit_group;" ::: "memory"); }
template <int N> DEVINL void bulk_wait_n() { asm volatile("cp.async.bulk.wait_group %0;\nbar.warp.sync 0xffffffff;" ::"n"(N) : "memory"); }
DEVINL void l2_prefetch(const void* g, uint32_t bytes) { asm volatile(EL("cp.async.bulk.prefetch.L2.global [%0], %1;") ::"l"(g), "r"(bytes) : "memory"); }
DEVINL void fence_async_smem() { asm volatile("fence.proxy.async.shared::cta;" ::: "memory"); }
DEVINL void fence_async_gl() { asm volatile("fence.proxy.async.global;" ::: "memory"); }
DEVINL void cluster_wait() { asm volatile("barrier.cluster.wait.aligned;" ::: "memory"); }
DEVINL void bar_sync(int id, int n) { asm volatile("bar.sync %0, %1;" ::"r"(id), "r"(n) : "memory"); }
DEVINL void bar_arrive(int id, int n) { asm volatile("bar.arrive %0, %1;" ::"r"(id), "r"(n) : "memory"); }
DEVINL uint32_t ld_acquire(const uint32_t* p) { uint32_t v; asm volatile("ld.acquire.gpu.global.u32 %0, [%1];" : "=r"(v) : "l"(p) : "memory"); return v; }
DEVINL void await_flag(int j, uint32_t& rdy, const uint32_t* p, uint32_t target) {
  if ((rdy >> j) & 1) return;
#pragma unroll 1
  for (uint32_t n = 0; n < 200000u && !((rdy >> j) & 1); n++) rdy = __ballot_sync(~0u, (int)(ld_acquire(p) - target) >= 0);
  asm volatile("fence.proxy.async.global;" ::: "memory");
}
DEVINL void poll_ge(const uint32_t* p, uint32_t target) {
#pragma unroll 1
  for (uint32_t n = 0; n < 200000u; n++) if (__all_sync(~0u, (int)(ld_acquire(p) - target) >= 0)) break;
}
DEVINL int lane_id() { int v; asm volatile("mov.u32 %0, %%laneid;" : "=r"(v)); return v; }
__host__ DEVINL int remap(int v) {
  const int c = v >> 1, u = c - 36, r = (u * 37) >> 8;
  const int L = c < 4 ? 32 + 8 * c : c < 36 ? c - 4 : 33 + u + r;
  return 2 * L + (v & 1);
}
DEVINL int block_id() { int v; asm volatile("mov.u32 %0, %%ctaid.x;" : "=r"(v)); return v; }
#define cta_id() prm.map[block_id()]
#define IDS() const int lane = lane_id(), b = cta_id(), bm = b >> 4, bn = b & 15, rank = b & 1, pm = 2 * bm + (bn >> 3), pn = bn & 7, po = pm & 1; \
  (void)lane; (void)bm; (void)bn; (void)rank; (void)pm; (void)pn; (void)po
DEVINL void st_tagged(uint4* p, uint32_t a, uint32_t b, uint32_t c, uint32_t tag) {
  asm volatile("{\n.reg .b64 u, v;\n.reg .b128 t;\nmov.b64 u, {%1, %2};\nmov.b64 v, {%3, %4};\nmov.b128 t, {u, v};\nst.relaxed.gpu.global.b128 [%0], t;\n}"
               ::"l"(p), "r"(a), "r"(b), "r"(c), "r"(tag) : "memory");
}
DEVINL uint32_t ld_tagged(const uint4* p, uint32_t* r) {
  uint32_t tag;
  asm volatile("{\n.reg .b64 u, v;\n.reg .b128 t;\nld.relaxed.gpu.global.b128 t, [%4];\nmov.b128 {u, v}, t;\nmov.b64 {%0, %1}, u;\nmov.b64 {%2, %3}, v;\n}"
               : "=r"(r[0]), "=r"(r[1]), "=r"(r[2]), "=r"(tag) : "l"(p) : "memory");
  return tag;
}
DEVINL float ex2(float x) { float y; asm("ex2.approx.ftz.f32 %0, %1;" : "=f"(y) : "f"(x)); return y; }
DEVINL float rcp(float x) { float y; asm("rcp.approx.ftz.f32 %0, %1;" : "=f"(y) : "f"(x)); return y; }
DEVINL uint32_t pack2(float lo, float hi) { uint32_t r; asm("cvt.rn.bf16x2.f32 %0, %1, %2;" : "=r"(r) : "f"(hi), "f"(lo)); return r; }
DEVINL uint32_t pack2h(float lo, float hi) { uint32_t r; asm("cvt.rz.f16x2.f32 %0, %1, %2;" : "=r"(r) : "f"(hi), "f"(lo)); return r; }
DEVINL uint32_t prmt0(uint32_t a, uint32_t sel) { uint32_t r; asm("prmt.b32 %0, %1, 0, %2;" : "=r"(r) : "r"(a), "r"(sel)); return r; }
DEVINL void stg128(const void* p, uint32_t a, uint32_t b, uint32_t c, uint32_t d) {
  asm volatile("st.global.v4.b32 [%0], {%1, %2, %3, %4};" ::"l"(p), "r"(a), "r"(b), "r"(c), "r"(d) : "memory");
}
DEVINL float bf_lo(uint32_t w) { return __uint_as_float(w << 16); }
DEVINL float bf_hi(uint32_t w) { return __uint_as_float(w & 0xFFFF0000u); }
DEVINL float bf_round(float x) { return bf_lo(pack2(x, 0.f)); }
DEVINL uint32_t add_bf16x2(uint32_t a, uint32_t b) { uint32_t r; asm("add.rn.bf16x2 %0, %1, %2;" : "=r"(r) : "r"(a), "r"(b)); return r; }
DEVINL void stsm4(uint32_t addr, uint32_t a, uint32_t b, uint32_t c, uint32_t d) {
  asm volatile("stmatrix.sync.aligned.m8n8.x4.shared.b16 [%0], {%1, %2, %3, %4};" ::"r"(addr), "r"(a), "r"(b), "r"(c), "r"(d) : "memory");
}
DEVINL void ldsm4(uint32_t addr, uint32_t (&r)[4]) {
  asm volatile("ldmatrix.sync.aligned.m8n8.x4.shared.b16 {%0, %1, %2, %3}, [%4];" : "=r"(r[0]), "=r"(r[1]), "=r"(r[2]), "=r"(r[3]) : "r"(addr) : "memory");
}
DEVINL void ldsm4t(uint32_t addr, uint32_t (&r)[4]) {
  asm volatile("ldmatrix.sync.aligned.m8n8.x4.trans.shared.b16 {%0, %1, %2, %3}, [%4];" : "=r"(r[0]), "=r"(r[1]), "=r"(r[2]), "=r"(r[3]) : "r"(addr) : "memory");
}
DEVINL void sts128(uint32_t addr, uint32_t a, uint32_t b, uint32_t c, uint32_t d) {
  asm volatile("st.shared.v4.b32 [%0], {%1, %2, %3, %4};" ::"r"(addr), "r"(a), "r"(b), "r"(c), "r"(d) : "memory");
}
DEVINL float2 lds64f(uint32_t addr) { float2 v; asm volatile("ld.shared.v2.f32 {%0, %1}, [%2];" : "=f"(v.x), "=f"(v.y) : "r"(addr) : "memory"); return v; }
DEVINL void mma16816(float (&d)[4], uint32_t a0, uint32_t a1, uint32_t a2, uint32_t a3, uint32_t b0, uint32_t b1) {
  asm("mma.sync.aligned.m16n8k16.row.col.f32.bf16.bf16.f32 {%0, %1, %2, %3}, {%4, %5, %6, %7}, {%8, %9}, {%0, %1, %2, %3};"
               : "+f"(d[0]), "+f"(d[1]), "+f"(d[2]), "+f"(d[3]) : "r"(a0), "r"(a1), "r"(a2), "r"(a3), "r"(b0), "r"(b1));
}
template <int N> DEVINL void fence_regs(float (&d)[N]) {
#pragma unroll
  for (int i = 0; i < N; i++) asm volatile("" : "+f"(d[i])::"memory");
}
template <int N> DEVINL void fence_regs(uint32_t (&d)[N]) {
#pragma unroll
  for (int i = 0; i < N; i++) asm volatile("" : "+r"(d[i])::"memory");
}
DEVINL void lds128(uint32_t addr, uint32_t* r) {
  asm volatile("ld.shared.v4.b32 {%0, %1, %2, %3}, [%4];" : "=r"(r[0]), "=r"(r[1]), "=r"(r[2]), "=r"(r[3]) : "r"(addr) : "memory");
}
DEVINL void sched_fence() { asm volatile("griddepcontrol.launch_dependents;" ::: "memory"); }

struct Scratch {
  bf16 k[32 * 2048 * 32];
  bf16 xs[2048 * 1024];
  bf16 os[2048 * 1024];
  bf16 v[32 * 2048 * 32];
  float kn[2 * 128 * 16];
  uint32_t cnt[256 * 32];
  float2 stats[8 * 2048];
  uint4 halo[128 * 12 * 32];
  float csp[2 * 16 * 8 * 192];
  uint4 qsave[128 * 256 * 8];
  uint32_t esc[4 * 65536 * 20];
};
__device__ __align__(1024) Scratch g_s;
#define g_k g_s.k
#define g_xs g_s.xs
#define g_os g_s.os
#define g_v g_s.v
#define g_kn g_s.kn
#define g_cnt g_s.cnt
#define g_stats g_s.stats
#define g_halo g_s.halo
#define g_csp g_s.csp
#define g_qsave g_s.qsave
#define g_esc g_s.esc
#define g_epoch g_s.cnt[255 * 32]

DEVINL uint32_t* cnt_x(int bm) { return g_cnt + bm * 32; }
DEVINL uint32_t* cnt_o(int l, int pm, int h) { return g_cnt + (32 + (l * 16 + pm) * 2 + h) * 32; }
DEVINL uint32_t* cnt_kv(int lb, int bn) { return g_cnt + (160 + lb * 16 + bn) * 32; }
DEVINL uint32_t* cnt_ad(int bn) { return g_cnt + (192 + bn) * 32; }
DEVINL uint32_t* cnt_cs(int t, int bn) { return g_cnt + (208 + t * 16 + bn) * 32; }

DEVINL int qord(int i, int l, int pn) {
  const int u = i < 9 ? i - 3 : i - 9;
  return l == 0 ? i : i < 3 ? ((2 * pn) ^ (2 * (i & 1))) + (i >> 1) : i == 15 ? (2 * pn) ^ 3 : 2 * (u < (pn & 6) ? u : u + 2) + (i >= 9);
}
struct Params {
  CUtensorMap m[16];
  const bf16* x0;
  const bf16* wq[2];
  uint32_t zero;
  int map[128];
  uint64_t wd, xd;
  struct __align__(16) { uint64_t kd, vd; } kv[4];
};
enum { M_X0A = 0, M_XSA, M_WQA, M_WQB, M_WOA, M_WOB, M_OS, M_K, M_V, M_X0R, M_XSR, M_XSO, M_OUT, M_XST, M_X0H, M_OL, M_COUNT };

constexpr uint32_t QSTG = 57344;
constexpr uint32_t T0 = 65536, TSTG = 32768;
constexpr uint32_t ONES = 230400;
constexpr uint32_t PSTG = 32768, RES = 196608;
constexpr uint32_t KSC = 98304, VSC = 133120, HRS = 167936;
constexpr uint32_t ROWST = 229376, COLS = 231424, BARS = 232192, SMEM_BYTES = 232448;
constexpr uint32_t B_QF = BARS, B_QE = BARS + 32, B_TF = BARS + 64, B_TE = BARS + 96, B_PF = BARS + 128, B_PE = BARS + 176,
                   B_RF = BARS + 224, W_X = BARS + 232, B_QL = BARS + 240, B_PA = BARS + 248;
enum { NB_ST = 1, NB_KV = 2  , NB_DONE = 3, NB_SC = 4, NB_SIG = 5  , NB_KN = 9  , NB_X = 11, NB_HALO = 12  , NB_X0 = 15 };

DEVINL uint32_t pslot_b(uint32_t s) { return ((0x320415u >> (4 * s)) & 7) * 16384u; }
DEVINL uint32_t pslot_a(uint32_t s, int l) { return 98304u + ((((l & 1) ? 0x541230u : 0x041235u) >> (4 * s)) & 7) * 16384u; }

constexpr float QSCALE = 0.17677669529663687f * 1.4426950408889634f;
constexpr uint32_t QPARK = 32768;

DEVINL uint32_t exp2_h2(uint32_t s, uint32_t c852) {
  uint32_t r, t, w, m, d;
  asm volatile("{.reg .b64 t; add.rn.f16x2 %0, %1, %2; cvt.u64.u32 t, %0; cvt.u32.u64 %0, t;}" : "=r"(r) : "r"(s), "r"(0x65EA65EAu));
  asm volatile("fma.rn.f16x2 %0, %1, %2, %3;" : "=r"(t) : "r"(r), "r"(0xB880B880u), "r"(c852));
  asm volatile("fma.rn.f16x2 %0, %1, %2, %3;" : "=r"(w) : "r"(s), "r"(0x38803880u), "r"(t));
  asm volatile("fma.rn.f16x2 %0, %1, %1, %2;" : "=r"(m) : "r"(w), "r"(0x4A1F4A2Du));
  asm volatile("{.reg .b32 t; shf.l.clamp.b32 t, %2, %1, 7; add.u32 %0, t, %2;}" : "=r"(d) : "r"(r), "r"(m));
  return d;
}
DEVINL float exp2_fix(float s) { float z; asm volatile("add.rn.f32 %0, %1, 0f43BF34BC;" : "=f"(z) : "f"(s)); return z; }
DEVINL uint32_t exp2_base(float z0, float z1) { uint32_t B; asm volatile("prmt.b32 %0, %1, %2, 0x6521;" : "=r"(B) : "r"(__float_as_uint(z0)), "r"(__float_as_uint(z1))); return B; }
template <uint32_t MASK> DEVINL uint32_t and_or(uint32_t a, uint32_t c) { uint32_t r; asm volatile("lop3.b32 %0, %1, %3, %2, 0xEA;" : "=r"(r) : "r"(a), "r"(c), "n"(MASK)); return r; }
DEVINL uint32_t fma_bf2(uint32_t a, uint32_t b, uint32_t c) { uint32_t r; asm volatile("fma.rn.bf16x2 %0, %1, %2, %3;" : "=r"(r) : "r"(a), "r"(b), "r"(c)); return r; }
DEVINL float ex2v(float x) { float y; asm volatile("ex2.approx.ftz.f32 %0, %1;" : "=f"(y) : "f"(x)); return y; }
DEVINL uint32_t pack2v(float lo, float hi) { uint32_t r; asm volatile("cvt.rn.bf16x2.f32 %0, %1, %2;" : "=r"(r) : "f"(hi), "f"(lo)); return r; }
DEVINL void unesc(uint32_t (&u)[4], const uint32_t* esc, uint32_t tag) {
  const bool saved = __ldcg(esc + 16) == tag;
#pragma unroll
  for (int j = 0; j < 4; j++) {
    float lo, hi;
    asm("{.reg .f16 a, b; mov.b32 {a, b}, %2; cvt.f32.f16 %0, a; cvt.f32.f16 %1, b;}" : "=f"(lo), "=f"(hi) : "r"(u[j]));
    u[j] = saved ? __ldcg(esc + 4 * j) : pack2(lo, hi);
  }
}

DEVINL void attn_slow(const uint32_t (&q)[8], int head, const uint32_t* kesc, uint32_t tag, float (&res)[20], int lane) {
  const int g = lane >> 2, qd = lane & 3;
  const bf16* kb = g_k + (size_t)head * 2048 * 32;
  const bf16* vb = g_v + (size_t)head * 2048 * 32;
  float o[4][4], m0 = -INFINITY, m1 = -INFINITY, l0 = 0.f, l1 = 0.f;
#pragma unroll
  for (int j = 0; j < 4; j++) { o[j][0] = o[j][1] = o[j][2] = o[j][3] = 0.f; }
#pragma unroll 1
  for (int k0 = 0; k0 < 2048; k0 += 16) {
    float s[2][4];
#pragma unroll
    for (int nt = 0; nt < 2; nt++) {
      s[nt][0] = s[nt][1] = s[nt][2] = s[nt][3] = 0.f;
      const uint32_t* kp = (const uint32_t*)(kb + (size_t)(k0 + nt * 8 + g) * 32) + qd;
      uint32_t k[4] = {__ldcg(kp), __ldcg(kp + 4), __ldcg(kp + 8), __ldcg(kp + 12)};
      unesc(k, kesc + (k0 + nt * 8 + g) * 20 + qd, tag);
      __syncwarp();
      mma16816(s[nt], q[0], q[1], q[2], q[3], k[0], k[1]);
      mma16816(s[nt], q[4], q[5], q[6], q[7], k[2], k[3]);
    }
    float a0 = fmaxf(fmaxf(s[0][0], s[0][1]), fmaxf(s[1][0], s[1][1]));
    float a1 = fmaxf(fmaxf(s[0][2], s[0][3]), fmaxf(s[1][2], s[1][3]));
    a0 = fmaxf(a0, __shfl_xor_sync(~0u, a0, 1)); a0 = fmaxf(a0, __shfl_xor_sync(~0u, a0, 2));
    a1 = fmaxf(a1, __shfl_xor_sync(~0u, a1, 1)); a1 = fmaxf(a1, __shfl_xor_sync(~0u, a1, 2));
    const float n0 = fmaxf(m0, a0), n1 = fmaxf(m1, a1);
    const float c0 = (m0 == n0) ? 1.f : ex2(m0 - n0), c1 = (m1 == n1) ? 1.f : ex2(m1 - n1);
    m0 = n0; m1 = n1;
    const uint32_t p0 = pack2(ex2(s[0][0] - n0), ex2(s[0][1] - n0)), p1 = pack2(ex2(s[0][2] - n1), ex2(s[0][3] - n1));
    const uint32_t p2 = pack2(ex2(s[1][0] - n0), ex2(s[1][1] - n0)), p3 = pack2(ex2(s[1][2] - n1), ex2(s[1][3] - n1));
    l0 = l0 * c0 + bf_lo(p0) + bf_hi(p0) + bf_lo(p2) + bf_hi(p2);
    l1 = l1 * c1 + bf_lo(p1) + bf_hi(p1) + bf_lo(p3) + bf_hi(p3);
#pragma unroll
    for (int j = 0; j < 4; j++) {
      o[j][0] *= c0; o[j][1] *= c0; o[j][2] *= c1; o[j][3] *= c1;
      const unsigned short* vp = (const unsigned short*)(vb + (size_t)(k0 + 2 * qd) * 32 + j * 8 + g);
      const uint32_t b0 = (uint32_t)__ldcg(vp) | ((uint32_t)__ldcg(vp + 32) << 16);
      const uint32_t b1 = (uint32_t)__ldcg(vp + 256) | ((uint32_t)__ldcg(vp + 288) << 16);
      mma16816(o[j], p0, p1, p2, p3, b0, b1);
    }
  }
  l0 += __shfl_xor_sync(~0u, l0, 1); l0 += __shfl_xor_sync(~0u, l0, 2);
  l1 += __shfl_xor_sync(~0u, l1, 1); l1 += __shfl_xor_sync(~0u, l1, 2);
#pragma unroll
  for (int j = 0; j < 4; j++) { res[4 * j] = o[j][0]; res[4 * j + 1] = o[j][1]; res[4 * j + 2] = o[j][2]; res[4 * j + 3] = o[j][3]; }
  res[16] = l0; res[18] = l1;
}

__device__ __noinline__ void attn_redo(int redo, int l, int b, int wg, int w, uint32_t tag) {
  const int lane = lane_id();
#pragma unroll 1
  for (int t = 0; t < 4; t++) {
    const int h = t >> 1, head = 2 * (b & 15) + h, row = (b >> 4) * 256 + wg * 128 + (t & 1) * 64 + w * 16 + (lane >> 2);
    if ((redo >> t) & 1) {
      const uint32_t* esc = g_esc + (size_t)((l & 2) * 65536 + head * 2048) * 20;
      const uint32_t* qs = (const uint32_t*)(g_qsave + (block_id() * 256 + wg * 128 + w * 32 + lane) * 8 + 2 * t);
      uint32_t q[8]; float o[20];
#pragma unroll
      for (int i = 0; i < 2; i++) {
        uint32_t u[4] = {__ldcg(qs + i), __ldcg(qs + i + 2), __ldcg(qs + i + 4), __ldcg(qs + i + 6)};
        unesc(u, esc + (row + i * 8) * 20 + (lane & 3), tag);
        q[i] = u[0]; q[i + 2] = u[1]; q[i + 4] = u[2]; q[i + 6] = u[3];
      }
      __syncwarp();
      attn_slow(q, head, esc + 65536 * 20, tag, o, lane);
      const float i0 = rcp(o[16]), i1 = rcp(o[18]);
      bf16* op = g_os + (size_t)row * 1024 + h * 512 + (b & 15) * 32 + (lane & 3) * 8;
      *(uint4*)op = make_uint4(pack2(o[0] * i0, o[1] * i0), pack2(o[4] * i0, o[5] * i0), pack2(o[8] * i0, o[9] * i0), pack2(o[12] * i0, o[13] * i0));
      *(uint4*)(op + 8 * 1024) = make_uint4(pack2(o[2] * i1, o[3] * i1), pack2(o[6] * i1, o[7] * i1), pack2(o[10] * i1, o[11] * i1), pack2(o[14] * i1, o[15] * i1));
    }
    if ((t & 1) && ((redo >> 2 * h) & 3)) bar_arrive(NB_SIG + 2 * h + wg, 160 + 32 * (h & wg));
  }
}

__global__ void __cluster_dims__(2, 1, 1) __launch_bounds__(384, 1) fused_kernel(const __grid_constant__ Params prm) {
  extern __shared__ __align__(1024) char smem[];
  const uint32_t sb = (uint32_t)__cvta_generic_to_shared(smem);
  const int tid = threadIdx.x, lane = tid & 31;
  const int wg = __shfl_sync(0xffffffffu, tid >> 7, 0);
  const int w = __shfl_sync(0xffffffffu, (tid >> 5) & 3, 0);
  const int bm = remap(blockIdx.x) >> 4, bn = remap(blockIdx.x) & 15;

  auto first_tile = [&](int kt) {
    e_expect_tx(sb + B_QF + 8 * kt, QSTG);
    tma_ld(sb + kt * QSTG, &prm.m[M_X0A], kt * 64, bm * 256, sb + B_QF + 8 * kt);
    tma_ld3(sb + kt * QSTG + 32768, &prm.m[M_WQA], bn * 64, kt * 64, 0, sb + B_QF + 8 * kt);
  };
  auto init4 = [&](uint32_t bar, uint32_t c0, uint32_t c1, uint32_t c2, uint32_t c3) {
    asm volatile("{\n.reg .pred pe;\nelect.sync _|pe, 0xffffffff;\n@pe mbarrier.init.shared::cta.b64 [%0], %1;\n@pe mbarrier.init.shared::cta.b64 [%0+8], %2;\n"
                 "@pe mbarrier.init.shared::cta.b64 [%0+16], %3;\n@pe mbarrier.init.shared::cta.b64 [%0+24], %4;\n@pe fence.mbarrier_init.release.cluster;\n}"
                 ::"r"(bar), "r"(c0), "r"(c1), "r"(c2), "r"(c3) : "memory");
  };
  if (wg < 2) {
    const uint32_t k = wg * 4 + w, lo = (0x1411814u >> (4 * k)) & 15, hi = (0x1441814u >> (4 * k)) & 15;
    if (tid < 32) asm volatile("prefetch.global.L2 [%0];" ::"l"(prm.x0 + (size_t)(bm * 256 + bn * 16 + (tid & 15)) * 1024 + (tid >> 4) * 64));
    else if (tid < 80) asm volatile("prefetch.global.L2 [%0];" ::"l"(prm.wq[0] + (bm * 16 + (tid & 15)) * 3072 + ((tid >> 4) - 2) * 1024 + bn * 64));
    __syncwarp();
    if (k < 7) init4(sb + B_QE + 32 * k, lo, lo, hi, k == 6 ? 2 : hi);
    __syncwarp();
    if (k == 6 && lane == 0) *(volatile unsigned long long*)(smem + W_X) = 0ull;
  } else if (w == 0) {
    init4(sb + B_QF, 1, 1, 1, 1);
    __syncwarp();
    first_tile(0);
  }
  __syncthreads();
  asm volatile("barrier.cluster.arrive.relaxed.aligned;" ::: "memory");

  if (wg == 2) {
    asm volatile("setmaxnreg.dec.sync.aligned.u32 56;");
    const uint32_t ep1 = *(volatile uint32_t*)&g_epoch + 1;
    if (w == 0) {
      first_tile(1);
      mbar_wait(sb + B_QF, 0);
      first_tile(2); first_tile(3);
#pragma unroll 1
      for (int kt = 4; kt < 16; kt++) l2_prefetch(prm.wq[0] + kt * 196608 + blockIdx.x * 1536, 3072);
      cluster_wait();
#pragma unroll 1
      for (int l = 0; l < 4; l++) {
        IDS();
        const CUtensorMap* mw = &prm.m[M_WQA + (l & 1)];
        const CUtensorMap* mx = &prm.m[l == 0 ? M_X0A : M_XSA];
        const CUtensorMap* mh = &prm.m[l == 0 ? M_X0H : M_XSO];
        const CUtensorMap* mo = &prm.m[M_WOA + (l & 1)];
        auto q_b = [&](int i) {
          const int s = i & 3;
          mbar_wait(sb + B_QE + 8 * s, ((i >> 2) & 1) ^ 1);
          e_expect_tx(sb + B_QF + 8 * s, QSTG);
          tma_ld3(sb + s * QSTG + 32768, mw, bn * 64, qord(i, l, pn) * 64, 0, sb + B_QF + 8 * s);
        };
        uint32_t rdy = l ? 0u : ~0u;
        auto q_a = [&](int i) {
          const int kt = qord(i, l, pn);
          await_flag(kt, rdy, cnt_x(bm) + (lane & 15), ep1 * 9 - 6 + 2 * l);
          if (i == 3 || (i == 15 && l)) tma_ld(sb + 3 * QSTG, mx, kt * 64, bm * 256, sb + B_QF + 24);
          else tma_ld_mc(sb + (i & 3) * QSTG + rank * 16384, mh, kt * 64, bm * 256 + rank * 128, sb + B_QF + 8 * (i & 3));
        };
        if (l > 0) {
#pragma unroll 1
          for (int i = 0; i < 3; i++) {
            if (i == 2) { q_b(3); q_a(3); }
            const int kt = qord(i, l, pn);
            await_flag(kt, rdy, cnt_x(bm) + (lane & 15), ep1 * 9 - 6 + 2 * l);
            e_expect_tx(sb + B_QF + 8 * i, 16384);
            tma_ld(sb + i * QSTG + (po ^ 1) * 16384, &prm.m[M_XSO], kt * 64, (pm ^ 1) * 128, sb + B_QF + 8 * i);
          }
        }
#pragma unroll 1
        for (int i = 4; i < 16; i++) {
          if (l == 3 && i == 12) poll_ge(cnt_ad(bn), ep1 * 16);
          q_b(i); q_a(i);
        }
        if (l & 1) {
          const int krow = 2 * bn * 2048 + bm * 256;
          uint32_t* kvc = cnt_kv(l >> 1, bn);
          uint32_t seen = 0;
#pragma unroll 1
          for (int it = 1; it < 16; it++) {
            const int s = it & 3;
            if (it == 4) {
              bar_sync(NB_KV + 12, 288);
              mbar_wait(sb + B_TF + 24, 0);
#pragma unroll 1
              for (int i = 0; i < 4; i++) tma_st(&prm.m[M_K + (i & 1)], 0, krow + 2048 + (i >> 1) * 128, sb + i * 8192);
              bulk_commit();
            }
            if (it == 5) { bulk_wait_n<0>(); e_red(kvc + 16 + bm); }
            if (it == 12) { e_expect_tx(sb + B_RF, 32768); tma_ld3(sb + RES, &prm.m[M_XSR], 0, pm * 128, 2 * pn, sb + B_RF); }
            if (it == 1 || it == 3) mbar_wait(sb + B_QE + 12 + 4 * it, 1);
            mbar_wait(sb + B_TE + 8 * s, ((it >> 2) & 1) ^ 1);
            if (it < 8) {
#pragma unroll 1
              for (uint32_t n = 0; n < 200000u && (~seen & (3u << (2 * it - 2) | (it == 4 ? 0xC000u : 0u))); n++)
                seen = __ballot_sync(~0u, (int)(ld_acquire(kvc + (lane < 7 || lane == 15 ? (bm + 1 + lane) & 7 : 8 + ((bm + 2 + lane) & 7))) - ep1) >= 0);
              fence_async_gl();
            } else if (it == 8) { poll_ge(kvc + 16 + (lane & 7), ep1); fence_async_gl(); }
            e_expect_tx(sb + B_TF + 8 * s, 32768);
#pragma unroll 1
            for (int i = 0; i < 2; i++) {
              const int u = 2 * it - 2 + i;
              const int row = 2 * bn * 2048 + (it > 7 ? 2048 + ((bm + it) & 7) * 256 + i * 128 : u < 7 ? ((bm + 1 + u) & 7) * 256 : ((bm + 2 + u) & 7) * 256 + 128);
              tma_ld(sb + T0 + s * TSTG + i * 8192, &prm.m[M_K], 0, row, sb + B_TF + 8 * s);
              tma_ld(sb + T0 + s * TSTG + 16384 + i * 8192, &prm.m[M_V], 0, row, sb + B_TF + 8 * s);
            }
          }
        }
        auto p_b = [&](int i, uint32_t s, uint32_t par) {
          mbar_wait(sb + B_PE + 8 * s, par ^ 1);
          e_expect_tx(sb + B_PF + 8 * s, PSTG);
          tma_ld5(sb + pslot_b(s), mo, i >> 3, (2 * i + bn) & 14, 2 * pn, sb + B_PF + 8 * s);
        };
        auto p_a = [&](int i, uint32_t s) {
          await_flag(i, rdy, cnt_o(l, pm, (lane >> 3) & 1) + ((lane + (bn >> 1)) & 7), ep1 * 2);
          tma_ld_mc(sb + pslot_a(s, l) + rank * 8192, &prm.m[M_OS], (i & 8) * 64 + ((2 * i + bn) & 14) * 32, pm * 128 + rank * 64, sb + B_PF + 8 * s);
        };
        auto p_a2 = [&](int i) {
          await_flag(i, rdy, cnt_o(l, pm, (lane >> 3) & 1) + ((lane + (bn >> 1)) & 7), ep1 * 2);
          tma_ld(sb + pslot_a(i, l), &prm.m[M_OS], (i & 8) * 64 + ((2 * i + bn) & 14) * 32, pm * 128, sb + B_PF + 8 * i);
          tma_ld(sb + pslot_a(i, l) + 8192, &prm.m[M_OS], (i & 8) * 64 + ((2 * i + bn) & 14) * 32, pm * 128 + 64, sb + B_PF + 8 * i);
        };
        rdy = 0;
        if (l & 1) {
#pragma unroll 1
          for (int u = 0; u < 6; u++) { const int i = (0x205413 >> (4 * u)) & 7; if (u == 4) mbar_wait(sb + B_TE, 1); p_b(i, i, i < 4 ? 1 : 0); }
#pragma unroll 1
          for (int u = 0; u < 6; u++) {
            const int i = (0x542130 >> (4 * u)) & 7;
            if (!(u & 1)) mbar_wait(sb + B_TE + 8 + 4 * u, 1);
            if (u == 4) bar_sync(NB_SIG + 3, 192);
            p_a2(i);
          }
        } else {
#pragma unroll 1
          for (int u = 0; u < 6; u++) { const int i = (0x543120 >> (4 * u)) & 7; if (u == 0 || u == 2) mbar_wait(sb + B_QE + 8 - 4 * u, 1); p_b(i, i, 0); }
          mbar_wait(sb + B_QE + 24, 1);
          e_expect_tx(sb + B_RF, 32768);
          tma_ld3(sb + RES, &prm.m[l == 0 ? M_X0R : M_XSR], 0, pm * 128, 2 * pn, sb + B_RF);
          await_flag(1, rdy, cnt_o(l, pm, (lane >> 3) & 1) + ((lane + (bn >> 1)) & 7), ep1 * 2);
          bar_sync(NB_DONE, 288);
          e_arrive_both(sb + B_PA);
          p_a2(1);
          mbar_wait(sb + B_PA, (l >> 1) & 1);
#pragma unroll 1
          for (int i = 2; i < 6; i++) { if (i > 3) mbar_wait(sb + B_PF + 8 * (i - 3), 0); p_a(i, i); }
        }
        uint32_t s = 0, lap = 1;
#pragma unroll 1
        for (int i = 6; i < 16; i++) {
          p_b(i, s, ((s < 4 ? l : 0) + lap) & 1);
          p_a(i, s);
          if (++s == 6) { s = 0; lap++; }
        }
        const CUtensorMap* mn = &prm.m[M_WQA + ((l + 1) & 1)];
        if (l < 3) {
          mbar_wait(sb + B_PE + 8 * 4, 1); mbar_wait(sb + B_PE + 8 * 5, 1);
          tma_ld3(sb + 32768, mn, bn * 64, 2 * pn * 64, 0, sb + B_QL);
          mbar_wait(sb + B_PE + 8 * 0, l & 1);
          e_expect_tx(sb + B_PA, 24576); e_expect_tx(sb + B_PA, 16384);
          tma_ld3(sb + QSTG + 32768, mn, bn * 64, ((2 * pn) ^ 2) * 64, 0, sb + B_PA);
          mbar_wait(sb + B_PE + 8 * 1, l & 1);
          tma_ld3(sb + 2 * QSTG + 32768, mn, bn * 64, (2 * pn + 1) * 64, 0, sb + B_QL);
          mbar_wait(sb + B_PE + 24, l & 1);
          bar_sync(NB_X0, 320);
          fence_async_gl();
          tma_ld_mc(sb + QSTG + po * 16384, &prm.m[M_XSO], 2 * pn * 64, pm * 128, sb + B_PA, 2 - rank);
        }
        if (l < 3) { bar_sync(NB_X, 320); e_expect_tx(sb + B_QL, 49152); }
      }
      if (blockIdx.x == 0 && lane_id() == 0) *(volatile uint32_t*)&g_epoch = ep1;
    } else {
      const int hw = w - 1;
      if (lane < 5) asm volatile("prefetch.tensormap [%0];" ::"l"(&prm.m[1 + 5 * hw + lane]) : "memory");
      __syncwarp();
      cluster_wait();
      mbar_wait(sb + B_QF, 0);
#pragma unroll 1
      for (int l = 0; l < 4; l++) {
        IDS();
        if (l > 0) { mbar_wait(sb + B_QL, (l + 1) & 1); mbar_wait(sb + B_QF + 24, 0); }
        if (l == 0) {
#pragma unroll 1
          for (int r = 2 * hw; r < 16; r += 6) {
            const uint4* p = (const uint4*)(prm.x0 + (size_t)(b * 16 + r) * 1024) + lane;
            float s1[2] = {0.f, 0.f}, s2[2] = {0.f, 0.f};
#pragma unroll
            for (int i = 0; i < 8; i++) {
              const uint4 v = __ldg(p + 32 * i);
              const uint32_t u[4] = {v.x, v.y, v.z, v.w};
#pragma unroll
              for (int k = 0; k < 4; k++) { const float a = bf_lo(u[k]), c = bf_hi(u[k]); s1[i >> 2] += a + c; s2[i >> 2] = fmaf(a, a, fmaf(c, c, s2[i >> 2])); }
            }
#pragma unroll
            for (int o = 16; o; o >>= 1)
#pragma unroll
              for (int rr = 0; rr < 2; rr++) { s1[rr] += __shfl_xor_sync(~0u, s1[rr], o); s2[rr] += __shfl_xor_sync(~0u, s2[rr], o); }
            if (lane == 0) *(float4*)&g_stats[b * 16 + r] = make_float4(s1[0], s2[0], s1[1], s2[1]);
          }
        }
        if (l < 2) {
          float cs[8];
#pragma unroll
          for (int i = 0; i < 8; i++) cs[i] = 0.f;
          const uint4* wp = (const uint4*)(prm.wq[l] + (size_t)(bm * 128 + (lane >> 3)) * 3072 + hw * 1024 + bn * 64) + (lane & 7);
#pragma unroll 8
          for (int i = 0; i < 32; i++) {
            const uint4 v = __ldg(wp + (size_t)i * 4 * 384);
            cs[0] += bf_lo(v.x); cs[1] += bf_hi(v.x); cs[2] += bf_lo(v.y); cs[3] += bf_hi(v.y);
            cs[4] += bf_lo(v.z); cs[5] += bf_hi(v.z); cs[6] += bf_lo(v.w); cs[7] += bf_hi(v.w);
          }
#pragma unroll
          for (int i = 0; i < 8; i++) { cs[i] += __shfl_xor_sync(~0u, cs[i], 8); cs[i] += __shfl_xor_sync(~0u, cs[i], 16); }
          if (lane < 8) {
            float4* d = (float4*)(g_csp + ((l * 16 + bn) * 8 + bm) * 192 + hw * 64 + lane * 8);
            d[0] = make_float4(cs[0], cs[1], cs[2], cs[3]); d[1] = make_float4(cs[4], cs[5], cs[6], cs[7]);
          }
          __syncwarp();
          asm volatile("fence.acq_rel.gpu;" ::: "memory");
          e_red_relaxed(cnt_cs(l, bn));
          if (l == 0) e_red_relaxed(cnt_x(bm) + bn);
          poll_ge(lane < 16 && l == 0 ? cnt_x(bm) + lane : cnt_cs(l, bn), lane < 16 && l == 0 ? ep1 * 9 - 6 : ep1 * 24);
        }
        if (l > 0) poll_ge(cnt_x(bm) + (lane & 15), ep1 * 9 - 6 + 2 * l);
#pragma unroll 1
        for (int it = hw * 32 + lane; it < 176; it += 96) {
          const bool rows = it < 128;
          const float4* p = rows ? (const float4*)(g_stats + bm * 256) + it : (const float4*)(g_csp + ((l & 1) * 16 + bn) * 8 * 192) + (it - 128);
          const int stride = rows ? 1024 : 48, np = rows && l == 0 ? 1 : 8;
          float4 a = make_float4(0.f, 0.f, 0.f, 0.f);
#pragma unroll
          for (int k = 0; k < 8; k++) if (k < np) { const float4 v = __ldcg(p + k * stride); a.x += v.x; a.y += v.y; a.z += v.z; a.w += v.w; }
          if (rows) {
            const float m0 = a.x * (1.f / 1024.f), m1 = a.z * (1.f / 1024.f);
            const float v0 = fmaxf(a.y * (1.f / 1024.f) - m0 * m0, 0.f), v1 = fmaxf(a.w * (1.f / 1024.f) - m1 * m1, 0.f);
            const float r0 = __fdividef(1.f, bf_round(sqrtf(bf_round(bf_round(v0) + 1e-5f)))), r1 = __fdividef(1.f, bf_round(sqrtf(bf_round(bf_round(v1) + 1e-5f))));
            a = make_float4(r0, -bf_round(m0), r1, -bf_round(m1));
          }
          if (rows && (l & 1) && (it & 4)) a = make_float4(a.y, a.x, a.w, a.z);
          *(float4*)(smem + ROWST + it * 16) = a;
        }
        __syncwarp();
        if (lane == 0) asm volatile("red.release.cta.shared.add.u32 [%0], 1;" ::"r"(sb + W_X) : "memory");
        if (hw == 2) {
          if (!(l & 1)) {
            bar_sync(NB_ST, 288);
            const uint4* hp = g_halo + (b - 16) * 384 + lane;
#pragma unroll 1
            for (int h = 0; h < 2; h++) {
              uint32_t t[18];
#pragma unroll
              for (int i = 0; i < 18; i++) t[i] = 0;
#pragma unroll 1
              for (uint32_t n = bm ? 0 : 100000u; n < 100000u; n++) {
                uint32_t miss = 0;
#pragma unroll
                for (int i = 0; i < 6; i++) miss |= ld_tagged(hp + h * 192 + i * 32, &t[3 * i]) ^ (4 * ep1 + l);
                if (__all_sync(~0u, !miss)) break;
              }
              mbar_wait(sb + B_QE + 16, 1);
              const uint32_t r = (lane & 7) + ((lane >> 3) & 1) * 8, rv = lane >> 2;
#pragma unroll
              for (int jj = 0; jj < 2; jj++) stsm4(sb + KSC + r * 128 + (((4 * h + 2 * jj + (lane >> 4)) ^ (r & 7)) << 4), t[4 * jj], t[4 * jj + 1], t[4 * jj + 2], t[4 * jj + 3]);
              const uint32_t ad = sb + VSC + rv * 128 + (((4 * h + (lane & 3)) ^ (rv & 7)) << 4);
              sts128(ad, t[8], t[10], t[12], t[14]); sts128(ad + 1024, t[9], t[11], t[13], t[15]);
              if (h == 0 && !(lane & 2)) *(uint32_t*)(smem + HRS + ((lane >> 2) + 8 * (lane & 1)) * 8) = t[16];
              bar_arrive(NB_HALO + h, 64);
            }
          } else {
            bar_sync(NB_KV, 288);
            sts128(sb + ONES + lane * 32, 0x3f803f80u, 0x3f803f80u, 0x3f803f80u, 0x3f803f80u);
            sts128(sb + ONES + lane * 32 + 16, 0x3f803f80u, 0x3f803f80u, 0x3f803f80u, 0x3f803f80u);
            sts128(sb + ROWST + 16, 0x62A962A9u, 0x00010001u, 0x3F003F00u, 0u);
            fence_async_smem();
            __syncwarp();
            e_arrive(sb + B_TF);
            mbar_wait(sb + B_TF + 16, 0); mbar_wait(sb + B_TF + 16, 1);
            poll_ge(cnt_kv(l >> 1, bn) + 16 + (lane & 7), ep1);
            const uint4 v = __ldcg((const uint4*)(g_kn + ((l >> 1) * 128 + bn * 8) * 16) + lane);
            const uint32_t mx = max(max(v.x, v.y), max(v.z, v.w));
            const uint32_t m0 = __reduce_max_sync(~0u, (lane & 2) ? 0u : mx), m1 = __reduce_max_sync(~0u, (lane & 2) ? mx : 0u);
            if (lane == 0) *(uint2*)(smem + ROWST) = make_uint2(m0, m1);
            __syncwarp();
            bar_arrive(NB_KN, 160); bar_arrive(NB_KN + 1, 160);
          }
        } else {
          if (l & 1) {
            uint32_t* p = cnt_kv(l >> 1, bn) + 8 * hw + bm;
            int on = lane == 0;
            PREPARED(p, on);
            bar_sync(hw ? NB_HALO : NB_DONE, 160);
            tma_st(&prm.m[M_K], 0, 2 * bn * 2048 + bm * 256 + hw * 128, sb + T0 + hw * 8192);
            tma_st(&prm.m[M_V], 0, 2 * bn * 2048 + bm * 256 + hw * 128, sb + T0 + 16384 + hw * 8192);
            bulk_commit(); bulk_wait_n<0>();
            release_add(p, on);
          }
#pragma unroll 1
          for (int h = l & 1 ? 0 : hw; h <= (l & 1 ? 1 : hw); h++) {
            uint32_t* p = l == 1 && lane == 1 ? cnt_ad(bn) : cnt_o(l, 2 * bm + (l & 1 ? hw : lane & 1), h) + (bn >> 1);
            int on = lane == 0 || (lane == 1 && (!(l & 1) || (l == 1 && h == 1)));
            int id = NB_SIG + 2 * h + (l & hw), n = l & 1 ? 160 + 32 * (h & hw) : 288;
            asm volatile("" : "+r"(id), "+r"(n));
            PREPARED(p, on);
            bar_sync(id, n);
            release_add(p, on);
            if (!(l & 1) && hw == 0) {
              mbar_wait(sb + B_QE + 24, 1);
              fence_async_gl();
              tma_ld_mc(sb + pslot_a(0, 0) + rank * 8192, &prm.m[M_OL], bn * 32, pm * 128, sb + B_PF);
            }
          }
        }
        if (hw < 2 && l < 3) {
          uint32_t* p = cnt_x(bm) + 2 * pn + hw;
          int on = lane == 0;
          PREPARED(p, on);
          if (hw) {
            bar_sync(NB_X, 320);
            tma_st(&prm.m[M_XSO], pn * 128 + 64, pm * 128, sb + 2 * QSTG + po * 16384);
            bulk_commit();
            bar_sync(NB_KV, 288);
            bulk_wait_n<0>();
          } else bar_sync(NB_X0, 320);
          release_add(p, on);
        }
      }
    }
  } else {
    asm volatile("setmaxnreg.inc.sync.aligned.u32 224;");
    const uint32_t zero = prm.zero;
    cluster_wait();
#pragma unroll 1
    for (int l = 0; l < 4; l++) {
      {
        float acc[2][96];
        const bool early = l > 0 && wg == ((cta_id() >> 3) & 1);
        uint32_t ep1 = 0;
        if (l > 0) mbar_wait(sb + B_QL, (l + 1) & 1);
        if (!early) mbar_wait(sb + B_QF, 0);
        wg_fence();
#pragma unroll
        for (int k = 0; k < 4; k++)
#pragma unroll
          for (int m = 0; m < 2; m++) {
            if (k) wgmma_m64n192k16_ss_tb(acc[m], prm.xd + wg * 1024 + m * 512 + k * 2, prm.wd + k * 128, 1);
            else wgmma_m64n192k16_ss_tb_z(acc[m], prm.xd + wg * 1024 + m * 512, prm.wd, 0);
          }
        wg_commit();
#pragma unroll 1
        for (int kt = 1; kt < 13; kt++) {
          const int s = kt == 12 ? 1 : kt & 3;
          if (l > 0 && kt == 1) mbar_wait(sb + B_PA, l == 1);
          if (!(early && kt < 3)) mbar_wait(sb + B_QF + 8 * s, (kt >> 2) & 1);
          const uint64_t da = prm.xd + wg * 1024 + s * (QSTG >> 4), db = prm.wd + s * (QSTG >> 4);
          wg_fence();
#pragma unroll
          for (int k = 0; k < 4; k++)
#pragma unroll
            for (int m = 0; m < 2; m++) wgmma_m64n192k16_ss_tb(acc[m], da + m * 512 + k * 2, db + k * 128, 1);
          wg_commit();
          if (kt == 4) ep1 = *(volatile uint32_t*)&g_epoch + 1;
          wg_wait<1>();
          if (early && kt < 4) {
            if (kt < 2) continue;
            if (kt == 2) { mbar_wait(sb + B_QF, 0); if (w == 0) e_arrive_both(sb + B_QE); }
            mbar_wait(sb + B_QF + 8 * (kt - 1), 0);
          }
          if (w == 0) e_arrive_both(sb + B_QE + 8 * ((kt - 1) & 3));
        }
        {
          const bool lag = (l & 1) == wg;
          const uint32_t s0 = 2 * (~l & 1);
          const uint64_t da = prm.xd + wg * 1024 + 2 * (QSTG >> 4), db = prm.wd + 2 * (QSTG >> 4);
          mbar_wait(sb + B_QF + 8 * s0, 1);
#pragma unroll
          for (int t = 0; t < 2; t++) {
            if (lag && t != wg) {
              wg_wait<0>();
              if (w == 0) e_arrive_both(sb + B_QE + 8 + 8 * t);
              if (t == 0) mbar_wait(sb + B_QF + 16, 1);
              mbar_wait(sb + B_QF + 24, 1);
              if (t == 1) bar_arrive(NB_ST, 288);
              bar_sync(NB_SC, 256);
            }
            const uint64_t so = (uint64_t)(t ? s0 : s0 ^ 2) * (QSTG >> 4);
            wg_fence();
#pragma unroll
            for (int k = 0; k < 4; k++)
#pragma unroll
              for (int m = 0; m < 2; m++) wgmma_m64n192k16_ss_tb(acc[m], da - so + m * 512 + k * 2, db - so + k * 128, 1);
            wg_commit();
            if (!lag || t + wg == 0) {
              wg_wait<1>();
              if (w == 0) e_arrive_both(sb + B_QE + 8 * (t ? s0 : 1));
              mbar_wait(sb + B_QF + 8 * (t ? 3 : s0 ^ 2), 1);
            }
          }
          wg_fence();
#pragma unroll
          for (int m = 1; m >= 0; m--) {
#pragma unroll
            for (int k = 0; k < 4; k++) wgmma_m64n192k16_ss_tb(acc[m], da + (QSTG >> 4) + m * 512 + k * 2, db + (QSTG >> 4) + k * 128, 1);
            wg_commit();
          }
          if (!lag) { bar_arrive(NB_SC, 256); if (wg) bar_arrive(NB_ST, 288); }
          wg_wait<2>();
          if (w == 0) { e_arrive_both(sb + B_QE + 8 * (s0 ^ 2)); if (lag && wg) e_arrive_both(sb + B_QE); }
        }
#pragma unroll 1
        for (uint32_t n = 0; n < 4000000u; n++) {
          uint32_t v;
          asm volatile("ld.acquire.cta.shared.u32 %0, [%1];" : "=r"(v) : "r"(sb + W_X) : "memory");
          if (v == (uint32_t)(3 * l + 3)) break;
        }
        IDS();
        const int g = lane >> 2, qd = lane & 3;
        float2 st[2][2];
#pragma unroll
        for (int m = 0; m < 2; m++)
#pragma unroll
          for (int hh = 0; hh < 2; hh++) st[m][hh] = lds64f(sb + ROWST + (wg * 128 + m * 64 + w * 16 + g + 8 * hh) * 8);
        float2 cs[4];
        auto load_cs = [&](int gi) {
#pragma unroll
          for (int j = 0; j < 4; j++) cs[j] = lds64f(sb + COLS + (gi * 32 + j * 8 + 2 * qd) * 4);
        };
        load_cs(2 + 2 * (l & 1));
        auto drain = [&]() {
          wg_wait<0>(); fence_regs(acc[0]);
          if (w == 0) e_arrive_both(sb + B_QE + 8 * 3);
        };
        wg_wait<1>(); fence_regs(acc[1]);
        auto norm_tile = [&](int gi, int m, float sc, uint32_t (&t)[8], float (&nrm)[2], bool h16 = false) {
          const float r0 = st[m][0].x * sc, s0 = st[m][0].y, r1 = st[m][1].y * sc, s1 = st[m][1].x;
          float n0 = 0.f, n1 = 0.f;
#pragma unroll
          for (int j = 0; j < 4; j++) {
            const float* a = &acc[m][16 * gi + 4 * j];
            const float v0 = fmaf(s0, cs[j].x, a[0]) * r0, v1 = fmaf(s0, cs[j].y, a[1]) * r0;
            const float v2 = fmaf(s1, cs[j].x, a[2]) * r1, v3 = fmaf(s1, cs[j].y, a[3]) * r1;
            n0 = fmaf(v0, v0, fmaf(v1, v1, n0)); n1 = fmaf(v2, v2, fmaf(v3, v3, n1));
            t[2 * j] = h16 ? pack2h(v0, v1) : pack2(v0, v1); t[2 * j + 1] = h16 ? pack2h(v2, v3) : pack2(v2, v3);
          }
          nrm[0] = n0; nrm[1] = n1;
        };
        auto norm_group = [&](int gi, float sc, uint32_t (&t)[2][8], float (&nrm)[2][2]) { norm_tile(gi, 0, sc, t[0], nrm[0]); norm_tile(gi, 1, sc, t[1], nrm[1]); };
        uint32_t q[2][2][8];
        const uint32_t srow = (lane & 7) + ((lane >> 3) & 1) * 8;
        const uint32_t row0 = wg * 128 + w * 16;
        if (!(l & 1)) {
          auto put_kv = [&](int gi, uint32_t r0, const uint32_t (&t)[8]) {
            if (gi < 4) {
              const uint32_t r = r0 + srow;
#pragma unroll
              for (int jj = 0; jj < 2; jj++) stsm4(sb + KSC + r * 128 + (((4 * (gi - 2) + 2 * jj + (lane >> 4)) ^ (r & 7)) << 4), t[4 * jj], t[4 * jj + 1], t[4 * jj + 2], t[4 * jj + 3]);
            } else {
              const uint32_t r = r0 + g, ad = sb + VSC + r * 128 + (((4 * (gi - 4) + qd) ^ (r & 7)) << 4);
              sts128(ad, t[0], t[2], t[4], t[6]); sts128(ad + 1024, t[1], t[3], t[5], t[7]);
            }
          };
          auto cen_tile = [&](int gi, int m, uint32_t (&t)[8]) {
#pragma unroll
            for (int j = 0; j < 4; j++) {
              const float* a = &acc[m][16 * gi + 4 * j];
              t[2 * j] = pack2(fmaf(st[m][0].y, cs[j].x, a[0]), fmaf(st[m][0].y, cs[j].y, a[1]));
              t[2 * j + 1] = pack2(fmaf(st[m][1].y, cs[j].x, a[2]), fmaf(st[m][1].y, cs[j].y, a[3]));
            }
          };
          const bool send = wg == 1 && w == 3 && bm < 7;
          uint4* hp = g_halo + b * 384 + lane;
          ep1 = 4 * ep1 + l;
          mbar_wait(sb + B_QE + 16, 1);
          float2 cn[4];
          auto next_cs = [&](int gi) {
#pragma unroll
            for (int j = 0; j < 4; j++) { cs[j] = cn[j]; cn[j] = lds64f(sb + COLS + (gi * 32 + j * 8 + 2 * qd) * 4); }
          };
#pragma unroll
          for (int j = 0; j < 4; j++) cn[j] = cs[j];
#pragma unroll
          for (int h = 0; h < 2; h++) {
            uint32_t k[8], v[8];
            next_cs(4 + h);
            cen_tile(2 + h, 1, k); put_kv(2 + h, 16 + row0 + 64, k);
            next_cs(h ? 2 : 3);
            cen_tile(4 + h, 1, v); put_kv(4 + h, 16 + row0 + 64, v);
            if (send) {
              uint4* p = hp + h * 192;
              st_tagged(p, k[0], k[1], k[2], ep1); st_tagged(p + 32, k[3], k[4], k[5], ep1); st_tagged(p + 64, k[6], k[7], v[0], ep1);
              st_tagged(p + 96, v[1], v[2], v[3], ep1); st_tagged(p + 128, v[4], v[5], v[6], ep1);
              st_tagged(p + 160, v[7], __float_as_uint(qd & 1 ? st[1][1].x : st[1][0].x), 0u, ep1);
            }
            sched_fence();
          }
          drain();
          {
            uint32_t t[8];
            next_cs(4); cen_tile(2, 0, t); put_kv(2, 16 + row0, t);
            next_cs(0); cen_tile(4, 0, t); put_kv(4, 16 + row0, t);
            next_cs(3); cen_tile(0, 0, q[0][0]); cen_tile(0, 1, q[0][1]);
          }
          const bool e = g & 1, sel = 2 * qd + (g & 1) >= g + 2, first = bm == 0 && row0 == 0;
          uint32_t ka = sb + KSC + (row0 + (lane & 7)) * 128 + (((lane >> 3) ^ (lane & 7)) << 4);
          uint32_t wa = sb + VSC + (row0 + srow) * 128 + (((lane >> 4) ^ (lane & 7)) << 4);
          uint32_t psel[3] = {e ? 0x1044u : 0x4410u, !sel ? 0x4444u : e ? 0x3244u : 0x4432u, sel ? 0x4444u : e ? 0x3244u : 0x4432u};
          bf16* op = g_os + (size_t)(bm * 256 + row0 + g) * 1024 + bn * 32 + qd * 8;
          asm volatile("" : "+r"(ka), "+r"(wa), "+l"(op));
          fence_regs(psel); fence_regs(q[0][0]); fence_regs(q[0][1]);
          sched_fence();
          bar_sync(NB_SC, 256);
          if (row0 == 0) bar_sync(NB_HALO, 64);
          float ra[4], rb[4], ca[4], cb[4];
#pragma unroll
          for (int m = 0; m < 2; m++) {
            float rk[3];
#pragma unroll
            for (int u = 0; u < 3; u++) {
              const int r = row0 + m * 64 + 8 * u + 2 * qd + e - (sel ? 16 : 8);
              rk[u] = lds64f(sb + (m == 0 && r < 0 ? HRS + 128 : ROWST) + r * 8).x;
            }
            ra[2 * m] = sel ? rk[1] : rk[0]; ra[2 * m + 1] = sel ? rk[2] : rk[1];
            rb[2 * m] = sel ? rk[0] : rk[1]; rb[2 * m + 1] = sel ? rk[1] : rk[2];
          }
#pragma unroll
          for (int i = 0; i < 4; i++) { const float rq = st[i >> 1][i & 1].x * QSCALE; ca[i] = rq * ra[i]; cb[i] = rq * rb[i]; }
#pragma unroll 1
          for (int h = 0; h < 2; h++) {
            float s[2][4][4];
            uint32_t vf[2][4][4], pf[2][2][4];
#pragma unroll
            for (int m = 0; m < 2; m++)
#pragma unroll
              for (int nt = 0; nt < 4; nt++) {
                uint32_t kf[4];
                ldsm4(ka + (m * 64 + 8 * nt) * 128, kf);
                s[m][nt][0] = s[m][nt][1] = s[m][nt][2] = s[m][nt][3] = 0.f;
                mma16816(s[m][nt], q[0][m][0], q[0][m][1], q[0][m][2], q[0][m][3], kf[0], kf[1]);
                mma16816(s[m][nt], q[0][m][4], q[0][m][5], q[0][m][6], q[0][m][7], kf[2], kf[3]);
              }
#pragma unroll
            for (int m = 0; m < 2; m++)
#pragma unroll
              for (int i = 0; i < 4; i++) {
                ldsm4t((wa ^ (32 * (i & 1))) + (m * 64 + 16 * (i >> 1)) * 128, vf[m][i]);
              }
            if (h) bar_arrive(NB_DONE, 288);
            float va[4], vb[4], mx[4];
#pragma unroll
            for (int i = 0; i < 4; i++) {
              const int m = i >> 1, hh = i & 1;
              const float a = e ? s[m][hh + 1][2 * hh + 1] : s[m][hh + 1][2 * hh];
              const float lo = e ? s[m][hh][2 * hh + 1] : s[m][hh][2 * hh], hi = e ? s[m][hh + 2][2 * hh + 1] : s[m][hh + 2][2 * hh];
              va[i] = (m == 0 && hh == 0 && first) ? -INFINITY : a * ca[i];
              vb[i] = (m == 0 && first && sel) ? -INFINITY : (sel ? lo : hi) * cb[i];
              mx[i] = fmaxf(va[i], vb[i]);
            }
#pragma unroll
            for (int i = 0; i < 4; i++) mx[i] = fmaxf(mx[i], __shfl_xor_sync(~0u, mx[i], 1));
#pragma unroll
            for (int i = 0; i < 4; i++) mx[i] = fmaxf(mx[i], __shfl_xor_sync(~0u, mx[i], 2));
#pragma unroll
            for (int i = 0; i < 4; i++) {
              va[i] = ex2(va[i] - mx[i]); vb[i] = ex2(vb[i] - mx[i]);
              mx[i] = va[i] + vb[i];
              va[i] *= ra[i]; vb[i] *= rb[i];
            }
#pragma unroll
            for (int i = 0; i < 4; i++) mx[i] += __shfl_xor_sync(~0u, mx[i], 1);
#pragma unroll
            for (int i = 0; i < 4; i++) mx[i] += __shfl_xor_sync(~0u, mx[i], 2);
#pragma unroll
            for (int i = 0; i < 4; i++) {
              const int m = i >> 1, hh = i & 1;
              const float inv = rcp(mx[i]);
              const uint32_t t = pack2(va[i] * inv, vb[i] * inv);
              pf[m][hh][hh + 1] = prmt0(t, psel[0]); pf[m][hh][hh] = prmt0(t, psel[1]); pf[m][hh][hh + 2] = prmt0(t, psel[2]);
              pf[m][hh][3 - 3 * hh] = t & zero;
            }
#pragma unroll
            for (int m = 0; m < 2; m++) {
              float o[4][4];
#pragma unroll
              for (int j = 0; j < 4; j++) o[j][0] = o[j][1] = o[j][2] = o[j][3] = 0.f;
#pragma unroll
              for (int i = 0; i < 4; i++) {
                const int kk = i >> 1, jj = 2 * (i & 1);
                mma16816(o[jj], pf[m][0][2 * kk], pf[m][1][2 * kk], pf[m][0][2 * kk + 1], pf[m][1][2 * kk + 1], vf[m][i][0], vf[m][i][1]);
                mma16816(o[jj + 1], pf[m][0][2 * kk], pf[m][1][2 * kk], pf[m][0][2 * kk + 1], pf[m][1][2 * kk + 1], vf[m][i][2], vf[m][i][3]);
              }
              stg128(op + m * 65536, pack2(o[0][0], o[0][1]), pack2(o[1][0], o[1][1]), pack2(o[2][0], o[2][1]), pack2(o[3][0], o[3][1]));
              stg128(op + m * 65536 + 8192, pack2(o[0][2], o[0][3]), pack2(o[1][2], o[1][3]), pack2(o[2][2], o[2][3]), pack2(o[3][2], o[3][3]));
            }
            bar_arrive(NB_SIG + 2 * h, 288);
            if (h == 0) {
              uint32_t t[8];
              next_cs(5); cen_tile(3, 0, t); put_kv(3, 16 + row0, t);
              next_cs(1); cen_tile(5, 0, t); put_kv(5, 16 + row0, t);
#pragma unroll
              for (int j = 0; j < 4; j++) cs[j] = cn[j];
              cen_tile(1, 0, q[0][0]); cen_tile(1, 1, q[0][1]);
              ka ^= 64; wa ^= 64; op += 512;
              bar_sync(NB_SC, 256);
              if (row0 == 0) bar_sync(NB_HALO + 1, 64);
            }
          }
        } else {
          float qn[2];
          mbar_wait(sb + B_QE + 8, 1);
          drain();
          auto esc_ptr = [&](int gi) { IDS(); return g_esc + (size_t)(((l & 2) + (gi >> 1)) * 65536 + (2 * bn + (gi & 1)) * 2048) * 20; };
          auto norm_half = [&](int gi, float sc, uint32_t (&t)[2][8], float (&nrm)[2][2], int nx) {
            norm_tile(gi, 0, sc, t[0], nrm[0], true); norm_tile(gi, 1, sc, t[1], nrm[1], true);
            float2 cn[4];
#pragma unroll
            for (int j = 0; j < 4; j++) if (nx >= 0) cn[j] = lds64f(sb + COLS + (nx * 32 + j * 8 + 2 * qd) * 4);
            if (!((nrm[0][0] + nrm[0][1]) + (nrm[1][0] + nrm[1][1]) <= 4e9f) || fminf(fminf(nrm[0][0], nrm[0][1]), fminf(nrm[1][0], nrm[1][1])) < 1.5e-5f) {
              uint32_t* p = esc_ptr(gi) + (bm * 256 + row0 + g) * 20 + qd;
#pragma unroll
              for (int m = 0; m < 2; m++) {
                uint32_t u[8]; float d[2];
                norm_tile(gi, m, sc, u, d);
#pragma unroll
                for (int i = 0; i < 10; i++) p[(m * 64 + (i & 1) * 8) * 20 + (i >> 1) * 4] = i < 8 ? u[i] : ep1;
              }
            }
            __syncwarp();
#pragma unroll
            for (int i = 0; i < 16; i++) asm volatile("{\n.reg .b32 u;\nadd.u32 u, %0, 0x00040004;\nand.b32 %0, u, 0xFFF8FFF8;\n}" : "+r"(t[i >> 3][i & 7]));
#pragma unroll
            for (int j = 0; j < 4; j++) if (nx >= 0) cs[j] = cn[j];
          };
          {
            auto max_norm = [&](const float (&nrm)[2][2]) {
              const bool o1 = qd & 1, o2 = qd & 2;
              const float a = (o1 ? nrm[1][0] : nrm[0][0]) + __shfl_xor_sync(~0u, o1 ? nrm[0][0] : nrm[1][0], 1);
              const float c = (o1 ? nrm[1][1] : nrm[0][1]) + __shfl_xor_sync(~0u, o1 ? nrm[0][1] : nrm[1][1], 1);
              const float d = (o2 ? c : a) + __shfl_xor_sync(~0u, o2 ? a : c, 2);
              return __uint_as_float(__reduce_max_sync(~0u, __float_as_uint(d)));
            };
#pragma unroll
            for (int h = 0; h < 2; h++) {
              uint32_t t[2][8]; float nrm[2][2];
              const uint32_t kb = sb + (h ? wg * 8192 : T0), vb = kb + (h ? 8192 : 16384);
              norm_group(4 + h, 1.f, t, nrm);
              load_cs(2 + h);
#pragma unroll
              for (int m = 0; m < 2; m++) {
                const uint32_t r = row0 + m * 64 + g, ad = vb + r * 64 + ((qd ^ ((r >> 1) & 3)) << 4);
                sts128(ad, t[m][0], t[m][2], t[m][4], t[m][6]); sts128(ad + 512, t[m][1], t[m][3], t[m][5], t[m][7]);
              }
              norm_half(2 + h, 1.f, t, nrm, h);
#pragma unroll
              for (int i = 0; i < 4; i++) {
                const uint32_t r = row0 + (i >> 1) * 64 + srow;
                stsm4(kb + r * 64 + (((2 * (i & 1) + (lane >> 4)) ^ ((r >> 1) & 3)) << 4), t[i >> 1][4 * (i & 1)], t[i >> 1][4 * (i & 1) + 1], t[i >> 1][4 * (i & 1) + 2], t[i >> 1][4 * (i & 1) + 3]);
              }
              if (h == 1) { const float kn = max_norm(nrm); if (lane == 0) g_kn[((l >> 1) * 128 + bn * 8 + bm) * 16 + 8 + wg * 4 + w] = kn; }
              fence_async_smem();
              bar_arrive(NB_KV + 12 * h, 288);
              if (h == 0) {
                bar_arrive(wg ? NB_HALO : NB_DONE, 160);
              }
              if (h == 0) { const float kn = max_norm(nrm); if (lane == 0) g_kn[((l >> 1) * 128 + bn * 8 + bm) * 16 + wg * 4 + w] = kn; }
              norm_half(h, QSCALE, q[h], nrm, h ? -1 : 5);
#pragma unroll
              for (int i = 0; i < 4 * h; i++) sts128(sb + QPARK + 24576 - wg * 8192 + (w * 32 + lane) * 16 + i * 2048, q[h][i >> 1][4 * (i & 1)], q[h][i >> 1][4 * (i & 1) + 1], q[h][i >> 1][4 * (i & 1) + 2], q[h][i >> 1][4 * (i & 1) + 3]);
              qn[h] = max_norm(nrm);
            }
          }
          constexpr uint64_t VSTEP = 64 - (64ull << 16);
          uint32_t cq[4];
          const uint32_t &c_852 = cq[0], &c_lsb = cq[1], &c_half = cq[2];
          float o[2][20], S[2][32];
          uint32_t H[2][16], P0[4] = {}, P1[4] = {};
#pragma unroll
          for (int m = 0; m < 2; m++) {
#pragma unroll
            for (int i = 0; i < 20; i++) o[m][i] = 0.f;
            fence_regs(o[m]);
          }
          auto qkf = [&](int b, int ks, uint64_t d) { wg_n64_rs_nb_f16_f32(S[b], q[0][0][4 * ks], q[0][0][4 * ks + 1], q[0][0][4 * ks + 2], q[0][0][4 * ks + 3], d + 2 * ks, ks ? 1 : zero); };
          auto qkh = [&](int b, int ks, uint64_t d) { wg_n64_rs_nb_f16_f16(H[b], q[0][1][4 * ks], q[0][1][4 * ks + 1], q[0][1][4 * ks + 2], q[0][1][4 * ks + 3], d + 2 * ks, ks ? 1 : zero); };
          auto pv0 = [&](uint64_t d) { wgmma_m64n40k16_rs_tb(o[0], P0[0], P0[1], P0[2], P0[3], d, 1); };
          auto pv1 = [&](uint64_t d) { wgmma_m64n40k16_rs_tb(o[1], P1[0], P1[1], P1[2], P1[3], d, 1); };
          float e[4] = {};
          auto finish = [&](int h) {
            const float* s = &S[(h >> 2) & 1][8 * (h & 3)];
            const uint32_t* u = &H[(h >> 2) & 1][4 * (h & 3)];
            const float z0 = exp2_fix(s[6]), z1 = exp2_fix(s[7]);
            P0[0] = pack2v(e[0], e[1]);
            P1[0] = exp2_h2(u[0], c_852);
            P0[1] = pack2v(e[2], e[3]);
            P1[1] = exp2_h2(u[1], c_852);
            const uint32_t B = exp2_base(z0, z1), E = and_or<0x7F807F80u>(B, c_lsb);
            P1[3] = exp2_h2(u[3], c_852);
            P0[3] = fma_bf2(B, and_or<0x807F807Fu>(B, c_half), E);
            const float e4 = ex2v(s[4]), e5 = ex2v(s[5]);
            P1[2] = exp2_h2(u[2], c_852);
            P0[2] = pack2v(e4, e5);
          };
          auto start = [&](int h) {
            const float* s = &S[(h >> 2) & 1][8 * (h & 3)];
            e[2] = ex2v(s[2]); e[1] = ex2v(s[1]); e[0] = ex2v(s[0]); e[3] = ex2v(s[3]);
          };
          uint64_t kd = prm.kv[0].kd;
          mbar_wait(sb + B_TF, 0);
          lds128(sb + ROWST + 16 + (lane_id() & zero), cq);
#pragma unroll
          for (int i = 0; i < 4; i++) sts128(sb + QPARK + (wg * 128 + w * 32 + lane_id()) * 16 + i * 4096, q[0][i >> 1][4 * (i & 1)], q[0][i >> 1][4 * (i & 1) + 1], q[0][i >> 1][4 * (i & 1) + 2], q[0][i >> 1][4 * (i & 1) + 3]);
          wg_fence();
#pragma unroll
          for (int b = 0; b < 2; b++) {
            wg_n64_rs_nb_f16_f32_z(S[b], q[0][0][0], q[0][0][1], q[0][0][2], q[0][0][3], kd + 256 * b, 0);
            wg_n64_rs_nb_f16_f16_z(H[b], q[0][1][0], q[0][1][1], q[0][1][2], q[0][1][3], kd + 256 * b, 0);
            if (b == 0) { qkf(0, 1, kd); qkh(0, 1, kd); }
            wg_commit();
          }
          wg_wait<1>(); fence_regs(S[0]); fence_regs(H[0]);
          start(0); finish(0); start(1);
          wg_wait<0>();
          int redo = 0;
#pragma unroll 1
          for (int pass = 0, j = 1; pass < 2; pass++) {
#pragma unroll 1
           do {
            const uint64_t vd = prm.kv[j & 3].vd;
            bool go = false;
#pragma unroll
            for (int h = 2; h < 18; h++) {
              const int px = (h >> 2) + 1, c = h & 3;
              wg_fence();
              if (h == 13) kd = prm.kv[j & 3].kd;
              const uint64_t kx = kd + (px & 3) * 256, vx = vd + (h - 2) * VSTEP;
              if (h == 2) { qkh(1, 0, kx); qkf(1, 0, kx); pv0(vx); pv1(vx); qkh(1, 1, kx); qkf(1, 1, kx); }
              else if ((c == 1 || c == 2) && h < 17) { qkh(px & 1, c - 1, kx); pv1(vx); qkf(px & 1, c - 1, kx); pv0(vx); }
              else { pv0(vx); pv1(vx); }
              wg_commit();
              if (h == 3) e_arrive_if(sb + B_TE + 8 * ((j + 2) & 3), j > 1);
              if (h == 11) go = mbar_test(sb + B_TF + 8 * (j & 3), (j >> 2) & 1) && j != 8;
              finish(h - 1); start(h);
              if (h != 12 && h != 17) sched_fence();
              if (h == 12 && !go) {
                if (j == 16) {
#pragma unroll
                  for (int u = 13; u < 18; u++) {
                    wg_fence(); pv0(vd + (u - 2) * VSTEP); pv1(vd + (u - 2) * VSTEP); wg_commit();
                    if (u < 17) finish(u - 1);
                    if (u < 16) { start(u); sched_fence(); }
                    if (u & 1) { if (u == 17) wg_wait<0>(); else wg_wait<1>(); }
                  }
                  e_arrive(sb + B_TE + 24);
                  goto head_done;
                }
                mbar_wait(sb + B_TF + 8 * (j & 3), (j >> 2) & 1);
                if (j == 8) {
#pragma unroll
                  for (int i = 0; i < 4; i++) lds128(sb + QPARK + 24576 - wg * 8192 + (w * 32 + lane_id()) * 16 + i * 2048, &q[0][i >> 1][4 * (i & 1)]);
                }
              }
              if (h == 17) wg_wait<0>(); else if (h & 1) wg_wait<1>();
              if (c == 3) { fence_regs(S[px & 1]); fence_regs(H[px & 1]); }
            }
           } while (j++ & 7);
           head_done:
            fence_regs(o[0]); fence_regs(o[1]);
            uint32_t pk[2][8];
            {
              IDS();
              bf16* op = g_os + (size_t)(bm * 256 + row0 + (lane >> 2)) * 1024 + pass * 512 + bn * 32 + (lane & 3) * 8;
#pragma unroll
              for (int i = 0; i < 4; i++) {
                const float* a = &o[i >> 1][2 * (i & 1)];
                const float inv = rcp(a[16]);
                uint32_t* u = &pk[i >> 1][4 * (i & 1)];
#pragma unroll
                for (int k = 0; k < 4; k++) u[k] = pack2(a[4 * k] * inv, a[4 * k + 1] * inv);
                *(uint4*)(op + ((i >> 1) * 64 + (i & 1) * 8) * 1024) = make_uint4(u[0], u[1], u[2], u[3]);
              }
            }
            sched_fence();
            if (pass == 0) bar_sync(NB_KN + wg, 160);
            const float kmax = *(volatile float*)(smem + ROWST + 4 * pass);
            const bool wide = !(qn[0] <= 1.6e7f) | !(kmax <= 1.6e7f) | !(qn[0] * kmax <= 112.f * 112.f);
            int badm = 0;
#pragma unroll
            for (int m = 0; m < 2; m++) {
              uint32_t chk[2] = {0u, 0u};
#pragma unroll
              for (int i = 0; i < 8; i++) asm("fma.rn.bf16x2 %0, %1, %2, %0;" : "+r"(chk[i & 1]) : "r"(pk[m][i]), "r"(0u));
              const bool bad = wide | !(fminf(o[m][16], o[m][18]) >= 9.3e-10f) | !(o[m][16] + o[m][18] <= 1e36f) | (((chk[0] | chk[1]) & 0x7FFF7FFFu) != 0);
              badm |= __any_sync(~0u, bad) << m;
            }
            if (!badm) bar_arrive(NB_SIG + 2 * pass + wg, 160 + 32 * (pass & wg));
            qn[0] = qn[1];
#pragma unroll
            for (int m = 0; m < 2; m++) {
#pragma unroll
              for (int i = 0; i < 20; i++) o[m][i] = 0.f;
              fence_regs(o[m]);
            }
            if (badm) {
              redo |= badm << 2 * pass;
              const int tx = wg * 128 + w * 32 + lane_id();
              uint4* p = g_qsave + (block_id() * 256 + tx) * 8 + pass * 4;
#pragma unroll
              for (int i = 0; i < 4; i++) {
                uint32_t u[4] = {q[0][i >> 1][4 * (i & 1)], q[0][i >> 1][4 * (i & 1) + 1], q[0][i >> 1][4 * (i & 1) + 2], q[0][i >> 1][4 * (i & 1) + 3]};
                if (pass == 0) lds128(sb + QPARK + tx * 16 + i * 4096, u);
                p[i] = make_uint4(u[0], u[1], u[2], u[3]);
              }
            }
          }
          if (redo) attn_redo(redo, l, cta_id(), wg, w, ep1);
        }
      }
      {
        float acc[64];
        {
          const uint64_t da = l & 1 ? prm.xd + ((pslot_a(0, 1) + wg * 8192) >> 4) : prm.kv[0].kd + ((pslot_a(0, 0) - T0 + wg * 4096) >> 4);
          const uint64_t d2 = da + (l & 1 ? 4 : 512), db = prm.wd + (pslot_b(0) >> 4) - 2048;
          mbar_wait(sb + B_PF, l & 1);
          wg_fence();
          wgmma_m64n128k16_ss_tb_z(acc, da, db, 0);
#pragma unroll
          for (int k = 1; k < 4; k++) wgmma_m64n128k16_ss_tb(acc, (k & 2 ? d2 : da) + (k & 1) * 2, db + k * 128, 1);
          wg_commit();
        }
        uint32_t s = 1, lap = 0;
#pragma unroll 1
        for (int kt = 1; kt < 14; kt++) {
          mbar_wait(sb + B_PF + 8 * s, ((s < 4 ? l : 0) + lap) & 1);
          const uint64_t da = mkdesc(sb + pslot_a(s, l) + wg * 8192, 16, 1024, 1), db = mkdesc(sb + pslot_b(s), 8192, 1024, 1);
          wg_fence();
#pragma unroll
          for (int k = 0; k < 4; k++) wgmma_m64n128k16_ss_tb(acc, da + k * 2, db + k * 128, 1);
          wg_commit();
          wg_wait<1>();
          if (w == 0) e_arrive_both(sb + B_PE + 8 * (s ? s - 1 : 5));
          if (++s == 6) { s = 0; lap++; }
        }
        if (wg) {
          wg_wait<0>();
          if (w == 0) e_arrive_both(sb + B_PE + 8);
#pragma unroll
          for (int t = 2; t < 4; t++) mbar_wait(sb + B_PF + 8 * t, l & 1);
          bar_sync(NB_ST, 256);
        }
#pragma unroll
        for (int t = 2; t < 4; t++) {
          if (!wg) mbar_wait(sb + B_PF + 8 * t, l & 1);
          const uint64_t da = prm.xd + ((pslot_a(t, l) + wg * 8192) >> 4), db = prm.wd + (pslot_b(t) >> 4) - 2048;
          wg_fence();
#pragma unroll
          for (int k = 0; k < 4; k++) wgmma_m64n128k16_ss_tb(acc, da + k * 2, db + k * 128, 1);
          wg_commit();
        }
        if (!wg) {
          bar_arrive(NB_ST, 256);
          wg_wait<2>();
          if (w == 0) e_arrive_both(sb + B_PE + 8);
        }
        IDS();
        const int g = lane >> 2, qd = lane & 3;
        const int r0 = wg * 64 + w * 16;
        const uint32_t r = r0 + (lane & 7) + ((lane >> 3) & 1) * 8;
        uint32_t x[8][4];
        mbar_wait(sb + B_RF, l & 1);
#pragma unroll
        for (int jj = 0; jj < 8; jj++) ldsm4(sb + RES + (jj >> 2) * 16384 + r * 128 + ((((2 * jj + (lane >> 4)) & 7) ^ (r & 7)) << 4), x[jj]);
        wg_wait<0>();
        fence_regs(acc);
        if (w == 0) { e_arrive_both(sb + B_PE + 16); e_arrive_both(sb + B_PE + 24); }
        const CUtensorMap* mo = &prm.m[l == 3 ? M_OUT : M_XST];
#pragma unroll
        for (int jj = 0; jj < 8; jj++) {
#pragma unroll
          for (int i = 0; i < 4; i++) x[jj][i] = add_bf16x2(x[jj][i], pack2(acc[8 * jj + 2 * i], acc[8 * jj + 2 * i + 1]));
          if (jj < 4) stsm4(sb + RES + r * 128 + ((((2 * jj + (lane >> 4)) & 7) ^ (r & 7)) << 4), x[jj][0], x[jj][1], x[jj][2], x[jj][3]);
          if (jj == 3) { fence_async_smem(); __syncwarp(); tma_st(mo, pn * 128, pm * 128 + r0, sb + RES + r0 * 128); bulk_commit(); sched_fence(); }
        }
        if (l == 3) {
#pragma unroll
          for (int jj = 4; jj < 8; jj++) stsm4(sb + RES + 16384 + r * 128 + ((((2 * jj + (lane >> 4)) & 7) ^ (r & 7)) << 4), x[jj][0], x[jj][1], x[jj][2], x[jj][3]);
          fence_async_smem(); __syncwarp();
          tma_st(mo, pn * 128 + 64, pm * 128 + r0, sb + RES + 16384 + r0 * 128);
          bulk_commit(); bulk_wait_n<0>();
        } else {
          bar_sync(NB_SC, 256);
#pragma unroll
          for (int jj = 0; jj < 8; jj++)
            stsm4(sb + (jj >> 2) * 2 * QSTG + po * 16384 + r * 128 + ((((2 * jj + (lane >> 4)) & 7) ^ (r & 7)) << 4), x[jj][0], x[jj][1], x[jj][2], x[jj][3]);
          bulk_wait_n<0>();
          bar_arrive(NB_X0, 320);
          float s1[4] = {0.f, 0.f, 0.f, 0.f}, sa[4] = {0.f, 0.f, 0.f, 0.f}, sc[4] = {0.f, 0.f, 0.f, 0.f};
#pragma unroll
          for (int jj = 0; jj < 8; jj++) {
            mma16816(s1, x[jj][0], x[jj][1], x[jj][2], x[jj][3], 0x3f803f80u, 0x3f803f80u);
            mma16816(sa, x[jj][0], x[jj][1], x[jj][2], x[jj][3], x[jj][0], x[jj][2]);
            mma16816(sc, x[jj][0], x[jj][1], x[jj][2], x[jj][3], x[jj][1], x[jj][3]);
          }
          fence_regs(s1); fence_regs(sa); fence_regs(sc);
          fence_async_smem();
          sched_fence();
          bar_arrive(NB_X, 320);
          if (qd == g >> 1) {
            float2* p = g_stats + pn * 2048 + pm * 128 + r0 + g;
            p[0] = make_float2(s1[0], g & 1 ? sa[1] : sa[0]);
            p[8] = make_float2(s1[2], g & 1 ? sc[3] : sc[2]);
          }
          bar_arrive(NB_KV, 288);
        }
      }
    }
  }
  asm volatile("barrier.cluster.arrive.relaxed.aligned;\nbarrier.cluster.wait.aligned;" ::: "memory");
}

typedef CUresult (*EncodeFn)(CUtensorMap*, CUtensorMapDataType, cuuint32_t, void*, const cuuint64_t*, const cuuint64_t*, const cuuint32_t*,
                             const cuuint32_t*, CUtensorMapInterleave, CUtensorMapSwizzle, CUtensorMapL2promotion, CUtensorMapFloatOOBfill);

static void make_map(EncodeFn fn, CUtensorMap* m, const void* ptr, int rank, const uint64_t* dims, const uint64_t* strides, const uint32_t* box, CUtensorMapSwizzle sw) {
  cuuint64_t d[5], st[4];
  cuuint32_t bx[5], es[5];
  for (int i = 0; i < rank; i++) { d[i] = dims[i]; bx[i] = box[i]; es[i] = 1; if (i) st[i - 1] = strides[i - 1] * 2; }
  fn(m, CU_TENSOR_MAP_DATA_TYPE_BFLOAT16, rank, (void*)ptr, d, st, bx, es, CU_TENSOR_MAP_INTERLEAVE_NONE, sw,
     CU_TENSOR_MAP_L2_PROMOTION_L2_128B, CU_TENSOR_MAP_FLOAT_OOB_FILL_NONE);
}
static void map2(EncodeFn fn, CUtensorMap* m, const void* ptr, uint64_t inner, uint64_t outer, uint32_t bi, uint32_t bo, CUtensorMapSwizzle sw) {
  const uint64_t d[2] = {inner, outer}, st[1] = {inner};
  const uint32_t bx[2] = {bi, bo};
  make_map(fn, m, ptr, 2, d, st, bx, sw);
}

extern "C" void kernel_launch(void* const* d_in, const int* in_sizes, int n_in, void* d_out, int out_size) {
  (void)in_sizes; (void)n_in; (void)out_size;
  static EncodeFn enc = nullptr;
  static void *xs, *os, *kk, *vv;
  static int sbase = 1024;
  if (!enc) {
    void* p = nullptr;
    cudaDriverEntryPointQueryResult qr;
    cudaGetDriverEntryPoint("cuTensorMapEncodeTiled", &p, cudaEnableDefault, &qr);
    enc = (EncodeFn)p;
    Scratch* sc = nullptr;
    cudaGetSymbolAddress((void**)&sc, g_s);
    xs = sc->xs; os = sc->os; kk = sc->k; vv = sc->v;
    int dev = 0;
    cudaGetDevice(&dev);
    cudaDeviceGetAttribute(&sbase, cudaDevAttrReservedSharedMemoryPerBlock, dev);
    cudaFuncSetAttribute(fused_kernel, cudaFuncAttributeMaxDynamicSharedMemorySize, SMEM_BYTES);
  }
  Params prm;
  const CUtensorMapSwizzle S128 = CU_TENSOR_MAP_SWIZZLE_128B, S64 = CU_TENSOR_MAP_SWIZZLE_64B;
  map2(enc, &prm.m[M_X0A], d_in[0], 1024, 2048, 64, 256, S128);
  map2(enc, &prm.m[M_XSA], xs, 1024, 2048, 64, 256, S128);
  for (int t = 0; t < 2; t++) {
    const uint64_t d3[3] = {1024, 1024, 3}, s3[2] = {3072, 1024};
    const uint32_t b3[3] = {64, 64, 3};
    make_map(enc, &prm.m[M_WQA + t], d_in[1 + 3 * t], 3, d3, s3, b3, S128);
    const uint64_t d5[5] = {64, 32, 2, 16, 16}, s5[4] = {1024, 32 * 1024, 64 * 1024, 64};
    const uint32_t b5[5] = {64, 32, 1, 2, 2};
    make_map(enc, &prm.m[M_WOA + t], d_in[2 + 3 * t], 5, d5, s5, b5, S128);
    const uint64_t dr[3] = {64, 2048, 16}, sr[2] = {1024, 64};
    const uint32_t br[3] = {64, 128, 2};
    make_map(enc, &prm.m[M_X0R + t], t ? xs : d_in[0], 3, dr, sr, br, S128);
  }
  map2(enc, &prm.m[M_OS], os, 1024, 2048, 64, 64, S128);
  map2(enc, &prm.m[M_OL], os, 1024, 2048, 32, 128, S64);
  map2(enc, &prm.m[M_K], kk, 32, 65536, 32, 128, S64);
  map2(enc, &prm.m[M_V], vv, 32, 65536, 32, 128, S64);
  map2(enc, &prm.m[M_XSO], xs, 1024, 2048, 64, 128, S128);
  map2(enc, &prm.m[M_X0H], d_in[0], 1024, 2048, 64, 128, S128);
  map2(enc, &prm.m[M_XST], xs, 1024, 2048, 64, 16, S128);
  map2(enc, &prm.m[M_OUT], d_out, 1024, 2048, 64, 16, S128);
  prm.x0 = (const bf16*)d_in[0];
  prm.wq[0] = (const bf16*)d_in[1]; prm.wq[1] = (const bf16*)d_in[4];
  prm.zero = 0;
  for (int i = 0; i < 128; i++) prm.map[i] = remap(i);
  {
    const uint64_t hi = 0x80000020ull << 32, k0 = sbase + T0, v0 = k0 + 16384, vstep = 64 - (64ull << 16);
    prm.wd = mkdesc(sbase + 32768, 8192, 1024, 1); prm.xd = mkdesc(sbase, 16, 1024, 1);
    for (int j = 0; j < 4; j++) {
      prm.kv[j].kd = (hi | 1u << 16 | k0 >> 4) + 2048 * ((j < 16 ? j : 15) & 3);
      prm.kv[j].vd = (hi | (uint64_t)(ONES - T0 - 16384) >> 4 << 16 | v0 >> 4) + 32 * vstep * ((j + 3) & 3);
    }
  }
  fused_kernel<<<128, 384, SMEM_BYTES>>>(prm);
}
```

```cpp
#include <cuda_runtime.h>
#include <cuda_bf16.h>
#include <cuda.h>
#include <stdint.h>

typedef __nv_bfloat16 bf16;

__device__ __forceinline__ void wgmma_m64n192k16_ss_tb(float (&d)[96], uint64_t da, uint64_t db, int scale_d) {
  asm volatile("{\n.reg .pred p;\nsetp.ne.b32 p, %98, 0;\n"
    "wgmma.mma_async.sync.aligned.m64n192k16.f32.bf16.bf16 "
    "{%0, %1, %2, %3, %4, %5, %6, %7, %8, %9, %10, %11, %12, %13, %14, %15, "
    "%16, %17, %18, %19, %20, %21, %22, %23, %24, %25, %26, %27, %28, %29, %30, %31, "
    "%32, %33, %34, %35, %36, %37, %38, %39, %40, %41, %42, %43, %44, %45, %46, %47, "
    "%48, %49, %50, %51, %52, %53, %54, %55, %56, %57, %58, %59, %60, %61, %62, %63, "
    "%64, %65, %66, %67, %68, %69, %70, %71, %72, %73, %74, %75, %76, %77, %78, %79, "
    "%80, %81, %82, %83, %84, %85, %86, %87, %88, %89, %90, %91, %92, %93, %94, %95}, "
    "%96, %97, p, 1, 1, 0, 1;\n}\n"
    : "+f"(d[0]), "+f"(d[1]), "+f"(d[2]), "+f"(d[3]), "+f"(d[4]), "+f"(d[5]), "+f"(d[6]), "+f"(d[7]),
      "+f"(d[8]), "+f"(d[9]), "+f"(d[10]), "+f"(d[11]), "+f"(d[12]), "+f"(d[13]), "+f"(d[14]), "+f"(d[15]),
      "+f"(d[16]), "+f"(d[17]), "+f"(d[18]), "+f"(d[19]), "+f"(d[20]), "+f"(d[21]), "+f"(d[22]), "+f"(d[23]),
      "+f"(d[24]), "+f"(d[25]), "+f"(d[26]), "+f"(d[27]), "+f"(d[28]), "+f"(d[29]), "+f"(d[30]), "+f"(d[31]),
      "+f"(d[32]), "+f"(d[33]), "+f"(d[34]), "+f"(d[35]), "+f"(d[36]), "+f"(d[37]), "+f"(d[38]), "+f"(d[39]),
      "+f"(d[40]), "+f"(d[41]), "+f"(d[42]), "+f"(d[43]), "+f"(d[44]), "+f"(d[45]), "+f"(d[46]), "+f"(d[47]),
      "+f"(d[48]), "+f"(d[49]), "+f"(d[50]), "+f"(d[51]), "+f"(d[52]), "+f"(d[53]), "+f"(d[54]), "+f"(d[55]),
      "+f"(d[56]), "+f"(d[57]), "+f"(d[58]), "+f"(d[59]), "+f"(d[60]), "+f"(d[61]), "+f"(d[62]), "+f"(d[63]),
      "+f"(d[64]), "+f"(d[65]), "+f"(d[66]), "+f"(d[67]), "+f"(d[68]), "+f"(d[69]), "+f"(d[70]), "+f"(d[71]),
      "+f"(d[72]), "+f"(d[73]), "+f"(d[74]), "+f"(d[75]), "+f"(d[76]), "+f"(d[77]), "+f"(d[78]), "+f"(d[79]),
      "+f"(d[80]), "+f"(d[81]), "+f"(d[82]), "+f"(d[83]), "+f"(d[84]), "+f"(d[85]), "+f"(d[86]), "+f"(d[87]),
      "+f"(d[88]), "+f"(d[89]), "+f"(d[90]), "+f"(d[91]), "+f"(d[92]), "+f"(d[93]), "+f"(d[94]), "+f"(d[95])
    : "l"(da), "l"(db), "r"(scale_d));
}

__device__ __forceinline__ void wgmma_m64n192k16_ss_tb_z(float (&d)[96], uint64_t da, uint64_t db, int scale_d) {
  asm volatile("{\n.reg .pred p;\nsetp.ne.b32 p, %98, 0;\n"
    "wgmma.mma_async.sync.aligned.m64n192k16.f32.bf16.bf16 "
    "{%0, %1, %2, %3, %4, %5, %6, %7, %8, %9, %10, %11, %12, %13, %14, %15, "
    "%16, %17, %18, %19, %20, %21, %22, %23, %24, %25, %26, %27, %28, %29, %30, %31, "
    "%32, %33, %34, %35, %36, %37, %38, %39, %40, %41, %42, %43, %44, %45, %46, %47, "
    "%48, %49, %50, %51, %52, %53, %54, %55, %56, %57, %58, %59, %60, %61, %62, %63, "
    "%64, %65, %66, %67, %68, %69, %70, %71, %72, %73, %74, %75, %76, %77, %78, %79, "
    "%80, %81, %82, %83, %84, %85, %86, %87, %88, %89, %90, %91, %92, %93, %94, %95}, "
    "%96, %97, p, 1, 1, 0, 1;\n}\n"
    : "=f"(d[0]), "=f"(d[1]), "=f"(d[2]), "=f"(d[3]), "=f"(d[4]), "=f"(d[5]), "=f"(d[6]), "=f"(d[7]),
      "=f"(d[8]), "=f"(d[9]), "=f"(d[10]), "=f"(d[11]), "=f"(d[12]), "=f"(d[13]), "=f"(d[14]), "=f"(d[15]),
      "=f"(d[16]), "=f"(d[17]), "=f"(d[18]), "=f"(d[19]), "=f"(d[20]), "=f"(d[21]), "=f"(d[22]), "=f"(d[23]),
      "=f"(d[24]), "=f"(d[25]), "=f"(d[26]), "=f"(d[27]), "=f"(d[28]), "=f"(d[29]), "=f"(d[30]), "=f"(d[31]),
      "=f"(d[32]), "=f"(d[33]), "=f"(d[34]), "=f"(d[35]), "=f"(d[36]), "=f"(d[37]), "=f"(d[38]), "=f"(d[39]),
      "=f"(d[40]), "=f"(d[41]), "=f"(d[42]), "=f"(d[43]), "=f"(d[44]), "=f"(d[45]), "=f"(d[46]), "=f"(d[47]),
      "=f"(d[48]), "=f"(d[49]), "=f"(d[50]), "=f"(d[51]), "=f"(d[52]), "=f"(d[53]), "=f"(d[54]), "=f"(d[55]),
      "=f"(d[56]), "=f"(d[57]), "=f"(d[58]), "=f"(d[59]), "=f"(d[60]), "=f"(d[61]), "=f"(d[62]), "=f"(d[63]),
      "=f"(d[64]), "=f"(d[65]), "=f"(d[66]), "=f"(d[67]), "=f"(d[68]), "=f"(d[69]), "=f"(d[70]), "=f"(d[71]),
      "=f"(d[72]), "=f"(d[73]), "=f"(d[74]), "=f"(d[75]), "=f"(d[76]), "=f"(d[77]), "=f"(d[78]), "=f"(d[79]),
      "=f"(d[80]), "=f"(d[81]), "=f"(d[82]), "=f"(d[83]), "=f"(d[84]), "=f"(d[85]), "=f"(d[86]), "=f"(d[87]),
      "=f"(d[88]), "=f"(d[89]), "=f"(d[90]), "=f"(d[91]), "=f"(d[92]), "=f"(d[93]), "=f"(d[94]), "=f"(d[95])
    : "l"(da), "l"(db), "r"(scale_d));
}

__device__ __forceinline__ void wgmma_m64n128k16_ss_tb(float (&d)[64], uint64_t da, uint64_t db, int scale_d) {
  asm volatile("{\n.reg .pred p;\nsetp.ne.b32 p, %66, 0;\n"
    "wgmma.mma_async.sync.aligned.m64n128k16.f32.bf16.bf16 "
    "{%0, %1, %2, %3, %4, %5, %6, %7, %8, %9, %10, %11, %12, %13, %14, %15, "
    "%16, %17, %18, %19, %20, %21, %22, %23, %24, %25, %26, %27, %28, %29, %30, %31, "
    "%32, %33, %34, %35, %36, %37, %38, %39, %40, %41, %42, %43, %44, %45, %46, %47, "
    "%48, %49, %50, %51, %52, %53, %54, %55, %56, %57, %58, %59, %60, %61, %62, %63}, "
    "%64, %65, p, 1, 1, 0, 1;\n}\n"
    : "+f"(d[0]), "+f"(d[1]), "+f"(d[2]), "+f"(d[3]), "+f"(d[4]), "+f"(d[5]), "+f"(d[6]), "+f"(d[7]),
      "+f"(d[8]), "+f"(d[9]), "+f"(d[10]), "+f"(d[11]), "+f"(d[12]), "+f"(d[13]), "+f"(d[14]), "+f"(d[15]),
      "+f"(d[16]), "+f"(d[17]), "+f"(d[18]), "+f"(d[19]), "+f"(d[20]), "+f"(d[21]), "+f"(d[22]), "+f"(d[23]),
      "+f"(d[24]), "+f"(d[25]), "+f"(d[26]), "+f"(d[27]), "+f"(d[28]), "+f"(d[29]), "+f"(d[30]), "+f"(d[31]),
      "+f"(d[32]), "+f"(d[33]), "+f"(d[34]), "+f"(d[35]), "+f"(d[36]), "+f"(d[37]), "+f"(d[38]), "+f"(d[39]),
      "+f"(d[40]), "+f"(d[41]), "+f"(d[42]), "+f"(d[43]), "+f"(d[44]), "+f"(d[45]), "+f"(d[46]), "+f"(d[47]),
      "+f"(d[48]), "+f"(d[49]), "+f"(d[50]), "+f"(d[51]), "+f"(d[52]), "+f"(d[53]), "+f"(d[54]), "+f"(d[55]),
      "+f"(d[56]), "+f"(d[57]), "+f"(d[58]), "+f"(d[59]), "+f"(d[60]), "+f"(d[61]), "+f"(d[62]), "+f"(d[63])
    : "l"(da), "l"(db), "r"(scale_d));
}

__device__ __forceinline__ void wgmma_m64n128k16_ss_tb_z(float (&d)[64], uint64_t da, uint64_t db, int scale_d) {
  asm volatile("{\n.reg .pred p;\nsetp.ne.b32 p, %66, 0;\n"
    "wgmma.mma_async.sync.aligned.m64n128k16.f32.bf16.bf16 "
    "{%0, %1, %2, %3, %4, %5, %6, %7, %8, %9, %10, %11, %12, %13, %14, %15, "
    "%16, %17, %18, %19, %20, %21, %22, %23, %24, %25, %26, %27, %28, %29, %30, %31, "
    "%32, %33, %34, %35, %36, %37, %38, %39, %40, %41, %42, %43, %44, %45, %46, %47, "
    "%48, %49, %50, %51, %52, %53, %54, %55, %56, %57, %58, %59, %60, %61, %62, %63}, "
    "%64, %65, p, 1, 1, 0, 1;\n}\n"
    : "=f"(d[0]), "=f"(d[1]), "=f"(d[2]), "=f"(d[3]), "=f"(d[4]), "=f"(d[5]), "=f"(d[6]), "=f"(d[7]),
      "=f"(d[8]), "=f"(d[9]), "=f"(d[10]), "=f"(d[11]), "=f"(d[12]), "=f"(d[13]), "=f"(d[14]), "=f"(d[15]),
      "=f"(d[16]), "=f"(d[17]), "=f"(d[18]), "=f"(d[19]), "=f"(d[20]), "=f"(d[21]), "=f"(d[22]), "=f"(d[23]),
      "=f"(d[24]), "=f"(d[25]), "=f"(d[26]), "=f"(d[27]), "=f"(d[28]), "=f"(d[29]), "=f"(d[30]), "=f"(d[31]),
      "=f"(d[32]), "=f"(d[33]), "=f"(d[34]), "=f"(d[35]), "=f"(d[36]), "=f"(d[37]), "=f"(d[38]), "=f"(d[39]),
      "=f"(d[40]), "=f"(d[41]), "=f"(d[42]), "=f"(d[43]), "=f"(d[44]), "=f"(d[45]), "=f"(d[46]), "=f"(d[47]),
      "=f"(d[48]), "=f"(d[49]), "=f"(d[50]), "=f"(d[51]), "=f"(d[52]), "=f"(d[53]), "=f"(d[54]), "=f"(d[55]),
      "=f"(d[56]), "=f"(d[57]), "=f"(d[58]), "=f"(d[59]), "=f"(d[60]), "=f"(d[61]), "=f"(d[62]), "=f"(d[63])
    : "l"(da), "l"(db), "r"(scale_d));
}

__device__ __forceinline__ void wgmma_m64n40k16_rs_tb(float (&d)[20], uint32_t a0, uint32_t a1, uint32_t a2, uint32_t a3, uint64_t db, int scale_d) {
  asm volatile("{\n.reg .pred p;\nsetp.ne.b32 p, %25, 0;\n"
    "wgmma.mma_async.sync.aligned.m64n40k16.f32.bf16.bf16 "
    "{%0, %1, %2, %3, %4, %5, %6, %7, %8, %9, %10, %11, %12, %13, %14, %15, "
    "%16, %17, %18, %19}, "
    "{%20, %21, %22, %23}, %24, p, 1, 1, 1;\n}\n"
    : "+f"(d[0]), "+f"(d[1]), "+f"(d[2]), "+f"(d[3]), "+f"(d[4]), "+f"(d[5]), "+f"(d[6]), "+f"(d[7]),
      "+f"(d[8]), "+f"(d[9]), "+f"(d[10]), "+f"(d[11]), "+f"(d[12]), "+f"(d[13]), "+f"(d[14]), "+f"(d[15]),
      "+f"(d[16]), "+f"(d[17]), "+f"(d[18]), "+f"(d[19])
    : "r"(a0), "r"(a1), "r"(a2), "r"(a3), "l"(db), "r"(scale_d));
}

__device__ __forceinline__ void wg_n64_rs_nb_f16_f32(float (&d)[32], uint32_t a0, uint32_t a1, uint32_t a2, uint32_t a3, uint64_t db, int scale_d) {
  asm volatile("{\n.reg .pred p;\nsetp.ne.b32 p, %37, 0;\n"
    "wgmma.mma_async.sync.aligned.m64n64k16.f32.f16.f16 "
    "{%0, %1, %2, %3, %4, %5, %6, %7, %8, %9, %10, %11, %12, %13, %14, %15, "
    "%16, %17, %18, %19, %20, %21, %22, %23, %24, %25, %26, %27, %28, %29, %30, %31}, "
    "{%32, %33, %34, %35}, %36, p, 1, 1, 0;\n}\n"
    : "+f"(d[0]), "+f"(d[1]), "+f"(d[2]), "+f"(d[3]), "+f"(d[4]), "+f"(d[5]), "+f"(d[6]), "+f"(d[7]),
      "+f"(d[8]), "+f"(d[9]), "+f"(d[10]), "+f"(d[11]), "+f"(d[12]), "+f"(d[13]), "+f"(d[14]), "+f"(d[15]),
      "+f"(d[16]), "+f"(d[17]), "+f"(d[18]), "+f"(d[19]), "+f"(d[20]), "+f"(d[21]), "+f"(d[22]), "+f"(d[23]),
      "+f"(d[24]), "+f"(d[25]), "+f"(d[26]), "+f"(d[27]), "+f"(d[28]), "+f"(d[29]), "+f"(d[30]), "+f"(d[31])
    : "r"(a0), "r"(a1), "r"(a2), "r"(a3), "l"(db), "r"(scale_d));
}

__device__ __forceinline__ void wg_n64_rs_nb_f16_f16(uint32_t (&d)[16], uint32_t a0, uint32_t a1, uint32_t a2, uint32_t a3, uint64_t db, int scale_d) {
  asm volatile("{\n.reg .pred p;\nsetp.ne.b32 p, %21, 0;\n"
    "wgmma.mma_async.sync.aligned.m64n64k16.f16.f16.f16 "
    "{%0, %1, %2, %3, %4, %5, %6, %7, %8, %9, %10, %11, %12, %13, %14, %15}, "
    "{%16, %17, %18, %19}, %20, p, 1, 1, 0;\n}\n"
    : "+r"(d[0]), "+r"(d[1]), "+r"(d[2]), "+r"(d[3]), "+r"(d[4]), "+r"(d[5]), "+r"(d[6]), "+r"(d[7]),
      "+r"(d[8]), "+r"(d[9]), "+r"(d[10]), "+r"(d[11]), "+r"(d[12]), "+r"(d[13]), "+r"(d[14]), "+r"(d[15])
    : "r"(a0), "r"(a1), "r"(a2), "r"(a3), "l"(db), "r"(scale_d));
}

__device__ __forceinline__ void wg_n64_rs_nb_f16_f32_z(float (&d)[32], uint32_t a0, uint32_t a1, uint32_t a2, uint32_t a3, uint64_t db, int scale_d) {
  asm volatile("{\n.reg .pred p;\nsetp.ne.b32 p, %37, 0;\n"
    "wgmma.mma_async.sync.aligned.m64n64k16.f32.f16.f16 "
    "{%0, %1, %2, %3, %4, %5, %6, %7, %8, %9, %10, %11, %12, %13, %14, %15, "
    "%16, %17, %18, %19, %20, %21, %22, %23, %24, %25, %26, %27, %28, %29, %30, %31}, "
    "{%32, %33, %34, %35}, %36, p, 1, 1, 0;\n}\n"
    : "=f"(d[0]), "=f"(d[1]), "=f"(d[2]), "=f"(d[3]), "=f"(d[4]), "=f"(d[5]), "=f"(d[6]), "=f"(d[7]),
      "=f"(d[8]), "=f"(d[9]), "=f"(d[10]), "=f"(d[11]), "=f"(d[12]), "=f"(d[13]), "=f"(d[14]), "=f"(d[15]),
      "=f"(d[16]), "=f"(d[17]), "=f"(d[18]), "=f"(d[19]), "=f"(d[20]), "=f"(d[21]), "=f"(d[22]), "=f"(d[23]),
      "=f"(d[24]), "=f"(d[25]), "=f"(d[26]), "=f"(d[27]), "=f"(d[28]), "=f"(d[29]), "=f"(d[30]), "=f"(d[31])
    : "r"(a0), "r"(a1), "r"(a2), "r"(a3), "l"(db), "r"(scale_d));
}

__device__ __forceinline__ void wg_n64_rs_nb_f16_f16_z(uint32_t (&d)[16], uint32_t a0, uint32_t a1, uint32_t a2, uint32_t a3, uint64_t db, int scale_d) {
  asm volatile("{\n.reg .pred p;\nsetp.ne.b32 p, %21, 0;\n"
    "wgmma.mma_async.sync.aligned.m64n64k16.f16.f16.f16 "
    "{%0, %1, %2, %3, %4, %5, %6, %7, %8, %9, %10, %11, %12, %13, %14, %15}, "
    "{%16, %17, %18, %19}, %20, p, 1, 1, 0;\n}\n"
    : "=r"(d[0]), "=r"(d[1]), "=r"(d[2]), "=r"(d[3]), "=r"(d[4]), "=r"(d[5]), "=r"(d[6]), "=r"(d[7]),
      "=r"(d[8]), "=r"(d[9]), "=r"(d[10]), "=r"(d[11]), "=r"(d[12]), "=r"(d[13]), "=r"(d[14]), "=r"(d[15])
    : "r"(a0), "r"(a1), "r"(a2), "r"(a3), "l"(db), "r"(scale_d));
}

#define DEVINL __device__ __forceinline__
DEVINL void wg_fence() { asm volatile("wgmma.fence.sync.aligned;" ::: "memory"); }
DEVINL void wg_commit() { asm volatile("wgmma.commit_group.sync.aligned;" ::: "memory"); }
template <int N> DEVINL void wg_wait() { asm volatile("wgmma.wait_group.sync.aligned %0;" ::"n"(N) : "memory"); }
__host__ DEVINL uint64_t mkdesc(uint32_t addr, uint32_t lbo, uint32_t sbo, int sw) {
  return (uint64_t)((addr & 0x3FFFF) >> 4) | ((uint64_t)(lbo >> 4) << 16) | ((uint64_t)(sbo >> 4) << 32) | ((uint64_t)sw << 62);
}
DEVINL bool mbar_try(uint32_t bar, uint32_t parity) {
  uint32_t ok;
  asm volatile("{\n.reg .pred p;\nmbarrier.try_wait.parity.shared::cta.b64 p, [%1], %2;\nselp.u32 %0, 1, 0, p;\n}" : "=r"(ok) : "r"(bar), "r"(parity) : "memory");
  return ok;
}
DEVINL bool mbar_test(uint32_t bar, uint32_t parity) {
  uint32_t ok;
  asm volatile("{\n.reg .pred p;\nmbarrier.test_wait.parity.shared::cta.b64 p, [%1], %2;\nselp.u32 %0, 1, 0, p;\n}" : "=r"(ok) : "r"(bar), "r"(parity) : "memory");
  return ok;
}
DEVINL void mbar_wait(uint32_t bar, uint32_t parity) {
#pragma unroll 1
  for (uint32_t n = 0; n < 100000u; n++) if (mbar_try(bar, parity)) break;
}
#define EL(txt) "{\n.reg .pred pe;\nelect.sync _|pe, 0xffffffff;\n@pe " txt "\n}"
DEVINL void e_expect_tx(uint32_t bar, uint32_t bytes) { asm volatile(EL("mbarrier.arrive.expect_tx.shared::cta.b64 _, [%0], %1;") ::"r"(bar), "r"(bytes) : "memory"); }
DEVINL void e_arrive(uint32_t bar) { asm volatile(EL("mbarrier.arrive.shared::cta.b64 _, [%0];") ::"r"(bar) : "memory"); }
DEVINL void e_arrive_if(uint32_t bar, int c) {
  asm volatile("{\n.reg .pred pe;\nelect.sync _|pe, 0xffffffff;\nsetp.ne.and.b32 pe, %1, 0, pe;\n@pe mbarrier.arrive.shared::cta.b64 _, [%0];\n}" ::"r"(bar), "r"(c) : "memory");
}
DEVINL void e_red(uint32_t* p) { asm volatile(EL("red.release.gpu.global.add.u32 [%0], 1;") ::"l"(p) : "memory"); }
DEVINL void e_red_relaxed(uint32_t* p) { asm volatile(EL("red.relaxed.gpu.global.add.u32 [%0], 1;") ::"l"(p) : "memory"); }
DEVINL void release_add(uint32_t* p, int on) {
  asm volatile("{\n.reg .pred q;\nsetp.ne.b32 q, %1, 0;\nfence.release.gpu;\n@q red.relaxed.gpu.global.add.u32 [%0], 1;\n}" ::"l"(p), "r"(on) : "memory");
}
#define PREPARED(p, on) do { asm volatile("" : "+l"(p), "+r"(on)); asm volatile("griddepcontrol.launch_dependents;" ::: "memory"); } while (0)
DEVINL void tma_ld(uint32_t dst, const CUtensorMap* m, int c0, int c1, uint32_t bar) {
  asm volatile(EL("cp.async.bulk.tensor.2d.shared::cluster.global.mbarrier::complete_tx::bytes [%0], [%1, {%3, %4}], [%2];")
               ::"r"(dst), "l"(m), "r"(bar), "r"(c0), "r"(c1) : "memory");
}
DEVINL void tma_ld3(uint32_t dst, const CUtensorMap* m, int c0, int c1, int c2, uint32_t bar) {
  asm volatile(EL("cp.async.bulk.tensor.3d.shared::cluster.global.mbarrier::complete_tx::bytes [%0], [%1, {%3, %4, %5}], [%2];")
               ::"r"(dst), "l"(m), "r"(bar), "r"(c0), "r"(c1), "r"(c2) : "memory");
}
DEVINL void tma_ld5(uint32_t dst, const CUtensorMap* m, int c2, int c3, int c4, uint32_t bar) {
  asm volatile(EL("cp.async.bulk.tensor.5d.shared::cluster.global.mbarrier::complete_tx::bytes [%0], [%1, {0, 0, %3, %4, %5}], [%2];")
               ::"r"(dst), "l"(m), "r"(bar), "r"(c2), "r"(c3), "r"(c4) : "memory");
}
DEVINL void tma_ld_mc(uint32_t dst, const CUtensorMap* m, int c0, int c1, uint32_t bar, uint16_t mask = 3) {
  asm volatile(EL("cp.async.bulk.tensor.2d.shared::cluster.global.mbarrier::complete_tx::bytes.multicast::cluster [%0], [%1, {%3, %4}], [%2], %5;")
               ::"r"(dst), "l"(m), "r"(bar), "r"(c0), "r"(c1), "h"(mask) : "memory");
}
DEVINL void e_arrive_both(uint32_t bar) {
  asm volatile("{\n.reg .pred pe;\n.reg .b32 r0, r1;\nelect.sync _|pe, 0xffffffff;\nmapa.shared::cluster.u32 r0, %0, 0;\nmapa.shared::cluster.u32 r1, %0, 1;\n"
               "@pe mbarrier.arrive.shared::cluster.b64 _, [r0];\n@pe mbarrier.arrive.shared::cluster.b64 _, [r1];\n}" ::"r"(bar) : "memory");
}
DEVINL void tma_st(const CUtensorMap* m, int c0, int c1, uint32_t src) {
  asm volatile(EL("cp.async.bulk.tensor.2d.global.shared::cta.bulk_group [%0, {%2, %3}], [%1];") ::"l"(m), "r"(src), "r"(c0), "r"(c1) : "memory");
}
DEVINL void bulk_commit() { asm volatile("cp.async.bulk.commit_group;" ::: "memory"); }
template <int N> DEVINL void bulk_wait_n() { asm volatile("cp.async.bulk.wait_group %0;\nbar.warp.sync 0xffffffff;" ::"n"(N) : "memory"); }
DEVINL void l2_prefetch(const void* g, uint32_t bytes) { asm volatile(EL("cp.async.bulk.prefetch.L2.global [%0], %1;") ::"l"(g), "r"(bytes) : "memory"); }
DEVINL void fence_async_smem() { asm volatile("fence.proxy.async.shared::cta;" ::: "memory"); }
DEVINL void fence_async_gl() { asm volatile("fence.proxy.async.global;" ::: "memory"); }
DEVINL void cluster_wait() { asm volatile("barrier.cluster.wait.aligned;" ::: "memory"); }
DEVINL void bar_sync(int id, int n) { asm volatile("bar.sync %0, %1;" ::"r"(id), "r"(n) : "memory"); }
DEVINL void bar_arrive(int id, int n) { asm volatile("bar.arrive %0, %1;" ::"r"(id), "r"(n) : "memory"); }
DEVINL uint32_t ld_acquire(const uint32_t* p) { uint32_t v; asm volatile("ld.acquire.gpu.global.u32 %0, [%1];" : "=r"(v) : "l"(p) : "memory"); return v; }
DEVINL void await_flag(int j, uint32_t& rdy, const uint32_t* p, uint32_t target) {
  if ((rdy >> j) & 1) return;
#pragma unroll 1
  for (uint32_t n = 0; n < 200000u && !((rdy >> j) & 1); n++) rdy = __ballot_sync(~0u, (int)(ld_acquire(p) - target) >= 0);
  asm volatile("fence.proxy.async.global;" ::: "memory");
}
DEVINL void poll_ge(const uint32_t* p, uint32_t target) {
#pragma unroll 1
  for (uint32_t n = 0; n < 200000u; n++) if (__all_sync(~0u, (int)(ld_acquire(p) - target) >= 0)) break;
}
DEVINL int lane_id() { int v; asm volatile("mov.u32 %0, %%laneid;" : "=r"(v)); return v; }
__host__ DEVINL int remap(int v) {
  const int c = v >> 1, u = c - 36, r = (u * 37) >> 8;
  const int L = c < 4 ? 32 + 8 * c : c < 36 ? c - 4 : 33 + u + r;
  return 2 * L + (v & 1);
}
DEVINL int block_id() { int v; asm volatile("mov.u32 %0, %%ctaid.x;" : "=r"(v)); return v; }
#define cta_id() prm.map[block_id()]
#define IDS() const int lane = lane_id(), b = cta_id(), bm = b >> 4, bn = b & 15, rank = b & 1, pm = 2 * bm + (bn >> 3), pn = bn & 7, po = pm & 1; \
  (void)lane; (void)bm; (void)bn; (void)rank; (void)pm; (void)pn; (void)po
DEVINL void st_tagged(uint4* p, uint32_t a, uint32_t b, uint32_t c, uint32_t tag) {
  asm volatile("{\n.reg .b64 u, v;\n.reg .b128 t;\nmov.b64 u, {%1, %2};\nmov.b64 v, {%3, %4};\nmov.b128 t, {u, v};\nst.relaxed.gpu.global.b128 [%0], t;\n}"
               ::"l"(p), "r"(a), "r"(b), "r"(c), "r"(tag) : "memory");
}
DEVINL uint32_t ld_tagged(const uint4* p, uint32_t* r) {
  uint32_t tag;
  asm volatile("{\n.reg .b64 u, v;\n.reg .b128 t;\nld.relaxed.gpu.global.b128 t, [%4];\nmov.b128 {u, v}, t;\nmov.b64 {%0, %1}, u;\nmov.b64 {%2, %3}, v;\n}"
               : "=r"(r[0]), "=r"(r[1]), "=r"(r[2]), "=r"(tag) : "l"(p) : "memory");
  return tag;
}
DEVINL float ex2(float x) { float y; asm("ex2.approx.ftz.f32 %0, %1;" : "=f"(y) : "f"(x)); return y; }
DEVINL float rcp(float x) { float y; asm("rcp.approx.ftz.f32 %0, %1;" : "=f"(y) : "f"(x)); return y; }
DEVINL uint32_t pack2(float lo, float hi) { uint32_t r; asm("cvt.rn.bf16x2.f32 %0, %1, %2;" : "=r"(r) : "f"(hi), "f"(lo)); return r; }
DEVINL uint32_t pack2h(float lo, float hi) { uint32_t r; asm("cvt.rz.f16x2.f32 %0, %1, %2;" : "=r"(r) : "f"(hi), "f"(lo)); return r; }
DEVINL uint32_t prmt0(uint32_t a, uint32_t sel) { uint32_t r; asm("prmt.b32 %0, %1, 0, %2;" : "=r"(r) : "r"(a), "r"(sel)); return r; }
DEVINL void stg128(const void* p, uint32_t a, uint32_t b, uint32_t c, uint32_t d) {
  asm volatile("st.global.v4.b32 [%0], {%1, %2, %3, %4};" ::"l"(p), "r"(a), "r"(b), "r"(c), "r"(d) : "memory");
}
DEVINL float bf_lo(uint32_t w) { return __uint_as_float(w << 16); }
DEVINL float bf_hi(uint32_t w) { return __uint_as_float(w & 0xFFFF0000u); }
DEVINL float bf_round(float x) { return bf_lo(pack2(x, 0.f)); }
DEVINL uint32_t add_bf16x2(uint32_t a, uint32_t b) { uint32_t r; asm("add.rn.bf16x2 %0, %1, %2;" : "=r"(r) : "r"(a), "r"(b)); return r; }
DEVINL void stsm4(uint32_t addr, uint32_t a, uint32_t b, uint32_t c, uint32_t d) {
  asm volatile("stmatrix.sync.aligned.m8n8.x4.shared.b16 [%0], {%1, %2, %3, %4};" ::"r"(addr), "r"(a), "r"(b), "r"(c), "r"(d) : "memory");
}
DEVINL void ldsm4(uint32_t addr, uint32_t (&r)[4]) {
  asm volatile("ldmatrix.sync.aligned.m8n8.x4.shared.b16 {%0, %1, %2, %3}, [%4];" : "=r"(r[0]), "=r"(r[1]), "=r"(r[2]), "=r"(r[3]) : "r"(addr) : "memory");
}
DEVINL void ldsm4t(uint32_t addr, uint32_t (&r)[4]) {
  asm volatile("ldmatrix.sync.aligned.m8n8.x4.trans.shared.b16 {%0, %1, %2, %3}, [%4];" : "=r"(r[0]), "=r"(r[1]), "=r"(r[2]), "=r"(r[3]) : "r"(addr) : "memory");
}
DEVINL void sts128(uint32_t addr, uint32_t a, uint32_t b, uint32_t c, uint32_t d) {
  asm volatile("st.shared.v4.b32 [%0], {%1, %2, %3, %4};" ::"r"(addr), "r"(a), "r"(b), "r"(c), "r"(d) : "memory");
}
DEVINL float2 lds64f(uint32_t addr) { float2 v; asm volatile("ld.shared.v2.f32 {%0, %1}, [%2];" : "=f"(v.x), "=f"(v.y) : "r"(addr) : "memory"); return v; }
DEVINL void mma16816(float (&d)[4], uint32_t a0, uint32_t a1, uint32_t a2, uint32_t a3, uint32_t b0, uint32_t b1) {
  asm("mma.sync.aligned.m16n8k16.row.col.f32.bf16.bf16.f32 {%0, %1, %2, %3}, {%4, %5, %6, %7}, {%8, %9}, {%0, %1, %2, %3};"
               : "+f"(d[0]), "+f"(d[1]), "+f"(d[2]), "+f"(d[3]) : "r"(a0), "r"(a1), "r"(a2), "r"(a3), "r"(b0), "r"(b1));
}
template <int N> DEVINL void fence_regs(float (&d)[N]) {
#pragma unroll
  for (int i = 0; i < N; i++) asm volatile("" : "+f"(d[i])::"memory");
}
template <int N> DEVINL void fence_regs(uint32_t (&d)[N]) {
#pragma unroll
  for (int i = 0; i < N; i++) asm volatile("" : "+r"(d[i])::"memory");
}
DEVINL void lds128(uint32_t addr, uint32_t* r) {
  asm volatile("ld.shared.v4.b32 {%0, %1, %2, %3}, [%4];" : "=r"(r[0]), "=r"(r[1]), "=r"(r[2]), "=r"(r[3]) : "r"(addr) : "memory");
}
DEVINL void sched_fence() { asm volatile("griddepcontrol.launch_dependents;" ::: "memory"); }

struct Scratch {
  bf16 k[32 * 2048 * 32];
  bf16 xs[2048 * 1024];
  bf16 os[2048 * 1024];
  bf16 v[32 * 2048 * 32];
  float kn[2 * 128 * 16];
  uint32_t cnt[256 * 32];
  float2 stats[8 * 2048];
  uint4 halo[128 * 12 * 32];
  float csp[2 * 16 * 8 * 192];
  uint4 qsave[128 * 256 * 8];
  uint32_t esc[4 * 65536 * 20];
};
__device__ __align__(1024) Scratch g_s;
#define g_k g_s.k
#define g_xs g_s.xs
#define g_os g_s.os
#define g_v g_s.v
#define g_kn g_s.kn
#define g_cnt g_s.cnt
#define g_stats g_s.stats
#define g_halo g_s.halo
#define g_csp g_s.csp
#define g_qsave g_s.qsave
#define g_esc g_s.esc
#define g_epoch g_s.cnt[255 * 32]

DEVINL uint32_t* cnt_x(int bm) { return g_cnt + bm * 32; }
DEVINL uint32_t* cnt_o(int l, int pm, int h) { return g_cnt + (32 + (l * 16 + pm) * 2 + h) * 32; }
DEVINL uint32_t* cnt_kv(int lb, int bn) { return g_cnt + (160 + lb * 16 + bn) * 32; }
DEVINL uint32_t* cnt_ad(int bn) { return g_cnt + (192 + bn) * 32; }
DEVINL uint32_t* cnt_cs(int t, int bn) { return g_cnt + (208 + t * 16 + bn) * 32; }

DEVINL int qord(int i, int l, int pn) {
  const int u = i < 10 ? i - 4 : i - 10;
  return l == 0 ? i : i < 4 ? ((2 * pn) ^ (2 * (i & 1))) + (i >> 1) : 2 * (u < (pn & 6) ? u : u + 2) + (i >= 10);
}
struct Params {
  CUtensorMap m[16];
  const bf16* x0;
  const bf16* wq[2];
  uint32_t zero;
  int map[128];
  uint64_t wd, xd;
  struct __align__(16) { uint64_t kd, vd; } kv[4];
};
enum { M_X0A = 0, M_XSA, M_WQA, M_WQB, M_WOA, M_WOB, M_OS, M_K, M_V, M_X0R, M_XSR, M_XSO, M_OUT, M_XST, M_X0H, M_OL, M_COUNT };

constexpr uint32_t QSTG = 57344;
constexpr uint32_t T0 = 65536, TSTG = 32768;
constexpr uint32_t ONES = 230400;
constexpr uint32_t PSTG = 32768, RES = 196608;
constexpr uint32_t KSC = 98304, VSC = 133120, HRS = 167936;
constexpr uint32_t ROWST = 229376, COLS = 231424, BARS = 232192, SMEM_BYTES = 232448;
constexpr uint32_t B_QF = BARS, B_QE = BARS + 32, B_TF = BARS + 64, B_TE = BARS + 96, B_PF = BARS + 128, B_PE = BARS + 176,
                   B_RF = BARS + 224, W_X = BARS + 232, B_QL = BARS + 240, B_PA = BARS + 248;
enum { NB_ST = 1, NB_KV = 2  , NB_DONE = 3, NB_SC = 4, NB_SIG = 5  , NB_KN = 9  , NB_X = 11, NB_HALO = 12  , NB_X0 = 15 };

DEVINL uint32_t pslot_b(uint32_t s) { return ((0x320415u >> (4 * s)) & 7) * 16384u; }
DEVINL uint32_t pslot_a(uint32_t s, int l) { return 98304u + ((((l & 1) ? 0x541230u : 0x041235u) >> (4 * s)) & 7) * 16384u; }

constexpr float QSCALE = 0.17677669529663687f * 1.4426950408889634f;
constexpr uint32_t QPARK = 32768;

DEVINL uint32_t exp2_h2(uint32_t s, uint32_t c852) {
  uint32_t r, t, w, m, d;
  asm volatile("{.reg .b64 t; add.rn.f16x2 %0, %1, %2; cvt.u64.u32 t, %0; cvt.u32.u64 %0, t;}" : "=r"(r) : "r"(s), "r"(0x65EA65EAu));
  asm volatile("fma.rn.f16x2 %0, %1, %2, %3;" : "=r"(t) : "r"(r), "r"(0xB880B880u), "r"(c852));
  asm volatile("fma.rn.f16x2 %0, %1, %2, %3;" : "=r"(w) : "r"(s), "r"(0x38803880u), "r"(t));
  asm volatile("fma.rn.f16x2 %0, %1, %1, %2;" : "=r"(m) : "r"(w), "r"(0x4A1F4A2Du));
  asm volatile("{.reg .b32 t; shf.l.clamp.b32 t, %2, %1, 7; add.u32 %0, t, %2;}" : "=r"(d) : "r"(r), "r"(m));
  return d;
}
DEVINL float exp2_fix(float s) { float z; asm volatile("add.rn.f32 %0, %1, 0f43BF34BC;" : "=f"(z) : "f"(s)); return z; }
DEVINL uint32_t exp2_base(float z0, float z1) { uint32_t B; asm volatile("prmt.b32 %0, %1, %2, 0x6521;" : "=r"(B) : "r"(__float_as_uint(z0)), "r"(__float_as_uint(z1))); return B; }
template <uint32_t MASK> DEVINL uint32_t and_or(uint32_t a, uint32_t c) { uint32_t r; asm volatile("lop3.b32 %0, %1, %3, %2, 0xEA;" : "=r"(r) : "r"(a), "r"(c), "n"(MASK)); return r; }
DEVINL uint32_t fma_bf2(uint32_t a, uint32_t b, uint32_t c) { uint32_t r; asm volatile("fma.rn.bf16x2 %0, %1, %2, %3;" : "=r"(r) : "r"(a), "r"(b), "r"(c)); return r; }
DEVINL float ex2v(float x) { float y; asm volatile("ex2.approx.ftz.f32 %0, %1;" : "=f"(y) : "f"(x)); return y; }
DEVINL uint32_t pack2v(float lo, float hi) { uint32_t r; asm volatile("cvt.rn.bf16x2.f32 %0, %1, %2;" : "=r"(r) : "f"(hi), "f"(lo)); return r; }
DEVINL void unesc(uint32_t (&u)[4], const uint32_t* esc, uint32_t tag) {
  const bool saved = __ldcg(esc + 16) == tag;
#pragma unroll
  for (int j = 0; j < 4; j++) {
    float lo, hi;
    asm("{.reg .f16 a, b; mov.b32 {a, b}, %2; cvt.f32.f16 %0, a; cvt.f32.f16 %1, b;}" : "=f"(lo), "=f"(hi) : "r"(u[j]));
    u[j] = saved ? __ldcg(esc + 4 * j) : pack2(lo, hi);
  }
}

DEVINL void attn_slow(const uint32_t (&q)[8], int head, const uint32_t* kesc, uint32_t tag, float (&res)[20], int lane) {
  const int g = lane >> 2, qd = lane & 3;
  const bf16* kb = g_k + (size_t)head * 2048 * 32;
  const bf16* vb = g_v + (size_t)head * 2048 * 32;
  float o[4][4], m0 = -INFINITY, m1 = -INFINITY, l0 = 0.f, l1 = 0.f;
#pragma unroll
  for (int j = 0; j < 4; j++) { o[j][0] = o[j][1] = o[j][2] = o[j][3] = 0.f; }
#pragma unroll 1
  for (int k0 = 0; k0 < 2048; k0 += 16) {
    float s[2][4];
#pragma unroll
    for (int nt = 0; nt < 2; nt++) {
      s[nt][0] = s[nt][1] = s[nt][2] = s[nt][3] = 0.f;
      const uint32_t* kp = (const uint32_t*)(kb + (size_t)(k0 + nt * 8 + g) * 32) + qd;
      uint32_t k[4] = {__ldcg(kp), __ldcg(kp + 4), __ldcg(kp + 8), __ldcg(kp + 12)};
      unesc(k, kesc + (k0 + nt * 8 + g) * 20 + qd, tag);
      __syncwarp();
      mma16816(s[nt], q[0], q[1], q[2], q[3], k[0], k[1]);
      mma16816(s[nt], q[4], q[5], q[6], q[7], k[2], k[3]);
    }
    float a0 = fmaxf(fmaxf(s[0][0], s[0][1]), fmaxf(s[1][0], s[1][1]));
    float a1 = fmaxf(fmaxf(s[0][2], s[0][3]), fmaxf(s[1][2], s[1][3]));
    a0 = fmaxf(a0, __shfl_xor_sync(~0u, a0, 1)); a0 = fmaxf(a0, __shfl_xor_sync(~0u, a0, 2));
    a1 = fmaxf(a1, __shfl_xor_sync(~0u, a1, 1)); a1 = fmaxf(a1, __shfl_xor_sync(~0u, a1, 2));
    const float n0 = fmaxf(m0, a0), n1 = fmaxf(m1, a1);
    const float c0 = (m0 == n0) ? 1.f : ex2(m0 - n0), c1 = (m1 == n1) ? 1.f : ex2(m1 - n1);
    m0 = n0; m1 = n1;
    const uint32_t p0 = pack2(ex2(s[0][0] - n0), ex2(s[0][1] - n0)), p1 = pack2(ex2(s[0][2] - n1), ex2(s[0][3] - n1));
    const uint32_t p2 = pack2(ex2(s[1][0] - n0), ex2(s[1][1] - n0)), p3 = pack2(ex2(s[1][2] - n1), ex2(s[1][3] - n1));
    l0 = l0 * c0 + bf_lo(p0) + bf_hi(p0) + bf_lo(p2) + bf_hi(p2);
    l1 = l1 * c1 + bf_lo(p1) + bf_hi(p1) + bf_lo(p3) + bf_hi(p3);
#pragma unroll
    for (int j = 0; j < 4; j++) {
      o[j][0] *= c0; o[j][1] *= c0; o[j][2] *= c1; o[j][3] *= c1;
      const unsigned short* vp = (const unsigned short*)(vb + (size_t)(k0 + 2 * qd) * 32 + j * 8 + g);
      const uint32_t b0 = (uint32_t)__ldcg(vp) | ((uint32_t)__ldcg(vp + 32) << 16);
      const uint32_t b1 = (uint32_t)__ldcg(vp + 256) | ((uint32_t)__ldcg(vp + 288) << 16);
      mma16816(o[j], p0, p1, p2, p3, b0, b1);
    }
  }
  l0 += __shfl_xor_sync(~0u, l0, 1); l0 += __shfl_xor_sync(~0u, l0, 2);
  l1 += __shfl_xor_sync(~0u, l1, 1); l1 += __shfl_xor_sync(~0u, l1, 2);
#pragma unroll
  for (int j = 0; j < 4; j++) { res[4 * j] = o[j][0]; res[4 * j + 1] = o[j][1]; res[4 * j + 2] = o[j][2]; res[4 * j + 3] = o[j][3]; }
  res[16] = l0; res[18] = l1;
}

__device__ __noinline__ void attn_redo(int redo, int l, int b, int wg, int w, uint32_t tag) {
  const int lane = lane_id();
#pragma unroll 1
  for (int t = 0; t < 4; t++) {
    const int h = t >> 1, head = 2 * (b & 15) + h, row = (b >> 4) * 256 + wg * 128 + (t & 1) * 64 + w * 16 + (lane >> 2);
    if ((redo >> t) & 1) {
      const uint32_t* esc = g_esc + (size_t)((l & 2) * 65536 + head * 2048) * 20;
      const uint32_t* qs = (const uint32_t*)(g_qsave + (block_id() * 256 + wg * 128 + w * 32 + lane) * 8 + 2 * t);
      uint32_t q[8]; float o[20];
#pragma unroll
      for (int i = 0; i < 2; i++) {
        uint32_t u[4] = {__ldcg(qs + i), __ldcg(qs + i + 2), __ldcg(qs + i + 4), __ldcg(qs + i + 6)};
        unesc(u, esc + (row + i * 8) * 20 + (lane & 3), tag);
        q[i] = u[0]; q[i + 2] = u[1]; q[i + 4] = u[2]; q[i + 6] = u[3];
      }
      __syncwarp();
      attn_slow(q, head, esc + 65536 * 20, tag, o, lane);
      const float i0 = rcp(o[16]), i1 = rcp(o[18]);
      bf16* op = g_os + (size_t)row * 1024 + h * 512 + (b & 15) * 32 + (lane & 3) * 8;
      *(uint4*)op = make_uint4(pack2(o[0] * i0, o[1] * i0), pack2(o[4] * i0, o[5] * i0), pack2(o[8] * i0, o[9] * i0), pack2(o[12] * i0, o[13] * i0));
      *(uint4*)(op + 8 * 1024) = make_uint4(pack2(o[2] * i1, o[3] * i1), pack2(o[6] * i1, o[7] * i1), pack2(o[10] * i1, o[11] * i1), pack2(o[14] * i1, o[15] * i1));
    }
    if ((t & 1) && ((redo >> 2 * h) & 3)) bar_arrive(NB_SIG + 2 * h + wg, 160 + 32 * (h & wg));
  }
}

__global__ void __cluster_dims__(2, 1, 1) __launch_bounds__(384, 1) fused_kernel(const __grid_constant__ Params prm) {
  extern __shared__ __align__(1024) char smem[];
  const uint32_t sb = (uint32_t)__cvta_generic_to_shared(smem);
  const int tid = threadIdx.x, lane = tid & 31;
  const int wg = __shfl_sync(0xffffffffu, tid >> 7, 0);
  const int w = __shfl_sync(0xffffffffu, (tid >> 5) & 3, 0);
  const int bm = remap(blockIdx.x) >> 4, bn = remap(blockIdx.x) & 15;

  auto first_tile = [&](int kt) {
    e_expect_tx(sb + B_QF + 8 * kt, QSTG);
    tma_ld(sb + kt * QSTG, &prm.m[M_X0A], kt * 64, bm * 256, sb + B_QF + 8 * kt);
    tma_ld3(sb + kt * QSTG + 32768, &prm.m[M_WQA], bn * 64, kt * 64, 0, sb + B_QF + 8 * kt);
  };
  auto init4 = [&](uint32_t bar, uint32_t c0, uint32_t c1, uint32_t c2, uint32_t c3) {
    asm volatile("{\n.reg .pred pe;\nelect.sync _|pe, 0xffffffff;\n@pe mbarrier.init.shared::cta.b64 [%0], %1;\n@pe mbarrier.init.shared::cta.b64 [%0+8], %2;\n"
                 "@pe mbarrier.init.shared::cta.b64 [%0+16], %3;\n@pe mbarrier.init.shared::cta.b64 [%0+24], %4;\n@pe fence.mbarrier_init.release.cluster;\n}"
                 ::"r"(bar), "r"(c0), "r"(c1), "r"(c2), "r"(c3) : "memory");
  };
  if (wg < 2) {
    const uint32_t k = wg * 4 + w, lo = (0x1411814u >> (4 * k)) & 15, hi = (0x1441814u >> (4 * k)) & 15;
    if (tid < 32) asm volatile("prefetch.global.L2 [%0];" ::"l"(prm.x0 + (size_t)(bm * 256 + bn * 16 + (tid & 15)) * 1024 + (tid >> 4) * 64));
    else if (tid < 80) asm volatile("prefetch.global.L2 [%0];" ::"l"(prm.wq[0] + (bm * 16 + (tid & 15)) * 3072 + ((tid >> 4) - 2) * 1024 + bn * 64));
    __syncwarp();
    if (k < 7) init4(sb + B_QE + 32 * k, lo, lo, hi, k == 6 ? 2 : hi);
    __syncwarp();
    if (k == 6 && lane == 0) *(volatile unsigned long long*)(smem + W_X) = 0ull;
  } else if (w == 0) {
    init4(sb + B_QF, 1, 1, 1, 1);
    __syncwarp();
    first_tile(0);
  }
  __syncthreads();
  asm volatile("barrier.cluster.arrive.relaxed.aligned;" ::: "memory");

  if (wg == 2) {
    asm volatile("setmaxnreg.dec.sync.aligned.u32 56;");
    const uint32_t ep1 = *(volatile uint32_t*)&g_epoch + 1;
    if (w == 0) {
      first_tile(1);
      mbar_wait(sb + B_QF, 0);
      first_tile(2); first_tile(3);
#pragma unroll 1
      for (int kt = 4; kt < 16; kt++) l2_prefetch(prm.wq[0] + kt * 196608 + blockIdx.x * 1536, 3072);
      cluster_wait();
#pragma unroll 1
      for (int l = 0; l < 4; l++) {
        IDS();
        const CUtensorMap* mw = &prm.m[M_WQA + (l & 1)];
        const CUtensorMap* mh = &prm.m[l == 0 ? M_X0H : M_XSO];
        const CUtensorMap* mo = &prm.m[M_WOA + (l & 1)];
        auto q_b = [&](int i) {
          const int s = i & 3;
          mbar_wait(sb + B_QE + 8 * s, ((i >> 2) & 1) ^ 1);
          e_expect_tx(sb + B_QF + 8 * s, QSTG);
          tma_ld3(sb + s * QSTG + 32768, mw, bn * 64, qord(i, l, pn) * 64, 0, sb + B_QF + 8 * s);
        };
        uint32_t rdy = l ? 0u : ~0u;
        auto q_a = [&](int i) {
          const int kt = qord(i, l, pn);
          await_flag(kt, rdy, cnt_x(bm) + (lane & 15), ep1 * 9 - 6 + 2 * l);
          tma_ld_mc(sb + (i & 3) * QSTG + rank * 16384, mh, kt * 64, bm * 256 + rank * 128, sb + B_QF + 8 * (i & 3));
        };
        if (l > 0) {
#pragma unroll 1
          for (int i = 0; i < 4; i++) {
            const int kt = qord(i, l, pn);
            await_flag(kt, rdy, cnt_x(bm) + (lane & 15), ep1 * 9 - 6 + 2 * l);
            e_expect_tx(sb + B_QF + 8 * i, 16384);
            tma_ld(sb + i * QSTG + (po ^ 1) * 16384, &prm.m[M_XSO], kt * 64, (pm ^ 1) * 128, sb + B_QF + 8 * i);
          }
        }
#pragma unroll 1
        for (int i = 4; i < 16; i++) {
          if (l == 3 && i == 12) poll_ge(cnt_ad(bn), ep1 * 16);
          q_b(i); q_a(i);
        }
        if (l & 1) {
          const int krow = 2 * bn * 2048 + bm * 256;
          uint32_t* kvc = cnt_kv(l >> 1, bn);
          uint32_t seen = 0;
#pragma unroll 1
          for (int it = 1; it < 16; it++) {
            const int s = it & 3;
            if (it == 4) {
              bar_sync(NB_KV + 12, 288);
              mbar_wait(sb + B_TF + 24, 0);
#pragma unroll 1
              for (int i = 0; i < 4; i++) tma_st(&prm.m[M_K + (i & 1)], 0, krow + 2048 + (i >> 1) * 128, sb + i * 8192);
              bulk_commit();
            }
            if (it == 5) { bulk_wait_n<0>(); e_red(kvc + 16 + bm); }
            if (it == 12) { e_expect_tx(sb + B_RF, 32768); tma_ld3(sb + RES, &prm.m[M_XSR], 0, pm * 128, 2 * pn, sb + B_RF); }
            if (it == 1 || it == 3) mbar_wait(sb + B_QE + 12 + 4 * it, 1);
            mbar_wait(sb + B_TE + 8 * s, ((it >> 2) & 1) ^ 1);
            if (it < 8) {
#pragma unroll 1
              for (uint32_t n = 0; n < 200000u && (~seen & (3u << (2 * it - 2) | (it == 4 ? 0xC000u : 0u))); n++)
                seen = __ballot_sync(~0u, (int)(ld_acquire(kvc + (lane < 7 || lane == 15 ? (bm + 1 + lane) & 7 : 8 + ((bm + 2 + lane) & 7))) - ep1) >= 0);
              fence_async_gl();
            } else if (it == 8) { poll_ge(kvc + 16 + (lane & 7), ep1); fence_async_gl(); }
            e_expect_tx(sb + B_TF + 8 * s, 32768);
#pragma unroll 1
            for (int i = 0; i < 2; i++) {
              const int u = 2 * it - 2 + i;
              const int row = 2 * bn * 2048 + (it > 7 ? 2048 + ((bm + it) & 7) * 256 + i * 128 : u < 7 ? ((bm + 1 + u) & 7) * 256 : ((bm + 2 + u) & 7) * 256 + 128);
              tma_ld(sb + T0 + s * TSTG + i * 8192, &prm.m[M_K], 0, row, sb + B_TF + 8 * s);
              tma_ld(sb + T0 + s * TSTG + 16384 + i * 8192, &prm.m[M_V], 0, row, sb + B_TF + 8 * s);
            }
          }
        }
        auto p_b = [&](int i, uint32_t s, uint32_t par) {
          mbar_wait(sb + B_PE + 8 * s, par ^ 1);
          e_expect_tx(sb + B_PF + 8 * s, PSTG);
          tma_ld5(sb + pslot_b(s), mo, i >> 3, (2 * i + bn) & 14, 2 * pn, sb + B_PF + 8 * s);
        };
        auto p_a = [&](int i, uint32_t s) {
          await_flag(i, rdy, cnt_o(l, pm, (lane >> 3) & 1) + ((lane + (bn >> 1)) & 7), ep1 * 2);
          tma_ld_mc(sb + pslot_a(s, l) + rank * 8192, &prm.m[M_OS], (i & 8) * 64 + ((2 * i + bn) & 14) * 32, pm * 128 + rank * 64, sb + B_PF + 8 * s);
        };
        auto p_a2 = [&](int i) {
          await_flag(i, rdy, cnt_o(l, pm, (lane >> 3) & 1) + ((lane + (bn >> 1)) & 7), ep1 * 2);
          tma_ld(sb + pslot_a(i, l), &prm.m[M_OS], (i & 8) * 64 + ((2 * i + bn) & 14) * 32, pm * 128, sb + B_PF + 8 * i);
          tma_ld(sb + pslot_a(i, l) + 8192, &prm.m[M_OS], (i & 8) * 64 + ((2 * i + bn) & 14) * 32, pm * 128 + 64, sb + B_PF + 8 * i);
        };
        rdy = 0;
        if (l & 1) {
#pragma unroll 1
          for (int u = 0; u < 6; u++) { const int i = (0x205413 >> (4 * u)) & 7; if (u == 4) mbar_wait(sb + B_TE, 1); p_b(i, i, i < 4 ? 1 : 0); }
#pragma unroll 1
          for (int u = 0; u < 6; u++) {
            const int i = (0x542130 >> (4 * u)) & 7;
            if (!(u & 1)) mbar_wait(sb + B_TE + 8 + 4 * u, 1);
            if (u == 4) bar_sync(NB_SIG + 3, 192);
            p_a2(i);
          }
        } else {
#pragma unroll 1
          for (int u = 0; u < 6; u++) { const int i = (0x543120 >> (4 * u)) & 7; if (u == 0 || u == 2) mbar_wait(sb + B_QE + 8 - 4 * u, 1); p_b(i, i, 0); }
          mbar_wait(sb + B_QE + 24, 1);
          e_expect_tx(sb + B_RF, 32768);
          tma_ld3(sb + RES, &prm.m[l == 0 ? M_X0R : M_XSR], 0, pm * 128, 2 * pn, sb + B_RF);
          await_flag(1, rdy, cnt_o(l, pm, (lane >> 3) & 1) + ((lane + (bn >> 1)) & 7), ep1 * 2);
          bar_sync(NB_DONE, 288);
          e_arrive_both(sb + B_PA);
          p_a2(1);
          mbar_wait(sb + B_PA, (l >> 1) & 1);
#pragma unroll 1
          for (int i = 2; i < 6; i++) { if (i > 3) mbar_wait(sb + B_PF + 8 * (i - 3), 0); p_a(i, i); }
        }
        uint32_t s = 0, lap = 1;
#pragma unroll 1
        for (int i = 6; i < 16; i++) {
          p_b(i, s, ((s < 4 ? l : 0) + lap) & 1);
          p_a(i, s);
          if (++s == 6) { s = 0; lap++; }
        }
        const CUtensorMap* mn = &prm.m[M_WQA + ((l + 1) & 1)];
        if (l < 3) {
          mbar_wait(sb + B_PE + 8 * 4, 1); mbar_wait(sb + B_PE + 8 * 5, 1);
          tma_ld3(sb + 32768, mn, bn * 64, 2 * pn * 64, 0, sb + B_QL);
          mbar_wait(sb + B_PE + 8 * 0, l & 1);
          e_expect_tx(sb + B_PA, 24576); e_expect_tx(sb + B_PA, 16384);
          tma_ld3(sb + QSTG + 32768, mn, bn * 64, ((2 * pn) ^ 2) * 64, 0, sb + B_PA);
          mbar_wait(sb + B_PE + 8 * 1, l & 1);
          tma_ld3(sb + 2 * QSTG + 32768, mn, bn * 64, (2 * pn + 1) * 64, 0, sb + B_QL);
          bar_sync(NB_KN, 288);
          e_expect_tx(sb + B_RF, 40960);
          tma_ld3(sb + 3 * QSTG + 32768, mn, bn * 64, ((2 * pn) ^ 3) * 64, 0, sb + B_RF);
          mbar_wait(sb + B_PE + 24, l & 1);
          bar_sync(NB_X0, 320);
          fence_async_gl();
          tma_ld_mc(sb + QSTG + po * 16384, &prm.m[M_XSO], 2 * pn * 64, pm * 128, sb + B_PA, 2 - rank);
          bar_sync(NB_X, 320);
          e_expect_tx(sb + B_QL, 49152);
        }
      }
      if (blockIdx.x == 0 && lane_id() == 0) *(volatile uint32_t*)&g_epoch = ep1;
    } else {
      const int hw = w - 1;
      if (lane < 5) asm volatile("prefetch.tensormap [%0];" ::"l"(&prm.m[1 + 5 * hw + lane]) : "memory");
      __syncwarp();
      cluster_wait();
      mbar_wait(sb + B_QF, 0);
#pragma unroll 1
      for (int l = 0; l < 4; l++) {
        IDS();
        if (l > 0) { mbar_wait(sb + B_QL, (l + 1) & 1); mbar_wait(sb + B_QF + 24, 0); }
        if (l == 0) {
#pragma unroll 1
          for (int r = 2 * hw; r < 16; r += 6) {
            const uint4* p = (const uint4*)(prm.x0 + (size_t)(b * 16 + r) * 1024) + lane;
            float s1[2] = {0.f, 0.f}, s2[2] = {0.f, 0.f};
#pragma unroll
            for (int i = 0; i < 8; i++) {
              const uint4 v = __ldg(p + 32 * i);
              const uint32_t u[4] = {v.x, v.y, v.z, v.w};
#pragma unroll
              for (int k = 0; k < 4; k++) { const float a = bf_lo(u[k]), c = bf_hi(u[k]); s1[i >> 2] += a + c; s2[i >> 2] = fmaf(a, a, fmaf(c, c, s2[i >> 2])); }
            }
#pragma unroll
            for (int o = 16; o; o >>= 1)
#pragma unroll
              for (int rr = 0; rr < 2; rr++) { s1[rr] += __shfl_xor_sync(~0u, s1[rr], o); s2[rr] += __shfl_xor_sync(~0u, s2[rr], o); }
            if (lane == 0) *(float4*)&g_stats[b * 16 + r] = make_float4(s1[0], s2[0], s1[1], s2[1]);
          }
        }
        if (l < 2) {
          float cs[8];
#pragma unroll
          for (int i = 0; i < 8; i++) cs[i] = 0.f;
          const uint4* wp = (const uint4*)(prm.wq[l] + (size_t)(bm * 128 + (lane >> 3)) * 3072 + hw * 1024 + bn * 64) + (lane & 7);
#pragma unroll 8
          for (int i = 0; i < 32; i++) {
            const uint4 v = __ldg(wp + (size_t)i * 4 * 384);
            cs[0] += bf_lo(v.x); cs[1] += bf_hi(v.x); cs[2] += bf_lo(v.y); cs[3] += bf_hi(v.y);
            cs[4] += bf_lo(v.z); cs[5] += bf_hi(v.z); cs[6] += bf_lo(v.w); cs[7] += bf_hi(v.w);
          }
#pragma unroll
          for (int i = 0; i < 8; i++) { cs[i] += __shfl_xor_sync(~0u, cs[i], 8); cs[i] += __shfl_xor_sync(~0u, cs[i], 16); }
          if (lane < 8) {
            float4* d = (float4*)(g_csp + ((l * 16 + bn) * 8 + bm) * 192 + hw * 64 + lane * 8);
            d[0] = make_float4(cs[0], cs[1], cs[2], cs[3]); d[1] = make_float4(cs[4], cs[5], cs[6], cs[7]);
          }
          __syncwarp();
          asm volatile("fence.acq_rel.gpu;" ::: "memory");
          e_red_relaxed(cnt_cs(l, bn));
          if (l == 0) e_red_relaxed(cnt_x(bm) + bn);
          poll_ge(lane < 16 && l == 0 ? cnt_x(bm) + lane : cnt_cs(l, bn), lane < 16 && l == 0 ? ep1 * 9 - 6 : ep1 * 24);
        }
        if (l > 0) poll_ge(cnt_x(bm) + (lane & 15), ep1 * 9 - 6 + 2 * l);
#pragma unroll 1
        for (int it = hw * 32 + lane; it < 176; it += 96) {
          const bool rows = it < 128;
          const float4* p = rows ? (const float4*)(g_stats + bm * 256) + it : (const float4*)(g_csp + ((l & 1) * 16 + bn) * 8 * 192) + (it - 128);
          const int stride = rows ? 1024 : 48, np = rows && l == 0 ? 1 : 8;
          float4 a = make_float4(0.f, 0.f, 0.f, 0.f);
#pragma unroll
          for (int k = 0; k < 8; k++) if (k < np) { const float4 v = __ldcg(p + k * stride); a.x += v.x; a.y += v.y; a.z += v.z; a.w += v.w; }
          if (rows) {
            const float m0 = a.x * (1.f / 1024.f), m1 = a.z * (1.f / 1024.f);
            const float v0 = fmaxf(a.y * (1.f / 1024.f) - m0 * m0, 0.f), v1 = fmaxf(a.w * (1.f / 1024.f) - m1 * m1, 0.f);
            const float r0 = __fdividef(1.f, bf_round(sqrtf(bf_round(bf_round(v0) + 1e-5f)))), r1 = __fdividef(1.f, bf_round(sqrtf(bf_round(bf_round(v1) + 1e-5f))));
            a = make_float4(r0, -bf_round(m0), r1, -bf_round(m1));
          }
          if (rows && (l & 1) && (it & 4)) a = make_float4(a.y, a.x, a.w, a.z);
          *(float4*)(smem + ROWST + it * 16) = a;
        }
        __syncwarp();
        if (lane == 0) asm volatile("red.release.cta.shared.add.u32 [%0], 1;" ::"r"(sb + W_X) : "memory");
        if (hw == 2) {
          if (!(l & 1)) {
            bar_sync(NB_ST, 288);
            const uint4* hp = g_halo + (b - 16) * 384 + lane;
#pragma unroll 1
            for (int h = 0; h < 2; h++) {
              uint32_t t[18];
#pragma unroll
              for (int i = 0; i < 18; i++) t[i] = 0;
#pragma unroll 1
              for (uint32_t n = bm ? 0 : 100000u; n < 100000u; n++) {
                uint32_t miss = 0;
#pragma unroll
                for (int i = 0; i < 6; i++) miss |= ld_tagged(hp + h * 192 + i * 32, &t[3 * i]) ^ (4 * ep1 + l);
                if (__all_sync(~0u, !miss)) break;
              }
              mbar_wait(sb + B_QE + 16, 1);
              const uint32_t r = (lane & 7) + ((lane >> 3) & 1) * 8, rv = lane >> 2;
#pragma unroll
              for (int jj = 0; jj < 2; jj++) stsm4(sb + KSC + r * 128 + (((4 * h + 2 * jj + (lane >> 4)) ^ (r & 7)) << 4), t[4 * jj], t[4 * jj + 1], t[4 * jj + 2], t[4 * jj + 3]);
              const uint32_t ad = sb + VSC + rv * 128 + (((4 * h + (lane & 3)) ^ (rv & 7)) << 4);
              sts128(ad, t[8], t[10], t[12], t[14]); sts128(ad + 1024, t[9], t[11], t[13], t[15]);
              if (h == 0 && !(lane & 2)) *(uint32_t*)(smem + HRS + ((lane >> 2) + 8 * (lane & 1)) * 8) = t[16];
              bar_arrive(NB_HALO + h, 64);
            }
          } else {
            bar_sync(NB_KV, 288);
            sts128(sb + ONES + lane * 32, 0x3f803f80u, 0x3f803f80u, 0x3f803f80u, 0x3f803f80u);
            sts128(sb + ONES + lane * 32 + 16, 0x3f803f80u, 0x3f803f80u, 0x3f803f80u, 0x3f803f80u);
            sts128(sb + ROWST + 16, 0x62A962A9u, 0x00010001u, 0x3F003F00u, 0u);
            fence_async_smem();
            __syncwarp();
            e_arrive(sb + B_TF);
            mbar_wait(sb + B_TF + 16, 0); mbar_wait(sb + B_TF + 16, 1);
            poll_ge(cnt_kv(l >> 1, bn) + 16 + (lane & 7), ep1);
            const uint4 v = __ldcg((const uint4*)(g_kn + ((l >> 1) * 128 + bn * 8) * 16) + lane);
            const uint32_t mx = max(max(v.x, v.y), max(v.z, v.w));
            const uint32_t m0 = __reduce_max_sync(~0u, (lane & 2) ? 0u : mx), m1 = __reduce_max_sync(~0u, (lane & 2) ? mx : 0u);
            if (lane == 0) *(uint2*)(smem + ROWST) = make_uint2(m0, m1);
            __syncwarp();
            bar_arrive(NB_KN, 160); bar_arrive(NB_KN + 1, 160);
          }
        } else {
          if (l & 1) {
            uint32_t* p = cnt_kv(l >> 1, bn) + 8 * hw + bm;
            int on = lane == 0;
            PREPARED(p, on);
            bar_sync(hw ? NB_HALO : NB_DONE, 160);
            tma_st(&prm.m[M_K], 0, 2 * bn * 2048 + bm * 256 + hw * 128, sb + T0 + hw * 8192);
            tma_st(&prm.m[M_V], 0, 2 * bn * 2048 + bm * 256 + hw * 128, sb + T0 + 16384 + hw * 8192);
            bulk_commit(); bulk_wait_n<0>();
            release_add(p, on);
          }
#pragma unroll 1
          for (int h = l & 1 ? 0 : hw; h <= (l & 1 ? 1 : hw); h++) {
            uint32_t* p = l == 1 && lane == 1 ? cnt_ad(bn) : cnt_o(l, 2 * bm + (l & 1 ? hw : lane & 1), h) + (bn >> 1);
            int on = lane == 0 || (lane == 1 && (!(l & 1) || (l == 1 && h == 1)));
            int id = NB_SIG + 2 * h + (l & hw), n = l & 1 ? 160 + 32 * (h & hw) : 288;
            asm volatile("" : "+r"(id), "+r"(n));
            PREPARED(p, on);
            bar_sync(id, n);
            release_add(p, on);
            if (!(l & 1) && hw == 0) {
              mbar_wait(sb + B_QE + 24, 1);
              fence_async_gl();
              tma_ld_mc(sb + pslot_a(0, 0) + rank * 8192, &prm.m[M_OL], bn * 32, pm * 128, sb + B_PF);
            }
          }
        }
        if (hw < 2 && l < 3) {
          uint32_t* p = cnt_x(bm) + 2 * pn + hw;
          int on = lane == 0;
          PREPARED(p, on);
          if (hw) {
            bar_sync(NB_X, 320);
            tma_st(&prm.m[M_XSO], pn * 128 + 64, pm * 128, sb + 2 * QSTG + po * 16384);
            bulk_commit();
            bar_sync(NB_KV, 288);
            bulk_wait_n<0>();
            mbar_wait(sb + B_PA, l == 0);
            fence_async_gl();
            tma_ld_mc(sb + 3 * QSTG + po * 16384, &prm.m[M_XSO], pn * 128 + 64, pm * 128, sb + B_RF, 2 - rank);
          } else bar_sync(NB_X0, 320);
          release_add(p, on);
        }
      }
    }
  } else {
    asm volatile("setmaxnreg.inc.sync.aligned.u32 224;");
    const uint32_t zero = prm.zero;
    cluster_wait();
#pragma unroll 1
    for (int l = 0; l < 4; l++) {
      {
        float acc[2][96];
        const bool early = l > 0 && wg == ((cta_id() >> 3) & 1);
        uint32_t ep1 = 0;
        if (l > 0) mbar_wait(sb + B_QL, (l + 1) & 1);
        if (!early) mbar_wait(sb + B_QF, 0);
        wg_fence();
#pragma unroll
        for (int k = 0; k < 4; k++)
#pragma unroll
          for (int m = 0; m < 2; m++) {
            if (k) wgmma_m64n192k16_ss_tb(acc[m], prm.xd + wg * 1024 + m * 512 + k * 2, prm.wd + k * 128, 1);
            else wgmma_m64n192k16_ss_tb_z(acc[m], prm.xd + wg * 1024 + m * 512, prm.wd, 0);
          }
        wg_commit();
#pragma unroll 1
        for (int kt = 1; kt < 13; kt++) {
          const int s = kt == 12 ? 1 : kt & 3;
          if (l > 0 && (kt | 2) == 3) mbar_wait(sb + (kt == 1 ? B_PA : B_RF), kt == 3 || l == 1);
          if (!(early && kt < 4)) mbar_wait(sb + B_QF + 8 * s, (kt >> 2) & 1);
          const uint64_t da = prm.xd + wg * 1024 + s * (QSTG >> 4), db = prm.wd + s * (QSTG >> 4);
          wg_fence();
#pragma unroll
          for (int k = 0; k < 4; k++)
#pragma unroll
            for (int m = 0; m < 2; m++) wgmma_m64n192k16_ss_tb(acc[m], da + m * 512 + k * 2, db + k * 128, 1);
          wg_commit();
          if (kt == 4) ep1 = *(volatile uint32_t*)&g_epoch + 1;
          wg_wait<1>();
          if (early && kt < 5) {
            if (kt < 3) continue;
#pragma unroll 1
            for (int i = 0; i < 8 - 2 * kt; i++) { mbar_wait(sb + B_QF + 8 * i, 0); if (w == 0) e_arrive_both(sb + B_QE + 8 * i); }
            mbar_wait(sb + B_QF + 8 * (kt - 1), 0);
          }
          if (w == 0) e_arrive_both(sb + B_QE + 8 * ((kt - 1) & 3));
        }
        {
          const bool lag = (l & 1) == wg;
          const uint32_t s0 = 2 * (~l & 1);
          const uint64_t da = prm.xd + wg * 1024 + 2 * (QSTG >> 4), db = prm.wd + 2 * (QSTG >> 4);
          mbar_wait(sb + B_QF + 8 * s0, 1);
#pragma unroll
          for (int t = 0; t < 2; t++) {
            if (lag && t != wg) {
              wg_wait<0>();
              if (w == 0) e_arrive_both(sb + B_QE + 8 + 8 * t);
              if (t == 0) mbar_wait(sb + B_QF + 16, 1);
              mbar_wait(sb + B_QF + 24, 1);
              if (t == 1) bar_arrive(NB_ST, 288);
              bar_sync(NB_SC, 256);
            }
            const uint64_t so = (uint64_t)(t ? s0 : s0 ^ 2) * (QSTG >> 4);
            wg_fence();
#pragma unroll
            for (int k = 0; k < 4; k++)
#pragma unroll
              for (int m = 0; m < 2; m++) wgmma_m64n192k16_ss_tb(acc[m], da - so + m * 512 + k * 2, db - so + k * 128, 1);
            wg_commit();
            if (!lag || t + wg == 0) {
              wg_wait<1>();
              if (w == 0) e_arrive_both(sb + B_QE + 8 * (t ? s0 : 1));
              mbar_wait(sb + B_QF + 8 * (t ? 3 : s0 ^ 2), 1);
            }
          }
          wg_fence();
#pragma unroll
          for (int m = 1; m >= 0; m--) {
#pragma unroll
            for (int k = 0; k < 4; k++) wgmma_m64n192k16_ss_tb(acc[m], da + (QSTG >> 4) + m * 512 + k * 2, db + (QSTG >> 4) + k * 128, 1);
            wg_commit();
          }
          if (!lag) { bar_arrive(NB_SC, 256); if (wg) bar_arrive(NB_ST, 288); }
          wg_wait<2>();
          if (w == 0) { e_arrive_both(sb + B_QE + 8 * (s0 ^ 2)); if (lag && wg) e_arrive_both(sb + B_QE); }
        }
#pragma unroll 1
        for (uint32_t n = 0; n < 4000000u; n++) {
          uint32_t v;
          asm volatile("ld.acquire.cta.shared.u32 %0, [%1];" : "=r"(v) : "r"(sb + W_X) : "memory");
          if (v == (uint32_t)(3 * l + 3)) break;
        }
        IDS();
        const int g = lane >> 2, qd = lane & 3;
        float2 st[2][2];
#pragma unroll
        for (int m = 0; m < 2; m++)
#pragma unroll
          for (int hh = 0; hh < 2; hh++) st[m][hh] = lds64f(sb + ROWST + (wg * 128 + m * 64 + w * 16 + g + 8 * hh) * 8);
        float2 cs[4];
        auto load_cs = [&](int gi) {
#pragma unroll
          for (int j = 0; j < 4; j++) cs[j] = lds64f(sb + COLS + (gi * 32 + j * 8 + 2 * qd) * 4);
        };
        load_cs(2 + 2 * (l & 1));
        auto drain = [&]() {
          wg_wait<0>(); fence_regs(acc[0]);
          if (w == 0) e_arrive_both(sb + B_QE + 8 * 3);
        };
        wg_wait<1>(); fence_regs(acc[1]);
        auto norm_tile = [&](int gi, int m, float sc, uint32_t (&t)[8], float (&nrm)[2], bool h16 = false) {
          const float r0 = st[m][0].x * sc, s0 = st[m][0].y, r1 = st[m][1].y * sc, s1 = st[m][1].x;
          float n0 = 0.f, n1 = 0.f;
#pragma unroll
          for (int j = 0; j < 4; j++) {
            const float* a = &acc[m][16 * gi + 4 * j];
            const float v0 = fmaf(s0, cs[j].x, a[0]) * r0, v1 = fmaf(s0, cs[j].y, a[1]) * r0;
            const float v2 = fmaf(s1, cs[j].x, a[2]) * r1, v3 = fmaf(s1, cs[j].y, a[3]) * r1;
            n0 = fmaf(v0, v0, fmaf(v1, v1, n0)); n1 = fmaf(v2, v2, fmaf(v3, v3, n1));
            t[2 * j] = h16 ? pack2h(v0, v1) : pack2(v0, v1); t[2 * j + 1] = h16 ? pack2h(v2, v3) : pack2(v2, v3);
          }
          nrm[0] = n0; nrm[1] = n1;
        };
        auto norm_group = [&](int gi, float sc, uint32_t (&t)[2][8], float (&nrm)[2][2]) { norm_tile(gi, 0, sc, t[0], nrm[0]); norm_tile(gi, 1, sc, t[1], nrm[1]); };
        uint32_t q[2][2][8];
        const uint32_t srow = (lane & 7) + ((lane >> 3) & 1) * 8;
        const uint32_t row0 = wg * 128 + w * 16;
        if (!(l & 1)) {
          auto put_kv = [&](int gi, uint32_t r0, const uint32_t (&t)[8]) {
            if (gi < 4) {
              const uint32_t r = r0 + srow;
#pragma unroll
              for (int jj = 0; jj < 2; jj++) stsm4(sb + KSC + r * 128 + (((4 * (gi - 2) + 2 * jj + (lane >> 4)) ^ (r & 7)) << 4), t[4 * jj], t[4 * jj + 1], t[4 * jj + 2], t[4 * jj + 3]);
            } else {
              const uint32_t r = r0 + g, ad = sb + VSC + r * 128 + (((4 * (gi - 4) + qd) ^ (r & 7)) << 4);
              sts128(ad, t[0], t[2], t[4], t[6]); sts128(ad + 1024, t[1], t[3], t[5], t[7]);
            }
          };
          auto cen_tile = [&](int gi, int m, uint32_t (&t)[8]) {
#pragma unroll
            for (int j = 0; j < 4; j++) {
              const float* a = &acc[m][16 * gi + 4 * j];
              t[2 * j] = pack2(fmaf(st[m][0].y, cs[j].x, a[0]), fmaf(st[m][0].y, cs[j].y, a[1]));
              t[2 * j + 1] = pack2(fmaf(st[m][1].y, cs[j].x, a[2]), fmaf(st[m][1].y, cs[j].y, a[3]));
            }
          };
          const bool send = wg == 1 && w == 3 && bm < 7;
          uint4* hp = g_halo + b * 384 + lane;
          ep1 = 4 * ep1 + l;
          mbar_wait(sb + B_QE + 16, 1);
          float2 cn[4];
          auto next_cs = [&](int gi) {
#pragma unroll
            for (int j = 0; j < 4; j++) { cs[j] = cn[j]; cn[j] = lds64f(sb + COLS + (gi * 32 + j * 8 + 2 * qd) * 4); }
          };
#pragma unroll
          for (int j = 0; j < 4; j++) cn[j] = cs[j];
          auto lower = [&](int h, int nx, bool snd) {
            uint32_t k[8], v[8];
            next_cs(4 + h);
            cen_tile(2 + h, 1, k); put_kv(2 + h, 16 + row0 + 64, k);
            next_cs(nx);
            cen_tile(4 + h, 1, v); put_kv(4 + h, 16 + row0 + 64, v);
            if (snd) {
              uint4* p = hp + h * 192;
              st_tagged(p, k[0], k[1], k[2], ep1); st_tagged(p + 32, k[3], k[4], k[5], ep1); st_tagged(p + 64, k[6], k[7], v[0], ep1);
              st_tagged(p + 96, v[1], v[2], v[3], ep1); st_tagged(p + 128, v[4], v[5], v[6], ep1);
              st_tagged(p + 160, v[7], __float_as_uint(qd & 1 ? st[1][1].x : st[1][0].x), 0u, ep1);
            }
          };
          lower(0, 2 + wg, send);
          sched_fence();
          if (wg) lower(1, 2, send);
          drain();
          {
            uint32_t t[8];
            next_cs(4); cen_tile(2, 0, t); put_kv(2, 16 + row0, t);
            next_cs(0); cen_tile(4, 0, t); put_kv(4, 16 + row0, t);
            next_cs(3); cen_tile(0, 0, q[0][0]); cen_tile(0, 1, q[0][1]);
          }
          auto upper = [&]() {
            uint32_t t[8];
            next_cs(5); cen_tile(3, 0, t); put_kv(3, 16 + row0, t);
            next_cs(1); cen_tile(5, 0, t); put_kv(5, 16 + row0, t);
          };
          if (wg) upper();
          const bool e = g & 1, sel = 2 * qd + (g & 1) >= g + 2, first = bm == 0 && row0 == 0;
          uint32_t ka = sb + KSC + (row0 + (lane & 7)) * 128 + (((lane >> 3) ^ (lane & 7)) << 4);
          uint32_t wa = sb + VSC + (row0 + srow) * 128 + (((lane >> 4) ^ (lane & 7)) << 4);
          uint32_t psel[3] = {e ? 0x1044u : 0x4410u, !sel ? 0x4444u : e ? 0x3244u : 0x4432u, sel ? 0x4444u : e ? 0x3244u : 0x4432u};
          bf16* op = g_os + (size_t)(bm * 256 + row0 + g) * 1024 + bn * 32 + qd * 8;
          asm volatile("" : "+r"(ka), "+r"(wa), "+l"(op));
          fence_regs(psel); fence_regs(q[0][0]); fence_regs(q[0][1]);
          sched_fence();
          bar_sync(NB_SC, 256);
          if (row0 == 0) bar_sync(NB_HALO, 64);
          float ra[4], rb[4], ca[4], cb[4];
#pragma unroll
          for (int m = 0; m < 2; m++) {
            float rk[3];
#pragma unroll
            for (int u = 0; u < 3; u++) {
              const int r = row0 + m * 64 + 8 * u + 2 * qd + e - (sel ? 16 : 8);
              rk[u] = lds64f(sb + (m == 0 && r < 0 ? HRS + 128 : ROWST) + r * 8).x;
            }
            ra[2 * m] = sel ? rk[1] : rk[0]; ra[2 * m + 1] = sel ? rk[2] : rk[1];
            rb[2 * m] = sel ? rk[0] : rk[1]; rb[2 * m + 1] = sel ? rk[1] : rk[2];
          }
#pragma unroll
          for (int i = 0; i < 4; i++) { const float rq = st[i >> 1][i & 1].x * QSCALE; ca[i] = rq * ra[i]; cb[i] = rq * rb[i]; }
#pragma unroll 1
          for (int h = 0; h < 2; h++) {
            float s[2][4][4];
            uint32_t vf[2][4][4], pf[2][2][4];
#pragma unroll
            for (int m = 0; m < 2; m++)
#pragma unroll
              for (int nt = 0; nt < 4; nt++) {
                uint32_t kf[4];
                ldsm4(ka + (m * 64 + 8 * nt) * 128, kf);
                s[m][nt][0] = s[m][nt][1] = s[m][nt][2] = s[m][nt][3] = 0.f;
                mma16816(s[m][nt], q[0][m][0], q[0][m][1], q[0][m][2], q[0][m][3], kf[0], kf[1]);
                mma16816(s[m][nt], q[0][m][4], q[0][m][5], q[0][m][6], q[0][m][7], kf[2], kf[3]);
              }
#pragma unroll
            for (int m = 0; m < 2; m++)
#pragma unroll
              for (int i = 0; i < 4; i++) {
                ldsm4t((wa ^ (32 * (i & 1))) + (m * 64 + 16 * (i >> 1)) * 128, vf[m][i]);
              }
            if (h) { fence_async_smem(); bar_arrive(NB_DONE, 288); }
            float va[4], vb[4], mx[4];
#pragma unroll
            for (int i = 0; i < 4; i++) {
              const int m = i >> 1, hh = i & 1;
              const float a = e ? s[m][hh + 1][2 * hh + 1] : s[m][hh + 1][2 * hh];
              const float lo = e ? s[m][hh][2 * hh + 1] : s[m][hh][2 * hh], hi = e ? s[m][hh + 2][2 * hh + 1] : s[m][hh + 2][2 * hh];
              va[i] = (m == 0 && hh == 0 && first) ? -INFINITY : a * ca[i];
              vb[i] = (m == 0 && first && sel) ? -INFINITY : (sel ? lo : hi) * cb[i];
              mx[i] = fmaxf(va[i], vb[i]);
            }
#pragma unroll
            for (int i = 0; i < 4; i++) mx[i] = fmaxf(mx[i], __shfl_xor_sync(~0u, mx[i], 1));
#pragma unroll
            for (int i = 0; i < 4; i++) mx[i] = fmaxf(mx[i], __shfl_xor_sync(~0u, mx[i], 2));
#pragma unroll
            for (int i = 0; i < 4; i++) {
              va[i] = ex2(va[i] - mx[i]); vb[i] = ex2(vb[i] - mx[i]);
              mx[i] = va[i] + vb[i];
              va[i] *= ra[i]; vb[i] *= rb[i];
            }
#pragma unroll
            for (int i = 0; i < 4; i++) mx[i] += __shfl_xor_sync(~0u, mx[i], 1);
#pragma unroll
            for (int i = 0; i < 4; i++) mx[i] += __shfl_xor_sync(~0u, mx[i], 2);
#pragma unroll
            for (int i = 0; i < 4; i++) {
              const int m = i >> 1, hh = i & 1;
              const float inv = rcp(mx[i]);
              const uint32_t t = pack2(va[i] * inv, vb[i] * inv);
              pf[m][hh][hh + 1] = prmt0(t, psel[0]); pf[m][hh][hh] = prmt0(t, psel[1]); pf[m][hh][hh + 2] = prmt0(t, psel[2]);
              pf[m][hh][3 - 3 * hh] = t & zero;
            }
#pragma unroll
            for (int m = 0; m < 2; m++) {
              float o[4][4];
#pragma unroll
              for (int j = 0; j < 4; j++) o[j][0] = o[j][1] = o[j][2] = o[j][3] = 0.f;
#pragma unroll
              for (int i = 0; i < 4; i++) {
                const int kk = i >> 1, jj = 2 * (i & 1);
                mma16816(o[jj], pf[m][0][2 * kk], pf[m][1][2 * kk], pf[m][0][2 * kk + 1], pf[m][1][2 * kk + 1], vf[m][i][0], vf[m][i][1]);
                mma16816(o[jj + 1], pf[m][0][2 * kk], pf[m][1][2 * kk], pf[m][0][2 * kk + 1], pf[m][1][2 * kk + 1], vf[m][i][2], vf[m][i][3]);
              }
              stg128(op + m * 65536, pack2(o[0][0], o[0][1]), pack2(o[1][0], o[1][1]), pack2(o[2][0], o[2][1]), pack2(o[3][0], o[3][1]));
              stg128(op + m * 65536 + 8192, pack2(o[0][2], o[0][3]), pack2(o[1][2], o[1][3]), pack2(o[2][2], o[2][3]), pack2(o[3][2], o[3][3]));
            }
            bar_arrive(NB_SIG + 2 * h, 288);
            if (h == 0) {
              if (!wg) { lower(1, 3, false); upper(); }
#pragma unroll
              for (int j = 0; j < 4; j++) cs[j] = cn[j];
              cen_tile(1, 0, q[0][0]); cen_tile(1, 1, q[0][1]);
              ka ^= 64; wa ^= 64; op += 512;
              bar_sync(NB_SC, 256);
              if (row0 == 0) bar_sync(NB_HALO + 1, 64);
            }
          }
        } else {
          float qn[2];
          mbar_wait(sb + B_QE + 8, 1);
          drain();
          auto esc_ptr = [&](int gi) { IDS(); return g_esc + (size_t)(((l & 2) + (gi >> 1)) * 65536 + (2 * bn + (gi & 1)) * 2048) * 20; };
          auto norm_half = [&](int gi, float sc, uint32_t (&t)[2][8], float (&nrm)[2][2], int nx) {
            norm_tile(gi, 0, sc, t[0], nrm[0], true); norm_tile(gi, 1, sc, t[1], nrm[1], true);
            float2 cn[4];
#pragma unroll
            for (int j = 0; j < 4; j++) if (nx >= 0) cn[j] = lds64f(sb + COLS + (nx * 32 + j * 8 + 2 * qd) * 4);
            if (!((nrm[0][0] + nrm[0][1]) + (nrm[1][0] + nrm[1][1]) <= 4e9f) || fminf(fminf(nrm[0][0], nrm[0][1]), fminf(nrm[1][0], nrm[1][1])) < 1.5e-5f) {
              uint32_t* p = esc_ptr(gi) + (bm * 256 + row0 + g) * 20 + qd;
#pragma unroll
              for (int m = 0; m < 2; m++) {
                uint32_t u[8]; float d[2];
                norm_tile(gi, m, sc, u, d);
#pragma unroll
                for (int i = 0; i < 10; i++) p[(m * 64 + (i & 1) * 8) * 20 + (i >> 1) * 4] = i < 8 ? u[i] : ep1;
              }
            }
            __syncwarp();
#pragma unroll
            for (int i = 0; i < 16; i++) asm volatile("{\n.reg .b32 u;\nadd.u32 u, %0, 0x00040004;\nand.b32 %0, u, 0xFFF8FFF8;\n}" : "+r"(t[i >> 3][i & 7]));
#pragma unroll
            for (int j = 0; j < 4; j++) if (nx >= 0) cs[j] = cn[j];
          };
          {
            auto max_norm = [&](const float (&nrm)[2][2]) {
              const bool o1 = qd & 1, o2 = qd & 2;
              const float a = (o1 ? nrm[1][0] : nrm[0][0]) + __shfl_xor_sync(~0u, o1 ? nrm[0][0] : nrm[1][0], 1);
              const float c = (o1 ? nrm[1][1] : nrm[0][1]) + __shfl_xor_sync(~0u, o1 ? nrm[0][1] : nrm[1][1], 1);
              const float d = (o2 ? c : a) + __shfl_xor_sync(~0u, o2 ? a : c, 2);
              return __uint_as_float(__reduce_max_sync(~0u, __float_as_uint(d)));
            };
#pragma unroll
            for (int h = 0; h < 2; h++) {
              uint32_t t[2][8]; float nrm[2][2];
              const uint32_t kb = sb + (h ? wg * 8192 : T0), vb = kb + (h ? 8192 : 16384);
              norm_group(4 + h, 1.f, t, nrm);
              load_cs(2 + h);
#pragma unroll
              for (int m = 0; m < 2; m++) {
                const uint32_t r = row0 + m * 64 + g, ad = vb + r * 64 + ((qd ^ ((r >> 1) & 3)) << 4);
                sts128(ad, t[m][0], t[m][2], t[m][4], t[m][6]); sts128(ad + 512, t[m][1], t[m][3], t[m][5], t[m][7]);
              }
              if (h == 0) sched_fence();
              norm_half(2 + h, 1.f, t, nrm, h);
#pragma unroll
              for (int i = 0; i < 4; i++) {
                const uint32_t r = row0 + (i >> 1) * 64 + srow;
                stsm4(kb + r * 64 + (((2 * (i & 1) + (lane >> 4)) ^ ((r >> 1) & 3)) << 4), t[i >> 1][4 * (i & 1)], t[i >> 1][4 * (i & 1) + 1], t[i >> 1][4 * (i & 1) + 2], t[i >> 1][4 * (i & 1) + 3]);
              }
              if (h == 1) { const float kn = max_norm(nrm); if (lane == 0) g_kn[((l >> 1) * 128 + bn * 8 + bm) * 16 + 8 + wg * 4 + w] = kn; }
              fence_async_smem();
              bar_arrive(NB_KV + 12 * h, 288);
              if (h == 0) {
                bar_arrive(wg ? NB_HALO : NB_DONE, 160);
              }
              if (h == 0) { const float kn = max_norm(nrm); if (lane == 0) g_kn[((l >> 1) * 128 + bn * 8 + bm) * 16 + wg * 4 + w] = kn; }
              norm_half(h, QSCALE, q[h], nrm, h ? -1 : 5);
#pragma unroll
              for (int i = 0; i < 4 * h; i++) sts128(sb + QPARK + 24576 - wg * 8192 + (w * 32 + lane) * 16 + i * 2048, q[h][i >> 1][4 * (i & 1)], q[h][i >> 1][4 * (i & 1) + 1], q[h][i >> 1][4 * (i & 1) + 2], q[h][i >> 1][4 * (i & 1) + 3]);
              qn[h] = max_norm(nrm);
            }
          }
          constexpr uint64_t VSTEP = 64 - (64ull << 16);
          uint32_t cq[4];
          const uint32_t &c_852 = cq[0], &c_lsb = cq[1], &c_half = cq[2];
          float o[2][20], S[2][32];
          uint32_t H[2][16], P0[4] = {}, P1[4] = {};
#pragma unroll
          for (int m = 0; m < 2; m++) {
#pragma unroll
            for (int i = 0; i < 20; i++) o[m][i] = 0.f;
            fence_regs(o[m]);
          }
          auto qkf = [&](int b, int ks, uint64_t d) { wg_n64_rs_nb_f16_f32(S[b], q[0][0][4 * ks], q[0][0][4 * ks + 1], q[0][0][4 * ks + 2], q[0][0][4 * ks + 3], d + 2 * ks, ks ? 1 : zero); };
          auto qkh = [&](int b, int ks, uint64_t d) { wg_n64_rs_nb_f16_f16(H[b], q[0][1][4 * ks], q[0][1][4 * ks + 1], q[0][1][4 * ks + 2], q[0][1][4 * ks + 3], d + 2 * ks, ks ? 1 : zero); };
          auto pv0 = [&](uint64_t d) { wgmma_m64n40k16_rs_tb(o[0], P0[0], P0[1], P0[2], P0[3], d, 1); };
          auto pv1 = [&](uint64_t d) { wgmma_m64n40k16_rs_tb(o[1], P1[0], P1[1], P1[2], P1[3], d, 1); };
          float e[4] = {};
          auto finish = [&](int h) {
            const float* s = &S[(h >> 2) & 1][8 * (h & 3)];
            const uint32_t* u = &H[(h >> 2) & 1][4 * (h & 3)];
            const float z0 = exp2_fix(s[6]), z1 = exp2_fix(s[7]);
            P0[0] = pack2v(e[0], e[1]);
            P1[0] = exp2_h2(u[0], c_852);
            P0[1] = pack2v(e[2], e[3]);
            P1[1] = exp2_h2(u[1], c_852);
            const uint32_t B = exp2_base(z0, z1), E = and_or<0x7F807F80u>(B, c_lsb);
            P1[3] = exp2_h2(u[3], c_852);
            P0[3] = fma_bf2(B, and_or<0x807F807Fu>(B, c_half), E);
            const float e4 = ex2v(s[4]), e5 = ex2v(s[5]);
            P1[2] = exp2_h2(u[2], c_852);
            P0[2] = pack2v(e4, e5);
          };
          auto start = [&](int h) {
            const float* s = &S[(h >> 2) & 1][8 * (h & 3)];
            e[2] = ex2v(s[2]); e[1] = ex2v(s[1]); e[0] = ex2v(s[0]); e[3] = ex2v(s[3]);
          };
          uint64_t kd = prm.kv[0].kd;
          mbar_wait(sb + B_TF, 0);
          lds128(sb + ROWST + 16 + (lane_id() & zero), cq);
#pragma unroll
          for (int i = 0; i < 4; i++) sts128(sb + QPARK + (wg * 128 + w * 32 + lane_id()) * 16 + i * 4096, q[0][i >> 1][4 * (i & 1)], q[0][i >> 1][4 * (i & 1) + 1], q[0][i >> 1][4 * (i & 1) + 2], q[0][i >> 1][4 * (i & 1) + 3]);
          wg_fence();
#pragma unroll
          for (int b = 0; b < 2; b++) {
            wg_n64_rs_nb_f16_f32_z(S[b], q[0][0][0], q[0][0][1], q[0][0][2], q[0][0][3], kd + 256 * b, 0);
            wg_n64_rs_nb_f16_f16_z(H[b], q[0][1][0], q[0][1][1], q[0][1][2], q[0][1][3], kd + 256 * b, 0);
            if (b == 0) { qkf(0, 1, kd); qkh(0, 1, kd); }
            wg_commit();
          }
          wg_wait<1>(); fence_regs(S[0]); fence_regs(H[0]);
          start(0); finish(0); start(1);
          wg_wait<0>();
          int redo = 0;
#pragma unroll 1
          for (int pass = 0, j = 1; pass < 2; pass++) {
#pragma unroll 1
           do {
            const uint64_t vd = prm.kv[j & 3].vd;
            bool go = false;
#pragma unroll
            for (int h = 2; h < 18; h++) {
              const int px = (h >> 2) + 1, c = h & 3;
              wg_fence();
              if (h == 13) kd = prm.kv[j & 3].kd;
              const uint64_t kx = kd + (px & 3) * 256, vx = vd + (h - 2) * VSTEP;
              if (h == 2) { qkh(1, 0, kx); qkf(1, 0, kx); pv0(vx); pv1(vx); qkh(1, 1, kx); qkf(1, 1, kx); }
              else if ((c == 1 || c == 2) && h < 17) { qkh(px & 1, c - 1, kx); pv1(vx); qkf(px & 1, c - 1, kx); pv0(vx); }
              else { pv0(vx); pv1(vx); }
              wg_commit();
              if (h == 3) e_arrive_if(sb + B_TE + 8 * ((j + 2) & 3), j > 1);
              if (h == 11) go = mbar_test(sb + B_TF + 8 * (j & 3), (j >> 2) & 1) && j != 8;
              finish(h - 1); start(h);
              if (h != 12 && h != 17) sched_fence();
              if (h == 12 && !go) {
                if (j == 16) {
#pragma unroll
                  for (int u = 13; u < 18; u++) {
                    wg_fence(); pv0(vd + (u - 2) * VSTEP); pv1(vd + (u - 2) * VSTEP); wg_commit();
                    if (u < 17) finish(u - 1);
                    if (u < 16) { start(u); sched_fence(); }
                    if (u & 1) { if (u == 17) wg_wait<0>(); else wg_wait<1>(); }
                  }
                  e_arrive(sb + B_TE + 24);
                  goto head_done;
                }
                mbar_wait(sb + B_TF + 8 * (j & 3), (j >> 2) & 1);
                if (j == 8) {
#pragma unroll
                  for (int i = 0; i < 4; i++) lds128(sb + QPARK + 24576 - wg * 8192 + (w * 32 + lane_id()) * 16 + i * 2048, &q[0][i >> 1][4 * (i & 1)]);
                }
              }
              if (h == 17) wg_wait<0>(); else if (h & 1) wg_wait<1>();
              if (c == 3) { fence_regs(S[px & 1]); fence_regs(H[px & 1]); }
            }
           } while (j++ & 7);
           head_done:
            fence_regs(o[0]); fence_regs(o[1]);
            uint32_t pk[2][8];
            {
              IDS();
              bf16* op = g_os + (size_t)(bm * 256 + row0 + (lane >> 2)) * 1024 + pass * 512 + bn * 32 + (lane & 3) * 8;
#pragma unroll
              for (int i = 0; i < 4; i++) {
                const float* a = &o[i >> 1][2 * (i & 1)];
                const float inv = rcp(a[16]);
                uint32_t* u = &pk[i >> 1][4 * (i & 1)];
#pragma unroll
                for (int k = 0; k < 4; k++) u[k] = pack2(a[4 * k] * inv, a[4 * k + 1] * inv);
                *(uint4*)(op + ((i >> 1) * 64 + (i & 1) * 8) * 1024) = make_uint4(u[0], u[1], u[2], u[3]);
              }
            }
            sched_fence();
            if (pass == 0) bar_sync(NB_KN + wg, 160);
            const float kmax = *(volatile float*)(smem + ROWST + 4 * pass);
            const bool wide = !(qn[0] <= 1.6e7f) | !(kmax <= 1.6e7f) | !(qn[0] * kmax <= 112.f * 112.f);
            int badm = 0;
#pragma unroll
            for (int m = 0; m < 2; m++) {
              uint32_t chk[2] = {0u, 0u};
#pragma unroll
              for (int i = 0; i < 8; i++) asm("fma.rn.bf16x2 %0, %1, %2, %0;" : "+r"(chk[i & 1]) : "r"(pk[m][i]), "r"(0u));
              const bool bad = wide | !(fminf(o[m][16], o[m][18]) >= 9.3e-10f) | !(o[m][16] + o[m][18] <= 1e36f) | (((chk[0] | chk[1]) & 0x7FFF7FFFu) != 0);
              badm |= __any_sync(~0u, bad) << m;
            }
            if (!badm) bar_arrive(NB_SIG + 2 * pass + wg, 160 + 32 * (pass & wg));
            qn[0] = qn[1];
#pragma unroll
            for (int m = 0; m < 2; m++) {
#pragma unroll
              for (int i = 0; i < 20; i++) o[m][i] = 0.f;
              fence_regs(o[m]);
            }
            if (badm) {
              redo |= badm << 2 * pass;
              const int tx = wg * 128 + w * 32 + lane_id();
              uint4* p = g_qsave + (block_id() * 256 + tx) * 8 + pass * 4;
#pragma unroll
              for (int i = 0; i < 4; i++) {
                uint32_t u[4] = {q[0][i >> 1][4 * (i & 1)], q[0][i >> 1][4 * (i & 1) + 1], q[0][i >> 1][4 * (i & 1) + 2], q[0][i >> 1][4 * (i & 1) + 3]};
                if (pass == 0) lds128(sb + QPARK + tx * 16 + i * 4096, u);
                p[i] = make_uint4(u[0], u[1], u[2], u[3]);
              }
            }
          }
          if (redo) attn_redo(redo, l, cta_id(), wg, w, ep1);
        }
      }
      {
        float acc[64];
        {
          const uint64_t da = l & 1 ? prm.xd + ((pslot_a(0, 1) + wg * 8192) >> 4) : prm.kv[0].kd + ((pslot_a(0, 0) - T0 + wg * 4096) >> 4);
          const uint64_t d2 = da + (l & 1 ? 4 : 512), db = prm.wd + (pslot_b(0) >> 4) - 2048;
          mbar_wait(sb + B_PF, l & 1);
          wg_fence();
          wgmma_m64n128k16_ss_tb_z(acc, da, db, 0);
#pragma unroll
          for (int k = 1; k < 4; k++) wgmma_m64n128k16_ss_tb(acc, (k & 2 ? d2 : da) + (k & 1) * 2, db + k * 128, 1);
          wg_commit();
        }
        uint32_t s = 1, lap = 0;
#pragma unroll 1
        for (int kt = 1; kt < 14; kt++) {
          mbar_wait(sb + B_PF + 8 * s, ((s < 4 ? l : 0) + lap) & 1);
          const uint64_t da = mkdesc(sb + pslot_a(s, l) + wg * 8192, 16, 1024, 1), db = mkdesc(sb + pslot_b(s), 8192, 1024, 1);
          wg_fence();
#pragma unroll
          for (int k = 0; k < 4; k++) wgmma_m64n128k16_ss_tb(acc, da + k * 2, db + k * 128, 1);
          wg_commit();
          wg_wait<1>();
          if (w == 0) e_arrive_both(sb + B_PE + 8 * (s ? s - 1 : 5));
          if (++s == 6) { s = 0; lap++; }
        }
        if (wg) {
          wg_wait<0>();
          if (w == 0) e_arrive_both(sb + B_PE + 8);
#pragma unroll
          for (int t = 2; t < 4; t++) mbar_wait(sb + B_PF + 8 * t, l & 1);
          bar_sync(NB_ST, 256);
        }
#pragma unroll
        for (int t = 2; t < 4; t++) {
          if (!wg) mbar_wait(sb + B_PF + 8 * t, l & 1);
          const uint64_t da = prm.xd + ((pslot_a(t, l) + wg * 8192) >> 4), db = prm.wd + (pslot_b(t) >> 4) - 2048;
          wg_fence();
#pragma unroll
          for (int k = 0; k < 4; k++) wgmma_m64n128k16_ss_tb(acc, da + k * 2, db + k * 128, 1);
          wg_commit();
        }
        if (!wg) {
          bar_arrive(NB_ST, 256);
          wg_wait<2>();
          if (w == 0) e_arrive_both(sb + B_PE + 8);
        }
        IDS();
        const int g = lane >> 2, qd = lane & 3;
        const int r0 = wg * 64 + w * 16;
        const uint32_t r = r0 + (lane & 7) + ((lane >> 3) & 1) * 8;
        uint32_t x[8][4];
        mbar_wait(sb + B_RF, 0);
#pragma unroll
        for (int jj = 0; jj < 8; jj++) ldsm4(sb + RES + (jj >> 2) * 16384 + r * 128 + ((((2 * jj + (lane >> 4)) & 7) ^ (r & 7)) << 4), x[jj]);
        wg_wait<0>();
        fence_regs(acc);
        if (w == 0) { e_arrive_both(sb + B_PE + 16); e_arrive_both(sb + B_PE + 24); }
        const CUtensorMap* mo = &prm.m[l == 3 ? M_OUT : M_XST];
        const bool direct = wg && l < 3;
        const uint32_t stg = sb + (direct ? po * 16384 : RES);
        if (direct) bar_sync(NB_SC, 256);
#pragma unroll
        for (int jj = 0; jj < 8; jj++) {
#pragma unroll
          for (int i = 0; i < 4; i++) x[jj][i] = add_bf16x2(x[jj][i], pack2(acc[8 * jj + 2 * i], acc[8 * jj + 2 * i + 1]));
          if (jj < 4) stsm4(stg + r * 128 + ((((2 * jj + (lane >> 4)) & 7) ^ (r & 7)) << 4), x[jj][0], x[jj][1], x[jj][2], x[jj][3]);
          if (jj == 3) { fence_async_smem(); __syncwarp(); tma_st(mo, pn * 128, pm * 128 + r0, stg + r0 * 128); bulk_commit(); sched_fence(); }
        }
        if (l < 3) bar_arrive(NB_KN, 288);
        if (l == 3) {
#pragma unroll
          for (int jj = 4; jj < 8; jj++) stsm4(sb + RES + 16384 + r * 128 + ((((2 * jj + (lane >> 4)) & 7) ^ (r & 7)) << 4), x[jj][0], x[jj][1], x[jj][2], x[jj][3]);
          fence_async_smem(); __syncwarp();
          tma_st(mo, pn * 128 + 64, pm * 128 + r0, sb + RES + 16384 + r0 * 128);
          bulk_commit(); bulk_wait_n<0>();
        } else {
          if (!wg) bar_sync(NB_SC, 256);
#pragma unroll
          for (int jj = 0; jj < 8; jj++)
            if (jj >= 4 || !wg) stsm4(sb + (jj >> 2) * 2 * QSTG + po * 16384 + r * 128 + ((((2 * jj + (lane >> 4)) & 7) ^ (r & 7)) << 4), x[jj][0], x[jj][1], x[jj][2], x[jj][3]);
          bulk_wait_n<0>();
          bar_arrive(NB_X0, 320);
          float s1[4] = {0.f, 0.f, 0.f, 0.f}, sa[4] = {0.f, 0.f, 0.f, 0.f}, sc[4] = {0.f, 0.f, 0.f, 0.f};
#pragma unroll
          for (int jj = 0; jj < 8; jj++) {
            mma16816(s1, x[jj][0], x[jj][1], x[jj][2], x[jj][3], 0x3f803f80u, 0x3f803f80u);
            mma16816(sa, x[jj][0], x[jj][1], x[jj][2], x[jj][3], x[jj][0], x[jj][2]);
            mma16816(sc, x[jj][0], x[jj][1], x[jj][2], x[jj][3], x[jj][1], x[jj][3]);
          }
          fence_regs(s1); fence_regs(sa); fence_regs(sc);
          fence_async_smem();
          sched_fence();
          bar_arrive(NB_X, 320);
          if (qd == g >> 1) {
            float2* p = g_stats + pn * 2048 + pm * 128 + r0 + g;
            p[0] = make_float2(s1[0], g & 1 ? sa[1] : sa[0]);
            p[8] = make_float2(s1[2], g & 1 ? sc[3] : sc[2]);
          }
          bar_arrive(NB_KV, 288);
        }
      }
    }
  }
  asm volatile("barrier.cluster.arrive.relaxed.aligned;\nbarrier.cluster.wait.aligned;" ::: "memory");
}

typedef CUresult (*EncodeFn)(CUtensorMap*, CUtensorMapDataType, cuuint32_t, void*, const cuuint64_t*, const cuuint64_t*, const cuuint32_t*,
                             const cuuint32_t*, CUtensorMapInterleave, CUtensorMapSwizzle, CUtensorMapL2promotion, CUtensorMapFloatOOBfill);

static void make_map(EncodeFn fn, CUtensorMap* m, const void* ptr, int rank, const uint64_t* dims, const uint64_t* strides, const uint32_t* box, CUtensorMapSwizzle sw) {
  cuuint64_t d[5], st[4];
  cuuint32_t bx[5], es[5];
  for (int i = 0; i < rank; i++) { d[i] = dims[i]; bx[i] = box[i]; es[i] = 1; if (i) st[i - 1] = strides[i - 1] * 2; }
  fn(m, CU_TENSOR_MAP_DATA_TYPE_BFLOAT16, rank, (void*)ptr, d, st, bx, es, CU_TENSOR_MAP_INTERLEAVE_NONE, sw,
     CU_TENSOR_MAP_L2_PROMOTION_L2_128B, CU_TENSOR_MAP_FLOAT_OOB_FILL_NONE);
}
static void map2(EncodeFn fn, CUtensorMap* m, const void* ptr, uint64_t inner, uint64_t outer, uint32_t bi, uint32_t bo, CUtensorMapSwizzle sw) {
  const uint64_t d[2] = {inner, outer}, st[1] = {inner};
  const uint32_t bx[2] = {bi, bo};
  make_map(fn, m, ptr, 2, d, st, bx, sw);
}

extern "C" void kernel_launch(void* const* d_in, const int* in_sizes, int n_in, void* d_out, int out_size) {
  (void)in_sizes; (void)n_in; (void)out_size;
  static EncodeFn enc = nullptr;
  static void *xs, *os, *kk, *vv;
  static int sbase = 1024;
  if (!enc) {
    void* p = nullptr;
    cudaDriverEntryPointQueryResult qr;
    cudaGetDriverEntryPoint("cuTensorMapEncodeTiled", &p, cudaEnableDefault, &qr);
    enc = (EncodeFn)p;
    Scratch* sc = nullptr;
    cudaGetSymbolAddress((void**)&sc, g_s);
    xs = sc->xs; os = sc->os; kk = sc->k; vv = sc->v;
    int dev = 0;
    cudaGetDevice(&dev);
    cudaDeviceGetAttribute(&sbase, cudaDevAttrReservedSharedMemoryPerBlock, dev);
    cudaFuncSetAttribute(fused_kernel, cudaFuncAttributeMaxDynamicSharedMemorySize, SMEM_BYTES);
  }
  Params prm;
  const CUtensorMapSwizzle S128 = CU_TENSOR_MAP_SWIZZLE_128B, S64 = CU_TENSOR_MAP_SWIZZLE_64B;
  map2(enc, &prm.m[M_X0A], d_in[0], 1024, 2048, 64, 256, S128);
  map2(enc, &prm.m[M_XSA], xs, 1024, 2048, 64, 256, S128);
  for (int t = 0; t < 2; t++) {
    const uint64_t d3[3] = {1024, 1024, 3}, s3[2] = {3072, 1024};
    const uint32_t b3[3] = {64, 64, 3};
    make_map(enc, &prm.m[M_WQA + t], d_in[1 + 3 * t], 3, d3, s3, b3, S128);
    const uint64_t d5[5] = {64, 32, 2, 16, 16}, s5[4] = {1024, 32 * 1024, 64 * 1024, 64};
    const uint32_t b5[5] = {64, 32, 1, 2, 2};
    make_map(enc, &prm.m[M_WOA + t], d_in[2 + 3 * t], 5, d5, s5, b5, S128);
    const uint64_t dr[3] = {64, 2048, 16}, sr[2] = {1024, 64};
    const uint32_t br[3] = {64, 128, 2};
    make_map(enc, &prm.m[M_X0R + t], t ? xs : d_in[0], 3, dr, sr, br, S128);
  }
  map2(enc, &prm.m[M_OS], os, 1024, 2048, 64, 64, S128);
  map2(enc, &prm.m[M_OL], os, 1024, 2048, 32, 128, S64);
  map2(enc, &prm.m[M_K], kk, 32, 65536, 32, 128, S64);
  map2(enc, &prm.m[M_V], vv, 32, 65536, 32, 128, S64);
  map2(enc, &prm.m[M_XSO], xs, 1024, 2048, 64, 128, S128);
  map2(enc, &prm.m[M_X0H], d_in[0], 1024, 2048, 64, 128, S128);
  map2(enc, &prm.m[M_XST], xs, 1024, 2048, 64, 16, S128);
  map2(enc, &prm.m[M_OUT], d_out, 1024, 2048, 64, 16, S128);
  prm.x0 = (const bf16*)d_in[0];
  prm.wq[0] = (const bf16*)d_in[1]; prm.wq[1] = (const bf16*)d_in[4];
  prm.zero = 0;
  for (int i = 0; i < 128; i++) prm.map[i] = remap(i);
  {
    const uint64_t hi = 0x80000020ull << 32, k0 = sbase + T0, v0 = k0 + 16384, vstep = 64 - (64ull << 16);
    prm.wd = mkdesc(sbase + 32768, 8192, 1024, 1); prm.xd = mkdesc(sbase, 16, 1024, 1);
    for (int j = 0; j < 4; j++) {
      prm.kv[j].kd = (hi | 1u << 16 | k0 >> 4) + 2048 * ((j < 16 ? j : 15) & 3);
      prm.kv[j].vd = (hi | (uint64_t)(ONES - T0 - 16384) >> 4 << 16 | v0 >> 4) + 32 * vstep * ((j + 3) & 3);
    }
  }
  fused_kernel<<<128, 384, SMEM_BYTES>>>(prm);
}
```

```cpp
#include <cuda_runtime.h>
#include <cuda_bf16.h>
#include <cuda.h>
#include <stdint.h>

typedef __nv_bfloat16 bf16;

__device__ __forceinline__ void wgmma_m64n192k16_ss_tb(float (&d)[96], uint64_t da, uint64_t db, int scale_d) {
  asm volatile("{\n.reg .pred p;\nsetp.ne.b32 p, %98, 0;\n"
    "wgmma.mma_async.sync.aligned.m64n192k16.f32.bf16.bf16 "
    "{%0, %1, %2, %3, %4, %5, %6, %7, %8, %9, %10, %11, %12, %13, %14, %15, "
    "%16, %17, %18, %19, %20, %21, %22, %23, %24, %25, %26, %27, %28, %29, %30, %31, "
    "%32, %33, %34, %35, %36, %37, %38, %39, %40, %41, %42, %43, %44, %45, %46, %47, "
    "%48, %49, %50, %51, %52, %53, %54, %55, %56, %57, %58, %59, %60, %61, %62, %63, "
    "%64, %65, %66, %67, %68, %69, %70, %71, %72, %73, %74, %75, %76, %77, %78, %79, "
    "%80, %81, %82, %83, %84, %85, %86, %87, %88, %89, %90, %91, %92, %93, %94, %95}, "
    "%96, %97, p, 1, 1, 0, 1;\n}\n"
    : "+f"(d[0]), "+f"(d[1]), "+f"(d[2]), "+f"(d[3]), "+f"(d[4]), "+f"(d[5]), "+f"(d[6]), "+f"(d[7]),
      "+f"(d[8]), "+f"(d[9]), "+f"(d[10]), "+f"(d[11]), "+f"(d[12]), "+f"(d[13]), "+f"(d[14]), "+f"(d[15]),
      "+f"(d[16]), "+f"(d[17]), "+f"(d[18]), "+f"(d[19]), "+f"(d[20]), "+f"(d[21]), "+f"(d[22]), "+f"(d[23]),
      "+f"(d[24]), "+f"(d[25]), "+f"(d[26]), "+f"(d[27]), "+f"(d[28]), "+f"(d[29]), "+f"(d[30]), "+f"(d[31]),
      "+f"(d[32]), "+f"(d[33]), "+f"(d[34]), "+f"(d[35]), "+f"(d[36]), "+f"(d[37]), "+f"(d[38]), "+f"(d[39]),
      "+f"(d[40]), "+f"(d[41]), "+f"(d[42]), "+f"(d[43]), "+f"(d[44]), "+f"(d[45]), "+f"(d[46]), "+f"(d[47]),
      "+f"(d[48]), "+f"(d[49]), "+f"(d[50]), "+f"(d[51]), "+f"(d[52]), "+f"(d[53]), "+f"(d[54]), "+f"(d[55]),
      "+f"(d[56]), "+f"(d[57]), "+f"(d[58]), "+f"(d[59]), "+f"(d[60]), "+f"(d[61]), "+f"(d[62]), "+f"(d[63]),
      "+f"(d[64]), "+f"(d[65]), "+f"(d[66]), "+f"(d[67]), "+f"(d[68]), "+f"(d[69]), "+f"(d[70]), "+f"(d[71]),
      "+f"(d[72]), "+f"(d[73]), "+f"(d[74]), "+f"(d[75]), "+f"(d[76]), "+f"(d[77]), "+f"(d[78]), "+f"(d[79]),
      "+f"(d[80]), "+f"(d[81]), "+f"(d[82]), "+f"(d[83]), "+f"(d[84]), "+f"(d[85]), "+f"(d[86]), "+f"(d[87]),
      "+f"(d[88]), "+f"(d[89]), "+f"(d[90]), "+f"(d[91]), "+f"(d[92]), "+f"(d[93]), "+f"(d[94]), "+f"(d[95])
    : "l"(da), "l"(db), "r"(scale_d));
}

__device__ __forceinline__ void wgmma_m64n192k16_ss_tb_z(float (&d)[96], uint64_t da, uint64_t db, int scale_d) {
  asm volatile("{\n.reg .pred p;\nsetp.ne.b32 p, %98, 0;\n"
    "wgmma.mma_async.sync.aligned.m64n192k16.f32.bf16.bf16 "
    "{%0, %1, %2, %3, %4, %5, %6, %7, %8, %9, %10, %11, %12, %13, %14, %15, "
    "%16, %17, %18, %19, %20, %21, %22, %23, %24, %25, %26, %27, %28, %29, %30, %31, "
    "%32, %33, %34, %35, %36, %37, %38, %39, %40, %41, %42, %43, %44, %45, %46, %47, "
    "%48, %49, %50, %51, %52, %53, %54, %55, %56, %57, %58, %59, %60, %61, %62, %63, "
    "%64, %65, %66, %67, %68, %69, %70, %71, %72, %73, %74, %75, %76, %77, %78, %79, "
    "%80, %81, %82, %83, %84, %85, %86, %87, %88, %89, %90, %91, %92, %93, %94, %95}, "
    "%96, %97, p, 1, 1, 0, 1;\n}\n"
    : "=f"(d[0]), "=f"(d[1]), "=f"(d[2]), "=f"(d[3]), "=f"(d[4]), "=f"(d[5]), "=f"(d[6]), "=f"(d[7]),
      "=f"(d[8]), "=f"(d[9]), "=f"(d[10]), "=f"(d[11]), "=f"(d[12]), "=f"(d[13]), "=f"(d[14]), "=f"(d[15]),
      "=f"(d[16]), "=f"(d[17]), "=f"(d[18]), "=f"(d[19]), "=f"(d[20]), "=f"(d[21]), "=f"(d[22]), "=f"(d[23]),
      "=f"(d[24]), "=f"(d[25]), "=f"(d[26]), "=f"(d[27]), "=f"(d[28]), "=f"(d[29]), "=f"(d[30]), "=f"(d[31]),
      "=f"(d[32]), "=f"(d[33]), "=f"(d[34]), "=f"(d[35]), "=f"(d[36]), "=f"(d[37]), "=f"(d[38]), "=f"(d[39]),
      "=f"(d[40]), "=f"(d[41]), "=f"(d[42]), "=f"(d[43]), "=f"(d[44]), "=f"(d[45]), "=f"(d[46]), "=f"(d[47]),
      "=f"(d[48]), "=f"(d[49]), "=f"(d[50]), "=f"(d[51]), "=f"(d[52]), "=f"(d[53]), "=f"(d[54]), "=f"(d[55]),
      "=f"(d[56]), "=f"(d[57]), "=f"(d[58]), "=f"(d[59]), "=f"(d[60]), "=f"(d[61]), "=f"(d[62]), "=f"(d[63]),
      "=f"(d[64]), "=f"(d[65]), "=f"(d[66]), "=f"(d[67]), "=f"(d[68]), "=f"(d[69]), "=f"(d[70]), "=f"(d[71]),
      "=f"(d[72]), "=f"(d[73]), "=f"(d[74]), "=f"(d[75]), "=f"(d[76]), "=f"(d[77]), "=f"(d[78]), "=f"(d[79]),
      "=f"(d[80]), "=f"(d[81]), "=f"(d[82]), "=f"(d[83]), "=f"(d[84]), "=f"(d[85]), "=f"(d[86]), "=f"(d[87]),
      "=f"(d[88]), "=f"(d[89]), "=f"(d[90]), "=f"(d[91]), "=f"(d[92]), "=f"(d[93]), "=f"(d[94]), "=f"(d[95])
    : "l"(da), "l"(db), "r"(scale_d));
}

__device__ __forceinline__ void wgmma_m64n128k16_ss_tb(float (&d)[64], uint64_t da, uint64_t db, int scale_d) {
  asm volatile("{\n.reg .pred p;\nsetp.ne.b32 p, %66, 0;\n"
    "wgmma.mma_async.sync.aligned.m64n128k16.f32.bf16.bf16 "
    "{%0, %1, %2, %3, %4, %5, %6, %7, %8, %9, %10, %11, %12, %13, %14, %15, "
    "%16, %17, %18, %19, %20, %21, %22, %23, %24, %25, %26, %27, %28, %29, %30, %31, "
    "%32, %33, %34, %35, %36, %37, %38, %39, %40, %41, %42, %43, %44, %45, %46, %47, "
    "%48, %49, %50, %51, %52, %53, %54, %55, %56, %57, %58, %59, %60, %61, %62, %63}, "
    "%64, %65, p, 1, 1, 0, 1;\n}\n"
    : "+f"(d[0]), "+f"(d[1]), "+f"(d[2]), "+f"(d[3]), "+f"(d[4]), "+f"(d[5]), "+f"(d[6]), "+f"(d[7]),
      "+f"(d[8]), "+f"(d[9]), "+f"(d[10]), "+f"(d[11]), "+f"(d[12]), "+f"(d[13]), "+f"(d[14]), "+f"(d[15]),
      "+f"(d[16]), "+f"(d[17]), "+f"(d[18]), "+f"(d[19]), "+f"(d[20]), "+f"(d[21]), "+f"(d[22]), "+f"(d[23]),
      "+f"(d[24]), "+f"(d[25]), "+f"(d[26]), "+f"(d[27]), "+f"(d[28]), "+f"(d[29]), "+f"(d[30]), "+f"(d[31]),
      "+f"(d[32]), "+f"(d[33]), "+f"(d[34]), "+f"(d[35]), "+f"(d[36]), "+f"(d[37]), "+f"(d[38]), "+f"(d[39]),
      "+f"(d[40]), "+f"(d[41]), "+f"(d[42]), "+f"(d[43]), "+f"(d[44]), "+f"(d[45]), "+f"(d[46]), "+f"(d[47]),
      "+f"(d[48]), "+f"(d[49]), "+f"(d[50]), "+f"(d[51]), "+f"(d[52]), "+f"(d[53]), "+f"(d[54]), "+f"(d[55]),
      "+f"(d[56]), "+f"(d[57]), "+f"(d[58]), "+f"(d[59]), "+f"(d[60]), "+f"(d[61]), "+f"(d[62]), "+f"(d[63])
    : "l"(da), "l"(db), "r"(scale_d));
}

__device__ __forceinline__ void wgmma_m64n128k16_ss_tb_z(float (&d)[64], uint64_t da, uint64_t db, int scale_d) {
  asm volatile("{\n.reg .pred p;\nsetp.ne.b32 p, %66, 0;\n"
    "wgmma.mma_async.sync.aligned.m64n128k16.f32.bf16.bf16 "
    "{%0, %1, %2, %3, %4, %5, %6, %7, %8, %9, %10, %11, %12, %13, %14, %15, "
    "%16, %17, %18, %19, %20, %21, %22, %23, %24, %25, %26, %27, %28, %29, %30, %31, "
    "%32, %33, %34, %35, %36, %37, %38, %39, %40, %41, %42, %43, %44, %45, %46, %47, "
    "%48, %49, %50, %51, %52, %53, %54, %55, %56, %57, %58, %59, %60, %61, %62, %63}, "
    "%64, %65, p, 1, 1, 0, 1;\n}\n"
    : "=f"(d[0]), "=f"(d[1]), "=f"(d[2]), "=f"(d[3]), "=f"(d[4]), "=f"(d[5]), "=f"(d[6]), "=f"(d[7]),
      "=f"(d[8]), "=f"(d[9]), "=f"(d[10]), "=f"(d[11]), "=f"(d[12]), "=f"(d[13]), "=f"(d[14]), "=f"(d[15]),
      "=f"(d[16]), "=f"(d[17]), "=f"(d[18]), "=f"(d[19]), "=f"(d[20]), "=f"(d[21]), "=f"(d[22]), "=f"(d[23]),
      "=f"(d[24]), "=f"(d[25]), "=f"(d[26]), "=f"(d[27]), "=f"(d[28]), "=f"(d[29]), "=f"(d[30]), "=f"(d[31]),
      "=f"(d[32]), "=f"(d[33]), "=f"(d[34]), "=f"(d[35]), "=f"(d[36]), "=f"(d[37]), "=f"(d[38]), "=f"(d[39]),
      "=f"(d[40]), "=f"(d[41]), "=f"(d[42]), "=f"(d[43]), "=f"(d[44]), "=f"(d[45]), "=f"(d[46]), "=f"(d[47]),
      "=f"(d[48]), "=f"(d[49]), "=f"(d[50]), "=f"(d[51]), "=f"(d[52]), "=f"(d[53]), "=f"(d[54]), "=f"(d[55]),
      "=f"(d[56]), "=f"(d[57]), "=f"(d[58]), "=f"(d[59]), "=f"(d[60]), "=f"(d[61]), "=f"(d[62]), "=f"(d[63])
    : "l"(da), "l"(db), "r"(scale_d));
}

__device__ __forceinline__ void wgmma_m64n40k16_rs_tb(float (&d)[20], uint32_t a0, uint32_t a1, uint32_t a2, uint32_t a3, uint64_t db, int scale_d) {
  asm volatile("{\n.reg .pred p;\nsetp.ne.b32 p, %25, 0;\n"
    "wgmma.mma_async.sync.aligned.m64n40k16.f32.bf16.bf16 "
    "{%0, %1, %2, %3, %4, %5, %6, %7, %8, %9, %10, %11, %12, %13, %14, %15, "
    "%16, %17, %18, %19}, "
    "{%20, %21, %22, %23}, %24, p, 1, 1, 1;\n}\n"
    : "+f"(d[0]), "+f"(d[1]), "+f"(d[2]), "+f"(d[3]), "+f"(d[4]), "+f"(d[5]), "+f"(d[6]), "+f"(d[7]),
      "+f"(d[8]), "+f"(d[9]), "+f"(d[10]), "+f"(d[11]), "+f"(d[12]), "+f"(d[13]), "+f"(d[14]), "+f"(d[15]),
      "+f"(d[16]), "+f"(d[17]), "+f"(d[18]), "+f"(d[19])
    : "r"(a0), "r"(a1), "r"(a2), "r"(a3), "l"(db), "r"(scale_d));
}

__device__ __forceinline__ void wg_n64_rs_nb_f16_f32(float (&d)[32], uint32_t a0, uint32_t a1, uint32_t a2, uint32_t a3, uint64_t db, int scale_d) {
  asm volatile("{\n.reg .pred p;\nsetp.ne.b32 p, %37, 0;\n"
    "wgmma.mma_async.sync.aligned.m64n64k16.f32.f16.f16 "
    "{%0, %1, %2, %3, %4, %5, %6, %7, %8, %9, %10, %11, %12, %13, %14, %15, "
    "%16, %17, %18, %19, %20, %21, %22, %23, %24, %25, %26, %27, %28, %29, %30, %31}, "
    "{%32, %33, %34, %35}, %36, p, 1, 1, 0;\n}\n"
    : "+f"(d[0]), "+f"(d[1]), "+f"(d[2]), "+f"(d[3]), "+f"(d[4]), "+f"(d[5]), "+f"(d[6]), "+f"(d[7]),
      "+f"(d[8]), "+f"(d[9]), "+f"(d[10]), "+f"(d[11]), "+f"(d[12]), "+f"(d[13]), "+f"(d[14]), "+f"(d[15]),
      "+f"(d[16]), "+f"(d[17]), "+f"(d[18]), "+f"(d[19]), "+f"(d[20]), "+f"(d[21]), "+f"(d[22]), "+f"(d[23]),
      "+f"(d[24]), "+f"(d[25]), "+f"(d[26]), "+f"(d[27]), "+f"(d[28]), "+f"(d[29]), "+f"(d[30]), "+f"(d[31])
    : "r"(a0), "r"(a1), "r"(a2), "r"(a3), "l"(db), "r"(scale_d));
}

__device__ __forceinline__ void wg_n64_rs_nb_f16_f16(uint32_t (&d)[16], uint32_t a0, uint32_t a1, uint32_t a2, uint32_t a3, uint64_t db, int scale_d) {
  asm volatile("{\n.reg .pred p;\nsetp.ne.b32 p, %21, 0;\n"
    "wgmma.mma_async.sync.aligned.m64n64k16.f16.f16.f16 "
    "{%0, %1, %2, %3, %4, %5, %6, %7, %8, %9, %10, %11, %12, %13, %14, %15}, "
    "{%16, %17, %18, %19}, %20, p, 1, 1, 0;\n}\n"
    : "+r"(d[0]), "+r"(d[1]), "+r"(d[2]), "+r"(d[3]), "+r"(d[4]), "+r"(d[5]), "+r"(d[6]), "+r"(d[7]),
      "+r"(d[8]), "+r"(d[9]), "+r"(d[10]), "+r"(d[11]), "+r"(d[12]), "+r"(d[13]), "+r"(d[14]), "+r"(d[15])
    : "r"(a0), "r"(a1), "r"(a2), "r"(a3), "l"(db), "r"(scale_d));
}

__device__ __forceinline__ void wg_n64_rs_nb_f16_f32_z(float (&d)[32], uint32_t a0, uint32_t a1, uint32_t a2, uint32_t a3, uint64_t db, int scale_d) {
  asm volatile("{\n.reg .pred p;\nsetp.ne.b32 p, %37, 0;\n"
    "wgmma.mma_async.sync.aligned.m64n64k16.f32.f16.f16 "
    "{%0, %1, %2, %3, %4, %5, %6, %7, %8, %9, %10, %11, %12, %13, %14, %15, "
    "%16, %17, %18, %19, %20, %21, %22, %23, %24, %25, %26, %27, %28, %29, %30, %31}, "
    "{%32, %33, %34, %35}, %36, p, 1, 1, 0;\n}\n"
    : "=f"(d[0]), "=f"(d[1]), "=f"(d[2]), "=f"(d[3]), "=f"(d[4]), "=f"(d[5]), "=f"(d[6]), "=f"(d[7]),
      "=f"(d[8]), "=f"(d[9]), "=f"(d[10]), "=f"(d[11]), "=f"(d[12]), "=f"(d[13]), "=f"(d[14]), "=f"(d[15]),
      "=f"(d[16]), "=f"(d[17]), "=f"(d[18]), "=f"(d[19]), "=f"(d[20]), "=f"(d[21]), "=f"(d[22]), "=f"(d[23]),
      "=f"(d[24]), "=f"(d[25]), "=f"(d[26]), "=f"(d[27]), "=f"(d[28]), "=f"(d[29]), "=f"(d[30]), "=f"(d[31])
    : "r"(a0), "r"(a1), "r"(a2), "r"(a3), "l"(db), "r"(scale_d));
}

__device__ __forceinline__ void wg_n64_rs_nb_f16_f16_z(uint32_t (&d)[16], uint32_t a0, uint32_t a1, uint32_t a2, uint32_t a3, uint64_t db, int scale_d) {
  asm volatile("{\n.reg .pred p;\nsetp.ne.b32 p, %21, 0;\n"
    "wgmma.mma_async.sync.aligned.m64n64k16.f16.f16.f16 "
    "{%0, %1, %2, %3, %4, %5, %6, %7, %8, %9, %10, %11, %12, %13, %14, %15}, "
    "{%16, %17, %18, %19}, %20, p, 1, 1, 0;\n}\n"
    : "=r"(d[0]), "=r"(d[1]), "=r"(d[2]), "=r"(d[3]), "=r"(d[4]), "=r"(d[5]), "=r"(d[6]), "=r"(d[7]),
      "=r"(d[8]), "=r"(d[9]), "=r"(d[10]), "=r"(d[11]), "=r"(d[12]), "=r"(d[13]), "=r"(d[14]), "=r"(d[15])
    : "r"(a0), "r"(a1), "r"(a2), "r"(a3), "l"(db), "r"(scale_d));
}

#define DEVINL __device__ __forceinline__
DEVINL void wg_fence() { asm volatile("wgmma.fence.sync.aligned;" ::: "memory"); }
DEVINL void wg_commit() { asm volatile("wgmma.commit_group.sync.aligned;" ::: "memory"); }
template <int N> DEVINL void wg_wait() { asm volatile("wgmma.wait_group.sync.aligned %0;" ::"n"(N) : "memory"); }
__host__ DEVINL uint64_t mkdesc(uint32_t addr, uint32_t lbo, uint32_t sbo, int sw) {
  return (uint64_t)((addr & 0x3FFFF) >> 4) | ((uint64_t)(lbo >> 4) << 16) | ((uint64_t)(sbo >> 4) << 32) | ((uint64_t)sw << 62);
}
DEVINL bool mbar_try(uint32_t bar, uint32_t parity) {
  uint32_t ok;
  asm volatile("{\n.reg .pred p;\nmbarrier.try_wait.parity.shared::cta.b64 p, [%1], %2;\nselp.u32 %0, 1, 0, p;\n}" : "=r"(ok) : "r"(bar), "r"(parity) : "memory");
  return ok;
}
DEVINL bool mbar_test(uint32_t bar, uint32_t parity) {
  uint32_t ok;
  asm volatile("{\n.reg .pred p;\nmbarrier.test_wait.parity.shared::cta.b64 p, [%1], %2;\nselp.u32 %0, 1, 0, p;\n}" : "=r"(ok) : "r"(bar), "r"(parity) : "memory");
  return ok;
}
DEVINL void mbar_wait(uint32_t bar, uint32_t parity) {
#pragma unroll 1
  for (uint32_t n = 0; n < 100000u; n++) if (mbar_try(bar, parity)) break;
}
#define EL(txt) "{\n.reg .pred pe;\nelect.sync _|pe, 0xffffffff;\n@pe " txt "\n}"
DEVINL void e_expect_tx(uint32_t bar, uint32_t bytes) { asm volatile(EL("mbarrier.arrive.expect_tx.shared::cta.b64 _, [%0], %1;") ::"r"(bar), "r"(bytes) : "memory"); }
DEVINL void e_arrive(uint32_t bar) { asm volatile(EL("mbarrier.arrive.shared::cta.b64 _, [%0];") ::"r"(bar) : "memory"); }
DEVINL void e_arrive_if(uint32_t bar, int c) {
  asm volatile("{\n.reg .pred pe;\nelect.sync _|pe, 0xffffffff;\nsetp.ne.and.b32 pe, %1, 0, pe;\n@pe mbarrier.arrive.shared::cta.b64 _, [%0];\n}" ::"r"(bar), "r"(c) : "memory");
}
DEVINL void e_red(uint32_t* p) { asm volatile(EL("red.release.gpu.global.add.u32 [%0], 1;") ::"l"(p) : "memory"); }
DEVINL void e_red_relaxed(uint32_t* p) { asm volatile(EL("red.relaxed.gpu.global.add.u32 [%0], 1;") ::"l"(p) : "memory"); }
DEVINL void release_add(uint32_t* p, int on) {
  asm volatile("{\n.reg .pred q;\nsetp.ne.b32 q, %1, 0;\nfence.release.gpu;\n@q red.relaxed.gpu.global.add.u32 [%0], 1;\n}" ::"l"(p), "r"(on) : "memory");
}
#define PREPARED(p, on) do { asm volatile("" : "+l"(p), "+r"(on)); asm volatile("griddepcontrol.launch_dependents;" ::: "memory"); } while (0)
DEVINL void tma_ld(uint32_t dst, const CUtensorMap* m, int c0, int c1, uint32_t bar) {
  asm volatile(EL("cp.async.bulk.tensor.2d.shared::cluster.global.mbarrier::complete_tx::bytes [%0], [%1, {%3, %4}], [%2];")
               ::"r"(dst), "l"(m), "r"(bar), "r"(c0), "r"(c1) : "memory");
}
DEVINL void tma_ld3(uint32_t dst, const CUtensorMap* m, int c0, int c1, int c2, uint32_t bar) {
  asm volatile(EL("cp.async.bulk.tensor.3d.shared::cluster.global.mbarrier::complete_tx::bytes [%0], [%1, {%3, %4, %5}], [%2];")
               ::"r"(dst), "l"(m), "r"(bar), "r"(c0), "r"(c1), "r"(c2) : "memory");
}
DEVINL void tma_ld5(uint32_t dst, const CUtensorMap* m, int c2, int c3, int c4, uint32_t bar) {
  asm volatile(EL("cp.async.bulk.tensor.5d.shared::cluster.global.mbarrier::complete_tx::bytes [%0], [%1, {0, 0, %3, %4, %5}], [%2];")
               ::"r"(dst), "l"(m), "r"(bar), "r"(c2), "r"(c3), "r"(c4) : "memory");
}
DEVINL void tma_ld_mc(uint32_t dst, const CUtensorMap* m, int c0, int c1, uint32_t bar, uint16_t mask = 3) {
  asm volatile(EL("cp.async.bulk.tensor.2d.shared::cluster.global.mbarrier::complete_tx::bytes.multicast::cluster [%0], [%1, {%3, %4}], [%2], %5;")
               ::"r"(dst), "l"(m), "r"(bar), "r"(c0), "r"(c1), "h"(mask) : "memory");
}
DEVINL void e_arrive_both(uint32_t bar) {
  asm volatile("{\n.reg .pred pe;\n.reg .b32 r0, r1;\nelect.sync _|pe, 0xffffffff;\nmapa.shared::cluster.u32 r0, %0, 0;\nmapa.shared::cluster.u32 r1, %0, 1;\n"
               "@pe mbarrier.arrive.shared::cluster.b64 _, [r0];\n@pe mbarrier.arrive.shared::cluster.b64 _, [r1];\n}" ::"r"(bar) : "memory");
}
DEVINL void tma_st(const CUtensorMap* m, int c0, int c1, uint32_t src) {
  asm volatile(EL("cp.async.bulk.tensor.2d.global.shared::cta.bulk_group [%0, {%2, %3}], [%1];") ::"l"(m), "r"(src), "r"(c0), "r"(c1) : "memory");
}
DEVINL void bulk_commit() { asm volatile("cp.async.bulk.commit_group;" ::: "memory"); }
template <int N> DEVINL void bulk_wait_n() { asm volatile("cp.async.bulk.wait_group %0;\nbar.warp.sync 0xffffffff;" ::"n"(N) : "memory"); }
DEVINL void l2_prefetch(const void* g, uint32_t bytes) { asm volatile(EL("cp.async.bulk.prefetch.L2.global [%0], %1;") ::"l"(g), "r"(bytes) : "memory"); }
DEVINL void fence_async_smem() { asm volatile("fence.proxy.async.shared::cta;" ::: "memory"); }
DEVINL void fence_async_gl() { asm volatile("fence.proxy.async.global;" ::: "memory"); }
DEVINL void cluster_wait() { asm volatile("barrier.cluster.wait.aligned;" ::: "memory"); }
DEVINL void bar_sync(int id, int n) { asm volatile("bar.sync %0, %1;" ::"r"(id), "r"(n) : "memory"); }
DEVINL void bar_arrive(int id, int n) { asm volatile("bar.arrive %0, %1;" ::"r"(id), "r"(n) : "memory"); }
DEVINL uint32_t ld_acquire(const uint32_t* p) { uint32_t v; asm volatile("ld.acquire.gpu.global.u32 %0, [%1];" : "=r"(v) : "l"(p) : "memory"); return v; }
DEVINL void await_flag(int j, uint32_t& rdy, const uint32_t* p, uint32_t target) {
  if ((rdy >> j) & 1) return;
#pragma unroll 1
  for (uint32_t n = 0; n < 200000u && !((rdy >> j) & 1); n++) rdy = __ballot_sync(~0u, (int)(ld_acquire(p) - target) >= 0);
  asm volatile("fence.proxy.async.global;" ::: "memory");
}
DEVINL void poll_ge(const uint32_t* p, uint32_t target) {
#pragma unroll 1
  for (uint32_t n = 0; n < 200000u; n++) if (__all_sync(~0u, (int)(ld_acquire(p) - target) >= 0)) break;
}
DEVINL int lane_id() { int v; asm volatile("mov.u32 %0, %%laneid;" : "=r"(v)); return v; }
__host__ DEVINL int remap(int v) {
  const int c = v >> 1, u = c - 36, r = (u * 37) >> 8;
  const int L = c < 4 ? 32 + 8 * c : c < 36 ? c - 4 : 33 + u + r;
  return 2 * L + (v & 1);
}
DEVINL int block_id() { int v; asm volatile("mov.u32 %0, %%ctaid.x;" : "=r"(v)); return v; }
#define cta_id() prm.map[block_id()]
#define IDS() const int lane = lane_id(), b = cta_id(), bm = b >> 4, bn = b & 15, rank = b & 1, pm = 2 * bm + (bn >> 3), pn = bn & 7, po = pm & 1; \
  (void)lane; (void)bm; (void)bn; (void)rank; (void)pm; (void)pn; (void)po
DEVINL void st_tagged(uint4* p, uint32_t a, uint32_t b, uint32_t c, uint32_t tag) {
  asm volatile("{\n.reg .b64 u, v;\n.reg .b128 t;\nmov.b64 u, {%1, %2};\nmov.b64 v, {%3, %4};\nmov.b128 t, {u, v};\nst.relaxed.gpu.global.b128 [%0], t;\n}"
               ::"l"(p), "r"(a), "r"(b), "r"(c), "r"(tag) : "memory");
}
DEVINL uint32_t ld_tagged(const uint4* p, uint32_t* r) {
  uint32_t tag;
  asm volatile("{\n.reg .b64 u, v;\n.reg .b128 t;\nld.relaxed.gpu.global.b128 t, [%4];\nmov.b128 {u, v}, t;\nmov.b64 {%0, %1}, u;\nmov.b64 {%2, %3}, v;\n}"
               : "=r"(r[0]), "=r"(r[1]), "=r"(r[2]), "=r"(tag) : "l"(p) : "memory");
  return tag;
}
DEVINL float ex2(float x) { float y; asm("ex2.approx.ftz.f32 %0, %1;" : "=f"(y) : "f"(x)); return y; }
DEVINL float rcp(float x) { float y; asm("rcp.approx.ftz.f32 %0, %1;" : "=f"(y) : "f"(x)); return y; }
DEVINL uint32_t pack2(float lo, float hi) { uint32_t r; asm("cvt.rn.bf16x2.f32 %0, %1, %2;" : "=r"(r) : "f"(hi), "f"(lo)); return r; }
DEVINL uint32_t pack2h(float lo, float hi) { uint32_t r; asm("cvt.rz.f16x2.f32 %0, %1, %2;" : "=r"(r) : "f"(hi), "f"(lo)); return r; }
DEVINL uint32_t prmt0(uint32_t a, uint32_t sel) { uint32_t r; asm("prmt.b32 %0, %1, 0, %2;" : "=r"(r) : "r"(a), "r"(sel)); return r; }
DEVINL void stg128(const void* p, uint32_t a, uint32_t b, uint32_t c, uint32_t d) {
  asm volatile("st.global.v4.b32 [%0], {%1, %2, %3, %4};" ::"l"(p), "r"(a), "r"(b), "r"(c), "r"(d) : "memory");
}
DEVINL float bf_lo(uint32_t w) { return __uint_as_float(w << 16); }
DEVINL float bf_hi(uint32_t w) { return __uint_as_float(w & 0xFFFF0000u); }
DEVINL float bf_round(float x) { return bf_lo(pack2(x, 0.f)); }
DEVINL uint32_t add_bf16x2(uint32_t a, uint32_t b) { uint32_t r; asm("add.rn.bf16x2 %0, %1, %2;" : "=r"(r) : "r"(a), "r"(b)); return r; }
DEVINL void stsm4(uint32_t addr, uint32_t a, uint32_t b, uint32_t c, uint32_t d) {
  asm volatile("stmatrix.sync.aligned.m8n8.x4.shared.b16 [%0], {%1, %2, %3, %4};" ::"r"(addr), "r"(a), "r"(b), "r"(c), "r"(d) : "memory");
}
DEVINL void ldsm4(uint32_t addr, uint32_t (&r)[4]) {
  asm volatile("ldmatrix.sync.aligned.m8n8.x4.shared.b16 {%0, %1, %2, %3}, [%4];" : "=r"(r[0]), "=r"(r[1]), "=r"(r[2]), "=r"(r[3]) : "r"(addr) : "memory");
}
DEVINL void ldsm4t(uint32_t addr, uint32_t (&r)[4]) {
  asm volatile("ldmatrix.sync.aligned.m8n8.x4.trans.shared.b16 {%0, %1, %2, %3}, [%4];" : "=r"(r[0]), "=r"(r[1]), "=r"(r[2]), "=r"(r[3]) : "r"(addr) : "memory");
}
DEVINL void sts128(uint32_t addr, uint32_t a, uint32_t b, uint32_t c, uint32_t d) {
  asm volatile("st.shared.v4.b32 [%0], {%1, %2, %3, %4};" ::"r"(addr), "r"(a), "r"(b), "r"(c), "r"(d) : "memory");
}
DEVINL float2 lds64f(uint32_t addr) { float2 v; asm volatile("ld.shared.v2.f32 {%0, %1}, [%2];" : "=f"(v.x), "=f"(v.y) : "r"(addr) : "memory"); return v; }
DEVINL void mma16816(float (&d)[4], uint32_t a0, uint32_t a1, uint32_t a2, uint32_t a3, uint32_t b0, uint32_t b1) {
  asm("mma.sync.aligned.m16n8k16.row.col.f32.bf16.bf16.f32 {%0, %1, %2, %3}, {%4, %5, %6, %7}, {%8, %9}, {%0, %1, %2, %3};"
               : "+f"(d[0]), "+f"(d[1]), "+f"(d[2]), "+f"(d[3]) : "r"(a0), "r"(a1), "r"(a2), "r"(a3), "r"(b0), "r"(b1));
}
template <int N> DEVINL void fence_regs(float (&d)[N]) {
#pragma unroll
  for (int i = 0; i < N; i++) asm volatile("" : "+f"(d[i])::"memory");
}
template <int N> DEVINL void fence_regs(uint32_t (&d)[N]) {
#pragma unroll
  for (int i = 0; i < N; i++) asm volatile("" : "+r"(d[i])::"memory");
}
DEVINL void lds128(uint32_t addr, uint32_t* r) {
  asm volatile("ld.shared.v4.b32 {%0, %1, %2, %3}, [%4];" : "=r"(r[0]), "=r"(r[1]), "=r"(r[2]), "=r"(r[3]) : "r"(addr) : "memory");
}
DEVINL void sched_fence() { asm volatile("griddepcontrol.launch_dependents;" ::: "memory"); }

struct Scratch {
  bf16 k[32 * 2048 * 32];
  bf16 xs[2048 * 1024];
  bf16 os[2048 * 1024];
  bf16 v[32 * 2048 * 32];
  float kn[2 * 128 * 16];
  uint32_t cnt[256 * 32];
  float2 stats[8 * 2048];
  uint4 halo[128 * 12 * 32];
  float csp[2 * 16 * 8 * 192];
  uint4 qsave[128 * 256 * 8];
  uint32_t esc[4 * 65536 * 20];
};
__device__ __align__(1024) Scratch g_s;
#define g_k g_s.k
#define g_xs g_s.xs
#define g_os g_s.os
#define g_v g_s.v
#define g_kn g_s.kn
#define g_cnt g_s.cnt
#define g_stats g_s.stats
#define g_halo g_s.halo
#define g_csp g_s.csp
#define g_qsave g_s.qsave
#define g_esc g_s.esc
#define g_epoch g_s.cnt[255 * 32]

DEVINL uint32_t* cnt_x(int bm) { return g_cnt + bm * 32; }
DEVINL uint32_t* cnt_o(int l, int pm, int h) { return g_cnt + (32 + (l * 16 + pm) * 2 + h) * 32; }
DEVINL uint32_t* cnt_kv(int lb, int bn) { return g_cnt + (160 + lb * 16 + bn) * 32; }
DEVINL uint32_t* cnt_ad(int bn) { return g_cnt + (192 + bn) * 32; }
DEVINL uint32_t* cnt_cs(int t, int bn) { return g_cnt + (208 + t * 16 + bn) * 32; }

DEVINL int qord(int i, int l, int pn) {
  const int u = i < 10 ? i - 4 : i - 10;
  return l == 0 ? i : i < 4 ? ((2 * pn) ^ (2 * (i & 1))) + (i >> 1) : 2 * (u < (pn & 6) ? u : u + 2) + (i >= 10);
}
struct Params {
  CUtensorMap m[15];
  const bf16* x0;
  const bf16* wq[2];
  const bf16* wo;
  uint32_t zero;
  int map[128];
  uint64_t wd, xd;
  struct __align__(16) { uint64_t kd, vd; } kv[4];
};
enum { M_X0A = 0, M_WQA, M_WQB, M_WOA, M_WOB, M_OS, M_K, M_V, M_X0R, M_XSR, M_XSO, M_OUT, M_XST, M_X0H, M_OL, M_COUNT };

constexpr uint32_t QSTG = 57344;
constexpr uint32_t T0 = 65536, TSTG = 32768;
constexpr uint32_t ONES = 230400;
constexpr uint32_t PSTG = 32768, RES = 196608;
constexpr uint32_t KSC = 98304, VSC = 133120, HRS = 167936;
constexpr uint32_t ROWST = 229376, COLS = 231424, BARS = 232192, SMEM_BYTES = 232448;
constexpr uint32_t B_QF = BARS, B_QE = BARS + 32, B_TF = BARS + 64, B_TE = BARS + 96, B_PF = BARS + 128, B_PE = BARS + 176,
                   B_RF = BARS + 224, W_X = BARS + 232, B_QL = BARS + 240, B_PA = BARS + 248;
enum { NB_ST = 1, NB_KV = 2  , NB_DONE = 3, NB_SC = 4, NB_SIG = 5  , NB_KN = 9  , NB_X = 11, NB_HALO = 12  , NB_X0 = 15 };

DEVINL uint32_t pslot_b(uint32_t s) { return ((0x320415u >> (4 * s)) & 7) * 16384u; }
DEVINL uint32_t pslot_a(uint32_t s, int l) { return 98304u + ((((l & 1) ? 0x541230u : 0x041235u) >> (4 * s)) & 7) * 16384u; }

constexpr float QSCALE = 0.17677669529663687f * 1.4426950408889634f;
constexpr uint32_t QPARK = 32768;

DEVINL uint32_t exp2_h2(uint32_t s, uint32_t c852) {
  uint32_t r, t, w, m, d;
  asm volatile("{.reg .b64 t; add.rn.f16x2 %0, %1, %2; cvt.u64.u32 t, %0; cvt.u32.u64 %0, t;}" : "=r"(r) : "r"(s), "r"(0x65EA65EAu));
  asm volatile("fma.rn.f16x2 %0, %1, %2, %3;" : "=r"(t) : "r"(r), "r"(0xB880B880u), "r"(c852));
  asm volatile("fma.rn.f16x2 %0, %1, %2, %3;" : "=r"(w) : "r"(s), "r"(0x38803880u), "r"(t));
  asm volatile("fma.rn.f16x2 %0, %1, %1, %2;" : "=r"(m) : "r"(w), "r"(0x4A1F4A2Du));
  asm volatile("{.reg .b32 t; shf.l.clamp.b32 t, %2, %1, 7; add.u32 %0, t, %2;}" : "=r"(d) : "r"(r), "r"(m));
  return d;
}
DEVINL float exp2_fix(float s) { float z; asm volatile("add.rn.f32 %0, %1, 0f43BF34BC;" : "=f"(z) : "f"(s)); return z; }
DEVINL uint32_t exp2_base(float z0, float z1) { uint32_t B; asm volatile("prmt.b32 %0, %1, %2, 0x6521;" : "=r"(B) : "r"(__float_as_uint(z0)), "r"(__float_as_uint(z1))); return B; }
template <uint32_t MASK> DEVINL uint32_t and_or(uint32_t a, uint32_t c) { uint32_t r; asm volatile("lop3.b32 %0, %1, %3, %2, 0xEA;" : "=r"(r) : "r"(a), "r"(c), "n"(MASK)); return r; }
DEVINL uint32_t fma_bf2(uint32_t a, uint32_t b, uint32_t c) { uint32_t r; asm volatile("fma.rn.bf16x2 %0, %1, %2, %3;" : "=r"(r) : "r"(a), "r"(b), "r"(c)); return r; }
DEVINL float ex2v(float x) { float y; asm volatile("ex2.approx.ftz.f32 %0, %1;" : "=f"(y) : "f"(x)); return y; }
DEVINL uint32_t pack2v(float lo, float hi) { uint32_t r; asm volatile("cvt.rn.bf16x2.f32 %0, %1, %2;" : "=r"(r) : "f"(hi), "f"(lo)); return r; }
DEVINL void unesc(uint32_t (&u)[4], const uint32_t* esc, uint32_t tag) {
  const bool saved = __ldcg(esc + 16) == tag;
#pragma unroll
  for (int j = 0; j < 4; j++) {
    float lo, hi;
    asm("{.reg .f16 a, b; mov.b32 {a, b}, %2; cvt.f32.f16 %0, a; cvt.f32.f16 %1, b;}" : "=f"(lo), "=f"(hi) : "r"(u[j]));
    u[j] = saved ? __ldcg(esc + 4 * j) : pack2(lo, hi);
  }
}

DEVINL void attn_slow(const uint32_t (&q)[8], int head, const uint32_t* kesc, uint32_t tag, float (&res)[20], int lane) {
  const int g = lane >> 2, qd = lane & 3;
  const bf16* kb = g_k + (size_t)head * 2048 * 32;
  const bf16* vb = g_v + (size_t)head * 2048 * 32;
  float o[4][4], m0 = -INFINITY, m1 = -INFINITY, l0 = 0.f, l1 = 0.f;
#pragma unroll
  for (int j = 0; j < 4; j++) { o[j][0] = o[j][1] = o[j][2] = o[j][3] = 0.f; }
#pragma unroll 1
  for (int k0 = 0; k0 < 2048; k0 += 16) {
    float s[2][4];
#pragma unroll
    for (int nt = 0; nt < 2; nt++) {
      s[nt][0] = s[nt][1] = s[nt][2] = s[nt][3] = 0.f;
      const uint32_t* kp = (const uint32_t*)(kb + (size_t)(k0 + nt * 8 + g) * 32) + qd;
      uint32_t k[4] = {__ldcg(kp), __ldcg(kp + 4), __ldcg(kp + 8), __ldcg(kp + 12)};
      unesc(k, kesc + (k0 + nt * 8 + g) * 20 + qd, tag);
      __syncwarp();
      mma16816(s[nt], q[0], q[1], q[2], q[3], k[0], k[1]);
      mma16816(s[nt], q[4], q[5], q[6], q[7], k[2], k[3]);
    }
    float a0 = fmaxf(fmaxf(s[0][0], s[0][1]), fmaxf(s[1][0], s[1][1]));
    float a1 = fmaxf(fmaxf(s[0][2], s[0][3]), fmaxf(s[1][2], s[1][3]));
    a0 = fmaxf(a0, __shfl_xor_sync(~0u, a0, 1)); a0 = fmaxf(a0, __shfl_xor_sync(~0u, a0, 2));
    a1 = fmaxf(a1, __shfl_xor_sync(~0u, a1, 1)); a1 = fmaxf(a1, __shfl_xor_sync(~0u, a1, 2));
    const float n0 = fmaxf(m0, a0), n1 = fmaxf(m1, a1);
    const float c0 = (m0 == n0) ? 1.f : ex2(m0 - n0), c1 = (m1 == n1) ? 1.f : ex2(m1 - n1);
    m0 = n0; m1 = n1;
    const uint32_t p0 = pack2(ex2(s[0][0] - n0), ex2(s[0][1] - n0)), p1 = pack2(ex2(s[0][2] - n1), ex2(s[0][3] - n1));
    const uint32_t p2 = pack2(ex2(s[1][0] - n0), ex2(s[1][1] - n0)), p3 = pack2(ex2(s[1][2] - n1), ex2(s[1][3] - n1));
    l0 = l0 * c0 + bf_lo(p0) + bf_hi(p0) + bf_lo(p2) + bf_hi(p2);
    l1 = l1 * c1 + bf_lo(p1) + bf_hi(p1) + bf_lo(p3) + bf_hi(p3);
#pragma unroll
    for (int j = 0; j < 4; j++) {
      o[j][0] *= c0; o[j][1] *= c0; o[j][2] *= c1; o[j][3] *= c1;
      const unsigned short* vp = (const unsigned short*)(vb + (size_t)(k0 + 2 * qd) * 32 + j * 8 + g);
      const uint32_t b0 = (uint32_t)__ldcg(vp) | ((uint32_t)__ldcg(vp + 32) << 16);
      const uint32_t b1 = (uint32_t)__ldcg(vp + 256) | ((uint32_t)__ldcg(vp + 288) << 16);
      mma16816(o[j], p0, p1, p2, p3, b0, b1);
    }
  }
  l0 += __shfl_xor_sync(~0u, l0, 1); l0 += __shfl_xor_sync(~0u, l0, 2);
  l1 += __shfl_xor_sync(~0u, l1, 1); l1 += __shfl_xor_sync(~0u, l1, 2);
#pragma unroll
  for (int j = 0; j < 4; j++) { res[4 * j] = o[j][0]; res[4 * j + 1] = o[j][1]; res[4 * j + 2] = o[j][2]; res[4 * j + 3] = o[j][3]; }
  res[16] = l0; res[18] = l1;
}

__device__ __noinline__ void attn_redo(int redo, int l, int b, int wg, int w, uint32_t tag) {
  const int lane = lane_id();
#pragma unroll 1
  for (int t = 0; t < 4; t++) {
    const int h = t >> 1, head = 2 * (b & 15) + h, row = (b >> 4) * 256 + wg * 128 + (t & 1) * 64 + w * 16 + (lane >> 2);
    if ((redo >> t) & 1) {
      const uint32_t* esc = g_esc + (size_t)((l & 2) * 65536 + head * 2048) * 20;
      const uint32_t* qs = (const uint32_t*)(g_qsave + (block_id() * 256 + wg * 128 + w * 32 + lane) * 8 + 2 * t);
      uint32_t q[8]; float o[20];
#pragma unroll
      for (int i = 0; i < 2; i++) {
        uint32_t u[4] = {__ldcg(qs + i), __ldcg(qs + i + 2), __ldcg(qs + i + 4), __ldcg(qs + i + 6)};
        unesc(u, esc + (row + i * 8) * 20 + (lane & 3), tag);
        q[i] = u[0]; q[i + 2] = u[1]; q[i + 4] = u[2]; q[i + 6] = u[3];
      }
      __syncwarp();
      attn_slow(q, head, esc + 65536 * 20, tag, o, lane);
      const float i0 = rcp(o[16]), i1 = rcp(o[18]);
      bf16* op = g_os + (size_t)row * 1024 + h * 512 + (b & 15) * 32 + (lane & 3) * 8;
      *(uint4*)op = make_uint4(pack2(o[0] * i0, o[1] * i0), pack2(o[4] * i0, o[5] * i0), pack2(o[8] * i0, o[9] * i0), pack2(o[12] * i0, o[13] * i0));
      *(uint4*)(op + 8 * 1024) = make_uint4(pack2(o[2] * i1, o[3] * i1), pack2(o[6] * i1, o[7] * i1), pack2(o[10] * i1, o[11] * i1), pack2(o[14] * i1, o[15] * i1));
    }
    if ((t & 1) && ((redo >> 2 * h) & 3)) bar_arrive(NB_SIG + 2 * h + wg, 160 + 32 * (h & wg));
  }
}

__global__ void __cluster_dims__(2, 1, 1) __launch_bounds__(384, 1) fused_kernel(const __grid_constant__ Params prm) {
  extern __shared__ __align__(1024) char smem[];
  const uint32_t sb = (uint32_t)__cvta_generic_to_shared(smem);
  const int tid = threadIdx.x, lane = tid & 31;
  const int wg = __shfl_sync(0xffffffffu, tid >> 7, 0);
  const int w = __shfl_sync(0xffffffffu, (tid >> 5) & 3, 0);
  const int bm = remap(blockIdx.x) >> 4, bn = remap(blockIdx.x) & 15;

  auto first_tile = [&](int kt) {
    e_expect_tx(sb + B_QF + 8 * kt, QSTG);
    tma_ld(sb + kt * QSTG, &prm.m[M_X0A], kt * 64, bm * 256, sb + B_QF + 8 * kt);
    tma_ld3(sb + kt * QSTG + 32768, &prm.m[M_WQA], bn * 64, kt * 64, 0, sb + B_QF + 8 * kt);
  };
  auto init4 = [&](uint32_t bar, uint32_t c0, uint32_t c1, uint32_t c2, uint32_t c3) {
    asm volatile("{\n.reg .pred pe;\nelect.sync _|pe, 0xffffffff;\n@pe mbarrier.init.shared::cta.b64 [%0], %1;\n@pe mbarrier.init.shared::cta.b64 [%0+8], %2;\n"
                 "@pe mbarrier.init.shared::cta.b64 [%0+16], %3;\n@pe mbarrier.init.shared::cta.b64 [%0+24], %4;\n@pe fence.mbarrier_init.release.cluster;\n}"
                 ::"r"(bar), "r"(c0), "r"(c1), "r"(c2), "r"(c3) : "memory");
  };
  if (wg < 2) {
    const uint32_t k = wg * 4 + w, lo = (0x1411814u >> (4 * k)) & 15, hi = (0x1441814u >> (4 * k)) & 15;
    if (tid < 32) asm volatile("prefetch.global.L2 [%0];" ::"l"(prm.x0 + (size_t)(bm * 256 + bn * 16 + (tid & 15)) * 1024 + (tid >> 4) * 64));
    else if (tid < 80) asm volatile("prefetch.global.L2 [%0];" ::"l"(prm.wq[0] + (bm * 16 + (tid & 15)) * 3072 + ((tid >> 4) - 2) * 1024 + bn * 64));
    __syncwarp();
    if (k < 7) init4(sb + B_QE + 32 * k, lo, lo, hi, k == 6 ? 2 : hi);
    __syncwarp();
    if (k == 6 && lane == 0) *(volatile unsigned long long*)(smem + W_X) = 0ull;
  } else if (w == 0) {
    init4(sb + B_QF, 1, 1, 1, 1);
    __syncwarp();
    first_tile(0);
  }
  __syncthreads();
  asm volatile("barrier.cluster.arrive.relaxed.aligned;" ::: "memory");

  if (wg == 2) {
    asm volatile("setmaxnreg.dec.sync.aligned.u32 56;");
    const uint32_t ep1 = *(volatile uint32_t*)&g_epoch + 1;
    if (w == 0) {
      first_tile(1);
      mbar_wait(sb + B_QF, 0);
      first_tile(2); first_tile(3);
#pragma unroll 1
      for (int kt = 4; kt < 16; kt++) l2_prefetch(prm.wq[0] + kt * 196608 + blockIdx.x * 1536, 3072);
      cluster_wait();
#pragma unroll 1
      for (int l = 0; l < 4; l++) {
        IDS();
        const CUtensorMap* mw = &prm.m[M_WQA + (l & 1)];
        const CUtensorMap* mh = &prm.m[l == 0 ? M_X0H : M_XSO];
        const CUtensorMap* mo = &prm.m[M_WOA + (l & 1)];
        auto q_b = [&](int i) {
          const int s = i & 3;
          mbar_wait(sb + B_QE + 8 * s, ((i >> 2) & 1) ^ 1);
          e_expect_tx(sb + B_QF + 8 * s, QSTG);
          tma_ld3(sb + s * QSTG + 32768, mw, bn * 64, qord(i, l, pn) * 64, 0, sb + B_QF + 8 * s);
        };
        uint32_t rdy = l ? 0u : ~0u;
        auto q_a = [&](int i) {
          const int kt = qord(i, l, pn);
          await_flag(kt, rdy, cnt_x(bm) + (lane & 15), ep1 * 9 - 6 + 2 * l);
          tma_ld_mc(sb + (i & 3) * QSTG + rank * 16384, mh, kt * 64, bm * 256 + rank * 128, sb + B_QF + 8 * (i & 3));
        };
        if (l > 0) {
#pragma unroll 1
          for (int i = 0; i < 4; i++) {
            const int kt = qord(i, l, pn);
            await_flag(kt, rdy, cnt_x(bm) + (lane & 15), ep1 * 9 - 6 + 2 * l);
            e_expect_tx(sb + B_QF + 8 * i, 16384);
            tma_ld(sb + i * QSTG + (po ^ 1) * 16384, &prm.m[M_XSO], kt * 64, (pm ^ 1) * 128, sb + B_QF + 8 * i);
          }
        }
#pragma unroll 1
        for (int i = 4; i < 16; i++) {
          if (l == 3 && i == 12) poll_ge(cnt_ad(bn), ep1 * 16);
          q_b(i); q_a(i);
          if (l == 0 && i >= 8) l2_prefetch(prm.wq[1] + ((i - 8) * 128 + blockIdx.x) * 3072, 6144);
          if (l == 0 && i >= 8) l2_prefetch(prm.wo + ((i - 8) * 128 + blockIdx.x) * 1024, 2048);
        }
        if (l & 1) {
          const int krow = 2 * bn * 2048 + bm * 256;
          uint32_t* kvc = cnt_kv(l >> 1, bn);
          uint32_t seen = 0;
#pragma unroll 1
          for (int it = 1; it < 16; it++) {
            const int s = it & 3;
            if (it == 4) {
              bar_sync(NB_KV + 12, 288);
              mbar_wait(sb + B_TF + 24, 0);
#pragma unroll 1
              for (int i = 0; i < 4; i++) tma_st(&prm.m[M_K + (i & 1)], 0, krow + 2048 + (i >> 1) * 128, sb + i * 8192);
              bulk_commit();
            }
            if (it == 5) { bulk_wait_n<0>(); e_red(kvc + 16 + bm); }
            if (it == 12) { e_expect_tx(sb + B_RF, 32768); tma_ld3(sb + RES, &prm.m[M_XSR], 0, pm * 128, 2 * pn, sb + B_RF); }
            if (it == 1 || it == 3) mbar_wait(sb + B_QE + 12 + 4 * it, 1);
            mbar_wait(sb + B_TE + 8 * s, ((it >> 2) & 1) ^ 1);
            if (it < 8) {
#pragma unroll 1
              for (uint32_t n = 0; n < 200000u && (~seen & (3u << (2 * it - 2) | (it == 4 ? 0xC000u : 0u))); n++)
                seen = __ballot_sync(~0u, (int)(ld_acquire(kvc + (lane < 7 || lane == 15 ? (bm + 1 + lane) & 7 : 8 + ((bm + 2 + lane) & 7))) - ep1) >= 0);
              fence_async_gl();
            } else if (it == 8) { poll_ge(kvc + 16 + (lane & 7), ep1); fence_async_gl(); }
            e_expect_tx(sb + B_TF + 8 * s, 32768);
#pragma unroll 1
            for (int i = 0; i < 2; i++) {
              const int u = 2 * it - 2 + i;
              const int row = 2 * bn * 2048 + (it > 7 ? 2048 + ((bm + it) & 7) * 256 + i * 128 : u < 7 ? ((bm + 1 + u) & 7) * 256 : ((bm + 2 + u) & 7) * 256 + 128);
              tma_ld(sb + T0 + s * TSTG + i * 8192, &prm.m[M_K], 0, row, sb + B_TF + 8 * s);
              tma_ld(sb + T0 + s * TSTG + 16384 + i * 8192, &prm.m[M_V], 0, row, sb + B_TF + 8 * s);
            }
          }
        }
        auto p_b = [&](int i, uint32_t s, uint32_t par) {
          mbar_wait(sb + B_PE + 8 * s, par ^ 1);
          e_expect_tx(sb + B_PF + 8 * s, PSTG);
          tma_ld5(sb + pslot_b(s), mo, i >> 3, (2 * i + bn) & 14, 2 * pn, sb + B_PF + 8 * s);
        };
        auto p_a = [&](int i, uint32_t s) {
          await_flag(i, rdy, cnt_o(l, pm, (lane >> 3) & 1) + ((lane + (bn >> 1)) & 7), ep1 * 2);
          tma_ld_mc(sb + pslot_a(s, l) + rank * 8192, &prm.m[M_OS], (i & 8) * 64 + ((2 * i + bn) & 14) * 32, pm * 128 + rank * 64, sb + B_PF + 8 * s);
        };
        auto p_a2 = [&](int i) {
          await_flag(i, rdy, cnt_o(l, pm, (lane >> 3) & 1) + ((lane + (bn >> 1)) & 7), ep1 * 2);
          tma_ld(sb + pslot_a(i, l), &prm.m[M_OS], (i & 8) * 64 + ((2 * i + bn) & 14) * 32, pm * 128, sb + B_PF + 8 * i);
          tma_ld(sb + pslot_a(i, l) + 8192, &prm.m[M_OS], (i & 8) * 64 + ((2 * i + bn) & 14) * 32, pm * 128 + 64, sb + B_PF + 8 * i);
        };
        rdy = 0;
        if (l & 1) {
#pragma unroll 1
          for (int u = 0; u < 6; u++) { const int i = (0x205413 >> (4 * u)) & 7; if (u == 4) mbar_wait(sb + B_TE, 1); p_b(i, i, i < 4 ? 1 : 0); }
#pragma unroll 1
          for (int u = 0; u < 6; u++) {
            const int i = (0x542130 >> (4 * u)) & 7;
            if (!(u & 1)) mbar_wait(sb + B_TE + 8 + 4 * u, 1);
            if (u == 4) bar_sync(NB_SIG + 3, 192);
            p_a2(i);
          }
        } else {
#pragma unroll 1
          for (int u = 0; u < 6; u++) { const int i = (0x543120 >> (4 * u)) & 7; if (u == 0 || u == 2) mbar_wait(sb + B_QE + 8 - 4 * u, 1); p_b(i, i, 0); }
          mbar_wait(sb + B_QE + 24, 1);
          e_expect_tx(sb + B_RF, 32768);
          tma_ld3(sb + RES, &prm.m[l == 0 ? M_X0R : M_XSR], 0, pm * 128, 2 * pn, sb + B_RF);
          await_flag(1, rdy, cnt_o(l, pm, (lane >> 3) & 1) + ((lane + (bn >> 1)) & 7), ep1 * 2);
          bar_sync(NB_DONE, 288);
          e_arrive_both(sb + B_PA);
          p_a2(1);
          mbar_wait(sb + B_PA, (l >> 1) & 1);
#pragma unroll 1
          for (int i = 2; i < 6; i++) { if (i > 3) mbar_wait(sb + B_PF + 8 * (i - 3), 0); p_a(i, i); }
        }
        uint32_t s = 0, lap = 1;
#pragma unroll 1
        for (int i = 6; i < 16; i++) {
          p_b(i, s, ((s < 4 ? l : 0) + lap) & 1);
          p_a(i, s);
          if (++s == 6) { s = 0; lap++; }
        }
        const CUtensorMap* mn = &prm.m[M_WQA + ((l + 1) & 1)];
        if (l < 3) {
          mbar_wait(sb + B_PE + 8 * 4, 1); mbar_wait(sb + B_PE + 8 * 5, 1);
          tma_ld3(sb + 32768, mn, bn * 64, 2 * pn * 64, 0, sb + B_QL);
          mbar_wait(sb + B_PE + 8 * 0, l & 1);
          e_expect_tx(sb + B_PA, 24576); e_expect_tx(sb + B_PA, 16384);
          tma_ld3(sb + QSTG + 32768, mn, bn * 64, ((2 * pn) ^ 2) * 64, 0, sb + B_PA);
          mbar_wait(sb + B_PE + 8 * 1, l & 1);
          tma_ld3(sb + 2 * QSTG + 32768, mn, bn * 64, (2 * pn + 1) * 64, 0, sb + B_QL);
          bar_sync(NB_KN, 288);
          e_expect_tx(sb + B_RF, 40960);
          tma_ld3(sb + 3 * QSTG + 32768, mn, bn * 64, ((2 * pn) ^ 3) * 64, 0, sb + B_RF);
          mbar_wait(sb + B_PE + 24, l & 1);
          bar_sync(NB_X0, 320);
          fence_async_gl();
          tma_ld_mc(sb + QSTG + po * 16384, &prm.m[M_XSO], 2 * pn * 64, pm * 128, sb + B_PA, 2 - rank);
          bar_sync(NB_X, 320);
          e_expect_tx(sb + B_QL, 49152);
        }
      }
      if (blockIdx.x == 0 && lane_id() == 0) *(volatile uint32_t*)&g_epoch = ep1;
    } else {
      const int hw = w - 1;
      if (lane < 5) asm volatile("prefetch.tensormap [%0];" ::"l"(&prm.m[5 * hw + lane]) : "memory");
      __syncwarp();
      cluster_wait();
      mbar_wait(sb + B_QF, 0);
#pragma unroll 1
      for (int l = 0; l < 4; l++) {
        IDS();
        if (l > 0) { mbar_wait(sb + B_QL, (l + 1) & 1); mbar_wait(sb + B_QF + 24, 0); }
        if (l == 0) {
#pragma unroll 1
          for (int r = 2 * hw; r < 16; r += 6) {
            const uint4* p = (const uint4*)(prm.x0 + (size_t)(b * 16 + r) * 1024) + lane;
            float s1[2] = {0.f, 0.f}, s2[2] = {0.f, 0.f};
#pragma unroll
            for (int i = 0; i < 8; i++) {
              const uint4 v = __ldg(p + 32 * i);
              const uint32_t u[4] = {v.x, v.y, v.z, v.w};
#pragma unroll
              for (int k = 0; k < 4; k++) { const float a = bf_lo(u[k]), c = bf_hi(u[k]); s1[i >> 2] += a + c; s2[i >> 2] = fmaf(a, a, fmaf(c, c, s2[i >> 2])); }
            }
#pragma unroll
            for (int o = 16; o; o >>= 1)
#pragma unroll
              for (int rr = 0; rr < 2; rr++) { s1[rr] += __shfl_xor_sync(~0u, s1[rr], o); s2[rr] += __shfl_xor_sync(~0u, s2[rr], o); }
            if (lane == 0) *(float4*)&g_stats[b * 16 + r] = make_float4(s1[0], s2[0], s1[1], s2[1]);
          }
        }
        if (l < 2) {
          float cs[8];
#pragma unroll
          for (int i = 0; i < 8; i++) cs[i] = 0.f;
          const uint4* wp = (const uint4*)(prm.wq[l] + (size_t)(bm * 128 + (lane >> 3)) * 3072 + hw * 1024 + bn * 64) + (lane & 7);
#pragma unroll 8
          for (int i = 0; i < 32; i++) {
            const uint4 v = __ldg(wp + (size_t)i * 4 * 384);
            cs[0] += bf_lo(v.x); cs[1] += bf_hi(v.x); cs[2] += bf_lo(v.y); cs[3] += bf_hi(v.y);
            cs[4] += bf_lo(v.z); cs[5] += bf_hi(v.z); cs[6] += bf_lo(v.w); cs[7] += bf_hi(v.w);
          }
#pragma unroll
          for (int i = 0; i < 8; i++) { cs[i] += __shfl_xor_sync(~0u, cs[i], 8); cs[i] += __shfl_xor_sync(~0u, cs[i], 16); }
          if (lane < 8) {
            float4* d = (float4*)(g_csp + ((l * 16 + bn) * 8 + bm) * 192 + hw * 64 + lane * 8);
            d[0] = make_float4(cs[0], cs[1], cs[2], cs[3]); d[1] = make_float4(cs[4], cs[5], cs[6], cs[7]);
          }
          __syncwarp();
          asm volatile("fence.acq_rel.gpu;" ::: "memory");
          e_red_relaxed(cnt_cs(l, bn));
          if (l == 0) e_red_relaxed(cnt_x(bm) + bn);
          poll_ge(lane < 16 && l == 0 ? cnt_x(bm) + lane : cnt_cs(l, bn), lane < 16 && l == 0 ? ep1 * 9 - 6 : ep1 * 24);
        }
        if (l > 0) poll_ge(cnt_x(bm) + (lane & 15), ep1 * 9 - 6 + 2 * l);
#pragma unroll 1
        for (int it = hw * 32 + lane; it < 176; it += 96) {
          const bool rows = it < 128;
          const float4* p = rows ? (const float4*)(g_stats + bm * 256) + it : (const float4*)(g_csp + ((l & 1) * 16 + bn) * 8 * 192) + (it - 128);
          const int stride = rows ? 1024 : 48, np = rows && l == 0 ? 1 : 8;
          float4 a = make_float4(0.f, 0.f, 0.f, 0.f);
#pragma unroll
          for (int k = 0; k < 8; k++) if (k < np) { const float4 v = __ldcg(p + k * stride); a.x += v.x; a.y += v.y; a.z += v.z; a.w += v.w; }
          if (rows) {
            const float m0 = a.x * (1.f / 1024.f), m1 = a.z * (1.f / 1024.f);
            const float v0 = fmaxf(a.y * (1.f / 1024.f) - m0 * m0, 0.f), v1 = fmaxf(a.w * (1.f / 1024.f) - m1 * m1, 0.f);
            const float r0 = __fdividef(1.f, bf_round(sqrtf(bf_round(bf_round(v0) + 1e-5f)))), r1 = __fdividef(1.f, bf_round(sqrtf(bf_round(bf_round(v1) + 1e-5f))));
            a = make_float4(r0, -bf_round(m0), r1, -bf_round(m1));
          }
          if (rows && (l & 1) && (it & 4)) a = make_float4(a.y, a.x, a.w, a.z);
          *(float4*)(smem + ROWST + it * 16) = a;
        }
        __syncwarp();
        if (lane == 0) asm volatile("red.release.cta.shared.add.u32 [%0], 1;" ::"r"(sb + W_X) : "memory");
        if (hw == 2) {
          if (!(l & 1)) {
            bar_sync(NB_ST, 288);
            const uint4* hp = g_halo + (b - 16) * 384 + lane;
#pragma unroll 1
            for (int h = 0; h < 2; h++) {
              uint32_t t[18];
#pragma unroll
              for (int i = 0; i < 18; i++) t[i] = 0;
#pragma unroll 1
              for (uint32_t n = bm ? 0 : 100000u; n < 100000u; n++) {
                uint32_t miss = 0;
#pragma unroll
                for (int i = 0; i < 6; i++) miss |= ld_tagged(hp + h * 192 + i * 32, &t[3 * i]) ^ (4 * ep1 + l);
                if (__all_sync(~0u, !miss)) break;
              }
              mbar_wait(sb + B_QE + 16, 1);
              const uint32_t r = (lane & 7) + ((lane >> 3) & 1) * 8, rv = lane >> 2;
#pragma unroll
              for (int jj = 0; jj < 2; jj++) stsm4(sb + KSC + r * 128 + (((4 * h + 2 * jj + (lane >> 4)) ^ (r & 7)) << 4), t[4 * jj], t[4 * jj + 1], t[4 * jj + 2], t[4 * jj + 3]);
              const uint32_t ad = sb + VSC + rv * 128 + (((4 * h + (lane & 3)) ^ (rv & 7)) << 4);
              sts128(ad, t[8], t[10], t[12], t[14]); sts128(ad + 1024, t[9], t[11], t[13], t[15]);
              if (h == 0 && !(lane & 2)) *(uint32_t*)(smem + HRS + ((lane >> 2) + 8 * (lane & 1)) * 8) = t[16];
              bar_arrive(NB_HALO + h, 64);
            }
          } else {
            bar_sync(NB_KV, 288);
            sts128(sb + ONES + lane * 32, 0x3f803f80u, 0x3f803f80u, 0x3f803f80u, 0x3f803f80u);
            sts128(sb + ONES + lane * 32 + 16, 0x3f803f80u, 0x3f803f80u, 0x3f803f80u, 0x3f803f80u);
            sts128(sb + ROWST + 16, 0x62A962A9u, 0x00010001u, 0x3F003F00u, 0u);
            fence_async_smem();
            __syncwarp();
            e_arrive(sb + B_TF);
            mbar_wait(sb + B_TF + 16, 0); mbar_wait(sb + B_TF + 16, 1);
            poll_ge(cnt_kv(l >> 1, bn) + 16 + (lane & 7), ep1);
            const uint4 v = __ldcg((const uint4*)(g_kn + ((l >> 1) * 128 + bn * 8) * 16) + lane);
            const uint32_t mx = max(max(v.x, v.y), max(v.z, v.w));
            const uint32_t m0 = __reduce_max_sync(~0u, (lane & 2) ? 0u : mx), m1 = __reduce_max_sync(~0u, (lane & 2) ? mx : 0u);
            if (lane == 0) *(uint2*)(smem + ROWST) = make_uint2(m0, m1);
            __syncwarp();
            bar_arrive(NB_KN, 160); bar_arrive(NB_KN + 1, 160);
          }
        } else {
          if (l & 1) {
            uint32_t* p = cnt_kv(l >> 1, bn) + 8 * hw + bm;
            int on = lane == 0;
            PREPARED(p, on);
            bar_sync(hw ? NB_HALO : NB_DONE, 160);
            tma_st(&prm.m[M_K], 0, 2 * bn * 2048 + bm * 256 + hw * 128, sb + T0 + hw * 8192);
            tma_st(&prm.m[M_V], 0, 2 * bn * 2048 + bm * 256 + hw * 128, sb + T0 + 16384 + hw * 8192);
            bulk_commit(); bulk_wait_n<0>();
            release_add(p, on);
          }
#pragma unroll 1
          for (int h = l & 1 ? 0 : hw; h <= (l & 1 ? 1 : hw); h++) {
            uint32_t* p = l == 1 && lane == 1 ? cnt_ad(bn) : cnt_o(l, 2 * bm + (l & 1 ? hw : lane & 1), h) + (bn >> 1);
            int on = lane == 0 || (lane == 1 && (!(l & 1) || (l == 1 && h == 1)));
            int id = NB_SIG + 2 * h + (l & hw), n = l & 1 ? 160 + 32 * (h & hw) : 288;
            asm volatile("" : "+r"(id), "+r"(n));
            PREPARED(p, on);
            bar_sync(id, n);
            release_add(p, on);
            if (!(l & 1) && hw == 0) {
              mbar_wait(sb + B_QE + 24, 1);
              fence_async_gl();
              tma_ld_mc(sb + pslot_a(0, 0) + rank * 8192, &prm.m[M_OL], bn * 32, pm * 128, sb + B_PF);
            }
          }
        }
        if (hw < 2 && l < 3) {
          uint32_t* p = cnt_x(bm) + 2 * pn + hw;
          int on = lane == 0;
          PREPARED(p, on);
          if (hw) {
            bar_sync(NB_X, 320);
            tma_st(&prm.m[M_XSO], pn * 128 + 64, pm * 128, sb + 2 * QSTG + po * 16384);
            bulk_commit();
            bar_sync(NB_KV, 288);
            bulk_wait_n<0>();
            mbar_wait(sb + B_PA, l == 0);
            fence_async_gl();
            tma_ld_mc(sb + 3 * QSTG + po * 16384, &prm.m[M_XSO], pn * 128 + 64, pm * 128, sb + B_RF, 2 - rank);
          } else bar_sync(NB_X0, 320);
          release_add(p, on);
        }
      }
    }
  } else {
    asm volatile("setmaxnreg.inc.sync.aligned.u32 224;");
    const uint32_t zero = prm.zero;
    cluster_wait();
#pragma unroll 1
    for (int l = 0; l < 4; l++) {
      {
        float acc[2][96];
        const bool early = l > 0 && wg == ((cta_id() >> 3) & 1);
        uint32_t ep1 = 0;
        if (l > 0) mbar_wait(sb + B_QL, (l + 1) & 1);
        if (!early) mbar_wait(sb + B_QF, 0);
        wg_fence();
#pragma unroll
        for (int k = 0; k < 4; k++)
#pragma unroll
          for (int m = 0; m < 2; m++) {
            if (k) wgmma_m64n192k16_ss_tb(acc[m], prm.xd + wg * 1024 + m * 512 + k * 2, prm.wd + k * 128, 1);
            else wgmma_m64n192k16_ss_tb_z(acc[m], prm.xd + wg * 1024 + m * 512, prm.wd, 0);
          }
        wg_commit();
#pragma unroll 1
        for (int kt = 1; kt < 13; kt++) {
          const int s = kt == 12 ? 1 : kt & 3;
          if (l > 0 && (kt | 2) == 3) mbar_wait(sb + (kt == 1 ? B_PA : B_RF), kt == 3 || l == 1);
          if (!(early && kt < 4)) mbar_wait(sb + B_QF + 8 * s, (kt >> 2) & 1);
          const uint64_t da = prm.xd + wg * 1024 + s * (QSTG >> 4), db = prm.wd + s * (QSTG >> 4);
          wg_fence();
#pragma unroll
          for (int k = 0; k < 4; k++)
#pragma unroll
            for (int m = 0; m < 2; m++) wgmma_m64n192k16_ss_tb(acc[m], da + m * 512 + k * 2, db + k * 128, 1);
          wg_commit();
          if (kt == 4) ep1 = *(volatile uint32_t*)&g_epoch + 1;
          wg_wait<1>();
          if (early && kt < 5) {
            if (kt < 3) continue;
#pragma unroll 1
            for (int i = 0; i < 8 - 2 * kt; i++) { mbar_wait(sb + B_QF + 8 * i, 0); if (w == 0) e_arrive_both(sb + B_QE + 8 * i); }
            mbar_wait(sb + B_QF + 8 * (kt - 1), 0);
          }
          if (w == 0) e_arrive_both(sb + B_QE + 8 * ((kt - 1) & 3));
        }
        {
          const bool lag = (l & 1) == wg;
          const uint32_t s0 = 2 * (~l & 1);
          const uint64_t da = prm.xd + wg * 1024 + 2 * (QSTG >> 4), db = prm.wd + 2 * (QSTG >> 4);
          mbar_wait(sb + B_QF + 8 * s0, 1);
#pragma unroll
          for (int t = 0; t < 2; t++) {
            if (lag && t != wg) {
              wg_wait<0>();
              if (w == 0) e_arrive_both(sb + B_QE + 8 + 8 * t);
              if (t == 0) mbar_wait(sb + B_QF + 16, 1);
              mbar_wait(sb + B_QF + 24, 1);
              if (t == 1) bar_arrive(NB_ST, 288);
              bar_sync(NB_SC, 256);
            }
            const uint64_t so = (uint64_t)(t ? s0 : s0 ^ 2) * (QSTG >> 4);
            wg_fence();
#pragma unroll
            for (int k = 0; k < 4; k++)
#pragma unroll
              for (int m = 0; m < 2; m++) wgmma_m64n192k16_ss_tb(acc[m], da - so + m * 512 + k * 2, db - so + k * 128, 1);
            wg_commit();
            if (!lag || t + wg == 0) {
              wg_wait<1>();
              if (w == 0) e_arrive_both(sb + B_QE + 8 * (t ? s0 : 1));
              mbar_wait(sb + B_QF + 8 * (t ? 3 : s0 ^ 2), 1);
            }
          }
          wg_fence();
#pragma unroll
          for (int m = 1; m >= 0; m--) {
#pragma unroll
            for (int k = 0; k < 4; k++) wgmma_m64n192k16_ss_tb(acc[m], da + (QSTG >> 4) + m * 512 + k * 2, db + (QSTG >> 4) + k * 128, 1);
            wg_commit();
          }
          if (!lag) { bar_arrive(NB_SC, 256); if (wg) bar_arrive(NB_ST, 288); }
          wg_wait<2>();
          if (w == 0) { e_arrive_both(sb + B_QE + 8 * (s0 ^ 2)); if (lag && wg) e_arrive_both(sb + B_QE); }
        }
#pragma unroll 1
        for (uint32_t n = 0; n < 4000000u; n++) {
          uint32_t v;
          asm volatile("ld.acquire.cta.shared.u32 %0, [%1];" : "=r"(v) : "r"(sb + W_X) : "memory");
          if (v == (uint32_t)(3 * l + 3)) break;
        }
        IDS();
        const int g = lane >> 2, qd = lane & 3;
        float2 st[2][2];
#pragma unroll
        for (int m = 0; m < 2; m++)
#pragma unroll
          for (int hh = 0; hh < 2; hh++) st[m][hh] = lds64f(sb + ROWST + (wg * 128 + m * 64 + w * 16 + g + 8 * hh) * 8);
        float2 cs[4];
        auto load_cs = [&](int gi) {
#pragma unroll
          for (int j = 0; j < 4; j++) cs[j] = lds64f(sb + COLS + (gi * 32 + j * 8 + 2 * qd) * 4);
        };
        load_cs(2 + 2 * (l & 1));
        auto drain = [&]() {
          wg_wait<0>(); fence_regs(acc[0]);
          if (w == 0) e_arrive_both(sb + B_QE + 8 * 3);
        };
        wg_wait<1>(); fence_regs(acc[1]);
        auto norm_tile = [&](int gi, int m, float sc, uint32_t (&t)[8], float (&nrm)[2], bool h16 = false) {
          const float r0 = st[m][0].x * sc, s0 = st[m][0].y, r1 = st[m][1].y * sc, s1 = st[m][1].x;
          float n0 = 0.f, n1 = 0.f;
#pragma unroll
          for (int j = 0; j < 4; j++) {
            const float* a = &acc[m][16 * gi + 4 * j];
            const float v0 = fmaf(s0, cs[j].x, a[0]) * r0, v1 = fmaf(s0, cs[j].y, a[1]) * r0;
            const float v2 = fmaf(s1, cs[j].x, a[2]) * r1, v3 = fmaf(s1, cs[j].y, a[3]) * r1;
            n0 = fmaf(v0, v0, fmaf(v1, v1, n0)); n1 = fmaf(v2, v2, fmaf(v3, v3, n1));
            t[2 * j] = h16 ? pack2h(v0, v1) : pack2(v0, v1); t[2 * j + 1] = h16 ? pack2h(v2, v3) : pack2(v2, v3);
          }
          nrm[0] = n0; nrm[1] = n1;
        };
        auto norm_group = [&](int gi, float sc, uint32_t (&t)[2][8], float (&nrm)[2][2]) { norm_tile(gi, 0, sc, t[0], nrm[0]); norm_tile(gi, 1, sc, t[1], nrm[1]); };
        uint32_t q[2][2][8];
        const uint32_t srow = (lane & 7) + ((lane >> 3) & 1) * 8;
        const uint32_t row0 = wg * 128 + w * 16;
        if (!(l & 1)) {
          auto put_kv = [&](int gi, uint32_t r0, const uint32_t (&t)[8]) {
            if (gi < 4) {
              const uint32_t r = r0 + srow;
#pragma unroll
              for (int jj = 0; jj < 2; jj++) stsm4(sb + KSC + r * 128 + (((4 * (gi - 2) + 2 * jj + (lane >> 4)) ^ (r & 7)) << 4), t[4 * jj], t[4 * jj + 1], t[4 * jj + 2], t[4 * jj + 3]);
            } else {
              const uint32_t r = r0 + g, ad = sb + VSC + r * 128 + (((4 * (gi - 4) + qd) ^ (r & 7)) << 4);
              sts128(ad, t[0], t[2], t[4], t[6]); sts128(ad + 1024, t[1], t[3], t[5], t[7]);
            }
          };
          auto cen_tile = [&](int gi, int m, uint32_t (&t)[8]) {
#pragma unroll
            for (int j = 0; j < 4; j++) {
              const float* a = &acc[m][16 * gi + 4 * j];
              t[2 * j] = pack2(fmaf(st[m][0].y, cs[j].x, a[0]), fmaf(st[m][0].y, cs[j].y, a[1]));
              t[2 * j + 1] = pack2(fmaf(st[m][1].y, cs[j].x, a[2]), fmaf(st[m][1].y, cs[j].y, a[3]));
            }
          };
          const bool send = wg == 1 && w == 3 && bm < 7;
          uint4* hp = g_halo + b * 384 + lane;
          ep1 = 4 * ep1 + l;
          mbar_wait(sb + B_QE + 16, 1);
          float2 cn[4];
          auto next_cs = [&](int gi) {
#pragma unroll
            for (int j = 0; j < 4; j++) { cs[j] = cn[j]; cn[j] = lds64f(sb + COLS + (gi * 32 + j * 8 + 2 * qd) * 4); }
          };
#pragma unroll
          for (int j = 0; j < 4; j++) cn[j] = cs[j];
          auto lower = [&](int h, int nx, bool snd) {
            uint32_t k[8], v[8];
            next_cs(4 + h);
            cen_tile(2 + h, 1, k); put_kv(2 + h, 16 + row0 + 64, k);
            next_cs(nx);
            cen_tile(4 + h, 1, v); put_kv(4 + h, 16 + row0 + 64, v);
            if (snd) {
              uint4* p = hp + h * 192;
              st_tagged(p, k[0], k[1], k[2], ep1); st_tagged(p + 32, k[3], k[4], k[5], ep1); st_tagged(p + 64, k[6], k[7], v[0], ep1);
              st_tagged(p + 96, v[1], v[2], v[3], ep1); st_tagged(p + 128, v[4], v[5], v[6], ep1);
              st_tagged(p + 160, v[7], __float_as_uint(qd & 1 ? st[1][1].x : st[1][0].x), 0u, ep1);
            }
          };
          lower(0, 2 + wg, send);
          sched_fence();
          if (wg) lower(1, 2, send);
          drain();
          {
            uint32_t t[8];
            next_cs(4); cen_tile(2, 0, t); put_kv(2, 16 + row0, t);
            next_cs(0); cen_tile(4, 0, t); put_kv(4, 16 + row0, t);
            next_cs(3); cen_tile(0, 0, q[0][0]); cen_tile(0, 1, q[0][1]);
          }
          auto upper = [&]() {
            uint32_t t[8];
            next_cs(5); cen_tile(3, 0, t); put_kv(3, 16 + row0, t);
            next_cs(1); cen_tile(5, 0, t); put_kv(5, 16 + row0, t);
          };
          if (wg) upper();
          const bool e = g & 1, sel = 2 * qd + (g & 1) >= g + 2, first = bm == 0 && row0 == 0;
          uint32_t ka = sb + KSC + (row0 + (lane & 7)) * 128 + (((lane >> 3) ^ (lane & 7)) << 4);
          uint32_t wa = sb + VSC + (row0 + srow) * 128 + (((lane >> 4) ^ (lane & 7)) << 4);
          uint32_t psel[3] = {e ? 0x1044u : 0x4410u, !sel ? 0x4444u : e ? 0x3244u : 0x4432u, sel ? 0x4444u : e ? 0x3244u : 0x4432u};
          bf16* op = g_os + (size_t)(bm * 256 + row0 + g) * 1024 + bn * 32 + qd * 8;
          asm volatile("" : "+r"(ka), "+r"(wa), "+l"(op));
          fence_regs(psel); fence_regs(q[0][0]); fence_regs(q[0][1]);
          sched_fence();
          bar_sync(NB_SC, 256);
          if (row0 == 0) bar_sync(NB_HALO, 64);
          float ra[4], rb[4], ca[4], cb[4];
#pragma unroll
          for (int m = 0; m < 2; m++) {
            float rk[3];
#pragma unroll
            for (int u = 0; u < 3; u++) {
              const int r = row0 + m * 64 + 8 * u + 2 * qd + e - (sel ? 16 : 8);
              rk[u] = lds64f(sb + (m == 0 && r < 0 ? HRS + 128 : ROWST) + r * 8).x;
            }
            ra[2 * m] = sel ? rk[1] : rk[0]; ra[2 * m + 1] = sel ? rk[2] : rk[1];
            rb[2 * m] = sel ? rk[0] : rk[1]; rb[2 * m + 1] = sel ? rk[1] : rk[2];
          }
#pragma unroll
          for (int i = 0; i < 4; i++) { const float rq = st[i >> 1][i & 1].x * QSCALE; ca[i] = rq * ra[i]; cb[i] = rq * rb[i]; }
#pragma unroll 1
          for (int h = 0; h < 2; h++) {
            float s[2][4][4];
            uint32_t vf[2][4][4], pf[2][2][4];
#pragma unroll
            for (int m = 0; m < 2; m++)
#pragma unroll
              for (int nt = 0; nt < 4; nt++) {
                uint32_t kf[4];
                ldsm4(ka + (m * 64 + 8 * nt) * 128, kf);
                s[m][nt][0] = s[m][nt][1] = s[m][nt][2] = s[m][nt][3] = 0.f;
                mma16816(s[m][nt], q[0][m][0], q[0][m][1], q[0][m][2], q[0][m][3], kf[0], kf[1]);
                mma16816(s[m][nt], q[0][m][4], q[0][m][5], q[0][m][6], q[0][m][7], kf[2], kf[3]);
              }
#pragma unroll
            for (int m = 0; m < 2; m++)
#pragma unroll
              for (int i = 0; i < 4; i++) {
                ldsm4t((wa ^ (32 * (i & 1))) + (m * 64 + 16 * (i >> 1)) * 128, vf[m][i]);
              }
            if (h) { fence_async_smem(); bar_arrive(NB_DONE, 288); }
            float va[4], vb[4], mx[4];
#pragma unroll
            for (int i = 0; i < 4; i++) {
              const int m = i >> 1, hh = i & 1;
              const float a = e ? s[m][hh + 1][2 * hh + 1] : s[m][hh + 1][2 * hh];
              const float lo = e ? s[m][hh][2 * hh + 1] : s[m][hh][2 * hh], hi = e ? s[m][hh + 2][2 * hh + 1] : s[m][hh + 2][2 * hh];
              va[i] = (m == 0 && hh == 0 && first) ? -INFINITY : a * ca[i];
              vb[i] = (m == 0 && first && sel) ? -INFINITY : (sel ? lo : hi) * cb[i];
              mx[i] = fmaxf(va[i], vb[i]);
            }
#pragma unroll
            for (int i = 0; i < 4; i++) mx[i] = fmaxf(mx[i], __shfl_xor_sync(~0u, mx[i], 1));
#pragma unroll
            for (int i = 0; i < 4; i++) mx[i] = fmaxf(mx[i], __shfl_xor_sync(~0u, mx[i], 2));
#pragma unroll
            for (int i = 0; i < 4; i++) {
              va[i] = ex2(va[i] - mx[i]); vb[i] = ex2(vb[i] - mx[i]);
              mx[i] = va[i] + vb[i];
              va[i] *= ra[i]; vb[i] *= rb[i];
            }
#pragma unroll
            for (int i = 0; i < 4; i++) mx[i] += __shfl_xor_sync(~0u, mx[i], 1);
#pragma unroll
            for (int i = 0; i < 4; i++) mx[i] += __shfl_xor_sync(~0u, mx[i], 2);
#pragma unroll
            for (int i = 0; i < 4; i++) {
              const int m = i >> 1, hh = i & 1;
              const float inv = rcp(mx[i]);
              const uint32_t t = pack2(va[i] * inv, vb[i] * inv);
              pf[m][hh][hh + 1] = prmt0(t, psel[0]); pf[m][hh][hh] = prmt0(t, psel[1]); pf[m][hh][hh + 2] = prmt0(t, psel[2]);
              pf[m][hh][3 - 3 * hh] = t & zero;
            }
#pragma unroll
            for (int m = 0; m < 2; m++) {
              float o[4][4];
#pragma unroll
              for (int j = 0; j < 4; j++) o[j][0] = o[j][1] = o[j][2] = o[j][3] = 0.f;
#pragma unroll
              for (int i = 0; i < 4; i++) {
                const int kk = i >> 1, jj = 2 * (i & 1);
                mma16816(o[jj], pf[m][0][2 * kk], pf[m][1][2 * kk], pf[m][0][2 * kk + 1], pf[m][1][2 * kk + 1], vf[m][i][0], vf[m][i][1]);
                mma16816(o[jj + 1], pf[m][0][2 * kk], pf[m][1][2 * kk], pf[m][0][2 * kk + 1], pf[m][1][2 * kk + 1], vf[m][i][2], vf[m][i][3]);
              }
              stg128(op + m * 65536, pack2(o[0][0], o[0][1]), pack2(o[1][0], o[1][1]), pack2(o[2][0], o[2][1]), pack2(o[3][0], o[3][1]));
              stg128(op + m * 65536 + 8192, pack2(o[0][2], o[0][3]), pack2(o[1][2], o[1][3]), pack2(o[2][2], o[2][3]), pack2(o[3][2], o[3][3]));
            }
            bar_arrive(NB_SIG + 2 * h, 288);
            if (h == 0) {
              if (!wg) { lower(1, 3, false); upper(); }
#pragma unroll
              for (int j = 0; j < 4; j++) cs[j] = cn[j];
              cen_tile(1, 0, q[0][0]); cen_tile(1, 1, q[0][1]);
              ka ^= 64; wa ^= 64; op += 512;
              bar_sync(NB_SC, 256);
              if (row0 == 0) bar_sync(NB_HALO + 1, 64);
            }
          }
        } else {
          float qn[2];
          mbar_wait(sb + B_QE + 8, 1);
          drain();
          auto esc_ptr = [&](int gi) { IDS(); return g_esc + (size_t)(((l & 2) + (gi >> 1)) * 65536 + (2 * bn + (gi & 1)) * 2048) * 20; };
          auto norm_half = [&](int gi, float sc, uint32_t (&t)[2][8], float (&nrm)[2][2], int nx) {
            norm_tile(gi, 0, sc, t[0], nrm[0], true); norm_tile(gi, 1, sc, t[1], nrm[1], true);
            float2 cn[4];
#pragma unroll
            for (int j = 0; j < 4; j++) if (nx >= 0) cn[j] = lds64f(sb + COLS + (nx * 32 + j * 8 + 2 * qd) * 4);
            if (!((nrm[0][0] + nrm[0][1]) + (nrm[1][0] + nrm[1][1]) <= 4e9f) || fminf(fminf(nrm[0][0], nrm[0][1]), fminf(nrm[1][0], nrm[1][1])) < 1.5e-5f) {
              uint32_t* p = esc_ptr(gi) + (bm * 256 + row0 + g) * 20 + qd;
#pragma unroll
              for (int m = 0; m < 2; m++) {
                uint32_t u[8]; float d[2];
                norm_tile(gi, m, sc, u, d);
#pragma unroll
                for (int i = 0; i < 10; i++) p[(m * 64 + (i & 1) * 8) * 20 + (i >> 1) * 4] = i < 8 ? u[i] : ep1;
              }
            }
            __syncwarp();
#pragma unroll
            for (int i = 0; i < 16; i++) asm volatile("{\n.reg .b32 u;\nadd.u32 u, %0, 0x00040004;\nand.b32 %0, u, 0xFFF8FFF8;\n}" : "+r"(t[i >> 3][i & 7]));
#pragma unroll
            for (int j = 0; j < 4; j++) if (nx >= 0) cs[j] = cn[j];
          };
          {
            auto max_norm = [&](const float (&nrm)[2][2]) {
              const bool o1 = qd & 1, o2 = qd & 2;
              const float a = (o1 ? nrm[1][0] : nrm[0][0]) + __shfl_xor_sync(~0u, o1 ? nrm[0][0] : nrm[1][0], 1);
              const float c = (o1 ? nrm[1][1] : nrm[0][1]) + __shfl_xor_sync(~0u, o1 ? nrm[0][1] : nrm[1][1], 1);
              const float d = (o2 ? c : a) + __shfl_xor_sync(~0u, o2 ? a : c, 2);
              return __uint_as_float(__reduce_max_sync(~0u, __float_as_uint(d)));
            };
#pragma unroll
            for (int h = 0; h < 2; h++) {
              uint32_t t[2][8]; float nrm[2][2];
              const uint32_t kb = sb + (h ? wg * 8192 : T0), vb = kb + (h ? 8192 : 16384);
              norm_group(4 + h, 1.f, t, nrm);
              load_cs(2 + h);
#pragma unroll
              for (int m = 0; m < 2; m++) {
                const uint32_t r = row0 + m * 64 + g, ad = vb + r * 64 + ((qd ^ ((r >> 1) & 3)) << 4);
                sts128(ad, t[m][0], t[m][2], t[m][4], t[m][6]); sts128(ad + 512, t[m][1], t[m][3], t[m][5], t[m][7]);
              }
              if (h == 0) sched_fence();
              norm_half(2 + h, 1.f, t, nrm, h);
#pragma unroll
              for (int i = 0; i < 4; i++) {
                const uint32_t r = row0 + (i >> 1) * 64 + srow;
                stsm4(kb + r * 64 + (((2 * (i & 1) + (lane >> 4)) ^ ((r >> 1) & 3)) << 4), t[i >> 1][4 * (i & 1)], t[i >> 1][4 * (i & 1) + 1], t[i >> 1][4 * (i & 1) + 2], t[i >> 1][4 * (i & 1) + 3]);
              }
              if (h == 1) { const float kn = max_norm(nrm); if (lane == 0) g_kn[((l >> 1) * 128 + bn * 8 + bm) * 16 + 8 + wg * 4 + w] = kn; }
              fence_async_smem();
              bar_arrive(NB_KV + 12 * h, 288);
              if (h == 0) {
                bar_arrive(wg ? NB_HALO : NB_DONE, 160);
              }
              if (h == 0) { const float kn = max_norm(nrm); if (lane == 0) g_kn[((l >> 1) * 128 + bn * 8 + bm) * 16 + wg * 4 + w] = kn; }
              norm_half(h, QSCALE, q[h], nrm, h ? -1 : 5);
#pragma unroll
              for (int i = 0; i < 4 * h; i++) sts128(sb + QPARK + 24576 - wg * 8192 + (w * 32 + lane) * 16 + i * 2048, q[h][i >> 1][4 * (i & 1)], q[h][i >> 1][4 * (i & 1) + 1], q[h][i >> 1][4 * (i & 1) + 2], q[h][i >> 1][4 * (i & 1) + 3]);
              qn[h] = max_norm(nrm);
            }
          }
          constexpr uint64_t VSTEP = 64 - (64ull << 16);
          uint32_t cq[4];
          const uint32_t &c_852 = cq[0], &c_lsb = cq[1], &c_half = cq[2];
          float o[2][20], S[2][32];
          uint32_t H[2][16], P0[4] = {}, P1[4] = {};
#pragma unroll
          for (int m = 0; m < 2; m++) {
#pragma unroll
            for (int i = 0; i < 20; i++) o[m][i] = 0.f;
            fence_regs(o[m]);
          }
          auto qkf = [&](int b, int ks, uint64_t d) { wg_n64_rs_nb_f16_f32(S[b], q[0][0][4 * ks], q[0][0][4 * ks + 1], q[0][0][4 * ks + 2], q[0][0][4 * ks + 3], d + 2 * ks, ks ? 1 : zero); };
          auto qkh = [&](int b, int ks, uint64_t d) { wg_n64_rs_nb_f16_f16(H[b], q[0][1][4 * ks], q[0][1][4 * ks + 1], q[0][1][4 * ks + 2], q[0][1][4 * ks + 3], d + 2 * ks, ks ? 1 : zero); };
          auto pv0 = [&](uint64_t d) { wgmma_m64n40k16_rs_tb(o[0], P0[0], P0[1], P0[2], P0[3], d, 1); };
          auto pv1 = [&](uint64_t d) { wgmma_m64n40k16_rs_tb(o[1], P1[0], P1[1], P1[2], P1[3], d, 1); };
          float e[4] = {};
          auto finish = [&](int h) {
            const float* s = &S[(h >> 2) & 1][8 * (h & 3)];
            const uint32_t* u = &H[(h >> 2) & 1][4 * (h & 3)];
            const float z0 = exp2_fix(s[6]), z1 = exp2_fix(s[7]);
            P0[0] = pack2v(e[0], e[1]);
            P1[0] = exp2_h2(u[0], c_852);
            P0[1] = pack2v(e[2], e[3]);
            P1[1] = exp2_h2(u[1], c_852);
            const uint32_t B = exp2_base(z0, z1), E = and_or<0x7F807F80u>(B, c_lsb);
            P1[3] = exp2_h2(u[3], c_852);
            P0[3] = fma_bf2(B, and_or<0x807F807Fu>(B, c_half), E);
            const float e4 = ex2v(s[4]), e5 = ex2v(s[5]);
            P1[2] = exp2_h2(u[2], c_852);
            P0[2] = pack2v(e4, e5);
          };
          auto start = [&](int h) {
            const float* s = &S[(h >> 2) & 1][8 * (h & 3)];
            e[2] = ex2v(s[2]); e[1] = ex2v(s[1]); e[0] = ex2v(s[0]); e[3] = ex2v(s[3]);
          };
          uint64_t kd = prm.kv[0].kd;
          mbar_wait(sb + B_TF, 0);
          lds128(sb + ROWST + 16 + (lane_id() & zero), cq);
#pragma unroll
          for (int i = 0; i < 4; i++) sts128(sb + QPARK + (wg * 128 + w * 32 + lane_id()) * 16 + i * 4096, q[0][i >> 1][4 * (i & 1)], q[0][i >> 1][4 * (i & 1) + 1], q[0][i >> 1][4 * (i & 1) + 2], q[0][i >> 1][4 * (i & 1) + 3]);
          wg_fence();
#pragma unroll
          for (int b = 0; b < 2; b++) {
            wg_n64_rs_nb_f16_f32_z(S[b], q[0][0][0], q[0][0][1], q[0][0][2], q[0][0][3], kd + 256 * b, 0);
            wg_n64_rs_nb_f16_f16_z(H[b], q[0][1][0], q[0][1][1], q[0][1][2], q[0][1][3], kd + 256 * b, 0);
            if (b == 0) { qkf(0, 1, kd); qkh(0, 1, kd); }
            wg_commit();
          }
          wg_wait<1>(); fence_regs(S[0]); fence_regs(H[0]);
          start(0); finish(0); start(1);
          wg_wait<0>();
          int redo = 0;
#pragma unroll 1
          for (int pass = 0, j = 1; pass < 2; pass++) {
#pragma unroll 1
           do {
            const uint64_t vd = prm.kv[j & 3].vd;
            bool go = false;
#pragma unroll
            for (int h = 2; h < 18; h++) {
              const int px = (h >> 2) + 1, c = h & 3;
              wg_fence();
              if (h == 13) kd = prm.kv[j & 3].kd;
              const uint64_t kx = kd + (px & 3) * 256, vx = vd + (h - 2) * VSTEP;
              if (h == 2) { qkh(1, 0, kx); qkf(1, 0, kx); pv0(vx); pv1(vx); qkh(1, 1, kx); qkf(1, 1, kx); }
              else if ((c == 1 || c == 2) && h < 17) { qkh(px & 1, c - 1, kx); pv1(vx); qkf(px & 1, c - 1, kx); pv0(vx); }
              else { pv0(vx); pv1(vx); }
              wg_commit();
              if (h == 3) e_arrive_if(sb + B_TE + 8 * ((j + 2) & 3), j > 1);
              if (h == 11) go = mbar_test(sb + B_TF + 8 * (j & 3), (j >> 2) & 1) && j != 8;
              finish(h - 1); start(h);
              if (h != 12 && h != 17) sched_fence();
              if (h == 12 && !go) {
                if (j == 16) {
#pragma unroll
                  for (int u = 13; u < 18; u++) {
                    wg_fence(); pv0(vd + (u - 2) * VSTEP); pv1(vd + (u - 2) * VSTEP); wg_commit();
                    if (u < 17) finish(u - 1);
                    if (u < 16) { start(u); sched_fence(); }
                    if (u & 1) { if (u == 17) wg_wait<0>(); else wg_wait<1>(); }
                  }
                  e_arrive(sb + B_TE + 24);
                  goto head_done;
                }
                mbar_wait(sb + B_TF + 8 * (j & 3), (j >> 2) & 1);
                if (j == 8) {
#pragma unroll
                  for (int i = 0; i < 4; i++) lds128(sb + QPARK + 24576 - wg * 8192 + (w * 32 + lane_id()) * 16 + i * 2048, &q[0][i >> 1][4 * (i & 1)]);
                }
              }
              if (h == 17) wg_wait<0>(); else if (h & 1) wg_wait<1>();
              if (c == 3) { fence_regs(S[px & 1]); fence_regs(H[px & 1]); }
            }
           } while (j++ & 7);
           head_done:
            fence_regs(o[0]); fence_regs(o[1]);
            uint32_t pk[2][8];
            {
              IDS();
              bf16* op = g_os + (size_t)(bm * 256 + row0 + (lane >> 2)) * 1024 + pass * 512 + bn * 32 + (lane & 3) * 8;
#pragma unroll
              for (int i = 0; i < 4; i++) {
                const float* a = &o[i >> 1][2 * (i & 1)];
                const float inv = rcp(a[16]);
                uint32_t* u = &pk[i >> 1][4 * (i & 1)];
#pragma unroll
                for (int k = 0; k < 4; k++) u[k] = pack2(a[4 * k] * inv, a[4 * k + 1] * inv);
                *(uint4*)(op + ((i >> 1) * 64 + (i & 1) * 8) * 1024) = make_uint4(u[0], u[1], u[2], u[3]);
              }
            }
            sched_fence();
            if (pass == 0) bar_sync(NB_KN + wg, 160);
            const float kmax = *(volatile float*)(smem + ROWST + 4 * pass);
            const bool wide = !(qn[0] <= 1.6e7f) | !(kmax <= 1.6e7f) | !(qn[0] * kmax <= 112.f * 112.f);
            int badm = 0;
#pragma unroll
            for (int m = 0; m < 2; m++) {
              uint32_t chk[2] = {0u, 0u};
#pragma unroll
              for (int i = 0; i < 8; i++) asm("fma.rn.bf16x2 %0, %1, %2, %0;" : "+r"(chk[i & 1]) : "r"(pk[m][i]), "r"(0u));
              const bool bad = wide | !(fminf(o[m][16], o[m][18]) >= 9.3e-10f) | !(o[m][16] + o[m][18] <= 1e36f) | (((chk[0] | chk[1]) & 0x7FFF7FFFu) != 0);
              badm |= __any_sync(~0u, bad) << m;
            }
            if (!badm) bar_arrive(NB_SIG + 2 * pass + wg, 160 + 32 * (pass & wg));
            qn[0] = qn[1];
#pragma unroll
            for (int m = 0; m < 2; m++) {
#pragma unroll
              for (int i = 0; i < 20; i++) o[m][i] = 0.f;
              fence_regs(o[m]);
            }
            if (badm) {
              redo |= badm << 2 * pass;
              const int tx = wg * 128 + w * 32 + lane_id();
              uint4* p = g_qsave + (block_id() * 256 + tx) * 8 + pass * 4;
#pragma unroll
              for (int i = 0; i < 4; i++) {
                uint32_t u[4] = {q[0][i >> 1][4 * (i & 1)], q[0][i >> 1][4 * (i & 1) + 1], q[0][i >> 1][4 * (i & 1) + 2], q[0][i >> 1][4 * (i & 1) + 3]};
                if (pass == 0) lds128(sb + QPARK + tx * 16 + i * 4096, u);
                p[i] = make_uint4(u[0], u[1], u[2], u[3]);
              }
            }
          }
          if (redo) attn_redo(redo, l, cta_id(), wg, w, ep1);
        }
      }
      {
        float acc[64];
        {
          const uint64_t da = l & 1 ? prm.xd + ((pslot_a(0, 1) + wg * 8192) >> 4) : prm.kv[0].kd + ((pslot_a(0, 0) - T0 + wg * 4096) >> 4);
          const uint64_t d2 = da + (l & 1 ? 4 : 512), db = prm.wd + (pslot_b(0) >> 4) - 2048;
          mbar_wait(sb + B_PF, l & 1);
          wg_fence();
          wgmma_m64n128k16_ss_tb_z(acc, da, db, 0);
#pragma unroll
          for (int k = 1; k < 4; k++) wgmma_m64n128k16_ss_tb(acc, (k & 2 ? d2 : da) + (k & 1) * 2, db + k * 128, 1);
          wg_commit();
        }
        uint32_t s = 1, lap = 0;
#pragma unroll 1
        for (int kt = 1; kt < 14; kt++) {
          mbar_wait(sb + B_PF + 8 * s, ((s < 4 ? l : 0) + lap) & 1);
          const uint64_t da = mkdesc(sb + pslot_a(s, l) + wg * 8192, 16, 1024, 1), db = mkdesc(sb + pslot_b(s), 8192, 1024, 1);
          wg_fence();
#pragma unroll
          for (int k = 0; k < 4; k++) wgmma_m64n128k16_ss_tb(acc, da + k * 2, db + k * 128, 1);
          wg_commit();
          wg_wait<1>();
          if (w == 0) e_arrive_both(sb + B_PE + 8 * (s ? s - 1 : 5));
          if (++s == 6) { s = 0; lap++; }
        }
        if (wg) {
          wg_wait<0>();
          if (w == 0) e_arrive_both(sb + B_PE + 8);
#pragma unroll
          for (int t = 2; t < 4; t++) mbar_wait(sb + B_PF + 8 * t, l & 1);
          bar_sync(NB_ST, 256);
        }
#pragma unroll
        for (int t = 2; t < 4; t++) {
          if (!wg) mbar_wait(sb + B_PF + 8 * t, l & 1);
          const uint64_t da = prm.xd + ((pslot_a(t, l) + wg * 8192) >> 4), db = prm.wd + (pslot_b(t) >> 4) - 2048;
          wg_fence();
#pragma unroll
          for (int k = 0; k < 4; k++) wgmma_m64n128k16_ss_tb(acc, da + k * 2, db + k * 128, 1);
          wg_commit();
        }
        if (!wg) {
          bar_arrive(NB_ST, 256);
          wg_wait<2>();
          if (w == 0) e_arrive_both(sb + B_PE + 8);
        }
        IDS();
        const int g = lane >> 2, qd = lane & 3;
        const int r0 = wg * 64 + w * 16;
        const uint32_t r = r0 + (lane & 7) + ((lane >> 3) & 1) * 8;
        uint32_t x[8][4];
        mbar_wait(sb + B_RF, 0);
#pragma unroll
        for (int jj = 0; jj < 8; jj++) ldsm4(sb + RES + (jj >> 2) * 16384 + r * 128 + ((((2 * jj + (lane >> 4)) & 7) ^ (r & 7)) << 4), x[jj]);
        wg_wait<0>();
        fence_regs(acc);
        if (w == 0) { e_arrive_both(sb + B_PE + 16); e_arrive_both(sb + B_PE + 24); }
        const CUtensorMap* mo = &prm.m[l == 3 ? M_OUT : M_XST];
        const bool direct = wg && l < 3;
        const uint32_t stg = sb + (direct ? po * 16384 : RES);
        if (direct) bar_sync(NB_SC, 256);
#pragma unroll
        for (int jj = 0; jj < 8; jj++) {
#pragma unroll
          for (int i = 0; i < 4; i++) x[jj][i] = add_bf16x2(x[jj][i], pack2(acc[8 * jj + 2 * i], acc[8 * jj + 2 * i + 1]));
          if (jj < 4) stsm4(stg + r * 128 + ((((2 * jj + (lane >> 4)) & 7) ^ (r & 7)) << 4), x[jj][0], x[jj][1], x[jj][2], x[jj][3]);
          if (jj == 3) { fence_async_smem(); __syncwarp(); tma_st(mo, pn * 128, pm * 128 + r0, stg + r0 * 128); bulk_commit(); sched_fence(); }
        }
        if (l < 3) bar_arrive(NB_KN, 288);
        if (l == 3) {
#pragma unroll
          for (int jj = 4; jj < 8; jj++) stsm4(sb + RES + 16384 + r * 128 + ((((2 * jj + (lane >> 4)) & 7) ^ (r & 7)) << 4), x[jj][0], x[jj][1], x[jj][2], x[jj][3]);
          fence_async_smem(); __syncwarp();
          tma_st(mo, pn * 128 + 64, pm * 128 + r0, sb + RES + 16384 + r0 * 128);
          bulk_commit(); bulk_wait_n<0>();
        } else {
          if (!wg) bar_sync(NB_SC, 256);
#pragma unroll
          for (int jj = 0; jj < 8; jj++)
            if (jj >= 4 || !wg) stsm4(sb + (jj >> 2) * 2 * QSTG + po * 16384 + r * 128 + ((((2 * jj + (lane >> 4)) & 7) ^ (r & 7)) << 4), x[jj][0], x[jj][1], x[jj][2], x[jj][3]);
          bulk_wait_n<0>();
          bar_arrive(NB_X0, 320);
          float s1[4] = {0.f, 0.f, 0.f, 0.f}, sa[4] = {0.f, 0.f, 0.f, 0.f}, sc[4] = {0.f, 0.f, 0.f, 0.f};
#pragma unroll
          for (int jj = 0; jj < 8; jj++) {
            mma16816(s1, x[jj][0], x[jj][1], x[jj][2], x[jj][3], 0x3f803f80u, 0x3f803f80u);
            mma16816(sa, x[jj][0], x[jj][1], x[jj][2], x[jj][3], x[jj][0], x[jj][2]);
            mma16816(sc, x[jj][0], x[jj][1], x[jj][2], x[jj][3], x[jj][1], x[jj][3]);
          }
          fence_regs(s1); fence_regs(sa); fence_regs(sc);
          fence_async_smem();
          sched_fence();
          bar_arrive(NB_X, 320);
          if (qd == g >> 1) {
            float2* p = g_stats + pn * 2048 + pm * 128 + r0 + g;
            p[0] = make_float2(s1[0], g & 1 ? sa[1] : sa[0]);
            p[8] = make_float2(s1[2], g & 1 ? sc[3] : sc[2]);
          }
          bar_arrive(NB_KV, 288);
        }
      }
    }
  }
  asm volatile("barrier.cluster.arrive.relaxed.aligned;\nbarrier.cluster.wait.aligned;" ::: "memory");
}

typedef CUresult (*EncodeFn)(CUtensorMap*, CUtensorMapDataType, cuuint32_t, void*, const cuuint64_t*, const cuuint64_t*, const cuuint32_t*,
                             const cuuint32_t*, CUtensorMapInterleave, CUtensorMapSwizzle, CUtensorMapL2promotion, CUtensorMapFloatOOBfill);

static void make_map(EncodeFn fn, CUtensorMap* m, const void* ptr, int rank, const uint64_t* dims, const uint64_t* strides, const uint32_t* box, CUtensorMapSwizzle sw) {
  cuuint64_t d[5], st[4];
  cuuint32_t bx[5], es[5];
  for (int i = 0; i < rank; i++) { d[i] = dims[i]; bx[i] = box[i]; es[i] = 1; if (i) st[i - 1] = strides[i - 1] * 2; }
  fn(m, CU_TENSOR_MAP_DATA_TYPE_BFLOAT16, rank, (void*)ptr, d, st, bx, es, CU_TENSOR_MAP_INTERLEAVE_NONE, sw,
     CU_TENSOR_MAP_L2_PROMOTION_L2_128B, CU_TENSOR_MAP_FLOAT_OOB_FILL_NONE);
}
static void map2(EncodeFn fn, CUtensorMap* m, const void* ptr, uint64_t inner, uint64_t outer, uint32_t bi, uint32_t bo, CUtensorMapSwizzle sw) {
  const uint64_t d[2] = {inner, outer}, st[1] = {inner};
  const uint32_t bx[2] = {bi, bo};
  make_map(fn, m, ptr, 2, d, st, bx, sw);
}

extern "C" void kernel_launch(void* const* d_in, const int* in_sizes, int n_in, void* d_out, int out_size) {
  (void)in_sizes; (void)n_in; (void)out_size;
  static EncodeFn enc = nullptr;
  static void *xs, *os, *kk, *vv;
  static int sbase = 1024;
  if (!enc) {
    void* p = nullptr;
    cudaDriverEntryPointQueryResult qr;
    cudaGetDriverEntryPoint("cuTensorMapEncodeTiled", &p, cudaEnableDefault, &qr);
    enc = (EncodeFn)p;
    Scratch* sc = nullptr;
    cudaGetSymbolAddress((void**)&sc, g_s);
    xs = sc->xs; os = sc->os; kk = sc->k; vv = sc->v;
    int dev = 0;
    cudaGetDevice(&dev);
    cudaDeviceGetAttribute(&sbase, cudaDevAttrReservedSharedMemoryPerBlock, dev);
    cudaFuncSetAttribute(fused_kernel, cudaFuncAttributeMaxDynamicSharedMemorySize, SMEM_BYTES);
  }
  Params prm;
  const CUtensorMapSwizzle S128 = CU_TENSOR_MAP_SWIZZLE_128B, S64 = CU_TENSOR_MAP_SWIZZLE_64B;
  map2(enc, &prm.m[M_X0A], d_in[0], 1024, 2048, 64, 256, S128);
  for (int t = 0; t < 2; t++) {
    const uint64_t d3[3] = {1024, 1024, 3}, s3[2] = {3072, 1024};
    const uint32_t b3[3] = {64, 64, 3};
    make_map(enc, &prm.m[M_WQA + t], d_in[1 + 3 * t], 3, d3, s3, b3, S128);
    const uint64_t d5[5] = {64, 32, 2, 16, 16}, s5[4] = {1024, 32 * 1024, 64 * 1024, 64};
    const uint32_t b5[5] = {64, 32, 1, 2, 2};
    make_map(enc, &prm.m[M_WOA + t], d_in[2 + 3 * t], 5, d5, s5, b5, S128);
    const uint64_t dr[3] = {64, 2048, 16}, sr[2] = {1024, 64};
    const uint32_t br[3] = {64, 128, 2};
    make_map(enc, &prm.m[M_X0R + t], t ? xs : d_in[0], 3, dr, sr, br, S128);
  }
  map2(enc, &prm.m[M_OS], os, 1024, 2048, 64, 64, S128);
  map2(enc, &prm.m[M_OL], os, 1024, 2048, 32, 128, S64);
  map2(enc, &prm.m[M_K], kk, 32, 65536, 32, 128, S64);
  map2(enc, &prm.m[M_V], vv, 32, 65536, 32, 128, S64);
  map2(enc, &prm.m[M_XSO], xs, 1024, 2048, 64, 128, S128);
  map2(enc, &prm.m[M_X0H], d_in[0], 1024, 2048, 64, 128, S128);
  map2(enc, &prm.m[M_XST], xs, 1024, 2048, 64, 16, S128);
  map2(enc, &prm.m[M_OUT], d_out, 1024, 2048, 64, 16, S128);
  prm.x0 = (const bf16*)d_in[0];
  prm.wq[0] = (const bf16*)d_in[1]; prm.wq[1] = (const bf16*)d_in[4];
  prm.wo = (const bf16*)d_in[2];
  prm.zero = 0;
  for (int i = 0; i < 128; i++) prm.map[i] = remap(i);
  {
    const uint64_t hi = 0x80000020ull << 32, k0 = sbase + T0, v0 = k0 + 16384, vstep = 64 - (64ull << 16);
    prm.wd = mkdesc(sbase + 32768, 8192, 1024, 1); prm.xd = mkdesc(sbase, 16, 1024, 1);
    for (int j = 0; j < 4; j++) {
      prm.kv[j].kd = (hi | 1u << 16 | k0 >> 4) + 2048 * ((j < 16 ? j : 15) & 3);
      prm.kv[j].vd = (hi | (uint64_t)(ONES - T0 - 16384) >> 4 << 16 | v0 >> 4) + 32 * vstep * ((j + 3) & 3);
    }
  }
  fused_kernel<<<128, 384, SMEM_BYTES>>>(prm);
}
```

```cpp
#include <cuda_runtime.h>
#include <cuda_bf16.h>
#include <cuda.h>
#include <stdint.h>

typedef __nv_bfloat16 bf16;

__device__ __forceinline__ void wgmma_m64n192k16_ss_tb(float (&d)[96], uint64_t da, uint64_t db, int scale_d) {
  asm volatile("{\n.reg .pred p;\nsetp.ne.b32 p, %98, 0;\n"
    "wgmma.mma_async.sync.aligned.m64n192k16.f32.bf16.bf16 "
    "{%0, %1, %2, %3, %4, %5, %6, %7, %8, %9, %10, %11, %12, %13, %14, %15, "
    "%16, %17, %18, %19, %20, %21, %22, %23, %24, %25, %26, %27, %28, %29, %30, %31, "
    "%32, %33, %34, %35, %36, %37, %38, %39, %40, %41, %42, %43, %44, %45, %46, %47, "
    "%48, %49, %50, %51, %52, %53, %54, %55, %56, %57, %58, %59, %60, %61, %62, %63, "
    "%64, %65, %66, %67, %68, %69, %70, %71, %72, %73, %74, %75, %76, %77, %78, %79, "
    "%80, %81, %82, %83, %84, %85, %86, %87, %88, %89, %90, %91, %92, %93, %94, %95}, "
    "%96, %97, p, 1, 1, 0, 1;\n}\n"
    : "+f"(d[0]), "+f"(d[1]), "+f"(d[2]), "+f"(d[3]), "+f"(d[4]), "+f"(d[5]), "+f"(d[6]), "+f"(d[7]),
      "+f"(d[8]), "+f"(d[9]), "+f"(d[10]), "+f"(d[11]), "+f"(d[12]), "+f"(d[13]), "+f"(d[14]), "+f"(d[15]),
      "+f"(d[16]), "+f"(d[17]), "+f"(d[18]), "+f"(d[19]), "+f"(d[20]), "+f"(d[21]), "+f"(d[22]), "+f"(d[23]),
      "+f"(d[24]), "+f"(d[25]), "+f"(d[26]), "+f"(d[27]), "+f"(d[28]), "+f"(d[29]), "+f"(d[30]), "+f"(d[31]),
      "+f"(d[32]), "+f"(d[33]), "+f"(d[34]), "+f"(d[35]), "+f"(d[36]), "+f"(d[37]), "+f"(d[38]), "+f"(d[39]),
      "+f"(d[40]), "+f"(d[41]), "+f"(d[42]), "+f"(d[43]), "+f"(d[44]), "+f"(d[45]), "+f"(d[46]), "+f"(d[47]),
      "+f"(d[48]), "+f"(d[49]), "+f"(d[50]), "+f"(d[51]), "+f"(d[52]), "+f"(d[53]), "+f"(d[54]), "+f"(d[55]),
      "+f"(d[56]), "+f"(d[57]), "+f"(d[58]), "+f"(d[59]), "+f"(d[60]), "+f"(d[61]), "+f"(d[62]), "+f"(d[63]),
      "+f"(d[64]), "+f"(d[65]), "+f"(d[66]), "+f"(d[67]), "+f"(d[68]), "+f"(d[69]), "+f"(d[70]), "+f"(d[71]),
      "+f"(d[72]), "+f"(d[73]), "+f"(d[74]), "+f"(d[75]), "+f"(d[76]), "+f"(d[77]), "+f"(d[78]), "+f"(d[79]),
      "+f"(d[80]), "+f"(d[81]), "+f"(d[82]), "+f"(d[83]), "+f"(d[84]), "+f"(d[85]), "+f"(d[86]), "+f"(d[87]),
      "+f"(d[88]), "+f"(d[89]), "+f"(d[90]), "+f"(d[91]), "+f"(d[92]), "+f"(d[93]), "+f"(d[94]), "+f"(d[95])
    : "l"(da), "l"(db), "r"(scale_d));
}

__device__ __forceinline__ void wgmma_m64n192k16_ss_tb_z(float (&d)[96], uint64_t da, uint64_t db, int scale_d) {
  asm volatile("{\n.reg .pred p;\nsetp.ne.b32 p, %98, 0;\n"
    "wgmma.mma_async.sync.aligned.m64n192k16.f32.bf16.bf16 "
    "{%0, %1, %2, %3, %4, %5, %6, %7, %8, %9, %10, %11, %12, %13, %14, %15, "
    "%16, %17, %18, %19, %20, %21, %22, %23, %24, %25, %26, %27, %28, %29, %30, %31, "
    "%32, %33, %34, %35, %36, %37, %38, %39, %40, %41, %42, %43, %44, %45, %46, %47, "
    "%48, %49, %50, %51, %52, %53, %54, %55, %56, %57, %58, %59, %60, %61, %62, %63, "
    "%64, %65, %66, %67, %68, %69, %70, %71, %72, %73, %74, %75, %76, %77, %78, %79, "
    "%80, %81, %82, %83, %84, %85, %86, %87, %88, %89, %90, %91, %92, %93, %94, %95}, "
    "%96, %97, p, 1, 1, 0, 1;\n}\n"
    : "=f"(d[0]), "=f"(d[1]), "=f"(d[2]), "=f"(d[3]), "=f"(d[4]), "=f"(d[5]), "=f"(d[6]), "=f"(d[7]),
      "=f"(d[8]), "=f"(d[9]), "=f"(d[10]), "=f"(d[11]), "=f"(d[12]), "=f"(d[13]), "=f"(d[14]), "=f"(d[15]),
      "=f"(d[16]), "=f"(d[17]), "=f"(d[18]), "=f"(d[19]), "=f"(d[20]), "=f"(d[21]), "=f"(d[22]), "=f"(d[23]),
      "=f"(d[24]), "=f"(d[25]), "=f"(d[26]), "=f"(d[27]), "=f"(d[28]), "=f"(d[29]), "=f"(d[30]), "=f"(d[31]),
      "=f"(d[32]), "=f"(d[33]), "=f"(d[34]), "=f"(d[35]), "=f"(d[36]), "=f"(d[37]), "=f"(d[38]), "=f"(d[39]),
      "=f"(d[40]), "=f"(d[41]), "=f"(d[42]), "=f"(d[43]), "=f"(d[44]), "=f"(d[45]), "=f"(d[46]), "=f"(d[47]),
      "=f"(d[48]), "=f"(d[49]), "=f"(d[50]), "=f"(d[51]), "=f"(d[52]), "=f"(d[53]), "=f"(d[54]), "=f"(d[55]),
      "=f"(d[56]), "=f"(d[57]), "=f"(d[58]), "=f"(d[59]), "=f"(d[60]), "=f"(d[61]), "=f"(d[62]), "=f"(d[63]),
      "=f"(d[64]), "=f"(d[65]), "=f"(d[66]), "=f"(d[67]), "=f"(d[68]), "=f"(d[69]), "=f"(d[70]), "=f"(d[71]),
      "=f"(d[72]), "=f"(d[73]), "=f"(d[74]), "=f"(d[75]), "=f"(d[76]), "=f"(d[77]), "=f"(d[78]), "=f"(d[79]),
      "=f"(d[80]), "=f"(d[81]), "=f"(d[82]), "=f"(d[83]), "=f"(d[84]), "=f"(d[85]), "=f"(d[86]), "=f"(d[87]),
      "=f"(d[88]), "=f"(d[89]), "=f"(d[90]), "=f"(d[91]), "=f"(d[92]), "=f"(d[93]), "=f"(d[94]), "=f"(d[95])
    : "l"(da), "l"(db), "r"(scale_d));
}

__device__ __forceinline__ void wgmma_m64n128k16_ss_tb(float (&d)[64], uint64_t da, uint64_t db, int scale_d) {
  asm volatile("{\n.reg .pred p;\nsetp.ne.b32 p, %66, 0;\n"
    "wgmma.mma_async.sync.aligned.m64n128k16.f32.bf16.bf16 "
    "{%0, %1, %2, %3, %4, %5, %6, %7, %8, %9, %10, %11, %12, %13, %14, %15, "
    "%16, %17, %18, %19, %20, %21, %22, %23, %24, %25, %26, %27, %28, %29, %30, %31, "
    "%32, %33, %34, %35, %36, %37, %38, %39, %40, %41, %42, %43, %44, %45, %46, %47, "
    "%48, %49, %50, %51, %52, %53, %54, %55, %56, %57, %58, %59, %60, %61, %62, %63}, "
    "%64, %65, p, 1, 1, 0, 1;\n}\n"
    : "+f"(d[0]), "+f"(d[1]), "+f"(d[2]), "+f"(d[3]), "+f"(d[4]), "+f"(d[5]), "+f"(d[6]), "+f"(d[7]),
      "+f"(d[8]), "+f"(d[9]), "+f"(d[10]), "+f"(d[11]), "+f"(d[12]), "+f"(d[13]), "+f"(d[14]), "+f"(d[15]),
      "+f"(d[16]), "+f"(d[17]), "+f"(d[18]), "+f"(d[19]), "+f"(d[20]), "+f"(d[21]), "+f"(d[22]), "+f"(d[23]),
      "+f"(d[24]), "+f"(d[25]), "+f"(d[26]), "+f"(d[27]), "+f"(d[28]), "+f"(d[29]), "+f"(d[30]), "+f"(d[31]),
      "+f"(d[32]), "+f"(d[33]), "+f"(d[34]), "+f"(d[35]), "+f"(d[36]), "+f"(d[37]), "+f"(d[38]), "+f"(d[39]),
      "+f"(d[40]), "+f"(d[41]), "+f"(d[42]), "+f"(d[43]), "+f"(d[44]), "+f"(d[45]), "+f"(d[46]), "+f"(d[47]),
      "+f"(d[48]), "+f"(d[49]), "+f"(d[50]), "+f"(d[51]), "+f"(d[52]), "+f"(d[53]), "+f"(d[54]), "+f"(d[55]),
      "+f"(d[56]), "+f"(d[57]), "+f"(d[58]), "+f"(d[59]), "+f"(d[60]), "+f"(d[61]), "+f"(d[62]), "+f"(d[63])
    : "l"(da), "l"(db), "r"(scale_d));
}

__device__ __forceinline__ void wgmma_m64n128k16_ss_tb_z(float (&d)[64], uint64_t da, uint64_t db, int scale_d) {
  asm volatile("{\n.reg .pred p;\nsetp.ne.b32 p, %66, 0;\n"
    "wgmma.mma_async.sync.aligned.m64n128k16.f32.bf16.bf16 "
    "{%0, %1, %2, %3, %4, %5, %6, %7, %8, %9, %10, %11, %12, %13, %14, %15, "
    "%16, %17, %18, %19, %20, %21, %22, %23, %24, %25, %26, %27, %28, %29, %30, %31, "
    "%32, %33, %34, %35, %36, %37, %38, %39, %40, %41, %42, %43, %44, %45, %46, %47, "
    "%48, %49, %50, %51, %52, %53, %54, %55, %56, %57, %58, %59, %60, %61, %62, %63}, "
    "%64, %65, p, 1, 1, 0, 1;\n}\n"
    : "=f"(d[0]), "=f"(d[1]), "=f"(d[2]), "=f"(d[3]), "=f"(d[4]), "=f"(d[5]), "=f"(d[6]), "=f"(d[7]),
      "=f"(d[8]), "=f"(d[9]), "=f"(d[10]), "=f"(d[11]), "=f"(d[12]), "=f"(d[13]), "=f"(d[14]), "=f"(d[15]),
      "=f"(d[16]), "=f"(d[17]), "=f"(d[18]), "=f"(d[19]), "=f"(d[20]), "=f"(d[21]), "=f"(d[22]), "=f"(d[23]),
      "=f"(d[24]), "=f"(d[25]), "=f"(d[26]), "=f"(d[27]), "=f"(d[28]), "=f"(d[29]), "=f"(d[30]), "=f"(d[31]),
      "=f"(d[32]), "=f"(d[33]), "=f"(d[34]), "=f"(d[35]), "=f"(d[36]), "=f"(d[37]), "=f"(d[38]), "=f"(d[39]),
      "=f"(d[40]), "=f"(d[41]), "=f"(d[42]), "=f"(d[43]), "=f"(d[44]), "=f"(d[45]), "=f"(d[46]), "=f"(d[47]),
      "=f"(d[48]), "=f"(d[49]), "=f"(d[50]), "=f"(d[51]), "=f"(d[52]), "=f"(d[53]), "=f"(d[54]), "=f"(d[55]),
      "=f"(d[56]), "=f"(d[57]), "=f"(d[58]), "=f"(d[59]), "=f"(d[60]), "=f"(d[61]), "=f"(d[62]), "=f"(d[63])
    : "l"(da), "l"(db), "r"(scale_d));
}

__device__ __forceinline__ void wgmma_m64n40k16_rs_tb(float (&d)[20], uint32_t a0, uint32_t a1, uint32_t a2, uint32_t a3, uint64_t db, int scale_d) {
  asm volatile("{\n.reg .pred p;\nsetp.ne.b32 p, %25, 0;\n"
    "wgmma.mma_async.sync.aligned.m64n40k16.f32.bf16.bf16 "
    "{%0, %1, %2, %3, %4, %5, %6, %7, %8, %9, %10, %11, %12, %13, %14, %15, "
    "%16, %17, %18, %19}, "
    "{%20, %21, %22, %23}, %24, p, 1, 1, 1;\n}\n"
    : "+f"(d[0]), "+f"(d[1]), "+f"(d[2]), "+f"(d[3]), "+f"(d[4]), "+f"(d[5]), "+f"(d[6]), "+f"(d[7]),
      "+f"(d[8]), "+f"(d[9]), "+f"(d[10]), "+f"(d[11]), "+f"(d[12]), "+f"(d[13]), "+f"(d[14]), "+f"(d[15]),
      "+f"(d[16]), "+f"(d[17]), "+f"(d[18]), "+f"(d[19])
    : "r"(a0), "r"(a1), "r"(a2), "r"(a3), "l"(db), "r"(scale_d));
}

__device__ __forceinline__ void wg_n64_rs_nb_f16_f32(float (&d)[32], uint32_t a0, uint32_t a1, uint32_t a2, uint32_t a3, uint64_t db, int scale_d) {
  asm volatile("{\n.reg .pred p;\nsetp.ne.b32 p, %37, 0;\n"
    "wgmma.mma_async.sync.aligned.m64n64k16.f32.f16.f16 "
    "{%0, %1, %2, %3, %4, %5, %6, %7, %8, %9, %10, %11, %12, %13, %14, %15, "
    "%16, %17, %18, %19, %20, %21, %22, %23, %24, %25, %26, %27, %28, %29, %30, %31}, "
    "{%32, %33, %34, %35}, %36, p, 1, 1, 0;\n}\n"
    : "+f"(d[0]), "+f"(d[1]), "+f"(d[2]), "+f"(d[3]), "+f"(d[4]), "+f"(d[5]), "+f"(d[6]), "+f"(d[7]),
      "+f"(d[8]), "+f"(d[9]), "+f"(d[10]), "+f"(d[11]), "+f"(d[12]), "+f"(d[13]), "+f"(d[14]), "+f"(d[15]),
      "+f"(d[16]), "+f"(d[17]), "+f"(d[18]), "+f"(d[19]), "+f"(d[20]), "+f"(d[21]), "+f"(d[22]), "+f"(d[23]),
      "+f"(d[24]), "+f"(d[25]), "+f"(d[26]), "+f"(d[27]), "+f"(d[28]), "+f"(d[29]), "+f"(d[30]), "+f"(d[31])
    : "r"(a0), "r"(a1), "r"(a2), "r"(a3), "l"(db), "r"(scale_d));
}

__device__ __forceinline__ void wg_n64_rs_nb_f16_f16(uint32_t (&d)[16], uint32_t a0, uint32_t a1, uint32_t a2, uint32_t a3, uint64_t db, int scale_d) {
  asm volatile("{\n.reg .pred p;\nsetp.ne.b32 p, %21, 0;\n"
    "wgmma.mma_async.sync.aligned.m64n64k16.f16.f16.f16 "
    "{%0, %1, %2, %3, %4, %5, %6, %7, %8, %9, %10, %11, %12, %13, %14, %15}, "
    "{%16, %17, %18, %19}, %20, p, 1, 1, 0;\n}\n"
    : "+r"(d[0]), "+r"(d[1]), "+r"(d[2]), "+r"(d[3]), "+r"(d[4]), "+r"(d[5]), "+r"(d[6]), "+r"(d[7]),
      "+r"(d[8]), "+r"(d[9]), "+r"(d[10]), "+r"(d[11]), "+r"(d[12]), "+r"(d[13]), "+r"(d[14]), "+r"(d[15])
    : "r"(a0), "r"(a1), "r"(a2), "r"(a3), "l"(db), "r"(scale_d));
}

__device__ __forceinline__ void wg_n64_rs_nb_f16_f32_z(float (&d)[32], uint32_t a0, uint32_t a1, uint32_t a2, uint32_t a3, uint64_t db, int scale_d) {
  asm volatile("{\n.reg .pred p;\nsetp.ne.b32 p, %37, 0;\n"
    "wgmma.mma_async.sync.aligned.m64n64k16.f32.f16.f16 "
    "{%0, %1, %2, %3, %4, %5, %6, %7, %8, %9, %10, %11, %12, %13, %14, %15, "
    "%16, %17, %18, %19, %20, %21, %22, %23, %24, %25, %26, %27, %28, %29, %30, %31}, "
    "{%32, %33, %34, %35}, %36, p, 1, 1, 0;\n}\n"
    : "=f"(d[0]), "=f"(d[1]), "=f"(d[2]), "=f"(d[3]), "=f"(d[4]), "=f"(d[5]), "=f"(d[6]), "=f"(d[7]),
      "=f"(d[8]), "=f"(d[9]), "=f"(d[10]), "=f"(d[11]), "=f"(d[12]), "=f"(d[13]), "=f"(d[14]), "=f"(d[15]),
      "=f"(d[16]), "=f"(d[17]), "=f"(d[18]), "=f"(d[19]), "=f"(d[20]), "=f"(d[21]), "=f"(d[22]), "=f"(d[23]),
      "=f"(d[24]), "=f"(d[25]), "=f"(d[26]), "=f"(d[27]), "=f"(d[28]), "=f"(d[29]), "=f"(d[30]), "=f"(d[31])
    : "r"(a0), "r"(a1), "r"(a2), "r"(a3), "l"(db), "r"(scale_d));
}

__device__ __forceinline__ void wg_n64_rs_nb_f16_f16_z(uint32_t (&d)[16], uint32_t a0, uint32_t a1, uint32_t a2, uint32_t a3, uint64_t db, int scale_d) {
  asm volatile("{\n.reg .pred p;\nsetp.ne.b32 p, %21, 0;\n"
    "wgmma.mma_async.sync.aligned.m64n64k16.f16.f16.f16 "
    "{%0, %1, %2, %3, %4, %5, %6, %7, %8, %9, %10, %11, %12, %13, %14, %15}, "
    "{%16, %17, %18, %19}, %20, p, 1, 1, 0;\n}\n"
    : "=r"(d[0]), "=r"(d[1]), "=r"(d[2]), "=r"(d[3]), "=r"(d[4]), "=r"(d[5]), "=r"(d[6]), "=r"(d[7]),
      "=r"(d[8]), "=r"(d[9]), "=r"(d[10]), "=r"(d[11]), "=r"(d[12]), "=r"(d[13]), "=r"(d[14]), "=r"(d[15])
    : "r"(a0), "r"(a1), "r"(a2), "r"(a3), "l"(db), "r"(scale_d));
}

#define DEVINL __device__ __forceinline__
DEVINL void wg_fence() { asm volatile("wgmma.fence.sync.aligned;" ::: "memory"); }
DEVINL void wg_commit() { asm volatile("wgmma.commit_group.sync.aligned;" ::: "memory"); }
template <int N> DEVINL void wg_wait() { asm volatile("wgmma.wait_group.sync.aligned %0;" ::"n"(N) : "memory"); }
__host__ DEVINL uint64_t mkdesc(uint32_t addr, uint32_t lbo, uint32_t sbo, int sw) {
  return (uint64_t)((addr & 0x3FFFF) >> 4) | ((uint64_t)(lbo >> 4) << 16) | ((uint64_t)(sbo >> 4) << 32) | ((uint64_t)sw << 62);
}
DEVINL bool mbar_try(uint32_t bar, uint32_t parity) {
  uint32_t ok;
  asm volatile("{\n.reg .pred p;\nmbarrier.try_wait.parity.shared::cta.b64 p, [%1], %2;\nselp.u32 %0, 1, 0, p;\n}" : "=r"(ok) : "r"(bar), "r"(parity) : "memory");
  return ok;
}
DEVINL bool mbar_test(uint32_t bar, uint32_t parity) {
  uint32_t ok;
  asm volatile("{\n.reg .pred p;\nmbarrier.test_wait.parity.shared::cta.b64 p, [%1], %2;\nselp.u32 %0, 1, 0, p;\n}" : "=r"(ok) : "r"(bar), "r"(parity) : "memory");
  return ok;
}
DEVINL void mbar_wait(uint32_t bar, uint32_t parity) {
#pragma unroll 1
  for (uint32_t n = 0; n < 100000u; n++) if (mbar_try(bar, parity)) break;
}
#define EL(txt) "{\n.reg .pred pe;\nelect.sync _|pe, 0xffffffff;\n@pe " txt "\n}"
DEVINL void e_expect_tx(uint32_t bar, uint32_t bytes) { asm volatile(EL("mbarrier.arrive.expect_tx.shared::cta.b64 _, [%0], %1;") ::"r"(bar), "r"(bytes) : "memory"); }
DEVINL void e_arrive(uint32_t bar) { asm volatile(EL("mbarrier.arrive.shared::cta.b64 _, [%0];") ::"r"(bar) : "memory"); }
DEVINL void e_arrive_if(uint32_t bar, int c) {
  asm volatile("{\n.reg .pred pe;\nelect.sync _|pe, 0xffffffff;\nsetp.ne.and.b32 pe, %1, 0, pe;\n@pe mbarrier.arrive.shared::cta.b64 _, [%0];\n}" ::"r"(bar), "r"(c) : "memory");
}
DEVINL void e_red(uint32_t* p) { asm volatile(EL("red.release.gpu.global.add.u32 [%0], 1;") ::"l"(p) : "memory"); }
DEVINL void e_red_relaxed(uint32_t* p) { asm volatile(EL("red.relaxed.gpu.global.add.u32 [%0], 1;") ::"l"(p) : "memory"); }
DEVINL void release_add(uint32_t* p, int on) {
  asm volatile("{\n.reg .pred q;\nsetp.ne.b32 q, %1, 0;\nfence.release.gpu;\n@q red.relaxed.gpu.global.add.u32 [%0], 1;\n}" ::"l"(p), "r"(on) : "memory");
}
#define PREPARED(p, on) do { asm volatile("" : "+l"(p), "+r"(on)); asm volatile("griddepcontrol.launch_dependents;" ::: "memory"); } while (0)
DEVINL void tma_ld(uint32_t dst, const CUtensorMap* m, int c0, int c1, uint32_t bar) {
  asm volatile(EL("cp.async.bulk.tensor.2d.shared::cluster.global.mbarrier::complete_tx::bytes [%0], [%1, {%3, %4}], [%2];")
               ::"r"(dst), "l"(m), "r"(bar), "r"(c0), "r"(c1) : "memory");
}
DEVINL void tma_ld3(uint32_t dst, const CUtensorMap* m, int c0, int c1, int c2, uint32_t bar) {
  asm volatile(EL("cp.async.bulk.tensor.3d.shared::cluster.global.mbarrier::complete_tx::bytes [%0], [%1, {%3, %4, %5}], [%2];")
               ::"r"(dst), "l"(m), "r"(bar), "r"(c0), "r"(c1), "r"(c2) : "memory");
}
DEVINL void tma_ld5(uint32_t dst, const CUtensorMap* m, int c2, int c3, int c4, uint32_t bar) {
  asm volatile(EL("cp.async.bulk.tensor.5d.shared::cluster.global.mbarrier::complete_tx::bytes [%0], [%1, {0, 0, %3, %4, %5}], [%2];")
               ::"r"(dst), "l"(m), "r"(bar), "r"(c2), "r"(c3), "r"(c4) : "memory");
}
DEVINL void tma_ld_mc(uint32_t dst, const CUtensorMap* m, int c0, int c1, uint32_t bar, uint16_t mask = 3) {
  asm volatile(EL("cp.async.bulk.tensor.2d.shared::cluster.global.mbarrier::complete_tx::bytes.multicast::cluster [%0], [%1, {%3, %4}], [%2], %5;")
               ::"r"(dst), "l"(m), "r"(bar), "r"(c0), "r"(c1), "h"(mask) : "memory");
}
DEVINL void e_arrive_both(uint32_t bar) {
  asm volatile("{\n.reg .pred pe;\n.reg .b32 r0, r1;\nelect.sync _|pe, 0xffffffff;\nmapa.shared::cluster.u32 r0, %0, 0;\nmapa.shared::cluster.u32 r1, %0, 1;\n"
               "@pe mbarrier.arrive.shared::cluster.b64 _, [r0];\n@pe mbarrier.arrive.shared::cluster.b64 _, [r1];\n}" ::"r"(bar) : "memory");
}
DEVINL void tma_st(const CUtensorMap* m, int c0, int c1, uint32_t src) {
  asm volatile(EL("cp.async.bulk.tensor.2d.global.shared::cta.bulk_group [%0, {%2, %3}], [%1];") ::"l"(m), "r"(src), "r"(c0), "r"(c1) : "memory");
}
DEVINL void bulk_commit() { asm volatile("cp.async.bulk.commit_group;" ::: "memory"); }
template <int N> DEVINL void bulk_wait_n() { asm volatile("cp.async.bulk.wait_group %0;\nbar.warp.sync 0xffffffff;" ::"n"(N) : "memory"); }
DEVINL void l2_prefetch(const void* g, uint32_t bytes) { asm volatile(EL("cp.async.bulk.prefetch.L2.global [%0], %1;") ::"l"(g), "r"(bytes) : "memory"); }
DEVINL void fence_async_smem() { asm volatile("fence.proxy.async.shared::cta;" ::: "memory"); }
DEVINL void fence_async_gl() { asm volatile("fence.proxy.async.global;" ::: "memory"); }
DEVINL void cluster_wait() { asm volatile("barrier.cluster.wait.aligned;" ::: "memory"); }
DEVINL void bar_sync(int id, int n) { asm volatile("bar.sync %0, %1;" ::"r"(id), "r"(n) : "memory"); }
DEVINL void bar_arrive(int id, int n) { asm volatile("bar.arrive %0, %1;" ::"r"(id), "r"(n) : "memory"); }
DEVINL uint32_t ld_acquire(const uint32_t* p) { uint32_t v; asm volatile("ld.acquire.gpu.global.u32 %0, [%1];" : "=r"(v) : "l"(p) : "memory"); return v; }
DEVINL void await_flag(int j, uint32_t& rdy, const uint32_t* p, uint32_t target) {
  if ((rdy >> j) & 1) return;
#pragma unroll 1
  for (uint32_t n = 0; n < 200000u && !((rdy >> j) & 1); n++) rdy = __ballot_sync(~0u, (int)(ld_acquire(p) - target) >= 0);
  asm volatile("fence.proxy.async.global;" ::: "memory");
}
DEVINL void poll_ge(const uint32_t* p, uint32_t target) {
#pragma unroll 1
  for (uint32_t n = 0; n < 200000u; n++) if (__all_sync(~0u, (int)(ld_acquire(p) - target) >= 0)) break;
}
DEVINL int lane_id() { int v; asm volatile("mov.u32 %0, %%laneid;" : "=r"(v)); return v; }
__host__ DEVINL int remap(int v) {
  const int c = v >> 1, u = c - 36, r = (u * 37) >> 8;
  const int L = c < 4 ? 32 + 8 * c : c < 36 ? c - 4 : 33 + u + r;
  return 2 * L + (v & 1);
}
DEVINL int block_id() { int v; asm volatile("mov.u32 %0, %%ctaid.x;" : "=r"(v)); return v; }
#define cta_id() prm.map[block_id()]
#define IDS() const int lane = lane_id(), b = cta_id(), bm = b >> 4, bn = b & 15, rank = b & 1, pm = 2 * bm + (bn >> 3), pn = bn & 7, po = pm & 1; \
  (void)lane; (void)bm; (void)bn; (void)rank; (void)pm; (void)pn; (void)po
DEVINL void st_tagged(uint4* p, uint32_t a, uint32_t b, uint32_t c, uint32_t tag) {
  asm volatile("{\n.reg .b64 u, v;\n.reg .b128 t;\nmov.b64 u, {%1, %2};\nmov.b64 v, {%3, %4};\nmov.b128 t, {u, v};\nst.relaxed.gpu.global.b128 [%0], t;\n}"
               ::"l"(p), "r"(a), "r"(b), "r"(c), "r"(tag) : "memory");
}
DEVINL uint32_t ld_tagged(const uint4* p, uint32_t* r) {
  uint32_t tag;
  asm volatile("{\n.reg .b64 u, v;\n.reg .b128 t;\nld.relaxed.gpu.global.b128 t, [%4];\nmov.b128 {u, v}, t;\nmov.b64 {%0, %1}, u;\nmov.b64 {%2, %3}, v;\n}"
               : "=r"(r[0]), "=r"(r[1]), "=r"(r[2]), "=r"(tag) : "l"(p) : "memory");
  return tag;
}
DEVINL float ex2(float x) { float y; asm("ex2.approx.ftz.f32 %0, %1;" : "=f"(y) : "f"(x)); return y; }
DEVINL float rcp(float x) { float y; asm("rcp.approx.ftz.f32 %0, %1;" : "=f"(y) : "f"(x)); return y; }
DEVINL uint32_t pack2(float lo, float hi) { uint32_t r; asm("cvt.rn.bf16x2.f32 %0, %1, %2;" : "=r"(r) : "f"(hi), "f"(lo)); return r; }
DEVINL uint32_t pack2h(float lo, float hi) { uint32_t r; asm("cvt.rz.f16x2.f32 %0, %1, %2;" : "=r"(r) : "f"(hi), "f"(lo)); return r; }
DEVINL uint32_t prmt0(uint32_t a, uint32_t sel) { uint32_t r; asm("prmt.b32 %0, %1, 0, %2;" : "=r"(r) : "r"(a), "r"(sel)); return r; }
DEVINL void stg128(const void* p, uint32_t a, uint32_t b, uint32_t c, uint32_t d) {
  asm volatile("st.global.v4.b32 [%0], {%1, %2, %3, %4};" ::"l"(p), "r"(a), "r"(b), "r"(c), "r"(d) : "memory");
}
DEVINL uint32_t hadd2(uint32_t a, uint32_t b) { uint32_t r; asm("add.rn.f16x2 %0, %1, %2;" : "=r"(r) : "r"(a), "r"(b)); return r; }
DEVINL uint32_t hfma2(uint32_t a, uint32_t b, uint32_t c) { uint32_t r; asm("fma.rn.f16x2 %0, %1, %2, %3;" : "=r"(r) : "r"(a), "r"(b), "r"(c)); return r; }
DEVINL float bf_lo(uint32_t w) { return __uint_as_float(w << 16); }
DEVINL float bf_hi(uint32_t w) { return __uint_as_float(w & 0xFFFF0000u); }
DEVINL float bf_round(float x) { return bf_lo(pack2(x, 0.f)); }
DEVINL uint32_t add_bf16x2(uint32_t a, uint32_t b) { uint32_t r; asm("add.rn.bf16x2 %0, %1, %2;" : "=r"(r) : "r"(a), "r"(b)); return r; }
DEVINL void stsm4(uint32_t addr, uint32_t a, uint32_t b, uint32_t c, uint32_t d) {
  asm volatile("stmatrix.sync.aligned.m8n8.x4.shared.b16 [%0], {%1, %2, %3, %4};" ::"r"(addr), "r"(a), "r"(b), "r"(c), "r"(d) : "memory");
}
DEVINL void ldsm4(uint32_t addr, uint32_t (&r)[4]) {
  asm volatile("ldmatrix.sync.aligned.m8n8.x4.shared.b16 {%0, %1, %2, %3}, [%4];" : "=r"(r[0]), "=r"(r[1]), "=r"(r[2]), "=r"(r[3]) : "r"(addr) : "memory");
}
DEVINL void ldsm4t(uint32_t addr, uint32_t (&r)[4]) {
  asm volatile("ldmatrix.sync.aligned.m8n8.x4.trans.shared.b16 {%0, %1, %2, %3}, [%4];" : "=r"(r[0]), "=r"(r[1]), "=r"(r[2]), "=r"(r[3]) : "r"(addr) : "memory");
}
DEVINL void sts128(uint32_t addr, uint32_t a, uint32_t b, uint32_t c, uint32_t d) {
  asm volatile("st.shared.v4.b32 [%0], {%1, %2, %3, %4};" ::"r"(addr), "r"(a), "r"(b), "r"(c), "r"(d) : "memory");
}
DEVINL float2 lds64f(uint32_t addr) { float2 v; asm volatile("ld.shared.v2.f32 {%0, %1}, [%2];" : "=f"(v.x), "=f"(v.y) : "r"(addr) : "memory"); return v; }
DEVINL void mma16816(float (&d)[4], uint32_t a0, uint32_t a1, uint32_t a2, uint32_t a3, uint32_t b0, uint32_t b1) {
  asm("mma.sync.aligned.m16n8k16.row.col.f32.bf16.bf16.f32 {%0, %1, %2, %3}, {%4, %5, %6, %7}, {%8, %9}, {%0, %1, %2, %3};"
               : "+f"(d[0]), "+f"(d[1]), "+f"(d[2]), "+f"(d[3]) : "r"(a0), "r"(a1), "r"(a2), "r"(a3), "r"(b0), "r"(b1));
}
template <int N> DEVINL void fence_regs(float (&d)[N]) {
#pragma unroll
  for (int i = 0; i < N; i++) asm volatile("" : "+f"(d[i])::"memory");
}
template <int N> DEVINL void fence_regs(uint32_t (&d)[N]) {
#pragma unroll
  for (int i = 0; i < N; i++) asm volatile("" : "+r"(d[i])::"memory");
}
DEVINL void lds128(uint32_t addr, uint32_t* r) {
  asm volatile("ld.shared.v4.b32 {%0, %1, %2, %3}, [%4];" : "=r"(r[0]), "=r"(r[1]), "=r"(r[2]), "=r"(r[3]) : "r"(addr) : "memory");
}
DEVINL void sched_fence() { asm volatile("griddepcontrol.launch_dependents;" ::: "memory"); }

struct Scratch {
  bf16 k[32 * 2048 * 32];
  bf16 xs[2048 * 1024];
  bf16 os[2048 * 1024];
  bf16 v[32 * 2048 * 32];
  float kn[2 * 128 * 16];
  uint32_t cnt[256 * 32];
  float2 stats[8 * 2048];
  uint4 halo[128 * 12 * 32];
  float csp[2 * 16 * 8 * 192];
  uint4 qsave[128 * 256 * 8];
  uint32_t esc[4 * 65536 * 20];
};
__device__ __align__(1024) Scratch g_s;
#define g_k g_s.k
#define g_xs g_s.xs
#define g_os g_s.os
#define g_v g_s.v
#define g_kn g_s.kn
#define g_cnt g_s.cnt
#define g_stats g_s.stats
#define g_halo g_s.halo
#define g_csp g_s.csp
#define g_qsave g_s.qsave
#define g_esc g_s.esc
#define g_epoch g_s.cnt[255 * 32]

DEVINL uint32_t* cnt_x(int bm) { return g_cnt + bm * 32; }
DEVINL uint32_t* cnt_o(int l, int pm, int h) { return g_cnt + (32 + (l * 16 + pm) * 2 + h) * 32; }
DEVINL uint32_t* cnt_kv(int lb, int bn) { return g_cnt + (160 + lb * 16 + bn) * 32; }
DEVINL uint32_t* cnt_ad(int bn) { return g_cnt + (192 + bn) * 32; }
DEVINL uint32_t* cnt_cs(int t, int bn) { return g_cnt + (208 + t * 16 + bn) * 32; }

DEVINL int qord(int i, int l, int pn) {
  const int u = i < 10 ? i - 4 : i - 10;
  return l == 0 ? i : i < 4 ? ((2 * pn) ^ (2 * (i & 1))) + (i >> 1) : 2 * (u < (pn & 6) ? u : u + 2) + (i >= 10);
}
struct Params {
  CUtensorMap m[15];
  const bf16* x0;
  const bf16* wq[2];
  const bf16* wo;
  uint32_t zero;
  int map[128];
  uint64_t wd, xd;
  struct __align__(16) { uint64_t kd, vd; } kv[4];
};
enum { M_X0A = 0, M_WQA, M_WQB, M_WOA, M_WOB, M_OS, M_K, M_V, M_X0R, M_XSR, M_XSO, M_OUT, M_XST, M_X0H, M_OL, M_COUNT };

constexpr uint32_t QSTG = 57344;
constexpr uint32_t T0 = 65536, TSTG = 32768;
constexpr uint32_t ONES = 230400;
constexpr uint32_t PSTG = 32768, RES = 196608;
constexpr uint32_t KSC = 98304, VSC = 133120, HRS = 167936;
constexpr uint32_t ROWST = 229376, COLS = 231424, BARS = 232192, SMEM_BYTES = 232448;
constexpr uint32_t B_QF = BARS, B_QE = BARS + 32, B_TF = BARS + 64, B_TE = BARS + 96, B_PF = BARS + 128, B_PE = BARS + 176,
                   B_RF = BARS + 224, W_X = BARS + 232, B_QL = BARS + 240, B_PA = BARS + 248;
enum { NB_ST = 1, NB_KV = 2  , NB_DONE = 3, NB_SC = 4, NB_SIG = 5  , NB_KN = 9  , NB_X = 11, NB_HALO = 12  , NB_X0 = 15 };

DEVINL uint32_t pslot_b(uint32_t s) { return ((0x320415u >> (4 * s)) & 7) * 16384u; }
DEVINL uint32_t pslot_a(uint32_t s, int l) { return 98304u + ((((l & 1) ? 0x541230u : 0x041235u) >> (4 * s)) & 7) * 16384u; }

constexpr float QSCALE = 0.17677669529663687f * 1.4426950408889634f;
constexpr uint32_t QPARK = 32768;

DEVINL uint32_t exp2_h2(uint32_t s, uint32_t c852) {
  uint32_t r, t, w, m, d;
  asm volatile("{.reg .b64 t; add.rn.f16x2 %0, %1, %2; cvt.u64.u32 t, %0; cvt.u32.u64 %0, t;}" : "=r"(r) : "r"(s), "r"(0x65EA65EAu));
  asm volatile("fma.rn.f16x2 %0, %1, %2, %3;" : "=r"(t) : "r"(r), "r"(0xB880B880u), "r"(c852));
  asm volatile("fma.rn.f16x2 %0, %1, %2, %3;" : "=r"(w) : "r"(s), "r"(0x38803880u), "r"(t));
  asm volatile("fma.rn.f16x2 %0, %1, %1, %2;" : "=r"(m) : "r"(w), "r"(0x4A1F4A2Du));
  asm volatile("{.reg .b32 t; shf.l.clamp.b32 t, %2, %1, 7; add.u32 %0, t, %2;}" : "=r"(d) : "r"(r), "r"(m));
  return d;
}
DEVINL float exp2_fix(float s) { float z; asm volatile("add.rn.f32 %0, %1, 0f43BF34BC;" : "=f"(z) : "f"(s)); return z; }
DEVINL uint32_t exp2_base(float z0, float z1) { uint32_t B; asm volatile("prmt.b32 %0, %1, %2, 0x6521;" : "=r"(B) : "r"(__float_as_uint(z0)), "r"(__float_as_uint(z1))); return B; }
template <uint32_t MASK> DEVINL uint32_t and_or(uint32_t a, uint32_t c) { uint32_t r; asm volatile("lop3.b32 %0, %1, %3, %2, 0xEA;" : "=r"(r) : "r"(a), "r"(c), "n"(MASK)); return r; }
DEVINL uint32_t fma_bf2(uint32_t a, uint32_t b, uint32_t c) { uint32_t r; asm volatile("fma.rn.bf16x2 %0, %1, %2, %3;" : "=r"(r) : "r"(a), "r"(b), "r"(c)); return r; }
DEVINL float ex2v(float x) { float y; asm volatile("ex2.approx.ftz.f32 %0, %1;" : "=f"(y) : "f"(x)); return y; }
DEVINL uint32_t pack2v(float lo, float hi) { uint32_t r; asm volatile("cvt.rn.bf16x2.f32 %0, %1, %2;" : "=r"(r) : "f"(hi), "f"(lo)); return r; }
DEVINL void unesc(uint32_t (&u)[4], const uint32_t* esc, uint32_t tag) {
  const bool saved = __ldcg(esc + 16) == tag;
#pragma unroll
  for (int j = 0; j < 4; j++) {
    float lo, hi;
    asm("{.reg .f16 a, b; mov.b32 {a, b}, %2; cvt.f32.f16 %0, a; cvt.f32.f16 %1, b;}" : "=f"(lo), "=f"(hi) : "r"(u[j]));
    u[j] = saved ? __ldcg(esc + 4 * j) : pack2(lo, hi);
  }
}

DEVINL void attn_slow(const uint32_t (&q)[8], int head, const uint32_t* kesc, uint32_t tag, float (&res)[20], int lane) {
  const int g = lane >> 2, qd = lane & 3;
  const bf16* kb = g_k + (size_t)head * 2048 * 32;
  const bf16* vb = g_v + (size_t)head * 2048 * 32;
  float o[4][4], m0 = -INFINITY, m1 = -INFINITY, l0 = 0.f, l1 = 0.f;
#pragma unroll
  for (int j = 0; j < 4; j++) { o[j][0] = o[j][1] = o[j][2] = o[j][3] = 0.f; }
#pragma unroll 1
  for (int k0 = 0; k0 < 2048; k0 += 16) {
    float s[2][4];
#pragma unroll
    for (int nt = 0; nt < 2; nt++) {
      s[nt][0] = s[nt][1] = s[nt][2] = s[nt][3] = 0.f;
      const uint32_t* kp = (const uint32_t*)(kb + (size_t)(k0 + nt * 8 + g) * 32) + qd;
      uint32_t k[4] = {__ldcg(kp), __ldcg(kp + 4), __ldcg(kp + 8), __ldcg(kp + 12)};
      unesc(k, kesc + (k0 + nt * 8 + g) * 20 + qd, tag);
      __syncwarp();
      mma16816(s[nt], q[0], q[1], q[2], q[3], k[0], k[1]);
      mma16816(s[nt], q[4], q[5], q[6], q[7], k[2], k[3]);
    }
    float a0 = fmaxf(fmaxf(s[0][0], s[0][1]), fmaxf(s[1][0], s[1][1]));
    float a1 = fmaxf(fmaxf(s[0][2], s[0][3]), fmaxf(s[1][2], s[1][3]));
    a0 = fmaxf(a0, __shfl_xor_sync(~0u, a0, 1)); a0 = fmaxf(a0, __shfl_xor_sync(~0u, a0, 2));
    a1 = fmaxf(a1, __shfl_xor_sync(~0u, a1, 1)); a1 = fmaxf(a1, __shfl_xor_sync(~0u, a1, 2));
    const float n0 = fmaxf(m0, a0), n1 = fmaxf(m1, a1);
    const float c0 = (m0 == n0) ? 1.f : ex2(m0 - n0), c1 = (m1 == n1) ? 1.f : ex2(m1 - n1);
    m0 = n0; m1 = n1;
    const uint32_t p0 = pack2(ex2(s[0][0] - n0), ex2(s[0][1] - n0)), p1 = pack2(ex2(s[0][2] - n1), ex2(s[0][3] - n1));
    const uint32_t p2 = pack2(ex2(s[1][0] - n0), ex2(s[1][1] - n0)), p3 = pack2(ex2(s[1][2] - n1), ex2(s[1][3] - n1));
    l0 = l0 * c0 + bf_lo(p0) + bf_hi(p0) + bf_lo(p2) + bf_hi(p2);
    l1 = l1 * c1 + bf_lo(p1) + bf_hi(p1) + bf_lo(p3) + bf_hi(p3);
#pragma unroll
    for (int j = 0; j < 4; j++) {
      o[j][0] *= c0; o[j][1] *= c0; o[j][2] *= c1; o[j][3] *= c1;
      const unsigned short* vp = (const unsigned short*)(vb + (size_t)(k0 + 2 * qd) * 32 + j * 8 + g);
      const uint32_t b0 = (uint32_t)__ldcg(vp) | ((uint32_t)__ldcg(vp + 32) << 16);
      const uint32_t b1 = (uint32_t)__ldcg(vp + 256) | ((uint32_t)__ldcg(vp + 288) << 16);
      mma16816(o[j], p0, p1, p2, p3, b0, b1);
    }
  }
  l0 += __shfl_xor_sync(~0u, l0, 1); l0 += __shfl_xor_sync(~0u, l0, 2);
  l1 += __shfl_xor_sync(~0u, l1, 1); l1 += __shfl_xor_sync(~0u, l1, 2);
#pragma unroll
  for (int j = 0; j < 4; j++) { res[4 * j] = o[j][0]; res[4 * j + 1] = o[j][1]; res[4 * j + 2] = o[j][2]; res[4 * j + 3] = o[j][3]; }
  res[16] = l0; res[18] = l1;
}

__device__ __noinline__ void attn_redo(int redo, int l, int b, int wg, int w, uint32_t tag) {
  const int lane = lane_id();
#pragma unroll 1
  for (int t = 0; t < 4; t++) {
    const int h = t >> 1, head = 2 * (b & 15) + h, row = (b >> 4) * 256 + wg * 128 + (t & 1) * 64 + w * 16 + (lane >> 2);
    if ((redo >> t) & 1) {
      const uint32_t* esc = g_esc + (size_t)((l & 2) * 65536 + head * 2048) * 20;
      const uint32_t* qs = (const uint32_t*)(g_qsave + (block_id() * 256 + wg * 128 + w * 32 + lane) * 8 + 2 * t);
      uint32_t q[8]; float o[20];
#pragma unroll
      for (int i = 0; i < 2; i++) {
        uint32_t u[4] = {__ldcg(qs + i), __ldcg(qs + i + 2), __ldcg(qs + i + 4), __ldcg(qs + i + 6)};
        unesc(u, esc + (row + i * 8) * 20 + (lane & 3), tag);
        q[i] = u[0]; q[i + 2] = u[1]; q[i + 4] = u[2]; q[i + 6] = u[3];
      }
      __syncwarp();
      attn_slow(q, head, esc + 65536 * 20, tag, o, lane);
      const float i0 = rcp(o[16]), i1 = rcp(o[18]);
      bf16* op = g_os + (size_t)row * 1024 + h * 512 + (b & 15) * 32 + (lane & 3) * 8;
      *(uint4*)op = make_uint4(pack2(o[0] * i0, o[1] * i0), pack2(o[4] * i0, o[5] * i0), pack2(o[8] * i0, o[9] * i0), pack2(o[12] * i0, o[13] * i0));
      *(uint4*)(op + 8 * 1024) = make_uint4(pack2(o[2] * i1, o[3] * i1), pack2(o[6] * i1, o[7] * i1), pack2(o[10] * i1, o[11] * i1), pack2(o[14] * i1, o[15] * i1));
    }
    if ((t & 1) && ((redo >> 2 * h) & 3)) bar_arrive(NB_SIG + 2 * h + wg, 160 + 32 * (h & wg));
  }
}

__global__ void __cluster_dims__(2, 1, 1) __launch_bounds__(384, 1) fused_kernel(const __grid_constant__ Params prm) {
  extern __shared__ __align__(1024) char smem[];
  const uint32_t sb = (uint32_t)__cvta_generic_to_shared(smem);
  const int tid = threadIdx.x, lane = tid & 31;
  const int wg = __shfl_sync(0xffffffffu, tid >> 7, 0);
  const int w = __shfl_sync(0xffffffffu, (tid >> 5) & 3, 0);
  const int bm = remap(blockIdx.x) >> 4, bn = remap(blockIdx.x) & 15;

  auto first_tile = [&](int kt) {
    e_expect_tx(sb + B_QF + 8 * kt, QSTG);
    tma_ld(sb + kt * QSTG, &prm.m[M_X0A], kt * 64, bm * 256, sb + B_QF + 8 * kt);
    tma_ld3(sb + kt * QSTG + 32768, &prm.m[M_WQA], bn * 64, kt * 64, 0, sb + B_QF + 8 * kt);
  };
  auto init4 = [&](uint32_t bar, uint32_t c0, uint32_t c1, uint32_t c2, uint32_t c3) {
    asm volatile("{\n.reg .pred pe;\nelect.sync _|pe, 0xffffffff;\n@pe mbarrier.init.shared::cta.b64 [%0], %1;\n@pe mbarrier.init.shared::cta.b64 [%0+8], %2;\n"
                 "@pe mbarrier.init.shared::cta.b64 [%0+16], %3;\n@pe mbarrier.init.shared::cta.b64 [%0+24], %4;\n@pe fence.mbarrier_init.release.cluster;\n}"
                 ::"r"(bar), "r"(c0), "r"(c1), "r"(c2), "r"(c3) : "memory");
  };
  if (wg < 2) {
    const uint32_t k = wg * 4 + w, lo = (0x1411814u >> (4 * k)) & 15, hi = (0x1441814u >> (4 * k)) & 15;
    if (tid < 32) asm volatile("prefetch.global.L2 [%0];" ::"l"(prm.x0 + (size_t)(bm * 256 + bn * 16 + (tid & 15)) * 1024 + (tid >> 4) * 64));
    else if (tid < 80) asm volatile("prefetch.global.L2 [%0];" ::"l"(prm.wq[0] + (bm * 16 + (tid & 15)) * 3072 + ((tid >> 4) - 2) * 1024 + bn * 64));
    __syncwarp();
    if (k < 7) init4(sb + B_QE + 32 * k, lo, lo, hi, k == 6 ? 2 : hi);
    __syncwarp();
    if (k == 6 && lane == 0) *(volatile unsigned long long*)(smem + W_X) = 0ull;
  } else if (w == 0) {
    init4(sb + B_QF, 1, 1, 1, 1);
    __syncwarp();
    first_tile(0);
  }
  __syncthreads();
  asm volatile("barrier.cluster.arrive.relaxed.aligned;" ::: "memory");

  if (wg == 2) {
    asm volatile("setmaxnreg.dec.sync.aligned.u32 56;");
    const uint32_t ep1 = *(volatile uint32_t*)&g_epoch + 1;
    if (w == 0) {
      first_tile(1);
      mbar_wait(sb + B_QF, 0);
      first_tile(2); first_tile(3);
#pragma unroll 1
      for (int kt = 4; kt < 16; kt++) l2_prefetch(prm.wq[0] + kt * 196608 + blockIdx.x * 1536, 3072);
      cluster_wait();
#pragma unroll 1
      for (int l = 0; l < 4; l++) {
        IDS();
        const CUtensorMap* mw = &prm.m[M_WQA + (l & 1)];
        const CUtensorMap* mh = &prm.m[l == 0 ? M_X0H : M_XSO];
        const CUtensorMap* mo = &prm.m[M_WOA + (l & 1)];
        auto q_b = [&](int i) {
          const int s = i & 3;
          mbar_wait(sb + B_QE + 8 * s, ((i >> 2) & 1) ^ 1);
          e_expect_tx(sb + B_QF + 8 * s, QSTG);
          tma_ld3(sb + s * QSTG + 32768, mw, bn * 64, qord(i, l, pn) * 64, 0, sb + B_QF + 8 * s);
        };
        uint32_t rdy = l ? 0u : ~0u;
        auto q_a = [&](int i) {
          const int kt = qord(i, l, pn);
          await_flag(kt, rdy, cnt_x(bm) + (lane & 15), ep1 * 9 - 6 + 2 * l);
          tma_ld_mc(sb + (i & 3) * QSTG + rank * 16384, mh, kt * 64, bm * 256 + rank * 128, sb + B_QF + 8 * (i & 3));
        };
        if (l > 0) {
#pragma unroll 1
          for (int i = 0; i < 4; i++) {
            const int kt = qord(i, l, pn);
            await_flag(kt, rdy, cnt_x(bm) + (lane & 15), ep1 * 9 - 6 + 2 * l);
            e_expect_tx(sb + B_QF + 8 * i, 16384);
            tma_ld(sb + i * QSTG + (po ^ 1) * 16384, &prm.m[M_XSO], kt * 64, (pm ^ 1) * 128, sb + B_QF + 8 * i);
          }
        }
#pragma unroll 1
        for (int i = 4; i < 16; i++) {
          if (l == 3 && i == 12) poll_ge(cnt_ad(bn), ep1 * 16);
          q_b(i); q_a(i);
          if (l == 0 && i >= 8) l2_prefetch(prm.wq[1] + ((i - 8) * 128 + blockIdx.x) * 3072, 6144);
          if (l == 0 && i >= 8) l2_prefetch(prm.wo + ((i - 8) * 128 + blockIdx.x) * 1024, 2048);
        }
        if (l & 1) {
          const int krow = 2 * bn * 2048 + bm * 256;
          uint32_t* kvc = cnt_kv(l >> 1, bn);
          uint32_t seen = 0;
#pragma unroll 1
          for (int it = 1; it < 16; it++) {
            const int s = it & 3;
            if (it == 4) {
              bar_sync(NB_KV + 12, 288);
              mbar_wait(sb + B_TF + 24, 0);
#pragma unroll 1
              for (int i = 0; i < 4; i++) tma_st(&prm.m[M_K + (i & 1)], 0, krow + 2048 + (i >> 1) * 128, sb + i * 8192);
              bulk_commit();
            }
            if (it == 5) { bulk_wait_n<0>(); e_red(kvc + 16 + bm); }
            if (it == 12) { e_expect_tx(sb + B_RF, 32768); tma_ld3(sb + RES, &prm.m[M_XSR], 0, pm * 128, 2 * pn, sb + B_RF); }
            if (it == 1 || it == 3) mbar_wait(sb + B_QE + 12 + 4 * it, 1);
            mbar_wait(sb + B_TE + 8 * s, ((it >> 2) & 1) ^ 1);
            if (it < 8) {
#pragma unroll 1
              for (uint32_t n = 0; n < 200000u && (~seen & (3u << (2 * it - 2) | (it == 4 ? 0xC000u : 0u))); n++)
                seen = __ballot_sync(~0u, (int)(ld_acquire(kvc + (lane < 7 || lane == 15 ? (bm + 1 + lane) & 7 : 8 + ((bm + 2 + lane) & 7))) - ep1) >= 0);
              fence_async_gl();
            } else if (it == 8) { poll_ge(kvc + 16 + (lane & 7), ep1); fence_async_gl(); }
            e_expect_tx(sb + B_TF + 8 * s, 32768);
#pragma unroll 1
            for (int i = 0; i < 2; i++) {
              const int u = 2 * it - 2 + i;
              const int row = 2 * bn * 2048 + (it > 7 ? 2048 + ((bm + it) & 7) * 256 + i * 128 : u < 7 ? ((bm + 1 + u) & 7) * 256 : ((bm + 2 + u) & 7) * 256 + 128);
              tma_ld(sb + T0 + s * TSTG + i * 8192, &prm.m[M_K], 0, row, sb + B_TF + 8 * s);
              tma_ld(sb + T0 + s * TSTG + 16384 + i * 8192, &prm.m[M_V], 0, row, sb + B_TF + 8 * s);
            }
          }
        }
        auto p_b = [&](int i, uint32_t s, uint32_t par) {
          mbar_wait(sb + B_PE + 8 * s, par ^ 1);
          e_expect_tx(sb + B_PF + 8 * s, PSTG);
          tma_ld5(sb + pslot_b(s), mo, i >> 3, (2 * i + bn) & 14, 2 * pn, sb + B_PF + 8 * s);
        };
        auto p_a = [&](int i, uint32_t s) {
          await_flag(i, rdy, cnt_o(l, pm, (lane >> 3) & 1) + ((lane + (bn >> 1)) & 7), ep1 * 2);
          tma_ld_mc(sb + pslot_a(s, l) + rank * 8192, &prm.m[M_OS], (i & 8) * 64 + ((2 * i + bn) & 14) * 32, pm * 128 + rank * 64, sb + B_PF + 8 * s);
        };
        auto p_a2 = [&](int i) {
          await_flag(i, rdy, cnt_o(l, pm, (lane >> 3) & 1) + ((lane + (bn >> 1)) & 7), ep1 * 2);
          tma_ld(sb + pslot_a(i, l), &prm.m[M_OS], (i & 8) * 64 + ((2 * i + bn) & 14) * 32, pm * 128, sb + B_PF + 8 * i);
          tma_ld(sb + pslot_a(i, l) + 8192, &prm.m[M_OS], (i & 8) * 64 + ((2 * i + bn) & 14) * 32, pm * 128 + 64, sb + B_PF + 8 * i);
        };
        rdy = 0;
        if (l & 1) {
#pragma unroll 1
          for (int u = 0; u < 6; u++) { const int i = (0x205413 >> (4 * u)) & 7; if (u == 4) mbar_wait(sb + B_TE, 1); p_b(i, i, i < 4 ? 1 : 0); }
#pragma unroll 1
          for (int u = 0; u < 6; u++) {
            const int i = (0x542130 >> (4 * u)) & 7;
            if (!(u & 1)) mbar_wait(sb + B_TE + 8 + 4 * u, 1);
            if (u == 4) bar_sync(NB_SIG + 3, 192);
            p_a2(i);
          }
        } else {
#pragma unroll 1
          for (int u = 0; u < 6; u++) { const int i = (0x543120 >> (4 * u)) & 7; if (u == 0 || u == 2) mbar_wait(sb + B_QE + 8 - 4 * u, 1); p_b(i, i, 0); }
          mbar_wait(sb + B_QE + 24, 1);
          e_expect_tx(sb + B_RF, 32768);
          tma_ld3(sb + RES, &prm.m[l == 0 ? M_X0R : M_XSR], 0, pm * 128, 2 * pn, sb + B_RF);
          await_flag(1, rdy, cnt_o(l, pm, (lane >> 3) & 1) + ((lane + (bn >> 1)) & 7), ep1 * 2);
          bar_sync(NB_DONE, 288);
          e_arrive_both(sb + B_PA);
          mbar_wait(sb + B_PA, (l >> 1) & 1);
#pragma unroll 1
          for (int i = 1; i < 6; i++) { if (i > 3) mbar_wait(sb + B_PF + 8 * (i - 3), 0); p_a(i, i); }
        }
        uint32_t s = 0, lap = 1;
#pragma unroll 1
        for (int i = 6; i < 16; i++) {
          p_b(i, s, ((s < 4 ? l : 0) + lap) & 1);
          p_a(i, s);
          if (++s == 6) { s = 0; lap++; }
        }
        const CUtensorMap* mn = &prm.m[M_WQA + ((l + 1) & 1)];
        if (l < 3) {
          mbar_wait(sb + B_PE + 8 * 4, 1); mbar_wait(sb + B_PE + 8 * 5, 1);
          tma_ld3(sb + 32768, mn, bn * 64, 2 * pn * 64, 0, sb + B_QL);
          mbar_wait(sb + B_PE + 8 * 0, l & 1);
          e_expect_tx(sb + B_PA, 24576); e_expect_tx(sb + B_PA, 16384);
          tma_ld3(sb + QSTG + 32768, mn, bn * 64, ((2 * pn) ^ 2) * 64, 0, sb + B_PA);
          mbar_wait(sb + B_PE + 8 * 1, l & 1);
          tma_ld3(sb + 2 * QSTG + 32768, mn, bn * 64, (2 * pn + 1) * 64, 0, sb + B_QL);
          bar_sync(NB_KN, 288);
          e_expect_tx(sb + B_RF, 40960);
          tma_ld3(sb + 3 * QSTG + 32768, mn, bn * 64, ((2 * pn) ^ 3) * 64, 0, sb + B_RF);
          mbar_wait(sb + B_PE + 24, l & 1);
          bar_sync(NB_X0, 320);
          fence_async_gl();
          tma_ld_mc(sb + QSTG + po * 16384, &prm.m[M_XSO], 2 * pn * 64, pm * 128, sb + B_PA, 2 - rank);
          bar_sync(NB_X, 320);
          e_expect_tx(sb + B_QL, 49152);
        }
      }
      if (blockIdx.x == 0 && lane_id() == 0) *(volatile uint32_t*)&g_epoch = ep1;
    } else {
      const int hw = w - 1;
      if (lane < 5) asm volatile("prefetch.tensormap [%0];" ::"l"(&prm.m[5 * hw + lane]) : "memory");
      __syncwarp();
      cluster_wait();
      mbar_wait(sb + B_QF, 0);
#pragma unroll 1
      for (int l = 0; l < 4; l++) {
        IDS();
        if (l > 0) { mbar_wait(sb + B_QL, (l + 1) & 1); mbar_wait(sb + B_QF + 24, 0); }
        if (l == 0) {
#pragma unroll 1
          for (int r = 2 * hw; r < 16; r += 6) {
            const uint4* p = (const uint4*)(prm.x0 + (size_t)(b * 16 + r) * 1024) + lane;
            float s1[2] = {0.f, 0.f}, s2[2] = {0.f, 0.f};
#pragma unroll
            for (int i = 0; i < 8; i++) {
              const uint4 v = __ldg(p + 32 * i);
              const uint32_t u[4] = {v.x, v.y, v.z, v.w};
#pragma unroll
              for (int k = 0; k < 4; k++) { const float a = bf_lo(u[k]), c = bf_hi(u[k]); s1[i >> 2] += a + c; s2[i >> 2] = fmaf(a, a, fmaf(c, c, s2[i >> 2])); }
            }
#pragma unroll
            for (int o = 16; o; o >>= 1)
#pragma unroll
              for (int rr = 0; rr < 2; rr++) { s1[rr] += __shfl_xor_sync(~0u, s1[rr], o); s2[rr] += __shfl_xor_sync(~0u, s2[rr], o); }
            if (lane == 0) *(float4*)&g_stats[b * 16 + r] = make_float4(s1[0], s2[0], s1[1], s2[1]);
          }
        }
        if (l < 2) {
          float cs[8];
#pragma unroll
          for (int i = 0; i < 8; i++) cs[i] = 0.f;
          const uint4* wp = (const uint4*)(prm.wq[l] + (size_t)(bm * 128 + (lane >> 3)) * 3072 + hw * 1024 + bn * 64) + (lane & 7);
#pragma unroll 8
          for (int i = 0; i < 32; i++) {
            const uint4 v = __ldg(wp + (size_t)i * 4 * 384);
            cs[0] += bf_lo(v.x); cs[1] += bf_hi(v.x); cs[2] += bf_lo(v.y); cs[3] += bf_hi(v.y);
            cs[4] += bf_lo(v.z); cs[5] += bf_hi(v.z); cs[6] += bf_lo(v.w); cs[7] += bf_hi(v.w);
          }
#pragma unroll
          for (int i = 0; i < 8; i++) { cs[i] += __shfl_xor_sync(~0u, cs[i], 8); cs[i] += __shfl_xor_sync(~0u, cs[i], 16); }
          if (lane < 8) {
            float4* d = (float4*)(g_csp + ((l * 16 + bn) * 8 + bm) * 192 + hw * 64 + lane * 8);
            d[0] = make_float4(cs[0], cs[1], cs[2], cs[3]); d[1] = make_float4(cs[4], cs[5], cs[6], cs[7]);
          }
          __syncwarp();
          asm volatile("fence.acq_rel.gpu;" ::: "memory");
          e_red_relaxed(cnt_cs(l, bn));
          if (l == 0) e_red_relaxed(cnt_x(bm) + bn);
          poll_ge(lane < 16 && l == 0 ? cnt_x(bm) + lane : cnt_cs(l, bn), lane < 16 && l == 0 ? ep1 * 9 - 6 : ep1 * 24);
        }
        if (l > 0) poll_ge(cnt_x(bm) + (lane & 15), ep1 * 9 - 6 + 2 * l);
#pragma unroll 1
        for (int it = hw * 32 + lane; it < 176; it += 96) {
          const bool rows = it < 128;
          const float4* p = rows ? (const float4*)(g_stats + bm * 256) + it : (const float4*)(g_csp + ((l & 1) * 16 + bn) * 8 * 192) + (it - 128);
          const int stride = rows ? 1024 : 48, np = rows && l == 0 ? 1 : 8;
          float4 a = make_float4(0.f, 0.f, 0.f, 0.f);
#pragma unroll
          for (int k = 0; k < 8; k++) if (k < np) { const float4 v = __ldcg(p + k * stride); a.x += v.x; a.y += v.y; a.z += v.z; a.w += v.w; }
          if (rows) {
            const float m0 = a.x * (1.f / 1024.f), m1 = a.z * (1.f / 1024.f);
            const float v0 = fmaxf(a.y * (1.f / 1024.f) - m0 * m0, 0.f), v1 = fmaxf(a.w * (1.f / 1024.f) - m1 * m1, 0.f);
            const float r0 = __fdividef(1.f, bf_round(sqrtf(bf_round(bf_round(v0) + 1e-5f)))), r1 = __fdividef(1.f, bf_round(sqrtf(bf_round(bf_round(v1) + 1e-5f))));
            a = make_float4(r0, -bf_round(m0), r1, -bf_round(m1));
          }
          if (rows && (l & 1) && (it & 4)) a = make_float4(a.y, a.x, a.w, a.z);
          *(float4*)(smem + ROWST + it * 16) = a;
        }
        __syncwarp();
        if (lane == 0) asm volatile("red.release.cta.shared.add.u32 [%0], 1;" ::"r"(sb + W_X) : "memory");
        if (hw == 2) {
          if (!(l & 1)) {
            bar_sync(NB_ST, 288);
            const uint4* hp = g_halo + (b - 16) * 384 + lane;
#pragma unroll 1
            for (int h = 0; h < 2; h++) {
              uint32_t t[18];
#pragma unroll
              for (int i = 0; i < 18; i++) t[i] = 0;
#pragma unroll 1
              for (uint32_t n = bm ? 0 : 100000u; n < 100000u; n++) {
                uint32_t miss = 0;
#pragma unroll
                for (int i = 0; i < 6; i++) miss |= ld_tagged(hp + h * 192 + i * 32, &t[3 * i]) ^ (4 * ep1 + l);
                if (__all_sync(~0u, !miss)) break;
              }
              mbar_wait(sb + B_QE + 16, 1);
              const uint32_t r = (lane & 7) + ((lane >> 3) & 1) * 8, rv = lane >> 2;
#pragma unroll
              for (int jj = 0; jj < 2; jj++) stsm4(sb + KSC + r * 128 + (((4 * h + 2 * jj + (lane >> 4)) ^ (r & 7)) << 4), t[4 * jj], t[4 * jj + 1], t[4 * jj + 2], t[4 * jj + 3]);
              const uint32_t ad = sb + VSC + rv * 128 + (((4 * h + (lane & 3)) ^ (rv & 7)) << 4);
              sts128(ad, t[8], t[10], t[12], t[14]); sts128(ad + 1024, t[9], t[11], t[13], t[15]);
              if (h == 0 && !(lane & 2)) *(uint32_t*)(smem + HRS + ((lane >> 2) + 8 * (lane & 1)) * 8) = t[16];
              bar_arrive(NB_HALO + h, 64);
            }
          } else {
            bar_sync(NB_KV, 288);
            sts128(sb + ONES + lane * 32, 0x3f803f80u, 0x3f803f80u, 0x3f803f80u, 0x3f803f80u);
            sts128(sb + ONES + lane * 32 + 16, 0x3f803f80u, 0x3f803f80u, 0x3f803f80u, 0x3f803f80u);
            sts128(sb + ROWST + 16, 0x62A962A9u, 0x00010001u, 0x3F003F00u, 0u);
            fence_async_smem();
            __syncwarp();
            e_arrive(sb + B_TF);
            mbar_wait(sb + B_TF + 16, 0); mbar_wait(sb + B_TF + 16, 1);
            poll_ge(cnt_kv(l >> 1, bn) + 16 + (lane & 7), ep1);
            const uint4 v = __ldcg((const uint4*)(g_kn + ((l >> 1) * 128 + bn * 8) * 16) + lane);
            const uint32_t mx = max(max(v.x, v.y), max(v.z, v.w));
            const uint32_t m0 = __reduce_max_sync(~0u, (lane & 2) ? 0u : mx), m1 = __reduce_max_sync(~0u, (lane & 2) ? mx : 0u);
            if (lane == 0) *(uint2*)(smem + ROWST) = make_uint2(m0, m1);
            __syncwarp();
            bar_arrive(NB_KN, 160); bar_arrive(NB_KN + 1, 160);
          }
        } else {
          if (l & 1) {
            uint32_t* p = cnt_kv(l >> 1, bn) + 8 * hw + bm;
            int on = lane == 0;
            PREPARED(p, on);
            bar_sync(hw ? NB_HALO : NB_DONE, 160);
            tma_st(&prm.m[M_K], 0, 2 * bn * 2048 + bm * 256 + hw * 128, sb + T0 + hw * 8192);
            tma_st(&prm.m[M_V], 0, 2 * bn * 2048 + bm * 256 + hw * 128, sb + T0 + 16384 + hw * 8192);
            bulk_commit(); bulk_wait_n<0>();
            release_add(p, on);
          }
#pragma unroll 1
          for (int h = l & 1 ? 0 : hw; h <= (l & 1 ? 1 : hw); h++) {
            uint32_t* p = l == 1 && lane == 1 ? cnt_ad(bn) : cnt_o(l, 2 * bm + (l & 1 ? hw : lane & 1), h) + (bn >> 1);
            int on = lane == 0 || (lane == 1 && (!(l & 1) || (l == 1 && h == 1)));
            int id = NB_SIG + 2 * h + (l & hw), n = l & 1 ? 160 + 32 * (h & hw) : 288;
            asm volatile("" : "+r"(id), "+r"(n));
            PREPARED(p, on);
            bar_sync(id, n);
            release_add(p, on);
            if (!(l & 1) && hw == 0) {
              mbar_wait(sb + B_QE + 24, 1);
              fence_async_gl();
              tma_ld_mc(sb + pslot_a(0, 0) + rank * 8192, &prm.m[M_OL], bn * 32, pm * 128, sb + B_PF);
            }
          }
        }
        if (hw < 2 && l < 3) {
          uint32_t* p = cnt_x(bm) + 2 * pn + hw;
          int on = lane == 0;
          PREPARED(p, on);
          if (hw) {
            bar_sync(NB_X, 320);
            tma_st(&prm.m[M_XSO], pn * 128 + 64, pm * 128, sb + 2 * QSTG + po * 16384);
            bulk_commit();
            bar_sync(NB_KV, 288);
            bulk_wait_n<0>();
            mbar_wait(sb + B_PA, l == 0);
            fence_async_gl();
            tma_ld_mc(sb + 3 * QSTG + po * 16384, &prm.m[M_XSO], pn * 128 + 64, pm * 128, sb + B_RF, 2 - rank);
          } else bar_sync(NB_X0, 320);
          release_add(p, on);
        }
      }
    }
  } else {
    asm volatile("setmaxnreg.inc.sync.aligned.u32 224;");
    const uint32_t zero = prm.zero;
    cluster_wait();
#pragma unroll 1
    for (int l = 0; l < 4; l++) {
      {
        float acc[2][96];
        const bool early = l > 0 && wg == ((cta_id() >> 3) & 1);
        uint32_t ep1 = 0;
        if (l > 0) mbar_wait(sb + B_QL, (l + 1) & 1);
        if (!early) mbar_wait(sb + B_QF, 0);
        wg_fence();
#pragma unroll
        for (int k = 0; k < 4; k++)
#pragma unroll
          for (int m = 0; m < 2; m++) {
            if (k) wgmma_m64n192k16_ss_tb(acc[m], prm.xd + wg * 1024 + m * 512 + k * 2, prm.wd + k * 128, 1);
            else wgmma_m64n192k16_ss_tb_z(acc[m], prm.xd + wg * 1024 + m * 512, prm.wd, 0);
          }
        wg_commit();
#pragma unroll 1
        for (int kt = 1; kt < 13; kt++) {
          const int s = kt == 12 ? 1 : kt & 3;
          if (l > 0 && (kt | 2) == 3) mbar_wait(sb + (kt == 1 ? B_PA : B_RF), kt == 3 || l == 1);
          if (!(early && kt < 4)) mbar_wait(sb + B_QF + 8 * s, (kt >> 2) & 1);
          const uint64_t da = prm.xd + wg * 1024 + s * (QSTG >> 4), db = prm.wd + s * (QSTG >> 4);
          wg_fence();
#pragma unroll
          for (int k = 0; k < 4; k++)
#pragma unroll
            for (int m = 0; m < 2; m++) wgmma_m64n192k16_ss_tb(acc[m], da + m * 512 + k * 2, db + k * 128, 1);
          wg_commit();
          if (kt == 4) ep1 = *(volatile uint32_t*)&g_epoch + 1;
          wg_wait<1>();
          if (early && kt < 5) {
            if (kt < 3) continue;
#pragma unroll 1
            for (int i = 0; i < 8 - 2 * kt; i++) { mbar_wait(sb + B_QF + 8 * i, 0); if (w == 0) e_arrive_both(sb + B_QE + 8 * i); }
            mbar_wait(sb + B_QF + 8 * (kt - 1), 0);
          }
          if (w == 0) e_arrive_both(sb + B_QE + 8 * ((kt - 1) & 3));
        }
        {
          const bool lag = (l & 1) == wg;
          const uint32_t s0 = 2 * (~l & 1);
          const uint64_t da = prm.xd + wg * 1024 + 2 * (QSTG >> 4), db = prm.wd + 2 * (QSTG >> 4);
          mbar_wait(sb + B_QF + 8 * s0, 1);
#pragma unroll
          for (int t = 0; t < 2; t++) {
            if (lag && t != wg) {
              wg_wait<0>();
              if (w == 0) e_arrive_both(sb + B_QE + 8 + 8 * t);
              if (t == 0) mbar_wait(sb + B_QF + 16, 1);
              mbar_wait(sb + B_QF + 24, 1);
              if (t == 1) bar_arrive(NB_ST, 288);
              bar_sync(NB_SC, 256);
            }
            const uint64_t so = (uint64_t)(t ? s0 : s0 ^ 2) * (QSTG >> 4);
            wg_fence();
#pragma unroll
            for (int k = 0; k < 4; k++)
#pragma unroll
              for (int m = 0; m < 2; m++) wgmma_m64n192k16_ss_tb(acc[m], da - so + m * 512 + k * 2, db - so + k * 128, 1);
            wg_commit();
            if (!lag || t + wg == 0) {
              wg_wait<1>();
              if (w == 0) e_arrive_both(sb + B_QE + 8 * (t ? s0 : 1));
              mbar_wait(sb + B_QF + 8 * (t ? 3 : s0 ^ 2), 1);
            }
          }
          wg_fence();
#pragma unroll
          for (int m = 1; m >= 0; m--) {
#pragma unroll
            for (int k = 0; k < 4; k++) wgmma_m64n192k16_ss_tb(acc[m], da + (QSTG >> 4) + m * 512 + k * 2, db + (QSTG >> 4) + k * 128, 1);
            wg_commit();
          }
          if (!lag) { bar_arrive(NB_SC, 256); if (wg) bar_arrive(NB_ST, 288); }
          wg_wait<2>();
          if (w == 0) { e_arrive_both(sb + B_QE + 8 * (s0 ^ 2)); if (lag && wg) e_arrive_both(sb + B_QE); }
        }
#pragma unroll 1
        for (uint32_t n = 0; n < 4000000u; n++) {
          uint32_t v;
          asm volatile("ld.acquire.cta.shared.u32 %0, [%1];" : "=r"(v) : "r"(sb + W_X) : "memory");
          if (v == (uint32_t)(3 * l + 3)) break;
        }
        IDS();
        const int g = lane >> 2, qd = lane & 3;
        float2 st[2][2];
#pragma unroll
        for (int m = 0; m < 2; m++)
#pragma unroll
          for (int hh = 0; hh < 2; hh++) st[m][hh] = lds64f(sb + ROWST + (wg * 128 + m * 64 + w * 16 + g + 8 * hh) * 8);
        float2 cs[4];
        auto load_cs = [&](int gi) {
#pragma unroll
          for (int j = 0; j < 4; j++) cs[j] = lds64f(sb + COLS + (gi * 32 + j * 8 + 2 * qd) * 4);
        };
        load_cs(2 + 2 * (l & 1));
        auto drain = [&]() {
          wg_wait<0>(); fence_regs(acc[0]);
          if (w == 0) e_arrive_both(sb + B_QE + 8 * 3);
        };
        wg_wait<1>(); fence_regs(acc[1]);
        auto norm_tile = [&](int gi, int m, float sc, uint32_t (&t)[8], bool h16 = false) {
          const float r0 = st[m][0].x * sc, s0 = st[m][0].y, r1 = st[m][1].y * sc, s1 = st[m][1].x;
#pragma unroll
          for (int j = 0; j < 4; j++) {
            const float* a = &acc[m][16 * gi + 4 * j];
            const float v0 = fmaf(s0, cs[j].x, a[0]) * r0, v1 = fmaf(s0, cs[j].y, a[1]) * r0;
            const float v2 = fmaf(s1, cs[j].x, a[2]) * r1, v3 = fmaf(s1, cs[j].y, a[3]) * r1;
            t[2 * j] = h16 ? pack2h(v0, v1) : pack2(v0, v1); t[2 * j + 1] = h16 ? pack2h(v2, v3) : pack2(v2, v3);
          }
        };
        uint32_t q[2][2][8];
        const uint32_t srow = (lane & 7) + ((lane >> 3) & 1) * 8;
        const uint32_t row0 = wg * 128 + w * 16;
        if (!(l & 1)) {
          auto put_kv = [&](int gi, uint32_t r0, const uint32_t (&t)[8]) {
            if (gi < 4) {
              const uint32_t r = r0 + srow;
#pragma unroll
              for (int jj = 0; jj < 2; jj++) stsm4(sb + KSC + r * 128 + (((4 * (gi - 2) + 2 * jj + (lane >> 4)) ^ (r & 7)) << 4), t[4 * jj], t[4 * jj + 1], t[4 * jj + 2], t[4 * jj + 3]);
            } else {
              const uint32_t r = r0 + g, ad = sb + VSC + r * 128 + (((4 * (gi - 4) + qd) ^ (r & 7)) << 4);
              sts128(ad, t[0], t[2], t[4], t[6]); sts128(ad + 1024, t[1], t[3], t[5], t[7]);
            }
          };
          auto cen_tile = [&](int gi, int m, uint32_t (&t)[8]) {
#pragma unroll
            for (int j = 0; j < 4; j++) {
              const float* a = &acc[m][16 * gi + 4 * j];
              t[2 * j] = pack2(fmaf(st[m][0].y, cs[j].x, a[0]), fmaf(st[m][0].y, cs[j].y, a[1]));
              t[2 * j + 1] = pack2(fmaf(st[m][1].y, cs[j].x, a[2]), fmaf(st[m][1].y, cs[j].y, a[3]));
            }
          };
          const bool send = wg == 1 && w == 3 && bm < 7;
          uint4* hp = g_halo + b * 384 + lane;
          ep1 = 4 * ep1 + l;
          mbar_wait(sb + B_QE + 16, 1);
          float2 cn[4];
          auto next_cs = [&](int gi) {
#pragma unroll
            for (int j = 0; j < 4; j++) { cs[j] = cn[j]; cn[j] = lds64f(sb + COLS + (gi * 32 + j * 8 + 2 * qd) * 4); }
          };
#pragma unroll
          for (int j = 0; j < 4; j++) cn[j] = cs[j];
          auto lower = [&](int h, int nx, bool snd) {
            uint32_t k[8], v[8];
            next_cs(4 + h);
            cen_tile(2 + h, 1, k); put_kv(2 + h, 16 + row0 + 64, k);
            next_cs(nx);
            cen_tile(4 + h, 1, v); put_kv(4 + h, 16 + row0 + 64, v);
            if (snd) {
              uint4* p = hp + h * 192;
              st_tagged(p, k[0], k[1], k[2], ep1); st_tagged(p + 32, k[3], k[4], k[5], ep1); st_tagged(p + 64, k[6], k[7], v[0], ep1);
              st_tagged(p + 96, v[1], v[2], v[3], ep1); st_tagged(p + 128, v[4], v[5], v[6], ep1);
              st_tagged(p + 160, v[7], __float_as_uint(qd & 1 ? st[1][1].x : st[1][0].x), 0u, ep1);
            }
          };
          lower(0, 2 + wg, send);
          sched_fence();
          if (wg) lower(1, 2, send);
          drain();
          {
            uint32_t t[8];
            next_cs(4); cen_tile(2, 0, t); put_kv(2, 16 + row0, t);
            next_cs(0); cen_tile(4, 0, t); put_kv(4, 16 + row0, t);
            next_cs(3); cen_tile(0, 0, q[0][0]); cen_tile(0, 1, q[0][1]);
          }
          auto upper = [&]() {
            uint32_t t[8];
            next_cs(5); cen_tile(3, 0, t); put_kv(3, 16 + row0, t);
            next_cs(1); cen_tile(5, 0, t); put_kv(5, 16 + row0, t);
          };
          if (wg) upper();
          const bool e = g & 1, sel = 2 * qd + (g & 1) >= g + 2, first = bm == 0 && row0 == 0;
          uint32_t ka = sb + KSC + (row0 + (lane & 7)) * 128 + (((lane >> 3) ^ (lane & 7)) << 4);
          uint32_t wa = sb + VSC + (row0 + srow) * 128 + (((lane >> 4) ^ (lane & 7)) << 4);
          uint32_t psel[3] = {e ? 0x1044u : 0x4410u, !sel ? 0x4444u : e ? 0x3244u : 0x4432u, sel ? 0x4444u : e ? 0x3244u : 0x4432u};
          bf16* op = g_os + (size_t)(bm * 256 + row0 + g) * 1024 + bn * 32 + qd * 8;
          asm volatile("" : "+r"(ka), "+r"(wa), "+l"(op));
          fence_regs(psel); fence_regs(q[0][0]); fence_regs(q[0][1]);
          sched_fence();
          bar_sync(NB_SC, 256);
          if (row0 == 0) bar_sync(NB_HALO, 64);
          float ra[4], rb[4], ca[4], cb[4];
#pragma unroll
          for (int m = 0; m < 2; m++) {
            float rk[3];
#pragma unroll
            for (int u = 0; u < 3; u++) {
              const int r = row0 + m * 64 + 8 * u + 2 * qd + e - (sel ? 16 : 8);
              rk[u] = lds64f(sb + (m == 0 && r < 0 ? HRS + 128 : ROWST) + r * 8).x;
            }
            ra[2 * m] = sel ? rk[1] : rk[0]; ra[2 * m + 1] = sel ? rk[2] : rk[1];
            rb[2 * m] = sel ? rk[0] : rk[1]; rb[2 * m + 1] = sel ? rk[1] : rk[2];
          }
#pragma unroll
          for (int i = 0; i < 4; i++) { const float rq = st[i >> 1][i & 1].x * QSCALE; ca[i] = rq * ra[i]; cb[i] = rq * rb[i]; }
#pragma unroll 1
          for (int h = 0; h < 2; h++) {
            float s[2][4][4];
            uint32_t vf[2][4][4], pf[2][2][4];
#pragma unroll
            for (int m = 0; m < 2; m++)
#pragma unroll
              for (int nt = 0; nt < 4; nt++) {
                uint32_t kf[4];
                ldsm4(ka + (m * 64 + 8 * nt) * 128, kf);
                s[m][nt][0] = s[m][nt][1] = s[m][nt][2] = s[m][nt][3] = 0.f;
                mma16816(s[m][nt], q[0][m][0], q[0][m][1], q[0][m][2], q[0][m][3], kf[0], kf[1]);
                mma16816(s[m][nt], q[0][m][4], q[0][m][5], q[0][m][6], q[0][m][7], kf[2], kf[3]);
              }
#pragma unroll
            for (int m = 0; m < 2; m++)
#pragma unroll
              for (int i = 0; i < 4; i++) {
                ldsm4t((wa ^ (32 * (i & 1))) + (m * 64 + 16 * (i >> 1)) * 128, vf[m][i]);
              }
            float va[4], vb[4], mx[4];
#pragma unroll
            for (int i = 0; i < 4; i++) {
              const int m = i >> 1, hh = i & 1;
              const float a = e ? s[m][hh + 1][2 * hh + 1] : s[m][hh + 1][2 * hh];
              const float lo = e ? s[m][hh][2 * hh + 1] : s[m][hh][2 * hh], hi = e ? s[m][hh + 2][2 * hh + 1] : s[m][hh + 2][2 * hh];
              va[i] = (m == 0 && hh == 0 && first) ? -INFINITY : a * ca[i];
              vb[i] = (m == 0 && first && sel) ? -INFINITY : (sel ? lo : hi) * cb[i];
              mx[i] = fmaxf(va[i], vb[i]);
            }
#pragma unroll
            for (int i = 0; i < 4; i++) mx[i] = fmaxf(mx[i], __shfl_xor_sync(~0u, mx[i], 1));
#pragma unroll
            for (int i = 0; i < 4; i++) mx[i] = fmaxf(mx[i], __shfl_xor_sync(~0u, mx[i], 2));
#pragma unroll
            for (int i = 0; i < 4; i++) {
              va[i] = ex2(va[i] - mx[i]); vb[i] = ex2(vb[i] - mx[i]);
              mx[i] = va[i] + vb[i];
              va[i] *= ra[i]; vb[i] *= rb[i];
            }
#pragma unroll
            for (int i = 0; i < 4; i++) mx[i] += __shfl_xor_sync(~0u, mx[i], 1);
#pragma unroll
            for (int i = 0; i < 4; i++) mx[i] += __shfl_xor_sync(~0u, mx[i], 2);
#pragma unroll
            for (int i = 0; i < 4; i++) {
              const int m = i >> 1, hh = i & 1;
              const float inv = rcp(mx[i]);
              const uint32_t t = pack2(va[i] * inv, vb[i] * inv);
              pf[m][hh][hh + 1] = prmt0(t, psel[0]); pf[m][hh][hh] = prmt0(t, psel[1]); pf[m][hh][hh + 2] = prmt0(t, psel[2]);
              pf[m][hh][3 - 3 * hh] = t & zero;
            }
#pragma unroll
            for (int m = 0; m < 2; m++) {
              float o[4][4];
#pragma unroll
              for (int j = 0; j < 4; j++) o[j][0] = o[j][1] = o[j][2] = o[j][3] = 0.f;
#pragma unroll
              for (int i = 0; i < 4; i++) {
                const int kk = i >> 1, jj = 2 * (i & 1);
                mma16816(o[jj], pf[m][0][2 * kk], pf[m][1][2 * kk], pf[m][0][2 * kk + 1], pf[m][1][2 * kk + 1], vf[m][i][0], vf[m][i][1]);
                mma16816(o[jj + 1], pf[m][0][2 * kk], pf[m][1][2 * kk], pf[m][0][2 * kk + 1], pf[m][1][2 * kk + 1], vf[m][i][2], vf[m][i][3]);
              }
              stg128(op + m * 65536, pack2(o[0][0], o[0][1]), pack2(o[1][0], o[1][1]), pack2(o[2][0], o[2][1]), pack2(o[3][0], o[3][1]));
              stg128(op + m * 65536 + 8192, pack2(o[0][2], o[0][3]), pack2(o[1][2], o[1][3]), pack2(o[2][2], o[2][3]), pack2(o[3][2], o[3][3]));
            }
            if (h) bar_arrive(NB_DONE, 288);
            bar_arrive(NB_SIG + 2 * h, 288);
            if (h == 0) {
              if (!wg) { lower(1, 3, false); upper(); }
#pragma unroll
              for (int j = 0; j < 4; j++) cs[j] = cn[j];
              cen_tile(1, 0, q[0][0]); cen_tile(1, 1, q[0][1]);
              ka ^= 64; wa ^= 64; op += 512;
              bar_sync(NB_SC, 256);
              if (row0 == 0) bar_sync(NB_HALO + 1, 64);
            }
          }
        } else {
          float qn[2];
          mbar_wait(sb + B_QE + 8, 1);
          drain();
          auto esc_ptr = [&](int gi) { IDS(); return g_esc + (size_t)(((l & 2) + (gi >> 1)) * 65536 + (2 * bn + (gi & 1)) * 2048) * 20; };
          auto norm_half = [&](int gi, float sc, uint32_t (&t)[2][8], uint32_t (&n)[2], int nx) {
#pragma unroll
            for (int m = 0; m < 2; m++) {
              norm_tile(gi, m, sc, t[m], true);
              uint32_t a = hfma2(t[m][0], t[m][0], 0u), c = hfma2(t[m][1], t[m][1], 0u);
#pragma unroll
              for (int j = 1; j < 4; j++) { a = hfma2(t[m][2 * j], t[m][2 * j], a); c = hfma2(t[m][2 * j + 1], t[m][2 * j + 1], c); }
              n[m] = hadd2(__byte_perm(a, c, 0x5410), __byte_perm(a, c, 0x7632));
            }
            float2 cn[4];
#pragma unroll
            for (int j = 0; j < 4; j++) if (nx >= 0) cn[j] = lds64f(sb + COLS + (nx * 32 + j * 8 + 2 * qd) * 4);
            if (((n[0] - 0x01000100u) | (n[0] + 0x04000400u) | (n[1] - 0x01000100u) | (n[1] + 0x04000400u)) & 0x80008000u) {
              uint32_t* p = esc_ptr(gi) + (bm * 256 + row0 + g) * 20 + qd;
#pragma unroll
              for (int m = 0; m < 2; m++) {
                uint32_t u[8];
                norm_tile(gi, m, sc, u);
#pragma unroll
                for (int i = 0; i < 10; i++) p[(m * 64 + (i & 1) * 8) * 20 + (i >> 1) * 4] = i < 8 ? u[i] : ep1;
              }
            }
            __syncwarp();
#pragma unroll
            for (int i = 0; i < 16; i++) asm volatile("{\n.reg .b32 u;\nadd.u32 u, %0, 0x00040004;\nand.b32 %0, u, 0xFFF8FFF8;\n}" : "+r"(t[i >> 3][i & 7]));
#pragma unroll
            for (int j = 0; j < 4; j++) if (nx >= 0) cs[j] = cn[j];
          };
          {
            auto max_norm = [&](const uint32_t (&n)[2]) {
              const bool o1 = qd & 1;
              uint32_t a = hadd2(o1 ? n[1] : n[0], __shfl_xor_sync(~0u, o1 ? n[0] : n[1], 1));
              a = hadd2(a, __shfl_xor_sync(~0u, a, 2));
              float lo, hi;
              asm("{.reg .f16 a, b; mov.b32 {a, b}, %2; cvt.f32.f16 %0, a; cvt.f32.f16 %1, b;}" : "=f"(lo), "=f"(hi) : "r"(a));
              return __uint_as_float(__reduce_max_sync(~0u, max(__float_as_uint(lo), __float_as_uint(hi))));
            };
#pragma unroll
            for (int h = 0; h < 2; h++) {
              uint32_t t[2][8], nrm[2];
              const uint32_t kb = sb + (h ? wg * 8192 : T0), vb = kb + (h ? 8192 : 16384);
              norm_tile(4 + h, 0, 1.f, t[0]); norm_tile(4 + h, 1, 1.f, t[1]);
              load_cs(2 + h);
#pragma unroll
              for (int m = 0; m < 2; m++) {
                const uint32_t r = row0 + m * 64 + g, ad = vb + r * 64 + ((qd ^ ((r >> 1) & 3)) << 4);
                sts128(ad, t[m][0], t[m][2], t[m][4], t[m][6]); sts128(ad + 512, t[m][1], t[m][3], t[m][5], t[m][7]);
              }
              if (h == 0) sched_fence();
              norm_half(2 + h, 1.f, t, nrm, h);
#pragma unroll
              for (int i = 0; i < 4; i++) {
                const uint32_t r = row0 + (i >> 1) * 64 + srow;
                stsm4(kb + r * 64 + (((2 * (i & 1) + (lane >> 4)) ^ ((r >> 1) & 3)) << 4), t[i >> 1][4 * (i & 1)], t[i >> 1][4 * (i & 1) + 1], t[i >> 1][4 * (i & 1) + 2], t[i >> 1][4 * (i & 1) + 3]);
              }
              if (h == 1) { const float kn = max_norm(nrm); if (lane == 0) g_kn[((l >> 1) * 128 + bn * 8 + bm) * 16 + 8 + wg * 4 + w] = kn; }
              fence_async_smem();
              bar_arrive(NB_KV + 12 * h, 288);
              if (h == 0) {
                bar_arrive(wg ? NB_HALO : NB_DONE, 160);
              }
              if (h == 0) { const float kn = max_norm(nrm); if (lane == 0) g_kn[((l >> 1) * 128 + bn * 8 + bm) * 16 + wg * 4 + w] = kn; }
              norm_half(h, QSCALE, q[h], nrm, h ? -1 : 5);
#pragma unroll
              for (int i = 0; i < 4 * h; i++) sts128(sb + QPARK + 24576 - wg * 8192 + (w * 32 + lane) * 16 + i * 2048, q[h][i >> 1][4 * (i & 1)], q[h][i >> 1][4 * (i & 1) + 1], q[h][i >> 1][4 * (i & 1) + 2], q[h][i >> 1][4 * (i & 1) + 3]);
              qn[h] = max_norm(nrm);
            }
          }
          constexpr uint64_t VSTEP = 64 - (64ull << 16);
          uint32_t cq[4];
          const uint32_t &c_852 = cq[0], &c_lsb = cq[1], &c_half = cq[2];
          float o[2][20], S[2][32];
          uint32_t H[2][16], P0[4] = {}, P1[4] = {};
#pragma unroll
          for (int m = 0; m < 2; m++) {
#pragma unroll
            for (int i = 0; i < 20; i++) o[m][i] = 0.f;
            fence_regs(o[m]);
          }
          auto qkf = [&](int b, int ks, uint64_t d) { wg_n64_rs_nb_f16_f32(S[b], q[0][0][4 * ks], q[0][0][4 * ks + 1], q[0][0][4 * ks + 2], q[0][0][4 * ks + 3], d + 2 * ks, ks ? 1 : zero); };
          auto qkh = [&](int b, int ks, uint64_t d) { wg_n64_rs_nb_f16_f16(H[b], q[0][1][4 * ks], q[0][1][4 * ks + 1], q[0][1][4 * ks + 2], q[0][1][4 * ks + 3], d + 2 * ks, ks ? 1 : zero); };
          auto pv0 = [&](uint64_t d) { wgmma_m64n40k16_rs_tb(o[0], P0[0], P0[1], P0[2], P0[3], d, 1); };
          auto pv1 = [&](uint64_t d) { wgmma_m64n40k16_rs_tb(o[1], P1[0], P1[1], P1[2], P1[3], d, 1); };
          float e[4] = {};
          auto finish = [&](int h) {
            const float* s = &S[(h >> 2) & 1][8 * (h & 3)];
            const uint32_t* u = &H[(h >> 2) & 1][4 * (h & 3)];
            const float z0 = exp2_fix(s[6]), z1 = exp2_fix(s[7]);
            P0[0] = pack2v(e[0], e[1]);
            P1[0] = exp2_h2(u[0], c_852);
            P0[1] = pack2v(e[2], e[3]);
            P1[1] = exp2_h2(u[1], c_852);
            const uint32_t B = exp2_base(z0, z1), E = and_or<0x7F807F80u>(B, c_lsb);
            P1[3] = exp2_h2(u[3], c_852);
            P0[3] = fma_bf2(B, and_or<0x807F807Fu>(B, c_half), E);
            const float e4 = ex2v(s[4]), e5 = ex2v(s[5]);
            P1[2] = exp2_h2(u[2], c_852);
            P0[2] = pack2v(e4, e5);
          };
          auto start = [&](int h) {
            const float* s = &S[(h >> 2) & 1][8 * (h & 3)];
            e[2] = ex2v(s[2]); e[1] = ex2v(s[1]); e[0] = ex2v(s[0]); e[3] = ex2v(s[3]);
          };
          uint64_t kd = prm.kv[0].kd;
          mbar_wait(sb + B_TF, 0);
          lds128(sb + ROWST + 16 + (lane_id() & zero), cq);
#pragma unroll
          for (int i = 0; i < 4; i++) sts128(sb + QPARK + (wg * 128 + w * 32 + lane_id()) * 16 + i * 4096, q[0][i >> 1][4 * (i & 1)], q[0][i >> 1][4 * (i & 1) + 1], q[0][i >> 1][4 * (i & 1) + 2], q[0][i >> 1][4 * (i & 1) + 3]);
          wg_fence();
#pragma unroll
          for (int b = 0; b < 2; b++) {
            wg_n64_rs_nb_f16_f32_z(S[b], q[0][0][0], q[0][0][1], q[0][0][2], q[0][0][3], kd + 256 * b, 0);
            wg_n64_rs_nb_f16_f16_z(H[b], q[0][1][0], q[0][1][1], q[0][1][2], q[0][1][3], kd + 256 * b, 0);
            if (b == 0) { qkf(0, 1, kd); qkh(0, 1, kd); }
            wg_commit();
          }
          wg_wait<1>(); fence_regs(S[0]); fence_regs(H[0]);
          start(0); finish(0); start(1);
          wg_wait<0>();
          int redo = 0;
#pragma unroll 1
          for (int pass = 0, j = 1; pass < 2; pass++) {
#pragma unroll 1
           do {
            const uint64_t vd = prm.kv[j & 3].vd;
            bool go = false;
#pragma unroll
            for (int h = 2; h < 18; h++) {
              const int px = (h >> 2) + 1, c = h & 3;
              wg_fence();
              if (h == 13) kd = prm.kv[j & 3].kd;
              const uint64_t kx = kd + (px & 3) * 256, vx = vd + (h - 2) * VSTEP;
              if (h == 2) { qkh(1, 0, kx); qkf(1, 0, kx); pv0(vx); pv1(vx); qkh(1, 1, kx); qkf(1, 1, kx); }
              else if ((c == 1 || c == 2) && h < 17) { qkh(px & 1, c - 1, kx); pv1(vx); qkf(px & 1, c - 1, kx); pv0(vx); }
              else { pv0(vx); pv1(vx); }
              wg_commit();
              if (h == 3) e_arrive_if(sb + B_TE + 8 * ((j + 2) & 3), j > 1);
              if (h == 11) go = mbar_test(sb + B_TF + 8 * (j & 3), (j >> 2) & 1) && j != 8;
              finish(h - 1); start(h);
              if (h != 12 && h != 17) sched_fence();
              if (h == 12 && !go) {
                if (j == 16) {
#pragma unroll
                  for (int u = 13; u < 18; u++) {
                    wg_fence(); pv0(vd + (u - 2) * VSTEP); pv1(vd + (u - 2) * VSTEP); wg_commit();
                    if (u < 17) finish(u - 1);
                    if (u < 16) { start(u); sched_fence(); }
                    if (u & 1) { if (u == 17) wg_wait<0>(); else wg_wait<1>(); }
                  }
                  e_arrive(sb + B_TE + 24);
                  goto head_done;
                }
                mbar_wait(sb + B_TF + 8 * (j & 3), (j >> 2) & 1);
                if (j == 8) {
#pragma unroll
                  for (int i = 0; i < 4; i++) lds128(sb + QPARK + 24576 - wg * 8192 + (w * 32 + lane_id()) * 16 + i * 2048, &q[0][i >> 1][4 * (i & 1)]);
                }
              }
              if (h == 17) wg_wait<0>(); else if (h & 1) wg_wait<1>();
              if (c == 3) { fence_regs(S[px & 1]); fence_regs(H[px & 1]); }
            }
           } while (j++ & 7);
           head_done:
            fence_regs(o[0]); fence_regs(o[1]);
            uint32_t pk[2][8];
            {
              IDS();
              bf16* op = g_os + (size_t)(bm * 256 + row0 + (lane >> 2)) * 1024 + pass * 512 + bn * 32 + (lane & 3) * 8;
#pragma unroll
              for (int i = 0; i < 4; i++) {
                const float* a = &o[i >> 1][2 * (i & 1)];
                const float inv = rcp(a[16]);
                uint32_t* u = &pk[i >> 1][4 * (i & 1)];
#pragma unroll
                for (int k = 0; k < 4; k++) u[k] = pack2(a[4 * k] * inv, a[4 * k + 1] * inv);
                *(uint4*)(op + ((i >> 1) * 64 + (i & 1) * 8) * 1024) = make_uint4(u[0], u[1], u[2], u[3]);
              }
            }
            sched_fence();
            if (pass == 0) bar_sync(NB_KN + wg, 160);
            const float kmax = *(volatile float*)(smem + ROWST + 4 * pass);
            const bool wide = !(qn[0] + kmax <= 1.4e5f) | !(qn[0] * kmax <= 110.f * 110.f);
            int badm = 0;
#pragma unroll
            for (int m = 0; m < 2; m++) {
              uint32_t chk[2] = {0u, 0u};
#pragma unroll
              for (int i = 0; i < 8; i++) asm("fma.rn.bf16x2 %0, %1, %2, %0;" : "+r"(chk[i & 1]) : "r"(pk[m][i]), "r"(0u));
              const bool bad = wide | !(fminf(o[m][16], o[m][18]) >= 9.3e-10f) | !(o[m][16] + o[m][18] <= 1e36f) | (((chk[0] | chk[1]) & 0x7FFF7FFFu) != 0);
              badm |= __any_sync(~0u, bad) << m;
            }
            if (!badm) bar_arrive(NB_SIG + 2 * pass + wg, 160 + 32 * (pass & wg));
            qn[0] = qn[1];
#pragma unroll
            for (int m = 0; m < 2; m++) {
#pragma unroll
              for (int i = 0; i < 20; i++) o[m][i] = 0.f;
              fence_regs(o[m]);
            }
            if (badm) {
              redo |= badm << 2 * pass;
              const int tx = wg * 128 + w * 32 + lane_id();
              uint4* p = g_qsave + (block_id() * 256 + tx) * 8 + pass * 4;
#pragma unroll
              for (int i = 0; i < 4; i++) {
                uint32_t u[4] = {q[0][i >> 1][4 * (i & 1)], q[0][i >> 1][4 * (i & 1) + 1], q[0][i >> 1][4 * (i & 1) + 2], q[0][i >> 1][4 * (i & 1) + 3]};
                if (pass == 0) lds128(sb + QPARK + tx * 16 + i * 4096, u);
                p[i] = make_uint4(u[0], u[1], u[2], u[3]);
              }
            }
          }
          if (redo) attn_redo(redo, l, cta_id(), wg, w, ep1);
        }
      }
      {
        float acc[64];
        {
          const uint64_t da = l & 1 ? prm.xd + ((pslot_a(0, 1) + wg * 8192) >> 4) : prm.kv[0].kd + ((pslot_a(0, 0) - T0 + wg * 4096) >> 4);
          const uint64_t d2 = da + (l & 1 ? 4 : 512), db = prm.wd + (pslot_b(0) >> 4) - 2048;
          mbar_wait(sb + B_PF, l & 1);
          wg_fence();
          wgmma_m64n128k16_ss_tb_z(acc, da, db, 0);
#pragma unroll
          for (int k = 1; k < 4; k++) wgmma_m64n128k16_ss_tb(acc, (k & 2 ? d2 : da) + (k & 1) * 2, db + k * 128, 1);
          wg_commit();
        }
        uint32_t s = 1, lap = 0;
#pragma unroll 1
        for (int kt = 1; kt < 14; kt++) {
          mbar_wait(sb + B_PF + 8 * s, ((s < 4 ? l : 0) + lap) & 1);
          const uint64_t da = mkdesc(sb + pslot_a(s, l) + wg * 8192, 16, 1024, 1), db = mkdesc(sb + pslot_b(s), 8192, 1024, 1);
          wg_fence();
#pragma unroll
          for (int k = 0; k < 4; k++) wgmma_m64n128k16_ss_tb(acc, da + k * 2, db + k * 128, 1);
          wg_commit();
          wg_wait<1>();
          if (w == 0) e_arrive_both(sb + B_PE + 8 * (s ? s - 1 : 5));
          if (++s == 6) { s = 0; lap++; }
        }
        if (wg) {
          wg_wait<0>();
          if (w == 0) e_arrive_both(sb + B_PE + 8);
#pragma unroll
          for (int t = 2; t < 4; t++) mbar_wait(sb + B_PF + 8 * t, l & 1);
          bar_sync(NB_ST, 256);
        }
#pragma unroll
        for (int t = 2; t < 4; t++) {
          if (!wg) mbar_wait(sb + B_PF + 8 * t, l & 1);
          const uint64_t da = prm.xd + ((pslot_a(t, l) + wg * 8192) >> 4), db = prm.wd + (pslot_b(t) >> 4) - 2048;
          wg_fence();
#pragma unroll
          for (int k = 0; k < 4; k++) wgmma_m64n128k16_ss_tb(acc, da + k * 2, db + k * 128, 1);
          wg_commit();
        }
        if (!wg) {
          bar_arrive(NB_ST, 256);
          wg_wait<2>();
          if (w == 0) e_arrive_both(sb + B_PE + 8);
        }
        IDS();
        const int g = lane >> 2, qd = lane & 3;
        const int r0 = wg * 64 + w * 16;
        const uint32_t r = r0 + (lane & 7) + ((lane >> 3) & 1) * 8;
        uint32_t x[8][4];
        mbar_wait(sb + B_RF, 0);
#pragma unroll
        for (int jj = 0; jj < 8; jj++) ldsm4(sb + RES + (jj >> 2) * 16384 + r * 128 + ((((2 * jj + (lane >> 4)) & 7) ^ (r & 7)) << 4), x[jj]);
        wg_wait<0>();
        fence_regs(acc);
        if (w == 0) { e_arrive_both(sb + B_PE + 16); e_arrive_both(sb + B_PE + 24); }
        const CUtensorMap* mo = &prm.m[l == 3 ? M_OUT : M_XST];
        const bool direct = wg && l < 3;
        const uint32_t stg = sb + (direct ? po * 16384 : RES);
        if (direct) bar_sync(NB_SC, 256);
#pragma unroll
        for (int jj = 0; jj < 8; jj++) {
#pragma unroll
          for (int i = 0; i < 4; i++) x[jj][i] = add_bf16x2(x[jj][i], pack2(acc[8 * jj + 2 * i], acc[8 * jj + 2 * i + 1]));
          if (jj < 4) stsm4(stg + r * 128 + ((((2 * jj + (lane >> 4)) & 7) ^ (r & 7)) << 4), x[jj][0], x[jj][1], x[jj][2], x[jj][3]);
          if (jj == 3) { fence_async_smem(); __syncwarp(); tma_st(mo, pn * 128, pm * 128 + r0, stg + r0 * 128); bulk_commit(); sched_fence(); }
        }
        if (l < 3) bar_arrive(NB_KN, 288);
        if (l == 3) {
#pragma unroll
          for (int jj = 4; jj < 8; jj++) stsm4(sb + RES + 16384 + r * 128 + ((((2 * jj + (lane >> 4)) & 7) ^ (r & 7)) << 4), x[jj][0], x[jj][1], x[jj][2], x[jj][3]);
          fence_async_smem(); __syncwarp();
          tma_st(mo, pn * 128 + 64, pm * 128 + r0, sb + RES + 16384 + r0 * 128);
          bulk_commit(); bulk_wait_n<0>();
        } else {
          if (!wg) bar_sync(NB_SC, 256);
#pragma unroll
          for (int jj = 0; jj < 8; jj++)
            if (jj >= 4 || !wg) stsm4(sb + (jj >> 2) * 2 * QSTG + po * 16384 + r * 128 + ((((2 * jj + (lane >> 4)) & 7) ^ (r & 7)) << 4), x[jj][0], x[jj][1], x[jj][2], x[jj][3]);
          bulk_wait_n<0>();
          bar_arrive(NB_X0, 320);
          float s1[4] = {0.f, 0.f, 0.f, 0.f}, sa[4] = {0.f, 0.f, 0.f, 0.f}, sc[4] = {0.f, 0.f, 0.f, 0.f};
#pragma unroll
          for (int jj = 0; jj < 8; jj++) {
            mma16816(s1, x[jj][0], x[jj][1], x[jj][2], x[jj][3], 0x3f803f80u, 0x3f803f80u);
            mma16816(sa, x[jj][0], x[jj][1], x[jj][2], x[jj][3], x[jj][0], x[jj][2]);
            mma16816(sc, x[jj][0], x[jj][1], x[jj][2], x[jj][3], x[jj][1], x[jj][3]);
          }
          fence_regs(s1); fence_regs(sa); fence_regs(sc);
          fence_async_smem();
          sched_fence();
          bar_arrive(NB_X, 320);
          if (qd == g >> 1) {
            float2* p = g_stats + pn * 2048 + pm * 128 + r0 + g;
            p[0] = make_float2(s1[0], g & 1 ? sa[1] : sa[0]);
            p[8] = make_float2(s1[2], g & 1 ? sc[3] : sc[2]);
          }
          bar_arrive(NB_KV, 288);
        }
      }
    }
  }
  asm volatile("barrier.cluster.arrive.relaxed.aligned;\nbarrier.cluster.wait.aligned;" ::: "memory");
}

typedef CUresult (*EncodeFn)(CUtensorMap*, CUtensorMapDataType, cuuint32_t, void*, const cuuint64_t*, const cuuint64_t*, const cuuint32_t*,
                             const cuuint32_t*, CUtensorMapInterleave, CUtensorMapSwizzle, CUtensorMapL2promotion, CUtensorMapFloatOOBfill);

static void make_map(EncodeFn fn, CUtensorMap* m, const void* ptr, int rank, const uint64_t* dims, const uint64_t* strides, const uint32_t* box, CUtensorMapSwizzle sw) {
  cuuint64_t d[5], st[4];
  cuuint32_t bx[5], es[5];
  for (int i = 0; i < rank; i++) { d[i] = dims[i]; bx[i] = box[i]; es[i] = 1; if (i) st[i - 1] = strides[i - 1] * 2; }
  fn(m, CU_TENSOR_MAP_DATA_TYPE_BFLOAT16, rank, (void*)ptr, d, st, bx, es, CU_TENSOR_MAP_INTERLEAVE_NONE, sw,
     CU_TENSOR_MAP_L2_PROMOTION_L2_128B, CU_TENSOR_MAP_FLOAT_OOB_FILL_NONE);
}
static void map2(EncodeFn fn, CUtensorMap* m, const void* ptr, uint64_t inner, uint64_t outer, uint32_t bi, uint32_t bo, CUtensorMapSwizzle sw) {
  const uint64_t d[2] = {inner, outer}, st[1] = {inner};
  const uint32_t bx[2] = {bi, bo};
  make_map(fn, m, ptr, 2, d, st, bx, sw);
}

extern "C" void kernel_launch(void* const* d_in, const int* in_sizes, int n_in, void* d_out, int out_size) {
  (void)in_sizes; (void)n_in; (void)out_size;
  static EncodeFn enc = nullptr;
  static void *xs, *os, *kk, *vv;
  static int sbase = 1024;
  if (!enc) {
    void* p = nullptr;
    cudaDriverEntryPointQueryResult qr;
    cudaGetDriverEntryPoint("cuTensorMapEncodeTiled", &p, cudaEnableDefault, &qr);
    enc = (EncodeFn)p;
    Scratch* sc = nullptr;
    cudaGetSymbolAddress((void**)&sc, g_s);
    xs = sc->xs; os = sc->os; kk = sc->k; vv = sc->v;
    int dev = 0;
    cudaGetDevice(&dev);
    cudaDeviceGetAttribute(&sbase, cudaDevAttrReservedSharedMemoryPerBlock, dev);
    cudaFuncSetAttribute(fused_kernel, cudaFuncAttributeMaxDynamicSharedMemorySize, SMEM_BYTES);
  }
  Params prm;
  const CUtensorMapSwizzle S128 = CU_TENSOR_MAP_SWIZZLE_128B, S64 = CU_TENSOR_MAP_SWIZZLE_64B;
  map2(enc, &prm.m[M_X0A], d_in[0], 1024, 2048, 64, 256, S128);
  for (int t = 0; t < 2; t++) {
    const uint64_t d3[3] = {1024, 1024, 3}, s3[2] = {3072, 1024};
    const uint32_t b3[3] = {64, 64, 3};
    make_map(enc, &prm.m[M_WQA + t], d_in[1 + 3 * t], 3, d3, s3, b3, S128);
    const uint64_t d5[5] = {64, 32, 2, 16, 16}, s5[4] = {1024, 32 * 1024, 64 * 1024, 64};
    const uint32_t b5[5] = {64, 32, 1, 2, 2};
    make_map(enc, &prm.m[M_WOA + t], d_in[2 + 3 * t], 5, d5, s5, b5, S128);
    const uint64_t dr[3] = {64, 2048, 16}, sr[2] = {1024, 64};
    const uint32_t br[3] = {64, 128, 2};
    make_map(enc, &prm.m[M_X0R + t], t ? xs : d_in[0], 3, dr, sr, br, S128);
  }
  map2(enc, &prm.m[M_OS], os, 1024, 2048, 64, 64, S128);
  map2(enc, &prm.m[M_OL], os, 1024, 2048, 32, 128, S64);
  map2(enc, &prm.m[M_K], kk, 32, 65536, 32, 128, S64);
  map2(enc, &prm.m[M_V], vv, 32, 65536, 32, 128, S64);
  map2(enc, &prm.m[M_XSO], xs, 1024, 2048, 64, 128, S128);
  map2(enc, &prm.m[M_X0H], d_in[0], 1024, 2048, 64, 128, S128);
  map2(enc, &prm.m[M_XST], xs, 1024, 2048, 64, 16, S128);
  map2(enc, &prm.m[M_OUT], d_out, 1024, 2048, 64, 16, S128);
  prm.x0 = (const bf16*)d_in[0];
  prm.wq[0] = (const bf16*)d_in[1]; prm.wq[1] = (const bf16*)d_in[4];
  prm.wo = (const bf16*)d_in[2];
  prm.zero = 0;
  for (int i = 0; i < 128; i++) prm.map[i] = remap(i);
  {
    const uint64_t hi = 0x80000020ull << 32, k0 = sbase + T0, v0 = k0 + 16384, vstep = 64 - (64ull << 16);
    prm.wd = mkdesc(sbase + 32768, 8192, 1024, 1); prm.xd = mkdesc(sbase, 16, 1024, 1);
    for (int j = 0; j < 4; j++) {
      prm.kv[j].kd = (hi | 1u << 16 | k0 >> 4) + 2048 * ((j < 16 ? j : 15) & 3);
      prm.kv[j].vd = (hi | (uint64_t)(ONES - T0 - 16384) >> 4 << 16 | v0 >> 4) + 32 * vstep * ((j + 3) & 3);
    }
  }
  fused_kernel<<<128, 384, SMEM_BYTES>>>(prm);
}
```

```cpp
#include <cuda_runtime.h>
#include <cuda_bf16.h>
#include <cuda.h>
#include <stdint.h>

typedef __nv_bfloat16 bf16;

__device__ __forceinline__ void wgmma_m64n192k16_ss_tb(float (&d)[96], uint64_t da, uint64_t db, int scale_d) {
  asm volatile("{\n.reg .pred p;\nsetp.ne.b32 p, %98, 0;\n"
    "wgmma.mma_async.sync.aligned.m64n192k16.f32.bf16.bf16 "
    "{%0, %1, %2, %3, %4, %5, %6, %7, %8, %9, %10, %11, %12, %13, %14, %15, "
    "%16, %17, %18, %19, %20, %21, %22, %23, %24, %25, %26, %27, %28, %29, %30, %31, "
    "%32, %33, %34, %35, %36, %37, %38, %39, %40, %41, %42, %43, %44, %45, %46, %47, "
    "%48, %49, %50, %51, %52, %53, %54, %55, %56, %57, %58, %59, %60, %61, %62, %63, "
    "%64, %65, %66, %67, %68, %69, %70, %71, %72, %73, %74, %75, %76, %77, %78, %79, "
    "%80, %81, %82, %83, %84, %85, %86, %87, %88, %89, %90, %91, %92, %93, %94, %95}, "
    "%96, %97, p, 1, 1, 0, 1;\n}\n"
    : "+f"(d[0]), "+f"(d[1]), "+f"(d[2]), "+f"(d[3]), "+f"(d[4]), "+f"(d[5]), "+f"(d[6]), "+f"(d[7]),
      "+f"(d[8]), "+f"(d[9]), "+f"(d[10]), "+f"(d[11]), "+f"(d[12]), "+f"(d[13]), "+f"(d[14]), "+f"(d[15]),
      "+f"(d[16]), "+f"(d[17]), "+f"(d[18]), "+f"(d[19]), "+f"(d[20]), "+f"(d[21]), "+f"(d[22]), "+f"(d[23]),
      "+f"(d[24]), "+f"(d[25]), "+f"(d[26]), "+f"(d[27]), "+f"(d[28]), "+f"(d[29]), "+f"(d[30]), "+f"(d[31]),
      "+f"(d[32]), "+f"(d[33]), "+f"(d[34]), "+f"(d[35]), "+f"(d[36]), "+f"(d[37]), "+f"(d[38]), "+f"(d[39]),
      "+f"(d[40]), "+f"(d[41]), "+f"(d[42]), "+f"(d[43]), "+f"(d[44]), "+f"(d[45]), "+f"(d[46]), "+f"(d[47]),
      "+f"(d[48]), "+f"(d[49]), "+f"(d[50]), "+f"(d[51]), "+f"(d[52]), "+f"(d[53]), "+f"(d[54]), "+f"(d[55]),
      "+f"(d[56]), "+f"(d[57]), "+f"(d[58]), "+f"(d[59]), "+f"(d[60]), "+f"(d[61]), "+f"(d[62]), "+f"(d[63]),
      "+f"(d[64]), "+f"(d[65]), "+f"(d[66]), "+f"(d[67]), "+f"(d[68]), "+f"(d[69]), "+f"(d[70]), "+f"(d[71]),
      "+f"(d[72]), "+f"(d[73]), "+f"(d[74]), "+f"(d[75]), "+f"(d[76]), "+f"(d[77]), "+f"(d[78]), "+f"(d[79]),
      "+f"(d[80]), "+f"(d[81]), "+f"(d[82]), "+f"(d[83]), "+f"(d[84]), "+f"(d[85]), "+f"(d[86]), "+f"(d[87]),
      "+f"(d[88]), "+f"(d[89]), "+f"(d[90]), "+f"(d[91]), "+f"(d[92]), "+f"(d[93]), "+f"(d[94]), "+f"(d[95])
    : "l"(da), "l"(db), "r"(scale_d));
}

__device__ __forceinline__ void wgmma_m64n192k16_ss_tb_z(float (&d)[96], uint64_t da, uint64_t db, int scale_d) {
  asm volatile("{\n.reg .pred p;\nsetp.ne.b32 p, %98, 0;\n"
    "wgmma.mma_async.sync.aligned.m64n192k16.f32.bf16.bf16 "
    "{%0, %1, %2, %3, %4, %5, %6, %7, %8, %9, %10, %11, %12, %13, %14, %15, "
    "%16, %17, %18, %19, %20, %21, %22, %23, %24, %25, %26, %27, %28, %29, %30, %31, "
    "%32, %33, %34, %35, %36, %37, %38, %39, %40, %41, %42, %43, %44, %45, %46, %47, "
    "%48, %49, %50, %51, %52, %53, %54, %55, %56, %57, %58, %59, %60, %61, %62, %63, "
    "%64, %65, %66, %67, %68, %69, %70, %71, %72, %73, %74, %75, %76, %77, %78, %79, "
    "%80, %81, %82, %83, %84, %85, %86, %87, %88, %89, %90, %91, %92, %93, %94, %95}, "
    "%96, %97, p, 1, 1, 0, 1;\n}\n"
    : "=f"(d[0]), "=f"(d[1]), "=f"(d[2]), "=f"(d[3]), "=f"(d[4]), "=f"(d[5]), "=f"(d[6]), "=f"(d[7]),
      "=f"(d[8]), "=f"(d[9]), "=f"(d[10]), "=f"(d[11]), "=f"(d[12]), "=f"(d[13]), "=f"(d[14]), "=f"(d[15]),
      "=f"(d[16]), "=f"(d[17]), "=f"(d[18]), "=f"(d[19]), "=f"(d[20]), "=f"(d[21]), "=f"(d[22]), "=f"(d[23]),
      "=f"(d[24]), "=f"(d[25]), "=f"(d[26]), "=f"(d[27]), "=f"(d[28]), "=f"(d[29]), "=f"(d[30]), "=f"(d[31]),
      "=f"(d[32]), "=f"(d[33]), "=f"(d[34]), "=f"(d[35]), "=f"(d[36]), "=f"(d[37]), "=f"(d[38]), "=f"(d[39]),
      "=f"(d[40]), "=f"(d[41]), "=f"(d[42]), "=f"(d[43]), "=f"(d[44]), "=f"(d[45]), "=f"(d[46]), "=f"(d[47]),
      "=f"(d[48]), "=f"(d[49]), "=f"(d[50]), "=f"(d[51]), "=f"(d[52]), "=f"(d[53]), "=f"(d[54]), "=f"(d[55]),
      "=f"(d[56]), "=f"(d[57]), "=f"(d[58]), "=f"(d[59]), "=f"(d[60]), "=f"(d[61]), "=f"(d[62]), "=f"(d[63]),
      "=f"(d[64]), "=f"(d[65]), "=f"(d[66]), "=f"(d[67]), "=f"(d[68]), "=f"(d[69]), "=f"(d[70]), "=f"(d[71]),
      "=f"(d[72]), "=f"(d[73]), "=f"(d[74]), "=f"(d[75]), "=f"(d[76]), "=f"(d[77]), "=f"(d[78]), "=f"(d[79]),
      "=f"(d[80]), "=f"(d[81]), "=f"(d[82]), "=f"(d[83]), "=f"(d[84]), "=f"(d[85]), "=f"(d[86]), "=f"(d[87]),
      "=f"(d[88]), "=f"(d[89]), "=f"(d[90]), "=f"(d[91]), "=f"(d[92]), "=f"(d[93]), "=f"(d[94]), "=f"(d[95])
    : "l"(da), "l"(db), "r"(scale_d));
}

__device__ __forceinline__ void wgmma_m64n128k16_ss_tb(float (&d)[64], uint64_t da, uint64_t db, int scale_d) {
  asm volatile("{\n.reg .pred p;\nsetp.ne.b32 p, %66, 0;\n"
    "wgmma.mma_async.sync.aligned.m64n128k16.f32.bf16.bf16 "
    "{%0, %1, %2, %3, %4, %5, %6, %7, %8, %9, %10, %11, %12, %13, %14, %15, "
    "%16, %17, %18, %19, %20, %21, %22, %23, %24, %25, %26, %27, %28, %29, %30, %31, "
    "%32, %33, %34, %35, %36, %37, %38, %39, %40, %41, %42, %43, %44, %45, %46, %47, "
    "%48, %49, %50, %51, %52, %53, %54, %55, %56, %57, %58, %59, %60, %61, %62, %63}, "
    "%64, %65, p, 1, 1, 0, 1;\n}\n"
    : "+f"(d[0]), "+f"(d[1]), "+f"(d[2]), "+f"(d[3]), "+f"(d[4]), "+f"(d[5]), "+f"(d[6]), "+f"(d[7]),
      "+f"(d[8]), "+f"(d[9]), "+f"(d[10]), "+f"(d[11]), "+f"(d[12]), "+f"(d[13]), "+f"(d[14]), "+f"(d[15]),
      "+f"(d[16]), "+f"(d[17]), "+f"(d[18]), "+f"(d[19]), "+f"(d[20]), "+f"(d[21]), "+f"(d[22]), "+f"(d[23]),
      "+f"(d[24]), "+f"(d[25]), "+f"(d[26]), "+f"(d[27]), "+f"(d[28]), "+f"(d[29]), "+f"(d[30]), "+f"(d[31]),
      "+f"(d[32]), "+f"(d[33]), "+f"(d[34]), "+f"(d[35]), "+f"(d[36]), "+f"(d[37]), "+f"(d[38]), "+f"(d[39]),
      "+f"(d[40]), "+f"(d[41]), "+f"(d[42]), "+f"(d[43]), "+f"(d[44]), "+f"(d[45]), "+f"(d[46]), "+f"(d[47]),
      "+f"(d[48]), "+f"(d[49]), "+f"(d[50]), "+f"(d[51]), "+f"(d[52]), "+f"(d[53]), "+f"(d[54]), "+f"(d[55]),
      "+f"(d[56]), "+f"(d[57]), "+f"(d[58]), "+f"(d[59]), "+f"(d[60]), "+f"(d[61]), "+f"(d[62]), "+f"(d[63])
    : "l"(da), "l"(db), "r"(scale_d));
}

__device__ __forceinline__ void wgmma_m64n128k16_ss_tb_z(float (&d)[64], uint64_t da, uint64_t db, int scale_d) {
  asm volatile("{\n.reg .pred p;\nsetp.ne.b32 p, %66, 0;\n"
    "wgmma.mma_async.sync.aligned.m64n128k16.f32.bf16.bf16 "
    "{%0, %1, %2, %3, %4, %5, %6, %7, %8, %9, %10, %11, %12, %13, %14, %15, "
    "%16, %17, %18, %19, %20, %21, %22, %23, %24, %25, %26, %27, %28, %29, %30, %31, "
    "%32, %33, %34, %35, %36, %37, %38, %39, %40, %41, %42, %43, %44, %45, %46, %47, "
    "%48, %49, %50, %51, %52, %53, %54, %55, %56, %57, %58, %59, %60, %61, %62, %63}, "
    "%64, %65, p, 1, 1, 0, 1;\n}\n"
    : "=f"(d[0]), "=f"(d[1]), "=f"(d[2]), "=f"(d[3]), "=f"(d[4]), "=f"(d[5]), "=f"(d[6]), "=f"(d[7]),
      "=f"(d[8]), "=f"(d[9]), "=f"(d[10]), "=f"(d[11]), "=f"(d[12]), "=f"(d[13]), "=f"(d[14]), "=f"(d[15]),
      "=f"(d[16]), "=f"(d[17]), "=f"(d[18]), "=f"(d[19]), "=f"(d[20]), "=f"(d[21]), "=f"(d[22]), "=f"(d[23]),
      "=f"(d[24]), "=f"(d[25]), "=f"(d[26]), "=f"(d[27]), "=f"(d[28]), "=f"(d[29]), "=f"(d[30]), "=f"(d[31]),
      "=f"(d[32]), "=f"(d[33]), "=f"(d[34]), "=f"(d[35]), "=f"(d[36]), "=f"(d[37]), "=f"(d[38]), "=f"(d[39]),
      "=f"(d[40]), "=f"(d[41]), "=f"(d[42]), "=f"(d[43]), "=f"(d[44]), "=f"(d[45]), "=f"(d[46]), "=f"(d[47]),
      "=f"(d[48]), "=f"(d[49]), "=f"(d[50]), "=f"(d[51]), "=f"(d[52]), "=f"(d[53]), "=f"(d[54]), "=f"(d[55]),
      "=f"(d[56]), "=f"(d[57]), "=f"(d[58]), "=f"(d[59]), "=f"(d[60]), "=f"(d[61]), "=f"(d[62]), "=f"(d[63])
    : "l"(da), "l"(db), "r"(scale_d));
}

__device__ __forceinline__ void wgmma_m64n40k16_rs_tb(float (&d)[20], uint32_t a0, uint32_t a1, uint32_t a2, uint32_t a3, uint64_t db, int scale_d) {
  asm volatile("{\n.reg .pred p;\nsetp.ne.b32 p, %25, 0;\n"
    "wgmma.mma_async.sync.aligned.m64n40k16.f32.bf16.bf16 "
    "{%0, %1, %2, %3, %4, %5, %6, %7, %8, %9, %10, %11, %12, %13, %14, %15, "
    "%16, %17, %18, %19}, "
    "{%20, %21, %22, %23}, %24, p, 1, 1, 1;\n}\n"
    : "+f"(d[0]), "+f"(d[1]), "+f"(d[2]), "+f"(d[3]), "+f"(d[4]), "+f"(d[5]), "+f"(d[6]), "+f"(d[7]),
      "+f"(d[8]), "+f"(d[9]), "+f"(d[10]), "+f"(d[11]), "+f"(d[12]), "+f"(d[13]), "+f"(d[14]), "+f"(d[15]),
      "+f"(d[16]), "+f"(d[17]), "+f"(d[18]), "+f"(d[19])
    : "r"(a0), "r"(a1), "r"(a2), "r"(a3), "l"(db), "r"(scale_d));
}

__device__ __forceinline__ void wg_n64_rs_nb_f16_f32(float (&d)[32], uint32_t a0, uint32_t a1, uint32_t a2, uint32_t a3, uint64_t db, int scale_d) {
  asm volatile("{\n.reg .pred p;\nsetp.ne.b32 p, %37, 0;\n"
    "wgmma.mma_async.sync.aligned.m64n64k16.f32.f16.f16 "
    "{%0, %1, %2, %3, %4, %5, %6, %7, %8, %9, %10, %11, %12, %13, %14, %15, "
    "%16, %17, %18, %19, %20, %21, %22, %23, %24, %25, %26, %27, %28, %29, %30, %31}, "
    "{%32, %33, %34, %35}, %36, p, 1, 1, 0;\n}\n"
    : "+f"(d[0]), "+f"(d[1]), "+f"(d[2]), "+f"(d[3]), "+f"(d[4]), "+f"(d[5]), "+f"(d[6]), "+f"(d[7]),
      "+f"(d[8]), "+f"(d[9]), "+f"(d[10]), "+f"(d[11]), "+f"(d[12]), "+f"(d[13]), "+f"(d[14]), "+f"(d[15]),
      "+f"(d[16]), "+f"(d[17]), "+f"(d[18]), "+f"(d[19]), "+f"(d[20]), "+f"(d[21]), "+f"(d[22]), "+f"(d[23]),
      "+f"(d[24]), "+f"(d[25]), "+f"(d[26]), "+f"(d[27]), "+f"(d[28]), "+f"(d[29]), "+f"(d[30]), "+f"(d[31])
    : "r"(a0), "r"(a1), "r"(a2), "r"(a3), "l"(db), "r"(scale_d));
}

__device__ __forceinline__ void wg_n64_rs_nb_f16_f16(uint32_t (&d)[16], uint32_t a0, uint32_t a1, uint32_t a2, uint32_t a3, uint64_t db, int scale_d) {
  asm volatile("{\n.reg .pred p;\nsetp.ne.b32 p, %21, 0;\n"
    "wgmma.mma_async.sync.aligned.m64n64k16.f16.f16.f16 "
    "{%0, %1, %2, %3, %4, %5, %6, %7, %8, %9, %10, %11, %12, %13, %14, %15}, "
    "{%16, %17, %18, %19}, %20, p, 1, 1, 0;\n}\n"
    : "+r"(d[0]), "+r"(d[1]), "+r"(d[2]), "+r"(d[3]), "+r"(d[4]), "+r"(d[5]), "+r"(d[6]), "+r"(d[7]),
      "+r"(d[8]), "+r"(d[9]), "+r"(d[10]), "+r"(d[11]), "+r"(d[12]), "+r"(d[13]), "+r"(d[14]), "+r"(d[15])
    : "r"(a0), "r"(a1), "r"(a2), "r"(a3), "l"(db), "r"(scale_d));
}

__device__ __forceinline__ void wg_n64_rs_nb_f16_f32_z(float (&d)[32], uint32_t a0, uint32_t a1, uint32_t a2, uint32_t a3, uint64_t db, int scale_d) {
  asm volatile("{\n.reg .pred p;\nsetp.ne.b32 p, %37, 0;\n"
    "wgmma.mma_async.sync.aligned.m64n64k16.f32.f16.f16 "
    "{%0, %1, %2, %3, %4, %5, %6, %7, %8, %9, %10, %11, %12, %13, %14, %15, "
    "%16, %17, %18, %19, %20, %21, %22, %23, %24, %25, %26, %27, %28, %29, %30, %31}, "
    "{%32, %33, %34, %35}, %36, p, 1, 1, 0;\n}\n"
    : "=f"(d[0]), "=f"(d[1]), "=f"(d[2]), "=f"(d[3]), "=f"(d[4]), "=f"(d[5]), "=f"(d[6]), "=f"(d[7]),
      "=f"(d[8]), "=f"(d[9]), "=f"(d[10]), "=f"(d[11]), "=f"(d[12]), "=f"(d[13]), "=f"(d[14]), "=f"(d[15]),
      "=f"(d[16]), "=f"(d[17]), "=f"(d[18]), "=f"(d[19]), "=f"(d[20]), "=f"(d[21]), "=f"(d[22]), "=f"(d[23]),
      "=f"(d[24]), "=f"(d[25]), "=f"(d[26]), "=f"(d[27]), "=f"(d[28]), "=f"(d[29]), "=f"(d[30]), "=f"(d[31])
    : "r"(a0), "r"(a1), "r"(a2), "r"(a3), "l"(db), "r"(scale_d));
}

__device__ __forceinline__ void wg_n64_rs_nb_f16_f16_z(uint32_t (&d)[16], uint32_t a0, uint32_t a1, uint32_t a2, uint32_t a3, uint64_t db, int scale_d) {
  asm volatile("{\n.reg .pred p;\nsetp.ne.b32 p, %21, 0;\n"
    "wgmma.mma_async.sync.aligned.m64n64k16.f16.f16.f16 "
    "{%0, %1, %2, %3, %4, %5, %6, %7, %8, %9, %10, %11, %12, %13, %14, %15}, "
    "{%16, %17, %18, %19}, %20, p, 1, 1, 0;\n}\n"
    : "=r"(d[0]), "=r"(d[1]), "=r"(d[2]), "=r"(d[3]), "=r"(d[4]), "=r"(d[5]), "=r"(d[6]), "=r"(d[7]),
      "=r"(d[8]), "=r"(d[9]), "=r"(d[10]), "=r"(d[11]), "=r"(d[12]), "=r"(d[13]), "=r"(d[14]), "=r"(d[15])
    : "r"(a0), "r"(a1), "r"(a2), "r"(a3), "l"(db), "r"(scale_d));
}

#define DEVINL __device__ __forceinline__
DEVINL void wg_fence() { asm volatile("wgmma.fence.sync.aligned;" ::: "memory"); }
DEVINL void wg_commit() { asm volatile("wgmma.commit_group.sync.aligned;" ::: "memory"); }
template <int N> DEVINL void wg_wait() { asm volatile("wgmma.wait_group.sync.aligned %0;" ::"n"(N) : "memory"); }
__host__ DEVINL uint64_t mkdesc(uint32_t addr, uint32_t lbo, uint32_t sbo, int sw) {
  return (uint64_t)((addr & 0x3FFFF) >> 4) | ((uint64_t)(lbo >> 4) << 16) | ((uint64_t)(sbo >> 4) << 32) | ((uint64_t)sw << 62);
}
DEVINL bool mbar_try(uint32_t bar, uint32_t parity) {
  uint32_t ok;
  asm volatile("{\n.reg .pred p;\nmbarrier.try_wait.parity.shared::cta.b64 p, [%1], %2;\nselp.u32 %0, 1, 0, p;\n}" : "=r"(ok) : "r"(bar), "r"(parity) : "memory");
  return ok;
}
DEVINL bool mbar_test(uint32_t bar, uint32_t parity) {
  uint32_t ok;
  asm volatile("{\n.reg .pred p;\nmbarrier.test_wait.parity.shared::cta.b64 p, [%1], %2;\nselp.u32 %0, 1, 0, p;\n}" : "=r"(ok) : "r"(bar), "r"(parity) : "memory");
  return ok;
}
DEVINL void mbar_wait(uint32_t bar, uint32_t parity) {
#pragma unroll 1
  for (uint32_t n = 0; n < 100000u; n++) if (mbar_try(bar, parity)) break;
}
#define EL(txt) "{\n.reg .pred pe;\nelect.sync _|pe, 0xffffffff;\n@pe " txt "\n}"
DEVINL void e_expect_tx(uint32_t bar, uint32_t bytes) { asm volatile(EL("mbarrier.arrive.expect_tx.shared::cta.b64 _, [%0], %1;") ::"r"(bar), "r"(bytes) : "memory"); }
DEVINL void e_arrive(uint32_t bar) { asm volatile(EL("mbarrier.arrive.shared::cta.b64 _, [%0];") ::"r"(bar) : "memory"); }
DEVINL void e_arrive_if(uint32_t bar, int c) {
  asm volatile("{\n.reg .pred pe;\nelect.sync _|pe, 0xffffffff;\nsetp.ne.and.b32 pe, %1, 0, pe;\n@pe mbarrier.arrive.shared::cta.b64 _, [%0];\n}" ::"r"(bar), "r"(c) : "memory");
}
DEVINL void e_red(uint32_t* p) { asm volatile(EL("red.release.gpu.global.add.u32 [%0], 1;") ::"l"(p) : "memory"); }
DEVINL void e_red_relaxed(uint32_t* p) { asm volatile(EL("red.relaxed.gpu.global.add.u32 [%0], 1;") ::"l"(p) : "memory"); }
DEVINL void release_add(uint32_t* p, int on) {
  asm volatile("{\n.reg .pred q;\nsetp.ne.b32 q, %1, 0;\nfence.release.gpu;\n@q red.relaxed.gpu.global.add.u32 [%0], 1;\n}" ::"l"(p), "r"(on) : "memory");
}
#define PREPARED(p, on) do { asm volatile("" : "+l"(p), "+r"(on)); asm volatile("griddepcontrol.launch_dependents;" ::: "memory"); } while (0)
DEVINL void tma_ld(uint32_t dst, const CUtensorMap* m, int c0, int c1, uint32_t bar) {
  asm volatile(EL("cp.async.bulk.tensor.2d.shared::cluster.global.mbarrier::complete_tx::bytes [%0], [%1, {%3, %4}], [%2];")
               ::"r"(dst), "l"(m), "r"(bar), "r"(c0), "r"(c1) : "memory");
}
DEVINL void tma_ld3(uint32_t dst, const CUtensorMap* m, int c0, int c1, int c2, uint32_t bar) {
  asm volatile(EL("cp.async.bulk.tensor.3d.shared::cluster.global.mbarrier::complete_tx::bytes [%0], [%1, {%3, %4, %5}], [%2];")
               ::"r"(dst), "l"(m), "r"(bar), "r"(c0), "r"(c1), "r"(c2) : "memory");
}
DEVINL void tma_ld5(uint32_t dst, const CUtensorMap* m, int c2, int c3, int c4, uint32_t bar) {
  asm volatile(EL("cp.async.bulk.tensor.5d.shared::cluster.global.mbarrier::complete_tx::bytes [%0], [%1, {0, 0, %3, %4, %5}], [%2];")
               ::"r"(dst), "l"(m), "r"(bar), "r"(c2), "r"(c3), "r"(c4) : "memory");
}
DEVINL void tma_ld_mc(uint32_t dst, const CUtensorMap* m, int c0, int c1, uint32_t bar, uint16_t mask = 3) {
  asm volatile(EL("cp.async.bulk.tensor.2d.shared::cluster.global.mbarrier::complete_tx::bytes.multicast::cluster [%0], [%1, {%3, %4}], [%2], %5;")
               ::"r"(dst), "l"(m), "r"(bar), "r"(c0), "r"(c1), "h"(mask) : "memory");
}
DEVINL void e_arrive_both(uint32_t bar) {
  asm volatile("{\n.reg .pred pe;\n.reg .b32 r0, r1;\nelect.sync _|pe, 0xffffffff;\nmapa.shared::cluster.u32 r0, %0, 0;\nmapa.shared::cluster.u32 r1, %0, 1;\n"
               "@pe mbarrier.arrive.shared::cluster.b64 _, [r0];\n@pe mbarrier.arrive.shared::cluster.b64 _, [r1];\n}" ::"r"(bar) : "memory");
}
DEVINL void tma_st(const CUtensorMap* m, int c0, int c1, uint32_t src) {
  asm volatile(EL("cp.async.bulk.tensor.2d.global.shared::cta.bulk_group [%0, {%2, %3}], [%1];") ::"l"(m), "r"(src), "r"(c0), "r"(c1) : "memory");
}
DEVINL void bulk_commit() { asm volatile("cp.async.bulk.commit_group;" ::: "memory"); }
template <int N> DEVINL void bulk_wait_n() { asm volatile("cp.async.bulk.wait_group %0;\nbar.warp.sync 0xffffffff;" ::"n"(N) : "memory"); }
DEVINL void l2_prefetch(const void* g, uint32_t bytes) { asm volatile(EL("cp.async.bulk.prefetch.L2.global [%0], %1;") ::"l"(g), "r"(bytes) : "memory"); }
DEVINL void fence_async_smem() { asm volatile("fence.proxy.async.shared::cta;" ::: "memory"); }
DEVINL void fence_async_gl() { asm volatile("fence.proxy.async.global;" ::: "memory"); }
DEVINL void cluster_wait() { asm volatile("barrier.cluster.wait.aligned;" ::: "memory"); }
DEVINL void bar_sync(int id, int n) { asm volatile("bar.sync %0, %1;" ::"r"(id), "r"(n) : "memory"); }
DEVINL void bar_arrive(int id, int n) { asm volatile("bar.arrive %0, %1;" ::"r"(id), "r"(n) : "memory"); }
DEVINL uint32_t ld_acquire(const uint32_t* p) { uint32_t v; asm volatile("ld.acquire.gpu.global.u32 %0, [%1];" : "=r"(v) : "l"(p) : "memory"); return v; }
DEVINL void await_flag(int j, uint32_t& rdy, const uint32_t* p, uint32_t target) {
  if ((rdy >> j) & 1) return;
#pragma unroll 1
  for (uint32_t n = 0; n < 200000u && !((rdy >> j) & 1); n++) rdy = __ballot_sync(~0u, (int)(ld_acquire(p) - target) >= 0);
  asm volatile("fence.proxy.async.global;" ::: "memory");
}
DEVINL void poll_ge(const uint32_t* p, uint32_t target) {
#pragma unroll 1
  for (uint32_t n = 0; n < 200000u; n++) if (__all_sync(~0u, (int)(ld_acquire(p) - target) >= 0)) break;
}
DEVINL int lane_id() { int v; asm volatile("mov.u32 %0, %%laneid;" : "=r"(v)); return v; }
__host__ DEVINL int remap(int v) {
  const int c = v >> 1, u = c - 36, r = (u * 37) >> 8;
  const int L = c < 4 ? 32 + 8 * c : c < 36 ? c - 4 : 33 + u + r;
  return 2 * L + (v & 1);
}
DEVINL int block_id() { int v; asm volatile("mov.u32 %0, %%ctaid.x;" : "=r"(v)); return v; }
#define cta_id() prm.map[block_id()]
#define IDS() const int lane = lane_id(), b = cta_id(), bm = b >> 4, bn = b & 15, rank = b & 1, pm = 2 * bm + (bn >> 3), pn = bn & 7, po = pm & 1; \
  (void)lane; (void)bm; (void)bn; (void)rank; (void)pm; (void)pn; (void)po
DEVINL void st_tagged(uint4* p, uint32_t a, uint32_t b, uint32_t c, uint32_t tag) {
  asm volatile("{\n.reg .b64 u, v;\n.reg .b128 t;\nmov.b64 u, {%1, %2};\nmov.b64 v, {%3, %4};\nmov.b128 t, {u, v};\nst.relaxed.gpu.global.b128 [%0], t;\n}"
               ::"l"(p), "r"(a), "r"(b), "r"(c), "r"(tag) : "memory");
}
DEVINL uint32_t ld_tagged(const uint4* p, uint32_t* r) {
  uint32_t tag;
  asm volatile("{\n.reg .b64 u, v;\n.reg .b128 t;\nld.relaxed.gpu.global.b128 t, [%4];\nmov.b128 {u, v}, t;\nmov.b64 {%0, %1}, u;\nmov.b64 {%2, %3}, v;\n}"
               : "=r"(r[0]), "=r"(r[1]), "=r"(r[2]), "=r"(tag) : "l"(p) : "memory");
  return tag;
}
DEVINL float ex2(float x) { float y; asm("ex2.approx.ftz.f32 %0, %1;" : "=f"(y) : "f"(x)); return y; }
DEVINL float rcp(float x) { float y; asm("rcp.approx.ftz.f32 %0, %1;" : "=f"(y) : "f"(x)); return y; }
DEVINL uint32_t pack2(float lo, float hi) { uint32_t r; asm("cvt.rn.bf16x2.f32 %0, %1, %2;" : "=r"(r) : "f"(hi), "f"(lo)); return r; }
DEVINL uint32_t pack2h(float lo, float hi) { uint32_t r; asm("cvt.rz.f16x2.f32 %0, %1, %2;" : "=r"(r) : "f"(hi), "f"(lo)); return r; }
DEVINL uint32_t prmt0(uint32_t a, uint32_t sel) { uint32_t r; asm("prmt.b32 %0, %1, 0, %2;" : "=r"(r) : "r"(a), "r"(sel)); return r; }
DEVINL void stg128(const void* p, uint32_t a, uint32_t b, uint32_t c, uint32_t d) {
  asm volatile("st.global.v4.b32 [%0], {%1, %2, %3, %4};" ::"l"(p), "r"(a), "r"(b), "r"(c), "r"(d) : "memory");
}
DEVINL uint32_t hadd2(uint32_t a, uint32_t b) { uint32_t r; asm("add.rn.f16x2 %0, %1, %2;" : "=r"(r) : "r"(a), "r"(b)); return r; }
DEVINL uint32_t hfma2(uint32_t a, uint32_t b, uint32_t c) { uint32_t r; asm("fma.rn.f16x2 %0, %1, %2, %3;" : "=r"(r) : "r"(a), "r"(b), "r"(c)); return r; }
DEVINL float bf_lo(uint32_t w) { return __uint_as_float(w << 16); }
DEVINL float bf_hi(uint32_t w) { return __uint_as_float(w & 0xFFFF0000u); }
DEVINL float bf_round(float x) { return bf_lo(pack2(x, 0.f)); }
DEVINL uint32_t add_bf16x2(uint32_t a, uint32_t b) { uint32_t r; asm("add.rn.bf16x2 %0, %1, %2;" : "=r"(r) : "r"(a), "r"(b)); return r; }
DEVINL void stsm4(uint32_t addr, uint32_t a, uint32_t b, uint32_t c, uint32_t d) {
  asm volatile("stmatrix.sync.aligned.m8n8.x4.shared.b16 [%0], {%1, %2, %3, %4};" ::"r"(addr), "r"(a), "r"(b), "r"(c), "r"(d) : "memory");
}
DEVINL void ldsm4(uint32_t addr, uint32_t (&r)[4]) {
  asm volatile("ldmatrix.sync.aligned.m8n8.x4.shared.b16 {%0, %1, %2, %3}, [%4];" : "=r"(r[0]), "=r"(r[1]), "=r"(r[2]), "=r"(r[3]) : "r"(addr) : "memory");
}
DEVINL void ldsm4t(uint32_t addr, uint32_t (&r)[4]) {
  asm volatile("ldmatrix.sync.aligned.m8n8.x4.trans.shared.b16 {%0, %1, %2, %3}, [%4];" : "=r"(r[0]), "=r"(r[1]), "=r"(r[2]), "=r"(r[3]) : "r"(addr) : "memory");
}
DEVINL void sts128(uint32_t addr, uint32_t a, uint32_t b, uint32_t c, uint32_t d) {
  asm volatile("st.shared.v4.b32 [%0], {%1, %2, %3, %4};" ::"r"(addr), "r"(a), "r"(b), "r"(c), "r"(d) : "memory");
}
DEVINL float2 lds64f(uint32_t addr) { float2 v; asm volatile("ld.shared.v2.f32 {%0, %1}, [%2];" : "=f"(v.x), "=f"(v.y) : "r"(addr) : "memory"); return v; }
DEVINL void mma16816(float (&d)[4], uint32_t a0, uint32_t a1, uint32_t a2, uint32_t a3, uint32_t b0, uint32_t b1) {
  asm("mma.sync.aligned.m16n8k16.row.col.f32.bf16.bf16.f32 {%0, %1, %2, %3}, {%4, %5, %6, %7}, {%8, %9}, {%0, %1, %2, %3};"
               : "+f"(d[0]), "+f"(d[1]), "+f"(d[2]), "+f"(d[3]) : "r"(a0), "r"(a1), "r"(a2), "r"(a3), "r"(b0), "r"(b1));
}
template <int N> DEVINL void fence_regs(float (&d)[N]) {
#pragma unroll
  for (int i = 0; i < N; i++) asm volatile("" : "+f"(d[i])::"memory");
}
template <int N> DEVINL void fence_regs(uint32_t (&d)[N]) {
#pragma unroll
  for (int i = 0; i < N; i++) asm volatile("" : "+r"(d[i])::"memory");
}
DEVINL void lds128(uint32_t addr, uint32_t* r) {
  asm volatile("ld.shared.v4.b32 {%0, %1, %2, %3}, [%4];" : "=r"(r[0]), "=r"(r[1]), "=r"(r[2]), "=r"(r[3]) : "r"(addr) : "memory");
}
DEVINL void sched_fence() { asm volatile("griddepcontrol.launch_dependents;" ::: "memory"); }

struct Scratch {
  bf16 k[32 * 2048 * 32];
  bf16 xs[2048 * 1024];
  bf16 os[2048 * 1024];
  bf16 v[32 * 2048 * 32];
  float kn[2 * 128 * 16];
  uint32_t cnt[256 * 32];
  float2 stats[8 * 2048];
  uint4 halo[128 * 12 * 32];
  float csp[2 * 16 * 8 * 192];
  uint4 qsave[128 * 256 * 8];
  uint32_t esc[4 * 65536 * 20];
};
__device__ __align__(1024) Scratch g_s;
#define g_k g_s.k
#define g_xs g_s.xs
#define g_os g_s.os
#define g_v g_s.v
#define g_kn g_s.kn
#define g_cnt g_s.cnt
#define g_stats g_s.stats
#define g_halo g_s.halo
#define g_csp g_s.csp
#define g_qsave g_s.qsave
#define g_esc g_s.esc
#define g_epoch g_s.cnt[255 * 32]

DEVINL uint32_t* cnt_x(int bm) { return g_cnt + bm * 32; }
DEVINL uint32_t* cnt_o(int l, int pm, int h) { return g_cnt + (32 + (l * 16 + pm) * 2 + h) * 32; }
DEVINL uint32_t* cnt_kv(int lb, int bn) { return g_cnt + (160 + lb * 16 + bn) * 32; }
DEVINL uint32_t* cnt_ad(int bn) { return g_cnt + (192 + bn) * 32; }
DEVINL uint32_t* cnt_cs(int t, int bn) { return g_cnt + (208 + t * 16 + bn) * 32; }

DEVINL int qord(int i, int l, int pn) {
  const int u = i < 10 ? i - 4 : i - 10;
  return l == 0 ? i : i < 4 ? ((2 * pn) ^ (2 * (i & 1))) + (i >> 1) : 2 * (u < (pn & 6) ? u : u + 2) + (i >= 10);
}
struct Params {
  CUtensorMap m[15];
  const bf16* x0;
  const bf16* wq[2];
  const bf16* wo;
  uint32_t zero;
  int map[128];
  uint64_t wd, xd;
  struct __align__(16) { uint64_t kd, vd; } kv[4];
};
enum { M_X0A = 0, M_WQA, M_WQB, M_WOA, M_WOB, M_OS, M_K, M_V, M_X0R, M_XSR, M_XSO, M_OUT, M_XST, M_X0H, M_OL, M_COUNT };

constexpr uint32_t QSTG = 57344;
constexpr uint32_t T0 = 65536, TSTG = 32768;
constexpr uint32_t ONES = 230400;
constexpr uint32_t PSTG = 32768, RES = 196608;
constexpr uint32_t KSC = 98304, VSC = 133120, HRS = 167936;
constexpr uint32_t ROWST = 229376, COLS = 231424, BARS = 232192, SMEM_BYTES = 232448;
constexpr uint32_t B_QF = BARS, B_QE = BARS + 32, B_TF = BARS + 64, B_TE = BARS + 96, B_PF = BARS + 128, B_PE = BARS + 176,
                   B_RF = BARS + 224, W_X = BARS + 232, B_QL = BARS + 240, B_PA = BARS + 248;
enum { NB_LAG = 0, NB_ST = 1, NB_KV = 2  , NB_DONE = 3, NB_SC = 4, NB_SIG = 5  , NB_KN = 9  , NB_X = 11, NB_HALO = 12  , NB_X0 = 15 };

DEVINL uint32_t pslot_b(uint32_t s) { return ((0x320415u >> (4 * s)) & 7) * 16384u; }
DEVINL uint32_t pslot_a(uint32_t s, int l) { return 98304u + ((((l & 1) ? 0x541230u : 0x041235u) >> (4 * s)) & 7) * 16384u; }

constexpr float QSCALE = 0.17677669529663687f * 1.4426950408889634f;
constexpr uint32_t QPARK = 32768;

DEVINL uint32_t exp2_h2(uint32_t s, uint32_t c852) {
  uint32_t r, t, w, m, d;
  asm volatile("{.reg .b64 t; add.rn.f16x2 %0, %1, %2; cvt.u64.u32 t, %0; cvt.u32.u64 %0, t;}" : "=r"(r) : "r"(s), "r"(0x65EA65EAu));
  asm volatile("fma.rn.f16x2 %0, %1, %2, %3;" : "=r"(t) : "r"(r), "r"(0xB880B880u), "r"(c852));
  asm volatile("fma.rn.f16x2 %0, %1, %2, %3;" : "=r"(w) : "r"(s), "r"(0x38803880u), "r"(t));
  asm volatile("fma.rn.f16x2 %0, %1, %1, %2;" : "=r"(m) : "r"(w), "r"(0x4A1F4A2Du));
  asm volatile("{.reg .b32 t; shf.l.clamp.b32 t, %2, %1, 7; add.u32 %0, t, %2;}" : "=r"(d) : "r"(r), "r"(m));
  return d;
}
DEVINL float exp2_fix(float s) { float z; asm volatile("add.rn.f32 %0, %1, 0f43BF34BC;" : "=f"(z) : "f"(s)); return z; }
DEVINL uint32_t exp2_base(float z0, float z1) { uint32_t B; asm volatile("prmt.b32 %0, %1, %2, 0x6521;" : "=r"(B) : "r"(__float_as_uint(z0)), "r"(__float_as_uint(z1))); return B; }
template <uint32_t MASK> DEVINL uint32_t and_or(uint32_t a, uint32_t c) { uint32_t r; asm volatile("lop3.b32 %0, %1, %3, %2, 0xEA;" : "=r"(r) : "r"(a), "r"(c), "n"(MASK)); return r; }
DEVINL uint32_t fma_bf2(uint32_t a, uint32_t b, uint32_t c) { uint32_t r; asm volatile("fma.rn.bf16x2 %0, %1, %2, %3;" : "=r"(r) : "r"(a), "r"(b), "r"(c)); return r; }
DEVINL float ex2v(float x) { float y; asm volatile("ex2.approx.ftz.f32 %0, %1;" : "=f"(y) : "f"(x)); return y; }
DEVINL uint32_t pack2v(float lo, float hi) { uint32_t r; asm volatile("cvt.rn.bf16x2.f32 %0, %1, %2;" : "=r"(r) : "f"(hi), "f"(lo)); return r; }
DEVINL void unesc(uint32_t (&u)[4], const uint32_t* esc, uint32_t tag) {
  const bool saved = __ldcg(esc + 16) == tag;
#pragma unroll
  for (int j = 0; j < 4; j++) {
    float lo, hi;
    asm("{.reg .f16 a, b; mov.b32 {a, b}, %2; cvt.f32.f16 %0, a; cvt.f32.f16 %1, b;}" : "=f"(lo), "=f"(hi) : "r"(u[j]));
    u[j] = saved ? __ldcg(esc + 4 * j) : pack2(lo, hi);
  }
}

DEVINL void attn_slow(const uint32_t (&q)[8], int head, const uint32_t* kesc, uint32_t tag, float (&res)[20], int lane) {
  const int g = lane >> 2, qd = lane & 3;
  const bf16* kb = g_k + (size_t)head * 2048 * 32;
  const bf16* vb = g_v + (size_t)head * 2048 * 32;
  float o[4][4], m0 = -INFINITY, m1 = -INFINITY, l0 = 0.f, l1 = 0.f;
#pragma unroll
  for (int j = 0; j < 4; j++) { o[j][0] = o[j][1] = o[j][2] = o[j][3] = 0.f; }
#pragma unroll 1
  for (int k0 = 0; k0 < 2048; k0 += 16) {
    float s[2][4];
#pragma unroll
    for (int nt = 0; nt < 2; nt++) {
      s[nt][0] = s[nt][1] = s[nt][2] = s[nt][3] = 0.f;
      const uint32_t* kp = (const uint32_t*)(kb + (size_t)(k0 + nt * 8 + g) * 32) + qd;
      uint32_t k[4] = {__ldcg(kp), __ldcg(kp + 4), __ldcg(kp + 8), __ldcg(kp + 12)};
      unesc(k, kesc + (k0 + nt * 8 + g) * 20 + qd, tag);
      __syncwarp();
      mma16816(s[nt], q[0], q[1], q[2], q[3], k[0], k[1]);
      mma16816(s[nt], q[4], q[5], q[6], q[7], k[2], k[3]);
    }
    float a0 = fmaxf(fmaxf(s[0][0], s[0][1]), fmaxf(s[1][0], s[1][1]));
    float a1 = fmaxf(fmaxf(s[0][2], s[0][3]), fmaxf(s[1][2], s[1][3]));
    a0 = fmaxf(a0, __shfl_xor_sync(~0u, a0, 1)); a0 = fmaxf(a0, __shfl_xor_sync(~0u, a0, 2));
    a1 = fmaxf(a1, __shfl_xor_sync(~0u, a1, 1)); a1 = fmaxf(a1, __shfl_xor_sync(~0u, a1, 2));
    const float n0 = fmaxf(m0, a0), n1 = fmaxf(m1, a1);
    const float c0 = (m0 == n0) ? 1.f : ex2(m0 - n0), c1 = (m1 == n1) ? 1.f : ex2(m1 - n1);
    m0 = n0; m1 = n1;
    const uint32_t p0 = pack2(ex2(s[0][0] - n0), ex2(s[0][1] - n0)), p1 = pack2(ex2(s[0][2] - n1), ex2(s[0][3] - n1));
    const uint32_t p2 = pack2(ex2(s[1][0] - n0), ex2(s[1][1] - n0)), p3 = pack2(ex2(s[1][2] - n1), ex2(s[1][3] - n1));
    l0 = l0 * c0 + bf_lo(p0) + bf_hi(p0) + bf_lo(p2) + bf_hi(p2);
    l1 = l1 * c1 + bf_lo(p1) + bf_hi(p1) + bf_lo(p3) + bf_hi(p3);
#pragma unroll
    for (int j = 0; j < 4; j++) {
      o[j][0] *= c0; o[j][1] *= c0; o[j][2] *= c1; o[j][3] *= c1;
      const unsigned short* vp = (const unsigned short*)(vb + (size_t)(k0 + 2 * qd) * 32 + j * 8 + g);
      const uint32_t b0 = (uint32_t)__ldcg(vp) | ((uint32_t)__ldcg(vp + 32) << 16);
      const uint32_t b1 = (uint32_t)__ldcg(vp + 256) | ((uint32_t)__ldcg(vp + 288) << 16);
      mma16816(o[j], p0, p1, p2, p3, b0, b1);
    }
  }
  l0 += __shfl_xor_sync(~0u, l0, 1); l0 += __shfl_xor_sync(~0u, l0, 2);
  l1 += __shfl_xor_sync(~0u, l1, 1); l1 += __shfl_xor_sync(~0u, l1, 2);
#pragma unroll
  for (int j = 0; j < 4; j++) { res[4 * j] = o[j][0]; res[4 * j + 1] = o[j][1]; res[4 * j + 2] = o[j][2]; res[4 * j + 3] = o[j][3]; }
  res[16] = l0; res[18] = l1;
}

__device__ __noinline__ void attn_redo(int redo, int l, int b, int wg, int w, uint32_t tag) {
  const int lane = lane_id();
#pragma unroll 1
  for (int t = 0; t < 4; t++) {
    const int h = t >> 1, head = 2 * (b & 15) + h, row = (b >> 4) * 256 + wg * 128 + (t & 1) * 64 + w * 16 + (lane >> 2);
    if ((redo >> t) & 1) {
      const uint32_t* esc = g_esc + (size_t)((l & 2) * 65536 + head * 2048) * 20;
      const uint32_t* qs = (const uint32_t*)(g_qsave + (block_id() * 256 + wg * 128 + w * 32 + lane) * 8 + 2 * t);
      uint32_t q[8]; float o[20];
#pragma unroll
      for (int i = 0; i < 2; i++) {
        uint32_t u[4] = {__ldcg(qs + i), __ldcg(qs + i + 2), __ldcg(qs + i + 4), __ldcg(qs + i + 6)};
        unesc(u, esc + (row + i * 8) * 20 + (lane & 3), tag);
        q[i] = u[0]; q[i + 2] = u[1]; q[i + 4] = u[2]; q[i + 6] = u[3];
      }
      __syncwarp();
      attn_slow(q, head, esc + 65536 * 20, tag, o, lane);
      const float i0 = rcp(o[16]), i1 = rcp(o[18]);
      bf16* op = g_os + (size_t)row * 1024 + h * 512 + (b & 15) * 32 + (lane & 3) * 8;
      *(uint4*)op = make_uint4(pack2(o[0] * i0, o[1] * i0), pack2(o[4] * i0, o[5] * i0), pack2(o[8] * i0, o[9] * i0), pack2(o[12] * i0, o[13] * i0));
      *(uint4*)(op + 8 * 1024) = make_uint4(pack2(o[2] * i1, o[3] * i1), pack2(o[6] * i1, o[7] * i1), pack2(o[10] * i1, o[11] * i1), pack2(o[14] * i1, o[15] * i1));
    }
    if ((t & 1) && ((redo >> 2 * h) & 3)) bar_arrive(NB_SIG + 2 * h + wg, 160 + 32 * (h & wg));
  }
}

__global__ void __cluster_dims__(2, 1, 1) __launch_bounds__(384, 1) fused_kernel(const __grid_constant__ Params prm) {
  extern __shared__ __align__(1024) char smem[];
  const uint32_t sb = (uint32_t)__cvta_generic_to_shared(smem);
  const int tid = threadIdx.x, lane = tid & 31;
  const int wg = __shfl_sync(0xffffffffu, tid >> 7, 0);
  const int w = __shfl_sync(0xffffffffu, (tid >> 5) & 3, 0);
  const int bm = remap(blockIdx.x) >> 4, bn = remap(blockIdx.x) & 15;

  auto first_tile = [&](int kt) {
    e_expect_tx(sb + B_QF + 8 * kt, QSTG);
    tma_ld(sb + kt * QSTG, &prm.m[M_X0A], kt * 64, bm * 256, sb + B_QF + 8 * kt);
    tma_ld3(sb + kt * QSTG + 32768, &prm.m[M_WQA], bn * 64, kt * 64, 0, sb + B_QF + 8 * kt);
  };
  auto init4 = [&](uint32_t bar, uint32_t c0, uint32_t c1, uint32_t c2, uint32_t c3) {
    asm volatile("{\n.reg .pred pe;\nelect.sync _|pe, 0xffffffff;\n@pe mbarrier.init.shared::cta.b64 [%0], %1;\n@pe mbarrier.init.shared::cta.b64 [%0+8], %2;\n"
                 "@pe mbarrier.init.shared::cta.b64 [%0+16], %3;\n@pe mbarrier.init.shared::cta.b64 [%0+24], %4;\n@pe fence.mbarrier_init.release.cluster;\n}"
                 ::"r"(bar), "r"(c0), "r"(c1), "r"(c2), "r"(c3) : "memory");
  };
  if (wg < 2) {
    const uint32_t k = wg * 4 + w, lo = (0x1411814u >> (4 * k)) & 15, hi = (0x1441814u >> (4 * k)) & 15;
    if (tid < 32) asm volatile("prefetch.global.L2 [%0];" ::"l"(prm.x0 + (size_t)(bm * 256 + bn * 16 + (tid & 15)) * 1024 + (tid >> 4) * 64));
    else if (tid < 80) asm volatile("prefetch.global.L2 [%0];" ::"l"(prm.wq[0] + (bm * 16 + (tid & 15)) * 3072 + ((tid >> 4) - 2) * 1024 + bn * 64));
    __syncwarp();
    if (k < 7) init4(sb + B_QE + 32 * k, lo, lo, hi, k == 6 ? 2 : hi);
    __syncwarp();
    if (k == 6 && lane == 0) *(volatile unsigned long long*)(smem + W_X) = 0ull;
  } else if (w == 0) {
    init4(sb + B_QF, 1, 1, 1, 1);
    __syncwarp();
    first_tile(0);
  }
  __syncthreads();
  asm volatile("barrier.cluster.arrive.relaxed.aligned;" ::: "memory");

  if (wg == 2) {
    asm volatile("setmaxnreg.dec.sync.aligned.u32 56;");
    const uint32_t ep1 = *(volatile uint32_t*)&g_epoch + 1;
    if (w == 0) {
      first_tile(1);
      mbar_wait(sb + B_QF, 0);
      first_tile(2); first_tile(3);
#pragma unroll 1
      for (int kt = 4; kt < 16; kt++) l2_prefetch(prm.wq[0] + kt * 196608 + blockIdx.x * 1536, 3072);
      cluster_wait();
#pragma unroll 1
      for (int l = 0; l < 4; l++) {
        IDS();
        const CUtensorMap* mw = &prm.m[M_WQA + (l & 1)];
        const CUtensorMap* mh = &prm.m[l == 0 ? M_X0H : M_XSO];
        const CUtensorMap* mo = &prm.m[M_WOA + (l & 1)];
        auto q_b = [&](int i) {
          const int s = i & 3;
          mbar_wait(sb + B_QE + 8 * s, ((i >> 2) & 1) ^ 1);
          e_expect_tx(sb + B_QF + 8 * s, QSTG);
          tma_ld3(sb + s * QSTG + 32768, mw, bn * 64, qord(i, l, pn) * 64, 0, sb + B_QF + 8 * s);
        };
        uint32_t rdy = l ? 0u : ~0u;
        auto q_a = [&](int i) {
          const int kt = qord(i, l, pn);
          await_flag(kt, rdy, cnt_x(bm) + (lane & 15), ep1 * 9 - 6 + 2 * l);
          tma_ld_mc(sb + (i & 3) * QSTG + rank * 16384, mh, kt * 64, bm * 256 + rank * 128, sb + B_QF + 8 * (i & 3));
        };
        if (l > 0) {
#pragma unroll 1
          for (int i = 0; i < 4; i++) {
            const int kt = qord(i, l, pn);
            await_flag(kt, rdy, cnt_x(bm) + (lane & 15), ep1 * 9 - 6 + 2 * l);
            e_expect_tx(sb + B_QF + 8 * i, 16384);
            tma_ld(sb + i * QSTG + (po ^ 1) * 16384, &prm.m[M_XSO], kt * 64, (pm ^ 1) * 128, sb + B_QF + 8 * i);
          }
        }
#pragma unroll 1
        for (int i = 4; i < 16; i++) {
          if (l == 3 && i == 12) poll_ge(cnt_ad(bn), ep1 * 16);
          q_b(i); q_a(i);
          if (l == 0 && i >= 8) l2_prefetch(prm.wq[1] + ((i - 8) * 128 + blockIdx.x) * 3072, 6144);
          if (l == 0 && i >= 8) l2_prefetch(prm.wo + ((i - 8) * 128 + blockIdx.x) * 1024, 2048);
        }
        if (l & 1) {
          const int krow = 2 * bn * 2048 + bm * 256;
          uint32_t* kvc = cnt_kv(l >> 1, bn);
          uint32_t seen = 0;
#pragma unroll 1
          for (int it = 1; it < 16; it++) {
            const int s = it & 3;
            if (it == 4) {
              bar_sync(NB_KV + 12, 288);
              mbar_wait(sb + B_TF + 24, 0);
#pragma unroll 1
              for (int i = 0; i < 4; i++) tma_st(&prm.m[M_K + (i & 1)], 0, krow + 2048 + (i >> 1) * 128, sb + i * 8192);
              bulk_commit();
            }
            if (it == 5) { bulk_wait_n<0>(); e_red(kvc + 16 + bm); }
            if (it == 12) { e_expect_tx(sb + B_RF, 32768); tma_ld3(sb + RES, &prm.m[M_XSR], 0, pm * 128, 2 * pn, sb + B_RF); }
            if (it == 1 || it == 3) mbar_wait(sb + B_QE + 12 + 4 * it, 1);
            mbar_wait(sb + B_TE + 8 * s, ((it >> 2) & 1) ^ 1);
            if (it < 8) {
#pragma unroll 1
              for (uint32_t n = 0; n < 200000u && (~seen & (3u << (2 * it - 2) | (it == 4 ? 0xC000u : 0u))); n++)
                seen = __ballot_sync(~0u, (int)(ld_acquire(kvc + (lane < 7 || lane == 15 ? (bm + 1 + lane) & 7 : 8 + ((bm + 2 + lane) & 7))) - ep1) >= 0);
              fence_async_gl();
            } else if (it == 8) { poll_ge(kvc + 16 + (lane & 7), ep1); fence_async_gl(); }
            e_expect_tx(sb + B_TF + 8 * s, 32768);
#pragma unroll 1
            for (int i = 0; i < 2; i++) {
              const int u = 2 * it - 2 + i;
              const int row = 2 * bn * 2048 + (it > 7 ? 2048 + ((bm + it) & 7) * 256 + i * 128 : u < 7 ? ((bm + 1 + u) & 7) * 256 : ((bm + 2 + u) & 7) * 256 + 128);
              tma_ld(sb + T0 + s * TSTG + i * 8192, &prm.m[M_K], 0, row, sb + B_TF + 8 * s);
              tma_ld(sb + T0 + s * TSTG + 16384 + i * 8192, &prm.m[M_V], 0, row, sb + B_TF + 8 * s);
            }
          }
        }
        auto p_b = [&](int i, uint32_t s, uint32_t par) {
          mbar_wait(sb + B_PE + 8 * s, par ^ 1);
          e_expect_tx(sb + B_PF + 8 * s, PSTG);
          tma_ld5(sb + pslot_b(s), mo, i >> 3, (2 * i + bn) & 14, 2 * pn, sb + B_PF + 8 * s);
        };
        auto p_a = [&](int i, uint32_t s) {
          await_flag(i, rdy, cnt_o(l, pm, (lane >> 3) & 1) + ((lane + (bn >> 1)) & 7), ep1 * 2);
          tma_ld_mc(sb + pslot_a(s, l) + rank * 8192, &prm.m[M_OS], (i & 8) * 64 + ((2 * i + bn) & 14) * 32, pm * 128 + rank * 64, sb + B_PF + 8 * s);
        };
        auto p_a2 = [&](int i) {
          await_flag(i, rdy, cnt_o(l, pm, (lane >> 3) & 1) + ((lane + (bn >> 1)) & 7), ep1 * 2);
          tma_ld(sb + pslot_a(i, l), &prm.m[M_OS], (i & 8) * 64 + ((2 * i + bn) & 14) * 32, pm * 128, sb + B_PF + 8 * i);
          tma_ld(sb + pslot_a(i, l) + 8192, &prm.m[M_OS], (i & 8) * 64 + ((2 * i + bn) & 14) * 32, pm * 128 + 64, sb + B_PF + 8 * i);
        };
        rdy = 0;
        if (l & 1) {
#pragma unroll 1
          for (int u = 0; u < 6; u++) { const int i = (0x205413 >> (4 * u)) & 7; if (u == 4) mbar_wait(sb + B_TE, 1); p_b(i, i, i < 4 ? 1 : 0); }
#pragma unroll 1
          for (int u = 0; u < 6; u++) {
            const int i = (0x542130 >> (4 * u)) & 7;
            if (!(u & 1)) mbar_wait(sb + B_TE + 8 + 4 * u, 1);
            if (u == 4) bar_sync(NB_SIG + 3, 192);
            p_a2(i);
          }
        } else {
#pragma unroll 1
          for (int u = 0; u < 6; u++) { const int i = (0x543120 >> (4 * u)) & 7; if (u == 0 || u == 2) mbar_wait(sb + B_QE + 8 - 4 * u, 1); p_b(i, i, 0); }
          mbar_wait(sb + B_QE + 24, 1);
          e_expect_tx(sb + B_RF, 32768);
          tma_ld3(sb + RES, &prm.m[l == 0 ? M_X0R : M_XSR], 0, pm * 128, 2 * pn, sb + B_RF);
          await_flag(1, rdy, cnt_o(l, pm, (lane >> 3) & 1) + ((lane + (bn >> 1)) & 7), ep1 * 2);
          bar_sync(NB_DONE, 288);
          e_arrive_both(sb + B_PA);
          mbar_wait(sb + B_PA, (l >> 1) & 1);
#pragma unroll 1
          for (int i = 1; i < 6; i++) { if (i > 3) mbar_wait(sb + B_PF + 8 * (i - 3), 0); p_a(i, i); }
        }
        uint32_t s = 0, lap = 1;
#pragma unroll 1
        for (int i = 6; i < 16; i++) {
          p_b(i, s, ((s < 4 ? l : 0) + lap) & 1);
          p_a(i, s);
          if (++s == 6) { s = 0; lap++; }
        }
        const CUtensorMap* mn = &prm.m[M_WQA + ((l + 1) & 1)];
        if (l < 3) {
          mbar_wait(sb + B_PE + 8 * 4, 1); mbar_wait(sb + B_PE + 8 * 5, 1);
          tma_ld3(sb + 32768, mn, bn * 64, 2 * pn * 64, 0, sb + B_QL);
          mbar_wait(sb + B_PE + 8 * 0, l & 1);
          e_expect_tx(sb + B_PA, 24576); e_expect_tx(sb + B_PA, 16384);
          tma_ld3(sb + QSTG + 32768, mn, bn * 64, ((2 * pn) ^ 2) * 64, 0, sb + B_PA);
          mbar_wait(sb + B_PE + 8 * 1, l & 1);
          tma_ld3(sb + 2 * QSTG + 32768, mn, bn * 64, (2 * pn + 1) * 64, 0, sb + B_QL);
          bar_sync(NB_KN, 288);
          e_expect_tx(sb + B_RF, 40960);
          tma_ld3(sb + 3 * QSTG + 32768, mn, bn * 64, ((2 * pn) ^ 3) * 64, 0, sb + B_RF);
          mbar_wait(sb + B_PE + 24, l & 1);
          bar_sync(NB_X0, 320);
          fence_async_gl();
          tma_ld_mc(sb + QSTG + po * 16384, &prm.m[M_XSO], 2 * pn * 64, pm * 128, sb + B_PA, 2 - rank);
          bar_sync(NB_X, 320);
          e_expect_tx(sb + B_QL, 49152);
        }
      }
      if (blockIdx.x == 0 && lane_id() == 0) *(volatile uint32_t*)&g_epoch = ep1;
    } else {
      const int hw = w - 1;
      if (lane < 5) asm volatile("prefetch.tensormap [%0];" ::"l"(&prm.m[5 * hw + lane]) : "memory");
      __syncwarp();
      cluster_wait();
      mbar_wait(sb + B_QF, 0);
#pragma unroll 1
      for (int l = 0; l < 4; l++) {
        IDS();
        if (l > 0) { mbar_wait(sb + B_QL, (l + 1) & 1); mbar_wait(sb + B_QF + 24, 0); }
        if (l == 0) {
#pragma unroll 1
          for (int r = 2 * hw; r < 16; r += 6) {
            const uint4* p = (const uint4*)(prm.x0 + (size_t)(b * 16 + r) * 1024) + lane;
            float s1[2] = {0.f, 0.f}, s2[2] = {0.f, 0.f};
#pragma unroll
            for (int i = 0; i < 8; i++) {
              const uint4 v = __ldg(p + 32 * i);
              const uint32_t u[4] = {v.x, v.y, v.z, v.w};
#pragma unroll
              for (int k = 0; k < 4; k++) { const float a = bf_lo(u[k]), c = bf_hi(u[k]); s1[i >> 2] += a + c; s2[i >> 2] = fmaf(a, a, fmaf(c, c, s2[i >> 2])); }
            }
#pragma unroll
            for (int o = 16; o; o >>= 1)
#pragma unroll
              for (int rr = 0; rr < 2; rr++) { s1[rr] += __shfl_xor_sync(~0u, s1[rr], o); s2[rr] += __shfl_xor_sync(~0u, s2[rr], o); }
            if (lane == 0) *(float4*)&g_stats[b * 16 + r] = make_float4(s1[0], s2[0], s1[1], s2[1]);
          }
        }
        if (l < 2) {
          float cs[8];
#pragma unroll
          for (int i = 0; i < 8; i++) cs[i] = 0.f;
          const uint4* wp = (const uint4*)(prm.wq[l] + (size_t)(bm * 128 + (lane >> 3)) * 3072 + hw * 1024 + bn * 64) + (lane & 7);
#pragma unroll 8
          for (int i = 0; i < 32; i++) {
            const uint4 v = __ldg(wp + (size_t)i * 4 * 384);
            cs[0] += bf_lo(v.x); cs[1] += bf_hi(v.x); cs[2] += bf_lo(v.y); cs[3] += bf_hi(v.y);
            cs[4] += bf_lo(v.z); cs[5] += bf_hi(v.z); cs[6] += bf_lo(v.w); cs[7] += bf_hi(v.w);
          }
#pragma unroll
          for (int i = 0; i < 8; i++) { cs[i] += __shfl_xor_sync(~0u, cs[i], 8); cs[i] += __shfl_xor_sync(~0u, cs[i], 16); }
          if (lane < 8) {
            float4* d = (float4*)(g_csp + ((l * 16 + bn) * 8 + bm) * 192 + hw * 64 + lane * 8);
            d[0] = make_float4(cs[0], cs[1], cs[2], cs[3]); d[1] = make_float4(cs[4], cs[5], cs[6], cs[7]);
          }
          __syncwarp();
          asm volatile("fence.acq_rel.gpu;" ::: "memory");
          e_red_relaxed(cnt_cs(l, bn));
          if (l == 0) e_red_relaxed(cnt_x(bm) + bn);
          poll_ge(lane < 16 && l == 0 ? cnt_x(bm) + lane : cnt_cs(l, bn), lane < 16 && l == 0 ? ep1 * 9 - 6 : ep1 * 24);
        }
        if (l > 0) poll_ge(cnt_x(bm) + (lane & 15), ep1 * 9 - 6 + 2 * l);
#pragma unroll 1
        for (int it = hw * 32 + lane; it < 176; it += 96) {
          const bool rows = it < 128;
          const float4* p = rows ? (const float4*)(g_stats + bm * 256) + it : (const float4*)(g_csp + ((l & 1) * 16 + bn) * 8 * 192) + (it - 128);
          const int stride = rows ? 1024 : 48, np = rows && l == 0 ? 1 : 8;
          float4 a = make_float4(0.f, 0.f, 0.f, 0.f);
#pragma unroll
          for (int k = 0; k < 8; k++) if (k < np) { const float4 v = __ldcg(p + k * stride); a.x += v.x; a.y += v.y; a.z += v.z; a.w += v.w; }
          if (rows) {
            const float m0 = a.x * (1.f / 1024.f), m1 = a.z * (1.f / 1024.f);
            const float v0 = fmaxf(a.y * (1.f / 1024.f) - m0 * m0, 0.f), v1 = fmaxf(a.w * (1.f / 1024.f) - m1 * m1, 0.f);
            const float r0 = __fdividef(1.f, bf_round(sqrtf(bf_round(bf_round(v0) + 1e-5f)))), r1 = __fdividef(1.f, bf_round(sqrtf(bf_round(bf_round(v1) + 1e-5f))));
            a = make_float4(r0, -bf_round(m0), r1, -bf_round(m1));
          }
          if (rows && (l & 1) && (it & 4)) a = make_float4(a.y, a.x, a.w, a.z);
          *(float4*)(smem + ROWST + it * 16) = a;
        }
        __syncwarp();
        if (lane == 0) asm volatile("red.release.cta.shared.add.u32 [%0], 1;" ::"r"(sb + W_X) : "memory");
        if (hw == 2) {
          if (!(l & 1)) {
            bar_sync(NB_ST, 288);
            const uint4* hp = g_halo + (b - 16) * 384 + lane;
#pragma unroll 1
            for (int h = 0; h < 2; h++) {
              uint32_t t[18];
#pragma unroll
              for (int i = 0; i < 18; i++) t[i] = 0;
#pragma unroll 1
              for (uint32_t n = bm ? 0 : 100000u; n < 100000u; n++) {
                uint32_t miss = 0;
#pragma unroll
                for (int i = 0; i < 6; i++) miss |= ld_tagged(hp + h * 192 + i * 32, &t[3 * i]) ^ (4 * ep1 + l);
                if (__all_sync(~0u, !miss)) break;
              }
              mbar_wait(sb + B_QE + 16, 1);
              const uint32_t r = (lane & 7) + ((lane >> 3) & 1) * 8, rv = lane >> 2;
#pragma unroll
              for (int jj = 0; jj < 2; jj++) stsm4(sb + KSC + r * 128 + (((4 * h + 2 * jj + (lane >> 4)) ^ (r & 7)) << 4), t[4 * jj], t[4 * jj + 1], t[4 * jj + 2], t[4 * jj + 3]);
              const uint32_t ad = sb + VSC + rv * 128 + (((4 * h + (lane & 3)) ^ (rv & 7)) << 4);
              sts128(ad, t[8], t[10], t[12], t[14]); sts128(ad + 1024, t[9], t[11], t[13], t[15]);
              if (h == 0 && !(lane & 2)) *(uint32_t*)(smem + HRS + ((lane >> 2) + 8 * (lane & 1)) * 8) = t[16];
              bar_arrive(NB_HALO + h, 64);
            }
          } else {
            bar_sync(NB_KV, 288);
            sts128(sb + ONES + lane * 32, 0x3f803f80u, 0x3f803f80u, 0x3f803f80u, 0x3f803f80u);
            sts128(sb + ONES + lane * 32 + 16, 0x3f803f80u, 0x3f803f80u, 0x3f803f80u, 0x3f803f80u);
            sts128(sb + ROWST + 16, 0x62A962A9u, 0x00010001u, 0x3F003F00u, 0u);
            fence_async_smem();
            __syncwarp();
            e_arrive(sb + B_TF);
            mbar_wait(sb + B_TF + 16, 0); mbar_wait(sb + B_TF + 16, 1);
            poll_ge(cnt_kv(l >> 1, bn) + 16 + (lane & 7), ep1);
            const uint4 v = __ldcg((const uint4*)(g_kn + ((l >> 1) * 128 + bn * 8) * 16) + lane);
            const uint32_t mx = max(max(v.x, v.y), max(v.z, v.w));
            const uint32_t m0 = __reduce_max_sync(~0u, (lane & 2) ? 0u : mx), m1 = __reduce_max_sync(~0u, (lane & 2) ? mx : 0u);
            if (lane == 0) *(uint2*)(smem + ROWST) = make_uint2(m0, m1);
            __syncwarp();
            bar_arrive(NB_KN, 160); bar_arrive(NB_KN + 1, 160);
          }
        } else {
          if (l & 1) {
            uint32_t* p = cnt_kv(l >> 1, bn) + 8 * hw + bm;
            int on = lane == 0;
            PREPARED(p, on);
            bar_sync(hw ? NB_HALO : NB_DONE, 160);
            tma_st(&prm.m[M_K], 0, 2 * bn * 2048 + bm * 256 + hw * 128, sb + T0 + hw * 8192);
            tma_st(&prm.m[M_V], 0, 2 * bn * 2048 + bm * 256 + hw * 128, sb + T0 + 16384 + hw * 8192);
            bulk_commit(); bulk_wait_n<0>();
            release_add(p, on);
          }
#pragma unroll 1
          for (int h = l & 1 ? 0 : hw; h <= (l & 1 ? 1 : hw); h++) {
            uint32_t* p = l == 1 && lane == 1 ? cnt_ad(bn) : cnt_o(l, 2 * bm + (l & 1 ? hw : lane & 1), h) + (bn >> 1);
            int on = lane == 0 || (lane == 1 && (!(l & 1) || (l == 1 && h == 1)));
            int id = NB_SIG + 2 * h + (l & hw), n = l & 1 ? 160 + 32 * (h & hw) : 288;
            asm volatile("" : "+r"(id), "+r"(n));
            PREPARED(p, on);
            bar_sync(id, n);
            release_add(p, on);
            if (!(l & 1) && hw == 0) {
              mbar_wait(sb + B_QE + 24, 1);
              fence_async_gl();
              tma_ld_mc(sb + pslot_a(0, 0) + rank * 8192, &prm.m[M_OL], bn * 32, pm * 128, sb + B_PF);
            }
          }
        }
        if (hw < 2 && l < 3) {
          uint32_t* p = cnt_x(bm) + 2 * pn + hw;
          int on = lane == 0;
          PREPARED(p, on);
          if (hw) {
            bar_sync(NB_X, 320);
            tma_st(&prm.m[M_XSO], pn * 128 + 64, pm * 128, sb + 2 * QSTG + po * 16384);
            bulk_commit();
            bar_sync(NB_KV, 288);
            bulk_wait_n<0>();
            mbar_wait(sb + B_PA, l == 0);
            fence_async_gl();
            tma_ld_mc(sb + 3 * QSTG + po * 16384, &prm.m[M_XSO], pn * 128 + 64, pm * 128, sb + B_RF, 2 - rank);
          } else bar_sync(NB_X0, 320);
          release_add(p, on);
        }
      }
    }
  } else {
    asm volatile("setmaxnreg.inc.sync.aligned.u32 224;");
    const uint32_t zero = prm.zero;
    cluster_wait();
#pragma unroll 1
    for (int l = 0; l < 4; l++) {
      {
        float acc[2][96];
        const bool early = l > 0 && wg == ((cta_id() >> 3) & 1);
        uint32_t ep1 = 0;
        if (l > 0) mbar_wait(sb + B_QL, (l + 1) & 1);
        if (!early) mbar_wait(sb + B_QF, 0);
        wg_fence();
#pragma unroll
        for (int k = 0; k < 4; k++)
#pragma unroll
          for (int m = 0; m < 2; m++) {
            if (k) wgmma_m64n192k16_ss_tb(acc[m], prm.xd + wg * 1024 + m * 512 + k * 2, prm.wd + k * 128, 1);
            else wgmma_m64n192k16_ss_tb_z(acc[m], prm.xd + wg * 1024 + m * 512, prm.wd, 0);
          }
        wg_commit();
#pragma unroll 1
        for (int kt = 1; kt < 13; kt++) {
          const int s = kt == 12 ? 1 : kt & 3;
          if (l > 0 && (kt | 2) == 3) mbar_wait(sb + (kt == 1 ? B_PA : B_RF), kt == 3 || l == 1);
          if (!(early && kt < 4)) mbar_wait(sb + B_QF + 8 * s, (kt >> 2) & 1);
          const uint64_t da = prm.xd + wg * 1024 + s * (QSTG >> 4), db = prm.wd + s * (QSTG >> 4);
          wg_fence();
#pragma unroll
          for (int k = 0; k < 4; k++)
#pragma unroll
            for (int m = 0; m < 2; m++) wgmma_m64n192k16_ss_tb(acc[m], da + m * 512 + k * 2, db + k * 128, 1);
          wg_commit();
          if (kt == 4) ep1 = *(volatile uint32_t*)&g_epoch + 1;
          wg_wait<1>();
          if (early && kt < 5) {
#pragma unroll 1
            for (int i = 3 * (kt - 3); i < kt && kt > 2; i++) { mbar_wait(sb + B_QF + 8 * i, 0); bar_sync(NB_SC, 128); if (w == 0) e_arrive_both(sb + B_QE + 8 * i); }
          } else if (w == 0) e_arrive_both(sb + B_QE + 8 * ((kt - 1) & 3));
        }
        {
          const bool lag = (l & 1) == wg;
          const uint32_t s0 = 2 * (~l & 1);
          const uint64_t da = prm.xd + wg * 1024 + 2 * (QSTG >> 4), db = prm.wd + 2 * (QSTG >> 4);
          mbar_wait(sb + B_QF + 8 * s0, 1);
#pragma unroll
          for (int t = 0; t < 2; t++) {
            if (lag && t != wg) {
              wg_wait<0>();
              if (w == 0) e_arrive_both(sb + B_QE + 8 + 8 * t);
              if (t == 0) mbar_wait(sb + B_QF + 16, 1);
              mbar_wait(sb + B_QF + 24, 1);
              if (t == 1) bar_arrive(NB_ST, 288);
              bar_sync(NB_LAG, 256);
            }
            const uint64_t so = (uint64_t)(t ? s0 : s0 ^ 2) * (QSTG >> 4);
            wg_fence();
#pragma unroll
            for (int k = 0; k < 4; k++)
#pragma unroll
              for (int m = 0; m < 2; m++) wgmma_m64n192k16_ss_tb(acc[m], da - so + m * 512 + k * 2, db - so + k * 128, 1);
            wg_commit();
            if (!lag || t + wg == 0) {
              wg_wait<1>();
              if (w == 0) e_arrive_both(sb + B_QE + 8 * (t ? s0 : 1));
              mbar_wait(sb + B_QF + 8 * (t ? 3 : s0 ^ 2), 1);
            }
          }
          wg_fence();
#pragma unroll
          for (int m = 1; m >= 0; m--) {
#pragma unroll
            for (int k = 0; k < 4; k++) wgmma_m64n192k16_ss_tb(acc[m], da + (QSTG >> 4) + m * 512 + k * 2, db + (QSTG >> 4) + k * 128, 1);
            wg_commit();
          }
          if (!lag) { bar_arrive(NB_LAG, 256); if (wg) bar_arrive(NB_ST, 288); }
          wg_wait<2>();
          if (w == 0) { e_arrive_both(sb + B_QE + 8 * (s0 ^ 2)); if (lag && wg) e_arrive_both(sb + B_QE); }
        }
#pragma unroll 1
        for (uint32_t n = 0; n < 4000000u; n++) {
          uint32_t v;
          asm volatile("ld.acquire.cta.shared.u32 %0, [%1];" : "=r"(v) : "r"(sb + W_X) : "memory");
          if (v == (uint32_t)(3 * l + 3)) break;
        }
        IDS();
        const int g = lane >> 2, qd = lane & 3;
        float2 st[2][2];
#pragma unroll
        for (int m = 0; m < 2; m++)
#pragma unroll
          for (int hh = 0; hh < 2; hh++) st[m][hh] = lds64f(sb + ROWST + (wg * 128 + m * 64 + w * 16 + g + 8 * hh) * 8);
        float2 cs[4];
        auto load_cs = [&](int gi) {
#pragma unroll
          for (int j = 0; j < 4; j++) cs[j] = lds64f(sb + COLS + (gi * 32 + j * 8 + 2 * qd) * 4);
        };
        load_cs(2 + 2 * (l & 1));
        auto drain = [&]() {
          wg_wait<0>(); fence_regs(acc[0]);
          if (w == 0) e_arrive_both(sb + B_QE + 8 * 3);
        };
        wg_wait<1>(); fence_regs(acc[1]);
        auto norm_tile = [&](int gi, int m, float sc, uint32_t (&t)[8], bool h16 = false) {
          const float r0 = st[m][0].x * sc, s0 = st[m][0].y, r1 = st[m][1].y * sc, s1 = st[m][1].x;
#pragma unroll
          for (int j = 0; j < 4; j++) {
            const float* a = &acc[m][16 * gi + 4 * j];
            const float v0 = fmaf(s0, cs[j].x, a[0]) * r0, v1 = fmaf(s0, cs[j].y, a[1]) * r0;
            const float v2 = fmaf(s1, cs[j].x, a[2]) * r1, v3 = fmaf(s1, cs[j].y, a[3]) * r1;
            t[2 * j] = h16 ? pack2h(v0, v1) : pack2(v0, v1); t[2 * j + 1] = h16 ? pack2h(v2, v3) : pack2(v2, v3);
          }
        };
        uint32_t q[2][2][8];
        const uint32_t srow = (lane & 7) + ((lane >> 3) & 1) * 8;
        const uint32_t row0 = wg * 128 + w * 16;
        if (!(l & 1)) {
          auto put_kv = [&](int gi, uint32_t r0, const uint32_t (&t)[8]) {
            if (gi < 4) {
              const uint32_t r = r0 + srow;
#pragma unroll
              for (int jj = 0; jj < 2; jj++) stsm4(sb + KSC + r * 128 + (((4 * (gi - 2) + 2 * jj + (lane >> 4)) ^ (r & 7)) << 4), t[4 * jj], t[4 * jj + 1], t[4 * jj + 2], t[4 * jj + 3]);
            } else {
              const uint32_t r = r0 + g, ad = sb + VSC + r * 128 + (((4 * (gi - 4) + qd) ^ (r & 7)) << 4);
              sts128(ad, t[0], t[2], t[4], t[6]); sts128(ad + 1024, t[1], t[3], t[5], t[7]);
            }
          };
          auto cen_tile = [&](int gi, int m, uint32_t (&t)[8]) {
#pragma unroll
            for (int j = 0; j < 4; j++) {
              const float* a = &acc[m][16 * gi + 4 * j];
              t[2 * j] = pack2(fmaf(st[m][0].y, cs[j].x, a[0]), fmaf(st[m][0].y, cs[j].y, a[1]));
              t[2 * j + 1] = pack2(fmaf(st[m][1].y, cs[j].x, a[2]), fmaf(st[m][1].y, cs[j].y, a[3]));
            }
          };
          const bool send = wg == 1 && w == 3 && bm < 7;
          uint4* hp = g_halo + b * 384 + lane;
          ep1 = 4 * ep1 + l;
          mbar_wait(sb + B_QE + 16, 1);
          float2 cn[4];
          auto next_cs = [&](int gi) {
#pragma unroll
            for (int j = 0; j < 4; j++) { cs[j] = cn[j]; cn[j] = lds64f(sb + COLS + (gi * 32 + j * 8 + 2 * qd) * 4); }
          };
#pragma unroll
          for (int j = 0; j < 4; j++) cn[j] = cs[j];
          auto lower = [&](int h, int nx, bool snd) {
            uint32_t k[8], v[8];
            next_cs(4 + h);
            cen_tile(2 + h, 1, k); put_kv(2 + h, 16 + row0 + 64, k);
            next_cs(nx);
            cen_tile(4 + h, 1, v); put_kv(4 + h, 16 + row0 + 64, v);
            if (snd) {
              uint4* p = hp + h * 192;
              st_tagged(p, k[0], k[1], k[2], ep1); st_tagged(p + 32, k[3], k[4], k[5], ep1); st_tagged(p + 64, k[6], k[7], v[0], ep1);
              st_tagged(p + 96, v[1], v[2], v[3], ep1); st_tagged(p + 128, v[4], v[5], v[6], ep1);
              st_tagged(p + 160, v[7], __float_as_uint(qd & 1 ? st[1][1].x : st[1][0].x), 0u, ep1);
            }
          };
          lower(0, 2 + wg, send);
          sched_fence();
          if (wg) lower(1, 2, send);
          drain();
          {
            uint32_t t[8];
            next_cs(4); cen_tile(2, 0, t); put_kv(2, 16 + row0, t);
            next_cs(0); cen_tile(4, 0, t); put_kv(4, 16 + row0, t);
            next_cs(3); cen_tile(0, 0, q[0][0]); cen_tile(0, 1, q[0][1]);
          }
          auto upper = [&]() {
            uint32_t t[8];
            next_cs(5); cen_tile(3, 0, t); put_kv(3, 16 + row0, t);
            next_cs(1); cen_tile(5, 0, t); put_kv(5, 16 + row0, t);
          };
          if (wg) upper();
          const bool e = g & 1, sel = 2 * qd + (g & 1) >= g + 2, first = bm == 0 && row0 == 0;
          uint32_t ka = sb + KSC + (row0 + (lane & 7)) * 128 + (((lane >> 3) ^ (lane & 7)) << 4);
          uint32_t wa = sb + VSC + (row0 + srow) * 128 + (((lane >> 4) ^ (lane & 7)) << 4);
          uint32_t psel[3] = {e ? 0x1044u : 0x4410u, !sel ? 0x4444u : e ? 0x3244u : 0x4432u, sel ? 0x4444u : e ? 0x3244u : 0x4432u};
          bf16* op = g_os + (size_t)(bm * 256 + row0 + g) * 1024 + bn * 32 + qd * 8;
          asm volatile("" : "+r"(ka), "+r"(wa), "+l"(op));
          fence_regs(psel); fence_regs(q[0][0]); fence_regs(q[0][1]);
          sched_fence();
          bar_sync(NB_SC, 256);
          if (row0 == 0) bar_sync(NB_HALO, 64);
          float ra[4], rb[4], ca[4], cb[4];
#pragma unroll
          for (int m = 0; m < 2; m++) {
            float rk[3];
#pragma unroll
            for (int u = 0; u < 3; u++) {
              const int r = row0 + m * 64 + 8 * u + 2 * qd + e - (sel ? 16 : 8);
              rk[u] = lds64f(sb + (m == 0 && r < 0 ? HRS + 128 : ROWST) + r * 8).x;
            }
            ra[2 * m] = sel ? rk[1] : rk[0]; ra[2 * m + 1] = sel ? rk[2] : rk[1];
            rb[2 * m] = sel ? rk[0] : rk[1]; rb[2 * m + 1] = sel ? rk[1] : rk[2];
          }
#pragma unroll
          for (int i = 0; i < 4; i++) { const float rq = st[i >> 1][i & 1].x * QSCALE; ca[i] = rq * ra[i]; cb[i] = rq * rb[i]; }
#pragma unroll 1
          for (int h = 0; h < 2; h++) {
            float s[2][4][4];
            uint32_t vf[2][4][4], pf[2][2][4];
#pragma unroll
            for (int m = 0; m < 2; m++)
#pragma unroll
              for (int nt = 0; nt < 4; nt++) {
                uint32_t kf[4];
                ldsm4(ka + (m * 64 + 8 * nt) * 128, kf);
                s[m][nt][0] = s[m][nt][1] = s[m][nt][2] = s[m][nt][3] = 0.f;
                mma16816(s[m][nt], q[0][m][0], q[0][m][1], q[0][m][2], q[0][m][3], kf[0], kf[1]);
                mma16816(s[m][nt], q[0][m][4], q[0][m][5], q[0][m][6], q[0][m][7], kf[2], kf[3]);
              }
#pragma unroll
            for (int m = 0; m < 2; m++)
#pragma unroll
              for (int i = 0; i < 4; i++) {
                ldsm4t((wa ^ (32 * (i & 1))) + (m * 64 + 16 * (i >> 1)) * 128, vf[m][i]);
              }
            float va[4], vb[4], mx[4];
#pragma unroll
            for (int i = 0; i < 4; i++) {
              const int m = i >> 1, hh = i & 1;
              const float a = e ? s[m][hh + 1][2 * hh + 1] : s[m][hh + 1][2 * hh];
              const float lo = e ? s[m][hh][2 * hh + 1] : s[m][hh][2 * hh], hi = e ? s[m][hh + 2][2 * hh + 1] : s[m][hh + 2][2 * hh];
              va[i] = (m == 0 && hh == 0 && first) ? -INFINITY : a * ca[i];
              vb[i] = (m == 0 && first && sel) ? -INFINITY : (sel ? lo : hi) * cb[i];
              mx[i] = fmaxf(va[i], vb[i]);
            }
#pragma unroll
            for (int i = 0; i < 4; i++) mx[i] = fmaxf(mx[i], __shfl_xor_sync(~0u, mx[i], 1));
#pragma unroll
            for (int i = 0; i < 4; i++) mx[i] = fmaxf(mx[i], __shfl_xor_sync(~0u, mx[i], 2));
#pragma unroll
            for (int i = 0; i < 4; i++) {
              va[i] = ex2(va[i] - mx[i]); vb[i] = ex2(vb[i] - mx[i]);
              mx[i] = va[i] + vb[i];
              va[i] *= ra[i]; vb[i] *= rb[i];
            }
#pragma unroll
            for (int i = 0; i < 4; i++) mx[i] += __shfl_xor_sync(~0u, mx[i], 1);
#pragma unroll
            for (int i = 0; i < 4; i++) mx[i] += __shfl_xor_sync(~0u, mx[i], 2);
#pragma unroll
            for (int i = 0; i < 4; i++) {
              const int m = i >> 1, hh = i & 1;
              const float inv = rcp(mx[i]);
              const uint32_t t = pack2(va[i] * inv, vb[i] * inv);
              pf[m][hh][hh + 1] = prmt0(t, psel[0]); pf[m][hh][hh] = prmt0(t, psel[1]); pf[m][hh][hh + 2] = prmt0(t, psel[2]);
              pf[m][hh][3 - 3 * hh] = t & zero;
            }
#pragma unroll
            for (int m = 0; m < 2; m++) {
              float o[4][4];
#pragma unroll
              for (int j = 0; j < 4; j++) o[j][0] = o[j][1] = o[j][2] = o[j][3] = 0.f;
#pragma unroll
              for (int i = 0; i < 4; i++) {
                const int kk = i >> 1, jj = 2 * (i & 1);
                mma16816(o[jj], pf[m][0][2 * kk], pf[m][1][2 * kk], pf[m][0][2 * kk + 1], pf[m][1][2 * kk + 1], vf[m][i][0], vf[m][i][1]);
                mma16816(o[jj + 1], pf[m][0][2 * kk], pf[m][1][2 * kk], pf[m][0][2 * kk + 1], pf[m][1][2 * kk + 1], vf[m][i][2], vf[m][i][3]);
              }
              stg128(op + m * 65536, pack2(o[0][0], o[0][1]), pack2(o[1][0], o[1][1]), pack2(o[2][0], o[2][1]), pack2(o[3][0], o[3][1]));
              stg128(op + m * 65536 + 8192, pack2(o[0][2], o[0][3]), pack2(o[1][2], o[1][3]), pack2(o[2][2], o[2][3]), pack2(o[3][2], o[3][3]));
            }
            if (h) bar_arrive(NB_DONE, 288);
            bar_arrive(NB_SIG + 2 * h, 288);
            if (h == 0) {
              if (!wg) { lower(1, 3, false); upper(); }
#pragma unroll
              for (int j = 0; j < 4; j++) cs[j] = cn[j];
              cen_tile(1, 0, q[0][0]); cen_tile(1, 1, q[0][1]);
              ka ^= 64; wa ^= 64; op += 512;
              bar_sync(NB_SC, 256);
              if (row0 == 0) bar_sync(NB_HALO + 1, 64);
            }
          }
        } else {
          float qn[2];
          mbar_wait(sb + B_QE + 8, 1);
          drain();
          auto esc_ptr = [&](int gi) { IDS(); return g_esc + (size_t)(((l & 2) + (gi >> 1)) * 65536 + (2 * bn + (gi & 1)) * 2048) * 20; };
          auto norm_half = [&](int gi, float sc, uint32_t (&t)[2][8], uint32_t (&n)[2], int nx) {
#pragma unroll
            for (int m = 0; m < 2; m++) {
              norm_tile(gi, m, sc, t[m], true);
              uint32_t a = hfma2(t[m][0], t[m][0], 0u), c = hfma2(t[m][1], t[m][1], 0u);
#pragma unroll
              for (int j = 1; j < 4; j++) { a = hfma2(t[m][2 * j], t[m][2 * j], a); c = hfma2(t[m][2 * j + 1], t[m][2 * j + 1], c); }
              n[m] = hadd2(__byte_perm(a, c, 0x5410), __byte_perm(a, c, 0x7632));
            }
            float2 cn[4];
#pragma unroll
            for (int j = 0; j < 4; j++) if (nx >= 0) cn[j] = lds64f(sb + COLS + (nx * 32 + j * 8 + 2 * qd) * 4);
            if (((n[0] - 0x01000100u) | (n[0] + 0x04000400u) | (n[1] - 0x01000100u) | (n[1] + 0x04000400u)) & 0x80008000u) {
              uint32_t* p = esc_ptr(gi) + (bm * 256 + row0 + g) * 20 + qd;
#pragma unroll
              for (int m = 0; m < 2; m++) {
                uint32_t u[8];
                norm_tile(gi, m, sc, u);
#pragma unroll
                for (int i = 0; i < 10; i++) p[(m * 64 + (i & 1) * 8) * 20 + (i >> 1) * 4] = i < 8 ? u[i] : ep1;
              }
            }
            __syncwarp();
#pragma unroll
            for (int i = 0; i < 16; i++) asm volatile("{\n.reg .b32 u;\nadd.u32 u, %0, 0x00040004;\nand.b32 %0, u, 0xFFF8FFF8;\n}" : "+r"(t[i >> 3][i & 7]));
#pragma unroll
            for (int j = 0; j < 4; j++) if (nx >= 0) cs[j] = cn[j];
          };
          {
            auto max_norm = [&](const uint32_t (&n)[2]) {
              const bool o1 = qd & 1;
              uint32_t a = hadd2(o1 ? n[1] : n[0], __shfl_xor_sync(~0u, o1 ? n[0] : n[1], 1));
              a = hadd2(a, __shfl_xor_sync(~0u, a, 2));
              float lo, hi;
              asm("{.reg .f16 a, b; mov.b32 {a, b}, %2; cvt.f32.f16 %0, a; cvt.f32.f16 %1, b;}" : "=f"(lo), "=f"(hi) : "r"(a));
              return __uint_as_float(__reduce_max_sync(~0u, max(__float_as_uint(lo), __float_as_uint(hi))));
            };
#pragma unroll
            for (int h = 0; h < 2; h++) {
              uint32_t t[2][8], nrm[2];
              const uint32_t kb = sb + (h ? wg * 8192 : T0), vb = kb + (h ? 8192 : 16384);
              norm_tile(4 + h, 0, 1.f, t[0]); norm_tile(4 + h, 1, 1.f, t[1]);
              load_cs(2 + h);
#pragma unroll
              for (int m = 0; m < 2; m++) {
                const uint32_t r = row0 + m * 64 + g, ad = vb + r * 64 + ((qd ^ ((r >> 1) & 3)) << 4);
                sts128(ad, t[m][0], t[m][2], t[m][4], t[m][6]); sts128(ad + 512, t[m][1], t[m][3], t[m][5], t[m][7]);
              }
              if (h == 0) sched_fence();
              norm_half(2 + h, 1.f, t, nrm, h);
#pragma unroll
              for (int i = 0; i < 4; i++) {
                const uint32_t r = row0 + (i >> 1) * 64 + srow;
                stsm4(kb + r * 64 + (((2 * (i & 1) + (lane >> 4)) ^ ((r >> 1) & 3)) << 4), t[i >> 1][4 * (i & 1)], t[i >> 1][4 * (i & 1) + 1], t[i >> 1][4 * (i & 1) + 2], t[i >> 1][4 * (i & 1) + 3]);
              }
              if (h == 1) { const float kn = max_norm(nrm); if (lane == 0) g_kn[((l >> 1) * 128 + bn * 8 + bm) * 16 + 8 + wg * 4 + w] = kn; }
              fence_async_smem();
              bar_arrive(NB_KV + 12 * h, 288);
              if (h == 0) {
                bar_arrive(wg ? NB_HALO : NB_DONE, 160);
              }
              if (h == 0) { const float kn = max_norm(nrm); if (lane == 0) g_kn[((l >> 1) * 128 + bn * 8 + bm) * 16 + wg * 4 + w] = kn; }
              norm_half(h, QSCALE, q[h], nrm, h ? -1 : 5);
#pragma unroll
              for (int i = 0; i < 4 * h; i++) sts128(sb + QPARK + 24576 - wg * 8192 + (w * 32 + lane) * 16 + i * 2048, q[h][i >> 1][4 * (i & 1)], q[h][i >> 1][4 * (i & 1) + 1], q[h][i >> 1][4 * (i & 1) + 2], q[h][i >> 1][4 * (i & 1) + 3]);
              qn[h] = max_norm(nrm);
            }
          }
          constexpr uint64_t VSTEP = 64 - (64ull << 16);
          uint32_t cq[4];
          const uint32_t &c_852 = cq[0], &c_lsb = cq[1], &c_half = cq[2];
          float o[2][20], S[2][32];
          uint32_t H[2][16], P0[4] = {}, P1[4] = {};
#pragma unroll
          for (int m = 0; m < 2; m++) {
#pragma unroll
            for (int i = 0; i < 20; i++) o[m][i] = 0.f;
            fence_regs(o[m]);
          }
          auto qkf = [&](int b, int ks, uint64_t d) { wg_n64_rs_nb_f16_f32(S[b], q[0][0][4 * ks], q[0][0][4 * ks + 1], q[0][0][4 * ks + 2], q[0][0][4 * ks + 3], d + 2 * ks, ks ? 1 : zero); };
          auto qkh = [&](int b, int ks, uint64_t d) { wg_n64_rs_nb_f16_f16(H[b], q[0][1][4 * ks], q[0][1][4 * ks + 1], q[0][1][4 * ks + 2], q[0][1][4 * ks + 3], d + 2 * ks, ks ? 1 : zero); };
          auto pv0 = [&](uint64_t d) { wgmma_m64n40k16_rs_tb(o[0], P0[0], P0[1], P0[2], P0[3], d, 1); };
          auto pv1 = [&](uint64_t d) { wgmma_m64n40k16_rs_tb(o[1], P1[0], P1[1], P1[2], P1[3], d, 1); };
          float e[4] = {};
          auto finish = [&](int h) {
            const float* s = &S[(h >> 2) & 1][8 * (h & 3)];
            const uint32_t* u = &H[(h >> 2) & 1][4 * (h & 3)];
            const float z0 = exp2_fix(s[6]), z1 = exp2_fix(s[7]);
            P0[0] = pack2v(e[0], e[1]);
            P1[0] = exp2_h2(u[0], c_852);
            P0[1] = pack2v(e[2], e[3]);
            P1[1] = exp2_h2(u[1], c_852);
            const uint32_t B = exp2_base(z0, z1), E = and_or<0x7F807F80u>(B, c_lsb);
            P1[3] = exp2_h2(u[3], c_852);
            P0[3] = fma_bf2(B, and_or<0x807F807Fu>(B, c_half), E);
            const float e4 = ex2v(s[4]), e5 = ex2v(s[5]);
            P1[2] = exp2_h2(u[2], c_852);
            P0[2] = pack2v(e4, e5);
          };
          auto start = [&](int h) {
            const float* s = &S[(h >> 2) & 1][8 * (h & 3)];
            e[2] = ex2v(s[2]); e[1] = ex2v(s[1]); e[0] = ex2v(s[0]); e[3] = ex2v(s[3]);
          };
          uint64_t kd = prm.kv[0].kd;
          mbar_wait(sb + B_TF, 0);
          lds128(sb + ROWST + 16 + (lane_id() & zero), cq);
#pragma unroll
          for (int i = 0; i < 4; i++) sts128(sb + QPARK + (wg * 128 + w * 32 + lane_id()) * 16 + i * 4096, q[0][i >> 1][4 * (i & 1)], q[0][i >> 1][4 * (i & 1) + 1], q[0][i >> 1][4 * (i & 1) + 2], q[0][i >> 1][4 * (i & 1) + 3]);
          wg_fence();
#pragma unroll
          for (int b = 0; b < 2; b++) {
            wg_n64_rs_nb_f16_f32_z(S[b], q[0][0][0], q[0][0][1], q[0][0][2], q[0][0][3], kd + 256 * b, 0);
            wg_n64_rs_nb_f16_f16_z(H[b], q[0][1][0], q[0][1][1], q[0][1][2], q[0][1][3], kd + 256 * b, 0);
            if (b == 0) { qkf(0, 1, kd); qkh(0, 1, kd); }
            wg_commit();
          }
          wg_wait<1>(); fence_regs(S[0]); fence_regs(H[0]);
          start(0); finish(0); start(1);
          wg_wait<0>();
          int redo = 0;
#pragma unroll 1
          for (int pass = 0, j = 1; pass < 2; pass++) {
#pragma unroll 1
           do {
            const uint64_t vd = prm.kv[j & 3].vd;
            bool go = false;
#pragma unroll
            for (int h = 2; h < 18; h++) {
              const int px = (h >> 2) + 1, c = h & 3;
              wg_fence();
              if (h == 13) kd = prm.kv[j & 3].kd;
              const uint64_t kx = kd + (px & 3) * 256, vx = vd + (h - 2) * VSTEP;
              if (h == 2) { qkh(1, 0, kx); qkf(1, 0, kx); pv0(vx); pv1(vx); qkh(1, 1, kx); qkf(1, 1, kx); }
              else if ((c == 1 || c == 2) && h < 17) { qkh(px & 1, c - 1, kx); pv1(vx); qkf(px & 1, c - 1, kx); pv0(vx); }
              else { pv0(vx); pv1(vx); }
              wg_commit();
              if (h == 3) e_arrive_if(sb + B_TE + 8 * ((j + 2) & 3), j > 1);
              if (h == 11) go = mbar_test(sb + B_TF + 8 * (j & 3), (j >> 2) & 1) && j != 8;
              finish(h - 1); start(h);
              if (h != 12 && h != 17) sched_fence();
              if (h == 12 && !go) {
                if (j == 16) {
#pragma unroll
                  for (int u = 13; u < 18; u++) {
                    wg_fence(); pv0(vd + (u - 2) * VSTEP); pv1(vd + (u - 2) * VSTEP); wg_commit();
                    if (u < 17) finish(u - 1);
                    if (u < 16) { start(u); sched_fence(); }
                    if (u & 1) { if (u == 17) wg_wait<0>(); else wg_wait<1>(); }
                  }
                  e_arrive(sb + B_TE + 24);
                  goto head_done;
                }
                mbar_wait(sb + B_TF + 8 * (j & 3), (j >> 2) & 1);
                if (j == 8) {
#pragma unroll
                  for (int i = 0; i < 4; i++) lds128(sb + QPARK + 24576 - wg * 8192 + (w * 32 + lane_id()) * 16 + i * 2048, &q[0][i >> 1][4 * (i & 1)]);
                }
              }
              if (h == 17) wg_wait<0>(); else if (h & 1) wg_wait<1>();
              if (c == 3) { fence_regs(S[px & 1]); fence_regs(H[px & 1]); }
            }
           } while (j++ & 7);
           head_done:
            fence_regs(o[0]); fence_regs(o[1]);
            uint32_t pk[2][8];
            {
              IDS();
              bf16* op = g_os + (size_t)(bm * 256 + row0 + (lane >> 2)) * 1024 + pass * 512 + bn * 32 + (lane & 3) * 8;
#pragma unroll
              for (int i = 0; i < 4; i++) {
                const float* a = &o[i >> 1][2 * (i & 1)];
                const float inv = rcp(a[16]);
                uint32_t* u = &pk[i >> 1][4 * (i & 1)];
#pragma unroll
                for (int k = 0; k < 4; k++) u[k] = pack2(a[4 * k] * inv, a[4 * k + 1] * inv);
                *(uint4*)(op + ((i >> 1) * 64 + (i & 1) * 8) * 1024) = make_uint4(u[0], u[1], u[2], u[3]);
              }
            }
            sched_fence();
            if (pass == 0) bar_sync(NB_KN + wg, 160);
            const float kmax = *(volatile float*)(smem + ROWST + 4 * pass);
            const bool wide = !(qn[0] + kmax <= 1.4e5f) | !(qn[0] * kmax <= 110.f * 110.f);
            int badm = 0;
#pragma unroll
            for (int m = 0; m < 2; m++) {
              uint32_t chk[2] = {0u, 0u};
#pragma unroll
              for (int i = 0; i < 8; i++) asm("fma.rn.bf16x2 %0, %1, %2, %0;" : "+r"(chk[i & 1]) : "r"(pk[m][i]), "r"(0u));
              const bool bad = wide | !(fminf(o[m][16], o[m][18]) >= 9.3e-10f) | !(o[m][16] + o[m][18] <= 1e36f) | (((chk[0] | chk[1]) & 0x7FFF7FFFu) != 0);
              badm |= __any_sync(~0u, bad) << m;
            }
            if (!badm) bar_arrive(NB_SIG + 2 * pass + wg, 160 + 32 * (pass & wg));
            qn[0] = qn[1];
#pragma unroll
            for (int m = 0; m < 2; m++) {
#pragma unroll
              for (int i = 0; i < 20; i++) o[m][i] = 0.f;
              fence_regs(o[m]);
            }
            if (badm) {
              redo |= badm << 2 * pass;
              const int tx = wg * 128 + w * 32 + lane_id();
              uint4* p = g_qsave + (block_id() * 256 + tx) * 8 + pass * 4;
#pragma unroll
              for (int i = 0; i < 4; i++) {
                uint32_t u[4] = {q[0][i >> 1][4 * (i & 1)], q[0][i >> 1][4 * (i & 1) + 1], q[0][i >> 1][4 * (i & 1) + 2], q[0][i >> 1][4 * (i & 1) + 3]};
                if (pass == 0) lds128(sb + QPARK + tx * 16 + i * 4096, u);
                p[i] = make_uint4(u[0], u[1], u[2], u[3]);
              }
            }
          }
          if (redo) attn_redo(redo, l, cta_id(), wg, w, ep1);
        }
      }
      {
        float acc[64];
        {
          const uint64_t da = l & 1 ? prm.xd + ((pslot_a(0, 1) + wg * 8192) >> 4) : prm.kv[0].kd + ((pslot_a(0, 0) - T0 + wg * 4096) >> 4);
          const uint64_t d2 = da + (l & 1 ? 4 : 512), db = prm.wd + (pslot_b(0) >> 4) - 2048;
          mbar_wait(sb + B_PF, l & 1);
          wg_fence();
          wgmma_m64n128k16_ss_tb_z(acc, da, db, 0);
#pragma unroll
          for (int k = 1; k < 4; k++) wgmma_m64n128k16_ss_tb(acc, (k & 2 ? d2 : da) + (k & 1) * 2, db + k * 128, 1);
          wg_commit();
        }
        uint32_t s = 1, lap = 0;
#pragma unroll 1
        for (int kt = 1; kt < 14; kt++) {
          mbar_wait(sb + B_PF + 8 * s, ((s < 4 ? l : 0) + lap) & 1);
          const uint64_t da = mkdesc(sb + pslot_a(s, l) + wg * 8192, 16, 1024, 1), db = mkdesc(sb + pslot_b(s), 8192, 1024, 1);
          wg_fence();
#pragma unroll
          for (int k = 0; k < 4; k++) wgmma_m64n128k16_ss_tb(acc, da + k * 2, db + k * 128, 1);
          wg_commit();
          wg_wait<1>();
          if (w == 0) e_arrive_both(sb + B_PE + 8 * (s ? s - 1 : 5));
          if (++s == 6) { s = 0; lap++; }
        }
        if (wg) {
          wg_wait<0>();
          if (w == 0) e_arrive_both(sb + B_PE + 8);
#pragma unroll
          for (int t = 2; t < 4; t++) mbar_wait(sb + B_PF + 8 * t, l & 1);
          bar_sync(NB_LAG, 256);
        }
#pragma unroll
        for (int t = 2; t < 4; t++) {
          if (!wg) mbar_wait(sb + B_PF + 8 * t, l & 1);
          const uint64_t da = prm.xd + ((pslot_a(t, l) + wg * 8192) >> 4), db = prm.wd + (pslot_b(t) >> 4) - 2048;
          wg_fence();
#pragma unroll
          for (int k = 0; k < 4; k++) wgmma_m64n128k16_ss_tb(acc, da + k * 2, db + k * 128, 1);
          wg_commit();
        }
        if (!wg) {
          bar_arrive(NB_LAG, 256);
          wg_wait<2>();
          if (w == 0) e_arrive_both(sb + B_PE + 8);
        }
        IDS();
        const int g = lane >> 2, qd = lane & 3;
        const int r0 = wg * 64 + w * 16;
        const uint32_t r = r0 + (lane & 7) + ((lane >> 3) & 1) * 8;
        uint32_t x[8][4];
        mbar_wait(sb + B_RF, 0);
#pragma unroll
        for (int jj = 0; jj < 8; jj++) ldsm4(sb + RES + (jj >> 2) * 16384 + r * 128 + ((((2 * jj + (lane >> 4)) & 7) ^ (r & 7)) << 4), x[jj]);
        wg_wait<0>();
        fence_regs(acc);
        if (w == 0) { e_arrive_both(sb + B_PE + 16); e_arrive_both(sb + B_PE + 24); }
        const CUtensorMap* mo = &prm.m[l == 3 ? M_OUT : M_XST];
        const bool direct = wg && l < 3;
        const uint32_t stg = sb + (direct ? po * 16384 : RES);
        if (direct) bar_sync(NB_SC, 256);
#pragma unroll
        for (int jj = 0; jj < 8; jj++) {
#pragma unroll
          for (int i = 0; i < 4; i++) x[jj][i] = add_bf16x2(x[jj][i], pack2(acc[8 * jj + 2 * i], acc[8 * jj + 2 * i + 1]));
          if (jj < 4) stsm4(stg + r * 128 + ((((2 * jj + (lane >> 4)) & 7) ^ (r & 7)) << 4), x[jj][0], x[jj][1], x[jj][2], x[jj][3]);
          if (jj == 3) { fence_async_smem(); __syncwarp(); tma_st(mo, pn * 128, pm * 128 + r0, stg + r0 * 128); bulk_commit(); sched_fence(); }
        }
        if (l < 3) bar_arrive(NB_KN, 288);
        if (l == 3) {
#pragma unroll
          for (int jj = 4; jj < 8; jj++) stsm4(sb + RES + 16384 + r * 128 + ((((2 * jj + (lane >> 4)) & 7) ^ (r & 7)) << 4), x[jj][0], x[jj][1], x[jj][2], x[jj][3]);
          fence_async_smem(); __syncwarp();
          tma_st(mo, pn * 128 + 64, pm * 128 + r0, sb + RES + 16384 + r0 * 128);
          bulk_commit(); bulk_wait_n<0>();
        } else {
          if (!wg) bar_sync(NB_SC, 256);
#pragma unroll
          for (int jj = 0; jj < 8; jj++)
            if (jj >= 4 || !wg) stsm4(sb + (jj >> 2) * 2 * QSTG + po * 16384 + r * 128 + ((((2 * jj + (lane >> 4)) & 7) ^ (r & 7)) << 4), x[jj][0], x[jj][1], x[jj][2], x[jj][3]);
          bulk_wait_n<0>();
          bar_arrive(NB_X0, 320);
          float s1[4] = {0.f, 0.f, 0.f, 0.f}, sa[4] = {0.f, 0.f, 0.f, 0.f}, sc[4] = {0.f, 0.f, 0.f, 0.f};
#pragma unroll
          for (int jj = 0; jj < 8; jj++) {
            mma16816(s1, x[jj][0], x[jj][1], x[jj][2], x[jj][3], 0x3f803f80u, 0x3f803f80u);
            mma16816(sa, x[jj][0], x[jj][1], x[jj][2], x[jj][3], x[jj][0], x[jj][2]);
            mma16816(sc, x[jj][0], x[jj][1], x[jj][2], x[jj][3], x[jj][1], x[jj][3]);
          }
          fence_regs(s1); fence_regs(sa); fence_regs(sc);
          fence_async_smem();
          sched_fence();
          bar_arrive(NB_X, 320);
          if (qd == g >> 1) {
            float2* p = g_stats + pn * 2048 + pm * 128 + r0 + g;
            p[0] = make_float2(s1[0], g & 1 ? sa[1] : sa[0]);
            p[8] = make_float2(s1[2], g & 1 ? sc[3] : sc[2]);
          }
          bar_arrive(NB_KV, 288);
        }
      }
    }
  }
  asm volatile("barrier.cluster.arrive.relaxed.aligned;\nbarrier.cluster.wait.aligned;" ::: "memory");
}

typedef CUresult (*EncodeFn)(CUtensorMap*, CUtensorMapDataType, cuuint32_t, void*, const cuuint64_t*, const cuuint64_t*, const cuuint32_t*,
                             const cuuint32_t*, CUtensorMapInterleave, CUtensorMapSwizzle, CUtensorMapL2promotion, CUtensorMapFloatOOBfill);

static void make_map(EncodeFn fn, CUtensorMap* m, const void* ptr, int rank, const uint64_t* dims, const uint64_t* strides, const uint32_t* box, CUtensorMapSwizzle sw) {
  cuuint64_t d[5], st[4];
  cuuint32_t bx[5], es[5];
  for (int i = 0; i < rank; i++) { d[i] = dims[i]; bx[i] = box[i]; es[i] = 1; if (i) st[i - 1] = strides[i - 1] * 2; }
  fn(m, CU_TENSOR_MAP_DATA_TYPE_BFLOAT16, rank, (void*)ptr, d, st, bx, es, CU_TENSOR_MAP_INTERLEAVE_NONE, sw,
     CU_TENSOR_MAP_L2_PROMOTION_L2_128B, CU_TENSOR_MAP_FLOAT_OOB_FILL_NONE);
}
static void map2(EncodeFn fn, CUtensorMap* m, const void* ptr, uint64_t inner, uint64_t outer, uint32_t bi, uint32_t bo, CUtensorMapSwizzle sw) {
  const uint64_t d[2] = {inner, outer}, st[1] = {inner};
  const uint32_t bx[2] = {bi, bo};
  make_map(fn, m, ptr, 2, d, st, bx, sw);
}

extern "C" void kernel_launch(void* const* d_in, const int* in_sizes, int n_in, void* d_out, int out_size) {
  (void)in_sizes; (void)n_in; (void)out_size;
  static EncodeFn enc = nullptr;
  static void *xs, *os, *kk, *vv;
  static int sbase = 1024;
  if (!enc) {
    void* p = nullptr;
    cudaDriverEntryPointQueryResult qr;
    cudaGetDriverEntryPoint("cuTensorMapEncodeTiled", &p, cudaEnableDefault, &qr);
    enc = (EncodeFn)p;
    Scratch* sc = nullptr;
    cudaGetSymbolAddress((void**)&sc, g_s);
    xs = sc->xs; os = sc->os; kk = sc->k; vv = sc->v;
    int dev = 0;
    cudaGetDevice(&dev);
    cudaDeviceGetAttribute(&sbase, cudaDevAttrReservedSharedMemoryPerBlock, dev);
    cudaFuncSetAttribute(fused_kernel, cudaFuncAttributeMaxDynamicSharedMemorySize, SMEM_BYTES);
  }
  Params prm;
  const CUtensorMapSwizzle S128 = CU_TENSOR_MAP_SWIZZLE_128B, S64 = CU_TENSOR_MAP_SWIZZLE_64B;
  map2(enc, &prm.m[M_X0A], d_in[0], 1024, 2048, 64, 256, S128);
  for (int t = 0; t < 2; t++) {
    const uint64_t d3[3] = {1024, 1024, 3}, s3[2] = {3072, 1024};
    const uint32_t b3[3] = {64, 64, 3};
    make_map(enc, &prm.m[M_WQA + t], d_in[1 + 3 * t], 3, d3, s3, b3, S128);
    const uint64_t d5[5] = {64, 32, 2, 16, 16}, s5[4] = {1024, 32 * 1024, 64 * 1024, 64};
    const uint32_t b5[5] = {64, 32, 1, 2, 2};
    make_map(enc, &prm.m[M_WOA + t], d_in[2 + 3 * t], 5, d5, s5, b5, S128);
    const uint64_t dr[3] = {64, 2048, 16}, sr[2] = {1024, 64};
    const uint32_t br[3] = {64, 128, 2};
    make_map(enc, &prm.m[M_X0R + t], t ? xs : d_in[0], 3, dr, sr, br, S128);
  }
  map2(enc, &prm.m[M_OS], os, 1024, 2048, 64, 64, S128);
  map2(enc, &prm.m[M_OL], os, 1024, 2048, 32, 128, S64);
  map2(enc, &prm.m[M_K], kk, 32, 65536, 32, 128, S64);
  map2(enc, &prm.m[M_V], vv, 32, 65536, 32, 128, S64);
  map2(enc, &prm.m[M_XSO], xs, 1024, 2048, 64, 128, S128);
  map2(enc, &prm.m[M_X0H], d_in[0], 1024, 2048, 64, 128, S128);
  map2(enc, &prm.m[M_XST], xs, 1024, 2048, 64, 16, S128);
  map2(enc, &prm.m[M_OUT], d_out, 1024, 2048, 64, 16, S128);
  prm.x0 = (const bf16*)d_in[0];
  prm.wq[0] = (const bf16*)d_in[1]; prm.wq[1] = (const bf16*)d_in[4];
  prm.wo = (const bf16*)d_in[2];
  prm.zero = 0;
  for (int i = 0; i < 128; i++) prm.map[i] = remap(i);
  {
    const uint64_t hi = 0x80000020ull << 32, k0 = sbase + T0, v0 = k0 + 16384, vstep = 64 - (64ull << 16);
    prm.wd = mkdesc(sbase + 32768, 8192, 1024, 1); prm.xd = mkdesc(sbase, 16, 1024, 1);
    for (int j = 0; j < 4; j++) {
      prm.kv[j].kd = (hi | 1u << 16 | k0 >> 4) + 2048 * ((j < 16 ? j : 15) & 3);
      prm.kv[j].vd = (hi | (uint64_t)(ONES - T0 - 16384) >> 4 << 16 | v0 >> 4) + 32 * vstep * ((j + 3) & 3);
    }
  }
  fused_kernel<<<128, 384, SMEM_BYTES>>>(prm);
}
```

```cpp
#include <cuda_runtime.h>
#include <cuda_bf16.h>
#include <cuda.h>
#include <stdint.h>

typedef __nv_bfloat16 bf16;

__device__ __forceinline__ void wgmma_m64n192k16_ss_tb(float (&d)[96], uint64_t da, uint64_t db, int scale_d) {
  asm volatile("{\n.reg .pred p;\nsetp.ne.b32 p, %98, 0;\n"
    "wgmma.mma_async.sync.aligned.m64n192k16.f32.bf16.bf16 "
    "{%0, %1, %2, %3, %4, %5, %6, %7, %8, %9, %10, %11, %12, %13, %14, %15, "
    "%16, %17, %18, %19, %20, %21, %22, %23, %24, %25, %26, %27, %28, %29, %30, %31, "
    "%32, %33, %34, %35, %36, %37, %38, %39, %40, %41, %42, %43, %44, %45, %46, %47, "
    "%48, %49, %50, %51, %52, %53, %54, %55, %56, %57, %58, %59, %60, %61, %62, %63, "
    "%64, %65, %66, %67, %68, %69, %70, %71, %72, %73, %74, %75, %76, %77, %78, %79, "
    "%80, %81, %82, %83, %84, %85, %86, %87, %88, %89, %90, %91, %92, %93, %94, %95}, "
    "%96, %97, p, 1, 1, 0, 1;\n}\n"
    : "+f"(d[0]), "+f"(d[1]), "+f"(d[2]), "+f"(d[3]), "+f"(d[4]), "+f"(d[5]), "+f"(d[6]), "+f"(d[7]),
      "+f"(d[8]), "+f"(d[9]), "+f"(d[10]), "+f"(d[11]), "+f"(d[12]), "+f"(d[13]), "+f"(d[14]), "+f"(d[15]),
      "+f"(d[16]), "+f"(d[17]), "+f"(d[18]), "+f"(d[19]), "+f"(d[20]), "+f"(d[21]), "+f"(d[22]), "+f"(d[23]),
      "+f"(d[24]), "+f"(d[25]), "+f"(d[26]), "+f"(d[27]), "+f"(d[28]), "+f"(d[29]), "+f"(d[30]), "+f"(d[31]),
      "+f"(d[32]), "+f"(d[33]), "+f"(d[34]), "+f"(d[35]), "+f"(d[36]), "+f"(d[37]), "+f"(d[38]), "+f"(d[39]),
      "+f"(d[40]), "+f"(d[41]), "+f"(d[42]), "+f"(d[43]), "+f"(d[44]), "+f"(d[45]), "+f"(d[46]), "+f"(d[47]),
      "+f"(d[48]), "+f"(d[49]), "+f"(d[50]), "+f"(d[51]), "+f"(d[52]), "+f"(d[53]), "+f"(d[54]), "+f"(d[55]),
      "+f"(d[56]), "+f"(d[57]), "+f"(d[58]), "+f"(d[59]), "+f"(d[60]), "+f"(d[61]), "+f"(d[62]), "+f"(d[63]),
      "+f"(d[64]), "+f"(d[65]), "+f"(d[66]), "+f"(d[67]), "+f"(d[68]), "+f"(d[69]), "+f"(d[70]), "+f"(d[71]),
      "+f"(d[72]), "+f"(d[73]), "+f"(d[74]), "+f"(d[75]), "+f"(d[76]), "+f"(d[77]), "+f"(d[78]), "+f"(d[79]),
      "+f"(d[80]), "+f"(d[81]), "+f"(d[82]), "+f"(d[83]), "+f"(d[84]), "+f"(d[85]), "+f"(d[86]), "+f"(d[87]),
      "+f"(d[88]), "+f"(d[89]), "+f"(d[90]), "+f"(d[91]), "+f"(d[92]), "+f"(d[93]), "+f"(d[94]), "+f"(d[95])
    : "l"(da), "l"(db), "r"(scale_d));
}

__device__ __forceinline__ void wgmma_m64n192k16_ss_tb_z(float (&d)[96], uint64_t da, uint64_t db, int scale_d) {
  asm volatile("{\n.reg .pred p;\nsetp.ne.b32 p, %98, 0;\n"
    "wgmma.mma_async.sync.aligned.m64n192k16.f32.bf16.bf16 "
    "{%0, %1, %2, %3, %4, %5, %6, %7, %8, %9, %10, %11, %12, %13, %14, %15, "
    "%16, %17, %18, %19, %20, %21, %22, %23, %24, %25, %26, %27, %28, %29, %30, %31, "
    "%32, %33, %34, %35, %36, %37, %38, %39, %40, %41, %42, %43, %44, %45, %46, %47, "
    "%48, %49, %50, %51, %52, %53, %54, %55, %56, %57, %58, %59, %60, %61, %62, %63, "
    "%64, %65, %66, %67, %68, %69, %70, %71, %72, %73, %74, %75, %76, %77, %78, %79, "
    "%80, %81, %82, %83, %84, %85, %86, %87, %88, %89, %90, %91, %92, %93, %94, %95}, "
    "%96, %97, p, 1, 1, 0, 1;\n}\n"
    : "=f"(d[0]), "=f"(d[1]), "=f"(d[2]), "=f"(d[3]), "=f"(d[4]), "=f"(d[5]), "=f"(d[6]), "=f"(d[7]),
      "=f"(d[8]), "=f"(d[9]), "=f"(d[10]), "=f"(d[11]), "=f"(d[12]), "=f"(d[13]), "=f"(d[14]), "=f"(d[15]),
      "=f"(d[16]), "=f"(d[17]), "=f"(d[18]), "=f"(d[19]), "=f"(d[20]), "=f"(d[21]), "=f"(d[22]), "=f"(d[23]),
      "=f"(d[24]), "=f"(d[25]), "=f"(d[26]), "=f"(d[27]), "=f"(d[28]), "=f"(d[29]), "=f"(d[30]), "=f"(d[31]),
      "=f"(d[32]), "=f"(d[33]), "=f"(d[34]), "=f"(d[35]), "=f"(d[36]), "=f"(d[37]), "=f"(d[38]), "=f"(d[39]),
      "=f"(d[40]), "=f"(d[41]), "=f"(d[42]), "=f"(d[43]), "=f"(d[44]), "=f"(d[45]), "=f"(d[46]), "=f"(d[47]),
      "=f"(d[48]), "=f"(d[49]), "=f"(d[50]), "=f"(d[51]), "=f"(d[52]), "=f"(d[53]), "=f"(d[54]), "=f"(d[55]),
      "=f"(d[56]), "=f"(d[57]), "=f"(d[58]), "=f"(d[59]), "=f"(d[60]), "=f"(d[61]), "=f"(d[62]), "=f"(d[63]),
      "=f"(d[64]), "=f"(d[65]), "=f"(d[66]), "=f"(d[67]), "=f"(d[68]), "=f"(d[69]), "=f"(d[70]), "=f"(d[71]),
      "=f"(d[72]), "=f"(d[73]), "=f"(d[74]), "=f"(d[75]), "=f"(d[76]), "=f"(d[77]), "=f"(d[78]), "=f"(d[79]),
      "=f"(d[80]), "=f"(d[81]), "=f"(d[82]), "=f"(d[83]), "=f"(d[84]), "=f"(d[85]), "=f"(d[86]), "=f"(d[87]),
      "=f"(d[88]), "=f"(d[89]), "=f"(d[90]), "=f"(d[91]), "=f"(d[92]), "=f"(d[93]), "=f"(d[94]), "=f"(d[95])
    : "l"(da), "l"(db), "r"(scale_d));
}

__device__ __forceinline__ void wgmma_m64n128k16_ss_tb(float (&d)[64], uint64_t da, uint64_t db, int scale_d) {
  asm volatile("{\n.reg .pred p;\nsetp.ne.b32 p, %66, 0;\n"
    "wgmma.mma_async.sync.aligned.m64n128k16.f32.bf16.bf16 "
    "{%0, %1, %2, %3, %4, %5, %6, %7, %8, %9, %10, %11, %12, %13, %14, %15, "
    "%16, %17, %18, %19, %20, %21, %22, %23, %24, %25, %26, %27, %28, %29, %30, %31, "
    "%32, %33, %34, %35, %36, %37, %38, %39, %40, %41, %42, %43, %44, %45, %46, %47, "
    "%48, %49, %50, %51, %52, %53, %54, %55, %56, %57, %58, %59, %60, %61, %62, %63}, "
    "%64, %65, p, 1, 1, 0, 1;\n}\n"
    : "+f"(d[0]), "+f"(d[1]), "+f"(d[2]), "+f"(d[3]), "+f"(d[4]), "+f"(d[5]), "+f"(d[6]), "+f"(d[7]),
      "+f"(d[8]), "+f"(d[9]), "+f"(d[10]), "+f"(d[11]), "+f"(d[12]), "+f"(d[13]), "+f"(d[14]), "+f"(d[15]),
      "+f"(d[16]), "+f"(d[17]), "+f"(d[18]), "+f"(d[19]), "+f"(d[20]), "+f"(d[21]), "+f"(d[22]), "+f"(d[23]),
      "+f"(d[24]), "+f"(d[25]), "+f"(d[26]), "+f"(d[27]), "+f"(d[28]), "+f"(d[29]), "+f"(d[30]), "+f"(d[31]),
      "+f"(d[32]), "+f"(d[33]), "+f"(d[34]), "+f"(d[35]), "+f"(d[36]), "+f"(d[37]), "+f"(d[38]), "+f"(d[39]),
      "+f"(d[40]), "+f"(d[41]), "+f"(d[42]), "+f"(d[43]), "+f"(d[44]), "+f"(d[45]), "+f"(d[46]), "+f"(d[47]),
      "+f"(d[48]), "+f"(d[49]), "+f"(d[50]), "+f"(d[51]), "+f"(d[52]), "+f"(d[53]), "+f"(d[54]), "+f"(d[55]),
      "+f"(d[56]), "+f"(d[57]), "+f"(d[58]), "+f"(d[59]), "+f"(d[60]), "+f"(d[61]), "+f"(d[62]), "+f"(d[63])
    : "l"(da), "l"(db), "r"(scale_d));
}

__device__ __forceinline__ void wgmma_m64n128k16_ss_tb_z(float (&d)[64], uint64_t da, uint64_t db, int scale_d) {
  asm volatile("{\n.reg .pred p;\nsetp.ne.b32 p, %66, 0;\n"
    "wgmma.mma_async.sync.aligned.m64n128k16.f32.bf16.bf16 "
    "{%0, %1, %2, %3, %4, %5, %6, %7, %8, %9, %10, %11, %12, %13, %14, %15, "
    "%16, %17, %18, %19, %20, %21, %22, %23, %24, %25, %26, %27, %28, %29, %30, %31, "
    "%32, %33, %34, %35, %36, %37, %38, %39, %40, %41, %42, %43, %44, %45, %46, %47, "
    "%48, %49, %50, %51, %52, %53, %54, %55, %56, %57, %58, %59, %60, %61, %62, %63}, "
    "%64, %65, p, 1, 1, 0, 1;\n}\n"
    : "=f"(d[0]), "=f"(d[1]), "=f"(d[2]), "=f"(d[3]), "=f"(d[4]), "=f"(d[5]), "=f"(d[6]), "=f"(d[7]),
      "=f"(d[8]), "=f"(d[9]), "=f"(d[10]), "=f"(d[11]), "=f"(d[12]), "=f"(d[13]), "=f"(d[14]), "=f"(d[15]),
      "=f"(d[16]), "=f"(d[17]), "=f"(d[18]), "=f"(d[19]), "=f"(d[20]), "=f"(d[21]), "=f"(d[22]), "=f"(d[23]),
      "=f"(d[24]), "=f"(d[25]), "=f"(d[26]), "=f"(d[27]), "=f"(d[28]), "=f"(d[29]), "=f"(d[30]), "=f"(d[31]),
      "=f"(d[32]), "=f"(d[33]), "=f"(d[34]), "=f"(d[35]), "=f"(d[36]), "=f"(d[37]), "=f"(d[38]), "=f"(d[39]),
      "=f"(d[40]), "=f"(d[41]), "=f"(d[42]), "=f"(d[43]), "=f"(d[44]), "=f"(d[45]), "=f"(d[46]), "=f"(d[47]),
      "=f"(d[48]), "=f"(d[49]), "=f"(d[50]), "=f"(d[51]), "=f"(d[52]), "=f"(d[53]), "=f"(d[54]), "=f"(d[55]),
      "=f"(d[56]), "=f"(d[57]), "=f"(d[58]), "=f"(d[59]), "=f"(d[60]), "=f"(d[61]), "=f"(d[62]), "=f"(d[63])
    : "l"(da), "l"(db), "r"(scale_d));
}

__device__ __forceinline__ void wgmma_m64n40k16_rs_tb(float (&d)[20], uint32_t a0, uint32_t a1, uint32_t a2, uint32_t a3, uint64_t db, int scale_d) {
  asm volatile("{\n.reg .pred p;\nsetp.ne.b32 p, %25, 0;\n"
    "wgmma.mma_async.sync.aligned.m64n40k16.f32.bf16.bf16 "
    "{%0, %1, %2, %3, %4, %5, %6, %7, %8, %9, %10, %11, %12, %13, %14, %15, "
    "%16, %17, %18, %19}, "
    "{%20, %21, %22, %23}, %24, p, 1, 1, 1;\n}\n"
    : "+f"(d[0]), "+f"(d[1]), "+f"(d[2]), "+f"(d[3]), "+f"(d[4]), "+f"(d[5]), "+f"(d[6]), "+f"(d[7]),
      "+f"(d[8]), "+f"(d[9]), "+f"(d[10]), "+f"(d[11]), "+f"(d[12]), "+f"(d[13]), "+f"(d[14]), "+f"(d[15]),
      "+f"(d[16]), "+f"(d[17]), "+f"(d[18]), "+f"(d[19])
    : "r"(a0), "r"(a1), "r"(a2), "r"(a3), "l"(db), "r"(scale_d));
}

__device__ __forceinline__ void wg_n64_rs_nb_f16_f32(float (&d)[32], uint32_t a0, uint32_t a1, uint32_t a2, uint32_t a3, uint64_t db, int scale_d) {
  asm volatile("{\n.reg .pred p;\nsetp.ne.b32 p, %37, 0;\n"
    "wgmma.mma_async.sync.aligned.m64n64k16.f32.f16.f16 "
    "{%0, %1, %2, %3, %4, %5, %6, %7, %8, %9, %10, %11, %12, %13, %14, %15, "
    "%16, %17, %18, %19, %20, %21, %22, %23, %24, %25, %26, %27, %28, %29, %30, %31}, "
    "{%32, %33, %34, %35}, %36, p, 1, 1, 0;\n}\n"
    : "+f"(d[0]), "+f"(d[1]), "+f"(d[2]), "+f"(d[3]), "+f"(d[4]), "+f"(d[5]), "+f"(d[6]), "+f"(d[7]),
      "+f"(d[8]), "+f"(d[9]), "+f"(d[10]), "+f"(d[11]), "+f"(d[12]), "+f"(d[13]), "+f"(d[14]), "+f"(d[15]),
      "+f"(d[16]), "+f"(d[17]), "+f"(d[18]), "+f"(d[19]), "+f"(d[20]), "+f"(d[21]), "+f"(d[22]), "+f"(d[23]),
      "+f"(d[24]), "+f"(d[25]), "+f"(d[26]), "+f"(d[27]), "+f"(d[28]), "+f"(d[29]), "+f"(d[30]), "+f"(d[31])
    : "r"(a0), "r"(a1), "r"(a2), "r"(a3), "l"(db), "r"(scale_d));
}

__device__ __forceinline__ void wg_n64_rs_nb_f16_f16(uint32_t (&d)[16], uint32_t a0, uint32_t a1, uint32_t a2, uint32_t a3, uint64_t db, int scale_d) {
  asm volatile("{\n.reg .pred p;\nsetp.ne.b32 p, %21, 0;\n"
    "wgmma.mma_async.sync.aligned.m64n64k16.f16.f16.f16 "
    "{%0, %1, %2, %3, %4, %5, %6, %7, %8, %9, %10, %11, %12, %13, %14, %15}, "
    "{%16, %17, %18, %19}, %20, p, 1, 1, 0;\n}\n"
    : "+r"(d[0]), "+r"(d[1]), "+r"(d[2]), "+r"(d[3]), "+r"(d[4]), "+r"(d[5]), "+r"(d[6]), "+r"(d[7]),
      "+r"(d[8]), "+r"(d[9]), "+r"(d[10]), "+r"(d[11]), "+r"(d[12]), "+r"(d[13]), "+r"(d[14]), "+r"(d[15])
    : "r"(a0), "r"(a1), "r"(a2), "r"(a3), "l"(db), "r"(scale_d));
}

__device__ __forceinline__ void wg_n64_rs_nb_f16_f32_z(float (&d)[32], uint32_t a0, uint32_t a1, uint32_t a2, uint32_t a3, uint64_t db, int scale_d) {
  asm volatile("{\n.reg .pred p;\nsetp.ne.b32 p, %37, 0;\n"
    "wgmma.mma_async.sync.aligned.m64n64k16.f32.f16.f16 "
    "{%0, %1, %2, %3, %4, %5, %6, %7, %8, %9, %10, %11, %12, %13, %14, %15, "
    "%16, %17, %18, %19, %20, %21, %22, %23, %24, %25, %26, %27, %28, %29, %30, %31}, "
    "{%32, %33, %34, %35}, %36, p, 1, 1, 0;\n}\n"
    : "=f"(d[0]), "=f"(d[1]), "=f"(d[2]), "=f"(d[3]), "=f"(d[4]), "=f"(d[5]), "=f"(d[6]), "=f"(d[7]),
      "=f"(d[8]), "=f"(d[9]), "=f"(d[10]), "=f"(d[11]), "=f"(d[12]), "=f"(d[13]), "=f"(d[14]), "=f"(d[15]),
      "=f"(d[16]), "=f"(d[17]), "=f"(d[18]), "=f"(d[19]), "=f"(d[20]), "=f"(d[21]), "=f"(d[22]), "=f"(d[23]),
      "=f"(d[24]), "=f"(d[25]), "=f"(d[26]), "=f"(d[27]), "=f"(d[28]), "=f"(d[29]), "=f"(d[30]), "=f"(d[31])
    : "r"(a0), "r"(a1), "r"(a2), "r"(a3), "l"(db), "r"(scale_d));
}

__device__ __forceinline__ void wg_n64_rs_nb_f16_f16_z(uint32_t (&d)[16], uint32_t a0, uint32_t a1, uint32_t a2, uint32_t a3, uint64_t db, int scale_d) {
  asm volatile("{\n.reg .pred p;\nsetp.ne.b32 p, %21, 0;\n"
    "wgmma.mma_async.sync.aligned.m64n64k16.f16.f16.f16 "
    "{%0, %1, %2, %3, %4, %5, %6, %7, %8, %9, %10, %11, %12, %13, %14, %15}, "
    "{%16, %17, %18, %19}, %20, p, 1, 1, 0;\n}\n"
    : "=r"(d[0]), "=r"(d[1]), "=r"(d[2]), "=r"(d[3]), "=r"(d[4]), "=r"(d[5]), "=r"(d[6]), "=r"(d[7]),
      "=r"(d[8]), "=r"(d[9]), "=r"(d[10]), "=r"(d[11]), "=r"(d[12]), "=r"(d[13]), "=r"(d[14]), "=r"(d[15])
    : "r"(a0), "r"(a1), "r"(a2), "r"(a3), "l"(db), "r"(scale_d));
}

#define DEVINL __device__ __forceinline__
DEVINL void wg_fence() { asm volatile("wgmma.fence.sync.aligned;" ::: "memory"); }
DEVINL void wg_commit() { asm volatile("wgmma.commit_group.sync.aligned;" ::: "memory"); }
template <int N> DEVINL void wg_wait() { asm volatile("wgmma.wait_group.sync.aligned %0;" ::"n"(N) : "memory"); }
__host__ DEVINL uint64_t mkdesc(uint32_t addr, uint32_t lbo, uint32_t sbo, int sw) {
  return (uint64_t)((addr & 0x3FFFF) >> 4) | ((uint64_t)(lbo >> 4) << 16) | ((uint64_t)(sbo >> 4) << 32) | ((uint64_t)sw << 62);
}
DEVINL bool mbar_try(uint32_t bar, uint32_t parity) {
  uint32_t ok;
  asm volatile("{\n.reg .pred p;\nmbarrier.try_wait.parity.shared::cta.b64 p, [%1], %2;\nselp.u32 %0, 1, 0, p;\n}" : "=r"(ok) : "r"(bar), "r"(parity) : "memory");
  return ok;
}
DEVINL bool mbar_test(uint32_t bar, uint32_t parity) {
  uint32_t ok;
  asm volatile("{\n.reg .pred p;\nmbarrier.test_wait.parity.shared::cta.b64 p, [%1], %2;\nselp.u32 %0, 1, 0, p;\n}" : "=r"(ok) : "r"(bar), "r"(parity) : "memory");
  return ok;
}
DEVINL void mbar_hint(uint32_t bar, uint32_t parity) {
#pragma unroll 1
  for (uint32_t n = 0; n < 32u; n++) if (mbar_try(bar, parity)) break;
}
DEVINL void mbar_wait(uint32_t bar, uint32_t parity) {
#pragma unroll 1
  for (uint32_t n = 0; n < 100000u; n++) if (mbar_try(bar, parity)) break;
}
#define EL(txt) "{\n.reg .pred pe;\nelect.sync _|pe, 0xffffffff;\n@pe " txt "\n}"
DEVINL void e_expect_tx(uint32_t bar, uint32_t bytes) { asm volatile(EL("mbarrier.arrive.expect_tx.shared::cta.b64 _, [%0], %1;") ::"r"(bar), "r"(bytes) : "memory"); }
DEVINL void e_arrive(uint32_t bar) { asm volatile(EL("mbarrier.arrive.shared::cta.b64 _, [%0];") ::"r"(bar) : "memory"); }
DEVINL void e_arrive_if(uint32_t bar, int c) {
  asm volatile("{\n.reg .pred pe;\nelect.sync _|pe, 0xffffffff;\nsetp.ne.and.b32 pe, %1, 0, pe;\n@pe mbarrier.arrive.shared::cta.b64 _, [%0];\n}" ::"r"(bar), "r"(c) : "memory");
}
DEVINL void e_red(uint32_t* p) { asm volatile(EL("red.release.gpu.global.add.u32 [%0], 1;") ::"l"(p) : "memory"); }
DEVINL void e_red_relaxed(uint32_t* p) { asm volatile(EL("red.relaxed.gpu.global.add.u32 [%0], 1;") ::"l"(p) : "memory"); }
DEVINL void release_add(uint32_t* p, int on) {
  asm volatile("{\n.reg .pred q;\nsetp.ne.b32 q, %1, 0;\nfence.release.gpu;\n@q red.relaxed.gpu.global.add.u32 [%0], 1;\n}" ::"l"(p), "r"(on) : "memory");
}
#define PREPARED(p, on) do { asm volatile("" : "+l"(p), "+r"(on)); asm volatile("griddepcontrol.launch_dependents;" ::: "memory"); } while (0)
DEVINL void tma_ld(uint32_t dst, const CUtensorMap* m, int c0, int c1, uint32_t bar) {
  asm volatile(EL("cp.async.bulk.tensor.2d.shared::cluster.global.mbarrier::complete_tx::bytes [%0], [%1, {%3, %4}], [%2];")
               ::"r"(dst), "l"(m), "r"(bar), "r"(c0), "r"(c1) : "memory");
}
DEVINL void tma_ld3(uint32_t dst, const CUtensorMap* m, int c0, int c1, int c2, uint32_t bar) {
  asm volatile(EL("cp.async.bulk.tensor.3d.shared::cluster.global.mbarrier::complete_tx::bytes [%0], [%1, {%3, %4, %5}], [%2];")
               ::"r"(dst), "l"(m), "r"(bar), "r"(c0), "r"(c1), "r"(c2) : "memory");
}
DEVINL void tma_ld5(uint32_t dst, const CUtensorMap* m, int c2, int c3, int c4, uint32_t bar) {
  asm volatile(EL("cp.async.bulk.tensor.5d.shared::cluster.global.mbarrier::complete_tx::bytes [%0], [%1, {0, 0, %3, %4, %5}], [%2];")
               ::"r"(dst), "l"(m), "r"(bar), "r"(c2), "r"(c3), "r"(c4) : "memory");
}
DEVINL void tma_ld_mc(uint32_t dst, const CUtensorMap* m, int c0, int c1, uint32_t bar, uint16_t mask = 3) {
  asm volatile(EL("cp.async.bulk.tensor.2d.shared::cluster.global.mbarrier::complete_tx::bytes.multicast::cluster [%0], [%1, {%3, %4}], [%2], %5;")
               ::"r"(dst), "l"(m), "r"(bar), "r"(c0), "r"(c1), "h"(mask) : "memory");
}
DEVINL void e_arrive_both(uint32_t bar) {
  asm volatile("{\n.reg .pred pe;\n.reg .b32 r0, r1;\nelect.sync _|pe, 0xffffffff;\nmapa.shared::cluster.u32 r0, %0, 0;\nmapa.shared::cluster.u32 r1, %0, 1;\n"
               "@pe mbarrier.arrive.shared::cluster.b64 _, [r0];\n@pe mbarrier.arrive.shared::cluster.b64 _, [r1];\n}" ::"r"(bar) : "memory");
}
DEVINL void tma_st(const CUtensorMap* m, int c0, int c1, uint32_t src) {
  asm volatile(EL("cp.async.bulk.tensor.2d.global.shared::cta.bulk_group [%0, {%2, %3}], [%1];") ::"l"(m), "r"(src), "r"(c0), "r"(c1) : "memory");
}
DEVINL void bulk_commit() { asm volatile("cp.async.bulk.commit_group;" ::: "memory"); }
template <int N> DEVINL void bulk_wait_n() { asm volatile("cp.async.bulk.wait_group %0;\nbar.warp.sync 0xffffffff;" ::"n"(N) : "memory"); }
DEVINL void l2_prefetch(const void* g, uint32_t bytes) { asm volatile(EL("cp.async.bulk.prefetch.L2.global [%0], %1;") ::"l"(g), "r"(bytes) : "memory"); }
DEVINL void fence_async_smem() { asm volatile("fence.proxy.async.shared::cta;" ::: "memory"); }
DEVINL void fence_async_gl() { asm volatile("fence.proxy.async.global;" ::: "memory"); }
DEVINL void cluster_wait() { asm volatile("barrier.cluster.wait.aligned;" ::: "memory"); }
DEVINL void bar_sync(int id, int n) { asm volatile("bar.sync %0, %1;" ::"r"(id), "r"(n) : "memory"); }
DEVINL void bar_arrive(int id, int n) { asm volatile("bar.arrive %0, %1;" ::"r"(id), "r"(n) : "memory"); }
DEVINL uint32_t ld_acquire(const uint32_t* p) { uint32_t v; asm volatile("ld.acquire.gpu.global.u32 %0, [%1];" : "=r"(v) : "l"(p) : "memory"); return v; }
DEVINL void await_flag(int j, uint32_t& rdy, const uint32_t* p, uint32_t target) {
  if ((rdy >> j) & 1) return;
#pragma unroll 1
  for (uint32_t n = 0; n < 200000u && !((rdy >> j) & 1); n++) rdy = __ballot_sync(~0u, (int)(ld_acquire(p) - target) >= 0);
  asm volatile("fence.proxy.async.global;" ::: "memory");
}
DEVINL void poll_ge(const uint32_t* p, uint32_t target) {
#pragma unroll 1
  for (uint32_t n = 0; n < 200000u; n++) if (__all_sync(~0u, (int)(ld_acquire(p) - target) >= 0)) break;
}
DEVINL int lane_id() { int v; asm volatile("mov.u32 %0, %%laneid;" : "=r"(v)); return v; }
__host__ DEVINL int remap(int v) {
  const int c = v >> 1, u = c - 36, r = (u * 37) >> 8;
  const int L = c < 4 ? 32 + 8 * c : c < 36 ? c - 4 : 33 + u + r;
  return 2 * L + (v & 1);
}
DEVINL int block_id() { int v; asm volatile("mov.u32 %0, %%ctaid.x;" : "=r"(v)); return v; }
#define cta_id() prm.map[block_id()]
#define IDS() const int lane = lane_id(), b = cta_id(), bm = b >> 4, bn = b & 15, rank = b & 1, pm = 2 * bm + (bn >> 3), pn = bn & 7, po = pm & 1; \
  (void)lane; (void)bm; (void)bn; (void)rank; (void)pm; (void)pn; (void)po
DEVINL void st_tagged(uint4* p, uint32_t a, uint32_t b, uint32_t c, uint32_t tag) {
  asm volatile("{\n.reg .b64 u, v;\n.reg .b128 t;\nmov.b64 u, {%1, %2};\nmov.b64 v, {%3, %4};\nmov.b128 t, {u, v};\nst.relaxed.gpu.global.b128 [%0], t;\n}"
               ::"l"(p), "r"(a), "r"(b), "r"(c), "r"(tag) : "memory");
}
DEVINL uint32_t ld_tagged(const uint4* p, uint32_t* r) {
  uint32_t tag;
  asm volatile("{\n.reg .b64 u, v;\n.reg .b128 t;\nld.relaxed.gpu.global.b128 t, [%4];\nmov.b128 {u, v}, t;\nmov.b64 {%0, %1}, u;\nmov.b64 {%2, %3}, v;\n}"
               : "=r"(r[0]), "=r"(r[1]), "=r"(r[2]), "=r"(tag) : "l"(p) : "memory");
  return tag;
}
DEVINL float ex2(float x) { float y; asm("ex2.approx.ftz.f32 %0, %1;" : "=f"(y) : "f"(x)); return y; }
DEVINL float rcp(float x) { float y; asm("rcp.approx.ftz.f32 %0, %1;" : "=f"(y) : "f"(x)); return y; }
DEVINL uint32_t pack2(float lo, float hi) { uint32_t r; asm("cvt.rn.bf16x2.f32 %0, %1, %2;" : "=r"(r) : "f"(hi), "f"(lo)); return r; }
DEVINL uint32_t pack2h(float lo, float hi) { uint32_t r; asm("cvt.rz.f16x2.f32 %0, %1, %2;" : "=r"(r) : "f"(hi), "f"(lo)); return r; }
DEVINL uint32_t prmt0(uint32_t a, uint32_t sel) { uint32_t r; asm("prmt.b32 %0, %1, 0, %2;" : "=r"(r) : "r"(a), "r"(sel)); return r; }
DEVINL void stg128(const void* p, uint32_t a, uint32_t b, uint32_t c, uint32_t d) {
  asm volatile("st.global.v4.b32 [%0], {%1, %2, %3, %4};" ::"l"(p), "r"(a), "r"(b), "r"(c), "r"(d) : "memory");
}
DEVINL uint32_t hadd2(uint32_t a, uint32_t b) { uint32_t r; asm("add.rn.f16x2 %0, %1, %2;" : "=r"(r) : "r"(a), "r"(b)); return r; }
DEVINL uint32_t hfma2(uint32_t a, uint32_t b, uint32_t c) { uint32_t r; asm("fma.rn.f16x2 %0, %1, %2, %3;" : "=r"(r) : "r"(a), "r"(b), "r"(c)); return r; }
DEVINL float bf_lo(uint32_t w) { return __uint_as_float(w << 16); }
DEVINL float bf_hi(uint32_t w) { return __uint_as_float(w & 0xFFFF0000u); }
DEVINL float bf_round(float x) { return bf_lo(pack2(x, 0.f)); }
DEVINL uint32_t add_bf16x2(uint32_t a, uint32_t b) { uint32_t r; asm("add.rn.bf16x2 %0, %1, %2;" : "=r"(r) : "r"(a), "r"(b)); return r; }
DEVINL void stsm4(uint32_t addr, uint32_t a, uint32_t b, uint32_t c, uint32_t d) {
  asm volatile("stmatrix.sync.aligned.m8n8.x4.shared.b16 [%0], {%1, %2, %3, %4};" ::"r"(addr), "r"(a), "r"(b), "r"(c), "r"(d) : "memory");
}
DEVINL void ldsm4(uint32_t addr, uint32_t (&r)[4]) {
  asm volatile("ldmatrix.sync.aligned.m8n8.x4.shared.b16 {%0, %1, %2, %3}, [%4];" : "=r"(r[0]), "=r"(r[1]), "=r"(r[2]), "=r"(r[3]) : "r"(addr) : "memory");
}
DEVINL void ldsm4t(uint32_t addr, uint32_t (&r)[4]) {
  asm volatile("ldmatrix.sync.aligned.m8n8.x4.trans.shared.b16 {%0, %1, %2, %3}, [%4];" : "=r"(r[0]), "=r"(r[1]), "=r"(r[2]), "=r"(r[3]) : "r"(addr) : "memory");
}
DEVINL void sts128(uint32_t addr, uint32_t a, uint32_t b, uint32_t c, uint32_t d) {
  asm volatile("st.shared.v4.b32 [%0], {%1, %2, %3, %4};" ::"r"(addr), "r"(a), "r"(b), "r"(c), "r"(d) : "memory");
}
DEVINL float2 lds64f(uint32_t addr) { float2 v; asm volatile("ld.shared.v2.f32 {%0, %1}, [%2];" : "=f"(v.x), "=f"(v.y) : "r"(addr) : "memory"); return v; }
DEVINL void mma16816(float (&d)[4], uint32_t a0, uint32_t a1, uint32_t a2, uint32_t a3, uint32_t b0, uint32_t b1) {
  asm("mma.sync.aligned.m16n8k16.row.col.f32.bf16.bf16.f32 {%0, %1, %2, %3}, {%4, %5, %6, %7}, {%8, %9}, {%0, %1, %2, %3};"
               : "+f"(d[0]), "+f"(d[1]), "+f"(d[2]), "+f"(d[3]) : "r"(a0), "r"(a1), "r"(a2), "r"(a3), "r"(b0), "r"(b1));
}
template <int N> DEVINL void fence_regs(float (&d)[N]) {
#pragma unroll
  for (int i = 0; i < N; i++) asm volatile("" : "+f"(d[i])::"memory");
}
template <int N> DEVINL void fence_regs(uint32_t (&d)[N]) {
#pragma unroll
  for (int i = 0; i < N; i++) asm volatile("" : "+r"(d[i])::"memory");
}
DEVINL void lds128(uint32_t addr, uint32_t* r) {
  asm volatile("ld.shared.v4.b32 {%0, %1, %2, %3}, [%4];" : "=r"(r[0]), "=r"(r[1]), "=r"(r[2]), "=r"(r[3]) : "r"(addr) : "memory");
}
DEVINL void sched_fence() { asm volatile("griddepcontrol.launch_dependents;" ::: "memory"); }

struct Scratch {
  bf16 k[32 * 2048 * 32];
  bf16 xs[2048 * 1024];
  bf16 os[2048 * 1024];
  bf16 v[32 * 2048 * 32];
  float kn[2 * 128 * 16];
  uint32_t cnt[256 * 32];
  float2 stats[8 * 2048];
  uint4 halo[128 * 12 * 32];
  float csp[2 * 16 * 8 * 192];
  uint4 qsave[128 * 256 * 8];
  uint32_t esc[4 * 65536 * 20];
};
__device__ __align__(1024) Scratch g_s;
#define g_k g_s.k
#define g_xs g_s.xs
#define g_os g_s.os
#define g_v g_s.v
#define g_kn g_s.kn
#define g_cnt g_s.cnt
#define g_stats g_s.stats
#define g_halo g_s.halo
#define g_csp g_s.csp
#define g_qsave g_s.qsave
#define g_esc g_s.esc
#define g_epoch g_s.cnt[255 * 32]

DEVINL uint32_t* cnt_x(int bm) { return g_cnt + bm * 32; }
DEVINL uint32_t* cnt_o(int l, int pm, int h) { return g_cnt + (32 + (l * 16 + pm) * 2 + h) * 32; }
DEVINL uint32_t* cnt_kv(int lb, int bn) { return g_cnt + (160 + lb * 16 + bn) * 32; }
DEVINL uint32_t* cnt_ad(int bn) { return g_cnt + (192 + bn) * 32; }
DEVINL uint32_t* cnt_cs(int t, int bn) { return g_cnt + (208 + t * 16 + bn) * 32; }

DEVINL int qord(int i, int l, int pn) {
  const int u = i < 10 ? i - 4 : i - 10;
  return l == 0 ? i : i < 4 ? ((2 * pn) ^ (2 * (i & 1))) + (i >> 1) : 2 * (u < (pn & 6) ? u : u + 2) + (i >= 10);
}
struct Params {
  CUtensorMap m[15];
  const bf16* x0;
  const bf16* wq[2];
  const bf16* wo;
  uint32_t zero;
  int map[128];
  uint64_t wd, xd;
  struct __align__(16) { uint64_t kd, vd; } kv[4];
};
enum { M_X0A = 0, M_WQA, M_WQB, M_WOA, M_WOB, M_OS, M_K, M_V, M_X0R, M_XSR, M_XSO, M_OUT, M_XST, M_X0H, M_OL, M_COUNT };

constexpr uint32_t QSTG = 57344;
constexpr uint32_t T0 = 65536, TSTG = 32768;
constexpr uint32_t ONES = 230400;
constexpr uint32_t PSTG = 32768, RES = 196608;
constexpr uint32_t KSC = 98304, VSC = 133120, HRS = 167936;
constexpr uint32_t ROWST = 229376, COLS = 231424, BARS = 232192, SMEM_BYTES = 232448;
constexpr uint32_t B_QF = BARS, B_QE = BARS + 32, B_TF = BARS + 64, B_TE = BARS + 96, B_PF = BARS + 128, B_PE = BARS + 176,
                   B_RF = BARS + 224, W_X = BARS + 232, B_QL = BARS + 240, B_PA = BARS + 248;
enum { NB_LAG = 0, NB_ST = 1, NB_KV = 2  , NB_DONE = 3, NB_SC = 4, NB_SIG = 5  , NB_KN = 9  , NB_X = 11, NB_HALO = 12  , NB_X0 = 15 };

DEVINL uint32_t pslot_b(uint32_t s) { return ((0x320415u >> (4 * s)) & 7) * 16384u; }
DEVINL uint32_t pslot_a(uint32_t s, int l) { return 98304u + ((((l & 1) ? 0x541230u : 0x041235u) >> (4 * s)) & 7) * 16384u; }

constexpr float QSCALE = 0.17677669529663687f * 1.4426950408889634f;
constexpr uint32_t QPARK = 32768;

DEVINL uint32_t exp2_h2(uint32_t s, uint32_t c852) {
  uint32_t r, t, w, m, d;
  asm volatile("{.reg .b64 t; add.rn.f16x2 %0, %1, %2; cvt.u64.u32 t, %0; cvt.u32.u64 %0, t;}" : "=r"(r) : "r"(s), "r"(0x65EA65EAu));
  asm volatile("fma.rn.f16x2 %0, %1, %2, %3;" : "=r"(t) : "r"(r), "r"(0xB880B880u), "r"(c852));
  asm volatile("fma.rn.f16x2 %0, %1, %2, %3;" : "=r"(w) : "r"(s), "r"(0x38803880u), "r"(t));
  asm volatile("fma.rn.f16x2 %0, %1, %1, %2;" : "=r"(m) : "r"(w), "r"(0x4A1F4A2Du));
  asm volatile("{.reg .b32 t; shf.l.clamp.b32 t, %2, %1, 7; add.u32 %0, t, %2;}" : "=r"(d) : "r"(r), "r"(m));
  return d;
}
DEVINL float exp2_fix(float s) { float z; asm volatile("add.rn.f32 %0, %1, 0f43BF34BC;" : "=f"(z) : "f"(s)); return z; }
DEVINL uint32_t exp2_base(float z0, float z1) { uint32_t B; asm volatile("prmt.b32 %0, %1, %2, 0x6521;" : "=r"(B) : "r"(__float_as_uint(z0)), "r"(__float_as_uint(z1))); return B; }
template <uint32_t MASK> DEVINL uint32_t and_or(uint32_t a, uint32_t c) { uint32_t r; asm volatile("lop3.b32 %0, %1, %3, %2, 0xEA;" : "=r"(r) : "r"(a), "r"(c), "n"(MASK)); return r; }
DEVINL uint32_t fma_bf2(uint32_t a, uint32_t b, uint32_t c) { uint32_t r; asm volatile("fma.rn.bf16x2 %0, %1, %2, %3;" : "=r"(r) : "r"(a), "r"(b), "r"(c)); return r; }
DEVINL float ex2v(float x) { float y; asm volatile("ex2.approx.ftz.f32 %0, %1;" : "=f"(y) : "f"(x)); return y; }
DEVINL uint32_t pack2v(float lo, float hi) { uint32_t r; asm volatile("cvt.rn.bf16x2.f32 %0, %1, %2;" : "=r"(r) : "f"(hi), "f"(lo)); return r; }
DEVINL void unesc(uint32_t (&u)[4], const uint32_t* esc, uint32_t tag) {
  const bool saved = __ldcg(esc + 16) == tag;
#pragma unroll
  for (int j = 0; j < 4; j++) {
    float lo, hi;
    asm("{.reg .f16 a, b; mov.b32 {a, b}, %2; cvt.f32.f16 %0, a; cvt.f32.f16 %1, b;}" : "=f"(lo), "=f"(hi) : "r"(u[j]));
    u[j] = saved ? __ldcg(esc + 4 * j) : pack2(lo, hi);
  }
}

DEVINL void attn_slow(const uint32_t (&q)[8], int head, const uint32_t* kesc, uint32_t tag, float (&res)[20], int lane) {
  const int g = lane >> 2, qd = lane & 3;
  const bf16* kb = g_k + (size_t)head * 2048 * 32;
  const bf16* vb = g_v + (size_t)head * 2048 * 32;
  float o[4][4], m0 = -INFINITY, m1 = -INFINITY, l0 = 0.f, l1 = 0.f;
#pragma unroll
  for (int j = 0; j < 4; j++) { o[j][0] = o[j][1] = o[j][2] = o[j][3] = 0.f; }
#pragma unroll 1
  for (int k0 = 0; k0 < 2048; k0 += 16) {
    float s[2][4];
#pragma unroll
    for (int nt = 0; nt < 2; nt++) {
      s[nt][0] = s[nt][1] = s[nt][2] = s[nt][3] = 0.f;
      const uint32_t* kp = (const uint32_t*)(kb + (size_t)(k0 + nt * 8 + g) * 32) + qd;
      uint32_t k[4] = {__ldcg(kp), __ldcg(kp + 4), __ldcg(kp + 8), __ldcg(kp + 12)};
      unesc(k, kesc + (k0 + nt * 8 + g) * 20 + qd, tag);
      __syncwarp();
      mma16816(s[nt], q[0], q[1], q[2], q[3], k[0], k[1]);
      mma16816(s[nt], q[4], q[5], q[6], q[7], k[2], k[3]);
    }
    float a0 = fmaxf(fmaxf(s[0][0], s[0][1]), fmaxf(s[1][0], s[1][1]));
    float a1 = fmaxf(fmaxf(s[0][2], s[0][3]), fmaxf(s[1][2], s[1][3]));
    a0 = fmaxf(a0, __shfl_xor_sync(~0u, a0, 1)); a0 = fmaxf(a0, __shfl_xor_sync(~0u, a0, 2));
    a1 = fmaxf(a1, __shfl_xor_sync(~0u, a1, 1)); a1 = fmaxf(a1, __shfl_xor_sync(~0u, a1, 2));
    const float n0 = fmaxf(m0, a0), n1 = fmaxf(m1, a1);
    const float c0 = (m0 == n0) ? 1.f : ex2(m0 - n0), c1 = (m1 == n1) ? 1.f : ex2(m1 - n1);
    m0 = n0; m1 = n1;
    const uint32_t p0 = pack2(ex2(s[0][0] - n0), ex2(s[0][1] - n0)), p1 = pack2(ex2(s[0][2] - n1), ex2(s[0][3] - n1));
    const uint32_t p2 = pack2(ex2(s[1][0] - n0), ex2(s[1][1] - n0)), p3 = pack2(ex2(s[1][2] - n1), ex2(s[1][3] - n1));
    l0 = l0 * c0 + bf_lo(p0) + bf_hi(p0) + bf_lo(p2) + bf_hi(p2);
    l1 = l1 * c1 + bf_lo(p1) + bf_hi(p1) + bf_lo(p3) + bf_hi(p3);
#pragma unroll
    for (int j = 0; j < 4; j++) {
      o[j][0] *= c0; o[j][1] *= c0; o[j][2] *= c1; o[j][3] *= c1;
      const unsigned short* vp = (const unsigned short*)(vb + (size_t)(k0 + 2 * qd) * 32 + j * 8 + g);
      const uint32_t b0 = (uint32_t)__ldcg(vp) | ((uint32_t)__ldcg(vp + 32) << 16);
      const uint32_t b1 = (uint32_t)__ldcg(vp + 256) | ((uint32_t)__ldcg(vp + 288) << 16);
      mma16816(o[j], p0, p1, p2, p3, b0, b1);
    }
  }
  l0 += __shfl_xor_sync(~0u, l0, 1); l0 += __shfl_xor_sync(~0u, l0, 2);
  l1 += __shfl_xor_sync(~0u, l1, 1); l1 += __shfl_xor_sync(~0u, l1, 2);
#pragma unroll
  for (int j = 0; j < 4; j++) { res[4 * j] = o[j][0]; res[4 * j + 1] = o[j][1]; res[4 * j + 2] = o[j][2]; res[4 * j + 3] = o[j][3]; }
  res[16] = l0; res[18] = l1;
}

__device__ __noinline__ void attn_redo(int redo, int l, int b, int wg, int w, uint32_t tag) {
  const int lane = lane_id();
#pragma unroll 1
  for (int t = 0; t < 4; t++) {
    const int h = t >> 1, head = 2 * (b & 15) + h, row = (b >> 4) * 256 + wg * 128 + (t & 1) * 64 + w * 16 + (lane >> 2);
    if ((redo >> t) & 1) {
      const uint32_t* esc = g_esc + (size_t)((l & 2) * 65536 + head * 2048) * 20;
      const uint32_t* qs = (const uint32_t*)(g_qsave + (block_id() * 256 + wg * 128 + w * 32 + lane) * 8 + 2 * t);
      uint32_t q[8]; float o[20];
#pragma unroll
      for (int i = 0; i < 2; i++) {
        uint32_t u[4] = {__ldcg(qs + i), __ldcg(qs + i + 2), __ldcg(qs + i + 4), __ldcg(qs + i + 6)};
        unesc(u, esc + (row + i * 8) * 20 + (lane & 3), tag);
        q[i] = u[0]; q[i + 2] = u[1]; q[i + 4] = u[2]; q[i + 6] = u[3];
      }
      __syncwarp();
      attn_slow(q, head, esc + 65536 * 20, tag, o, lane);
      const float i0 = rcp(o[16]), i1 = rcp(o[18]);
      bf16* op = g_os + (size_t)row * 1024 + h * 512 + (b & 15) * 32 + (lane & 3) * 8;
      *(uint4*)op = make_uint4(pack2(o[0] * i0, o[1] * i0), pack2(o[4] * i0, o[5] * i0), pack2(o[8] * i0, o[9] * i0), pack2(o[12] * i0, o[13] * i0));
      *(uint4*)(op + 8 * 1024) = make_uint4(pack2(o[2] * i1, o[3] * i1), pack2(o[6] * i1, o[7] * i1), pack2(o[10] * i1, o[11] * i1), pack2(o[14] * i1, o[15] * i1));
    }
    if ((t & 1) && ((redo >> 2 * h) & 3)) bar_arrive(NB_SIG + 2 * h + wg, 160 + 32 * (h & wg));
  }
}

__global__ void __cluster_dims__(2, 1, 1) __launch_bounds__(384, 1) fused_kernel(const __grid_constant__ Params prm) {
  extern __shared__ __align__(1024) char smem[];
  const uint32_t sb = (uint32_t)__cvta_generic_to_shared(smem);
  const int tid = threadIdx.x, lane = tid & 31;
  const int wg = __shfl_sync(0xffffffffu, tid >> 7, 0);
  const int w = __shfl_sync(0xffffffffu, (tid >> 5) & 3, 0);
  const int bm = remap(blockIdx.x) >> 4, bn = remap(blockIdx.x) & 15;

  auto first_tile = [&](int kt) {
    e_expect_tx(sb + B_QF + 8 * kt, QSTG);
    tma_ld(sb + kt * QSTG, &prm.m[M_X0A], kt * 64, bm * 256, sb + B_QF + 8 * kt);
    tma_ld3(sb + kt * QSTG + 32768, &prm.m[M_WQA], bn * 64, kt * 64, 0, sb + B_QF + 8 * kt);
  };
  auto init4 = [&](uint32_t bar, uint32_t c0, uint32_t c1, uint32_t c2, uint32_t c3) {
    asm volatile("{\n.reg .pred pe;\nelect.sync _|pe, 0xffffffff;\n@pe mbarrier.init.shared::cta.b64 [%0], %1;\n@pe mbarrier.init.shared::cta.b64 [%0+8], %2;\n"
                 "@pe mbarrier.init.shared::cta.b64 [%0+16], %3;\n@pe mbarrier.init.shared::cta.b64 [%0+24], %4;\n@pe fence.mbarrier_init.release.cluster;\n}"
                 ::"r"(bar), "r"(c0), "r"(c1), "r"(c2), "r"(c3) : "memory");
  };
  if (wg < 2) {
    const uint32_t k = wg * 4 + w, lo = (0x1411814u >> (4 * k)) & 15, hi = (0x1441814u >> (4 * k)) & 15;
    if (tid < 32) asm volatile("prefetch.global.L2 [%0];" ::"l"(prm.x0 + (size_t)(bm * 256 + bn * 16 + (tid & 15)) * 1024 + (tid >> 4) * 64));
    else if (tid < 80) asm volatile("prefetch.global.L2 [%0];" ::"l"(prm.wq[0] + (bm * 16 + (tid & 15)) * 3072 + ((tid >> 4) - 2) * 1024 + bn * 64));
    __syncwarp();
    if (k < 7) init4(sb + B_QE + 32 * k, lo, lo, hi, k == 6 ? 2 : hi);
    __syncwarp();
    if (k == 6 && lane == 0) *(volatile unsigned long long*)(smem + W_X) = 0ull;
  } else if (w == 0) {
    init4(sb + B_QF, 1, 1, 1, 1);
    __syncwarp();
    first_tile(0);
  }
  __syncthreads();
  asm volatile("barrier.cluster.arrive.relaxed.aligned;" ::: "memory");

  if (wg == 2) {
    asm volatile("setmaxnreg.dec.sync.aligned.u32 56;");
    const uint32_t ep1 = *(volatile uint32_t*)&g_epoch + 1;
    if (w == 0) {
      first_tile(1);
      mbar_wait(sb + B_QF, 0);
      first_tile(2); first_tile(3);
#pragma unroll 1
      for (int kt = 4; kt < 16; kt++) l2_prefetch(prm.wq[0] + kt * 196608 + blockIdx.x * 1536, 3072);
      cluster_wait();
#pragma unroll 1
      for (int l = 0; l < 4; l++) {
        IDS();
        const CUtensorMap* mw = &prm.m[M_WQA + (l & 1)];
        const CUtensorMap* mh = &prm.m[l == 0 ? M_X0H : M_XSO];
        const CUtensorMap* mo = &prm.m[M_WOA + (l & 1)];
        auto q_b = [&](int i) {
          const int s = i & 3;
          mbar_wait(sb + B_QE + 8 * s, ((i >> 2) & 1) ^ 1);
          e_expect_tx(sb + B_QF + 8 * s, QSTG);
          tma_ld3(sb + s * QSTG + 32768, mw, bn * 64, qord(i, l, pn) * 64, 0, sb + B_QF + 8 * s);
        };
        uint32_t rdy = l ? 0u : ~0u;
        auto q_a = [&](int i) {
          const int kt = qord(i, l, pn);
          await_flag(kt, rdy, cnt_x(bm) + (lane & 15), ep1 * 9 - 6 + 2 * l);
          tma_ld_mc(sb + (i & 3) * QSTG + rank * 16384, mh, kt * 64, bm * 256 + rank * 128, sb + B_QF + 8 * (i & 3));
        };
        if (l > 0) {
#pragma unroll 1
          for (int i = 0; i < 4; i++) {
            const int kt = qord(i, l, pn);
            await_flag(kt, rdy, cnt_x(bm) + (lane & 15), ep1 * 9 - 6 + 2 * l);
            e_expect_tx(sb + B_QF + 8 * i, 16384);
            tma_ld(sb + i * QSTG + (po ^ 1) * 16384, &prm.m[M_XSO], kt * 64, (pm ^ 1) * 128, sb + B_QF + 8 * i);
          }
        }
#pragma unroll 1
        for (int i = 4; i < 16; i++) {
          if (l == 3 && i == 12) poll_ge(cnt_ad(bn), ep1 * 16);
          q_b(i); q_a(i);
          if (l == 0 && i >= 8) l2_prefetch(prm.wq[1] + ((i - 8) * 128 + blockIdx.x) * 3072, 6144);
          if (l == 0 && i >= 8) l2_prefetch(prm.wo + ((i - 8) * 128 + blockIdx.x) * 1024, 2048);
        }
        if (l & 1) {
          const int krow = 2 * bn * 2048 + bm * 256;
          uint32_t* kvc = cnt_kv(l >> 1, bn);
          uint32_t seen = 0;
#pragma unroll 1
          for (int it = 1; it < 16; it++) {
            const int s = it & 3;
            if (it == 4) {
              bar_sync(NB_KV + 12, 288);
              mbar_wait(sb + B_TF + 24, 0);
#pragma unroll 1
              for (int i = 0; i < 4; i++) tma_st(&prm.m[M_K + (i & 1)], 0, krow + 2048 + (i >> 1) * 128, sb + i * 8192);
              bulk_commit();
            }
            if (it == 5) { bulk_wait_n<0>(); e_red(kvc + 16 + bm); }
            if (it == 12) { e_expect_tx(sb + B_RF, 32768); tma_ld3(sb + RES, &prm.m[M_XSR], 0, pm * 128, 2 * pn, sb + B_RF); }
            if (it == 1 || it == 3) mbar_wait(sb + B_QE + 12 + 4 * it, 1);
            mbar_wait(sb + B_TE + 8 * s, ((it >> 2) & 1) ^ 1);
            if (it < 8) {
#pragma unroll 1
              for (uint32_t n = 0; n < 200000u && (~seen & (3u << (2 * it - 2) | (it == 4 ? 0xC000u : 0u))); n++)
                seen = __ballot_sync(~0u, (int)(ld_acquire(kvc + (lane < 7 || lane == 15 ? (bm + 1 + lane) & 7 : 8 + ((bm + 2 + lane) & 7))) - ep1) >= 0);
              fence_async_gl();
            } else if (it == 8) { poll_ge(kvc + 16 + (lane & 7), ep1); fence_async_gl(); }
            e_expect_tx(sb + B_TF + 8 * s, 32768);
#pragma unroll 1
            for (int i = 0; i < 2; i++) {
              const int u = 2 * it - 2 + i;
              const int row = 2 * bn * 2048 + (it > 7 ? 2048 + ((bm + it) & 7) * 256 + i * 128 : u < 7 ? ((bm + 1 + u) & 7) * 256 : ((bm + 2 + u) & 7) * 256 + 128);
              tma_ld(sb + T0 + s * TSTG + i * 8192, &prm.m[M_K], 0, row, sb + B_TF + 8 * s);
              tma_ld(sb + T0 + s * TSTG + 16384 + i * 8192, &prm.m[M_V], 0, row, sb + B_TF + 8 * s);
            }
          }
        }
        auto p_b = [&](int i, uint32_t s, uint32_t par) {
          mbar_wait(sb + B_PE + 8 * s, par ^ 1);
          e_expect_tx(sb + B_PF + 8 * s, PSTG);
          tma_ld5(sb + pslot_b(s), mo, i >> 3, (2 * i + bn) & 14, 2 * pn, sb + B_PF + 8 * s);
        };
        auto p_a = [&](int i, uint32_t s) {
          await_flag(i, rdy, cnt_o(l, pm, (lane >> 3) & 1) + ((lane + (bn >> 1)) & 7), ep1 * 2);
          tma_ld_mc(sb + pslot_a(s, l) + rank * 8192, &prm.m[M_OS], (i & 8) * 64 + ((2 * i + bn) & 14) * 32, pm * 128 + rank * 64, sb + B_PF + 8 * s);
        };
        auto p_a2 = [&](int i) {
          await_flag(i, rdy, cnt_o(l, pm, (lane >> 3) & 1) + ((lane + (bn >> 1)) & 7), ep1 * 2);
          tma_ld(sb + pslot_a(i, l), &prm.m[M_OS], (i & 8) * 64 + ((2 * i + bn) & 14) * 32, pm * 128, sb + B_PF + 8 * i);
          tma_ld(sb + pslot_a(i, l) + 8192, &prm.m[M_OS], (i & 8) * 64 + ((2 * i + bn) & 14) * 32, pm * 128 + 64, sb + B_PF + 8 * i);
        };
        rdy = 0;
        if (l & 1) {
#pragma unroll 1
          for (int u = 0; u < 6; u++) { const int i = (0x205413 >> (4 * u)) & 7; if (u == 4) mbar_wait(sb + B_TE, 1); p_b(i, i, i < 4 ? 1 : 0); }
#pragma unroll 1
          for (int u = 0; u < 6; u++) {
            const int i = (0x542130 >> (4 * u)) & 7;
            if (!(u & 1)) mbar_wait(sb + B_TE + 8 + 4 * u, 1);
            if (u == 4) bar_sync(NB_SIG + 3, 192);
            p_a2(i);
          }
        } else {
#pragma unroll 1
          for (int u = 0; u < 6; u++) { const int i = (0x543120 >> (4 * u)) & 7; if (u == 0 || u == 2) mbar_wait(sb + B_QE + 8 - 4 * u, 1); p_b(i, i, 0); }
          mbar_wait(sb + B_QE + 24, 1);
          e_expect_tx(sb + B_RF, 32768);
          tma_ld3(sb + RES, &prm.m[l == 0 ? M_X0R : M_XSR], 0, pm * 128, 2 * pn, sb + B_RF);
          await_flag(1, rdy, cnt_o(l, pm, (lane >> 3) & 1) + ((lane + (bn >> 1)) & 7), ep1 * 2);
          bar_sync(NB_DONE, 288);
          e_arrive_both(sb + B_PA);
          mbar_wait(sb + B_PA, (l >> 1) & 1);
#pragma unroll 1
          for (int i = 1; i < 6; i++) { if (i > 3) mbar_wait(sb + B_PF + 8 * (i - 3), 0); p_a(i, i); }
        }
        uint32_t s = 0, lap = 1;
#pragma unroll 1
        for (int i = 6; i < 16; i++) {
          p_b(i, s, ((s < 4 ? l : 0) + lap) & 1);
          p_a(i, s);
          if (++s == 6) { s = 0; lap++; }
        }
        const CUtensorMap* mn = &prm.m[M_WQA + ((l + 1) & 1)];
        if (l < 3) {
          mbar_wait(sb + B_PE + 8 * 4, 1); mbar_wait(sb + B_PE + 8 * 5, 1);
          tma_ld3(sb + 32768, mn, bn * 64, 2 * pn * 64, 0, sb + B_QL);
          mbar_wait(sb + B_PE + 8 * 0, l & 1);
          e_expect_tx(sb + B_PA, 24576); e_expect_tx(sb + B_PA, 16384);
          tma_ld3(sb + QSTG + 32768, mn, bn * 64, ((2 * pn) ^ 2) * 64, 0, sb + B_PA);
          mbar_wait(sb + B_PE + 8 * 1, l & 1);
          tma_ld3(sb + 2 * QSTG + 32768, mn, bn * 64, (2 * pn + 1) * 64, 0, sb + B_QL);
          bar_sync(NB_KN, 288);
          e_expect_tx(sb + B_RF, 40960);
          tma_ld3(sb + 3 * QSTG + 32768, mn, bn * 64, ((2 * pn) ^ 3) * 64, 0, sb + B_RF);
          mbar_wait(sb + B_PE + 24, l & 1);
          bar_sync(NB_X0, 320);
          fence_async_gl();
          tma_ld_mc(sb + QSTG + po * 16384, &prm.m[M_XSO], 2 * pn * 64, pm * 128, sb + B_PA, 2 - rank);
          bar_sync(NB_X, 320);
          e_expect_tx(sb + B_QL, 49152);
        }
      }
      if (blockIdx.x == 0 && lane_id() == 0) *(volatile uint32_t*)&g_epoch = ep1;
    } else {
      const int hw = w - 1;
      if (lane < 5) asm volatile("prefetch.tensormap [%0];" ::"l"(&prm.m[5 * hw + lane]) : "memory");
      __syncwarp();
      cluster_wait();
      mbar_hint(sb + B_QF, 0);
#pragma unroll 1
      for (int l = 0; l < 4; l++) {
        IDS();
        if (l > 0) { mbar_wait(sb + B_QL, (l + 1) & 1); mbar_hint(sb + B_QF + 24, 0); }
        if (l == 0) {
#pragma unroll 1
          for (int r = 2 * hw; r < 16; r += 6) {
            const uint4* p = (const uint4*)(prm.x0 + (size_t)(b * 16 + r) * 1024) + lane;
            float s1[2] = {0.f, 0.f}, s2[2] = {0.f, 0.f};
#pragma unroll
            for (int i = 0; i < 8; i++) {
              const uint4 v = __ldg(p + 32 * i);
              const uint32_t u[4] = {v.x, v.y, v.z, v.w};
#pragma unroll
              for (int k = 0; k < 4; k++) { const float a = bf_lo(u[k]), c = bf_hi(u[k]); s1[i >> 2] += a + c; s2[i >> 2] = fmaf(a, a, fmaf(c, c, s2[i >> 2])); }
            }
#pragma unroll
            for (int o = 16; o; o >>= 1)
#pragma unroll
              for (int rr = 0; rr < 2; rr++) { s1[rr] += __shfl_xor_sync(~0u, s1[rr], o); s2[rr] += __shfl_xor_sync(~0u, s2[rr], o); }
            if (lane == 0) *(float4*)&g_stats[b * 16 + r] = make_float4(s1[0], s2[0], s1[1], s2[1]);
          }
        }
        if (l < 2) {
          float cs[8];
#pragma unroll
          for (int i = 0; i < 8; i++) cs[i] = 0.f;
          const uint4* wp = (const uint4*)(prm.wq[l] + (size_t)(bm * 128 + (lane >> 3)) * 3072 + hw * 1024 + bn * 64) + (lane & 7);
#pragma unroll 8
          for (int i = 0; i < 32; i++) {
            const uint4 v = __ldg(wp + (size_t)i * 4 * 384);
            cs[0] += bf_lo(v.x); cs[1] += bf_hi(v.x); cs[2] += bf_lo(v.y); cs[3] += bf_hi(v.y);
            cs[4] += bf_lo(v.z); cs[5] += bf_hi(v.z); cs[6] += bf_lo(v.w); cs[7] += bf_hi(v.w);
          }
#pragma unroll
          for (int i = 0; i < 8; i++) { cs[i] += __shfl_xor_sync(~0u, cs[i], 8); cs[i] += __shfl_xor_sync(~0u, cs[i], 16); }
          if (lane < 8) {
            float4* d = (float4*)(g_csp + ((l * 16 + bn) * 8 + bm) * 192 + hw * 64 + lane * 8);
            d[0] = make_float4(cs[0], cs[1], cs[2], cs[3]); d[1] = make_float4(cs[4], cs[5], cs[6], cs[7]);
          }
          __syncwarp();
          asm volatile("fence.acq_rel.gpu;" ::: "memory");
          e_red_relaxed(cnt_cs(l, bn));
          if (l == 0) e_red_relaxed(cnt_x(bm) + bn);
          poll_ge(lane < 16 && l == 0 ? cnt_x(bm) + lane : cnt_cs(l, bn), lane < 16 && l == 0 ? ep1 * 9 - 6 : ep1 * 24);
        }
        if (l > 0) poll_ge(cnt_x(bm) + (lane & 15), ep1 * 9 - 6 + 2 * l);
#pragma unroll 1
        for (int it = hw * 32 + lane; it < 176; it += 96) {
          const bool rows = it < 128;
          const float4* p = rows ? (const float4*)(g_stats + bm * 256) + it : (const float4*)(g_csp + ((l & 1) * 16 + bn) * 8 * 192) + (it - 128);
          const int stride = rows ? 1024 : 48, np = rows && l == 0 ? 1 : 8;
          float4 a = make_float4(0.f, 0.f, 0.f, 0.f);
#pragma unroll
          for (int k = 0; k < 8; k++) if (k < np) { const float4 v = __ldcg(p + k * stride); a.x += v.x; a.y += v.y; a.z += v.z; a.w += v.w; }
          if (rows) {
            const float m0 = a.x * (1.f / 1024.f), m1 = a.z * (1.f / 1024.f);
            const float v0 = fmaxf(a.y * (1.f / 1024.f) - m0 * m0, 0.f), v1 = fmaxf(a.w * (1.f / 1024.f) - m1 * m1, 0.f);
            const float r0 = __fdividef(1.f, bf_round(sqrtf(bf_round(bf_round(v0) + 1e-5f)))), r1 = __fdividef(1.f, bf_round(sqrtf(bf_round(bf_round(v1) + 1e-5f))));
            a = make_float4(r0, -bf_round(m0), r1, -bf_round(m1));
          }
          if (rows && (l & 1) && (it & 4)) a = make_float4(a.y, a.x, a.w, a.z);
          *(float4*)(smem + ROWST + it * 16) = a;
        }
        __syncwarp();
        if (lane == 0) asm volatile("red.release.cta.shared.add.u32 [%0], 1;" ::"r"(sb + W_X) : "memory");
        if (hw == 2) {
          if (!(l & 1)) {
            bar_sync(NB_ST, 288);
            const uint4* hp = g_halo + (b - 16) * 384 + lane;
#pragma unroll 1
            for (int h = 0; h < 2; h++) {
              uint32_t t[18];
#pragma unroll
              for (int i = 0; i < 18; i++) t[i] = 0;
#pragma unroll 1
              for (uint32_t n = bm ? 0 : 100000u; n < 100000u; n++) {
                uint32_t miss = 0;
#pragma unroll
                for (int i = 0; i < 6; i++) miss |= ld_tagged(hp + h * 192 + i * 32, &t[3 * i]) ^ (4 * ep1 + l);
                if (__all_sync(~0u, !miss)) break;
              }
              mbar_wait(sb + B_QE + 16, 1);
              const uint32_t r = (lane & 7) + ((lane >> 3) & 1) * 8, rv = lane >> 2;
#pragma unroll
              for (int jj = 0; jj < 2; jj++) stsm4(sb + KSC + r * 128 + (((4 * h + 2 * jj + (lane >> 4)) ^ (r & 7)) << 4), t[4 * jj], t[4 * jj + 1], t[4 * jj + 2], t[4 * jj + 3]);
              const uint32_t ad = sb + VSC + rv * 128 + (((4 * h + (lane & 3)) ^ (rv & 7)) << 4);
              sts128(ad, t[8], t[10], t[12], t[14]); sts128(ad + 1024, t[9], t[11], t[13], t[15]);
              if (h == 0 && !(lane & 2)) *(uint32_t*)(smem + HRS + ((lane >> 2) + 8 * (lane & 1)) * 8) = t[16];
              bar_arrive(NB_HALO + h, 64);
            }
          } else {
            bar_sync(NB_KV, 288);
            sts128(sb + ONES + lane * 32, 0x3f803f80u, 0x3f803f80u, 0x3f803f80u, 0x3f803f80u);
            sts128(sb + ONES + lane * 32 + 16, 0x3f803f80u, 0x3f803f80u, 0x3f803f80u, 0x3f803f80u);
            sts128(sb + ROWST + 16, 0x62A962A9u, 0x00010001u, 0x3F003F00u, 0u);
            fence_async_smem();
            __syncwarp();
            e_arrive(sb + B_TF);
            mbar_hint(sb + B_TF + 16, 0); mbar_hint(sb + B_TF + 16, 1);
            poll_ge(cnt_kv(l >> 1, bn) + 16 + (lane & 7), ep1);
            const uint4 v = __ldcg((const uint4*)(g_kn + ((l >> 1) * 128 + bn * 8) * 16) + lane);
            const uint32_t mx = max(max(v.x, v.y), max(v.z, v.w));
            const uint32_t m0 = __reduce_max_sync(~0u, (lane & 2) ? 0u : mx), m1 = __reduce_max_sync(~0u, (lane & 2) ? mx : 0u);
            if (lane == 0) *(uint2*)(smem + ROWST) = make_uint2(m0, m1);
            __syncwarp();
            bar_arrive(NB_KN, 160); bar_arrive(NB_KN + 1, 160);
          }
        } else {
          if (l & 1) {
            uint32_t* p = cnt_kv(l >> 1, bn) + 8 * hw + bm;
            int on = lane == 0;
            PREPARED(p, on);
            bar_sync(hw ? NB_HALO : NB_DONE, 160);
            tma_st(&prm.m[M_K], 0, 2 * bn * 2048 + bm * 256 + hw * 128, sb + T0 + hw * 8192);
            tma_st(&prm.m[M_V], 0, 2 * bn * 2048 + bm * 256 + hw * 128, sb + T0 + 16384 + hw * 8192);
            bulk_commit(); bulk_wait_n<0>();
            release_add(p, on);
          }
#pragma unroll 1
          for (int h = l & 1 ? 0 : hw; h <= (l & 1 ? 1 : hw); h++) {
            uint32_t* p = l == 1 && lane == 1 ? cnt_ad(bn) : cnt_o(l, 2 * bm + (l & 1 ? hw : lane & 1), h) + (bn >> 1);
            int on = lane == 0 || (lane == 1 && (!(l & 1) || (l == 1 && h == 1)));
            int id = NB_SIG + 2 * h + (l & hw), n = l & 1 ? 160 + 32 * (h & hw) : 288;
            asm volatile("" : "+r"(id), "+r"(n));
            PREPARED(p, on);
            bar_sync(id, n);
            release_add(p, on);
            if (!(l & 1) && hw == 0) {
              mbar_wait(sb + B_QE + 24, 1);
              fence_async_gl();
              tma_ld_mc(sb + pslot_a(0, 0) + rank * 8192, &prm.m[M_OL], bn * 32, pm * 128, sb + B_PF);
            }
          }
        }
        if (hw < 2 && l < 3) {
          uint32_t* p = cnt_x(bm) + 2 * pn + hw;
          int on = lane == 0;
          PREPARED(p, on);
          if (hw) {
            bar_sync(NB_X, 320);
            tma_st(&prm.m[M_XSO], pn * 128 + 64, pm * 128, sb + 2 * QSTG + po * 16384);
            bulk_commit();
            bar_sync(NB_KV, 288);
            bulk_wait_n<0>();
            mbar_wait(sb + B_PA, l == 0);
            fence_async_gl();
            tma_ld_mc(sb + 3 * QSTG + po * 16384, &prm.m[M_XSO], pn * 128 + 64, pm * 128, sb + B_RF, 2 - rank);
          } else bar_sync(NB_X0, 320);
          release_add(p, on);
        }
      }
    }
  } else {
    asm volatile("setmaxnreg.inc.sync.aligned.u32 224;");
    const uint32_t zero = prm.zero;
    cluster_wait();
#pragma unroll 1
    for (int l = 0; l < 4; l++) {
      {
        float acc[2][96];
        const bool early = l > 0 && wg == ((cta_id() >> 3) & 1);
        uint32_t ep1 = 0;
        if (l > 0) mbar_wait(sb + B_QL, (l + 1) & 1);
        if (!early) mbar_wait(sb + B_QF, 0);
        wg_fence();
#pragma unroll
        for (int k = 0; k < 4; k++)
#pragma unroll
          for (int m = 0; m < 2; m++) {
            if (k) wgmma_m64n192k16_ss_tb(acc[m], prm.xd + wg * 1024 + m * 512 + k * 2, prm.wd + k * 128, 1);
            else wgmma_m64n192k16_ss_tb_z(acc[m], prm.xd + wg * 1024 + m * 512, prm.wd, 0);
          }
        wg_commit();
#pragma unroll 1
        for (int kt = 1; kt < 13; kt++) {
          const int s = kt == 12 ? 1 : kt & 3;
          if (l > 0 && (kt | 2) == 3) mbar_wait(sb + (kt == 1 ? B_PA : B_RF), kt == 3 || l == 1);
          if (!(early && kt < 4)) mbar_wait(sb + B_QF + 8 * s, (kt >> 2) & 1);
          const uint64_t da = prm.xd + wg * 1024 + s * (QSTG >> 4), db = prm.wd + s * (QSTG >> 4);
          wg_fence();
#pragma unroll
          for (int k = 0; k < 4; k++)
#pragma unroll
            for (int m = 0; m < 2; m++) wgmma_m64n192k16_ss_tb(acc[m], da + m * 512 + k * 2, db + k * 128, 1);
          wg_commit();
          if (kt == 4) ep1 = *(volatile uint32_t*)&g_epoch + 1;
          wg_wait<1>();
          if (early && kt < 5) {
#pragma unroll 1
            for (int i = 3 * (kt - 3); i < kt && kt > 2; i++) { mbar_wait(sb + B_QF + 8 * i, 0); bar_sync(NB_SC, 128); if (w == 0) e_arrive_both(sb + B_QE + 8 * i); }
          } else if (w == 0) e_arrive_both(sb + B_QE + 8 * ((kt - 1) & 3));
        }
        {
          const bool lag = (l & 1) == wg;
          const uint32_t s0 = 2 * (~l & 1);
          const uint64_t da = prm.xd + wg * 1024 + 2 * (QSTG >> 4), db = prm.wd + 2 * (QSTG >> 4);
          mbar_wait(sb + B_QF + 8 * s0, 1);
#pragma unroll
          for (int t = 0; t < 2; t++) {
            if (lag && t != wg) {
              wg_wait<0>();
              if (w == 0) e_arrive_both(sb + B_QE + 8 + 8 * t);
              if (t == 0) mbar_wait(sb + B_QF + 16, 1);
              mbar_wait(sb + B_QF + 24, 1);
              if (t == 1) bar_arrive(NB_ST, 288);
              bar_sync(NB_LAG, 256);
            }
            const uint64_t so = (uint64_t)(t ? s0 : s0 ^ 2) * (QSTG >> 4);
            wg_fence();
#pragma unroll
            for (int k = 0; k < 4; k++)
#pragma unroll
              for (int m = 0; m < 2; m++) wgmma_m64n192k16_ss_tb(acc[m], da - so + m * 512 + k * 2, db - so + k * 128, 1);
            wg_commit();
            if (!lag || t + wg == 0) {
              wg_wait<1>();
              if (w == 0) e_arrive_both(sb + B_QE + 8 * (t ? s0 : 1));
              mbar_wait(sb + B_QF + 8 * (t ? 3 : s0 ^ 2), 1);
            }
          }
          wg_fence();
#pragma unroll
          for (int m = 1; m >= 0; m--) {
#pragma unroll
            for (int k = 0; k < 4; k++) wgmma_m64n192k16_ss_tb(acc[m], da + (QSTG >> 4) + m * 512 + k * 2, db + (QSTG >> 4) + k * 128, 1);
            wg_commit();
          }
          if (!lag) { bar_arrive(NB_LAG, 256); if (wg) bar_arrive(NB_ST, 288); }
          wg_wait<2>();
          if (w == 0) { e_arrive_both(sb + B_QE + 8 * (s0 ^ 2)); if (lag && wg) e_arrive_both(sb + B_QE); }
        }
#pragma unroll 1
        for (uint32_t n = 0; n < 4000000u; n++) {
          uint32_t v;
          asm volatile("ld.acquire.cta.shared.u32 %0, [%1];" : "=r"(v) : "r"(sb + W_X) : "memory");
          if (v == (uint32_t)(3 * l + 3)) break;
        }
        IDS();
        const int g = lane >> 2, qd = lane & 3;
        float2 st[2][2];
#pragma unroll
        for (int m = 0; m < 2; m++)
#pragma unroll
          for (int hh = 0; hh < 2; hh++) st[m][hh] = lds64f(sb + ROWST + (wg * 128 + m * 64 + w * 16 + g + 8 * hh) * 8);
        float2 cs[4];
        auto load_cs = [&](int gi) {
#pragma unroll
          for (int j = 0; j < 4; j++) cs[j] = lds64f(sb + COLS + (gi * 32 + j * 8 + 2 * qd) * 4);
        };
        load_cs(2 + 2 * (l & 1));
        auto drain = [&]() {
          wg_wait<0>(); fence_regs(acc[0]);
          if (w == 0) e_arrive_both(sb + B_QE + 8 * 3);
        };
        wg_wait<1>(); fence_regs(acc[1]);
        auto norm_tile = [&](int gi, int m, float sc, uint32_t (&t)[8], bool h16 = false) {
          const float r0 = st[m][0].x * sc, s0 = st[m][0].y, r1 = st[m][1].y * sc, s1 = st[m][1].x;
#pragma unroll
          for (int j = 0; j < 4; j++) {
            const float* a = &acc[m][16 * gi + 4 * j];
            const float v0 = fmaf(s0, cs[j].x, a[0]) * r0, v1 = fmaf(s0, cs[j].y, a[1]) * r0;
            const float v2 = fmaf(s1, cs[j].x, a[2]) * r1, v3 = fmaf(s1, cs[j].y, a[3]) * r1;
            t[2 * j] = h16 ? pack2h(v0, v1) : pack2(v0, v1); t[2 * j + 1] = h16 ? pack2h(v2, v3) : pack2(v2, v3);
          }
        };
        uint32_t q[2][2][8];
        const uint32_t srow = (lane & 7) + ((lane >> 3) & 1) * 8;
        const uint32_t row0 = wg * 128 + w * 16;
        if (!(l & 1)) {
          auto put_kv = [&](int gi, uint32_t r0, const uint32_t (&t)[8]) {
            if (gi < 4) {
              const uint32_t r = r0 + srow;
#pragma unroll
              for (int jj = 0; jj < 2; jj++) stsm4(sb + KSC + r * 128 + (((4 * (gi - 2) + 2 * jj + (lane >> 4)) ^ (r & 7)) << 4), t[4 * jj], t[4 * jj + 1], t[4 * jj + 2], t[4 * jj + 3]);
            } else {
              const uint32_t r = r0 + g, ad = sb + VSC + r * 128 + (((4 * (gi - 4) + qd) ^ (r & 7)) << 4);
              sts128(ad, t[0], t[2], t[4], t[6]); sts128(ad + 1024, t[1], t[3], t[5], t[7]);
            }
          };
          auto cen_tile = [&](int gi, int m, uint32_t (&t)[8]) {
#pragma unroll
            for (int j = 0; j < 4; j++) {
              const float* a = &acc[m][16 * gi + 4 * j];
              t[2 * j] = pack2(fmaf(st[m][0].y, cs[j].x, a[0]), fmaf(st[m][0].y, cs[j].y, a[1]));
              t[2 * j + 1] = pack2(fmaf(st[m][1].y, cs[j].x, a[2]), fmaf(st[m][1].y, cs[j].y, a[3]));
            }
          };
          const bool send = wg == 1 && w == 3 && bm < 7;
          uint4* hp = g_halo + b * 384 + lane;
          ep1 = 4 * ep1 + l;
          mbar_wait(sb + B_QE + 16, 1);
          float2 cn[4];
          auto next_cs = [&](int gi) {
#pragma unroll
            for (int j = 0; j < 4; j++) { cs[j] = cn[j]; cn[j] = lds64f(sb + COLS + (gi * 32 + j * 8 + 2 * qd) * 4); }
          };
#pragma unroll
          for (int j = 0; j < 4; j++) cn[j] = cs[j];
          auto lower = [&](int h, int nx, bool snd) {
            uint32_t k[8], v[8];
            next_cs(4 + h);
            cen_tile(2 + h, 1, k); put_kv(2 + h, 16 + row0 + 64, k);
            next_cs(nx);
            cen_tile(4 + h, 1, v); put_kv(4 + h, 16 + row0 + 64, v);
            if (snd) {
              uint4* p = hp + h * 192;
              st_tagged(p, k[0], k[1], k[2], ep1); st_tagged(p + 32, k[3], k[4], k[5], ep1); st_tagged(p + 64, k[6], k[7], v[0], ep1);
              st_tagged(p + 96, v[1], v[2], v[3], ep1); st_tagged(p + 128, v[4], v[5], v[6], ep1);
              st_tagged(p + 160, v[7], __float_as_uint(qd & 1 ? st[1][1].x : st[1][0].x), 0u, ep1);
            }
          };
          lower(0, 2 + wg, send);
          sched_fence();
          if (wg) lower(1, 2, send);
          drain();
          if (!wg) bar_arrive(NB_KN + 1, 256);
          {
            uint32_t t[8];
            next_cs(4); cen_tile(2, 0, t); put_kv(2, 16 + row0, t);
            next_cs(0); cen_tile(4, 0, t); put_kv(4, 16 + row0, t);
            next_cs(3); cen_tile(0, 0, q[0][0]); cen_tile(0, 1, q[0][1]);
          }
          auto upper = [&]() {
            uint32_t t[8];
            next_cs(5); cen_tile(3, 0, t); put_kv(3, 16 + row0, t);
            next_cs(1); cen_tile(5, 0, t); put_kv(5, 16 + row0, t);
          };
          if (wg) upper();
          const bool e = g & 1, sel = 2 * qd + (g & 1) >= g + 2, first = bm == 0 && row0 == 0;
          uint32_t ka = sb + KSC + (row0 + (lane & 7)) * 128 + (((lane >> 3) ^ (lane & 7)) << 4);
          uint32_t wa = sb + VSC + (row0 + srow) * 128 + (((lane >> 4) ^ (lane & 7)) << 4);
          uint32_t psel[3] = {e ? 0x1044u : 0x4410u, !sel ? 0x4444u : e ? 0x3244u : 0x4432u, sel ? 0x4444u : e ? 0x3244u : 0x4432u};
          bf16* op = g_os + (size_t)(bm * 256 + row0 + g) * 1024 + bn * 32 + qd * 8;
          asm volatile("" : "+r"(ka), "+r"(wa), "+l"(op));
          fence_regs(psel); fence_regs(q[0][0]); fence_regs(q[0][1]);
          sched_fence();
          bar_sync(NB_KN + wg, 128 << wg);
          if (row0 == 0) bar_sync(NB_HALO, 64);
          float ra[4], rb[4], ca[4], cb[4];
#pragma unroll
          for (int m = 0; m < 2; m++) {
            float rk[3];
#pragma unroll
            for (int u = 0; u < 3; u++) {
              const int r = row0 + m * 64 + 8 * u + 2 * qd + e - (sel ? 16 : 8);
              rk[u] = lds64f(sb + (m == 0 && r < 0 ? HRS + 128 : ROWST) + r * 8).x;
            }
            ra[2 * m] = sel ? rk[1] : rk[0]; ra[2 * m + 1] = sel ? rk[2] : rk[1];
            rb[2 * m] = sel ? rk[0] : rk[1]; rb[2 * m + 1] = sel ? rk[1] : rk[2];
          }
#pragma unroll
          for (int i = 0; i < 4; i++) { const float rq = st[i >> 1][i & 1].x * QSCALE; ca[i] = rq * ra[i]; cb[i] = rq * rb[i]; }
#pragma unroll 1
          for (int h = 0; h < 2; h++) {
            float s[2][4][4];
            uint32_t vf[2][4][4], pf[2][2][4];
#pragma unroll
            for (int m = 0; m < 2; m++)
#pragma unroll
              for (int nt = 0; nt < 4; nt++) {
                uint32_t kf[4];
                ldsm4(ka + (m * 64 + 8 * nt) * 128, kf);
                s[m][nt][0] = s[m][nt][1] = s[m][nt][2] = s[m][nt][3] = 0.f;
                mma16816(s[m][nt], q[0][m][0], q[0][m][1], q[0][m][2], q[0][m][3], kf[0], kf[1]);
                mma16816(s[m][nt], q[0][m][4], q[0][m][5], q[0][m][6], q[0][m][7], kf[2], kf[3]);
              }
#pragma unroll
            for (int m = 0; m < 2; m++)
#pragma unroll
              for (int i = 0; i < 4; i++) {
                ldsm4t((wa ^ (32 * (i & 1))) + (m * 64 + 16 * (i >> 1)) * 128, vf[m][i]);
              }
            float va[4], vb[4], mx[4];
#pragma unroll
            for (int i = 0; i < 4; i++) {
              const int m = i >> 1, hh = i & 1;
              const float a = e ? s[m][hh + 1][2 * hh + 1] : s[m][hh + 1][2 * hh];
              const float lo = e ? s[m][hh][2 * hh + 1] : s[m][hh][2 * hh], hi = e ? s[m][hh + 2][2 * hh + 1] : s[m][hh + 2][2 * hh];
              va[i] = (m == 0 && hh == 0 && first) ? -INFINITY : a * ca[i];
              vb[i] = (m == 0 && first && sel) ? -INFINITY : (sel ? lo : hi) * cb[i];
              mx[i] = fmaxf(va[i], vb[i]);
            }
#pragma unroll
            for (int i = 0; i < 4; i++) mx[i] = fmaxf(mx[i], __shfl_xor_sync(~0u, mx[i], 1));
#pragma unroll
            for (int i = 0; i < 4; i++) mx[i] = fmaxf(mx[i], __shfl_xor_sync(~0u, mx[i], 2));
#pragma unroll
            for (int i = 0; i < 4; i++) {
              va[i] = ex2(va[i] - mx[i]); vb[i] = ex2(vb[i] - mx[i]);
              mx[i] = va[i] + vb[i];
              va[i] *= ra[i]; vb[i] *= rb[i];
            }
#pragma unroll
            for (int i = 0; i < 4; i++) mx[i] += __shfl_xor_sync(~0u, mx[i], 1);
#pragma unroll
            for (int i = 0; i < 4; i++) mx[i] += __shfl_xor_sync(~0u, mx[i], 2);
#pragma unroll
            for (int i = 0; i < 4; i++) {
              const int m = i >> 1, hh = i & 1;
              const float inv = rcp(mx[i]);
              const uint32_t t = pack2(va[i] * inv, vb[i] * inv);
              pf[m][hh][hh + 1] = prmt0(t, psel[0]); pf[m][hh][hh] = prmt0(t, psel[1]); pf[m][hh][hh + 2] = prmt0(t, psel[2]);
              pf[m][hh][3 - 3 * hh] = t & zero;
            }
#pragma unroll
            for (int m = 0; m < 2; m++) {
              float o[4][4];
#pragma unroll
              for (int j = 0; j < 4; j++) o[j][0] = o[j][1] = o[j][2] = o[j][3] = 0.f;
#pragma unroll
              for (int i = 0; i < 4; i++) {
                const int kk = i >> 1, jj = 2 * (i & 1);
                mma16816(o[jj], pf[m][0][2 * kk], pf[m][1][2 * kk], pf[m][0][2 * kk + 1], pf[m][1][2 * kk + 1], vf[m][i][0], vf[m][i][1]);
                mma16816(o[jj + 1], pf[m][0][2 * kk], pf[m][1][2 * kk], pf[m][0][2 * kk + 1], pf[m][1][2 * kk + 1], vf[m][i][2], vf[m][i][3]);
              }
              stg128(op + m * 65536, pack2(o[0][0], o[0][1]), pack2(o[1][0], o[1][1]), pack2(o[2][0], o[2][1]), pack2(o[3][0], o[3][1]));
              stg128(op + m * 65536 + 8192, pack2(o[0][2], o[0][3]), pack2(o[1][2], o[1][3]), pack2(o[2][2], o[2][3]), pack2(o[3][2], o[3][3]));
            }
            if (h) bar_arrive(NB_DONE, 288);
            bar_arrive(NB_SIG + 2 * h, 288);
            if (h == 0) {
              if (!wg) { lower(1, 3, false); upper(); }
#pragma unroll
              for (int j = 0; j < 4; j++) cs[j] = cn[j];
              cen_tile(1, 0, q[0][0]); cen_tile(1, 1, q[0][1]);
              ka ^= 64; wa ^= 64; op += 512;
              bar_sync(NB_SC, 256);
              if (row0 == 0) bar_sync(NB_HALO + 1, 64);
            }
          }
        } else {
          float qn[2];
          mbar_wait(sb + B_QE + 8, 1);
          drain();
          auto esc_ptr = [&](int gi) { IDS(); return g_esc + (size_t)(((l & 2) + (gi >> 1)) * 65536 + (2 * bn + (gi & 1)) * 2048) * 20; };
          auto norm_half = [&](int gi, float sc, uint32_t (&t)[2][8], uint32_t (&n)[2], int nx) {
#pragma unroll
            for (int m = 0; m < 2; m++) {
              norm_tile(gi, m, sc, t[m], true);
              uint32_t a = hfma2(t[m][0], t[m][0], 0u), c = hfma2(t[m][1], t[m][1], 0u);
#pragma unroll
              for (int j = 1; j < 4; j++) { a = hfma2(t[m][2 * j], t[m][2 * j], a); c = hfma2(t[m][2 * j + 1], t[m][2 * j + 1], c); }
              n[m] = hadd2(__byte_perm(a, c, 0x5410), __byte_perm(a, c, 0x7632));
            }
            float2 cn[4];
#pragma unroll
            for (int j = 0; j < 4; j++) if (nx >= 0) cn[j] = lds64f(sb + COLS + (nx * 32 + j * 8 + 2 * qd) * 4);
            if (((n[0] - 0x01000100u) | (n[0] + 0x04000400u) | (n[1] - 0x01000100u) | (n[1] + 0x04000400u)) & 0x80008000u) {
              uint32_t* p = esc_ptr(gi) + (bm * 256 + row0 + g) * 20 + qd;
#pragma unroll
              for (int m = 0; m < 2; m++) {
                uint32_t u[8];
                norm_tile(gi, m, sc, u);
#pragma unroll
                for (int i = 0; i < 10; i++) p[(m * 64 + (i & 1) * 8) * 20 + (i >> 1) * 4] = i < 8 ? u[i] : ep1;
              }
            }
            __syncwarp();
#pragma unroll
            for (int i = 0; i < 16; i++) asm volatile("{\n.reg .b32 u;\nadd.u32 u, %0, 0x00040004;\nand.b32 %0, u, 0xFFF8FFF8;\n}" : "+r"(t[i >> 3][i & 7]));
#pragma unroll
            for (int j = 0; j < 4; j++) if (nx >= 0) cs[j] = cn[j];
          };
          {
            auto max_norm = [&](const uint32_t (&n)[2]) {
              const bool o1 = qd & 1;
              uint32_t a = hadd2(o1 ? n[1] : n[0], __shfl_xor_sync(~0u, o1 ? n[0] : n[1], 1));
              a = hadd2(a, __shfl_xor_sync(~0u, a, 2));
              float lo, hi;
              asm("{.reg .f16 a, b; mov.b32 {a, b}, %2; cvt.f32.f16 %0, a; cvt.f32.f16 %1, b;}" : "=f"(lo), "=f"(hi) : "r"(a));
              return __uint_as_float(__reduce_max_sync(~0u, max(__float_as_uint(lo), __float_as_uint(hi))));
            };
#pragma unroll
            for (int h = 0; h < 2; h++) {
              uint32_t t[2][8], nrm[2];
              const uint32_t kb = sb + (h ? wg * 8192 : T0), vb = kb + (h ? 8192 : 16384);
              norm_tile(4 + h, 0, 1.f, t[0]); norm_tile(4 + h, 1, 1.f, t[1]);
              load_cs(2 + h);
#pragma unroll
              for (int m = 0; m < 2; m++) {
                const uint32_t r = row0 + m * 64 + g, ad = vb + r * 64 + ((qd ^ ((r >> 1) & 3)) << 4);
                sts128(ad, t[m][0], t[m][2], t[m][4], t[m][6]); sts128(ad + 512, t[m][1], t[m][3], t[m][5], t[m][7]);
              }
              if (h == 0) sched_fence();
              norm_half(2 + h, 1.f, t, nrm, h);
#pragma unroll
              for (int i = 0; i < 4; i++) {
                const uint32_t r = row0 + (i >> 1) * 64 + srow;
                stsm4(kb + r * 64 + (((2 * (i & 1) + (lane >> 4)) ^ ((r >> 1) & 3)) << 4), t[i >> 1][4 * (i & 1)], t[i >> 1][4 * (i & 1) + 1], t[i >> 1][4 * (i & 1) + 2], t[i >> 1][4 * (i & 1) + 3]);
              }
              if (h == 1) { const float kn = max_norm(nrm); if (lane == 0) g_kn[((l >> 1) * 128 + bn * 8 + bm) * 16 + 8 + wg * 4 + w] = kn; }
              fence_async_smem();
              bar_arrive(NB_KV + 12 * h, 288);
              if (h == 0) {
                bar_arrive(wg ? NB_HALO : NB_DONE, 160);
              }
              if (h == 0) { const float kn = max_norm(nrm); if (lane == 0) g_kn[((l >> 1) * 128 + bn * 8 + bm) * 16 + wg * 4 + w] = kn; }
              norm_half(h, QSCALE, q[h], nrm, h ? -1 : 5);
#pragma unroll
              for (int i = 0; i < 4 * h; i++) sts128(sb + QPARK + 24576 - wg * 8192 + (w * 32 + lane) * 16 + i * 2048, q[h][i >> 1][4 * (i & 1)], q[h][i >> 1][4 * (i & 1) + 1], q[h][i >> 1][4 * (i & 1) + 2], q[h][i >> 1][4 * (i & 1) + 3]);
              qn[h] = max_norm(nrm);
            }
          }
          constexpr uint64_t VSTEP = 64 - (64ull << 16);
          uint32_t cq[4];
          const uint32_t &c_852 = cq[0], &c_lsb = cq[1], &c_half = cq[2];
          float o[2][20], S[2][32];
          uint32_t H[2][16], P0[4] = {}, P1[4] = {};
#pragma unroll
          for (int m = 0; m < 2; m++) {
#pragma unroll
            for (int i = 0; i < 20; i++) o[m][i] = 0.f;
            fence_regs(o[m]);
          }
          auto qkf = [&](int b, int ks, uint64_t d) { wg_n64_rs_nb_f16_f32(S[b], q[0][0][4 * ks], q[0][0][4 * ks + 1], q[0][0][4 * ks + 2], q[0][0][4 * ks + 3], d + 2 * ks, ks ? 1 : zero); };
          auto qkh = [&](int b, int ks, uint64_t d) { wg_n64_rs_nb_f16_f16(H[b], q[0][1][4 * ks], q[0][1][4 * ks + 1], q[0][1][4 * ks + 2], q[0][1][4 * ks + 3], d + 2 * ks, ks ? 1 : zero); };
          auto pv0 = [&](uint64_t d) { wgmma_m64n40k16_rs_tb(o[0], P0[0], P0[1], P0[2], P0[3], d, 1); };
          auto pv1 = [&](uint64_t d) { wgmma_m64n40k16_rs_tb(o[1], P1[0], P1[1], P1[2], P1[3], d, 1); };
          float e[4] = {};
          auto finish = [&](int h) {
            const float* s = &S[(h >> 2) & 1][8 * (h & 3)];
            const uint32_t* u = &H[(h >> 2) & 1][4 * (h & 3)];
            const float z0 = exp2_fix(s[6]), z1 = exp2_fix(s[7]);
            P0[0] = pack2v(e[0], e[1]);
            P1[0] = exp2_h2(u[0], c_852);
            P0[1] = pack2v(e[2], e[3]);
            P1[1] = exp2_h2(u[1], c_852);
            const uint32_t B = exp2_base(z0, z1), E = and_or<0x7F807F80u>(B, c_lsb);
            P1[3] = exp2_h2(u[3], c_852);
            P0[3] = fma_bf2(B, and_or<0x807F807Fu>(B, c_half), E);
            const float e4 = ex2v(s[4]), e5 = ex2v(s[5]);
            P1[2] = exp2_h2(u[2], c_852);
            P0[2] = pack2v(e4, e5);
          };
          auto start = [&](int h) {
            const float* s = &S[(h >> 2) & 1][8 * (h & 3)];
            e[2] = ex2v(s[2]); e[1] = ex2v(s[1]); e[0] = ex2v(s[0]); e[3] = ex2v(s[3]);
          };
          uint64_t kd = prm.kv[0].kd;
          mbar_wait(sb + B_TF, 0);
          lds128(sb + ROWST + 16 + (lane_id() & zero), cq);
#pragma unroll
          for (int i = 0; i < 4; i++) sts128(sb + QPARK + (wg * 128 + w * 32 + lane_id()) * 16 + i * 4096, q[0][i >> 1][4 * (i & 1)], q[0][i >> 1][4 * (i & 1) + 1], q[0][i >> 1][4 * (i & 1) + 2], q[0][i >> 1][4 * (i & 1) + 3]);
          wg_fence();
#pragma unroll
          for (int b = 0; b < 2; b++) {
            wg_n64_rs_nb_f16_f32_z(S[b], q[0][0][0], q[0][0][1], q[0][0][2], q[0][0][3], kd + 256 * b, 0);
            wg_n64_rs_nb_f16_f16_z(H[b], q[0][1][0], q[0][1][1], q[0][1][2], q[0][1][3], kd + 256 * b, 0);
            if (b == 0) { qkf(0, 1, kd); qkh(0, 1, kd); }
            wg_commit();
          }
          wg_wait<1>(); fence_regs(S[0]); fence_regs(H[0]);
          start(0); finish(0); start(1);
          wg_wait<0>();
          int redo = 0;
#pragma unroll 1
          for (int pass = 0, j = 1; pass < 2; pass++) {
#pragma unroll 1
           do {
            const uint64_t vd = prm.kv[j & 3].vd;
            bool go = false;
#pragma unroll
            for (int h = 2; h < 18; h++) {
              const int px = (h >> 2) + 1, c = h & 3;
              wg_fence();
              if (h == 13) kd = prm.kv[j & 3].kd;
              const uint64_t kx = kd + (px & 3) * 256, vx = vd + (h - 2) * VSTEP;
              if (h == 2) { qkh(1, 0, kx); qkf(1, 0, kx); pv0(vx); pv1(vx); qkh(1, 1, kx); qkf(1, 1, kx); }
              else if ((c == 1 || c == 2) && h < 17) { qkh(px & 1, c - 1, kx); pv1(vx); qkf(px & 1, c - 1, kx); pv0(vx); }
              else { pv0(vx); pv1(vx); }
              wg_commit();
              if (h == 3) e_arrive_if(sb + B_TE + 8 * ((j + 2) & 3), j > 1);
              if (h == 11) go = mbar_test(sb + B_TF + 8 * (j & 3), (j >> 2) & 1) && j != 8;
              finish(h - 1); start(h);
              if (h != 12 && h != 17) sched_fence();
              if (h == 12 && !go) {
                if (j == 16) {
#pragma unroll
                  for (int u = 13; u < 18; u++) {
                    wg_fence(); pv0(vd + (u - 2) * VSTEP); pv1(vd + (u - 2) * VSTEP); wg_commit();
                    if (u < 17) finish(u - 1);
                    if (u < 16) { start(u); sched_fence(); }
                    if (u & 1) { if (u == 17) wg_wait<0>(); else wg_wait<1>(); }
                  }
                  e_arrive(sb + B_TE + 24);
                  goto head_done;
                }
                mbar_wait(sb + B_TF + 8 * (j & 3), (j >> 2) & 1);
                if (j == 8) {
#pragma unroll
                  for (int i = 0; i < 4; i++) lds128(sb + QPARK + 24576 - wg * 8192 + (w * 32 + lane_id()) * 16 + i * 2048, &q[0][i >> 1][4 * (i & 1)]);
                }
              }
              if (h == 17) wg_wait<0>(); else if (h & 1) wg_wait<1>();
              if (c == 3) { fence_regs(S[px & 1]); fence_regs(H[px & 1]); }
            }
           } while (j++ & 7);
           head_done:
            fence_regs(o[0]); fence_regs(o[1]);
            uint32_t pk[2][8];
            {
              IDS();
              bf16* op = g_os + (size_t)(bm * 256 + row0 + (lane >> 2)) * 1024 + pass * 512 + bn * 32 + (lane & 3) * 8;
#pragma unroll
              for (int i = 0; i < 4; i++) {
                const float* a = &o[i >> 1][2 * (i & 1)];
                const float inv = rcp(a[16]);
                uint32_t* u = &pk[i >> 1][4 * (i & 1)];
#pragma unroll
                for (int k = 0; k < 4; k++) u[k] = pack2(a[4 * k] * inv, a[4 * k + 1] * inv);
                *(uint4*)(op + ((i >> 1) * 64 + (i & 1) * 8) * 1024) = make_uint4(u[0], u[1], u[2], u[3]);
              }
            }
            sched_fence();
            if (pass == 0) bar_sync(NB_KN + wg, 160);
            const float kmax = *(volatile float*)(smem + ROWST + 4 * pass);
            const bool wide = !(qn[0] + kmax <= 1.4e5f) | !(qn[0] * kmax <= 110.f * 110.f);
            int badm = 0;
#pragma unroll
            for (int m = 0; m < 2; m++) {
              uint32_t chk[2] = {0u, 0u};
#pragma unroll
              for (int i = 0; i < 8; i++) asm("fma.rn.bf16x2 %0, %1, %2, %0;" : "+r"(chk[i & 1]) : "r"(pk[m][i]), "r"(0u));
              const bool bad = wide | !(fminf(o[m][16], o[m][18]) >= 9.3e-10f) | !(o[m][16] + o[m][18] <= 1e36f) | (((chk[0] | chk[1]) & 0x7FFF7FFFu) != 0);
              badm |= __any_sync(~0u, bad) << m;
            }
            if (!badm) bar_arrive(NB_SIG + 2 * pass + wg, 160 + 32 * (pass & wg));
            qn[0] = qn[1];
#pragma unroll
            for (int m = 0; m < 2; m++) {
#pragma unroll
              for (int i = 0; i < 20; i++) o[m][i] = 0.f;
              fence_regs(o[m]);
            }
            if (badm) {
              redo |= badm << 2 * pass;
              const int tx = wg * 128 + w * 32 + lane_id();
              uint4* p = g_qsave + (block_id() * 256 + tx) * 8 + pass * 4;
#pragma unroll
              for (int i = 0; i < 4; i++) {
                uint32_t u[4] = {q[0][i >> 1][4 * (i & 1)], q[0][i >> 1][4 * (i & 1) + 1], q[0][i >> 1][4 * (i & 1) + 2], q[0][i >> 1][4 * (i & 1) + 3]};
                if (pass == 0) lds128(sb + QPARK + tx * 16 + i * 4096, u);
                p[i] = make_uint4(u[0], u[1], u[2], u[3]);
              }
            }
          }
          if (redo) attn_redo(redo, l, cta_id(), wg, w, ep1);
        }
      }
      {
        float acc[64];
        {
          const uint64_t da = l & 1 ? prm.xd + ((pslot_a(0, 1) + wg * 8192) >> 4) : prm.kv[0].kd + ((pslot_a(0, 0) - T0 + wg * 4096) >> 4);
          const uint64_t d2 = da + (l & 1 ? 4 : 512), db = prm.wd + (pslot_b(0) >> 4) - 2048;
          mbar_wait(sb + B_PF, l & 1);
          wg_fence();
          wgmma_m64n128k16_ss_tb_z(acc, da, db, 0);
#pragma unroll
          for (int k = 1; k < 4; k++) wgmma_m64n128k16_ss_tb(acc, (k & 2 ? d2 : da) + (k & 1) * 2, db + k * 128, 1);
          wg_commit();
        }
        uint32_t s = 1, lap = 0;
#pragma unroll 1
        for (int kt = 1; kt < 14; kt++) {
          mbar_wait(sb + B_PF + 8 * s, ((s < 4 ? l : 0) + lap) & 1);
          const uint64_t da = mkdesc(sb + pslot_a(s, l) + wg * 8192, 16, 1024, 1), db = mkdesc(sb + pslot_b(s), 8192, 1024, 1);
          wg_fence();
#pragma unroll
          for (int k = 0; k < 4; k++) wgmma_m64n128k16_ss_tb(acc, da + k * 2, db + k * 128, 1);
          wg_commit();
          wg_wait<1>();
          if (w == 0) e_arrive_both(sb + B_PE + 8 * (s ? s - 1 : 5));
          if (++s == 6) { s = 0; lap++; }
        }
        if (wg) {
          wg_wait<0>();
          if (w == 0) e_arrive_both(sb + B_PE + 8);
#pragma unroll
          for (int t = 2; t < 4; t++) mbar_wait(sb + B_PF + 8 * t, l & 1);
          bar_sync(NB_LAG, 256);
        }
#pragma unroll
        for (int t = 2; t < 4; t++) {
          if (!wg) mbar_wait(sb + B_PF + 8 * t, l & 1);
          const uint64_t da = prm.xd + ((pslot_a(t, l) + wg * 8192) >> 4), db = prm.wd + (pslot_b(t) >> 4) - 2048;
          wg_fence();
#pragma unroll
          for (int k = 0; k < 4; k++) wgmma_m64n128k16_ss_tb(acc, da + k * 2, db + k * 128, 1);
          wg_commit();
        }
        if (!wg) {
          bar_arrive(NB_LAG, 256);
          wg_wait<2>();
          if (w == 0) e_arrive_both(sb + B_PE + 8);
        }
        IDS();
        const int g = lane >> 2, qd = lane & 3;
        const int r0 = wg * 64 + w * 16;
        const uint32_t r = r0 + (lane & 7) + ((lane >> 3) & 1) * 8;
        uint32_t x[8][4];
        mbar_wait(sb + B_RF, 0);
#pragma unroll
        for (int jj = 0; jj < 8; jj++) ldsm4(sb + RES + (jj >> 2) * 16384 + r * 128 + ((((2 * jj + (lane >> 4)) & 7) ^ (r & 7)) << 4), x[jj]);
        wg_wait<0>();
        fence_regs(acc);
        if (w == 0) { e_arrive_both(sb + B_PE + 16); e_arrive_both(sb + B_PE + 24); }
        const CUtensorMap* mo = &prm.m[l == 3 ? M_OUT : M_XST];
        const bool direct = wg && l < 3;
        const uint32_t stg = sb + (direct ? po * 16384 : RES);
        if (direct) bar_sync(NB_SC, 256);
#pragma unroll
        for (int jj = 0; jj < 8; jj++) {
#pragma unroll
          for (int i = 0; i < 4; i++) x[jj][i] = add_bf16x2(x[jj][i], pack2(acc[8 * jj + 2 * i], acc[8 * jj + 2 * i + 1]));
          if (jj < 4) stsm4(stg + r * 128 + ((((2 * jj + (lane >> 4)) & 7) ^ (r & 7)) << 4), x[jj][0], x[jj][1], x[jj][2], x[jj][3]);
          if (jj == 3) { fence_async_smem(); __syncwarp(); tma_st(mo, pn * 128, pm * 128 + r0, stg + r0 * 128); bulk_commit(); sched_fence(); }
        }
        if (l < 3) bar_arrive(NB_KN, 288);
        if (l == 3) {
#pragma unroll
          for (int jj = 4; jj < 8; jj++) stsm4(sb + RES + 16384 + r * 128 + ((((2 * jj + (lane >> 4)) & 7) ^ (r & 7)) << 4), x[jj][0], x[jj][1], x[jj][2], x[jj][3]);
          fence_async_smem(); __syncwarp();
          tma_st(mo, pn * 128 + 64, pm * 128 + r0, sb + RES + 16384 + r0 * 128);
          bulk_commit(); bulk_wait_n<0>();
        } else {
          if (!wg) bar_sync(NB_SC, 256);
#pragma unroll
          for (int jj = 0; jj < 8; jj++)
            if (jj >= 4 || !wg) stsm4(sb + (jj >> 2) * 2 * QSTG + po * 16384 + r * 128 + ((((2 * jj + (lane >> 4)) & 7) ^ (r & 7)) << 4), x[jj][0], x[jj][1], x[jj][2], x[jj][3]);
          bulk_wait_n<0>();
          bar_arrive(NB_X0, 320);
          float s1[4] = {0.f, 0.f, 0.f, 0.f}, sa[4] = {0.f, 0.f, 0.f, 0.f}, sc[4] = {0.f, 0.f, 0.f, 0.f};
#pragma unroll
          for (int jj = 0; jj < 8; jj++) {
            mma16816(s1, x[jj][0], x[jj][1], x[jj][2], x[jj][3], 0x3f803f80u, 0x3f803f80u);
            mma16816(sa, x[jj][0], x[jj][1], x[jj][2], x[jj][3], x[jj][0], x[jj][2]);
            mma16816(sc, x[jj][0], x[jj][1], x[jj][2], x[jj][3], x[jj][1], x[jj][3]);
          }
          fence_regs(s1); fence_regs(sa); fence_regs(sc);
          fence_async_smem();
          sched_fence();
          bar_arrive(NB_X, 320);
          if (qd == g >> 1) {
            float2* p = g_stats + pn * 2048 + pm * 128 + r0 + g;
            p[0] = make_float2(s1[0], g & 1 ? sa[1] : sa[0]);
            p[8] = make_float2(s1[2], g & 1 ? sc[3] : sc[2]);
          }
          bar_arrive(NB_KV, 288);
        }
      }
    }
  }
  asm volatile("barrier.cluster.arrive.relaxed.aligned;\nbarrier.cluster.wait.aligned;" ::: "memory");
}

typedef CUresult (*EncodeFn)(CUtensorMap*, CUtensorMapDataType, cuuint32_t, void*, const cuuint64_t*, const cuuint64_t*, const cuuint32_t*,
                             const cuuint32_t*, CUtensorMapInterleave, CUtensorMapSwizzle, CUtensorMapL2promotion, CUtensorMapFloatOOBfill);

static void make_map(EncodeFn fn, CUtensorMap* m, const void* ptr, int rank, const uint64_t* dims, const uint64_t* strides, const uint32_t* box, CUtensorMapSwizzle sw) {
  cuuint64_t d[5], st[4];
  cuuint32_t bx[5], es[5];
  for (int i = 0; i < rank; i++) { d[i] = dims[i]; bx[i] = box[i]; es[i] = 1; if (i) st[i - 1] = strides[i - 1] * 2; }
  fn(m, CU_TENSOR_MAP_DATA_TYPE_BFLOAT16, rank, (void*)ptr, d, st, bx, es, CU_TENSOR_MAP_INTERLEAVE_NONE, sw,
     CU_TENSOR_MAP_L2_PROMOTION_L2_128B, CU_TENSOR_MAP_FLOAT_OOB_FILL_NONE);
}
static void map2(EncodeFn fn, CUtensorMap* m, const void* ptr, uint64_t inner, uint64_t outer, uint32_t bi, uint32_t bo, CUtensorMapSwizzle sw) {
  const uint64_t d[2] = {inner, outer}, st[1] = {inner};
  const uint32_t bx[2] = {bi, bo};
  make_map(fn, m, ptr, 2, d, st, bx, sw);
}

extern "C" void kernel_launch(void* const* d_in, const int* in_sizes, int n_in, void* d_out, int out_size) {
  (void)in_sizes; (void)n_in; (void)out_size;
  static EncodeFn enc = nullptr;
  static void *xs, *os, *kk, *vv;
  static int sbase = 1024;
  if (!enc) {
    void* p = nullptr;
    cudaDriverEntryPointQueryResult qr;
    cudaGetDriverEntryPoint("cuTensorMapEncodeTiled", &p, cudaEnableDefault, &qr);
    enc = (EncodeFn)p;
    Scratch* sc = nullptr;
    cudaGetSymbolAddress((void**)&sc, g_s);
    xs = sc->xs; os = sc->os; kk = sc->k; vv = sc->v;
    int dev = 0;
    cudaGetDevice(&dev);
    cudaDeviceGetAttribute(&sbase, cudaDevAttrReservedSharedMemoryPerBlock, dev);
    cudaFuncSetAttribute(fused_kernel, cudaFuncAttributeMaxDynamicSharedMemorySize, SMEM_BYTES);
  }
  Params prm;
  const CUtensorMapSwizzle S128 = CU_TENSOR_MAP_SWIZZLE_128B, S64 = CU_TENSOR_MAP_SWIZZLE_64B;
  map2(enc, &prm.m[M_X0A], d_in[0], 1024, 2048, 64, 256, S128);
  for (int t = 0; t < 2; t++) {
    const uint64_t d3[3] = {1024, 1024, 3}, s3[2] = {3072, 1024};
    const uint32_t b3[3] = {64, 64, 3};
    make_map(enc, &prm.m[M_WQA + t], d_in[1 + 3 * t], 3, d3, s3, b3, S128);
    const uint64_t d5[5] = {64, 32, 2, 16, 16}, s5[4] = {1024, 32 * 1024, 64 * 1024, 64};
    const uint32_t b5[5] = {64, 32, 1, 2, 2};
    make_map(enc, &prm.m[M_WOA + t], d_in[2 + 3 * t], 5, d5, s5, b5, S128);
    const uint64_t dr[3] = {64, 2048, 16}, sr[2] = {1024, 64};
    const uint32_t br[3] = {64, 128, 2};
    make_map(enc, &prm.m[M_X0R + t], t ? xs : d_in[0], 3, dr, sr, br, S128);
  }
  map2(enc, &prm.m[M_OS], os, 1024, 2048, 64, 64, S128);
  map2(enc, &prm.m[M_OL], os, 1024, 2048, 32, 128, S64);
  map2(enc, &prm.m[M_K], kk, 32, 65536, 32, 128, S64);
  map2(enc, &prm.m[M_V], vv, 32, 65536, 32, 128, S64);
  map2(enc, &prm.m[M_XSO], xs, 1024, 2048, 64, 128, S128);
  map2(enc, &prm.m[M_X0H], d_in[0], 1024, 2048, 64, 128, S128);
  map2(enc, &prm.m[M_XST], xs, 1024, 2048, 64, 16, S128);
  map2(enc, &prm.m[M_OUT], d_out, 1024, 2048, 64, 16, S128);
  prm.x0 = (const bf16*)d_in[0];
  prm.wq[0] = (const bf16*)d_in[1]; prm.wq[1] = (const bf16*)d_in[4];
  prm.wo = (const bf16*)d_in[2];
  prm.zero = 0;
  for (int i = 0; i < 128; i++) prm.map[i] = remap(i);
  {
    const uint64_t hi = 0x80000020ull << 32, k0 = sbase + T0, v0 = k0 + 16384, vstep = 64 - (64ull << 16);
    prm.wd = mkdesc(sbase + 32768, 8192, 1024, 1); prm.xd = mkdesc(sbase, 16, 1024, 1);
    for (int j = 0; j < 4; j++) {
      prm.kv[j].kd = (hi | 1u << 16 | k0 >> 4) + 2048 * ((j < 16 ? j : 15) & 3);
      prm.kv[j].vd = (hi | (uint64_t)(ONES - T0 - 16384) >> 4 << 16 | v0 >> 4) + 32 * vstep * ((j + 3) & 3);
    }
  }
  fused_kernel<<<128, 384, SMEM_BYTES>>>(prm);
}
```

```cpp
#include <cuda_runtime.h>
#include <cuda_bf16.h>
#include <cuda.h>
#include <stdint.h>

typedef __nv_bfloat16 bf16;

__device__ __forceinline__ void wgmma_m64n192k16_ss_tb(float (&d)[96], uint64_t da, uint64_t db, int scale_d) {
  asm volatile("{\n.reg .pred p;\nsetp.ne.b32 p, %98, 0;\n"
    "wgmma.mma_async.sync.aligned.m64n192k16.f32.bf16.bf16 "
    "{%0, %1, %2, %3, %4, %5, %6, %7, %8, %9, %10, %11, %12, %13, %14, %15, "
    "%16, %17, %18, %19, %20, %21, %22, %23, %24, %25, %26, %27, %28, %29, %30, %31, "
    "%32, %33, %34, %35, %36, %37, %38, %39, %40, %41, %42, %43, %44, %45, %46, %47, "
    "%48, %49, %50, %51, %52, %53, %54, %55, %56, %57, %58, %59, %60, %61, %62, %63, "
    "%64, %65, %66, %67, %68, %69, %70, %71, %72, %73, %74, %75, %76, %77, %78, %79, "
    "%80, %81, %82, %83, %84, %85, %86, %87, %88, %89, %90, %91, %92, %93, %94, %95}, "
    "%96, %97, p, 1, 1, 0, 1;\n}\n"
    : "+f"(d[0]), "+f"(d[1]), "+f"(d[2]), "+f"(d[3]), "+f"(d[4]), "+f"(d[5]), "+f"(d[6]), "+f"(d[7]),
      "+f"(d[8]), "+f"(d[9]), "+f"(d[10]), "+f"(d[11]), "+f"(d[12]), "+f"(d[13]), "+f"(d[14]), "+f"(d[15]),
      "+f"(d[16]), "+f"(d[17]), "+f"(d[18]), "+f"(d[19]), "+f"(d[20]), "+f"(d[21]), "+f"(d[22]), "+f"(d[23]),
      "+f"(d[24]), "+f"(d[25]), "+f"(d[26]), "+f"(d[27]), "+f"(d[28]), "+f"(d[29]), "+f"(d[30]), "+f"(d[31]),
      "+f"(d[32]), "+f"(d[33]), "+f"(d[34]), "+f"(d[35]), "+f"(d[36]), "+f"(d[37]), "+f"(d[38]), "+f"(d[39]),
      "+f"(d[40]), "+f"(d[41]), "+f"(d[42]), "+f"(d[43]), "+f"(d[44]), "+f"(d[45]), "+f"(d[46]), "+f"(d[47]),
      "+f"(d[48]), "+f"(d[49]), "+f"(d[50]), "+f"(d[51]), "+f"(d[52]), "+f"(d[53]), "+f"(d[54]), "+f"(d[55]),
      "+f"(d[56]), "+f"(d[57]), "+f"(d[58]), "+f"(d[59]), "+f"(d[60]), "+f"(d[61]), "+f"(d[62]), "+f"(d[63]),
      "+f"(d[64]), "+f"(d[65]), "+f"(d[66]), "+f"(d[67]), "+f"(d[68]), "+f"(d[69]), "+f"(d[70]), "+f"(d[71]),
      "+f"(d[72]), "+f"(d[73]), "+f"(d[74]), "+f"(d[75]), "+f"(d[76]), "+f"(d[77]), "+f"(d[78]), "+f"(d[79]),
      "+f"(d[80]), "+f"(d[81]), "+f"(d[82]), "+f"(d[83]), "+f"(d[84]), "+f"(d[85]), "+f"(d[86]), "+f"(d[87]),
      "+f"(d[88]), "+f"(d[89]), "+f"(d[90]), "+f"(d[91]), "+f"(d[92]), "+f"(d[93]), "+f"(d[94]), "+f"(d[95])
    : "l"(da), "l"(db), "r"(scale_d));
}

__device__ __forceinline__ void wgmma_m64n192k16_ss_tb_z(float (&d)[96], uint64_t da, uint64_t db, int scale_d) {
  asm volatile("{\n.reg .pred p;\nsetp.ne.b32 p, %98, 0;\n"
    "wgmma.mma_async.sync.aligned.m64n192k16.f32.bf16.bf16 "
    "{%0, %1, %2, %3, %4, %5, %6, %7, %8, %9, %10, %11, %12, %13, %14, %15, "
    "%16, %17, %18, %19, %20, %21, %22, %23, %24, %25, %26, %27, %28, %29, %30, %31, "
    "%32, %33, %34, %35, %36, %37, %38, %39, %40, %41, %42, %43, %44, %45, %46, %47, "
    "%48, %49, %50, %51, %52, %53, %54, %55, %56, %57, %58, %59, %60, %61, %62, %63, "
    "%64, %65, %66, %67, %68, %69, %70, %71, %72, %73, %74, %75, %76, %77, %78, %79, "
    "%80, %81, %82, %83, %84, %85, %86, %87, %88, %89, %90, %91, %92, %93, %94, %95}, "
    "%96, %97, p, 1, 1, 0, 1;\n}\n"
    : "=f"(d[0]), "=f"(d[1]), "=f"(d[2]), "=f"(d[3]), "=f"(d[4]), "=f"(d[5]), "=f"(d[6]), "=f"(d[7]),
      "=f"(d[8]), "=f"(d[9]), "=f"(d[10]), "=f"(d[11]), "=f"(d[12]), "=f"(d[13]), "=f"(d[14]), "=f"(d[15]),
      "=f"(d[16]), "=f"(d[17]), "=f"(d[18]), "=f"(d[19]), "=f"(d[20]), "=f"(d[21]), "=f"(d[22]), "=f"(d[23]),
      "=f"(d[24]), "=f"(d[25]), "=f"(d[26]), "=f"(d[27]), "=f"(d[28]), "=f"(d[29]), "=f"(d[30]), "=f"(d[31]),
      "=f"(d[32]), "=f"(d[33]), "=f"(d[34]), "=f"(d[35]), "=f"(d[36]), "=f"(d[37]), "=f"(d[38]), "=f"(d[39]),
      "=f"(d[40]), "=f"(d[41]), "=f"(d[42]), "=f"(d[43]), "=f"(d[44]), "=f"(d[45]), "=f"(d[46]), "=f"(d[47]),
      "=f"(d[48]), "=f"(d[49]), "=f"(d[50]), "=f"(d[51]), "=f"(d[52]), "=f"(d[53]), "=f"(d[54]), "=f"(d[55]),
      "=f"(d[56]), "=f"(d[57]), "=f"(d[58]), "=f"(d[59]), "=f"(d[60]), "=f"(d[61]), "=f"(d[62]), "=f"(d[63]),
      "=f"(d[64]), "=f"(d[65]), "=f"(d[66]), "=f"(d[67]), "=f"(d[68]), "=f"(d[69]), "=f"(d[70]), "=f"(d[71]),
      "=f"(d[72]), "=f"(d[73]), "=f"(d[74]), "=f"(d[75]), "=f"(d[76]), "=f"(d[77]), "=f"(d[78]), "=f"(d[79]),
      "=f"(d[80]), "=f"(d[81]), "=f"(d[82]), "=f"(d[83]), "=f"(d[84]), "=f"(d[85]), "=f"(d[86]), "=f"(d[87]),
      "=f"(d[88]), "=f"(d[89]), "=f"(d[90]), "=f"(d[91]), "=f"(d[92]), "=f"(d[93]), "=f"(d[94]), "=f"(d[95])
    : "l"(da), "l"(db), "r"(scale_d));
}

__device__ __forceinline__ void wgmma_m64n128k16_ss_tb(float (&d)[64], uint64_t da, uint64_t db, int scale_d) {
  asm volatile("{\n.reg .pred p;\nsetp.ne.b32 p, %66, 0;\n"
    "wgmma.mma_async.sync.aligned.m64n128k16.f32.bf16.bf16 "
    "{%0, %1, %2, %3, %4, %5, %6, %7, %8, %9, %10, %11, %12, %13, %14, %15, "
    "%16, %17, %18, %19, %20, %21, %22, %23, %24, %25, %26, %27, %28, %29, %30, %31, "
    "%32, %33, %34, %35, %36, %37, %38, %39, %40, %41, %42, %43, %44, %45, %46, %47, "
    "%48, %49, %50, %51, %52, %53, %54, %55, %56, %57, %58, %59, %60, %61, %62, %63}, "
    "%64, %65, p, 1, 1, 0, 1;\n}\n"
    : "+f"(d[0]), "+f"(d[1]), "+f"(d[2]), "+f"(d[3]), "+f"(d[4]), "+f"(d[5]), "+f"(d[6]), "+f"(d[7]),
      "+f"(d[8]), "+f"(d[9]), "+f"(d[10]), "+f"(d[11]), "+f"(d[12]), "+f"(d[13]), "+f"(d[14]), "+f"(d[15]),
      "+f"(d[16]), "+f"(d[17]), "+f"(d[18]), "+f"(d[19]), "+f"(d[20]), "+f"(d[21]), "+f"(d[22]), "+f"(d[23]),
      "+f"(d[24]), "+f"(d[25]), "+f"(d[26]), "+f"(d[27]), "+f"(d[28]), "+f"(d[29]), "+f"(d[30]), "+f"(d[31]),
      "+f"(d[32]), "+f"(d[33]), "+f"(d[34]), "+f"(d[35]), "+f"(d[36]), "+f"(d[37]), "+f"(d[38]), "+f"(d[39]),
      "+f"(d[40]), "+f"(d[41]), "+f"(d[42]), "+f"(d[43]), "+f"(d[44]), "+f"(d[45]), "+f"(d[46]), "+f"(d[47]),
      "+f"(d[48]), "+f"(d[49]), "+f"(d[50]), "+f"(d[51]), "+f"(d[52]), "+f"(d[53]), "+f"(d[54]), "+f"(d[55]),
      "+f"(d[56]), "+f"(d[57]), "+f"(d[58]), "+f"(d[59]), "+f"(d[60]), "+f"(d[61]), "+f"(d[62]), "+f"(d[63])
    : "l"(da), "l"(db), "r"(scale_d));
}

__device__ __forceinline__ void wgmma_m64n128k16_ss_tb_z(float (&d)[64], uint64_t da, uint64_t db, int scale_d) {
  asm volatile("{\n.reg .pred p;\nsetp.ne.b32 p, %66, 0;\n"
    "wgmma.mma_async.sync.aligned.m64n128k16.f32.bf16.bf16 "
    "{%0, %1, %2, %3, %4, %5, %6, %7, %8, %9, %10, %11, %12, %13, %14, %15, "
    "%16, %17, %18, %19, %20, %21, %22, %23, %24, %25, %26, %27, %28, %29, %30, %31, "
    "%32, %33, %34, %35, %36, %37, %38, %39, %40, %41, %42, %43, %44, %45, %46, %47, "
    "%48, %49, %50, %51, %52, %53, %54, %55, %56, %57, %58, %59, %60, %61, %62, %63}, "
    "%64, %65, p, 1, 1, 0, 1;\n}\n"
    : "=f"(d[0]), "=f"(d[1]), "=f"(d[2]), "=f"(d[3]), "=f"(d[4]), "=f"(d[5]), "=f"(d[6]), "=f"(d[7]),
      "=f"(d[8]), "=f"(d[9]), "=f"(d[10]), "=f"(d[11]), "=f"(d[12]), "=f"(d[13]), "=f"(d[14]), "=f"(d[15]),
      "=f"(d[16]), "=f"(d[17]), "=f"(d[18]), "=f"(d[19]), "=f"(d[20]), "=f"(d[21]), "=f"(d[22]), "=f"(d[23]),
      "=f"(d[24]), "=f"(d[25]), "=f"(d[26]), "=f"(d[27]), "=f"(d[28]), "=f"(d[29]), "=f"(d[30]), "=f"(d[31]),
      "=f"(d[32]), "=f"(d[33]), "=f"(d[34]), "=f"(d[35]), "=f"(d[36]), "=f"(d[37]), "=f"(d[38]), "=f"(d[39]),
      "=f"(d[40]), "=f"(d[41]), "=f"(d[42]), "=f"(d[43]), "=f"(d[44]), "=f"(d[45]), "=f"(d[46]), "=f"(d[47]),
      "=f"(d[48]), "=f"(d[49]), "=f"(d[50]), "=f"(d[51]), "=f"(d[52]), "=f"(d[53]), "=f"(d[54]), "=f"(d[55]),
      "=f"(d[56]), "=f"(d[57]), "=f"(d[58]), "=f"(d[59]), "=f"(d[60]), "=f"(d[61]), "=f"(d[62]), "=f"(d[63])
    : "l"(da), "l"(db), "r"(scale_d));
}

__device__ __forceinline__ void wgmma_m64n40k16_rs_tb(float (&d)[20], uint32_t a0, uint32_t a1, uint32_t a2, uint32_t a3, uint64_t db, int scale_d) {
  asm volatile("{\n.reg .pred p;\nsetp.ne.b32 p, %25, 0;\n"
    "wgmma.mma_async.sync.aligned.m64n40k16.f32.bf16.bf16 "
    "{%0, %1, %2, %3, %4, %5, %6, %7, %8, %9, %10, %11, %12, %13, %14, %15, "
    "%16, %17, %18, %19}, "
    "{%20, %21, %22, %23}, %24, p, 1, 1, 1;\n}\n"
    : "+f"(d[0]), "+f"(d[1]), "+f"(d[2]), "+f"(d[3]), "+f"(d[4]), "+f"(d[5]), "+f"(d[6]), "+f"(d[7]),
      "+f"(d[8]), "+f"(d[9]), "+f"(d[10]), "+f"(d[11]), "+f"(d[12]), "+f"(d[13]), "+f"(d[14]), "+f"(d[15]),
      "+f"(d[16]), "+f"(d[17]), "+f"(d[18]), "+f"(d[19])
    : "r"(a0), "r"(a1), "r"(a2), "r"(a3), "l"(db), "r"(scale_d));
}

__device__ __forceinline__ void wg_n64_rs_nb_f16_f32(float (&d)[32], uint32_t a0, uint32_t a1, uint32_t a2, uint32_t a3, uint64_t db, int scale_d) {
  asm volatile("{\n.reg .pred p;\nsetp.ne.b32 p, %37, 0;\n"
    "wgmma.mma_async.sync.aligned.m64n64k16.f32.f16.f16 "
    "{%0, %1, %2, %3, %4, %5, %6, %7, %8, %9, %10, %11, %12, %13, %14, %15, "
    "%16, %17, %18, %19, %20, %21, %22, %23, %24, %25, %26, %27, %28, %29, %30, %31}, "
    "{%32, %33, %34, %35}, %36, p, 1, 1, 0;\n}\n"
    : "+f"(d[0]), "+f"(d[1]), "+f"(d[2]), "+f"(d[3]), "+f"(d[4]), "+f"(d[5]), "+f"(d[6]), "+f"(d[7]),
      "+f"(d[8]), "+f"(d[9]), "+f"(d[10]), "+f"(d[11]), "+f"(d[12]), "+f"(d[13]), "+f"(d[14]), "+f"(d[15]),
      "+f"(d[16]), "+f"(d[17]), "+f"(d[18]), "+f"(d[19]), "+f"(d[20]), "+f"(d[21]), "+f"(d[22]), "+f"(d[23]),
      "+f"(d[24]), "+f"(d[25]), "+f"(d[26]), "+f"(d[27]), "+f"(d[28]), "+f"(d[29]), "+f"(d[30]), "+f"(d[31])
    : "r"(a0), "r"(a1), "r"(a2), "r"(a3), "l"(db), "r"(scale_d));
}

__device__ __forceinline__ void wg_n64_rs_nb_f16_f16(uint32_t (&d)[16], uint32_t a0, uint32_t a1, uint32_t a2, uint32_t a3, uint64_t db, int scale_d) {
  asm volatile("{\n.reg .pred p;\nsetp.ne.b32 p, %21, 0;\n"
    "wgmma.mma_async.sync.aligned.m64n64k16.f16.f16.f16 "
    "{%0, %1, %2, %3, %4, %5, %6, %7, %8, %9, %10, %11, %12, %13, %14, %15}, "
    "{%16, %17, %18, %19}, %20, p, 1, 1, 0;\n}\n"
    : "+r"(d[0]), "+r"(d[1]), "+r"(d[2]), "+r"(d[3]), "+r"(d[4]), "+r"(d[5]), "+r"(d[6]), "+r"(d[7]),
      "+r"(d[8]), "+r"(d[9]), "+r"(d[10]), "+r"(d[11]), "+r"(d[12]), "+r"(d[13]), "+r"(d[14]), "+r"(d[15])
    : "r"(a0), "r"(a1), "r"(a2), "r"(a3), "l"(db), "r"(scale_d));
}

__device__ __forceinline__ void wg_n64_rs_nb_f16_f32_z(float (&d)[32], uint32_t a0, uint32_t a1, uint32_t a2, uint32_t a3, uint64_t db, int scale_d) {
  asm volatile("{\n.reg .pred p;\nsetp.ne.b32 p, %37, 0;\n"
    "wgmma.mma_async.sync.aligned.m64n64k16.f32.f16.f16 "
    "{%0, %1, %2, %3, %4, %5, %6, %7, %8, %9, %10, %11, %12, %13, %14, %15, "
    "%16, %17, %18, %19, %20, %21, %22, %23, %24, %25, %26, %27, %28, %29, %30, %31}, "
    "{%32, %33, %34, %35}, %36, p, 1, 1, 0;\n}\n"
    : "=f"(d[0]), "=f"(d[1]), "=f"(d[2]), "=f"(d[3]), "=f"(d[4]), "=f"(d[5]), "=f"(d[6]), "=f"(d[7]),
      "=f"(d[8]), "=f"(d[9]), "=f"(d[10]), "=f"(d[11]), "=f"(d[12]), "=f"(d[13]), "=f"(d[14]), "=f"(d[15]),
      "=f"(d[16]), "=f"(d[17]), "=f"(d[18]), "=f"(d[19]), "=f"(d[20]), "=f"(d[21]), "=f"(d[22]), "=f"(d[23]),
      "=f"(d[24]), "=f"(d[25]), "=f"(d[26]), "=f"(d[27]), "=f"(d[28]), "=f"(d[29]), "=f"(d[30]), "=f"(d[31])
    : "r"(a0), "r"(a1), "r"(a2), "r"(a3), "l"(db), "r"(scale_d));
}

__device__ __forceinline__ void wg_n64_rs_nb_f16_f16_z(uint32_t (&d)[16], uint32_t a0, uint32_t a1, uint32_t a2, uint32_t a3, uint64_t db, int scale_d) {
  asm volatile("{\n.reg .pred p;\nsetp.ne.b32 p, %21, 0;\n"
    "wgmma.mma_async.sync.aligned.m64n64k16.f16.f16.f16 "
    "{%0, %1, %2, %3, %4, %5, %6, %7, %8, %9, %10, %11, %12, %13, %14, %15}, "
    "{%16, %17, %18, %19}, %20, p, 1, 1, 0;\n}\n"
    : "=r"(d[0]), "=r"(d[1]), "=r"(d[2]), "=r"(d[3]), "=r"(d[4]), "=r"(d[5]), "=r"(d[6]), "=r"(d[7]),
      "=r"(d[8]), "=r"(d[9]), "=r"(d[10]), "=r"(d[11]), "=r"(d[12]), "=r"(d[13]), "=r"(d[14]), "=r"(d[15])
    : "r"(a0), "r"(a1), "r"(a2), "r"(a3), "l"(db), "r"(scale_d));
}

#define DEVINL __device__ __forceinline__
DEVINL void wg_fence() { asm volatile("wgmma.fence.sync.aligned;" ::: "memory"); }
DEVINL void wg_commit() { asm volatile("wgmma.commit_group.sync.aligned;" ::: "memory"); }
template <int N> DEVINL void wg_wait() { asm volatile("wgmma.wait_group.sync.aligned %0;" ::"n"(N) : "memory"); }
__host__ DEVINL uint64_t mkdesc(uint32_t addr, uint32_t lbo, uint32_t sbo, int sw) {
  return (uint64_t)((addr & 0x3FFFF) >> 4) | ((uint64_t)(lbo >> 4) << 16) | ((uint64_t)(sbo >> 4) << 32) | ((uint64_t)sw << 62);
}
DEVINL bool mbar_try(uint32_t bar, uint32_t parity) {
  uint32_t ok;
  asm volatile("{\n.reg .pred p;\nmbarrier.try_wait.parity.shared::cta.b64 p, [%1], %2;\nselp.u32 %0, 1, 0, p;\n}" : "=r"(ok) : "r"(bar), "r"(parity) : "memory");
  return ok;
}
DEVINL bool mbar_test(uint32_t bar, uint32_t parity) {
  uint32_t ok;
  asm volatile("{\n.reg .pred p;\nmbarrier.test_wait.parity.shared::cta.b64 p, [%1], %2;\nselp.u32 %0, 1, 0, p;\n}" : "=r"(ok) : "r"(bar), "r"(parity) : "memory");
  return ok;
}
DEVINL void mbar_hint(uint32_t bar, uint32_t parity) {
#pragma unroll 1
  for (uint32_t n = 0; n < 32u; n++) if (mbar_try(bar, parity)) break;
}
DEVINL void mbar_wait(uint32_t bar, uint32_t parity) {
#pragma unroll 1
  for (uint32_t n = 0; n < 100000u; n++) if (mbar_try(bar, parity)) break;
}
#define EL(txt) "{\n.reg .pred pe;\nelect.sync _|pe, 0xffffffff;\n@pe " txt "\n}"
DEVINL void e_expect_tx(uint32_t bar, uint32_t bytes) { asm volatile(EL("mbarrier.arrive.expect_tx.shared::cta.b64 _, [%0], %1;") ::"r"(bar), "r"(bytes) : "memory"); }
DEVINL void e_arrive(uint32_t bar) { asm volatile(EL("mbarrier.arrive.shared::cta.b64 _, [%0];") ::"r"(bar) : "memory"); }
DEVINL void e_arrive_if(uint32_t bar, int c) {
  asm volatile("{\n.reg .pred pe;\nelect.sync _|pe, 0xffffffff;\nsetp.ne.and.b32 pe, %1, 0, pe;\n@pe mbarrier.arrive.shared::cta.b64 _, [%0];\n}" ::"r"(bar), "r"(c) : "memory");
}
DEVINL void e_red(uint32_t* p) { asm volatile(EL("red.release.gpu.global.add.u32 [%0], 1;") ::"l"(p) : "memory"); }
DEVINL void e_red_relaxed(uint32_t* p) { asm volatile(EL("red.relaxed.gpu.global.add.u32 [%0], 1;") ::"l"(p) : "memory"); }
DEVINL void release_add(uint32_t* p, int on) {
  asm volatile("{\n.reg .pred q;\nsetp.ne.b32 q, %1, 0;\nfence.release.gpu;\n@q red.relaxed.gpu.global.add.u32 [%0], 1;\n}" ::"l"(p), "r"(on) : "memory");
}
#define PREPARED(p, on) do { asm volatile("" : "+l"(p), "+r"(on)); asm volatile("griddepcontrol.launch_dependents;" ::: "memory"); } while (0)
DEVINL void tma_ld(uint32_t dst, const CUtensorMap* m, int c0, int c1, uint32_t bar) {
  asm volatile(EL("cp.async.bulk.tensor.2d.shared::cluster.global.mbarrier::complete_tx::bytes [%0], [%1, {%3, %4}], [%2];")
               ::"r"(dst), "l"(m), "r"(bar), "r"(c0), "r"(c1) : "memory");
}
DEVINL void tma_ld3(uint32_t dst, const CUtensorMap* m, int c0, int c1, int c2, uint32_t bar) {
  asm volatile(EL("cp.async.bulk.tensor.3d.shared::cluster.global.mbarrier::complete_tx::bytes [%0], [%1, {%3, %4, %5}], [%2];")
               ::"r"(dst), "l"(m), "r"(bar), "r"(c0), "r"(c1), "r"(c2) : "memory");
}
DEVINL void tma_ld5(uint32_t dst, const CUtensorMap* m, int c2, int c3, int c4, uint32_t bar) {
  asm volatile(EL("cp.async.bulk.tensor.5d.shared::cluster.global.mbarrier::complete_tx::bytes [%0], [%1, {0, 0, %3, %4, %5}], [%2];")
               ::"r"(dst), "l"(m), "r"(bar), "r"(c2), "r"(c3), "r"(c4) : "memory");
}
DEVINL void tma_ld_mc(uint32_t dst, const CUtensorMap* m, int c0, int c1, uint32_t bar, uint16_t mask = 3) {
  asm volatile(EL("cp.async.bulk.tensor.2d.shared::cluster.global.mbarrier::complete_tx::bytes.multicast::cluster [%0], [%1, {%3, %4}], [%2], %5;")
               ::"r"(dst), "l"(m), "r"(bar), "r"(c0), "r"(c1), "h"(mask) : "memory");
}
DEVINL void e_arrive_both(uint32_t bar) {
  asm volatile("{\n.reg .pred pe;\n.reg .b32 r0, r1;\nelect.sync _|pe, 0xffffffff;\nmapa.shared::cluster.u32 r0, %0, 0;\nmapa.shared::cluster.u32 r1, %0, 1;\n"
               "@pe mbarrier.arrive.shared::cluster.b64 _, [r0];\n@pe mbarrier.arrive.shared::cluster.b64 _, [r1];\n}" ::"r"(bar) : "memory");
}
DEVINL void tma_st(const CUtensorMap* m, int c0, int c1, uint32_t src) {
  asm volatile(EL("cp.async.bulk.tensor.2d.global.shared::cta.bulk_group [%0, {%2, %3}], [%1];") ::"l"(m), "r"(src), "r"(c0), "r"(c1) : "memory");
}
DEVINL void bulk_commit() { asm volatile("cp.async.bulk.commit_group;" ::: "memory"); }
template <int N> DEVINL void bulk_wait_n() { asm volatile("cp.async.bulk.wait_group %0;\nbar.warp.sync 0xffffffff;" ::"n"(N) : "memory"); }
DEVINL void l2_prefetch(const void* g, uint32_t bytes) { asm volatile(EL("cp.async.bulk.prefetch.L2.global [%0], %1;") ::"l"(g), "r"(bytes) : "memory"); }
DEVINL void fence_async_smem() { asm volatile("fence.proxy.async.shared::cta;" ::: "memory"); }
DEVINL void fence_async_gl() { asm volatile("fence.proxy.async.global;" ::: "memory"); }
DEVINL void cluster_wait() { asm volatile("barrier.cluster.wait.aligned;" ::: "memory"); }
DEVINL void bar_sync(int id, int n) { asm volatile("bar.sync %0, %1;" ::"r"(id), "r"(n) : "memory"); }
DEVINL void bar_arrive(int id, int n) { asm volatile("bar.arrive %0, %1;" ::"r"(id), "r"(n) : "memory"); }
DEVINL uint32_t ld_acquire(const uint32_t* p) { uint32_t v; asm volatile("ld.acquire.gpu.global.u32 %0, [%1];" : "=r"(v) : "l"(p) : "memory"); return v; }
DEVINL void await_flag(int j, uint32_t& rdy, const uint32_t* p, uint32_t target) {
  if ((rdy >> j) & 1) return;
#pragma unroll 1
  for (uint32_t n = 0; n < 200000u && !((rdy >> j) & 1); n++) rdy = __ballot_sync(~0u, (int)(ld_acquire(p) - target) >= 0);
  asm volatile("fence.proxy.async.global;" ::: "memory");
}
DEVINL void poll_ge(const uint32_t* p, uint32_t target) {
#pragma unroll 1
  for (uint32_t n = 0; n < 200000u; n++) if (__all_sync(~0u, (int)(ld_acquire(p) - target) >= 0)) break;
}
DEVINL int lane_id() { int v; asm volatile("mov.u32 %0, %%laneid;" : "=r"(v)); return v; }
__host__ DEVINL int remap(int v) {
  const int c = v >> 1, u = c - 36, r = (u * 37) >> 8;
  const int L = c < 4 ? 32 + 8 * c : c < 36 ? c - 4 : 33 + u + r;
  return 2 * L + (v & 1);
}
DEVINL int block_id() { int v; asm volatile("mov.u32 %0, %%ctaid.x;" : "=r"(v)); return v; }
#define cta_id() prm.map[block_id()]
#define IDS() const int lane = lane_id(), b = cta_id(), bm = b >> 4, bn = b & 15, rank = b & 1, pm = 2 * bm + (bn >> 3), pn = bn & 7, po = pm & 1; \
  (void)lane; (void)bm; (void)bn; (void)rank; (void)pm; (void)pn; (void)po
DEVINL void st_tagged(uint4* p, uint32_t a, uint32_t b, uint32_t c, uint32_t tag) {
  asm volatile("{\n.reg .b64 u, v;\n.reg .b128 t;\nmov.b64 u, {%1, %2};\nmov.b64 v, {%3, %4};\nmov.b128 t, {u, v};\nst.relaxed.gpu.global.b128 [%0], t;\n}"
               ::"l"(p), "r"(a), "r"(b), "r"(c), "r"(tag) : "memory");
}
DEVINL uint32_t ld_tagged(const uint4* p, uint32_t* r) {
  uint32_t tag;
  asm volatile("{\n.reg .b64 u, v;\n.reg .b128 t;\nld.relaxed.gpu.global.b128 t, [%4];\nmov.b128 {u, v}, t;\nmov.b64 {%0, %1}, u;\nmov.b64 {%2, %3}, v;\n}"
               : "=r"(r[0]), "=r"(r[1]), "=r"(r[2]), "=r"(tag) : "l"(p) : "memory");
  return tag;
}
DEVINL float ex2(float x) { float y; asm("ex2.approx.ftz.f32 %0, %1;" : "=f"(y) : "f"(x)); return y; }
DEVINL float rcp(float x) { float y; asm("rcp.approx.ftz.f32 %0, %1;" : "=f"(y) : "f"(x)); return y; }
DEVINL uint32_t pack2(float lo, float hi) { uint32_t r; asm("cvt.rn.bf16x2.f32 %0, %1, %2;" : "=r"(r) : "f"(hi), "f"(lo)); return r; }
DEVINL uint32_t pack2h(float lo, float hi) { uint32_t r; asm("cvt.rz.f16x2.f32 %0, %1, %2;" : "=r"(r) : "f"(hi), "f"(lo)); return r; }
DEVINL uint32_t prmt0(uint32_t a, uint32_t sel) { uint32_t r; asm("prmt.b32 %0, %1, 0, %2;" : "=r"(r) : "r"(a), "r"(sel)); return r; }
DEVINL void stg128(const void* p, uint32_t a, uint32_t b, uint32_t c, uint32_t d) {
  asm volatile("st.global.v4.b32 [%0], {%1, %2, %3, %4};" ::"l"(p), "r"(a), "r"(b), "r"(c), "r"(d) : "memory");
}
DEVINL uint32_t hadd2(uint32_t a, uint32_t b) { uint32_t r; asm("add.rn.f16x2 %0, %1, %2;" : "=r"(r) : "r"(a), "r"(b)); return r; }
DEVINL uint32_t hfma2(uint32_t a, uint32_t b, uint32_t c) { uint32_t r; asm("fma.rn.f16x2 %0, %1, %2, %3;" : "=r"(r) : "r"(a), "r"(b), "r"(c)); return r; }
DEVINL float bf_lo(uint32_t w) { return __uint_as_float(w << 16); }
DEVINL float bf_hi(uint32_t w) { return __uint_as_float(w & 0xFFFF0000u); }
DEVINL float bf_round(float x) { return bf_lo(pack2(x, 0.f)); }
DEVINL uint32_t add_bf16x2(uint32_t a, uint32_t b) { uint32_t r; asm("add.rn.bf16x2 %0, %1, %2;" : "=r"(r) : "r"(a), "r"(b)); return r; }
DEVINL void stsm4(uint32_t addr, uint32_t a, uint32_t b, uint32_t c, uint32_t d) {
  asm volatile("stmatrix.sync.aligned.m8n8.x4.shared.b16 [%0], {%1, %2, %3, %4};" ::"r"(addr), "r"(a), "r"(b), "r"(c), "r"(d) : "memory");
}
DEVINL void ldsm4(uint32_t addr, uint32_t (&r)[4]) {
  asm volatile("ldmatrix.sync.aligned.m8n8.x4.shared.b16 {%0, %1, %2, %3}, [%4];" : "=r"(r[0]), "=r"(r[1]), "=r"(r[2]), "=r"(r[3]) : "r"(addr) : "memory");
}
DEVINL void ldsm4t(uint32_t addr, uint32_t (&r)[4]) {
  asm volatile("ldmatrix.sync.aligned.m8n8.x4.trans.shared.b16 {%0, %1, %2, %3}, [%4];" : "=r"(r[0]), "=r"(r[1]), "=r"(r[2]), "=r"(r[3]) : "r"(addr) : "memory");
}
DEVINL void sts128(uint32_t addr, uint32_t a, uint32_t b, uint32_t c, uint32_t d) {
  asm volatile("st.shared.v4.b32 [%0], {%1, %2, %3, %4};" ::"r"(addr), "r"(a), "r"(b), "r"(c), "r"(d) : "memory");
}
DEVINL float2 lds64f(uint32_t addr) { float2 v; asm volatile("ld.shared.v2.f32 {%0, %1}, [%2];" : "=f"(v.x), "=f"(v.y) : "r"(addr) : "memory"); return v; }
DEVINL void mma16816(float (&d)[4], uint32_t a0, uint32_t a1, uint32_t a2, uint32_t a3, uint32_t b0, uint32_t b1) {
  asm("mma.sync.aligned.m16n8k16.row.col.f32.bf16.bf16.f32 {%0, %1, %2, %3}, {%4, %5, %6, %7}, {%8, %9}, {%0, %1, %2, %3};"
               : "+f"(d[0]), "+f"(d[1]), "+f"(d[2]), "+f"(d[3]) : "r"(a0), "r"(a1), "r"(a2), "r"(a3), "r"(b0), "r"(b1));
}
template <int N> DEVINL void fence_regs(float (&d)[N]) {
#pragma unroll
  for (int i = 0; i < N; i++) asm volatile("" : "+f"(d[i])::"memory");
}
template <int N> DEVINL void fence_regs(uint32_t (&d)[N]) {
#pragma unroll
  for (int i = 0; i < N; i++) asm volatile("" : "+r"(d[i])::"memory");
}
DEVINL void lds128(uint32_t addr, uint32_t* r) {
  asm volatile("ld.shared.v4.b32 {%0, %1, %2, %3}, [%4];" : "=r"(r[0]), "=r"(r[1]), "=r"(r[2]), "=r"(r[3]) : "r"(addr) : "memory");
}
DEVINL void sched_fence() { asm volatile("griddepcontrol.launch_dependents;" ::: "memory"); }

struct Scratch {
  bf16 k[32 * 2048 * 32];
  bf16 xs[2048 * 1024];
  bf16 os[2048 * 1024];
  bf16 v[32 * 2048 * 32];
  float kn[2 * 128 * 16];
  uint32_t cnt[256 * 32];
  float2 stats[8 * 2048];
  uint4 halo[128 * 12 * 32];
  float csp[2 * 16 * 8 * 192];
  uint4 qsave[128 * 256 * 8];
  uint32_t esc[4 * 65536 * 20];
};
__device__ __align__(1024) Scratch g_s;
#define g_k g_s.k
#define g_xs g_s.xs
#define g_os g_s.os
#define g_v g_s.v
#define g_kn g_s.kn
#define g_cnt g_s.cnt
#define g_stats g_s.stats
#define g_halo g_s.halo
#define g_csp g_s.csp
#define g_qsave g_s.qsave
#define g_esc g_s.esc
#define g_epoch g_s.cnt[255 * 32]

DEVINL uint32_t* cnt_x(int bm) { return g_cnt + bm * 32; }
DEVINL uint32_t* cnt_o(int l, int pm, int h) { return g_cnt + (32 + (l * 16 + pm) * 2 + h) * 32; }
DEVINL uint32_t* cnt_kv(int lb, int bn) { return g_cnt + (160 + lb * 16 + bn) * 32; }
DEVINL uint32_t* cnt_ad(int bn) { return g_cnt + (192 + bn) * 32; }
DEVINL uint32_t* cnt_cs(int t, int bn) { return g_cnt + (208 + t * 16 + bn) * 32; }

DEVINL int qord(int i, int l, int pn) {
  const int u = i < 10 ? i - 4 : i - 10;
  return l == 0 ? i : i < 4 ? ((2 * pn) ^ (2 * (i & 1))) + (i >> 1) : 2 * (u < (pn & 6) ? u : u + 2) + (i >= 10);
}
struct Params {
  CUtensorMap m[15];
  const bf16* x0;
  const bf16* wq[2];
  const bf16* wo;
  uint32_t zero;
  int map[128];
  uint64_t wd, xd;
  struct __align__(16) { uint64_t kd, vd; } kv[4];
};
enum { M_X0A = 0, M_WQA, M_WQB, M_WOA, M_WOB, M_OS, M_K, M_V, M_X0R, M_XSR, M_XSO, M_OUT, M_XST, M_X0H, M_OL, M_COUNT };

constexpr uint32_t QSTG = 57344;
constexpr uint32_t T0 = 65536, TSTG = 32768;
constexpr uint32_t ONES = 230400;
constexpr uint32_t PSTG = 32768, RES = 196608;
constexpr uint32_t VSC = 98304, KSC = 133120, HRS = 167936;
constexpr uint32_t ROWST = 229376, COLS = 231424, BARS = 232192, SMEM_BYTES = 232448;
constexpr uint32_t B_QF = BARS, B_QE = BARS + 32, B_TF = BARS + 64, B_TE = BARS + 96, B_PF = BARS + 128, B_PE = BARS + 176,
                   B_RF = BARS + 224, W_X = BARS + 232, B_QL = BARS + 240, B_PA = BARS + 248;
enum { NB_LAG = 0, NB_ST = 1, NB_KV = 2  , NB_DONE = 3, NB_SC = 4, NB_SIG = 5  , NB_KN = 9  , NB_X = 11, NB_HALO = 12  , NB_X0 = 15 };

DEVINL uint32_t pslot_b(uint32_t s) { return ((0x320415u >> (4 * s)) & 7) * 16384u; }
DEVINL uint32_t pslot_a(uint32_t s, int l) { return 98304u + ((((l & 1) ? 0x541230u : 0x041235u) >> (4 * s)) & 7) * 16384u; }

constexpr float QSCALE = 0.17677669529663687f * 1.4426950408889634f;
constexpr uint32_t QPARK = 32768;

DEVINL uint32_t exp2_h2(uint32_t s, uint32_t c852) {
  uint32_t r, t, w, m, d;
  asm volatile("{.reg .b64 t; add.rn.f16x2 %0, %1, %2; cvt.u64.u32 t, %0; cvt.u32.u64 %0, t;}" : "=r"(r) : "r"(s), "r"(0x65EA65EAu));
  asm volatile("fma.rn.f16x2 %0, %1, %2, %3;" : "=r"(t) : "r"(r), "r"(0xB880B880u), "r"(c852));
  asm volatile("fma.rn.f16x2 %0, %1, %2, %3;" : "=r"(w) : "r"(s), "r"(0x38803880u), "r"(t));
  asm volatile("fma.rn.f16x2 %0, %1, %1, %2;" : "=r"(m) : "r"(w), "r"(0x4A1F4A2Du));
  asm volatile("{.reg .b32 t; shf.l.clamp.b32 t, %2, %1, 7; add.u32 %0, t, %2;}" : "=r"(d) : "r"(r), "r"(m));
  return d;
}
DEVINL float exp2_fix(float s) { float z; asm volatile("add.rn.f32 %0, %1, 0f43BF34BC;" : "=f"(z) : "f"(s)); return z; }
DEVINL uint32_t exp2_base(float z0, float z1) { uint32_t B; asm volatile("prmt.b32 %0, %1, %2, 0x6521;" : "=r"(B) : "r"(__float_as_uint(z0)), "r"(__float_as_uint(z1))); return B; }
template <uint32_t MASK> DEVINL uint32_t and_or(uint32_t a, uint32_t c) { uint32_t r; asm volatile("lop3.b32 %0, %1, %3, %2, 0xEA;" : "=r"(r) : "r"(a), "r"(c), "n"(MASK)); return r; }
DEVINL uint32_t fma_bf2(uint32_t a, uint32_t b, uint32_t c) { uint32_t r; asm volatile("fma.rn.bf16x2 %0, %1, %2, %3;" : "=r"(r) : "r"(a), "r"(b), "r"(c)); return r; }
DEVINL float ex2v(float x) { float y; asm volatile("ex2.approx.ftz.f32 %0, %1;" : "=f"(y) : "f"(x)); return y; }
DEVINL uint32_t pack2v(float lo, float hi) { uint32_t r; asm volatile("cvt.rn.bf16x2.f32 %0, %1, %2;" : "=r"(r) : "f"(hi), "f"(lo)); return r; }
DEVINL void unesc(uint32_t (&u)[4], const uint32_t* esc, uint32_t tag) {
  const bool saved = __ldcg(esc + 16) == tag;
#pragma unroll
  for (int j = 0; j < 4; j++) {
    float lo, hi;
    asm("{.reg .f16 a, b; mov.b32 {a, b}, %2; cvt.f32.f16 %0, a; cvt.f32.f16 %1, b;}" : "=f"(lo), "=f"(hi) : "r"(u[j]));
    u[j] = saved ? __ldcg(esc + 4 * j) : pack2(lo, hi);
  }
}

DEVINL void attn_slow(const uint32_t (&q)[8], int head, const uint32_t* kesc, uint32_t tag, float (&res)[20], int lane) {
  const int g = lane >> 2, qd = lane & 3;
  const bf16* kb = g_k + (size_t)head * 2048 * 32;
  const bf16* vb = g_v + (size_t)head * 2048 * 32;
  float o[4][4], m0 = -INFINITY, m1 = -INFINITY, l0 = 0.f, l1 = 0.f;
#pragma unroll
  for (int j = 0; j < 4; j++) { o[j][0] = o[j][1] = o[j][2] = o[j][3] = 0.f; }
#pragma unroll 1
  for (int k0 = 0; k0 < 2048; k0 += 16) {
    float s[2][4];
#pragma unroll
    for (int nt = 0; nt < 2; nt++) {
      s[nt][0] = s[nt][1] = s[nt][2] = s[nt][3] = 0.f;
      const uint32_t* kp = (const uint32_t*)(kb + (size_t)(k0 + nt * 8 + g) * 32) + qd;
      uint32_t k[4] = {__ldcg(kp), __ldcg(kp + 4), __ldcg(kp + 8), __ldcg(kp + 12)};
      unesc(k, kesc + (k0 + nt * 8 + g) * 20 + qd, tag);
      __syncwarp();
      mma16816(s[nt], q[0], q[1], q[2], q[3], k[0], k[1]);
      mma16816(s[nt], q[4], q[5], q[6], q[7], k[2], k[3]);
    }
    float a0 = fmaxf(fmaxf(s[0][0], s[0][1]), fmaxf(s[1][0], s[1][1]));
    float a1 = fmaxf(fmaxf(s[0][2], s[0][3]), fmaxf(s[1][2], s[1][3]));
    a0 = fmaxf(a0, __shfl_xor_sync(~0u, a0, 1)); a0 = fmaxf(a0, __shfl_xor_sync(~0u, a0, 2));
    a1 = fmaxf(a1, __shfl_xor_sync(~0u, a1, 1)); a1 = fmaxf(a1, __shfl_xor_sync(~0u, a1, 2));
    const float n0 = fmaxf(m0, a0), n1 = fmaxf(m1, a1);
    const float c0 = (m0 == n0) ? 1.f : ex2(m0 - n0), c1 = (m1 == n1) ? 1.f : ex2(m1 - n1);
    m0 = n0; m1 = n1;
    const uint32_t p0 = pack2(ex2(s[0][0] - n0), ex2(s[0][1] - n0)), p1 = pack2(ex2(s[0][2] - n1), ex2(s[0][3] - n1));
    const uint32_t p2 = pack2(ex2(s[1][0] - n0), ex2(s[1][1] - n0)), p3 = pack2(ex2(s[1][2] - n1), ex2(s[1][3] - n1));
    l0 = l0 * c0 + bf_lo(p0) + bf_hi(p0) + bf_lo(p2) + bf_hi(p2);
    l1 = l1 * c1 + bf_lo(p1) + bf_hi(p1) + bf_lo(p3) + bf_hi(p3);
#pragma unroll
    for (int j = 0; j < 4; j++) {
      o[j][0] *= c0; o[j][1] *= c0; o[j][2] *= c1; o[j][3] *= c1;
      const unsigned short* vp = (const unsigned short*)(vb + (size_t)(k0 + 2 * qd) * 32 + j * 8 + g);
      const uint32_t b0 = (uint32_t)__ldcg(vp) | ((uint32_t)__ldcg(vp + 32) << 16);
      const uint32_t b1 = (uint32_t)__ldcg(vp + 256) | ((uint32_t)__ldcg(vp + 288) << 16);
      mma16816(o[j], p0, p1, p2, p3, b0, b1);
    }
  }
  l0 += __shfl_xor_sync(~0u, l0, 1); l0 += __shfl_xor_sync(~0u, l0, 2);
  l1 += __shfl_xor_sync(~0u, l1, 1); l1 += __shfl_xor_sync(~0u, l1, 2);
#pragma unroll
  for (int j = 0; j < 4; j++) { res[4 * j] = o[j][0]; res[4 * j + 1] = o[j][1]; res[4 * j + 2] = o[j][2]; res[4 * j + 3] = o[j][3]; }
  res[16] = l0; res[18] = l1;
}

__device__ __noinline__ void attn_redo(int redo, int l, int b, int wg, int w, uint32_t tag) {
  const int lane = lane_id();
#pragma unroll 1
  for (int t = 0; t < 4; t++) {
    const int h = t >> 1, head = 2 * (b & 15) + h, row = (b >> 4) * 256 + wg * 128 + (t & 1) * 64 + w * 16 + (lane >> 2);
    if ((redo >> t) & 1) {
      const uint32_t* esc = g_esc + (size_t)((l & 2) * 65536 + head * 2048) * 20;
      const uint32_t* qs = (const uint32_t*)(g_qsave + (block_id() * 256 + wg * 128 + w * 32 + lane) * 8 + 2 * t);
      uint32_t q[8]; float o[20];
#pragma unroll
      for (int i = 0; i < 2; i++) {
        uint32_t u[4] = {__ldcg(qs + i), __ldcg(qs + i + 2), __ldcg(qs + i + 4), __ldcg(qs + i + 6)};
        unesc(u, esc + (row + i * 8) * 20 + (lane & 3), tag);
        q[i] = u[0]; q[i + 2] = u[1]; q[i + 4] = u[2]; q[i + 6] = u[3];
      }
      __syncwarp();
      attn_slow(q, head, esc + 65536 * 20, tag, o, lane);
      const float i0 = rcp(o[16]), i1 = rcp(o[18]);
      bf16* op = g_os + (size_t)row * 1024 + h * 512 + (b & 15) * 32 + (lane & 3) * 8;
      *(uint4*)op = make_uint4(pack2(o[0] * i0, o[1] * i0), pack2(o[4] * i0, o[5] * i0), pack2(o[8] * i0, o[9] * i0), pack2(o[12] * i0, o[13] * i0));
      *(uint4*)(op + 8 * 1024) = make_uint4(pack2(o[2] * i1, o[3] * i1), pack2(o[6] * i1, o[7] * i1), pack2(o[10] * i1, o[11] * i1), pack2(o[14] * i1, o[15] * i1));
    }
    if ((t & 1) && ((redo >> 2 * h) & 3)) bar_arrive(NB_SIG + 2 * h + wg, 160);
  }
}

__global__ void __cluster_dims__(2, 1, 1) __launch_bounds__(384, 1) fused_kernel(const __grid_constant__ Params prm) {
  extern __shared__ __align__(1024) char smem[];
  const uint32_t sb = (uint32_t)__cvta_generic_to_shared(smem);
  const int tid = threadIdx.x, lane = tid & 31;
  const int wg = __shfl_sync(0xffffffffu, tid >> 7, 0);
  const int w = __shfl_sync(0xffffffffu, (tid >> 5) & 3, 0);
  const int bm = remap(blockIdx.x) >> 4, bn = remap(blockIdx.x) & 15;

  auto first_tile = [&](int kt) {
    e_expect_tx(sb + B_QF + 8 * kt, QSTG);
    tma_ld(sb + kt * QSTG, &prm.m[M_X0A], kt * 64, bm * 256, sb + B_QF + 8 * kt);
    tma_ld3(sb + kt * QSTG + 32768, &prm.m[M_WQA], bn * 64, kt * 64, 0, sb + B_QF + 8 * kt);
  };
  auto init4 = [&](uint32_t bar, uint32_t c0, uint32_t c1, uint32_t c2, uint32_t c3) {
    asm volatile("{\n.reg .pred pe;\nelect.sync _|pe, 0xffffffff;\n@pe mbarrier.init.shared::cta.b64 [%0], %1;\n@pe mbarrier.init.shared::cta.b64 [%0+8], %2;\n"
                 "@pe mbarrier.init.shared::cta.b64 [%0+16], %3;\n@pe mbarrier.init.shared::cta.b64 [%0+24], %4;\n@pe fence.mbarrier_init.release.cluster;\n}"
                 ::"r"(bar), "r"(c0), "r"(c1), "r"(c2), "r"(c3) : "memory");
  };
  if (wg < 2) {
    const uint32_t k = wg * 4 + w, lo = (0x1411814u >> (4 * k)) & 15, hi = (0x1441814u >> (4 * k)) & 15;
    if (tid < 32) asm volatile("prefetch.global.L2 [%0];" ::"l"(prm.x0 + (size_t)(bm * 256 + bn * 16 + (tid & 15)) * 1024 + (tid >> 4) * 64));
    else if (tid < 80) asm volatile("prefetch.global.L2 [%0];" ::"l"(prm.wq[0] + (bm * 16 + (tid & 15)) * 3072 + ((tid >> 4) - 2) * 1024 + bn * 64));
    __syncwarp();
    if (k < 7) init4(sb + B_QE + 32 * k, lo, lo, hi, k == 6 ? 2 : hi);
    __syncwarp();
    if (k == 6 && lane == 0) *(volatile unsigned long long*)(smem + W_X) = 0ull;
  } else if (w == 0) {
    init4(sb + B_QF, 1, 1, 1, 1);
    __syncwarp();
    first_tile(0);
  }
  __syncthreads();
  asm volatile("barrier.cluster.arrive.relaxed.aligned;" ::: "memory");

  if (wg == 2) {
    asm volatile("setmaxnreg.dec.sync.aligned.u32 56;");
    const uint32_t ep1 = *(volatile uint32_t*)&g_epoch + 1;
    if (w == 0) {
      first_tile(1);
      mbar_wait(sb + B_QF, 0);
      first_tile(2); first_tile(3);
#pragma unroll 1
      for (int kt = 4; kt < 16; kt++) l2_prefetch(prm.wq[0] + kt * 196608 + blockIdx.x * 1536, 3072);
      cluster_wait();
#pragma unroll 1
      for (int l = 0; l < 4; l++) {
        IDS();
        const CUtensorMap* mw = &prm.m[M_WQA + (l & 1)];
        const CUtensorMap* mh = &prm.m[l == 0 ? M_X0H : M_XSO];
        const CUtensorMap* mo = &prm.m[M_WOA + (l & 1)];
        auto q_b = [&](int i) {
          const int s = i & 3;
          mbar_wait(sb + B_QE + 8 * s, ((i >> 2) & 1) ^ 1);
          e_expect_tx(sb + B_QF + 8 * s, QSTG);
          tma_ld3(sb + s * QSTG + 32768, mw, bn * 64, qord(i, l, pn) * 64, 0, sb + B_QF + 8 * s);
        };
        uint32_t rdy = l ? 0u : ~0u;
        auto q_a = [&](int i) {
          const int kt = qord(i, l, pn);
          await_flag(kt, rdy, cnt_x(bm) + (lane & 15), ep1 * 9 - 6 + 2 * l);
          tma_ld_mc(sb + (i & 3) * QSTG + rank * 16384, mh, kt * 64, bm * 256 + rank * 128, sb + B_QF + 8 * (i & 3));
        };
        if (l > 0) {
#pragma unroll 1
          for (int i = 0; i < 4; i++) {
            const int kt = qord(i, l, pn);
            await_flag(kt, rdy, cnt_x(bm) + (lane & 15), ep1 * 9 - 6 + 2 * l);
            e_expect_tx(sb + B_QF + 8 * i, 16384);
            tma_ld(sb + i * QSTG + (po ^ 1) * 16384, &prm.m[M_XSO], kt * 64, (pm ^ 1) * 128, sb + B_QF + 8 * i);
          }
        }
#pragma unroll 1
        for (int i = 4; i < 16; i++) {
          if (l == 3 && i == 12) poll_ge(cnt_ad(bn), ep1 * 16);
          q_b(i); q_a(i);
          if (l == 0 && i >= 8) l2_prefetch(prm.wq[1] + ((i - 8) * 128 + blockIdx.x) * 3072, 6144);
          if (l == 0 && i >= 8) l2_prefetch(prm.wo + ((i - 8) * 128 + blockIdx.x) * 1024, 2048);
        }
        if (l & 1) {
          const int krow = 2 * bn * 2048 + bm * 256;
          uint32_t* kvc = cnt_kv(l >> 1, bn);
          uint32_t seen = 0;
#pragma unroll 1
          for (int it = 1; it < 16; it++) {
            const int s = it & 3;
            if (it == 4) {
              bar_sync(NB_KV + 12, 288);
              mbar_wait(sb + B_TF + 24, 0);
#pragma unroll 1
              for (int i = 0; i < 4; i++) tma_st(&prm.m[M_K + (i & 1)], 0, krow + 2048 + (i >> 1) * 128, sb + i * 8192);
              bulk_commit();
            }
            if (it == 5) { bulk_wait_n<0>(); e_red(kvc + 16 + bm); }
            if (it == 12) { e_expect_tx(sb + B_RF, 32768); tma_ld3(sb + RES, &prm.m[M_XSR], 0, pm * 128, 2 * pn, sb + B_RF); }
            if (it == 1 || it == 3) mbar_wait(sb + B_QE + 12 + 4 * it, 1);
            mbar_wait(sb + B_TE + 8 * s, ((it >> 2) & 1) ^ 1);
            if (it < 8) {
#pragma unroll 1
              for (uint32_t n = 0; n < 200000u && (~seen & (3u << (2 * it - 2) | (it == 4 ? 0xC000u : 0u))); n++)
                seen = __ballot_sync(~0u, (int)(ld_acquire(kvc + (lane < 7 || lane == 15 ? (bm + 1 + lane) & 7 : 8 + ((bm + 2 + lane) & 7))) - ep1) >= 0);
              fence_async_gl();
            } else if (it == 8) { poll_ge(kvc + 16 + (lane & 7), ep1); fence_async_gl(); }
            e_expect_tx(sb + B_TF + 8 * s, 32768);
#pragma unroll 1
            for (int i = 0; i < 2; i++) {
              const int u = 2 * it - 2 + i;
              const int row = 2 * bn * 2048 + (it > 7 ? 2048 + ((bm + it) & 7) * 256 + i * 128 : u < 7 ? ((bm + 1 + u) & 7) * 256 : ((bm + 2 + u) & 7) * 256 + 128);
              tma_ld(sb + T0 + s * TSTG + i * 8192, &prm.m[M_K], 0, row, sb + B_TF + 8 * s);
              tma_ld(sb + T0 + s * TSTG + 16384 + i * 8192, &prm.m[M_V], 0, row, sb + B_TF + 8 * s);
            }
          }
        }
        auto p_b = [&](int i, uint32_t s, uint32_t par) {
          mbar_wait(sb + B_PE + 8 * s, par ^ 1);
          e_expect_tx(sb + B_PF + 8 * s, PSTG);
          tma_ld5(sb + pslot_b(s), mo, i >> 3, (2 * i + bn) & 14, 2 * pn, sb + B_PF + 8 * s);
        };
        auto p_a = [&](int i, uint32_t s) {
          await_flag(i, rdy, cnt_o(l, pm, (lane >> 3) & 1) + ((lane + (bn >> 1)) & 7), ep1 * 2);
          tma_ld_mc(sb + pslot_a(s, l) + rank * 8192, &prm.m[M_OS], (i & 8) * 64 + ((2 * i + bn) & 14) * 32, pm * 128 + rank * 64, sb + B_PF + 8 * s);
        };
        auto p_a2 = [&](int i) {
          await_flag(i, rdy, cnt_o(l, pm, (lane >> 3) & 1) + ((lane + (bn >> 1)) & 7), ep1 * 2);
          tma_ld(sb + pslot_a(i, l), &prm.m[M_OS], (i & 8) * 64 + ((2 * i + bn) & 14) * 32, pm * 128, sb + B_PF + 8 * i);
          tma_ld(sb + pslot_a(i, l) + 8192, &prm.m[M_OS], (i & 8) * 64 + ((2 * i + bn) & 14) * 32, pm * 128 + 64, sb + B_PF + 8 * i);
        };
        rdy = 0;
        if (l & 1) {
#pragma unroll 1
          for (int u = 0; u < 6; u++) { const int i = (0x205413 >> (4 * u)) & 7; if (u == 4) mbar_wait(sb + B_TE, 1); p_b(i, i, i < 4 ? 1 : 0); }
#pragma unroll 1
          for (int u = 0; u < 6; u++) {
            const int i = (0x542130 >> (4 * u)) & 7;
            if (!(u & 1)) mbar_wait(sb + B_TE + 8 + 4 * u, 1);
            p_a2(i);
          }
        } else {
#pragma unroll 1
          for (int u = 0; u < 6; u++) { const int i = (0x543120 >> (4 * u)) & 7; if (u == 0 || u == 2) mbar_wait(sb + B_QE + 8 - 4 * u, 1); p_b(i, i, 0); }
          mbar_wait(sb + B_QE + 24, 1);
          e_expect_tx(sb + B_RF, 32768);
          tma_ld3(sb + RES, &prm.m[l == 0 ? M_X0R : M_XSR], 0, pm * 128, 2 * pn, sb + B_RF);
          await_flag(1, rdy, cnt_o(l, pm, (lane >> 3) & 1) + ((lane + (bn >> 1)) & 7), ep1 * 2);
          bar_sync(NB_KV, 288);
          p_a2(1);
          bar_sync(NB_DONE, 288);
          e_arrive_both(sb + B_PA);
          mbar_wait(sb + B_PA, (l >> 1) & 1);
#pragma unroll 1
          for (int i = 2; i < 6; i++) { if (i > 3) mbar_wait(sb + B_PF + 8 * (i - 3), 0); p_a(i, i); }
        }
        uint32_t s = 0, lap = 1;
#pragma unroll 1
        for (int i = 6; i < 16; i++) {
          p_b(i, s, ((s < 4 ? l : 0) + lap) & 1);
          p_a(i, s);
          if (++s == 6) { s = 0; lap++; }
        }
        const CUtensorMap* mn = &prm.m[M_WQA + ((l + 1) & 1)];
        if (l < 3) {
          mbar_wait(sb + B_PE + 8 * 4, 1); mbar_wait(sb + B_PE + 8 * 5, 1);
          tma_ld3(sb + 32768, mn, bn * 64, 2 * pn * 64, 0, sb + B_QL);
          mbar_wait(sb + B_PE + 8 * 0, l & 1);
          e_expect_tx(sb + B_PA, 24576); e_expect_tx(sb + B_PA, 16384);
          tma_ld3(sb + QSTG + 32768, mn, bn * 64, ((2 * pn) ^ 2) * 64, 0, sb + B_PA);
          mbar_wait(sb + B_PE + 8 * 1, l & 1);
          tma_ld3(sb + 2 * QSTG + 32768, mn, bn * 64, (2 * pn + 1) * 64, 0, sb + B_QL);
          bar_sync(NB_KN, 288);
          e_expect_tx(sb + B_RF, 40960);
          tma_ld3(sb + 3 * QSTG + 32768, mn, bn * 64, ((2 * pn) ^ 3) * 64, 0, sb + B_RF);
          mbar_wait(sb + B_PE + 24, l & 1);
          bar_sync(NB_X0, 320);
          fence_async_gl();
          tma_ld_mc(sb + QSTG + po * 16384, &prm.m[M_XSO], 2 * pn * 64, pm * 128, sb + B_PA, 2 - rank);
          bar_sync(NB_X, 320);
          e_expect_tx(sb + B_QL, 49152);
        }
      }
      if (blockIdx.x == 0 && lane_id() == 0) *(volatile uint32_t*)&g_epoch = ep1;
    } else {
      const int hw = w - 1;
      if (lane < 5) asm volatile("prefetch.tensormap [%0];" ::"l"(&prm.m[5 * hw + lane]) : "memory");
      __syncwarp();
      cluster_wait();
#pragma unroll 1
      for (int l = 0; l < 4; l++) {
        IDS();
        if (l > 0) mbar_wait(sb + B_QL, (l + 1) & 1);
        mbar_hint(sb + B_QF + 24, 0);
        if (l == 0) {
#pragma unroll 1
          for (int r = 2 * hw; r < 16; r += 6) {
            const uint4* p = (const uint4*)(prm.x0 + (size_t)(b * 16 + r) * 1024) + lane;
            float s1[2] = {0.f, 0.f}, s2[2] = {0.f, 0.f};
#pragma unroll
            for (int i = 0; i < 8; i++) {
              const uint4 v = __ldg(p + 32 * i);
              const uint32_t u[4] = {v.x, v.y, v.z, v.w};
#pragma unroll
              for (int k = 0; k < 4; k++) { const float a = bf_lo(u[k]), c = bf_hi(u[k]); s1[i >> 2] += a + c; s2[i >> 2] = fmaf(a, a, fmaf(c, c, s2[i >> 2])); }
            }
#pragma unroll
            for (int o = 16; o; o >>= 1)
#pragma unroll
              for (int rr = 0; rr < 2; rr++) { s1[rr] += __shfl_xor_sync(~0u, s1[rr], o); s2[rr] += __shfl_xor_sync(~0u, s2[rr], o); }
            if (lane == 0) *(float4*)&g_stats[b * 16 + r] = make_float4(s1[0], s2[0], s1[1], s2[1]);
          }
        }
        if (l < 2) {
          float cs[8];
#pragma unroll
          for (int i = 0; i < 8; i++) cs[i] = 0.f;
          const uint4* wp = (const uint4*)(prm.wq[l] + (size_t)(bm * 4 + (lane >> 3)) * 3072 + hw * 1024 + bn * 64) + (lane & 7);
#pragma unroll 8
          for (int i = 0; i < 32; i++) {
            const uint4 v = __ldg(wp + (size_t)i * 32 * 384);
            cs[0] += bf_lo(v.x); cs[1] += bf_hi(v.x); cs[2] += bf_lo(v.y); cs[3] += bf_hi(v.y);
            cs[4] += bf_lo(v.z); cs[5] += bf_hi(v.z); cs[6] += bf_lo(v.w); cs[7] += bf_hi(v.w);
          }
#pragma unroll
          for (int i = 0; i < 8; i++) { cs[i] += __shfl_xor_sync(~0u, cs[i], 8); cs[i] += __shfl_xor_sync(~0u, cs[i], 16); }
          if (lane < 8) {
            float4* d = (float4*)(g_csp + ((l * 16 + bn) * 8 + bm) * 192 + hw * 64 + lane * 8);
            d[0] = make_float4(cs[0], cs[1], cs[2], cs[3]); d[1] = make_float4(cs[4], cs[5], cs[6], cs[7]);
          }
          __syncwarp();
          asm volatile("fence.acq_rel.gpu;" ::: "memory");
          e_red_relaxed(cnt_cs(l, bn));
          if (l == 0) e_red_relaxed(cnt_x(bm) + bn);
          poll_ge(lane < 16 && l == 0 ? cnt_x(bm) + lane : cnt_cs(l, bn), lane < 16 && l == 0 ? ep1 * 9 - 6 : ep1 * 24);
        }
        if (l > 0) poll_ge(cnt_x(bm) + (lane & 15), ep1 * 9 - 6 + 2 * l);
#pragma unroll 1
        for (int it = hw * 32 + lane; it < 176; it += 96) {
          const bool rows = it < 128;
          const float4* p = rows ? (const float4*)(g_stats + bm * 256) + it : (const float4*)(g_csp + ((l & 1) * 16 + bn) * 8 * 192) + (it - 128);
          const int stride = rows ? 1024 : 48, np = rows && l == 0 ? 1 : 8;
          float4 a = make_float4(0.f, 0.f, 0.f, 0.f);
#pragma unroll
          for (int k = 0; k < 8; k++) if (k < np) { const float4 v = __ldcg(p + k * stride); a.x += v.x; a.y += v.y; a.z += v.z; a.w += v.w; }
          if (rows) {
            const float m0 = a.x * (1.f / 1024.f), m1 = a.z * (1.f / 1024.f);
            const float v0 = fmaxf(a.y * (1.f / 1024.f) - m0 * m0, 0.f), v1 = fmaxf(a.w * (1.f / 1024.f) - m1 * m1, 0.f);
            const float r0 = __fdividef(1.f, bf_round(sqrtf(bf_round(bf_round(v0) + 1e-5f)))), r1 = __fdividef(1.f, bf_round(sqrtf(bf_round(bf_round(v1) + 1e-5f))));
            a = make_float4(r0, -bf_round(m0), r1, -bf_round(m1));
          }
          if (rows && (l & 1) && (it & 4)) a = make_float4(a.y, a.x, a.w, a.z);
          *(float4*)(smem + ROWST + it * 16) = a;
        }
        __syncwarp();
        if (lane == 0) asm volatile("red.release.cta.shared.add.u32 [%0], 1;" ::"r"(sb + W_X) : "memory");
        if (hw == 2) {
          if (!(l & 1)) {
            bar_sync(NB_ST, 288);
            const uint4* hp = g_halo + (b - 16) * 384 + lane;
#pragma unroll 1
            for (int h = 0; h < 2; h++) {
              uint32_t t[18];
#pragma unroll
              for (int i = 0; i < 18; i++) t[i] = 0;
#pragma unroll 1
              for (uint32_t n = bm ? 0 : 100000u; n < 100000u; n++) {
                uint32_t miss = 0;
#pragma unroll
                for (int i = 0; i < 6; i++) miss |= ld_tagged(hp + h * 192 + i * 32, &t[3 * i]) ^ (4 * ep1 + l);
                if (__all_sync(~0u, !miss)) break;
              }
              mbar_wait(sb + B_QE + 16, 1);
              const uint32_t r = (lane & 7) + ((lane >> 3) & 1) * 8, rv = lane >> 2;
#pragma unroll
              for (int jj = 0; jj < 2; jj++) stsm4(sb + KSC + r * 128 + (((4 * h + 2 * jj + (lane >> 4)) ^ (r & 7)) << 4), t[4 * jj], t[4 * jj + 1], t[4 * jj + 2], t[4 * jj + 3]);
              const uint32_t ad = sb + VSC + rv * 128 + (((4 * h + (lane & 3)) ^ (rv & 7)) << 4);
              sts128(ad, t[8], t[10], t[12], t[14]); sts128(ad + 1024, t[9], t[11], t[13], t[15]);
              if (h == 0 && !(lane & 2)) *(uint32_t*)(smem + HRS + ((lane >> 2) + 8 * (lane & 1)) * 8) = t[16];
              bar_arrive(NB_HALO + h, 64);
            }
          } else {
            bar_sync(NB_KV, 288);
            sts128(sb + ONES + lane * 32, 0x3f803f80u, 0x3f803f80u, 0x3f803f80u, 0x3f803f80u);
            sts128(sb + ONES + lane * 32 + 16, 0x3f803f80u, 0x3f803f80u, 0x3f803f80u, 0x3f803f80u);
            sts128(sb + ROWST + 16, 0x62A962A9u, 0x00010001u, 0x3F003F00u, 0u);
            fence_async_smem();
            __syncwarp();
            e_arrive(sb + B_TF);
            mbar_hint(sb + B_TF + 16, 0); mbar_hint(sb + B_TF + 16, 1);
            poll_ge(cnt_kv(l >> 1, bn) + 16 + (lane & 7), ep1);
            const uint4 v = __ldcg((const uint4*)(g_kn + ((l >> 1) * 128 + bn * 8) * 16) + lane);
            const uint32_t mx = max(max(v.x, v.y), max(v.z, v.w));
            const uint32_t m0 = __reduce_max_sync(~0u, (lane & 2) ? 0u : mx), m1 = __reduce_max_sync(~0u, (lane & 2) ? mx : 0u);
            if (lane == 0) *(uint2*)(smem + ROWST) = make_uint2(m0, m1);
            __syncwarp();
            bar_arrive(NB_KN, 160); bar_arrive(NB_KN + 1, 160);
          }
        } else {
          if (l & 1) {
            uint32_t* p = cnt_kv(l >> 1, bn) + 8 * hw + bm;
            int on = lane == 0;
            PREPARED(p, on);
            bar_sync(hw ? NB_HALO : NB_DONE, 160);
            tma_st(&prm.m[M_K], 0, 2 * bn * 2048 + bm * 256 + hw * 128, sb + T0 + hw * 8192);
            tma_st(&prm.m[M_V], 0, 2 * bn * 2048 + bm * 256 + hw * 128, sb + T0 + 16384 + hw * 8192);
            bulk_commit(); bulk_wait_n<0>();
            release_add(p, on);
          }
#pragma unroll 1
          for (int h = l & 1 ? 0 : hw; h <= (l & 1 ? 1 : hw); h++) {
            uint32_t* p = l == 1 && lane == 1 ? cnt_ad(bn) : cnt_o(l, 2 * bm + (l & 1 ? hw : lane & 1), h) + (bn >> 1);
            int on = lane == 0 || (lane == 1 && (!(l & 1) || (l == 1 && h == 1)));
            int id = NB_SIG + 2 * h + (l & hw), n = l & 1 ? 160 : 288;
            asm volatile("" : "+r"(id), "+r"(n));
            PREPARED(p, on);
            bar_sync(id, n);
            release_add(p, on);
            if (!(l & 1) && hw == 0) {
              mbar_wait(sb + B_QE + 24, 1);
              fence_async_gl();
              tma_ld_mc(sb + pslot_a(0, 0) + rank * 8192, &prm.m[M_OL], bn * 32, pm * 128, sb + B_PF);
            }
          }
        }
        if (hw < 2 && l < 3) {
          uint32_t* p = cnt_x(bm) + 2 * pn + hw;
          int on = lane == 0;
          PREPARED(p, on);
          if (hw) {
            bar_sync(NB_X, 320);
            tma_st(&prm.m[M_XSO], pn * 128 + 64, pm * 128, sb + 2 * QSTG + po * 16384);
            bulk_commit();
            bar_sync(NB_KV, 288);
            bulk_wait_n<0>();
            mbar_wait(sb + B_PA, l == 0);
            fence_async_gl();
            tma_ld_mc(sb + 3 * QSTG + po * 16384, &prm.m[M_XSO], pn * 128 + 64, pm * 128, sb + B_RF, 2 - rank);
          } else bar_sync(NB_X0, 320);
          release_add(p, on);
        }
      }
    }
  } else {
    asm volatile("setmaxnreg.inc.sync.aligned.u32 224;");
    const uint32_t zero = prm.zero;
    cluster_wait();
#pragma unroll 1
    for (int l = 0; l < 4; l++) {
      {
        float acc[2][96];
        const bool early = l > 0 && wg == ((cta_id() >> 3) & 1);
        uint32_t ep1 = 0;
        if (l > 0) mbar_wait(sb + B_QL, (l + 1) & 1);
        if (!early) mbar_wait(sb + B_QF, 0);
        wg_fence();
#pragma unroll
        for (int k = 0; k < 4; k++)
#pragma unroll
          for (int m = 0; m < 2; m++) {
            if (k) wgmma_m64n192k16_ss_tb(acc[m], prm.xd + wg * 1024 + m * 512 + k * 2, prm.wd + k * 128, 1);
            else wgmma_m64n192k16_ss_tb_z(acc[m], prm.xd + wg * 1024 + m * 512, prm.wd, 0);
          }
        wg_commit();
#pragma unroll 1
        for (int kt = 1; kt < 13; kt++) {
          const int s = kt == 12 ? 1 : early && kt < 3 ? 3 - kt : kt & 3;
          if (l > 0 && kt < 4 && (s & 1)) mbar_wait(sb + (s == 1 ? B_PA : B_RF), s == 3 || l == 1);
          if (!(early && kt < 4)) mbar_wait(sb + B_QF + 8 * s, (kt >> 2) & 1);
          const uint64_t da = prm.xd + wg * 1024 + s * (QSTG >> 4), db = prm.wd + s * (QSTG >> 4);
          wg_fence();
#pragma unroll
          for (int k = 0; k < 4; k++)
#pragma unroll
            for (int m = 0; m < 2; m++) wgmma_m64n192k16_ss_tb(acc[m], da + m * 512 + k * 2, db + k * 128, 1);
          wg_commit();
          if (kt == 4) ep1 = *(volatile uint32_t*)&g_epoch + 1;
          wg_wait<1>();
          if (early && kt < 5) {
#pragma unroll 1
            for (int i = 3 * (kt - 3); i < kt && kt > 2; i++) { mbar_wait(sb + B_QF + 8 * i, 0); bar_sync(NB_SC, 128); if (w == 0) e_arrive_both(sb + B_QE + 8 * i); }
          } else if (w == 0) e_arrive_both(sb + B_QE + 8 * ((kt - 1) & 3));
        }
        {
          const bool lag = (l & 1) == wg;
          const uint32_t s0 = 2 * (~l & 1);
          const uint64_t da = prm.xd + wg * 1024 + 2 * (QSTG >> 4), db = prm.wd + 2 * (QSTG >> 4);
          mbar_wait(sb + B_QF + 8 * s0, 1);
#pragma unroll
          for (int t = 0; t < 2; t++) {
            if (lag && t != wg) {
              wg_wait<0>();
              if (w == 0) e_arrive_both(sb + B_QE + 8 + 8 * t);
              if (t == 0) mbar_wait(sb + B_QF + 16, 1);
              mbar_wait(sb + B_QF + 24, 1);
              if (t == 1) bar_arrive(NB_ST, 288);
              bar_sync(NB_LAG, 256);
            }
            const uint64_t so = (uint64_t)(t ? s0 : s0 ^ 2) * (QSTG >> 4);
            wg_fence();
#pragma unroll
            for (int k = 0; k < 4; k++)
#pragma unroll
              for (int m = 0; m < 2; m++) wgmma_m64n192k16_ss_tb(acc[m], da - so + m * 512 + k * 2, db - so + k * 128, 1);
            wg_commit();
            if (!lag || t + wg == 0) {
              wg_wait<1>();
              if (w == 0) e_arrive_both(sb + B_QE + 8 * (t ? s0 : 1));
              mbar_wait(sb + B_QF + 8 * (t ? 3 : s0 ^ 2), 1);
            }
          }
          wg_fence();
#pragma unroll
          for (int m = 1; m >= 0; m--) {
#pragma unroll
            for (int k = 0; k < 4; k++) wgmma_m64n192k16_ss_tb(acc[m], da + (QSTG >> 4) + m * 512 + k * 2, db + (QSTG >> 4) + k * 128, 1);
            wg_commit();
          }
          if (!lag) { bar_arrive(NB_LAG, 256); if (wg) bar_arrive(NB_ST, 288); }
          wg_wait<2>();
          if (w == 0) { e_arrive_both(sb + B_QE + 8 * (s0 ^ 2)); if (lag && wg) e_arrive_both(sb + B_QE); }
        }
#pragma unroll 1
        for (uint32_t n = 0; n < 4000000u; n++) {
          uint32_t v;
          asm volatile("ld.acquire.cta.shared.u32 %0, [%1];" : "=r"(v) : "r"(sb + W_X) : "memory");
          if (v == (uint32_t)(3 * l + 3)) break;
        }
        IDS();
        const int g = lane >> 2, qd = lane & 3;
        float2 st[2][2];
#pragma unroll
        for (int m = 0; m < 2; m++)
#pragma unroll
          for (int hh = 0; hh < 2; hh++) st[m][hh] = lds64f(sb + ROWST + (wg * 128 + m * 64 + w * 16 + g + 8 * hh) * 8);
        float2 cs[4];
        auto load_cs = [&](int gi) {
#pragma unroll
          for (int j = 0; j < 4; j++) cs[j] = lds64f(sb + COLS + (gi * 32 + j * 8 + 2 * qd) * 4);
        };
        load_cs(2 + 2 * (l & 1));
        auto drain = [&]() {
          wg_wait<0>(); fence_regs(acc[0]);
          if (w == 0) e_arrive_both(sb + B_QE + 8 * 3);
        };
        wg_wait<1>(); fence_regs(acc[1]);
        auto norm_tile = [&](int gi, int m, float sc, uint32_t (&t)[8], bool h16 = false) {
          const float r0 = st[m][0].x * sc, s0 = st[m][0].y, r1 = st[m][1].y * sc, s1 = st[m][1].x;
#pragma unroll
          for (int j = 0; j < 4; j++) {
            const float* a = &acc[m][16 * gi + 4 * j];
            const float v0 = fmaf(s0, cs[j].x, a[0]) * r0, v1 = fmaf(s0, cs[j].y, a[1]) * r0;
            const float v2 = fmaf(s1, cs[j].x, a[2]) * r1, v3 = fmaf(s1, cs[j].y, a[3]) * r1;
            t[2 * j] = h16 ? pack2h(v0, v1) : pack2(v0, v1); t[2 * j + 1] = h16 ? pack2h(v2, v3) : pack2(v2, v3);
          }
        };
        uint32_t q[2][2][8];
        const uint32_t srow = (lane & 7) + ((lane >> 3) & 1) * 8;
        const uint32_t row0 = wg * 128 + w * 16;
        if (!(l & 1)) {
          auto put_kv = [&](int gi, uint32_t r0, const uint32_t (&t)[8]) {
            if (gi < 4) {
              const uint32_t r = r0 + srow;
#pragma unroll
              for (int jj = 0; jj < 2; jj++) stsm4(sb + KSC + r * 128 + (((4 * (gi - 2) + 2 * jj + (lane >> 4)) ^ (r & 7)) << 4), t[4 * jj], t[4 * jj + 1], t[4 * jj + 2], t[4 * jj + 3]);
            } else {
              const uint32_t r = r0 + g, ad = sb + VSC + r * 128 + (((4 * (gi - 4) + qd) ^ (r & 7)) << 4);
              sts128(ad, t[0], t[2], t[4], t[6]); sts128(ad + 1024, t[1], t[3], t[5], t[7]);
            }
          };
          auto cen_tile = [&](int gi, int m, uint32_t (&t)[8]) {
#pragma unroll
            for (int j = 0; j < 4; j++) {
              const float* a = &acc[m][16 * gi + 4 * j];
              t[2 * j] = pack2(fmaf(st[m][0].y, cs[j].x, a[0]), fmaf(st[m][0].y, cs[j].y, a[1]));
              t[2 * j + 1] = pack2(fmaf(st[m][1].y, cs[j].x, a[2]), fmaf(st[m][1].y, cs[j].y, a[3]));
            }
          };
          const bool send = wg == 1 && w == 3 && bm < 7;
          uint4* hp = g_halo + b * 384 + lane;
          ep1 = 4 * ep1 + l;
          mbar_wait(sb + B_QE + 16, 1);
          float2 cn[4];
          auto next_cs = [&](int gi) {
#pragma unroll
            for (int j = 0; j < 4; j++) { cs[j] = cn[j]; cn[j] = lds64f(sb + COLS + (gi * 32 + j * 8 + 2 * qd) * 4); }
          };
#pragma unroll
          for (int j = 0; j < 4; j++) cn[j] = cs[j];
          auto lower = [&](int h, int nx, bool snd) {
            uint32_t k[8], v[8];
            next_cs(4 + h);
            cen_tile(2 + h, 1, k); put_kv(2 + h, 16 + row0 + 64, k);
            next_cs(nx);
            cen_tile(4 + h, 1, v); put_kv(4 + h, 16 + row0 + 64, v);
            if (snd) {
              uint4* p = hp + h * 192;
              st_tagged(p, k[0], k[1], k[2], ep1); st_tagged(p + 32, k[3], k[4], k[5], ep1); st_tagged(p + 64, k[6], k[7], v[0], ep1);
              st_tagged(p + 96, v[1], v[2], v[3], ep1); st_tagged(p + 128, v[4], v[5], v[6], ep1);
              st_tagged(p + 160, v[7], __float_as_uint(qd & 1 ? st[1][1].x : st[1][0].x), 0u, ep1);
            }
          };
          lower(0, 2 + wg, send);
          sched_fence();
          if (wg) lower(1, 2, send);
          drain();
          if (!wg) bar_arrive(NB_KN + 1, 256);
          {
            uint32_t t[8];
            next_cs(4); cen_tile(2, 0, t); put_kv(2, 16 + row0, t);
            next_cs(0); cen_tile(4, 0, t); put_kv(4, 16 + row0, t);
            next_cs(3); cen_tile(0, 0, q[0][0]); cen_tile(0, 1, q[0][1]);
          }
          auto upper = [&]() {
            uint32_t t[8];
            next_cs(5); cen_tile(3, 0, t); put_kv(3, 16 + row0, t);
            next_cs(1); cen_tile(5, 0, t); put_kv(5, 16 + row0, t);
          };
          if (wg) upper();
          const bool e = g & 1, sel = 2 * qd + (g & 1) >= g + 2, first = bm == 0 && row0 == 0;
          uint32_t ka = sb + KSC + (row0 + (lane & 7)) * 128 + (((lane >> 3) ^ (lane & 7)) << 4);
          uint32_t wa = sb + VSC + (row0 + srow) * 128 + (((lane >> 4) ^ (lane & 7)) << 4);
          uint32_t psel[3] = {e ? 0x1044u : 0x4410u, !sel ? 0x4444u : e ? 0x3244u : 0x4432u, sel ? 0x4444u : e ? 0x3244u : 0x4432u};
          bf16* op = g_os + (size_t)(bm * 256 + row0 + g) * 1024 + bn * 32 + qd * 8;
          asm volatile("" : "+r"(ka), "+r"(wa), "+l"(op));
          fence_regs(psel); fence_regs(q[0][0]); fence_regs(q[0][1]);
          sched_fence();
          bar_sync(NB_KN + wg, 128 << wg);
          if (row0 == 0) bar_sync(NB_HALO, 64);
          float ra[4], rb[4], ca[4], cb[4];
#pragma unroll
          for (int m = 0; m < 2; m++) {
            float rk[3];
#pragma unroll
            for (int u = 0; u < 3; u++) {
              const int r = row0 + m * 64 + 8 * u + 2 * qd + e - (sel ? 16 : 8);
              rk[u] = lds64f(sb + (m == 0 && r < 0 ? HRS + 128 : ROWST) + r * 8).x;
            }
            ra[2 * m] = sel ? rk[1] : rk[0]; ra[2 * m + 1] = sel ? rk[2] : rk[1];
            rb[2 * m] = sel ? rk[0] : rk[1]; rb[2 * m + 1] = sel ? rk[1] : rk[2];
          }
#pragma unroll
          for (int i = 0; i < 4; i++) { const float rq = st[i >> 1][i & 1].x * QSCALE; ca[i] = rq * ra[i]; cb[i] = rq * rb[i]; }
#pragma unroll 1
          for (int h = 0; h < 2; h++) {
            float s[2][4][4];
            uint32_t vf[2][4][4], pf[2][2][4];
#pragma unroll
            for (int m = 0; m < 2; m++)
#pragma unroll
              for (int nt = 0; nt < 4; nt++) {
                uint32_t kf[4];
                ldsm4(ka + (m * 64 + 8 * nt) * 128, kf);
                s[m][nt][0] = s[m][nt][1] = s[m][nt][2] = s[m][nt][3] = 0.f;
                mma16816(s[m][nt], q[0][m][0], q[0][m][1], q[0][m][2], q[0][m][3], kf[0], kf[1]);
                mma16816(s[m][nt], q[0][m][4], q[0][m][5], q[0][m][6], q[0][m][7], kf[2], kf[3]);
              }
            float va[4], vb[4], mx[4];
#pragma unroll
            for (int i = 0; i < 4; i++) {
              const int m = i >> 1, hh = i & 1;
              const float a = e ? s[m][hh + 1][2 * hh + 1] : s[m][hh + 1][2 * hh];
              const float lo = e ? s[m][hh][2 * hh + 1] : s[m][hh][2 * hh], hi = e ? s[m][hh + 2][2 * hh + 1] : s[m][hh + 2][2 * hh];
              va[i] = (m == 0 && hh == 0 && first) ? -INFINITY : a * ca[i];
              vb[i] = (m == 0 && first && sel) ? -INFINITY : (sel ? lo : hi) * cb[i];
              mx[i] = fmaxf(va[i], vb[i]);
            }
            if (h) bar_arrive(NB_KV + (__float_as_uint(mx[0]) & __float_as_uint(mx[1]) & __float_as_uint(mx[2]) & __float_as_uint(mx[3]) & zero), 288);
#pragma unroll
            for (int m = 0; m < 2; m++)
#pragma unroll
              for (int i = 0; i < 4; i++) {
                ldsm4t((wa ^ (32 * (i & 1))) + (m * 64 + 16 * (i >> 1)) * 128, vf[m][i]);
              }
#pragma unroll
            for (int i = 0; i < 4; i++) mx[i] = fmaxf(mx[i], __shfl_xor_sync(~0u, mx[i], 1));
#pragma unroll
            for (int i = 0; i < 4; i++) mx[i] = fmaxf(mx[i], __shfl_xor_sync(~0u, mx[i], 2));
#pragma unroll
            for (int i = 0; i < 4; i++) {
              va[i] = ex2(va[i] - mx[i]); vb[i] = ex2(vb[i] - mx[i]);
              mx[i] = va[i] + vb[i];
              va[i] *= ra[i]; vb[i] *= rb[i];
            }
#pragma unroll
            for (int i = 0; i < 4; i++) mx[i] += __shfl_xor_sync(~0u, mx[i], 1);
#pragma unroll
            for (int i = 0; i < 4; i++) mx[i] += __shfl_xor_sync(~0u, mx[i], 2);
#pragma unroll
            for (int i = 0; i < 4; i++) {
              const int m = i >> 1, hh = i & 1;
              const float inv = rcp(mx[i]);
              const uint32_t t = pack2(va[i] * inv, vb[i] * inv);
              pf[m][hh][hh + 1] = prmt0(t, psel[0]); pf[m][hh][hh] = prmt0(t, psel[1]); pf[m][hh][hh + 2] = prmt0(t, psel[2]);
              pf[m][hh][3 - 3 * hh] = t & zero;
            }
#pragma unroll
            for (int m = 0; m < 2; m++) {
              float o[4][4];
#pragma unroll
              for (int j = 0; j < 4; j++) o[j][0] = o[j][1] = o[j][2] = o[j][3] = 0.f;
#pragma unroll
              for (int i = 0; i < 4; i++) {
                const int kk = i >> 1, jj = 2 * (i & 1);
                mma16816(o[jj], pf[m][0][2 * kk], pf[m][1][2 * kk], pf[m][0][2 * kk + 1], pf[m][1][2 * kk + 1], vf[m][i][0], vf[m][i][1]);
                mma16816(o[jj + 1], pf[m][0][2 * kk], pf[m][1][2 * kk], pf[m][0][2 * kk + 1], pf[m][1][2 * kk + 1], vf[m][i][2], vf[m][i][3]);
              }
              stg128(op + m * 65536, pack2(o[0][0], o[0][1]), pack2(o[1][0], o[1][1]), pack2(o[2][0], o[2][1]), pack2(o[3][0], o[3][1]));
              stg128(op + m * 65536 + 8192, pack2(o[0][2], o[0][3]), pack2(o[1][2], o[1][3]), pack2(o[2][2], o[2][3]), pack2(o[3][2], o[3][3]));
            }
            if (h) bar_arrive(NB_DONE, 288);
            bar_arrive(NB_SIG + 2 * h, 288);
            if (h == 0) {
              if (!wg) { lower(1, 3, false); upper(); }
#pragma unroll
              for (int j = 0; j < 4; j++) cs[j] = cn[j];
              cen_tile(1, 0, q[0][0]); cen_tile(1, 1, q[0][1]);
              ka ^= 64; wa ^= 64; op += 512;
              bar_sync(NB_SC, 256);
              if (row0 == 0) bar_sync(NB_HALO + 1, 64);
            }
          }
        } else {
          float qn[2];
          mbar_wait(sb + B_QE + 8, 1);
          drain();
          auto esc_ptr = [&](int gi) { IDS(); return g_esc + (size_t)(((l & 2) + (gi >> 1)) * 65536 + (2 * bn + (gi & 1)) * 2048) * 20; };
          auto norm_half = [&](int gi, float sc, uint32_t (&t)[2][8], uint32_t (&n)[2], int nx) {
#pragma unroll
            for (int m = 0; m < 2; m++) {
              norm_tile(gi, m, sc, t[m], true);
              uint32_t a = hfma2(t[m][0], t[m][0], 0u), c = hfma2(t[m][1], t[m][1], 0u);
#pragma unroll
              for (int j = 1; j < 4; j++) { a = hfma2(t[m][2 * j], t[m][2 * j], a); c = hfma2(t[m][2 * j + 1], t[m][2 * j + 1], c); }
              n[m] = hadd2(__byte_perm(a, c, 0x5410), __byte_perm(a, c, 0x7632));
            }
            float2 cn[4];
#pragma unroll
            for (int j = 0; j < 4; j++) if (nx >= 0) cn[j] = lds64f(sb + COLS + (nx * 32 + j * 8 + 2 * qd) * 4);
            if (((n[0] - 0x01000100u) | (n[0] + 0x04000400u) | (n[1] - 0x01000100u) | (n[1] + 0x04000400u)) & 0x80008000u) {
              uint32_t* p = esc_ptr(gi) + (bm * 256 + row0 + g) * 20 + qd;
#pragma unroll
              for (int m = 0; m < 2; m++) {
                uint32_t u[8];
                norm_tile(gi, m, sc, u);
#pragma unroll
                for (int i = 0; i < 10; i++) p[(m * 64 + (i & 1) * 8) * 20 + (i >> 1) * 4] = i < 8 ? u[i] : ep1;
              }
            }
            __syncwarp();
#pragma unroll
            for (int i = 0; i < 16; i++) asm volatile("{\n.reg .b32 u;\nadd.u32 u, %0, 0x00040004;\nand.b32 %0, u, 0xFFF8FFF8;\n}" : "+r"(t[i >> 3][i & 7]));
#pragma unroll
            for (int j = 0; j < 4; j++) if (nx >= 0) cs[j] = cn[j];
          };
          {
            auto max_norm = [&](const uint32_t (&n)[2]) {
              const bool o1 = qd & 1;
              uint32_t a = hadd2(o1 ? n[1] : n[0], __shfl_xor_sync(~0u, o1 ? n[0] : n[1], 1));
              a = hadd2(a, __shfl_xor_sync(~0u, a, 2));
              float lo, hi;
              asm("{.reg .f16 a, b; mov.b32 {a, b}, %2; cvt.f32.f16 %0, a; cvt.f32.f16 %1, b;}" : "=f"(lo), "=f"(hi) : "r"(a));
              return __uint_as_float(__reduce_max_sync(~0u, max(__float_as_uint(lo), __float_as_uint(hi))));
            };
#pragma unroll
            for (int h = 0; h < 2; h++) {
              uint32_t t[2][8], nrm[2];
              const uint32_t kb = sb + (h ? wg * 8192 : T0), vb = kb + (h ? 8192 : 16384);
              norm_tile(4 + h, 0, 1.f, t[0]); norm_tile(4 + h, 1, 1.f, t[1]);
              load_cs(2 + h);
#pragma unroll
              for (int m = 0; m < 2; m++) {
                const uint32_t r = row0 + m * 64 + g, ad = vb + r * 64 + ((qd ^ ((r >> 1) & 3)) << 4);
                sts128(ad, t[m][0], t[m][2], t[m][4], t[m][6]); sts128(ad + 512, t[m][1], t[m][3], t[m][5], t[m][7]);
              }
              if (h == 0) sched_fence();
              norm_half(2 + h, 1.f, t, nrm, h);
#pragma unroll
              for (int i = 0; i < 4; i++) {
                const uint32_t r = row0 + (i >> 1) * 64 + srow;
                stsm4(kb + r * 64 + (((2 * (i & 1) + (lane >> 4)) ^ ((r >> 1) & 3)) << 4), t[i >> 1][4 * (i & 1)], t[i >> 1][4 * (i & 1) + 1], t[i >> 1][4 * (i & 1) + 2], t[i >> 1][4 * (i & 1) + 3]);
              }
              if (h == 1) { const float kn = max_norm(nrm); if (lane == 0) g_kn[((l >> 1) * 128 + bn * 8 + bm) * 16 + 8 + wg * 4 + w] = kn; }
              fence_async_smem();
              bar_arrive(NB_KV + 12 * h, 288);
              if (h == 0) {
                bar_arrive(wg ? NB_HALO : NB_DONE, 160);
              }
              if (h == 0) { const float kn = max_norm(nrm); if (lane == 0) g_kn[((l >> 1) * 128 + bn * 8 + bm) * 16 + wg * 4 + w] = kn; }
              norm_half(h, QSCALE, q[h], nrm, h ? -1 : 5);
#pragma unroll
              for (int i = 0; i < 4 * h; i++) sts128(sb + QPARK + 24576 - wg * 8192 + (w * 32 + lane) * 16 + i * 2048, q[h][i >> 1][4 * (i & 1)], q[h][i >> 1][4 * (i & 1) + 1], q[h][i >> 1][4 * (i & 1) + 2], q[h][i >> 1][4 * (i & 1) + 3]);
              qn[h] = max_norm(nrm);
            }
          }
          constexpr uint64_t VSTEP = 64 - (64ull << 16);
          uint32_t cq[4];
          const uint32_t &c_852 = cq[0], &c_lsb = cq[1], &c_half = cq[2];
          float o[2][20], S[2][32];
          uint32_t H[2][16], P0[4] = {}, P1[4] = {};
#pragma unroll
          for (int m = 0; m < 2; m++) {
#pragma unroll
            for (int i = 0; i < 20; i++) o[m][i] = 0.f;
            fence_regs(o[m]);
          }
          auto qkf = [&](int b, int ks, uint64_t d) { wg_n64_rs_nb_f16_f32(S[b], q[0][0][4 * ks], q[0][0][4 * ks + 1], q[0][0][4 * ks + 2], q[0][0][4 * ks + 3], d + 2 * ks, ks ? 1 : zero); };
          auto qkh = [&](int b, int ks, uint64_t d) { wg_n64_rs_nb_f16_f16(H[b], q[0][1][4 * ks], q[0][1][4 * ks + 1], q[0][1][4 * ks + 2], q[0][1][4 * ks + 3], d + 2 * ks, ks ? 1 : zero); };
          auto pv0 = [&](uint64_t d) { wgmma_m64n40k16_rs_tb(o[0], P0[0], P0[1], P0[2], P0[3], d, 1); };
          auto pv1 = [&](uint64_t d) { wgmma_m64n40k16_rs_tb(o[1], P1[0], P1[1], P1[2], P1[3], d, 1); };
          float e[4] = {};
          auto finish = [&](int h) {
            const float* s = &S[(h >> 2) & 1][8 * (h & 3)];
            const uint32_t* u = &H[(h >> 2) & 1][4 * (h & 3)];
            const float z0 = exp2_fix(s[6]), z1 = exp2_fix(s[7]);
            P0[0] = pack2v(e[0], e[1]);
            P1[0] = exp2_h2(u[0], c_852);
            P0[1] = pack2v(e[2], e[3]);
            P1[1] = exp2_h2(u[1], c_852);
            const uint32_t B = exp2_base(z0, z1), E = and_or<0x7F807F80u>(B, c_lsb);
            P1[3] = exp2_h2(u[3], c_852);
            P0[3] = fma_bf2(B, and_or<0x807F807Fu>(B, c_half), E);
            const float e4 = ex2v(s[4]), e5 = ex2v(s[5]);
            P1[2] = exp2_h2(u[2], c_852);
            P0[2] = pack2v(e4, e5);
          };
          auto start = [&](int h) {
            const float* s = &S[(h >> 2) & 1][8 * (h & 3)];
            e[2] = ex2v(s[2]); e[1] = ex2v(s[1]); e[0] = ex2v(s[0]); e[3] = ex2v(s[3]);
          };
          uint64_t kd = prm.kv[0].kd;
          mbar_wait(sb + B_TF, 0);
          lds128(sb + ROWST + 16 + (lane_id() & zero), cq);
#pragma unroll
          for (int i = 0; i < 4; i++) sts128(sb + QPARK + (wg * 128 + w * 32 + lane_id()) * 16 + i * 4096, q[0][i >> 1][4 * (i & 1)], q[0][i >> 1][4 * (i & 1) + 1], q[0][i >> 1][4 * (i & 1) + 2], q[0][i >> 1][4 * (i & 1) + 3]);
          wg_fence();
#pragma unroll
          for (int b = 0; b < 2; b++) {
            wg_n64_rs_nb_f16_f32_z(S[b], q[0][0][0], q[0][0][1], q[0][0][2], q[0][0][3], kd + 256 * b, 0);
            wg_n64_rs_nb_f16_f16_z(H[b], q[0][1][0], q[0][1][1], q[0][1][2], q[0][1][3], kd + 256 * b, 0);
            if (b == 0) { qkf(0, 1, kd); qkh(0, 1, kd); }
            wg_commit();
          }
          wg_wait<1>(); fence_regs(S[0]); fence_regs(H[0]);
          start(0); finish(0); start(1);
          wg_wait<0>();
          int redo = 0;
#pragma unroll 1
          for (int pass = 0, j = 1; pass < 2; pass++) {
#pragma unroll 1
           do {
            const uint64_t vd = prm.kv[j & 3].vd;
            bool go = false;
#pragma unroll
            for (int h = 2; h < 18; h++) {
              const int px = (h >> 2) + 1, c = h & 3;
              wg_fence();
              if (h == 13) kd = prm.kv[j & 3].kd;
              const uint64_t kx = kd + (px & 3) * 256, vx = vd + (h - 2) * VSTEP;
              if (h == 2) { qkh(1, 0, kx); qkf(1, 0, kx); pv0(vx); pv1(vx); qkh(1, 1, kx); qkf(1, 1, kx); }
              else if ((c == 1 || c == 2) && h < 17) { qkh(px & 1, c - 1, kx); pv1(vx); qkf(px & 1, c - 1, kx); pv0(vx); }
              else { pv0(vx); pv1(vx); }
              wg_commit();
              if (h == 3) e_arrive_if(sb + B_TE + 8 * ((j + 2) & 3), j > 1);
              if (h == 11) go = mbar_test(sb + B_TF + 8 * (j & 3), (j >> 2) & 1) && j != 8;
              finish(h - 1); start(h);
              if (h != 12 && h != 17) sched_fence();
              if (h == 12 && !go) {
                if (j == 16) {
#pragma unroll
                  for (int u = 13; u < 18; u++) {
                    wg_fence(); pv0(vd + (u - 2) * VSTEP); pv1(vd + (u - 2) * VSTEP); wg_commit();
                    if (u < 17) finish(u - 1);
                    if (u < 16) { start(u); sched_fence(); }
                    if (u & 1) { if (u == 17) wg_wait<0>(); else wg_wait<1>(); }
                  }
                  e_arrive(sb + B_TE + 24);
                  goto head_done;
                }
                mbar_wait(sb + B_TF + 8 * (j & 3), (j >> 2) & 1);
                if (j == 8) {
#pragma unroll
                  for (int i = 0; i < 4; i++) lds128(sb + QPARK + 24576 - wg * 8192 + (w * 32 + lane_id()) * 16 + i * 2048, &q[0][i >> 1][4 * (i & 1)]);
                }
              }
              if (h == 17) wg_wait<0>(); else if (h & 1) wg_wait<1>();
              if (c == 3) { fence_regs(S[px & 1]); fence_regs(H[px & 1]); }
            }
           } while (j++ & 7);
           head_done:
            fence_regs(o[0]); fence_regs(o[1]);
            uint32_t pk[2][8];
            {
              IDS();
              bf16* op = g_os + (size_t)(bm * 256 + row0 + (lane >> 2)) * 1024 + pass * 512 + bn * 32 + (lane & 3) * 8;
#pragma unroll
              for (int i = 0; i < 4; i++) {
                const float* a = &o[i >> 1][2 * (i & 1)];
                const float inv = rcp(a[16]);
                uint32_t* u = &pk[i >> 1][4 * (i & 1)];
#pragma unroll
                for (int k = 0; k < 4; k++) u[k] = pack2(a[4 * k] * inv, a[4 * k + 1] * inv);
                *(uint4*)(op + ((i >> 1) * 64 + (i & 1) * 8) * 1024) = make_uint4(u[0], u[1], u[2], u[3]);
              }
            }
            sched_fence();
            if (pass == 0) bar_sync(NB_KN + wg, 160);
            const float kmax = *(volatile float*)(smem + ROWST + 4 * pass);
            const bool wide = !(qn[0] + kmax <= 1.4e5f) | !(qn[0] * kmax <= 110.f * 110.f);
            int badm = 0;
#pragma unroll
            for (int m = 0; m < 2; m++) {
              uint32_t chk[2] = {0u, 0u};
#pragma unroll
              for (int i = 0; i < 8; i++) asm("fma.rn.bf16x2 %0, %1, %2, %0;" : "+r"(chk[i & 1]) : "r"(pk[m][i]), "r"(0u));
              const bool bad = wide | !(fminf(o[m][16], o[m][18]) >= 9.3e-10f) | !(o[m][16] + o[m][18] <= 1e36f) | (((chk[0] | chk[1]) & 0x7FFF7FFFu) != 0);
              badm |= __any_sync(~0u, bad) << m;
            }
            if (!badm) bar_arrive(NB_SIG + 2 * pass + wg, 160);
            qn[0] = qn[1];
#pragma unroll
            for (int m = 0; m < 2; m++) {
#pragma unroll
              for (int i = 0; i < 20; i++) o[m][i] = 0.f;
              fence_regs(o[m]);
            }
            if (badm) {
              redo |= badm << 2 * pass;
              const int tx = wg * 128 + w * 32 + lane_id();
              uint4* p = g_qsave + (block_id() * 256 + tx) * 8 + pass * 4;
#pragma unroll
              for (int i = 0; i < 4; i++) {
                uint32_t u[4] = {q[0][i >> 1][4 * (i & 1)], q[0][i >> 1][4 * (i & 1) + 1], q[0][i >> 1][4 * (i & 1) + 2], q[0][i >> 1][4 * (i & 1) + 3]};
                if (pass == 0) lds128(sb + QPARK + tx * 16 + i * 4096, u);
                p[i] = make_uint4(u[0], u[1], u[2], u[3]);
              }
            }
          }
          if (redo) attn_redo(redo, l, cta_id(), wg, w, ep1);
        }
      }
      {
        float acc[64];
        {
          const uint64_t da = l & 1 ? prm.xd + ((pslot_a(0, 1) + wg * 8192) >> 4) : prm.kv[0].kd + ((pslot_a(0, 0) - T0 + wg * 4096) >> 4);
          const uint64_t d2 = da + (l & 1 ? 4 : 512), db = prm.wd + (pslot_b(0) >> 4) - 2048;
          mbar_wait(sb + B_PF, l & 1);
          wg_fence();
          wgmma_m64n128k16_ss_tb_z(acc, da, db, 0);
#pragma unroll
          for (int k = 1; k < 4; k++) wgmma_m64n128k16_ss_tb(acc, (k & 2 ? d2 : da) + (k & 1) * 2, db + k * 128, 1);
          wg_commit();
        }
        uint32_t s = 1, lap = 0;
#pragma unroll 1
        for (int kt = 1; kt < 14; kt++) {
          mbar_wait(sb + B_PF + 8 * s, ((s < 4 ? l : 0) + lap) & 1);
          const uint64_t da = mkdesc(sb + pslot_a(s, l) + wg * 8192, 16, 1024, 1), db = mkdesc(sb + pslot_b(s), 8192, 1024, 1);
          wg_fence();
#pragma unroll
          for (int k = 0; k < 4; k++) wgmma_m64n128k16_ss_tb(acc, da + k * 2, db + k * 128, 1);
          wg_commit();
          wg_wait<1>();
          if (w == 0) e_arrive_both(sb + B_PE + 8 * (s ? s - 1 : 5));
          if (++s == 6) { s = 0; lap++; }
        }
        if (wg) {
          wg_wait<0>();
          if (w == 0) e_arrive_both(sb + B_PE + 8);
#pragma unroll
          for (int t = 2; t < 4; t++) mbar_wait(sb + B_PF + 8 * t, l & 1);
          bar_sync(NB_LAG, 256);
        }
#pragma unroll
        for (int t = 2; t < 4; t++) {
          if (!wg) mbar_wait(sb + B_PF + 8 * t, l & 1);
          const uint64_t da = prm.xd + ((pslot_a(t, l) + wg * 8192) >> 4), db = prm.wd + (pslot_b(t) >> 4) - 2048;
          wg_fence();
#pragma unroll
          for (int k = 0; k < 4; k++) wgmma_m64n128k16_ss_tb(acc, da + k * 2, db + k * 128, 1);
          wg_commit();
        }
        sched_fence();
        if (!wg) {
          bar_arrive(NB_LAG, 256);
          wg_wait<2>();
          if (w == 0) e_arrive_both(sb + B_PE + 8);
        }
        sched_fence();
        IDS();
        const int g = lane >> 2, qd = lane & 3;
        const int r0 = wg * 64 + w * 16;
        const uint32_t r = r0 + (lane & 7) + ((lane >> 3) & 1) * 8;
        uint32_t x[8][4];
        mbar_wait(sb + B_RF, 0);
#pragma unroll
        for (int jj = 0; jj < 8; jj++) ldsm4(sb + RES + (jj >> 2) * 16384 + r * 128 + ((((2 * jj + (lane >> 4)) & 7) ^ (r & 7)) << 4), x[jj]);
        wg_wait<0>();
        fence_regs(acc);
        if (w == 0) { e_arrive_both(sb + B_PE + 16); e_arrive_both(sb + B_PE + 24); }
        const CUtensorMap* mo = &prm.m[l == 3 ? M_OUT : M_XST];
        const bool direct = wg && l < 3;
        const uint32_t stg = sb + (direct ? po * 16384 : RES);
        if (direct) bar_sync(NB_SC, 256);
#pragma unroll
        for (int jj = 0; jj < 8; jj++) {
#pragma unroll
          for (int i = 0; i < 4; i++) x[jj][i] = add_bf16x2(x[jj][i], pack2(acc[8 * jj + 2 * i], acc[8 * jj + 2 * i + 1]));
          if (jj < 4) stsm4(stg + r * 128 + ((((2 * jj + (lane >> 4)) & 7) ^ (r & 7)) << 4), x[jj][0], x[jj][1], x[jj][2], x[jj][3]);
          if (jj == 3) { fence_async_smem(); __syncwarp(); tma_st(mo, pn * 128, pm * 128 + r0, stg + r0 * 128); bulk_commit(); sched_fence(); }
        }
        if (l < 3) bar_arrive(NB_KN, 288);
        if (l == 3) {
#pragma unroll
          for (int jj = 4; jj < 8; jj++) stsm4(sb + RES + 16384 + r * 128 + ((((2 * jj + (lane >> 4)) & 7) ^ (r & 7)) << 4), x[jj][0], x[jj][1], x[jj][2], x[jj][3]);
          fence_async_smem(); __syncwarp();
          tma_st(mo, pn * 128 + 64, pm * 128 + r0, sb + RES + 16384 + r0 * 128);
          bulk_commit(); bulk_wait_n<0>();
        } else {
          if (!wg) bar_sync(NB_SC, 256);
#pragma unroll
          for (int jj = 0; jj < 8; jj++)
            if (jj >= 4 || !wg) stsm4(sb + (jj >> 2) * 2 * QSTG + po * 16384 + r * 128 + ((((2 * jj + (lane >> 4)) & 7) ^ (r & 7)) << 4), x[jj][0], x[jj][1], x[jj][2], x[jj][3]);
          float s1[4] = {0.f, 0.f, 0.f, 0.f}, sa[4] = {0.f, 0.f, 0.f, 0.f}, sc[4] = {0.f, 0.f, 0.f, 0.f};
#pragma unroll
          for (int jj = 0; jj < 8; jj++) {
            mma16816(s1, x[jj][0], x[jj][1], x[jj][2], x[jj][3], 0x3f803f80u, 0x3f803f80u);
            mma16816(sa, x[jj][0], x[jj][1], x[jj][2], x[jj][3], x[jj][0], x[jj][2]);
            mma16816(sc, x[jj][0], x[jj][1], x[jj][2], x[jj][3], x[jj][1], x[jj][3]);
          }
          fence_regs(s1); fence_regs(sa); fence_regs(sc);
          sched_fence();
          bulk_wait_n<0>();
          bar_arrive(NB_X0, 320);
          fence_async_smem();
          sched_fence();
          bar_arrive(NB_X, 320);
          if (qd == g >> 1) {
            float2* p = g_stats + pn * 2048 + pm * 128 + r0 + g;
            p[0] = make_float2(s1[0], g & 1 ? sa[1] : sa[0]);
            p[8] = make_float2(s1[2], g & 1 ? sc[3] : sc[2]);
          }
          bar_arrive(NB_KV, 288);
        }
      }
    }
  }
  asm volatile("barrier.cluster.arrive.relaxed.aligned;\nbarrier.cluster.wait.aligned;" ::: "memory");
}

typedef CUresult (*EncodeFn)(CUtensorMap*, CUtensorMapDataType, cuuint32_t, void*, const cuuint64_t*, const cuuint64_t*, const cuuint32_t*,
                             const cuuint32_t*, CUtensorMapInterleave, CUtensorMapSwizzle, CUtensorMapL2promotion, CUtensorMapFloatOOBfill);

static void make_map(EncodeFn fn, CUtensorMap* m, const void* ptr, int rank, const uint64_t* dims, const uint64_t* strides, const uint32_t* box, CUtensorMapSwizzle sw) {
  cuuint64_t d[5], st[4];
  cuuint32_t bx[5], es[5];
  for (int i = 0; i < rank; i++) { d[i] = dims[i]; bx[i] = box[i]; es[i] = 1; if (i) st[i - 1] = strides[i - 1] * 2; }
  fn(m, CU_TENSOR_MAP_DATA_TYPE_BFLOAT16, rank, (void*)ptr, d, st, bx, es, CU_TENSOR_MAP_INTERLEAVE_NONE, sw,
     CU_TENSOR_MAP_L2_PROMOTION_L2_128B, CU_TENSOR_MAP_FLOAT_OOB_FILL_NONE);
}
static void map2(EncodeFn fn, CUtensorMap* m, const void* ptr, uint64_t inner, uint64_t outer, uint32_t bi, uint32_t bo, CUtensorMapSwizzle sw) {
  const uint64_t d[2] = {inner, outer}, st[1] = {inner};
  const uint32_t bx[2] = {bi, bo};
  make_map(fn, m, ptr, 2, d, st, bx, sw);
}

extern "C" void kernel_launch(void* const* d_in, const int* in_sizes, int n_in, void* d_out, int out_size) {
  (void)in_sizes; (void)n_in; (void)out_size;
  static EncodeFn enc = nullptr;
  static void *xs, *os, *kk, *vv;
  static int sbase = 1024;
  if (!enc) {
    void* p = nullptr;
    cudaDriverEntryPointQueryResult qr;
    cudaGetDriverEntryPoint("cuTensorMapEncodeTiled", &p, cudaEnableDefault, &qr);
    enc = (EncodeFn)p;
    Scratch* sc = nullptr;
    cudaGetSymbolAddress((void**)&sc, g_s);
    xs = sc->xs; os = sc->os; kk = sc->k; vv = sc->v;
    int dev = 0;
    cudaGetDevice(&dev);
    cudaDeviceGetAttribute(&sbase, cudaDevAttrReservedSharedMemoryPerBlock, dev);
    cudaFuncSetAttribute(fused_kernel, cudaFuncAttributeMaxDynamicSharedMemorySize, SMEM_BYTES);
  }
  Params prm;
  const CUtensorMapSwizzle S128 = CU_TENSOR_MAP_SWIZZLE_128B, S64 = CU_TENSOR_MAP_SWIZZLE_64B;
  map2(enc, &prm.m[M_X0A], d_in[0], 1024, 2048, 64, 256, S128);
  for (int t = 0; t < 2; t++) {
    const uint64_t d3[3] = {1024, 1024, 3}, s3[2] = {3072, 1024};
    const uint32_t b3[3] = {64, 64, 3};
    make_map(enc, &prm.m[M_WQA + t], d_in[1 + 3 * t], 3, d3, s3, b3, S128);
    const uint64_t d5[5] = {64, 32, 2, 16, 16}, s5[4] = {1024, 32 * 1024, 64 * 1024, 64};
    const uint32_t b5[5] = {64, 32, 1, 2, 2};
    make_map(enc, &prm.m[M_WOA + t], d_in[2 + 3 * t], 5, d5, s5, b5, S128);
    const uint64_t dr[3] = {64, 2048, 16}, sr[2] = {1024, 64};
    const uint32_t br[3] = {64, 128, 2};
    make_map(enc, &prm.m[M_X0R + t], t ? xs : d_in[0], 3, dr, sr, br, S128);
  }
  map2(enc, &prm.m[M_OS], os, 1024, 2048, 64, 64, S128);
  map2(enc, &prm.m[M_OL], os, 1024, 2048, 32, 128, S64);
  map2(enc, &prm.m[M_K], kk, 32, 65536, 32, 128, S64);
  map2(enc, &prm.m[M_V], vv, 32, 65536, 32, 128, S64);
  map2(enc, &prm.m[M_XSO], xs, 1024, 2048, 64, 128, S128);
  map2(enc, &prm.m[M_X0H], d_in[0], 1024, 2048, 64, 128, S128);
  map2(enc, &prm.m[M_XST], xs, 1024, 2048, 64, 16, S128);
  map2(enc, &prm.m[M_OUT], d_out, 1024, 2048, 64, 16, S128);
  prm.x0 = (const bf16*)d_in[0];
  prm.wq[0] = (const bf16*)d_in[1]; prm.wq[1] = (const bf16*)d_in[4];
  prm.wo = (const bf16*)d_in[2];
  prm.zero = 0;
  for (int i = 0; i < 128; i++) prm.map[i] = remap(i);
  {
    const uint64_t hi = 0x80000020ull << 32, k0 = sbase + T0, v0 = k0 + 16384, vstep = 64 - (64ull << 16);
    prm.wd = mkdesc(sbase + 32768, 8192, 1024, 1); prm.xd = mkdesc(sbase, 16, 1024, 1);
    for (int j = 0; j < 4; j++) {
      prm.kv[j].kd = (hi | 1u << 16 | k0 >> 4) + 2048 * ((j < 16 ? j : 15) & 3);
      prm.kv[j].vd = (hi | (uint64_t)(ONES - T0 - 16384) >> 4 << 16 | v0 >> 4) + 32 * vstep * ((j + 3) & 3);
    }
  }
  fused_kernel<<<128, 384, SMEM_BYTES>>>(prm);
}
```
